```python
import torch

def _softmax(x, axis=-1):
    return torch.softmax(x, dim=axis)

def _gelu(x):
    return torch.nn.functional.gelu(x, approximate='tanh')

def _silu(x):
    return torch.nn.functional.silu(x)

def _sigmoid(x):
    return torch.sigmoid(x)

def _layernorm(x, axis=-1, eps=1e-05):
    m = x.mean(dim=axis, keepdim=True)
    v = x.var(dim=axis, keepdim=True, unbiased=False)
    return (x - m) / torch.sqrt(v + eps)

def _scatter_add(tgt, idx, src, axis=0):
    return tgt.clone().index_add_(axis, idx, src)

def _segment_sum(src, seg, n):
    out = torch.zeros((n,) + src.shape[1:], dtype=src.dtype)
    return out.index_add_(0, seg, src)

def _pad(x, pw):
    flat = tuple((v for pair in reversed(pw) for v in pair))
    return torch.nn.functional.pad(x, flat)
kernel_name = 'gated_mix__compressed_kv_cla__memory_aug_recurrent_mem_tr__prompt'

def setup_inputs():

    _w = lambda a: (lambda t: t.to(torch.bfloat16) if t.is_floating_point() else t)(torch.as_tensor(a))

    def _A_setup():
        B, H, Sq, Sk, D, M = (1, 32, 2048, 2048, 128, 512)
        Dc = 4 * D
        return {'x': _w((lambda *s: torch.randn(*s, dtype=torch.bfloat16) * 0.05)(B, Sq, M)), 'c_kv': _w((lambda *s: torch.randn(*s, dtype=torch.bfloat16) * 0.8)(B, Sk, Dc)), 'w_q': _w((lambda *s: torch.randn(*s, dtype=torch.bfloat16) * 6.4)(M, H, D) * M ** (-0.5)), 'w_uk': _w((lambda *s: torch.randn(*s, dtype=torch.bfloat16) * 6.4)(Dc, H, D) * Dc ** (-0.5)), 'w_uv': _w((lambda *s: torch.randn(*s, dtype=torch.bfloat16) * 0.8)(Dc, H, D) * Dc ** (-0.5)), 'w_o': _w((lambda *s: torch.randn(*s, dtype=torch.bfloat16) * 0.8)(H, D, M) * (H * D) ** (-0.5))}
    _A_in = _A_setup()

    def _B_setup():
        B, S, Dm = (1, 2048, 512)
        H, Dh = (32, 128)
        M, seg = (8, 32)
        seg = min(seg, S)
        S = S // seg * seg
        return {'x': _w((lambda *s: torch.randn(*s, dtype=torch.bfloat16) * 0.05)(B, S, Dm)), 'mem0': _w((lambda *s: torch.randn(*s, dtype=torch.bfloat16) * 0.8)(B, M, Dm)), 'Wq': _w((lambda *s: torch.randn(*s, dtype=torch.bfloat16) * 3.2)(Dm, H, Dh) * Dm ** (-0.5)), 'Wk': _w((lambda *s: torch.randn(*s, dtype=torch.bfloat16) * 3.2)(Dm, H, Dh) * Dm ** (-0.5)), 'Wv': _w((lambda *s: torch.randn(*s, dtype=torch.bfloat16) * 0.8)(Dm, H, Dh) * Dm ** (-0.5)), 'Wo': _w((lambda *s: torch.randn(*s, dtype=torch.bfloat16) * 0.8)(H, Dh, Dm) * (H * Dh) ** (-0.5)), 'seg_len': seg}
    _B_in = _B_setup()
    return {'A_x': _A_in['x'], 'A_c_kv': _A_in['c_kv'], 'A_w_q': _A_in['w_q'], 'A_w_uk': _A_in['w_uk'], 'A_w_uv': _A_in['w_uv'], 'A_w_o': _A_in['w_o'], 'B_x': _B_in['x'], 'B_mem0': _B_in['mem0'], 'B_Wq': _B_in['Wq'], 'B_Wk': _B_in['Wk'], 'B_Wv': _B_in['Wv'], 'B_Wo': _B_in['Wo'], 'B_seg_len': _B_in['seg_len'], 'gate_w': _w((lambda *s: torch.randn(*s, dtype=torch.bfloat16) * 0.05)(512) * 16.0)}

def reference(A_x, A_c_kv, A_w_q, A_w_uk, A_w_uv, A_w_o, B_x, B_mem0, B_Wq, B_Wk, B_Wv, B_Wo, B_seg_len, gate_w):

    def _A_ref(x, c_kv, w_q, w_uk, w_uv, w_o):
        B, Sq, M = (x.shape[0], x.shape[1], x.shape[2])
        Sk = c_kv.shape[1]
        H, D = (w_q.shape[1], w_q.shape[2])
        q = torch.einsum('bqm,mhd->bhqd', x, w_q)
        k = torch.einsum('bkc,chd->bhkd', c_kv, w_uk)
        v = torch.einsum('bkc,chd->bhkd', c_kv, w_uv)
        scores = torch.einsum('bhqd,bhkd->bhqk', q, k) * D ** (-0.5)
        off = Sk - Sq
        qi = torch.arange(Sq)[:, None]
        kj = torch.arange(Sk)[None, :]
        cmask = kj <= qi + off
        scores = torch.where(cmask[None, None], scores, -1000000000.0)
        p = _softmax(scores, axis=-1)
        ctx = torch.einsum('bhqk,bhkd->bhqd', p, v)
        return torch.einsum('bhqd,hdm->bqm', ctx, w_o)

    def _B_ref(x, mem0, Wq, Wk, Wv, Wo, seg_len):
        B, S, Dm = x.shape
        H, Dh = (Wq.shape[1], Wq.shape[2])
        M = mem0.shape[1]
        scale = Dh ** (-0.5)
        n_seg = S // seg_len
        L = M + seg_len
        idx = torch.arange(L)
        mask = (idx[:, None] < M) | (idx[:, None] >= idx[None, :])
        mem = mem0
        outs = []
        for s in range(n_seg):
            xs = x[:, s * seg_len:(s + 1) * seg_len, :].clone()
            h = torch.concatenate([mem, xs], axis=1)
            q = torch.einsum('btd,dhe->bhte', h, Wq)
            k = torch.einsum('btd,dhe->bhte', h, Wk)
            v = torch.einsum('btd,dhe->bhte', h, Wv)
            scores = torch.einsum('bhqe,bhke->bhqk', q, k) * scale
            scores = torch.where(mask[None, None], scores, -1000000000.0)
            p = _softmax(scores, axis=-1)
            o = torch.einsum('bhqk,bhke->bhqe', p, v)
            o = torch.einsum('bhte,hed->btd', o, Wo)
            mem = o[:, :M, :].clone()
            outs.append(o[:, M:, :])
        return torch.concatenate(outs, axis=1)
    x = A_x
    g = _sigmoid((x * gate_w).sum(-1, keepdims=True))
    a = _A_ref(x, A_c_kv, A_w_q, A_w_uk, A_w_uv, A_w_o)
    b = _B_ref(x, B_mem0, B_Wq, B_Wk, B_Wv, B_Wo, B_seg_len)
    return g * a + (1 - g) * b
```

```cpp
#include <cuda_runtime.h>
#include <cuda_bf16.h>
#include <cuda.h>
#include <stdint.h>

constexpr int SEQ = 2048;
constexpr int DM = 512;
constexpr int NH = 32;
constexpr int HD = 128;
constexpr int NQ = NH * HD;
constexpr int SEGL = 32;
constexpr int NMEM = 8;
constexpr int NSEG = SEQ / SEGL;

typedef __nv_bfloat16 bf16;

__device__ bf16 g_QA[SEQ * NQ];
__device__ bf16 g_KA[SEQ * NQ];
__device__ bf16 g_VA[SEQ * NQ];
__device__ bf16 g_ctxA[SEQ * NQ];
__device__ bf16 g_ctxB[SEQ * NQ];
constexpr int CT_PROJ = 0, CT_ATTN = 1, CT_FIN = 5;
constexpr int CT_AP = 64;
#define O2_HE 18
constexpr int CT_CA = 128;
constexpr int CT_CB = 160;
constexpr int CT_OP = 192;
constexpr int CT_N = 224;
__device__ unsigned int g_ctr[CT_N];
__device__ uint32_t g_xbuf[4 * 8 * 2048];

#define FA_GRID 68

#define TS_BEGIN(id)
#define TS_END(id)
#define WAIT_LIMIT 200000
__device__ __forceinline__ void pdl_launch_dependents() { asm volatile("griddepcontrol.launch_dependents;" ::: "memory"); }
__device__ __forceinline__ void wait_ctr(int idx, unsigned int n) {
    unsigned int v; int it = 0;
    do { asm volatile("ld.acquire.gpu.global.u32 %0, [%1];" : "=r"(v) : "l"(&g_ctr[idx]) : "memory"); } while (v < n && ++it < WAIT_LIMIT);
    asm volatile("fence.proxy.async;" ::: "memory");
}
__device__ __forceinline__ void signal_ctr(int idx) {
    asm volatile("fence.proxy.async;" ::: "memory");
    __threadfence();
    atomicAdd(&g_ctr[idx], 1u);
}
__device__ __forceinline__ uint32_t smem_u32(const void* p) {
    return (uint32_t)__cvta_generic_to_shared(p);
}
__device__ __forceinline__ void mbar_init(uint32_t bar, uint32_t count) {
    asm volatile("mbarrier.init.shared::cta.b64 [%0], %1;" :: "r"(bar), "r"(count));
}
__device__ __forceinline__ void mbar_expect_tx(uint32_t bar, uint32_t bytes) {
    asm volatile("mbarrier.arrive.expect_tx.shared::cta.b64 _, [%0], %1;" :: "r"(bar), "r"(bytes) : "memory");
}
__device__ __forceinline__ void mbar_arrive(uint32_t bar) {
    asm volatile("mbarrier.arrive.shared::cta.b64 _, [%0];" :: "r"(bar) : "memory");
}
__device__ __forceinline__ void mbar_wait(uint32_t bar, uint32_t parity) {
    asm volatile(
        "{\n"
        ".reg .pred p, q;\n"
        ".reg .u32 c;\n"
        "mov.u32 c, 0;\n"
        "WAIT_LOOP:\n"
        "mbarrier.try_wait.parity.shared::cta.b64 p, [%0], %1;\n"
        "@p bra WAIT_DONE;\n"
        "add.u32 c, c, 1;\n"
        "setp.lt.u32 q, c, %2;\n"
        "@q bra WAIT_LOOP;\n"
        "WAIT_DONE:\n"
        "}\n" :: "r"(bar), "r"(parity), "n"(WAIT_LIMIT) : "memory");
}
__device__ __forceinline__ void tma_load_2d(uint32_t dst, const CUtensorMap* map, uint32_t bar, int c0, int c1) {
    asm volatile(
        "cp.async.bulk.tensor.2d.shared::cluster.global.mbarrier::complete_tx::bytes [%0], [%1, {%3, %4}], [%2];"
        :: "r"(dst), "l"((uint64_t)map), "r"(bar), "r"(c0), "r"(c1) : "memory");
}
__device__ __forceinline__ void wgmma_fence() { asm volatile("wgmma.fence.sync.aligned;" ::: "memory"); }
__device__ __forceinline__ void wgmma_commit() { asm volatile("wgmma.commit_group.sync.aligned;" ::: "memory"); }
template <int N> __device__ __forceinline__ void wgmma_wait() {
    asm volatile("wgmma.wait_group.sync.aligned %0;" :: "n"(N) : "memory");
}
__device__ __forceinline__ uint64_t make_desc(uint32_t addr, uint32_t lbo, uint32_t sbo) {
    uint64_t d = 0;
    d |= (uint64_t)((addr & 0x3FFFF) >> 4);
    d |= (uint64_t)((lbo >> 4) & 0x3FFF) << 16;
    d |= (uint64_t)((sbo >> 4) & 0x3FFF) << 32;
    d |= (uint64_t)1 << 62;
    return d;
}

#define ACC64(d) \
    "+f"(d[0]), "+f"(d[1]), "+f"(d[2]), "+f"(d[3]), "+f"(d[4]), "+f"(d[5]), "+f"(d[6]), "+f"(d[7]), \
    "+f"(d[8]), "+f"(d[9]), "+f"(d[10]), "+f"(d[11]), "+f"(d[12]), "+f"(d[13]), "+f"(d[14]), "+f"(d[15]), \
    "+f"(d[16]), "+f"(d[17]), "+f"(d[18]), "+f"(d[19]), "+f"(d[20]), "+f"(d[21]), "+f"(d[22]), "+f"(d[23]), \
    "+f"(d[24]), "+f"(d[25]), "+f"(d[26]), "+f"(d[27]), "+f"(d[28]), "+f"(d[29]), "+f"(d[30]), "+f"(d[31]), \
    "+f"(d[32]), "+f"(d[33]), "+f"(d[34]), "+f"(d[35]), "+f"(d[36]), "+f"(d[37]), "+f"(d[38]), "+f"(d[39]), \
    "+f"(d[40]), "+f"(d[41]), "+f"(d[42]), "+f"(d[43]), "+f"(d[44]), "+f"(d[45]), "+f"(d[46]), "+f"(d[47]), \
    "+f"(d[48]), "+f"(d[49]), "+f"(d[50]), "+f"(d[51]), "+f"(d[52]), "+f"(d[53]), "+f"(d[54]), "+f"(d[55]), \
    "+f"(d[56]), "+f"(d[57]), "+f"(d[58]), "+f"(d[59]), "+f"(d[60]), "+f"(d[61]), "+f"(d[62]), "+f"(d[63])
#define ACC64_STR \
    "{%0, %1, %2, %3, %4, %5, %6, %7, %8, %9, %10, %11, %12, %13, %14, %15, " \
    "%16, %17, %18, %19, %20, %21, %22, %23, %24, %25, %26, %27, %28, %29, %30, %31, " \
    "%32, %33, %34, %35, %36, %37, %38, %39, %40, %41, %42, %43, %44, %45, %46, %47, " \
    "%48, %49, %50, %51, %52, %53, %54, %55, %56, %57, %58, %59, %60, %61, %62, %63}"

template <int TB>
__device__ __forceinline__ void wgmma_ss_n128(float (&d)[64], uint64_t da, uint64_t db, int scale_d) {
    asm volatile(
        "{\n.reg .pred p;\nsetp.ne.b32 p, %66, 0;\n"
        "wgmma.mma_async.sync.aligned.m64n128k16.f32.bf16.bf16 " ACC64_STR ", %64, %65, p, 1, 1, 0, %67;\n}\n"
        : ACC64(d) : "l"(da), "l"(db), "r"(scale_d), "n"(TB));
}
__device__ __forceinline__ uint32_t desc_lo(uint32_t addr, uint32_t lbo) { return ((addr & 0x3FFFF) >> 4) | ((lbo >> 4) << 16); }
template <int TB>
__device__ __forceinline__ void wgmma_ss_n128_lo(float (&d)[64], uint32_t da_lo, uint32_t db_lo, int scale_d) {
    asm volatile(
        "{\n.reg .pred p;\n.reg .b64 da, db;\nsetp.ne.b32 p, %66, 0;\n"
        "mov.b64 da, {%64, 0x40000040};\nmov.b64 db, {%65, 0x40000040};\n"
        "wgmma.mma_async.sync.aligned.m64n128k16.f32.bf16.bf16 " ACC64_STR ", da, db, p, 1, 1, 0, %67;\n}\n"
        : ACC64(d) : "r"(da_lo), "r"(db_lo), "r"(scale_d), "n"(TB));
}
__device__ __forceinline__ void wgmma_rs_n128_tb(float (&d)[64], uint32_t a0, uint32_t a1, uint32_t a2, uint32_t a3,
                                                 uint64_t db, int scale_d) {
    asm volatile(
        "{\n.reg .pred p;\nsetp.ne.b32 p, %69, 0;\n"
        "wgmma.mma_async.sync.aligned.m64n128k16.f32.bf16.bf16 " ACC64_STR ", {%64, %65, %66, %67}, %68, p, 1, 1, 1;\n}\n"
        : ACC64(d) : "r"(a0), "r"(a1), "r"(a2), "r"(a3), "l"(db), "r"(scale_d));
}
__device__ __forceinline__ void wgmma_rs_n80(float (&d)[40], const uint32_t (&a)[4], uint32_t db_lo, int scale_d) {
    asm volatile(
        "{\n.reg .pred p;\n.reg .b64 db;\nsetp.ne.b32 p, %45, 0;\nmov.b64 db, {%44, 0x40000040};\n"
        "wgmma.mma_async.sync.aligned.m64n80k16.f32.bf16.bf16 "
        "{%0, %1, %2, %3, %4, %5, %6, %7, %8, %9, %10, %11, %12, %13, %14, %15, %16, %17, %18, %19, %20, %21, %22, %23, %24, %25, %26, %27, %28, %29, %30, %31, %32, %33, %34, %35, %36, %37, %38, %39}, "
        "{%40, %41, %42, %43}, db, p, 1, 1, 0;\n}\n"
        : "+f"(d[0]), "+f"(d[1]), "+f"(d[2]), "+f"(d[3]), "+f"(d[4]), "+f"(d[5]), "+f"(d[6]), "+f"(d[7]), "+f"(d[8]), "+f"(d[9]), "+f"(d[10]), "+f"(d[11]), "+f"(d[12]), "+f"(d[13]), "+f"(d[14]), "+f"(d[15]), "+f"(d[16]), "+f"(d[17]), "+f"(d[18]), "+f"(d[19]), "+f"(d[20]), "+f"(d[21]), "+f"(d[22]), "+f"(d[23]), "+f"(d[24]), "+f"(d[25]), "+f"(d[26]), "+f"(d[27]), "+f"(d[28]), "+f"(d[29]), "+f"(d[30]), "+f"(d[31]), "+f"(d[32]), "+f"(d[33]), "+f"(d[34]), "+f"(d[35]), "+f"(d[36]), "+f"(d[37]), "+f"(d[38]), "+f"(d[39])
        : "r"(a[0]), "r"(a[1]), "r"(a[2]), "r"(a[3]), "r"(db_lo), "r"(scale_d));
}
__device__ __forceinline__ void wgmma_ss_n256_tb(float (&d)[128], uint64_t da, uint64_t db, int scale_d) {
    asm volatile(
        "{\n.reg .pred p;\nsetp.ne.b32 p, %130, 0;\n"
        "wgmma.mma_async.sync.aligned.m64n256k16.f32.bf16.bf16 {%0, %1, %2, %3, %4, %5, %6, %7, %8, %9, %10, %11, %12, %13, %14, %15, %16, %17, %18, %19, %20, %21, %22, %23, %24, %25, %26, %27, %28, %29, %30, %31, %32, %33, %34, %35, %36, %37, %38, %39, %40, %41, %42, %43, %44, %45, %46, %47, %48, %49, %50, %51, %52, %53, %54, %55, %56, %57, %58, %59, %60, %61, %62, %63, %64, %65, %66, %67, %68, %69, %70, %71, %72, %73, %74, %75, %76, %77, %78, %79, %80, %81, %82, %83, %84, %85, %86, %87, %88, %89, %90, %91, %92, %93, %94, %95, %96, %97, %98, %99, %100, %101, %102, %103, %104, %105, %106, %107, %108, %109, %110, %111, %112, %113, %114, %115, %116, %117, %118, %119, %120, %121, %122, %123, %124, %125, %126, %127}, %128, %129, p, 1, 1, 0, 1;\n}\n"
        : "+f"(d[0]), "+f"(d[1]), "+f"(d[2]), "+f"(d[3]), "+f"(d[4]), "+f"(d[5]), "+f"(d[6]), "+f"(d[7]), "+f"(d[8]), "+f"(d[9]), "+f"(d[10]), "+f"(d[11]), "+f"(d[12]), "+f"(d[13]), "+f"(d[14]), "+f"(d[15]), "+f"(d[16]), "+f"(d[17]), "+f"(d[18]), "+f"(d[19]), "+f"(d[20]), "+f"(d[21]), "+f"(d[22]), "+f"(d[23]), "+f"(d[24]), "+f"(d[25]), "+f"(d[26]), "+f"(d[27]), "+f"(d[28]), "+f"(d[29]), "+f"(d[30]), "+f"(d[31]), "+f"(d[32]), "+f"(d[33]), "+f"(d[34]), "+f"(d[35]), "+f"(d[36]), "+f"(d[37]), "+f"(d[38]), "+f"(d[39]), "+f"(d[40]), "+f"(d[41]), "+f"(d[42]), "+f"(d[43]), "+f"(d[44]), "+f"(d[45]), "+f"(d[46]), "+f"(d[47]), "+f"(d[48]), "+f"(d[49]), "+f"(d[50]), "+f"(d[51]), "+f"(d[52]), "+f"(d[53]), "+f"(d[54]), "+f"(d[55]), "+f"(d[56]), "+f"(d[57]), "+f"(d[58]), "+f"(d[59]), "+f"(d[60]), "+f"(d[61]), "+f"(d[62]), "+f"(d[63]), "+f"(d[64]), "+f"(d[65]), "+f"(d[66]), "+f"(d[67]), "+f"(d[68]), "+f"(d[69]), "+f"(d[70]), "+f"(d[71]), "+f"(d[72]), "+f"(d[73]), "+f"(d[74]), "+f"(d[75]), "+f"(d[76]), "+f"(d[77]), "+f"(d[78]), "+f"(d[79]), "+f"(d[80]), "+f"(d[81]), "+f"(d[82]), "+f"(d[83]), "+f"(d[84]), "+f"(d[85]), "+f"(d[86]), "+f"(d[87]), "+f"(d[88]), "+f"(d[89]), "+f"(d[90]), "+f"(d[91]), "+f"(d[92]), "+f"(d[93]), "+f"(d[94]), "+f"(d[95]), "+f"(d[96]), "+f"(d[97]), "+f"(d[98]), "+f"(d[99]), "+f"(d[100]), "+f"(d[101]), "+f"(d[102]), "+f"(d[103]), "+f"(d[104]), "+f"(d[105]), "+f"(d[106]), "+f"(d[107]), "+f"(d[108]), "+f"(d[109]), "+f"(d[110]), "+f"(d[111]), "+f"(d[112]), "+f"(d[113]), "+f"(d[114]), "+f"(d[115]), "+f"(d[116]), "+f"(d[117]), "+f"(d[118]), "+f"(d[119]), "+f"(d[120]), "+f"(d[121]), "+f"(d[122]), "+f"(d[123]), "+f"(d[124]), "+f"(d[125]), "+f"(d[126]), "+f"(d[127])
        : "l"(da), "l"(db), "r"(scale_d));
}
__device__ __forceinline__ void stmatrix_x4(uint32_t addr, uint32_t r0, uint32_t r1, uint32_t r2, uint32_t r3) {
    asm volatile("stmatrix.sync.aligned.m8n8.x4.shared.b16 [%0], {%1, %2, %3, %4};" :: "r"(addr), "r"(r0), "r"(r1), "r"(r2), "r"(r3) : "memory");
}
__device__ __forceinline__ void tma_store_2d(const CUtensorMap* map, uint32_t src, int c0, int c1) {
    asm volatile("cp.async.bulk.tensor.2d.global.shared::cta.bulk_group [%0, {%2, %3}], [%1];"
                 :: "l"((uint64_t)map), "r"(src), "r"(c0), "r"(c1) : "memory");
}
__device__ __forceinline__ float ex2f(float x) { float y; asm("ex2.approx.ftz.f32 %0, %1;" : "=f"(y) : "f"(x)); return y; }
__device__ __forceinline__ uint32_t pack_bf16(float lo, float hi) {
    __nv_bfloat162 v = __floats2bfloat162_rn(lo, hi);
    return *reinterpret_cast<uint32_t*>(&v);
}
__device__ __forceinline__ void mma_16816(float (&c)[4], uint32_t a0, uint32_t a1, uint32_t a2, uint32_t a3,
                                          uint32_t b0, uint32_t b1) {
    asm volatile(
        "mma.sync.aligned.m16n8k16.row.col.f32.bf16.bf16.f32 {%0,%1,%2,%3}, {%4,%5,%6,%7}, {%8,%9}, {%0,%1,%2,%3};"
        : "+f"(c[0]), "+f"(c[1]), "+f"(c[2]), "+f"(c[3])
        : "r"(a0), "r"(a1), "r"(a2), "r"(a3), "r"(b0), "r"(b1));
}
__device__ __forceinline__ void ldmatrix_x4_trans(uint32_t& r0, uint32_t& r1, uint32_t& r2, uint32_t& r3, uint32_t addr) {
    asm volatile("ldmatrix.sync.aligned.m8n8.x4.trans.shared.b16 {%0,%1,%2,%3}, [%4];"
                 : "=r"(r0), "=r"(r1), "=r"(r2), "=r"(r3) : "r"(addr));
}

struct AttnParams {
    CUtensorMap mapQ, mapK, mapV;
    CUtensorMap mapO;
};
constexpr int FA_STAGES = 2;
constexpr int FA_SMEM = 32768 + FA_STAGES * 65536 + 32768 + 1024 + 256;
constexpr int FA_ITEMS = 16 * NH;
#define FA_RETIRE 100000
#define FA_LASTG 8
__device__ __forceinline__ int fa_qt(int t) {
    constexpr int T0 = (32 - FA_LASTG) * 16;
    return t < T0 ? 15 - ((t & 127) >> 3) : 15 - (t - T0) / FA_LASTG;
}
__device__ __forceinline__ int fa_head(int t) {
    constexpr int T0 = (32 - FA_LASTG) * 16;
    return t < T0 ? (t >> 7) * 8 + (t & 7) : (32 - FA_LASTG) + (t - T0) % FA_LASTG;
}

__global__ void __launch_bounds__(384, 1) attn_kernel(const __grid_constant__ AttnParams P, int retire_cta) {
    extern __shared__ uint8_t smem_raw[];
    uint32_t sbase = (smem_u32(smem_raw) + 1023) & ~1023u;
    const uint32_t sQ = sbase;
    const uint32_t sKV = sbase + 32768;
    const uint32_t sO = sKV + FA_STAGES * 65536;
    const uint32_t bars = sO + 32768;
    const uint32_t bar_q = bars, bar_qe = bars + 8, bar_kf = bars + 16, bar_vf = bar_kf + 8 * FA_STAGES, bar_e = bar_vf + 8 * FA_STAGES,
                   bar_ek = bar_e + 8 * FA_STAGES, slot = bar_ek + 8 * FA_STAGES, bar_of = slot + 16, bar_oe = bar_of + 16, oslot = bar_oe + 16;
    const int warp = threadIdx.x >> 5;
    TS_BEGIN(1);
    int tfirst = 0;
    if (threadIdx.x == 256) tfirst = (int)atomicAdd(&g_ctr[CT_ATTN], 1u);
    if (threadIdx.x == 0) {
        mbar_init(bar_q, 1); mbar_init(bar_qe, 8);
        for (int i = 0; i < FA_STAGES; i++) { mbar_init(bar_kf + 8 * i, 1); mbar_init(bar_vf + 8 * i, 1); mbar_init(bar_e + 8 * i, 8); mbar_init(bar_ek + 8 * i, 8); }
        for (int i = 0; i < 2; i++) { mbar_init(bar_of + 8 * i, 1); mbar_init(bar_oe + 8 * i, 1); }
        asm volatile("fence.mbarrier_init.release.cluster;" ::: "memory");
    }
    if (threadIdx.x == 256) asm volatile("st.shared.s32 [%0], %1;" :: "r"(slot + 8), "r"(tfirst) : "memory");
    __syncthreads();
    pdl_launch_dependents();
    if (warp >= 8) {
        asm volatile("setmaxnreg.dec.sync.aligned.u32 40;");
        if (threadIdx.x == 288 || threadIdx.x == 320) {
            const int wg = threadIdx.x == 288 ? 0 : 1;
            const uint32_t stg = sO + wg * 16384;
            for (int n = 0;; n++) {
                mbar_wait(bar_of + 8 * wg, n & 1);
                int t;
                asm volatile("ld.shared.s32 %0, [%1];" : "=r"(t) : "r"(oslot + wg * 4) : "memory");
                if (t < 0) break;
                const int qt = fa_qt(t), h = fa_head(t);
                tma_store_2d(&P.mapO, stg, 0, h * SEQ + qt * 128 + wg * 64);
                tma_store_2d(&P.mapO, stg + 8192, 64, h * SEQ + qt * 128 + wg * 64);
                asm volatile("cp.async.bulk.commit_group;" ::: "memory");
                asm volatile("cp.async.bulk.wait_group.read 0;" ::: "memory");
                mbar_arrive(bar_oe + 8 * wg);
                asm volatile("cp.async.bulk.wait_group 0;" ::: "memory");
                signal_ctr(CT_CA + qt * 2 + (h >= O2_HE));
            }
        }
        if (threadIdx.x == 256) {
            int it = 0, hp_ready = 0;
            for (int item = 0;; item++) {
                int t = tfirst;
                if (item > 0) {
                    bool quit = false;
                    if ((int)blockIdx.x >= retire_cta) {
                        unsigned int v;
                        asm volatile("ld.relaxed.gpu.global.u32 %0, [%1];" : "=r"(v) : "l"(&g_ctr[CT_ATTN]) : "memory");
                        quit = v >= FA_RETIRE;
                    }
                    t = quit ? FA_ITEMS : (int)atomicAdd(&g_ctr[CT_ATTN], 1u);
                }
                const bool valid = t < FA_ITEMS;
                const int qt = fa_qt(t), h = fa_head(t);
                if (valid && !((hp_ready >> (h >> 1)) & 1)) { wait_ctr(CT_AP + (h >> 1), 96u); hp_ready |= 1 << (h >> 1); }
                mbar_wait(bar_qe, (item & 1) ^ 1);
                asm volatile("st.shared.s32 [%0], %1;" :: "r"(slot + (item & 1) * 4), "r"(valid ? t : -1) : "memory");
                if (!valid) { mbar_arrive(bar_q); break; }
                mbar_expect_tx(bar_q, 32768);
                tma_load_2d(sQ, &P.mapQ, bar_q, 0, h * SEQ + qt * 128);
                tma_load_2d(sQ + 16384, &P.mapQ, bar_q, 64, h * SEQ + qt * 128);
                for (int j = 0; j <= qt; j++, it++) {
                    const int s = it % FA_STAGES;
                    mbar_wait(bar_ek + 8 * s, ((it / FA_STAGES) & 1) ^ 1);
                    const uint32_t sk = sKV + s * 65536, sv = sk + 32768;
                    mbar_expect_tx(bar_kf + 8 * s, 32768);
                    tma_load_2d(sk, &P.mapK, bar_kf + 8 * s, 0, h * SEQ + j * 128);
                    tma_load_2d(sk + 16384, &P.mapK, bar_kf + 8 * s, 64, h * SEQ + j * 128);
                    mbar_wait(bar_e + 8 * s, ((it / FA_STAGES) & 1) ^ 1);
                    mbar_expect_tx(bar_vf + 8 * s, 32768);
                    tma_load_2d(sv, &P.mapV, bar_vf + 8 * s, 0, h * SEQ + j * 128);
                    tma_load_2d(sv + 16384, &P.mapV, bar_vf + 8 * s, 64, h * SEQ + j * 128);
                }
            }
        }
    } else {
        asm volatile("setmaxnreg.inc.sync.aligned.u32 232;");
        const int wg = warp >> 2;
        const int lane = threadIdx.x & 31;
        float o[64];
        float mrow0, mrow1, lrow0, lrow1;
        const float sc = 0.08838834764831845f * 1.4426950408889634f;
        const int r0 = wg * 64 + (warp & 3) * 16 + (lane >> 2);
        float sacc[64];
        uint32_t pa[32];
        float a0 = 1.f, a1 = 1.f;
        auto issue_qk = [&](int it) {
            const int s = it % FA_STAGES;
            const uint32_t sk = sKV + s * 65536;
            mbar_wait(bar_kf + 8 * s, (it / FA_STAGES) & 1);
            wgmma_fence();
#pragma unroll
            for (int kk = 0; kk < 8; kk++) {
                uint64_t da = make_desc(sQ + (kk >> 2) * 16384 + wg * 8192 + (kk & 3) * 32, 16, 1024);
                uint64_t db = make_desc(sk + (kk >> 2) * 16384 + (kk & 3) * 32, 16, 1024);
                wgmma_ss_n128<0>(sacc, da, db, kk != 0);
            }
            wgmma_commit();
        };
        auto issue_pv = [&](int it) {
            const int s = it % FA_STAGES;
            const uint32_t sv = sKV + s * 65536 + 32768;
            mbar_wait(bar_vf + 8 * s, (it / FA_STAGES) & 1);
            wgmma_fence();
#pragma unroll
            for (int kk = 0; kk < 8; kk++) {
                uint64_t db = make_desc(sv + kk * 2048, 16384, 1024);
                wgmma_rs_n128_tb(o, pa[kk * 4 + 0], pa[kk * 4 + 1], pa[kk * 4 + 2], pa[kk * 4 + 3], db, 1);
            }
            wgmma_commit();
        };
        auto softmax_stats = [&](bool diag) {
            if (diag) {
#pragma unroll
                for (int i = 0; i < 64; i++) {
                    int col = (i >> 2) * 8 + (lane & 3) * 2 + (i & 1);
                    int row = r0 + ((i & 2) ? 8 : 0);
                    if (col > row) sacc[i] = -INFINITY;
                }
            }
            float mx0 = -INFINITY, mx1 = -INFINITY;
#pragma unroll
            for (int i = 0; i < 16; i++) {
                mx0 = fmaxf(mx0, fmaxf(sacc[i * 4 + 0], sacc[i * 4 + 1]));
                mx1 = fmaxf(mx1, fmaxf(sacc[i * 4 + 2], sacc[i * 4 + 3]));
            }
            mx0 = fmaxf(mx0, __shfl_xor_sync(0xffffffff, mx0, 1));
            mx0 = fmaxf(mx0, __shfl_xor_sync(0xffffffff, mx0, 2));
            mx1 = fmaxf(mx1, __shfl_xor_sync(0xffffffff, mx1, 1));
            mx1 = fmaxf(mx1, __shfl_xor_sync(0xffffffff, mx1, 2));
            const float mn0 = fmaxf(mrow0, mx0), mn1 = fmaxf(mrow1, mx1);
            a0 = ex2f((mrow0 - mn0) * sc); a1 = ex2f((mrow1 - mn1) * sc);
            mrow0 = mn0; mrow1 = mn1;
            const float ms0 = mn0 * sc, ms1 = mn1 * sc;
            float sum0 = 0.f, sum1 = 0.f;
#pragma unroll
            for (int i = 0; i < 16; i++) {
                sacc[i * 4 + 0] = ex2f(fmaf(sacc[i * 4 + 0], sc, -ms0));
                sacc[i * 4 + 1] = ex2f(fmaf(sacc[i * 4 + 1], sc, -ms0));
                sacc[i * 4 + 2] = ex2f(fmaf(sacc[i * 4 + 2], sc, -ms1));
                sacc[i * 4 + 3] = ex2f(fmaf(sacc[i * 4 + 3], sc, -ms1));
                sum0 += sacc[i * 4 + 0] + sacc[i * 4 + 1];
                sum1 += sacc[i * 4 + 2] + sacc[i * 4 + 3];
            }
            lrow0 = lrow0 * a0 + sum0;
            lrow1 = lrow1 * a1 + sum1;
        };
        auto pack_p = [&]() {
#pragma unroll
            for (int i = 0; i < 16; i++) {
                pa[i * 2 + 0] = pack_bf16(sacc[i * 4 + 0], sacc[i * 4 + 1]);
                pa[i * 2 + 1] = pack_bf16(sacc[i * 4 + 2], sacc[i * 4 + 3]);
            }
        };
        int it = 0;
        if (wg == 1) asm volatile("bar.arrive 1, 256;" ::: "memory");
        for (int item = 0;; item++) {
            mbar_wait(bar_q, item & 1);
            int t;
            asm volatile("ld.shared.s32 %0, [%1];" : "=r"(t) : "r"(slot + (item & 1) * 4) : "memory");
            if (t < 0) {
                if ((threadIdx.x & 127) == 0) {
                    mbar_wait(bar_oe + 8 * wg, (item & 1) ^ 1);
                    asm volatile("st.shared.s32 [%0], %1;" :: "r"(oslot + wg * 4), "r"(-1) : "memory");
                    mbar_arrive(bar_of + 8 * wg);
                }
                break;
            }
            const int qt = fa_qt(t);
            const int nkv = qt + 1;
#pragma unroll
            for (int i = 0; i < 64; i++) o[i] = 0.f;
            mrow0 = -INFINITY; mrow1 = -INFINITY; lrow0 = 0.f; lrow1 = 0.f;
            asm volatile("bar.sync %0, 256;" :: "r"(1 + wg) : "memory");
            issue_qk(it);
            asm volatile("bar.arrive %0, 256;" :: "r"(2 - wg) : "memory");
            wgmma_wait<0>();
            if (lane == 0) { mbar_arrive(bar_ek + 8 * (it % FA_STAGES)); if (nkv == 1) mbar_arrive(bar_qe); }
            softmax_stats(nkv == 1);
            pack_p();
#pragma unroll 1
            for (int j = 1; j < nkv; j++) {
                asm volatile("bar.sync %0, 256;" :: "r"(1 + wg) : "memory");
                issue_qk(it + j);
                issue_pv(it + j - 1);
                asm volatile("bar.arrive %0, 256;" :: "r"(2 - wg) : "memory");
                wgmma_wait<1>();
                if (lane == 0) { mbar_arrive(bar_ek + 8 * ((it + j) % FA_STAGES)); if (j == nkv - 1) mbar_arrive(bar_qe); }
                softmax_stats(j == nkv - 1);
                wgmma_wait<0>();
                if (lane == 0) mbar_arrive(bar_e + 8 * ((it + j - 1) % FA_STAGES));
#pragma unroll
                for (int i = 0; i < 16; i++) {
                    o[i * 4 + 0] *= a0; o[i * 4 + 1] *= a0; o[i * 4 + 2] *= a1; o[i * 4 + 3] *= a1;
                }
                pack_p();
            }
            issue_pv(it + nkv - 1);
            wgmma_wait<0>();
            if (lane == 0) mbar_arrive(bar_e + 8 * ((it + nkv - 1) % FA_STAGES));
            it += nkv;
            lrow0 += __shfl_xor_sync(0xffffffff, lrow0, 1);
            lrow0 += __shfl_xor_sync(0xffffffff, lrow0, 2);
            lrow1 += __shfl_xor_sync(0xffffffff, lrow1, 1);
            lrow1 += __shfl_xor_sync(0xffffffff, lrow1, 2);
            const float i0 = 1.f / lrow0, i1 = 1.f / lrow1;
            const uint32_t stg = sO + wg * 16384;
            mbar_wait(bar_oe + 8 * wg, (item & 1) ^ 1);
            {
                const int row = (warp & 3) * 16 + (lane >> 2);
#pragma unroll
                for (int i = 0; i < 4; i++) {
                    const int ch = i * 4 + (lane & 3);
                    const uint32_t a = stg + (ch >> 3) * 8192 + row * 128 + (((ch & 7) ^ (row & 7)) << 4);
                    const float* q = &o[i * 16];
                    asm volatile("st.shared.v4.b32 [%0], {%1, %2, %3, %4};" :: "r"(a), "r"(pack_bf16(q[0] * i0, q[1] * i0)), "r"(pack_bf16(q[4] * i0, q[5] * i0)),
                                 "r"(pack_bf16(q[8] * i0, q[9] * i0)), "r"(pack_bf16(q[12] * i0, q[13] * i0)) : "memory");
                    asm volatile("st.shared.v4.b32 [%0], {%1, %2, %3, %4};" :: "r"(a + 1024), "r"(pack_bf16(q[2] * i1, q[3] * i1)), "r"(pack_bf16(q[6] * i1, q[7] * i1)),
                                 "r"(pack_bf16(q[10] * i1, q[11] * i1)), "r"(pack_bf16(q[14] * i1, q[15] * i1)) : "memory");
                }
            }
            asm volatile("fence.proxy.async.shared::cta;" ::: "memory");
            asm volatile("bar.sync %0, 128;" :: "r"(3 + wg) : "memory");
            if ((threadIdx.x & 127) == 0) {
                asm volatile("st.shared.s32 [%0], %1;" :: "r"(oslot + wg * 4), "r"(t) : "memory");
                mbar_arrive(bar_of + 8 * wg);
            }
        }
        TS_END(1);
    }
}

__device__ __forceinline__ uint32_t cluster_ctarank() {
    uint32_t r; asm volatile("mov.u32 %0, %%cluster_ctarank;" : "=r"(r)); return r;
}
__device__ __forceinline__ uint32_t mapa_u32(uint32_t addr, uint32_t rank) {
    uint32_t r; asm volatile("mapa.shared::cluster.u32 %0, %1, %2;" : "=r"(r) : "r"(addr), "r"(rank)); return r;
}
__device__ __forceinline__ void cluster_sync_all() {
    asm volatile("barrier.cluster.arrive.release.aligned;\nbarrier.cluster.wait.acquire.aligned;" ::: "memory");
}
__device__ __forceinline__ void st_async_v4(uint32_t addr, uint32_t a, uint32_t b, uint32_t c, uint32_t d, uint32_t mbar) {
    asm volatile("st.async.weak.shared::cluster.mbarrier::complete_tx::bytes.v4.b32 [%0], {%1, %2, %3, %4}, [%5];"
                 :: "r"(addr), "r"(a), "r"(b), "r"(c), "r"(d), "r"(mbar) : "memory");
}
__device__ __forceinline__ void st_async_v2(uint32_t addr, uint32_t a, uint32_t b, uint32_t mbar) {
    asm volatile("st.async.weak.shared::cluster.mbarrier::complete_tx::bytes.v2.b32 [%0], {%1, %2}, [%3];"
                 :: "r"(addr), "r"(a), "r"(b), "r"(mbar) : "memory");
}
__device__ __forceinline__ void st_async_b32(uint32_t addr, uint32_t a, uint32_t mbar) {
    asm volatile("st.async.weak.shared::cluster.mbarrier::complete_tx::bytes.b32 [%0], %1, [%2];" :: "r"(addr), "r"(a), "r"(mbar) : "memory");
}
__device__ __forceinline__ void pace(int cycles) {
    if (cycles > 0) {
        uint32_t t0, t;
        asm volatile("mov.u32 %0, %%clock;" : "=r"(t0));
        do { asm volatile("mov.u32 %0, %%clock;" : "=r"(t)); } while (t - t0 < (uint32_t)cycles);
    }
}
__device__ __forceinline__ void mbar_wait_cl(uint32_t bar, uint32_t parity) {
    uint32_t done = 0;
    for (int it = 0; it < WAIT_LIMIT && !done; it++) {
        asm volatile(
            "{\n.reg .pred p;\n"
            "mbarrier.try_wait.parity.shared::cta.b64 p, [%1], %2;\n"
            "selp.u32 %0, 1, 0, p;\n}\n" : "=r"(done) : "r"(bar), "r"(parity) : "memory");
    }
}
__device__ __forceinline__ uint32_t mbar_test(uint32_t bar, uint32_t parity) {
    uint32_t done;
    asm volatile(
        "{\n.reg .pred p;\n"
        "mbarrier.test_wait.parity.shared::cta.b64 p, [%1], %2;\n"
        "selp.u32 %0, 1, 0, p;\n}\n" : "=r"(done) : "r"(bar), "r"(parity) : "memory");
    return done;
}
__device__ __forceinline__ void ldmatrix_x4(uint32_t& r0, uint32_t& r1, uint32_t& r2, uint32_t& r3, uint32_t addr) {
    asm volatile("ldmatrix.sync.aligned.m8n8.x4.shared.b16 {%0,%1,%2,%3}, [%4];"
                 : "=r"(r0), "=r"(r1), "=r"(r2), "=r"(r3) : "r"(addr));
}
__device__ __forceinline__ void cp_async16(uint32_t dst, const void* src) {
    asm volatile("cp.async.cg.shared.global [%0], [%1], 16;" :: "r"(dst), "l"(src) : "memory");
}
__device__ __forceinline__ float bf16r(float x) { return __uint_as_float(pack_bf16(0.f, x) & 0xffff0000u); }

#define DBG(i, w)
#define DBGD(i, w, dep)
__device__ __forceinline__ void tma_load_2d_mc(uint32_t dst, const CUtensorMap* map, uint32_t bar, int c0, int c1, uint16_t mask) {
    asm volatile(
        "cp.async.bulk.tensor.2d.shared::cluster.global.mbarrier::complete_tx::bytes.multicast::cluster [%0], [%1, {%3, %4}], [%2], %5;"
        :: "r"(dst), "l"((uint64_t)map), "r"(bar), "r"(c0), "r"(c1), "h"(mask) : "memory");
}
__device__ __forceinline__ void stmatrix_x4_trans(uint32_t addr, uint32_t r0, uint32_t r1, uint32_t r2, uint32_t r3) {
    asm volatile("stmatrix.sync.aligned.m8n8.x4.trans.shared.b16 [%0], {%1, %2, %3, %4};" :: "r"(addr), "r"(r0), "r"(r1), "r"(r2), "r"(r3) : "memory");
}
__device__ __forceinline__ void stmatrix_x2_trans(uint32_t addr, uint32_t r0, uint32_t r1) {
    asm volatile("stmatrix.sync.aligned.m8n8.x2.trans.shared.b16 [%0], {%1, %2};" :: "r"(addr), "r"(r0), "r"(r1) : "memory");
}
__device__ __forceinline__ uint4 lds128(uint32_t a) {
    uint4 v; asm volatile("ld.shared.v4.u32 {%0, %1, %2, %3}, [%4];" : "=r"(v.x), "=r"(v.y), "=r"(v.z), "=r"(v.w) : "r"(a) : "memory"); return v;
}
__device__ __forceinline__ float2 lds64f(uint32_t a) {
    float2 v; asm volatile("ld.shared.v2.f32 {%0, %1}, [%2];" : "=f"(v.x), "=f"(v.y) : "r"(a) : "memory"); return v;
}
__device__ __forceinline__ void fence_async_smem() { asm volatile("fence.proxy.async.shared::cta;" ::: "memory"); }
#define ACC16(d) "+f"(d[0]), "+f"(d[1]), "+f"(d[2]), "+f"(d[3]), "+f"(d[4]), "+f"(d[5]), "+f"(d[6]), "+f"(d[7]), "+f"(d[8]), "+f"(d[9]), "+f"(d[10]), "+f"(d[11]), "+f"(d[12]), "+f"(d[13]), "+f"(d[14]), "+f"(d[15])
template <int ND>
__device__ __forceinline__ void wgmma_rs_n32(float (&d)[ND], const uint32_t (&a)[4], uint32_t db_lo, int scale_d) {
    asm volatile(
        "{\n.reg .pred p;\n.reg .b64 db;\nsetp.ne.b32 p, %21, 0;\nmov.b64 db, {%20, 0x40000040};\n"
        "wgmma.mma_async.sync.aligned.m64n32k16.f32.bf16.bf16 {%0,%1,%2,%3,%4,%5,%6,%7,%8,%9,%10,%11,%12,%13,%14,%15}, {%16,%17,%18,%19}, db, p, 1, 1, 0;\n}\n"
        : ACC16(d) : "r"(a[0]), "r"(a[1]), "r"(a[2]), "r"(a[3]), "r"(db_lo), "r"(scale_d));
}
template <int ND>
__device__ __forceinline__ void wgmma_ss_n32(float (&d)[ND], uint32_t da_lo, uint32_t db_lo, int scale_d) {
    asm volatile(
        "{\n.reg .pred p;\n.reg .b64 da, db;\nsetp.ne.b32 p, %18, 0;\nmov.b64 da, {%16, 0x40000040};\nmov.b64 db, {%17, 0x40000040};\n"
        "wgmma.mma_async.sync.aligned.m64n32k16.f32.bf16.bf16 {%0,%1,%2,%3,%4,%5,%6,%7,%8,%9,%10,%11,%12,%13,%14,%15}, da, db, p, 1, 1, 1, 0;\n}\n"
        : ACC16(d) : "r"(da_lo), "r"(db_lo), "r"(scale_d));
}
__device__ __forceinline__ void wgmma_rs_n40(float (&d)[20], const uint32_t (&a)[4], uint32_t db_lo, int scale_d) {
    asm volatile(
        "{\n.reg .pred p;\n.reg .b64 db;\nsetp.ne.b32 p, %25, 0;\nmov.b64 db, {%24, 0x40000040};\n"
        "wgmma.mma_async.sync.aligned.m64n40k16.f32.bf16.bf16 {%0,%1,%2,%3,%4,%5,%6,%7,%8,%9,%10,%11,%12,%13,%14,%15,%16,%17,%18,%19}, {%20,%21,%22,%23}, db, p, 1, 1, 0;\n}\n"
        : "+f"(d[0]), "+f"(d[1]), "+f"(d[2]), "+f"(d[3]), "+f"(d[4]), "+f"(d[5]), "+f"(d[6]), "+f"(d[7]), "+f"(d[8]), "+f"(d[9]), "+f"(d[10]), "+f"(d[11]), "+f"(d[12]), "+f"(d[13]), "+f"(d[14]), "+f"(d[15]), "+f"(d[16]), "+f"(d[17]), "+f"(d[18]), "+f"(d[19])
        : "r"(a[0]), "r"(a[1]), "r"(a[2]), "r"(a[3]), "r"(db_lo), "r"(scale_d));
}
__device__ __forceinline__ void wgmma_ss_n40(float (&d)[20], uint32_t da_lo, uint32_t db_lo, int scale_d) {
    asm volatile(
        "{\n.reg .pred p;\n.reg .b64 da, db;\nsetp.ne.b32 p, %22, 0;\nmov.b64 da, {%20, 0x40000040};\nmov.b64 db, {%21, 0x40000040};\n"
        "wgmma.mma_async.sync.aligned.m64n40k16.f32.bf16.bf16 {%0,%1,%2,%3,%4,%5,%6,%7,%8,%9,%10,%11,%12,%13,%14,%15,%16,%17,%18,%19}, da, db, p, 1, 1, 1, 0;\n}\n"
        : ACC16(d), "+f"(d[16]), "+f"(d[17]), "+f"(d[18]), "+f"(d[19]) : "r"(da_lo), "r"(db_lo), "r"(scale_d));
}
__device__ __forceinline__ void wgmma_ss_n8(float (&d)[4], uint32_t da_lo, uint32_t db_lo, int scale_d) {
    asm volatile(
        "{\n.reg .pred p;\n.reg .b64 da, db;\nsetp.ne.b32 p, %6, 0;\nmov.b64 da, {%4, 0x40000040};\nmov.b64 db, {%5, 0x00000010};\n"
        "wgmma.mma_async.sync.aligned.m64n8k16.f32.bf16.bf16 {%0,%1,%2,%3}, da, db, p, 1, 1, 1, 0;\n}\n"
        : "+f"(d[0]), "+f"(d[1]), "+f"(d[2]), "+f"(d[3]) : "r"(da_lo), "r"(db_lo), "r"(scale_d));
}

struct ChainParams {
    CUtensorMap mapW[3];
    CUtensorMap mapX;
};
constexpr int CH_BLOCK = 384;
constexpr int CH_RS = 144;
constexpr int CH_XCH = 5120;
constexpr int CH_XB = 8 * CH_XCH;
constexpr int CO_WO = 0;
constexpr int CO_XB = 65536;
constexpr int CO_OB = CO_XB + 2 * CH_XB;
constexpr int CO_QX = CO_OB + 8192;
constexpr int CO_KX = CO_QX + 2 * 32 * CH_RS;
constexpr int CO_VX = CO_KX + 2 * 40 * CH_RS;
constexpr int CO_QM = CO_VX + 2 * 48 * CH_RS;
constexpr int CO_SC = CO_QM + 8 * CH_RS;
constexpr int CO_LS = CO_SC + 2 * 1280;
constexpr int CO_ST = CO_LS + 2 * 4 * 1280;
#define CH_NSM 2
constexpr int CO_WA = (CO_ST + 32 * CH_RS + 1023) / 1024 * 1024;
constexpr int CO_BAR = CO_WA + 3 * CH_NSM * 2048;
constexpr int CH_SMEM = CO_BAR + 256 + 1024;
static_assert(CO_WA >= 3 * 65536, "weight staging overlaps the barriers");
#define CH_POLL_AT 12

__device__ __forceinline__ float chain_softmax(float (&v)[10]) {
    float mx = fmaxf(fmaxf(fmaxf(v[0], v[1]), fmaxf(v[2], v[3])), fmaxf(fmaxf(v[4], v[5]), fmaxf(v[6], v[7])));
    mx = fmaxf(mx, fmaxf(v[8], v[9]));
    mx = fmaxf(mx, __shfl_xor_sync(0xffffffff, mx, 1));
    mx = fmaxf(mx, __shfl_xor_sync(0xffffffff, mx, 2));
    const float sc = 0.08838834764831845f * 1.4426950408889634f;
    const float mxl = mx * sc;
#pragma unroll
    for (int j = 0; j < 10; j++) v[j] = ex2f(fmaf(v[j], sc, -mxl));
    return ((v[0] + v[1]) + (v[2] + v[3])) + ((v[4] + v[5]) + (v[6] + v[7])) + (v[8] + v[9]);
}

__global__ void __cluster_dims__(8, 1, 1) __launch_bounds__(CH_BLOCK, 1)
chain_kernel(const __grid_constant__ ChainParams P, const bf16* __restrict__ mem0, const bf16* __restrict__ Wo, const bf16* __restrict__ x) {
    extern __shared__ uint8_t smem_raw[];
    const uint32_t sb = (smem_u32(smem_raw) + 1023) & ~1023u;
    const int tid = threadIdx.x, warp = __shfl_sync(0xffffffff, tid >> 5, 0), lane = tid & 31;
    const int rank = (int)cluster_ctarank();
    const int C = blockIdx.x >> 3;
    const int h = C * 4 + (rank >> 1);
    const int qd = lane >> 2, qc = lane & 3;
    const int t4 = warp & 3, wg = warp >> 2;
    pdl_launch_dependents();
    TS_BEGIN(2);
    const uint32_t bar_mem = sb + CO_BAR, bar_o = bar_mem + 32, bar_sc = bar_o + 32, bar_x = bar_sc + 8, bar_l = bar_x + 16, bar_w = bar_l + 64;
    if (tid == 0) {
        for (int j = 0; j < 22; j++) mbar_init(bar_mem + 8 * j, 1);
        asm volatile("fence.mbarrier_init.release.cluster;" ::: "memory");
    }
    __syncthreads();
    if ((tid & 127) == 0) {
        mbar_expect_tx(bar_w + 8 * wg, 65536);
        for (int i = 0; i < 8; i++)
            tma_load_2d(sb + wg * 65536 + i * 8192, &P.mapW[wg], bar_w + 8 * wg, h * HD + (rank & 1) * 64, i * 64);
    }
    {
        for (int i = tid; i < 512; i += CH_BLOCK) asm volatile("prefetch.global.L2 [%0];" :: "l"(Wo + (size_t)(C * 512 + i) * DM + rank * 64));
        if (tid < 64) asm volatile("prefetch.global.L2 [%0];" :: "l"(x + (size_t)tid * DM + rank * 64));
    }
    auto chunk = [&](int i) { return (uint32_t)((rank - (i >> 1) - 4 * (i & 1)) & 7); };
    const uint32_t wfrag = (((lane >> 4) << 3) + (lane & 7)) * 128 + (((t4 * 2 + ((lane >> 3) & 1)) ^ (lane & 7)) << 4);
    auto load_w = [&](uint32_t (&w)[32][4]) {
        mbar_wait(bar_w + 8 * wg, 0);
#pragma unroll
        for (int e = CH_NSM; e < 32; e++) ldmatrix_x4_trans(w[e][0], w[e][1], w[e][2], w[e][3], sb + wg * 65536 + wfrag + chunk(e >> 2) * 8192 + (e & 3) * 2048);
#pragma unroll
        for (int e = 0; e < CH_NSM; e++) {
            const uint4 u = lds128(sb + wg * 65536 + chunk(0) * 8192 + e * 2048 + (tid & 127) * 16);
            asm volatile("st.shared.v4.b32 [%0], {%1, %2, %3, %4};" :: "r"(sb + CO_WA + (wg * CH_NSM + e) * 2048 + (tid & 127) * 16), "r"(u.x), "r"(u.y), "r"(u.z), "r"(u.w) : "memory");
        }
        fence_async_smem();
    };
    auto prologue = [&]() {
    asm volatile("bar.sync 0, 384;" ::: "memory");
    if (tid == 0) {
        fence_async_smem();
        for (int b = 0; b < 2; b++) {
            mbar_expect_tx(bar_x + 8 * b, 32768);
            for (int i = 0; i < 8; i++) tma_load_2d(sb + CO_XB + b * CH_XB + i * CH_XCH, &P.mapX, bar_x + 8 * b, i * 64, b * SEGL);
        }
    }
#pragma unroll 2
    for (int i = tid; i < 512 * 4; i += CH_BLOCK) {
        const int r = i >> 2, cg = i & 3, ks = r >> 4, kp = r & 15;
        const int src = (rank - (ks >> 2)) & 7;
        const uint4* p = reinterpret_cast<const uint4*>(Wo + (size_t)(C * 512 + src * 64 + (ks & 3) * 16 + (kp >> 1) + 8 * (kp & 1)) * DM + rank * 64 + cg * 16);
        const uint4 u0 = __ldg(p), u1 = __ldg(p + 1);
        const uint32_t a = sb + CO_WO + r * 128;
        asm volatile("st.shared.v4.b32 [%0], {%1, %2, %3, %4};" :: "r"(a + (((cg * 2) ^ (r & 7)) << 4)), "r"(__byte_perm(u0.x, u0.y, 0x5410)),
                     "r"(__byte_perm(u0.z, u0.w, 0x5410)), "r"(__byte_perm(u1.x, u1.y, 0x5410)), "r"(__byte_perm(u1.z, u1.w, 0x5410)) : "memory");
        asm volatile("st.shared.v4.b32 [%0], {%1, %2, %3, %4};" :: "r"(a + (((cg * 2 + 1) ^ (r & 7)) << 4)), "r"(__byte_perm(u0.x, u0.y, 0x7632)),
                     "r"(__byte_perm(u0.z, u0.w, 0x7632)), "r"(__byte_perm(u1.x, u1.y, 0x7632)), "r"(__byte_perm(u1.z, u1.w, 0x7632)) : "memory");
    }
#pragma unroll 1
    for (int i = tid; i < 512; i += CH_BLOCK) {
        const int n = i >> 6, c = i & 63;
        const uint4 u = __ldg(reinterpret_cast<const uint4*>(mem0 + n * DM + c * 8));
        asm volatile("st.shared.v4.b32 [%0], {%1, %2, %3, %4};" :: "r"(sb + CO_XB + CH_XB + (c >> 3) * CH_XCH + 4096 + n * 128 + (((c & 7) ^ n) << 4)),
                     "r"(u.x), "r"(u.y), "r"(u.z), "r"(u.w) : "memory");
    }
#pragma unroll 1
    for (int i = tid; i < 2 * 8 * CH_RS / 4; i += CH_BLOCK)
        asm volatile("st.shared.b32 [%0], %1;" :: "r"(sb + CO_VX + (i >= 8 * CH_RS / 4 ? 40 * CH_RS : 0) + 40 * CH_RS + i * 4), "r"(0) : "memory");
    fence_async_smem();
    TS_END(6);
    mbar_wait(bar_x, 0);
    };
    auto store32 = [&](const float* d, uint32_t dst) {
        const uint32_t a = dst + (((lane >> 4) << 3) + (lane & 7)) * CH_RS + t4 * 32 + ((lane >> 3) & 1) * 16;
        stmatrix_x4_trans(a, pack_bf16(d[0], d[1]), pack_bf16(d[2], d[3]), pack_bf16(d[4], d[5]), pack_bf16(d[6], d[7]));
        stmatrix_x4_trans(a + 16 * CH_RS, pack_bf16(d[8], d[9]), pack_bf16(d[10], d[11]), pack_bf16(d[12], d[13]), pack_bf16(d[14], d[15]));
    };
    auto remote = [](uint32_t a, uint32_t r) { return mapa_u32(a, r); };

    if (wg < 2) {
        uint32_t w[32][4];
        float d[16];
        load_w(w);
        prologue();
        auto pass32 = [&](int b, int e0, int e1) {
            const uint32_t lo = desc_lo(sb + CO_XB + b * CH_XB, 16);
#pragma unroll
            for (int e = 0; e < 32; e++) if (e >= e0 && e < e1) {
                const uint32_t db = lo + chunk(e >> 2) * (CH_XCH >> 4) + (e & 3) * 2;
                if (e < CH_NSM) wgmma_ss_n32(d, desc_lo(sb + CO_WA + (wg * CH_NSM + e) * 2048, 16), db, e != 0);
                else wgmma_rs_n32(d, w[e], db, e != 0);
            }
        };
        wgmma_fence();
        pass32(0, 0, 32);
        wgmma_commit();
        wgmma_wait<0>();
        store32(d, sb + (wg == 0 ? CO_QX : CO_KX));
        asm volatile("bar.sync 0, 384;" ::: "memory");
        cluster_sync_all();
        TS_BEGIN(5);
#pragma unroll 1
        for (int s = 0; s < NSEG; s++) {
            const uint32_t par = s & 1;
            {
                float acc[2][4];
#pragma unroll
                for (int i = 0; i < 2; i++) acc[i][0] = acc[i][1] = acc[i][2] = acc[i][3] = 0.f;
#pragma unroll
                for (int e = 0; e < CH_NSM; e++) ldmatrix_x4_trans(w[e][0], w[e][1], w[e][2], w[e][3], sb + CO_WA + (wg * CH_NSM + e) * 2048 + wfrag);
                const uint32_t mb = sb + CO_XB + (par ^ 1) * CH_XB + 4096 + (lane & 7) * 128 + (((lane >> 3) ^ (lane & 7)) << 4);
                uint32_t ok = s == 0;
#pragma unroll
                for (int g = 0; g < 4; g++) {
                    if (!ok) mbar_wait_cl(bar_mem + 8 * g, par ^ 1);
                    if (g == 0) DBG(11, 0);
                    if (g == 3) DBG(13, 0);
                    uint32_t b[2][8];
#pragma unroll
                    for (int j = 0; j < 2; j++) {
                        const uint32_t a = mb + chunk(g * 2 + j) * CH_XCH;
                        ldmatrix_x4(b[j][0], b[j][1], b[j][2], b[j][3], a);
                        ldmatrix_x4(b[j][4], b[j][5], b[j][6], b[j][7], a ^ 64);
                    }
                    if (g < 3 && s > 0) ok = mbar_test(bar_mem + 8 * (g + 1), par ^ 1);
#pragma unroll
                    for (int i = 0; i < 8; i++) {
                        const int e = g * 8 + i;
                        mma_16816(acc[i & 1], w[e][0], w[e][1], w[e][2], w[e][3], b[i >> 2][(i & 3) * 2], b[i >> 2][(i & 3) * 2 + 1]);
                    }
                }
                const uint32_t r0 = pack_bf16(acc[0][0] + acc[1][0], acc[0][1] + acc[1][1]);
                const uint32_t r1 = pack_bf16(acc[0][2] + acc[1][2], acc[0][3] + acc[1][3]);
                DBGD(40 + warp, warp, r0 ^ r1);
                const uint32_t dst = wg == 0 ? sb + CO_QM : sb + CO_KX + (par * 40 + 32) * CH_RS;
                stmatrix_x2_trans(dst + (lane & 7) * CH_RS + t4 * 32 + ((lane >> 3) & 1) * 16, r0, r1);
            }
            if (s == NSEG - 1) {
                asm volatile("bar.sync 1, 256;" ::: "memory");
                if (warp < 5) asm volatile("bar.arrive 2, 288;" ::: "memory");
                break;
            }
            if (warp < 5) {
                asm volatile("bar.sync 1, 256;" ::: "memory");
                const uint32_t ka = sb + CO_KX + (par * 40 + warp * 8 + qd) * CH_RS + qc * 16, qa_ = sb + CO_QM + qd * CH_RS + qc * 16;
                const uint4 qa = lds128(qa_), k0 = lds128(ka), qb = lds128(qa_ + 64), k1 = lds128(ka + 64);
                DBGD(48 + warp, warp, qa.x ^ qb.x);
                float c[4] = {0.f, 0.f, 0.f, 0.f}, c2[4] = {0.f, 0.f, 0.f, 0.f};
                mma_16816(c, qa.x, 0u, qa.y, 0u, k0.x, k0.y);
                mma_16816(c2, qb.x, 0u, qb.y, 0u, k1.x, k1.y);
                mma_16816(c, qa.z, 0u, qa.w, 0u, k0.z, k0.w);
                mma_16816(c2, qb.z, 0u, qb.w, 0u, k1.z, k1.w);
                c[0] += c2[0]; c[1] += c2[1];
                DBGD(56 + warp, warp, __float_as_uint(c[0]));
                const uint32_t off = sb + CO_SC + warp * 256 + lane * 8;
                st_async_v2(remote(off + 1280, rank ^ 1), __float_as_uint(c[0]), __float_as_uint(c[1]), remote(bar_sc, rank ^ 1));
                st_async_v2(remote(off, rank), __float_as_uint(c[0]), __float_as_uint(c[1]), remote(bar_sc, rank));
                asm volatile("bar.arrive 2, 288;" ::: "memory");
                DBG(3, 0);
            } else {
                asm volatile("bar.arrive 1, 256;" ::: "memory");
            }
            uint32_t* xw = g_xbuf + (size_t)rank * 2048;
            if (wg == 0) {
                if (tid == 0) {
#pragma unroll
                    for (int j = 0; j < 4; j++) { mbar_expect_tx(bar_mem + 8 * j, 2048); mbar_expect_tx(bar_o + 8 * j, 2048); }
                    mbar_expect_tx(bar_sc, 2 * 1280);
                }
                __syncwarp();
                mbar_wait(bar_x + 8 * (par ^ 1), ((s + 1) >> 1) & 1);
                float c[4];
                const uint32_t alo = desc_lo(sb + CO_WO, 16), blo = desc_lo(sb + CO_OB, 128);
#pragma unroll
                for (int g = 0; g < 4; g++) {
                    mbar_wait_cl(bar_o + 8 * g, par);
                    if (g == 0) DBG(16, 0);
                    if (g == 3) DBG(18, 0);
                    fence_async_smem();
                    wgmma_fence();
#pragma unroll
                    for (int i = 0; i < 8; i++) wgmma_ss_n8(c, alo + (g * 8 + i) * 128, blo + (g * 8 + i) * 16, (g | i) != 0);
                    wgmma_commit();
                }
                wgmma_wait<0>();
                uint32_t* wp = xw + C * 256 + qc * 64 + t4 * 8 + qd;
                asm volatile("st.relaxed.gpu.global.u32 [%0], %1;" :: "l"(wp + (s & 3) * 16384), "r"(~pack_bf16(c[0], c[2])) : "memory");
                asm volatile("st.relaxed.gpu.global.u32 [%0], %1;" :: "l"(wp + (s & 3) * 16384 + 32), "r"(~pack_bf16(c[1], c[3])) : "memory");
                asm volatile("bar.arrive 4, 256;" ::: "memory");
                DBG(8, 0);
                asm volatile("st.relaxed.gpu.global.u32 [%0], %1;" :: "l"(wp + ((s + 2) & 3) * 16384), "r"(0) : "memory");
                asm volatile("st.relaxed.gpu.global.u32 [%0], %1;" :: "l"(wp + ((s + 2) & 3) * 16384 + 32), "r"(0) : "memory");
                if (tid == 0 && s + 2 < NSEG) {
                    mbar_expect_tx(bar_x + 8 * par, 32768);
                    tma_load_2d_mc(sb + CO_XB + par * CH_XB + rank * CH_XCH, &P.mapX, bar_x + 8 * par, rank * 64, (s + 2) * SEGL, (uint16_t)0xff);
                }
                __syncwarp();
            } else {
                uint32_t va[3][4];
                const uint32_t vaddr = sb + CO_VX + (par * 48 + (lane & 7) + ((lane >> 4) << 3)) * CH_RS + t4 * 32 + ((lane >> 3) & 1) * 16;
                ldmatrix_x4_trans(va[0][0], va[0][1], va[0][2], va[0][3], vaddr);
                ldmatrix_x4_trans(va[1][0], va[1][1], va[1][2], va[1][3], vaddr + 16 * CH_RS);
                mbar_wait_cl(bar_sc, par);
                DBG(4, 4);
                float v[10];
#pragma unroll
                for (int j = 0; j < 5; j++) {
                    const float2 a = lds64f(sb + CO_SC + j * 256 + lane * 8), b = lds64f(sb + CO_SC + 1280 + j * 256 + lane * 8);
                    v[2 * j] = a.x + b.x; v[2 * j + 1] = a.y + b.y;
                }
                float sm = chain_softmax(v);
                float c[4] = {0.f, 0.f, 0.f, 0.f}, c2[4] = {0.f, 0.f, 0.f, 0.f};
                DBG(19, 4);
                asm volatile("bar.sync 3, 256;" ::: "memory");
                ldmatrix_x4_trans(va[2][0], va[2][1], va[2][2], va[2][3], vaddr + 32 * CH_RS);
                mma_16816(c, va[0][0], va[0][1], va[0][2], va[0][3], pack_bf16(v[0], v[1]), pack_bf16(v[2], v[3]));
                mma_16816(c2, va[1][0], va[1][1], va[1][2], va[1][3], pack_bf16(v[4], v[5]), pack_bf16(v[6], v[7]));
                sm += __shfl_xor_sync(0xffffffff, sm, 1);
                sm += __shfl_xor_sync(0xffffffff, sm, 2);
                mma_16816(c, va[2][0], va[2][1], va[2][2], va[2][3], pack_bf16(v[8], v[9]), 0u);
                float inv;
                asm volatile("rcp.approx.ftz.f32 %0, %1;" : "=f"(inv) : "f"(sm));
                const float inv0 = __shfl_sync(0xffffffff, inv, (2 * qc) * 4), inv1 = __shfl_sync(0xffffffff, inv, (2 * qc + 1) * 4);
                DBG(20, 4);
                const uint32_t ra = pack_bf16((c[0] + c2[0]) * inv0, (c[2] + c2[2]) * inv0), rb = pack_bf16((c[1] + c2[1]) * inv1, (c[3] + c2[3]) * inv1);
                const uint32_t other = __shfl_xor_sync(0xffffffff, (qd & 1) ? ra : rb, 4);
                const uint32_t b0 = (qd & 1) ? other : ra, b1 = (qd & 1) ? rb : other;
                const uint32_t dsta = sb + CO_OB + t4 * 256 + (qd >> 2) * 128 + (2 * qc + (qd & 1)) * 16 + (qd & 2) * 4;
#pragma unroll
                for (int i = 0; i < 8; i++) {
                    const int dr = (rank + i) & 7;
                    st_async_v2(remote(dsta + i * 1024, dr), b0, b1, remote(bar_o + 8 * (i >> 1), dr));
                }
                DBG(5, 4);
                mbar_wait(bar_x + 8 * (par ^ 1), ((s + 1) >> 1) & 1);
                asm volatile("bar.sync 4, 256;" ::: "memory");
            }
            const uint2* xb = reinterpret_cast<const uint2*>(xw + (s & 3) * 16384 + (lane >> 4) * 1024 + warp * 32) + (lane & 15);
            uint2 p[4];
            wgmma_fence();
            pass32(par ^ 1, 0, CH_POLL_AT);
#pragma unroll
            for (int k = 0; k < 4; k++)
                asm volatile("ld.relaxed.gpu.global.v2.u32 {%0, %1}, [%2];" : "=r"(p[k].x), "=r"(p[k].y) : "l"(xb + k * 128) : "memory");
            pass32(par ^ 1, CH_POLL_AT, 32);
            wgmma_commit();
            DBG(21, 0);
            for (int it = 0; it < WAIT_LIMIT / 4; it++) {
                uint32_t bad = 0;
#pragma unroll
                for (int k = 0; k < 4; k++) bad |= (min(p[k].x, p[k].y) == 0u ? 1u : 0u) << k;
                if (__all_sync(0xffffffff, bad == 0u)) break;
#pragma unroll
                for (int k = 0; k < 4; k++)
                    if (bad & (1u << k))
                        asm volatile("ld.relaxed.gpu.global.v2.u32 {%0, %1}, [%2];" : "=r"(p[k].x), "=r"(p[k].y) : "l"(xb + k * 128) : "memory");
            }
            DBG(9, 0);
            {
                auto lo = [](uint32_t u) { return __uint_as_float(~u << 16); };
                auto hi = [](uint32_t u) { return __uint_as_float(~u & 0xffff0000u); };
                float r0 = (lo(p[0].x) + lo(p[1].x)) + (lo(p[2].x) + lo(p[3].x)), r1 = (hi(p[0].x) + hi(p[1].x)) + (hi(p[2].x) + hi(p[3].x));
                float r2 = (lo(p[0].y) + lo(p[1].y)) + (lo(p[2].y) + lo(p[3].y)), r3 = (hi(p[0].y) + hi(p[1].y)) + (hi(p[2].y) + hi(p[3].y));
                r0 += __shfl_xor_sync(0xffffffff, r0, 16); r1 += __shfl_xor_sync(0xffffffff, r1, 16);
                r2 += __shfl_xor_sync(0xffffffff, r2, 16); r3 += __shfl_xor_sync(0xffffffff, r3, 16);
                const uint32_t m0 = pack_bf16(r0, r1), m1 = pack_bf16(r2, r3);
                const uint32_t dsta = sb + CO_XB + par * CH_XB + rank * CH_XCH + 4096 + warp * 128 + ((((lane & 15) >> 1) ^ warp) << 4) + (lane & 1) * 8;
#pragma unroll
                for (int i = 0; i < 4; i++) {
                    const int dr = (rank + (lane >> 4) * 4 + i) & 7;
                    st_async_v2(remote(dsta, dr), m0, m1, remote(bar_mem + 8 * i, dr));
                }
            }
            DBG(10, 0);
            wgmma_wait<0>();
            store32(d, wg == 0 ? sb + CO_QX + (par ^ 1) * 32 * CH_RS : sb + CO_KX + (par ^ 1) * 40 * CH_RS);
            DBG(22, 0);
        }
        if (wg == 0) {
            uint32_t* wp = g_xbuf + 16384 + (size_t)rank * 2048 + C * 256 + tid * 2;
            *reinterpret_cast<uint2*>(wp) = make_uint2(0u, 0u);
        }
    } else {
        uint32_t w[32][4];
        float d[20];
        load_w(w);
        prologue();
        wgmma_fence();
#pragma unroll
        for (int e = 0; e < 32; e++) {
            const uint32_t db = desc_lo(sb + CO_XB, 16) + chunk(e >> 2) * (CH_XCH >> 4) + (e & 3) * 2;
            if (e < CH_NSM) wgmma_ss_n32(d, desc_lo(sb + CO_WA + (2 * CH_NSM + e) * 2048, 16), db, e != 0);
            else wgmma_rs_n32(d, w[e], db, e != 0);
        }
        wgmma_commit();
        wgmma_wait<0>();
        store32(d, sb + CO_VX);
        asm volatile("bar.sync 0, 384;" ::: "memory");
        cluster_sync_all();
#pragma unroll 1
        for (int s = 0; s < NSEG; s++) {
            const uint32_t par = s & 1;
            if (s + 1 < NSEG) mbar_wait(bar_x + 8 * (par ^ 1), ((s + 1) >> 1) & 1);
            asm volatile("bar.sync 2, 288;" ::: "memory");
            DBG(24, 8);
            fence_async_smem();
            wgmma_fence();
            {
                const uint32_t lo = desc_lo(sb + CO_XB + (par ^ 1) * CH_XB, 16);
#pragma unroll
                for (int e = 0; e < 32; e++) {
                    const uint32_t db = lo + chunk(e >> 2) * (CH_XCH >> 4) + (e & 3) * 2;
                    if (e < CH_NSM) wgmma_ss_n40(d, desc_lo(sb + CO_WA + (2 * CH_NSM + e) * 2048, 16), db, e != 0);
                    else wgmma_rs_n40(d, w[e], db, e != 0);
                }
            }
            wgmma_commit();
            wgmma_wait<0>();
            stmatrix_x2_trans(sb + CO_VX + (par * 48 + 32 + (lane & 7)) * CH_RS + t4 * 32 + ((lane >> 3) & 1) * 16, pack_bf16(d[16], d[17]), pack_bf16(d[18], d[19]));
            store32(d, sb + CO_VX + (par ^ 1) * 48 * CH_RS);
            if (s + 1 < NSEG) asm volatile("bar.arrive 3, 256;" ::: "memory");
            DBG(25, 8);
            if (s > 0 && (s & 3) == 0 && tid == 256) signal_ctr(CT_CB + ((s - 1) >> 2) * 2 + (h >= O2_HE));
            __syncwarp();
            float v[10];
            {
                const uint32_t qa_ = sb + CO_QX + (par * 32 + t4 * 8 + qd) * CH_RS + qc * 16;
                const uint4 qa = lds128(qa_), qb = lds128(qa_ + 64);
                const uint32_t lb = bar_l + (par * 4 + t4) * 8, ls = sb + CO_LS + (par * 4 + t4) * 1280 + lane * 8;
                if (lane == 0) mbar_expect_tx(lb, (t4 + 2) * 256);
#pragma unroll
                for (int n = 0; n < 5; n++) {
                    v[2 * n] = v[2 * n + 1] = -INFINITY;
                    if (n <= t4 || n == 4) {
                        const uint32_t ka = sb + CO_KX + (par * 40 + n * 8 + qd) * CH_RS + qc * 16;
                        const uint4 k0 = lds128(ka), k1 = lds128(ka + 64);
                        float c[4] = {0.f, 0.f, 0.f, 0.f};
                        mma_16816(c, qa.x, 0u, qa.y, 0u, k0.x, k0.y);
                        mma_16816(c, qa.z, 0u, qa.w, 0u, k0.z, k0.w);
                        mma_16816(c, qb.x, 0u, qb.y, 0u, k1.x, k1.y);
                        mma_16816(c, qb.z, 0u, qb.w, 0u, k1.z, k1.w);
                        v[2 * n] = c[0]; v[2 * n + 1] = c[1];
                        st_async_v2(remote(ls + n * 256, rank ^ 1), __float_as_uint(c[0]), __float_as_uint(c[1]), remote(lb, rank ^ 1));
                    }
                }
                DBG(26, 11);
                mbar_wait_cl(lb, (s >> 1) & 1);
                DBG(27, 11);
#pragma unroll
                for (int n = 0; n < 5; n++) {
                    if (n <= t4 || n == 4) {
                        const float2 a = lds64f(ls + n * 256);
                        v[2 * n] += a.x; v[2 * n + 1] += a.y;
                        if (n == t4) {
                            if (2 * qc > qd) v[2 * n] = -INFINITY;
                            if (2 * qc + 1 > qd) v[2 * n + 1] = -INFINITY;
                        }
                    }
                }
            }
            float sm = chain_softmax(v);
            sm += __shfl_xor_sync(0xffffffff, sm, 1);
            sm += __shfl_xor_sync(0xffffffff, sm, 2);
            float inv;
            asm("rcp.approx.ftz.f32 %0, %1;" : "=f"(inv) : "f"(sm));
            uint32_t pb[5];
#pragma unroll
            for (int j = 0; j < 5; j++) pb[j] = pack_bf16(v[2 * j] * inv, v[2 * j + 1] * inv);
            asm volatile("bar.sync 5, 128;" ::: "memory");
            const uint32_t stg = sb + CO_ST + t4 * 8 * CH_RS;
#pragma unroll
            for (int dt = 0; dt < 4; dt++) {
                const uint32_t vaddr = sb + CO_VX + (par * 48 + (lane & 7) + ((lane >> 4) << 3)) * CH_RS + dt * 32 + ((lane >> 3) & 1) * 16;
                uint32_t a0, a1, a2, a3;
                float c[4] = {0.f, 0.f, 0.f, 0.f};
                ldmatrix_x4_trans(a0, a1, a2, a3, vaddr);
                mma_16816(c, a0, a1, a2, a3, pb[0], pb[1]);
                if (t4 >= 2) {
                    ldmatrix_x4_trans(a0, a1, a2, a3, vaddr + 16 * CH_RS);
                    mma_16816(c, a0, a1, a2, a3, pb[2], pb[3]);
                }
                ldmatrix_x4_trans(a0, a1, a2, a3, vaddr + 32 * CH_RS);
                mma_16816(c, a0, a1, a2, a3, pb[4], 0u);
                stmatrix_x2_trans(stg + (lane & 7) * CH_RS + dt * 32 + ((lane >> 3) & 1) * 16, pack_bf16(c[0], c[1]), pack_bf16(c[2], c[3]));
            }
            __syncwarp();
            bf16* go = g_ctxB + ((size_t)h * SEQ + s * SEGL + t4 * 8 + (lane >> 3)) * HD + (rank & 1) * 64 + (lane & 7) * 8;
            const uint4 o0 = lds128(stg + (lane >> 3) * CH_RS + (lane & 7) * 16), o1 = lds128(stg + ((lane >> 3) + 4) * CH_RS + (lane & 7) * 16);
            *reinterpret_cast<uint4*>(go) = o0;
            *reinterpret_cast<uint4*>(go + 4 * HD) = o1;
            DBG(28, 11);
        }
        asm volatile("bar.sync 5, 128;" ::: "memory");
        if (tid == 256) signal_ctr(CT_CB + 15 * 2 + (h >= O2_HE));
    }
    __syncthreads();
    cluster_sync_all();
    TS_END(2);
}

struct Proj2Params {
    CUtensorMap mapA[2];
    CUtensorMap mapW[3];
    bf16* out[3];
};
#define P2T(i)
#define P2_NOMMA 0
#define P2_NOLOAD 0
constexpr int P2_STAGES = 6;
constexpr int P2_SMEM = 131072 + P2_STAGES * 16384 + 1024 + 1024;
constexpr int P2_ITEMS = 168 + 48;

__device__ __forceinline__ int p2_reps(int t) { return t >= 168 ? 1 : 2; }
__device__ __forceinline__ void p2_tile(int t, int w, int& z, int& mp, int& head) {
    if (t >= 168) { w += ((t - 168) & 1) * 2; t = 168 + ((t - 168) >> 1); }
    const int hq = t / 24, v = t % 24;
    mp = v & 7;
    if (v < 16) { head = hq * 4 + (v >> 3) * 2 + (w >> 1); z = 1 + (w & 1); }
    else { head = hq * 4 + w; z = 0; }
}
__device__ __forceinline__ void mbar_arrive_remote(uint32_t bar_cluster_addr) {
    asm volatile("mbarrier.arrive.release.cluster.shared::cluster.b64 _, [%0];" :: "r"(bar_cluster_addr) : "memory");
}
__device__ __forceinline__ void mbar_arrive_cl(uint32_t bar_cluster_addr) {
    asm volatile("mbarrier.arrive.shared::cluster.b64 _, [%0];" :: "r"(bar_cluster_addr) : "memory");
}
__device__ __forceinline__ void mbar_wait_acq_cluster(uint32_t bar, uint32_t parity) {
    asm volatile(
        "{\n"
        ".reg .pred p, q;\n"
        ".reg .u32 c;\n"
        "mov.u32 c, 0;\n"
        "WAIT_LOOP_C:\n"
        "mbarrier.try_wait.parity.acquire.cluster.shared::cta.b64 p, [%0], %1;\n"
        "@p bra WAIT_DONE_C;\n"
        "add.u32 c, c, 1;\n"
        "setp.lt.u32 q, c, 4000000;\n"
        "@q bra WAIT_LOOP_C;\n"
        "WAIT_DONE_C:\n"
        "}\n" :: "r"(bar), "r"(parity) : "memory");
}
__device__ __forceinline__ uint4 quad_transpose(uint32_t p0, uint32_t p1, uint32_t p2, uint32_t p3, int lane) {
    const bool o1 = lane & 1, o2 = lane & 2;
    uint32_t s0 = o1 ? p0 : p1, s1 = o1 ? p2 : p3;
    s0 = __shfl_xor_sync(0xffffffff, s0, 1); s1 = __shfl_xor_sync(0xffffffff, s1, 1);
    const uint32_t a_lo = o1 ? s0 : p0, a_hi = o1 ? p1 : s0, b_lo = o1 ? s1 : p2, b_hi = o1 ? p3 : s1;
    uint32_t t0 = o2 ? a_lo : b_lo, t1 = o2 ? a_hi : b_hi;
    t0 = __shfl_xor_sync(0xffffffff, t0, 2); t1 = __shfl_xor_sync(0xffffffff, t1, 2);
    return o2 ? make_uint4(t0, t1, b_lo, b_hi) : make_uint4(a_lo, a_hi, t0, t1);
}
#define P2_PACE 35
#define P2_PACE2 0
template <bool PERM, int PACE = 0>
__device__ __forceinline__ void store_frag_128(const float (&acc)[64], bf16* obase, int lane) {
#pragma unroll
    for (int rr = 0; rr < 2; rr++)
#pragma unroll
        for (int g = 0; g < 4; g++) {
            const float* a = &acc[g * 16 + rr * 2];
            const uint32_t p0 = pack_bf16(a[0], a[1]), p1 = pack_bf16(a[4], a[5]), p2 = pack_bf16(a[8], a[9]), p3 = pack_bf16(a[12], a[13]);
            *reinterpret_cast<uint4*>(obase + (size_t)(rr * 8) * HD + g * 32) = PERM ? make_uint4(p0, p1, p2, p3) : quad_transpose(p0, p1, p2, p3, lane);
            pace(PACE);
        }
}
__global__ void __cluster_dims__(2, 1, 1) __launch_bounds__(384, 1) proj2_kernel(const __grid_constant__ Proj2Params P) {
    extern __shared__ uint8_t smem_raw[];
    const uint32_t sbase = (smem_u32(smem_raw) + 1023) & ~1023u;
    const uint32_t sA = sbase, sB = sbase + 131072, sC = sB + P2_STAGES * 16384;
    const uint32_t bars = sC;
    const uint32_t a_full = bars, a_empty = bars + 64, b_full = bars + 128, b_empty = b_full + 8 * P2_STAGES;
    const uint32_t item_bar = b_empty + 8 * P2_STAGES, item_in = item_bar + 16, slot = item_in + 16;
    const uint32_t note_bar = slot + 16, note_free = note_bar + 64, note = note_free + 64;
    const int warp = threadIdx.x >> 5, lane = threadIdx.x & 31;
    const uint32_t rank = cluster_ctarank();
    TS_BEGIN(0);
    if (threadIdx.x == 0) {
        for (int i = 0; i < 8; i++) { mbar_init(a_full + 8 * i, 1); mbar_init(a_empty + 8 * i, 2); }
        for (int i = 0; i < P2_STAGES; i++) { mbar_init(b_full + 8 * i, 1); mbar_init(b_empty + 8 * i, 2); }
        mbar_init(item_bar, 1); mbar_init(item_bar + 8, 1); mbar_init(item_in, 2); mbar_init(item_in + 8, 2);
        for (int i = 0; i < 8; i++) { mbar_init(note_bar + 8 * i, 1); mbar_init(note_free + 8 * i, 1); }
        asm volatile("fence.mbarrier_init.release.cluster;" ::: "memory");
    }
    __syncthreads();
    cluster_sync_all();
    pdl_launch_dependents();
    if (warp == 9) {
        if (lane == 0) {
            for (int n = 0;; n++) {
                const int e = (n & 1) * 4 + ((n >> 1) & 3);
                mbar_wait(note_bar + 8 * e, (n >> 3) & 1);
                int m;
                asm volatile("ld.shared.s32 %0, [%1];" : "=r"(m) : "r"(note + e * 4) : "memory");
                mbar_arrive(note_free + 8 * e);
                if (m < 0) break;
                signal_ctr(m);
            }
        }
    } else if (warp == 10) {
        if (lane == 0) {
            auto publish = [&](int ic, int tq) {
                const int t = tq < P2_ITEMS ? tq : -1;
                asm volatile("st.shared.s32 [%0], %1;" :: "r"(slot + (ic & 3) * 4), "r"(t) : "memory");
                mbar_arrive(item_bar + 8 * (ic & 1));
                st_async_b32(mapa_u32(slot + (ic & 3) * 4, 1), (uint32_t)t, mapa_u32(item_bar + 8 * (ic & 1), 1));
            };
            const int npair = (int)(gridDim.x >> 1), pair = (int)(blockIdx.x >> 1);
            if (rank == 0) publish(0, pair);
            for (int ic = 0;; ic++) {
                if (rank == 1) mbar_expect_tx(item_bar + 8 * (ic & 1), 4);
                mbar_wait(item_bar + 8 * (ic & 1), (ic >> 1) & 1);
                int t;
                asm volatile("ld.shared.s32 %0, [%1];" : "=r"(t) : "r"(slot + (ic & 3) * 4) : "memory");
                if (t < 0) break;
                int z0, mp, h0;
                p2_tile(t, 0, z0, mp, h0);
                const int aidx = z0 >= 1 ? 1 : 0;
                const int m0 = (2 * mp + (int)rank) * 128;
                for (int k = 0; k < 8; k++) {
                    mbar_wait(a_empty + 8 * k, (ic & 1) ^ 1);
                    if (P2_NOLOAD) mbar_arrive(a_full + 8 * k); else {
                    mbar_expect_tx(a_full + 8 * k, 16384);
                    tma_load_2d(sA + k * 16384, &P.mapA[aidx], a_full + 8 * k, k * 64, m0); }
                }
                if (rank == 0) {
                    mbar_wait(item_in + 8 * (ic & 1), (ic >> 1) & 1);
                    publish(ic + 1, ic == 0 ? npair + pair : 2 * npair + (int)atomicAdd(&g_ctr[CT_PROJ], 1u));
                }
            }
        }
    } else if (warp == 8 || warp == 11) {
        if (lane == 0) {
            const int par2 = warp == 8 ? 0 : 1;
            int it = 0; uint32_t bph = 0;
            for (int ic = 0;; ic++) {
                mbar_wait(item_bar + 8 * (ic & 1), (ic >> 1) & 1);
                int t;
                asm volatile("ld.shared.s32 %0, [%1];" : "=r"(t) : "r"(slot + (ic & 3) * 4) : "memory");
                if (t < 0) break;
                const int nt = 2 * p2_reps(t);
                for (int w = 0; w < nt; w++) {
                    int z, mp, hd;
                    p2_tile(t, w, z, mp, hd);
                    for (int k = 0; k < 8; k++) {
                        const int s = it; const uint32_t phb = bph;
                        if (++it == P2_STAGES) { it = 0; bph ^= 1; }
                        if ((k & 1) != par2) continue;
                        mbar_wait(b_empty + 8 * s, phb ^ 1);
                        if (P2_NOLOAD) { mbar_arrive(b_full + 8 * s); continue; }
                        mbar_expect_tx(b_full + 8 * s, 16384);
                        tma_load_2d_mc(sB + s * 16384 + rank * 8192, &P.mapW[z], b_full + 8 * s, hd * 128 + (int)rank * 64, k * 64, (uint16_t)3);
                    }
                }
            }
        }
    } else {
        const int wg = warp >> 2;
        float acc[2][64];
        const uint32_t a_lo = desc_lo(sA, 16), b_lo0 = desc_lo(sB, 8192);
        const bool elected = (threadIdx.x & 127) == 0;
        int s = (wg * 8) % P2_STAGES;
        uint32_t ph = ((wg * 8) / P2_STAGES) & 1;
        int nnote = 0;
        if (wg == 1) asm volatile("bar.arrive 3, 256;" ::: "memory");
        for (int ic = 0;; ic++) {
            mbar_wait(item_bar + 8 * (ic & 1), (ic >> 1) & 1);
            int t;
            asm volatile("ld.shared.s32 %0, [%1];" : "=r"(t) : "r"(slot + (ic & 3) * 4) : "memory");
            P2T(7);
            if (wg == 0 && t < 0) {
                if (elected) {
                    const int e = nnote & 3;
                    mbar_wait(note_free + 8 * e, ((nnote >> 2) & 1) ^ 1);
                    asm volatile("st.shared.s32 [%0], %1;" :: "r"(note + e * 4), "r"(-1) : "memory");
                    mbar_arrive(note_bar + 8 * e);
                }
            }
            if (t < 0) break;
            const int reps = p2_reps(t);
#pragma unroll 1
            for (int rp = 0; rp < reps; rp++) {
            const bool first = rp == 0, last = rp == reps - 1;
            int z, mp, head;
            p2_tile(t, rp * 2 + wg, z, mp, head);
            asm volatile("bar.sync %0, 256;" :: "r"(3 + wg) : "memory");
            P2T(0);
            if (wg == 1 && last && elected) mbar_arrive_cl(mapa_u32(item_in + 8 * (ic & 1), 0));
            int sprev = 0;
#pragma unroll
            for (int k = 0; k < 8; k++) {
                if (k == 0) P2T(5);
                if (wg == 0 && first) mbar_wait(a_full + 8 * k, ic & 1);
                if (k == 0) P2T(6);
                mbar_wait(b_full + 8 * s, ph);
                if (k == 7) asm volatile("bar.arrive %0, 256;" :: "r"(4 - wg) : "memory");
                if (k == 0) P2T(1);
                if (k == 7) P2T(2);
                const uint32_t b_lo = b_lo0 + s * 1024;
                wgmma_fence();
#pragma unroll
                for (int kk = 0; kk < (P2_NOMMA ? 1 : 4); kk++) {
                    wgmma_ss_n128_lo<1>(acc[0], a_lo + k * 1024 + kk * 2, b_lo + kk * 128, (k | kk) != 0);
                    wgmma_ss_n128_lo<1>(acc[1], a_lo + k * 1024 + 512 + kk * 2, b_lo + kk * 128, (k | kk) != 0);
                }
                wgmma_commit();
                if (k > 0) {
                    wgmma_wait<1>();
                    if (elected) {
                        const uint32_t e = b_empty + 8 * sprev;
                        mbar_arrive_cl(mapa_u32(e, 0)); mbar_arrive_cl(mapa_u32(e, 1));
                        if (last) mbar_arrive(a_empty + 8 * (k - 1));
                    }
                }
                sprev = s;
                if (++s == P2_STAGES) { s = 0; ph ^= 1; }
            }
            wgmma_wait<0>();
            P2T(3);
            if (elected) {
                const uint32_t e = b_empty + 8 * sprev;
                mbar_arrive_cl(mapa_u32(e, 0)); mbar_arrive_cl(mapa_u32(e, 1));
                if (last) mbar_arrive(a_empty + 8 * 7);
            }
            s += 8 % P2_STAGES; ph ^= (8 / P2_STAGES) & 1;
            if (s >= P2_STAGES) { s -= P2_STAGES; ph ^= 1; }
            const int m0 = (2 * mp + (int)rank) * 128;
            bf16* obase = P.out[z] + ((size_t)head * SEQ + m0 + (warp & 3) * 16 + (lane >> 2)) * HD + (lane & 3) * 8;
            store_frag_128<true, P2_PACE>(acc[0], obase, lane); store_frag_128<true, P2_PACE>(acc[1], obase + (size_t)64 * HD, lane);
            P2T(4);
            {
                asm volatile("bar.sync %0, 128;" :: "r"(1 + wg) : "memory");
                if (elected) {
                    const int e = wg * 4 + (nnote & 3);
                    mbar_wait(note_free + 8 * e, ((nnote >> 2) & 1) ^ 1);
                    asm volatile("st.shared.s32 [%0], %1;" :: "r"(note + e * 4), "r"(CT_AP + (head >> 1)) : "memory");
                    mbar_arrive(note_bar + 8 * e);
                }
                nnote++;
            }
            }
        }
        TS_END(0);
    }
    __syncthreads();
    cluster_sync_all();
}

struct OutParams {
    CUtensorMap mapCtx[2];
    CUtensorMap mapWo[2];
    CUtensorMap mapPart;
};
__device__ float g_part[4 * SEQ * DM];

#define OT(i)
constexpr int O2_STAGES = 4;
constexpr int O2_SMEM = O2_STAGES * 49152 + 1024 + 256;

__global__ void __cluster_dims__(2, 1, 1) __launch_bounds__(352, 1)
out2_kernel(const __grid_constant__ OutParams P, const bf16* __restrict__ x, const bf16* __restrict__ gate_w, bf16* __restrict__ out) {
    extern __shared__ uint8_t smem_raw[];
    const uint32_t sbase = (smem_u32(smem_raw) + 1023) & ~1023u;
    const uint32_t bar_full = sbase + O2_STAGES * 49152, bar_empty = bar_full + 8 * O2_STAGES;
    __shared__ float s_gate[32];
    const int warp = threadIdx.x >> 5, lane = threadIdx.x & 31;
    const uint32_t rank = cluster_ctarank();
    const int cid = blockIdx.x >> 1;
    const int late = cid >> 5, mp = (cid >> 1) & 7, nh = cid & 1;
    const int b = late ? 1 - ((cid >> 4) & 1) : (cid >> 4) & 1, kq = b * 2 + late;
    const int h0 = late ? O2_HE : 0;
    const int KT = late ? 2 * (NH - O2_HE) : 2 * O2_HE;
    const int m0 = (2 * mp + (int)rank) * 128, n0 = nh * 256;
    TS_BEGIN(4);
    OT(0);
    if (threadIdx.x == 0) {
        for (int i = 0; i < O2_STAGES; i++) { mbar_init(bar_full + 8 * i, 1); mbar_init(bar_empty + 8 * i, 4); }
        asm volatile("fence.mbarrier_init.release.cluster;" ::: "memory");
    }
    __syncthreads();
    asm volatile("barrier.cluster.arrive.release.aligned;" ::: "memory");
    if (threadIdx.x == 256) wait_ctr((b == 0 ? CT_CA : CT_CB) + (m0 >> 7) * 2 + late, (unsigned)KT);
    __syncwarp();
    asm volatile("barrier.cluster.wait.acquire.aligned;" ::: "memory");
    if (warp >= 8) {
        if (lane == 0) {
            int s = 0; uint32_t ph = 0;
            for (int i = 0; i < KT; i++) {
                mbar_wait(bar_empty + 8 * s, ph ^ 1);
                const uint32_t sa = sbase + s * 49152;
                const int head = h0 + (i >> 1), dk = (i & 1) * 64;
                if (warp == 8) {
                    mbar_expect_tx(bar_full + 8 * s, 49152);
                    tma_load_2d(sa, &P.mapCtx[b], bar_full + 8 * s, dk, head * SEQ + m0);
                } else {
                    const int j = (int)rank * 2 + (warp - 9);
                    tma_load_2d_mc(sa + 16384 + j * 8192, &P.mapWo[b], bar_full + 8 * s, n0 + j * 64, head * HD + dk, (uint16_t)3);
                }
                if (++s == O2_STAGES) { s = 0; ph ^= 1; }
            }
        }
    } else {
        const int wg = warp >> 2;
        const bool elected = (threadIdx.x & 127) == 0;
        float acc[128];
        {
            const int r = m0 + kq * 32 + (threadIdx.x >> 3);
            float sum = 0.f;
#pragma unroll
            for (int c = 0; c < 8; c++) {
                const int col = c * 64 + (threadIdx.x & 7) * 8;
                const uint4 xv = __ldg(reinterpret_cast<const uint4*>(x + (size_t)r * DM + col));
                const uint4 gv = __ldg(reinterpret_cast<const uint4*>(gate_w + col));
                const bf16* xp = reinterpret_cast<const bf16*>(&xv);
                const bf16* gp = reinterpret_cast<const bf16*>(&gv);
#pragma unroll
                for (int e = 0; e < 8; e++)
                    sum += __bfloat162float(__float2bfloat16(__bfloat162float(xp[e]) * __bfloat162float(gp[e])));
            }
            sum += __shfl_xor_sync(0xffffffff, sum, 1);
            sum += __shfl_xor_sync(0xffffffff, sum, 2);
            sum += __shfl_xor_sync(0xffffffff, sum, 4);
            sum = __bfloat162float(__float2bfloat16(sum));
            if ((threadIdx.x & 7) == 0) s_gate[threadIdx.x >> 3] = __bfloat162float(__float2bfloat16(1.f / (1.f + __expf(-sum))));
        }
        int s = 0, sprev = 0; uint32_t ph = 0;
#pragma unroll 1
        for (int i = 0; i < KT; i++) {
            mbar_wait(bar_full + 8 * s, ph);
            if (i == 0) OT(1);
            if (i == 8) OT(2);
            const uint32_t sa = sbase + s * 49152 + wg * 8192, sb = sbase + s * 49152 + 16384;
            wgmma_fence();
#pragma unroll
            for (int kk = 0; kk < 4; kk++)
                wgmma_ss_n256_tb(acc, make_desc(sa + kk * 32, 16, 1024), make_desc(sb + kk * 2048, 8192, 1024), (i | kk) != 0);
            wgmma_commit();
            if (i > 0) {
                wgmma_wait<1>();
                if (elected) { const uint32_t e = bar_empty + 8 * sprev; mbar_arrive_cl(mapa_u32(e, 0)); mbar_arrive_cl(mapa_u32(e, 1)); }
            }
            sprev = s;
            if (++s == O2_STAGES) { s = 0; ph ^= 1; }
        }
        wgmma_wait<0>();
        OT(3);
        {
            const int r = wg * 64 + (warp & 3) * 16 + (lane >> 2);
            if ((warp >> 1) == kq) {
#pragma unroll
                for (int j = 0; j < 32; j++) {
                    const uint32_t a = sbase + (j >> 2) * 16384 + r * 128 + ((((j & 3) * 2 + ((lane & 3) >> 1)) ^ (r & 7)) << 4) + (lane & 1) * 8;
                    asm volatile("st.shared.v2.f32 [%0], {%1, %2};" :: "r"(a), "f"(acc[j * 4 + 0]), "f"(acc[j * 4 + 1]) : "memory");
                    asm volatile("st.shared.v2.f32 [%0], {%1, %2};" :: "r"(a + 1024), "f"(acc[j * 4 + 2]), "f"(acc[j * 4 + 3]) : "memory");
                }
            } else {
                float* pp = g_part + ((size_t)kq * SEQ + m0 + r) * DM + n0 + (lane & 3) * 2;
#pragma unroll
                for (int j = 0; j < 32; j++) {
                    *reinterpret_cast<float2*>(pp + j * 8) = make_float2(acc[j * 4 + 0], acc[j * 4 + 1]);
                    *reinterpret_cast<float2*>(pp + 8 * DM + j * 8) = make_float2(acc[j * 4 + 2], acc[j * 4 + 3]);
                }
            }
        }
        asm volatile("bar.sync 1, 256;" ::: "memory");
        OT(4);
        unsigned int* ctr = &g_ctr[CT_OP + (2 * mp + (int)rank) * 2 + nh];
        if (threadIdx.x == 0) {
            asm volatile("fence.proxy.async;" ::: "memory");
            __threadfence();
            atomicAdd(ctr, 1u);
            unsigned int v; int it = 0;
            do { asm volatile("ld.acquire.gpu.global.u32 %0, [%1];" : "=r"(v) : "l"(ctr) : "memory"); } while (v < 4u && ++it < WAIT_LIMIT);
        }
        asm volatile("bar.sync 1, 256;" ::: "memory");
        OT(5);
        {
            const int c8 = threadIdx.x & 31, r0 = threadIdx.x >> 5;
            float4 u[4][3][2];
#pragma unroll
            for (int i = 0; i < 4; i++)
#pragma unroll
                for (int q = 1; q < 4; q++) {
                    const float4* p4 = reinterpret_cast<const float4*>(g_part + ((size_t)((kq + q) & 3) * SEQ + m0 + kq * 32 + r0 + i * 8) * DM + n0 + c8 * 8);
                    asm volatile("ld.relaxed.gpu.global.v4.f32 {%0, %1, %2, %3}, [%4];"
                                 : "=f"(u[i][q - 1][0].x), "=f"(u[i][q - 1][0].y), "=f"(u[i][q - 1][0].z), "=f"(u[i][q - 1][0].w) : "l"(p4) : "memory");
                    asm volatile("ld.relaxed.gpu.global.v4.f32 {%0, %1, %2, %3}, [%4];"
                                 : "=f"(u[i][q - 1][1].x), "=f"(u[i][q - 1][1].y), "=f"(u[i][q - 1][1].z), "=f"(u[i][q - 1][1].w) : "l"(p4 + 1) : "memory");
                }
#pragma unroll
            for (int i = 0; i < 4; i++) {
                const int rl = kq * 32 + r0 + i * 8;
                const float ga = s_gate[r0 + i * 8], gb = 1.f - ga;
                float o8[8];
#pragma unroll
                for (int hf = 0; hf < 2; hf++) {
                    float4 own;
                    const uint32_t a = sbase + (c8 >> 2) * 16384 + rl * 128 + ((((c8 & 3) * 2 + hf) ^ (rl & 7)) << 4);
                    asm volatile("ld.shared.v4.f32 {%0, %1, %2, %3}, [%4];" : "=f"(own.x), "=f"(own.y), "=f"(own.z), "=f"(own.w) : "r"(a) : "memory");
                    const int qp = ((kq ^ 1) - kq) & 3;
                    const float4 pa = qp == 1 ? u[i][0][hf] : u[i][2][hf];
                    const float4 o1 = u[i][1][hf];
                    const float4 o2 = qp == 1 ? u[i][2][hf] : u[i][0][hf];
                    const float gm = b == 0 ? ga : gb, go = b == 0 ? gb : ga;
                    o8[hf * 4 + 0] = gm * (own.x + pa.x) + go * (o1.x + o2.x);
                    o8[hf * 4 + 1] = gm * (own.y + pa.y) + go * (o1.y + o2.y);
                    o8[hf * 4 + 2] = gm * (own.z + pa.z) + go * (o1.z + o2.z);
                    o8[hf * 4 + 3] = gm * (own.w + pa.w) + go * (o1.w + o2.w);
                }
                *reinterpret_cast<uint4*>(out + (size_t)(m0 + rl) * DM + n0 + c8 * 8) =
                    make_uint4(pack_bf16(o8[0], o8[1]), pack_bf16(o8[2], o8[3]), pack_bf16(o8[4], o8[5]), pack_bf16(o8[6], o8[7]));
            }
        }
        OT(6);
        if (threadIdx.x == 0) {
            const unsigned int tk = atomicAdd(&g_ctr[CT_FIN], 1u);
            asm volatile("st.shared.u32 [%0], %1;" :: "r"(bar_empty + 8 * O2_STAGES), "r"(tk) : "memory");
        }
        asm volatile("bar.sync 1, 256;" ::: "memory");
        unsigned int tk;
        asm volatile("ld.shared.u32 %0, [%1];" : "=r"(tk) : "r"(bar_empty + 8 * O2_STAGES) : "memory");
        if (tk == gridDim.x - 1 && threadIdx.x < CT_N) g_ctr[threadIdx.x] = 0u;
    }
    __syncthreads();
    cluster_sync_all();
    TS_END(4);
}

typedef CUresult (*PFN_encodeTiled)(CUtensorMap*, CUtensorMapDataType, cuuint32_t, void*, const cuuint64_t*,
                                    const cuuint64_t*, const cuuint32_t*, const cuuint32_t*, CUtensorMapInterleave,
                                    CUtensorMapSwizzle, CUtensorMapL2promotion, CUtensorMapFloatOOBfill);
static PFN_encodeTiled g_encode = nullptr;

static void make_map(CUtensorMap* m, const void* ptr, uint64_t rows, uint64_t cols, uint32_t box_rows, bool sw64 = false) {
    cuuint64_t dims[2] = {cols, rows};
    cuuint64_t strides[1] = {cols * 2};
    cuuint32_t box[2] = {sw64 ? 32u : 64u, box_rows};
    cuuint32_t es[2] = {1, 1};
    g_encode(m, CU_TENSOR_MAP_DATA_TYPE_BFLOAT16, 2, const_cast<void*>(ptr), dims, strides, box, es,
             CU_TENSOR_MAP_INTERLEAVE_NONE, sw64 ? CU_TENSOR_MAP_SWIZZLE_64B : CU_TENSOR_MAP_SWIZZLE_128B, CU_TENSOR_MAP_L2_PROMOTION_L2_256B,
             CU_TENSOR_MAP_FLOAT_OOB_FILL_NONE);
}

template <typename... KArgs, typename... Args>
static void launch_pdl(void (*kernel)(KArgs...), int grid, int block, size_t smem, cudaStream_t st, bool pdl, Args... args) {
    cudaLaunchConfig_t cfg = {};
    cfg.gridDim = dim3(grid); cfg.blockDim = dim3(block); cfg.dynamicSmemBytes = smem; cfg.stream = st;
    cudaLaunchAttribute at[1];
    at[0].id = cudaLaunchAttributeProgrammaticStreamSerialization;
    at[0].val.programmaticStreamSerializationAllowed = 1;
    cfg.attrs = at; cfg.numAttrs = pdl ? 1 : 0;
    cudaLaunchKernelEx(&cfg, kernel, KArgs(args)...);
}

extern "C" void kernel_launch(void* const* d_in, const int* in_sizes, int n_in, void* d_out, int out_size) {
    const bf16* x = (const bf16*)d_in[0];
    const bf16* ckv = (const bf16*)d_in[1];
    const bf16* wq = (const bf16*)d_in[2];
    const bf16* wuk = (const bf16*)d_in[3];
    const bf16* wuv = (const bf16*)d_in[4];
    const bf16* wo = (const bf16*)d_in[5];
    const bf16* mem0 = (const bf16*)d_in[7];
    const bf16* Wq = (const bf16*)d_in[8];
    const bf16* Wk = (const bf16*)d_in[9];
    const bf16* Wv = (const bf16*)d_in[10];
    const bf16* Wo = (const bf16*)d_in[11];
    const bf16* gate_w = (const bf16*)d_in[13];
    bf16* out = (bf16*)d_out;

    static Proj2Params P2;
    static ChainParams CP;
    static AttnParams AP;
    static OutParams OP;
    static bool init = false;
    static const void* last_in[14];
    bool same = init;
    for (int i = 0; i < 14 && same; i++) same = last_in[i] == d_in[i];
    if (!init) {
        cudaDriverEntryPointQueryResult qr;
        cudaGetDriverEntryPoint("cuTensorMapEncodeTiled", (void**)&g_encode, cudaEnableDefault, &qr);
        cudaFuncSetAttribute(proj2_kernel, cudaFuncAttributeMaxDynamicSharedMemorySize, P2_SMEM);
        cudaFuncSetAttribute(attn_kernel, cudaFuncAttributeMaxDynamicSharedMemorySize, FA_SMEM);
        cudaFuncSetAttribute(chain_kernel, cudaFuncAttributeMaxDynamicSharedMemorySize, CH_SMEM);
        cudaFuncSetAttribute(out2_kernel, cudaFuncAttributeMaxDynamicSharedMemorySize, O2_SMEM);
        init = true;
    }
    if (!same) {
        for (int i = 0; i < 14; i++) last_in[i] = d_in[i];
        void *pQA, *pKA, *pVA, *pCA, *pCB;
        cudaGetSymbolAddress(&pQA, g_QA); cudaGetSymbolAddress(&pKA, g_KA); cudaGetSymbolAddress(&pVA, g_VA);
        cudaGetSymbolAddress(&pCA, g_ctxA); cudaGetSymbolAddress(&pCB, g_ctxB);
        make_map(&P2.mapA[0], x, SEQ, DM, 128);
        make_map(&P2.mapA[1], ckv, SEQ, DM, 128);
        const void* ws[3] = {wq, wuk, wuv};
        void* cs[3] = {pQA, pKA, pVA};
        for (int i = 0; i < 3; i++) { make_map(&P2.mapW[i], ws[i], DM, NQ, 64); P2.out[i] = (bf16*)cs[i]; }
        make_map(&CP.mapW[0], Wq, DM, NQ, 64); make_map(&CP.mapW[1], Wk, DM, NQ, 64); make_map(&CP.mapW[2], Wv, DM, NQ, 64);
        make_map(&CP.mapX, x, SEQ, DM, 32);
        make_map(&AP.mapQ, pQA, NH * SEQ, HD, 128);
        make_map(&AP.mapK, pKA, NH * SEQ, HD, 128);
        make_map(&AP.mapV, pVA, NH * SEQ, HD, 128);
        make_map(&AP.mapO, pCA, NH * SEQ, HD, 64);
        make_map(&OP.mapCtx[0], pCA, NH * SEQ, HD, 128);
        make_map(&OP.mapCtx[1], pCB, NH * SEQ, HD, 128);
        make_map(&OP.mapWo[0], wo, NQ, DM, 64);
        make_map(&OP.mapWo[1], Wo, NQ, DM, 64);
        {
            void* pP; cudaGetSymbolAddress(&pP, g_part);
            cuuint64_t dims[2] = {DM, 4 * SEQ}; cuuint64_t strides[1] = {DM * 4}; cuuint32_t box[2] = {32, 32}; cuuint32_t es[2] = {1, 1};
            g_encode(&OP.mapPart, CU_TENSOR_MAP_DATA_TYPE_FLOAT32, 2, pP, dims, strides, box, es, CU_TENSOR_MAP_INTERLEAVE_NONE,
                     CU_TENSOR_MAP_SWIZZLE_128B, CU_TENSOR_MAP_L2_PROMOTION_NONE, CU_TENSOR_MAP_FLOAT_OOB_FILL_NONE);
        }
    }
    cudaStream_t s1 = cudaStreamPerThread;
    const bool pdl = true;
    launch_pdl(chain_kernel, 64, CH_BLOCK, CH_SMEM, s1, false, CP, mem0, Wo, x);
    launch_pdl(proj2_kernel, 68, 384, P2_SMEM, s1, pdl, P2);
    launch_pdl(attn_kernel, FA_GRID, 384, FA_SMEM, s1, pdl, AP, 1000);
    launch_pdl(out2_kernel, 128, 352, O2_SMEM, s1, pdl, OP, x, gate_w, out);
}
```

```cpp
#include <cuda_runtime.h>
#include <cuda_bf16.h>
#include <cuda.h>
#include <stdint.h>
#include <type_traits>

constexpr int SEQ = 2048;
constexpr int DM = 512;
constexpr int NH = 32;
constexpr int HD = 128;
constexpr int NQ = NH * HD;
constexpr int SEGL = 32;
constexpr int NMEM = 8;
constexpr int NSEG = SEQ / SEGL;

typedef __nv_bfloat16 bf16;

__device__ bf16 g_QA[SEQ * NQ];
__device__ bf16 g_KA[SEQ * NQ];
__device__ bf16 g_VA[SEQ * NQ];
__device__ bf16 g_ctxA[SEQ * NQ];
__device__ bf16 g_ctxB[SEQ * NQ];
constexpr int CT_PROJ = 0, CT_ATTN = 1, CT_FIN = 5;
constexpr int CT_AP = 64;
#define O2_HE 18
constexpr int CT_CA = 128;
constexpr int CT_CB = 160;
constexpr int CT_OP = 192;
constexpr int CT_N = 224;
__device__ unsigned int g_ctr[CT_N];
__device__ uint32_t g_xbuf[4 * 8 * 2048];

#define FA_GRID 68

#define TS_BEGIN(id)
#define TS_END(id)
#define WAIT_LIMIT 200000
__device__ __forceinline__ void pdl_launch_dependents() { asm volatile("griddepcontrol.launch_dependents;" ::: "memory"); }
__device__ __forceinline__ void wait_ctr(int idx, unsigned int n) {
    unsigned int v; int it = 0;
    do { asm volatile("ld.acquire.gpu.global.u32 %0, [%1];" : "=r"(v) : "l"(&g_ctr[idx]) : "memory"); } while (v < n && ++it < WAIT_LIMIT);
    asm volatile("fence.proxy.async;" ::: "memory");
}
__device__ __forceinline__ void signal_ctr(int idx) {
    asm volatile("fence.proxy.async;" ::: "memory");
    __threadfence();
    atomicAdd(&g_ctr[idx], 1u);
}
__device__ __forceinline__ void signal_ctr_generic(int idx) {
    asm volatile("red.release.gpu.global.add.u32 [%0], 1;" :: "l"(&g_ctr[idx]) : "memory");
}
__device__ __forceinline__ uint32_t smem_u32(const void* p) {
    return (uint32_t)__cvta_generic_to_shared(p);
}
__device__ __forceinline__ void mbar_init(uint32_t bar, uint32_t count) {
    asm volatile("mbarrier.init.shared::cta.b64 [%0], %1;" :: "r"(bar), "r"(count));
}
__device__ __forceinline__ void mbar_expect_tx(uint32_t bar, uint32_t bytes) {
    asm volatile("mbarrier.arrive.expect_tx.shared::cta.b64 _, [%0], %1;" :: "r"(bar), "r"(bytes) : "memory");
}
__device__ __forceinline__ void mbar_arrive(uint32_t bar) {
    asm volatile("mbarrier.arrive.shared::cta.b64 _, [%0];" :: "r"(bar) : "memory");
}
__device__ __forceinline__ void mbar_wait(uint32_t bar, uint32_t parity) {
    asm volatile(
        "{\n"
        ".reg .pred p, q;\n"
        ".reg .u32 c;\n"
        "mov.u32 c, 0;\n"
        "WAIT_LOOP:\n"
        "mbarrier.try_wait.parity.shared::cta.b64 p, [%0], %1;\n"
        "@p bra WAIT_DONE;\n"
        "add.u32 c, c, 1;\n"
        "setp.lt.u32 q, c, %2;\n"
        "@q bra WAIT_LOOP;\n"
        "WAIT_DONE:\n"
        "}\n" :: "r"(bar), "r"(parity), "n"(WAIT_LIMIT) : "memory");
}
__device__ __forceinline__ void tma_load_2d(uint32_t dst, const CUtensorMap* map, uint32_t bar, int c0, int c1) {
    asm volatile(
        "cp.async.bulk.tensor.2d.shared::cluster.global.mbarrier::complete_tx::bytes [%0], [%1, {%3, %4}], [%2];"
        :: "r"(dst), "l"((uint64_t)map), "r"(bar), "r"(c0), "r"(c1) : "memory");
}
__device__ __forceinline__ void wgmma_fence() { asm volatile("wgmma.fence.sync.aligned;" ::: "memory"); }
__device__ __forceinline__ void wgmma_commit() { asm volatile("wgmma.commit_group.sync.aligned;" ::: "memory"); }
template <int N> __device__ __forceinline__ void wgmma_wait() {
    asm volatile("wgmma.wait_group.sync.aligned %0;" :: "n"(N) : "memory");
}
__device__ __forceinline__ uint64_t make_desc(uint32_t addr, uint32_t lbo, uint32_t sbo) {
    uint64_t d = 0;
    d |= (uint64_t)((addr & 0x3FFFF) >> 4);
    d |= (uint64_t)((lbo >> 4) & 0x3FFF) << 16;
    d |= (uint64_t)((sbo >> 4) & 0x3FFF) << 32;
    d |= (uint64_t)1 << 62;
    return d;
}

#define ACC64(d) \
    "+f"(d[0]), "+f"(d[1]), "+f"(d[2]), "+f"(d[3]), "+f"(d[4]), "+f"(d[5]), "+f"(d[6]), "+f"(d[7]), \
    "+f"(d[8]), "+f"(d[9]), "+f"(d[10]), "+f"(d[11]), "+f"(d[12]), "+f"(d[13]), "+f"(d[14]), "+f"(d[15]), \
    "+f"(d[16]), "+f"(d[17]), "+f"(d[18]), "+f"(d[19]), "+f"(d[20]), "+f"(d[21]), "+f"(d[22]), "+f"(d[23]), \
    "+f"(d[24]), "+f"(d[25]), "+f"(d[26]), "+f"(d[27]), "+f"(d[28]), "+f"(d[29]), "+f"(d[30]), "+f"(d[31]), \
    "+f"(d[32]), "+f"(d[33]), "+f"(d[34]), "+f"(d[35]), "+f"(d[36]), "+f"(d[37]), "+f"(d[38]), "+f"(d[39]), \
    "+f"(d[40]), "+f"(d[41]), "+f"(d[42]), "+f"(d[43]), "+f"(d[44]), "+f"(d[45]), "+f"(d[46]), "+f"(d[47]), \
    "+f"(d[48]), "+f"(d[49]), "+f"(d[50]), "+f"(d[51]), "+f"(d[52]), "+f"(d[53]), "+f"(d[54]), "+f"(d[55]), \
    "+f"(d[56]), "+f"(d[57]), "+f"(d[58]), "+f"(d[59]), "+f"(d[60]), "+f"(d[61]), "+f"(d[62]), "+f"(d[63])
#define ACC64_STR \
    "{%0, %1, %2, %3, %4, %5, %6, %7, %8, %9, %10, %11, %12, %13, %14, %15, " \
    "%16, %17, %18, %19, %20, %21, %22, %23, %24, %25, %26, %27, %28, %29, %30, %31, " \
    "%32, %33, %34, %35, %36, %37, %38, %39, %40, %41, %42, %43, %44, %45, %46, %47, " \
    "%48, %49, %50, %51, %52, %53, %54, %55, %56, %57, %58, %59, %60, %61, %62, %63}"

template <int TB>
__device__ __forceinline__ void wgmma_ss_n128(float (&d)[64], uint64_t da, uint64_t db, int scale_d) {
    asm volatile(
        "{\n.reg .pred p;\nsetp.ne.b32 p, %66, 0;\n"
        "wgmma.mma_async.sync.aligned.m64n128k16.f32.bf16.bf16 " ACC64_STR ", %64, %65, p, 1, 1, 0, %67;\n}\n"
        : ACC64(d) : "l"(da), "l"(db), "r"(scale_d), "n"(TB));
}
__device__ __forceinline__ uint32_t desc_lo(uint32_t addr, uint32_t lbo) { return ((addr & 0x3FFFF) >> 4) | ((lbo >> 4) << 16); }
template <int TB>
__device__ __forceinline__ void wgmma_ss_n128_lo(float (&d)[64], uint32_t da_lo, uint32_t db_lo, int scale_d) {
    asm volatile(
        "{\n.reg .pred p;\n.reg .b64 da, db;\nsetp.ne.b32 p, %66, 0;\n"
        "mov.b64 da, {%64, 0x40000040};\nmov.b64 db, {%65, 0x40000040};\n"
        "wgmma.mma_async.sync.aligned.m64n128k16.f32.bf16.bf16 " ACC64_STR ", da, db, p, 1, 1, 0, %67;\n}\n"
        : ACC64(d) : "r"(da_lo), "r"(db_lo), "r"(scale_d), "n"(TB));
}
__device__ __forceinline__ void wgmma_rs_n128_tb(float (&d)[64], uint32_t a0, uint32_t a1, uint32_t a2, uint32_t a3,
                                                 uint64_t db, int scale_d) {
    asm volatile(
        "{\n.reg .pred p;\nsetp.ne.b32 p, %69, 0;\n"
        "wgmma.mma_async.sync.aligned.m64n128k16.f32.bf16.bf16 " ACC64_STR ", {%64, %65, %66, %67}, %68, p, 1, 1, 1;\n}\n"
        : ACC64(d) : "r"(a0), "r"(a1), "r"(a2), "r"(a3), "l"(db), "r"(scale_d));
}
__device__ __forceinline__ void wgmma_rs_n80(float (&d)[40], const uint32_t (&a)[4], uint32_t db_lo, int scale_d) {
    asm volatile(
        "{\n.reg .pred p;\n.reg .b64 db;\nsetp.ne.b32 p, %45, 0;\nmov.b64 db, {%44, 0x40000040};\n"
        "wgmma.mma_async.sync.aligned.m64n80k16.f32.bf16.bf16 "
        "{%0, %1, %2, %3, %4, %5, %6, %7, %8, %9, %10, %11, %12, %13, %14, %15, %16, %17, %18, %19, %20, %21, %22, %23, %24, %25, %26, %27, %28, %29, %30, %31, %32, %33, %34, %35, %36, %37, %38, %39}, "
        "{%40, %41, %42, %43}, db, p, 1, 1, 0;\n}\n"
        : "+f"(d[0]), "+f"(d[1]), "+f"(d[2]), "+f"(d[3]), "+f"(d[4]), "+f"(d[5]), "+f"(d[6]), "+f"(d[7]), "+f"(d[8]), "+f"(d[9]), "+f"(d[10]), "+f"(d[11]), "+f"(d[12]), "+f"(d[13]), "+f"(d[14]), "+f"(d[15]), "+f"(d[16]), "+f"(d[17]), "+f"(d[18]), "+f"(d[19]), "+f"(d[20]), "+f"(d[21]), "+f"(d[22]), "+f"(d[23]), "+f"(d[24]), "+f"(d[25]), "+f"(d[26]), "+f"(d[27]), "+f"(d[28]), "+f"(d[29]), "+f"(d[30]), "+f"(d[31]), "+f"(d[32]), "+f"(d[33]), "+f"(d[34]), "+f"(d[35]), "+f"(d[36]), "+f"(d[37]), "+f"(d[38]), "+f"(d[39])
        : "r"(a[0]), "r"(a[1]), "r"(a[2]), "r"(a[3]), "r"(db_lo), "r"(scale_d));
}
__device__ __forceinline__ void wgmma_ss_n256_tb(float (&d)[128], uint64_t da, uint64_t db, int scale_d) {
    asm volatile(
        "{\n.reg .pred p;\nsetp.ne.b32 p, %130, 0;\n"
        "wgmma.mma_async.sync.aligned.m64n256k16.f32.bf16.bf16 {%0, %1, %2, %3, %4, %5, %6, %7, %8, %9, %10, %11, %12, %13, %14, %15, %16, %17, %18, %19, %20, %21, %22, %23, %24, %25, %26, %27, %28, %29, %30, %31, %32, %33, %34, %35, %36, %37, %38, %39, %40, %41, %42, %43, %44, %45, %46, %47, %48, %49, %50, %51, %52, %53, %54, %55, %56, %57, %58, %59, %60, %61, %62, %63, %64, %65, %66, %67, %68, %69, %70, %71, %72, %73, %74, %75, %76, %77, %78, %79, %80, %81, %82, %83, %84, %85, %86, %87, %88, %89, %90, %91, %92, %93, %94, %95, %96, %97, %98, %99, %100, %101, %102, %103, %104, %105, %106, %107, %108, %109, %110, %111, %112, %113, %114, %115, %116, %117, %118, %119, %120, %121, %122, %123, %124, %125, %126, %127}, %128, %129, p, 1, 1, 0, 1;\n}\n"
        : "+f"(d[0]), "+f"(d[1]), "+f"(d[2]), "+f"(d[3]), "+f"(d[4]), "+f"(d[5]), "+f"(d[6]), "+f"(d[7]), "+f"(d[8]), "+f"(d[9]), "+f"(d[10]), "+f"(d[11]), "+f"(d[12]), "+f"(d[13]), "+f"(d[14]), "+f"(d[15]), "+f"(d[16]), "+f"(d[17]), "+f"(d[18]), "+f"(d[19]), "+f"(d[20]), "+f"(d[21]), "+f"(d[22]), "+f"(d[23]), "+f"(d[24]), "+f"(d[25]), "+f"(d[26]), "+f"(d[27]), "+f"(d[28]), "+f"(d[29]), "+f"(d[30]), "+f"(d[31]), "+f"(d[32]), "+f"(d[33]), "+f"(d[34]), "+f"(d[35]), "+f"(d[36]), "+f"(d[37]), "+f"(d[38]), "+f"(d[39]), "+f"(d[40]), "+f"(d[41]), "+f"(d[42]), "+f"(d[43]), "+f"(d[44]), "+f"(d[45]), "+f"(d[46]), "+f"(d[47]), "+f"(d[48]), "+f"(d[49]), "+f"(d[50]), "+f"(d[51]), "+f"(d[52]), "+f"(d[53]), "+f"(d[54]), "+f"(d[55]), "+f"(d[56]), "+f"(d[57]), "+f"(d[58]), "+f"(d[59]), "+f"(d[60]), "+f"(d[61]), "+f"(d[62]), "+f"(d[63]), "+f"(d[64]), "+f"(d[65]), "+f"(d[66]), "+f"(d[67]), "+f"(d[68]), "+f"(d[69]), "+f"(d[70]), "+f"(d[71]), "+f"(d[72]), "+f"(d[73]), "+f"(d[74]), "+f"(d[75]), "+f"(d[76]), "+f"(d[77]), "+f"(d[78]), "+f"(d[79]), "+f"(d[80]), "+f"(d[81]), "+f"(d[82]), "+f"(d[83]), "+f"(d[84]), "+f"(d[85]), "+f"(d[86]), "+f"(d[87]), "+f"(d[88]), "+f"(d[89]), "+f"(d[90]), "+f"(d[91]), "+f"(d[92]), "+f"(d[93]), "+f"(d[94]), "+f"(d[95]), "+f"(d[96]), "+f"(d[97]), "+f"(d[98]), "+f"(d[99]), "+f"(d[100]), "+f"(d[101]), "+f"(d[102]), "+f"(d[103]), "+f"(d[104]), "+f"(d[105]), "+f"(d[106]), "+f"(d[107]), "+f"(d[108]), "+f"(d[109]), "+f"(d[110]), "+f"(d[111]), "+f"(d[112]), "+f"(d[113]), "+f"(d[114]), "+f"(d[115]), "+f"(d[116]), "+f"(d[117]), "+f"(d[118]), "+f"(d[119]), "+f"(d[120]), "+f"(d[121]), "+f"(d[122]), "+f"(d[123]), "+f"(d[124]), "+f"(d[125]), "+f"(d[126]), "+f"(d[127])
        : "l"(da), "l"(db), "r"(scale_d));
}
__device__ __forceinline__ void stmatrix_x4(uint32_t addr, uint32_t r0, uint32_t r1, uint32_t r2, uint32_t r3) {
    asm volatile("stmatrix.sync.aligned.m8n8.x4.shared.b16 [%0], {%1, %2, %3, %4};" :: "r"(addr), "r"(r0), "r"(r1), "r"(r2), "r"(r3) : "memory");
}
__device__ __forceinline__ void tma_store_2d(const CUtensorMap* map, uint32_t src, int c0, int c1) {
    asm volatile("cp.async.bulk.tensor.2d.global.shared::cta.bulk_group [%0, {%2, %3}], [%1];"
                 :: "l"((uint64_t)map), "r"(src), "r"(c0), "r"(c1) : "memory");
}
__device__ __forceinline__ float ex2f(float x) { float y; asm("ex2.approx.ftz.f32 %0, %1;" : "=f"(y) : "f"(x)); return y; }
__device__ __forceinline__ uint32_t pack_bf16(float lo, float hi) {
    __nv_bfloat162 v = __floats2bfloat162_rn(lo, hi);
    return *reinterpret_cast<uint32_t*>(&v);
}
__device__ __forceinline__ void mma_16816(float (&c)[4], uint32_t a0, uint32_t a1, uint32_t a2, uint32_t a3,
                                          uint32_t b0, uint32_t b1) {
    asm volatile(
        "mma.sync.aligned.m16n8k16.row.col.f32.bf16.bf16.f32 {%0,%1,%2,%3}, {%4,%5,%6,%7}, {%8,%9}, {%0,%1,%2,%3};"
        : "+f"(c[0]), "+f"(c[1]), "+f"(c[2]), "+f"(c[3])
        : "r"(a0), "r"(a1), "r"(a2), "r"(a3), "r"(b0), "r"(b1));
}
__device__ __forceinline__ void ldmatrix_x4_trans(uint32_t& r0, uint32_t& r1, uint32_t& r2, uint32_t& r3, uint32_t addr) {
    asm volatile("ldmatrix.sync.aligned.m8n8.x4.trans.shared.b16 {%0,%1,%2,%3}, [%4];"
                 : "=r"(r0), "=r"(r1), "=r"(r2), "=r"(r3) : "r"(addr));
}

struct AttnParams {
    CUtensorMap mapQ, mapK, mapV;
    CUtensorMap mapO;
};
constexpr int FA_STAGES = 2;
constexpr int FA_SMEM = 32768 + FA_STAGES * 65536 + 32768 + 1024 + 256;
constexpr int FA_ITEMS = 16 * NH;
#define FA_RETIRE 100000
#define FA_LASTG 8
__device__ __forceinline__ int fa_qt(int t) {
    constexpr int T0 = (32 - FA_LASTG) * 16;
    return t < T0 ? 15 - ((t & 127) >> 3) : 15 - (t - T0) / FA_LASTG;
}
__device__ __forceinline__ int fa_head(int t) {
    constexpr int T0 = (32 - FA_LASTG) * 16;
    return t < T0 ? (t >> 7) * 8 + (t & 7) : (32 - FA_LASTG) + (t - T0) % FA_LASTG;
}

__global__ void __launch_bounds__(384, 1) attn_kernel(const __grid_constant__ AttnParams P, int retire_cta) {
    extern __shared__ uint8_t smem_raw[];
    uint32_t sbase = (smem_u32(smem_raw) + 1023) & ~1023u;
    const uint32_t sQ = sbase;
    const uint32_t sKV = sbase + 32768;
    const uint32_t sO = sKV + FA_STAGES * 65536;
    const uint32_t bars = sO + 32768;
    const uint32_t bar_q = bars, bar_qe = bars + 8, bar_kf = bars + 16, bar_vf = bar_kf + 8 * FA_STAGES, bar_e = bar_vf + 8 * FA_STAGES,
                   bar_ek = bar_e + 8 * FA_STAGES, slot = bar_ek + 8 * FA_STAGES, bar_of = slot + 16, bar_oe = bar_of + 16, oslot = bar_oe + 16;
    const int warp = threadIdx.x >> 5;
    TS_BEGIN(1);
    int tfirst = 0;
    if (threadIdx.x == 256) tfirst = (int)atomicAdd(&g_ctr[CT_ATTN], 1u);
    if (threadIdx.x == 0) {
        mbar_init(bar_q, 1); mbar_init(bar_qe, 8);
        for (int i = 0; i < FA_STAGES; i++) { mbar_init(bar_kf + 8 * i, 1); mbar_init(bar_vf + 8 * i, 1); mbar_init(bar_e + 8 * i, 8); mbar_init(bar_ek + 8 * i, 8); }
        for (int i = 0; i < 2; i++) { mbar_init(bar_of + 8 * i, 1); mbar_init(bar_oe + 8 * i, 1); }
        asm volatile("fence.mbarrier_init.release.cluster;" ::: "memory");
    }
    if (threadIdx.x == 256) asm volatile("st.shared.s32 [%0], %1;" :: "r"(slot + 8), "r"(tfirst) : "memory");
    __syncthreads();
    pdl_launch_dependents();
    if (warp >= 8) {
        asm volatile("setmaxnreg.dec.sync.aligned.u32 40;");
        if (threadIdx.x == 288 || threadIdx.x == 320) {
            const int wg = threadIdx.x == 288 ? 0 : 1;
            const uint32_t stg = sO + wg * 16384;
            for (int n = 0;; n++) {
                mbar_wait(bar_of + 8 * wg, n & 1);
                int t;
                asm volatile("ld.shared.s32 %0, [%1];" : "=r"(t) : "r"(oslot + wg * 4) : "memory");
                if (t < 0) break;
                const int qt = fa_qt(t), h = fa_head(t);
                tma_store_2d(&P.mapO, stg, 0, h * SEQ + qt * 128 + wg * 64);
                tma_store_2d(&P.mapO, stg + 8192, 64, h * SEQ + qt * 128 + wg * 64);
                asm volatile("cp.async.bulk.commit_group;" ::: "memory");
                asm volatile("cp.async.bulk.wait_group.read 0;" ::: "memory");
                mbar_arrive(bar_oe + 8 * wg);
                asm volatile("cp.async.bulk.wait_group 0;" ::: "memory");
                signal_ctr(CT_CA + qt * 2 + (h >= O2_HE));
            }
        }
        if (threadIdx.x == 256) {
            int it = 0, hp_ready = 0;
            for (int item = 0;; item++) {
                int t = tfirst;
                if (item > 0) {
                    bool quit = false;
                    if ((int)blockIdx.x >= retire_cta) {
                        unsigned int v;
                        asm volatile("ld.relaxed.gpu.global.u32 %0, [%1];" : "=r"(v) : "l"(&g_ctr[CT_ATTN]) : "memory");
                        quit = v >= FA_RETIRE;
                    }
                    t = quit ? FA_ITEMS : (int)atomicAdd(&g_ctr[CT_ATTN], 1u);
                }
                const bool valid = t < FA_ITEMS;
                const int qt = fa_qt(t), h = fa_head(t);
                if (valid && !((hp_ready >> (h >> 1)) & 1)) { wait_ctr(CT_AP + (h >> 1), 96u); hp_ready |= 1 << (h >> 1); }
                mbar_wait(bar_qe, (item & 1) ^ 1);
                asm volatile("st.shared.s32 [%0], %1;" :: "r"(slot + (item & 1) * 4), "r"(valid ? t : -1) : "memory");
                if (!valid) { mbar_arrive(bar_q); break; }
                mbar_expect_tx(bar_q, 32768);
                tma_load_2d(sQ, &P.mapQ, bar_q, 0, h * SEQ + qt * 128);
                tma_load_2d(sQ + 16384, &P.mapQ, bar_q, 64, h * SEQ + qt * 128);
                for (int j = 0; j <= qt; j++, it++) {
                    const int s = it % FA_STAGES;
                    mbar_wait(bar_ek + 8 * s, ((it / FA_STAGES) & 1) ^ 1);
                    const uint32_t sk = sKV + s * 65536, sv = sk + 32768;
                    mbar_expect_tx(bar_kf + 8 * s, 32768);
                    tma_load_2d(sk, &P.mapK, bar_kf + 8 * s, 0, h * SEQ + j * 128);
                    tma_load_2d(sk + 16384, &P.mapK, bar_kf + 8 * s, 64, h * SEQ + j * 128);
                    mbar_wait(bar_e + 8 * s, ((it / FA_STAGES) & 1) ^ 1);
                    mbar_expect_tx(bar_vf + 8 * s, 32768);
                    tma_load_2d(sv, &P.mapV, bar_vf + 8 * s, 0, h * SEQ + j * 128);
                    tma_load_2d(sv + 16384, &P.mapV, bar_vf + 8 * s, 64, h * SEQ + j * 128);
                }
            }
        }
    } else {
        asm volatile("setmaxnreg.inc.sync.aligned.u32 232;");
        const int wg = warp >> 2;
        const int lane = threadIdx.x & 31;
        float o[64];
        float mrow0, mrow1, lrow0, lrow1;
        const float sc = 0.08838834764831845f * 1.4426950408889634f;
        const int r0 = wg * 64 + (warp & 3) * 16 + (lane >> 2);
        float sacc[64];
        uint32_t pa[32];
        float a0 = 1.f, a1 = 1.f;
        auto issue_qk = [&](int it) {
            const int s = it % FA_STAGES;
            const uint32_t sk = sKV + s * 65536;
            mbar_wait(bar_kf + 8 * s, (it / FA_STAGES) & 1);
            wgmma_fence();
#pragma unroll
            for (int kk = 0; kk < 8; kk++) {
                uint64_t da = make_desc(sQ + (kk >> 2) * 16384 + wg * 8192 + (kk & 3) * 32, 16, 1024);
                uint64_t db = make_desc(sk + (kk >> 2) * 16384 + (kk & 3) * 32, 16, 1024);
                wgmma_ss_n128<0>(sacc, da, db, kk != 0);
            }
            wgmma_commit();
        };
        auto issue_pv = [&](int it) {
            const int s = it % FA_STAGES;
            const uint32_t sv = sKV + s * 65536 + 32768;
            mbar_wait(bar_vf + 8 * s, (it / FA_STAGES) & 1);
            wgmma_fence();
#pragma unroll
            for (int kk = 0; kk < 8; kk++) {
                uint64_t db = make_desc(sv + kk * 2048, 16384, 1024);
                wgmma_rs_n128_tb(o, pa[kk * 4 + 0], pa[kk * 4 + 1], pa[kk * 4 + 2], pa[kk * 4 + 3], db, 1);
            }
            wgmma_commit();
        };
        auto softmax_stats = [&](bool diag) {
            if (diag) {
#pragma unroll
                for (int i = 0; i < 64; i++) {
                    int col = (i >> 2) * 8 + (lane & 3) * 2 + (i & 1);
                    int row = r0 + ((i & 2) ? 8 : 0);
                    if (col > row) sacc[i] = -INFINITY;
                }
            }
            float mx0 = -INFINITY, mx1 = -INFINITY;
#pragma unroll
            for (int i = 0; i < 16; i++) {
                mx0 = fmaxf(mx0, fmaxf(sacc[i * 4 + 0], sacc[i * 4 + 1]));
                mx1 = fmaxf(mx1, fmaxf(sacc[i * 4 + 2], sacc[i * 4 + 3]));
            }
            mx0 = fmaxf(mx0, __shfl_xor_sync(0xffffffff, mx0, 1));
            mx0 = fmaxf(mx0, __shfl_xor_sync(0xffffffff, mx0, 2));
            mx1 = fmaxf(mx1, __shfl_xor_sync(0xffffffff, mx1, 1));
            mx1 = fmaxf(mx1, __shfl_xor_sync(0xffffffff, mx1, 2));
            const float mn0 = fmaxf(mrow0, mx0), mn1 = fmaxf(mrow1, mx1);
            a0 = ex2f((mrow0 - mn0) * sc); a1 = ex2f((mrow1 - mn1) * sc);
            mrow0 = mn0; mrow1 = mn1;
            const float ms0 = mn0 * sc, ms1 = mn1 * sc;
            float sum0 = 0.f, sum1 = 0.f;
#pragma unroll
            for (int i = 0; i < 16; i++) {
                sacc[i * 4 + 0] = ex2f(fmaf(sacc[i * 4 + 0], sc, -ms0));
                sacc[i * 4 + 1] = ex2f(fmaf(sacc[i * 4 + 1], sc, -ms0));
                sacc[i * 4 + 2] = ex2f(fmaf(sacc[i * 4 + 2], sc, -ms1));
                sacc[i * 4 + 3] = ex2f(fmaf(sacc[i * 4 + 3], sc, -ms1));
                sum0 += sacc[i * 4 + 0] + sacc[i * 4 + 1];
                sum1 += sacc[i * 4 + 2] + sacc[i * 4 + 3];
            }
            lrow0 = lrow0 * a0 + sum0;
            lrow1 = lrow1 * a1 + sum1;
        };
        auto pack_p = [&]() {
#pragma unroll
            for (int i = 0; i < 16; i++) {
                pa[i * 2 + 0] = pack_bf16(sacc[i * 4 + 0], sacc[i * 4 + 1]);
                pa[i * 2 + 1] = pack_bf16(sacc[i * 4 + 2], sacc[i * 4 + 3]);
            }
        };
        int it = 0;
        if (wg == 1) asm volatile("bar.arrive 1, 256;" ::: "memory");
        for (int item = 0;; item++) {
            mbar_wait(bar_q, item & 1);
            int t;
            asm volatile("ld.shared.s32 %0, [%1];" : "=r"(t) : "r"(slot + (item & 1) * 4) : "memory");
            if (t < 0) {
                if ((threadIdx.x & 127) == 0) {
                    mbar_wait(bar_oe + 8 * wg, (item & 1) ^ 1);
                    asm volatile("st.shared.s32 [%0], %1;" :: "r"(oslot + wg * 4), "r"(-1) : "memory");
                    mbar_arrive(bar_of + 8 * wg);
                }
                break;
            }
            const int qt = fa_qt(t);
            const int nkv = qt + 1;
#pragma unroll
            for (int i = 0; i < 64; i++) o[i] = 0.f;
            mrow0 = -INFINITY; mrow1 = -INFINITY; lrow0 = 0.f; lrow1 = 0.f;
            asm volatile("bar.sync %0, 256;" :: "r"(1 + wg) : "memory");
            issue_qk(it);
            asm volatile("bar.arrive %0, 256;" :: "r"(2 - wg) : "memory");
            wgmma_wait<0>();
            if (lane == 0) { mbar_arrive(bar_ek + 8 * (it % FA_STAGES)); if (nkv == 1) mbar_arrive(bar_qe); }
            softmax_stats(nkv == 1);
            pack_p();
#pragma unroll 1
            for (int j = 1; j < nkv; j++) {
                asm volatile("bar.sync %0, 256;" :: "r"(1 + wg) : "memory");
                issue_qk(it + j);
                issue_pv(it + j - 1);
                asm volatile("bar.arrive %0, 256;" :: "r"(2 - wg) : "memory");
                wgmma_wait<1>();
                if (lane == 0) { mbar_arrive(bar_ek + 8 * ((it + j) % FA_STAGES)); if (j == nkv - 1) mbar_arrive(bar_qe); }
                softmax_stats(j == nkv - 1);
                wgmma_wait<0>();
                if (lane == 0) mbar_arrive(bar_e + 8 * ((it + j - 1) % FA_STAGES));
#pragma unroll
                for (int i = 0; i < 16; i++) {
                    o[i * 4 + 0] *= a0; o[i * 4 + 1] *= a0; o[i * 4 + 2] *= a1; o[i * 4 + 3] *= a1;
                }
                pack_p();
            }
            issue_pv(it + nkv - 1);
            wgmma_wait<0>();
            if (lane == 0) mbar_arrive(bar_e + 8 * ((it + nkv - 1) % FA_STAGES));
            it += nkv;
            lrow0 += __shfl_xor_sync(0xffffffff, lrow0, 1);
            lrow0 += __shfl_xor_sync(0xffffffff, lrow0, 2);
            lrow1 += __shfl_xor_sync(0xffffffff, lrow1, 1);
            lrow1 += __shfl_xor_sync(0xffffffff, lrow1, 2);
            const float i0 = 1.f / lrow0, i1 = 1.f / lrow1;
            const uint32_t stg = sO + wg * 16384;
            mbar_wait(bar_oe + 8 * wg, (item & 1) ^ 1);
            {
                const int row = (warp & 3) * 16 + (lane >> 2);
#pragma unroll
                for (int i = 0; i < 4; i++) {
                    const int ch = i * 4 + (lane & 3);
                    const uint32_t a = stg + (ch >> 3) * 8192 + row * 128 + (((ch & 7) ^ (row & 7)) << 4);
                    const float* q = &o[i * 16];
                    asm volatile("st.shared.v4.b32 [%0], {%1, %2, %3, %4};" :: "r"(a), "r"(pack_bf16(q[0] * i0, q[1] * i0)), "r"(pack_bf16(q[4] * i0, q[5] * i0)),
                                 "r"(pack_bf16(q[8] * i0, q[9] * i0)), "r"(pack_bf16(q[12] * i0, q[13] * i0)) : "memory");
                    asm volatile("st.shared.v4.b32 [%0], {%1, %2, %3, %4};" :: "r"(a + 1024), "r"(pack_bf16(q[2] * i1, q[3] * i1)), "r"(pack_bf16(q[6] * i1, q[7] * i1)),
                                 "r"(pack_bf16(q[10] * i1, q[11] * i1)), "r"(pack_bf16(q[14] * i1, q[15] * i1)) : "memory");
                }
            }
            asm volatile("fence.proxy.async.shared::cta;" ::: "memory");
            asm volatile("bar.sync %0, 128;" :: "r"(3 + wg) : "memory");
            if ((threadIdx.x & 127) == 0) {
                asm volatile("st.shared.s32 [%0], %1;" :: "r"(oslot + wg * 4), "r"(t) : "memory");
                mbar_arrive(bar_of + 8 * wg);
            }
        }
        TS_END(1);
    }
}

__device__ __forceinline__ uint32_t cluster_ctarank() {
    uint32_t r; asm volatile("mov.u32 %0, %%cluster_ctarank;" : "=r"(r)); return r;
}
__device__ __forceinline__ uint32_t mapa_u32(uint32_t addr, uint32_t rank) {
    uint32_t r; asm volatile("mapa.shared::cluster.u32 %0, %1, %2;" : "=r"(r) : "r"(addr), "r"(rank)); return r;
}
__device__ __forceinline__ void cluster_sync_all() {
    asm volatile("barrier.cluster.arrive.release.aligned;\nbarrier.cluster.wait.acquire.aligned;" ::: "memory");
}
__device__ __forceinline__ void st_async_v4(uint32_t addr, uint32_t a, uint32_t b, uint32_t c, uint32_t d, uint32_t mbar) {
    asm volatile("st.async.weak.shared::cluster.mbarrier::complete_tx::bytes.v4.b32 [%0], {%1, %2, %3, %4}, [%5];"
                 :: "r"(addr), "r"(a), "r"(b), "r"(c), "r"(d), "r"(mbar) : "memory");
}
__device__ __forceinline__ void st_async_v2(uint32_t addr, uint32_t a, uint32_t b, uint32_t mbar) {
    asm volatile("st.async.weak.shared::cluster.mbarrier::complete_tx::bytes.v2.b32 [%0], {%1, %2}, [%3];"
                 :: "r"(addr), "r"(a), "r"(b), "r"(mbar) : "memory");
}
__device__ __forceinline__ void st_async_b32(uint32_t addr, uint32_t a, uint32_t mbar) {
    asm volatile("st.async.weak.shared::cluster.mbarrier::complete_tx::bytes.b32 [%0], %1, [%2];" :: "r"(addr), "r"(a), "r"(mbar) : "memory");
}
__device__ __forceinline__ void pace(int cycles) {
    if (cycles > 0) {
        uint32_t t0, t;
        asm volatile("mov.u32 %0, %%clock;" : "=r"(t0));
        do { asm volatile("mov.u32 %0, %%clock;" : "=r"(t)); } while (t - t0 < (uint32_t)cycles);
    }
}
__device__ __forceinline__ void mbar_wait_cl(uint32_t bar, uint32_t parity) {
    uint32_t done = 0;
    for (int it = 0; it < WAIT_LIMIT && !done; it++) {
        asm volatile(
            "{\n.reg .pred p;\n"
            "mbarrier.try_wait.parity.shared::cta.b64 p, [%1], %2;\n"
            "selp.u32 %0, 1, 0, p;\n}\n" : "=r"(done) : "r"(bar), "r"(parity) : "memory");
    }
}
__device__ __forceinline__ uint32_t mbar_test(uint32_t bar, uint32_t parity) {
    uint32_t done;
    asm volatile(
        "{\n.reg .pred p;\n"
        "mbarrier.test_wait.parity.shared::cta.b64 p, [%1], %2;\n"
        "selp.u32 %0, 1, 0, p;\n}\n" : "=r"(done) : "r"(bar), "r"(parity) : "memory");
    return done;
}
__device__ __forceinline__ void ldmatrix_x4(uint32_t& r0, uint32_t& r1, uint32_t& r2, uint32_t& r3, uint32_t addr) {
    asm volatile("ldmatrix.sync.aligned.m8n8.x4.shared.b16 {%0,%1,%2,%3}, [%4];"
                 : "=r"(r0), "=r"(r1), "=r"(r2), "=r"(r3) : "r"(addr));
}
__device__ __forceinline__ void cp_async16(uint32_t dst, const void* src) {
    asm volatile("cp.async.cg.shared.global [%0], [%1], 16;" :: "r"(dst), "l"(src) : "memory");
}
__device__ __forceinline__ float bf16r(float x) { return __uint_as_float(pack_bf16(0.f, x) & 0xffff0000u); }

#define DBG(i, w)
#define DBGD(i, w, dep)
#define DBG_EXTRA 0
__device__ __forceinline__ void tma_load_2d_mc(uint32_t dst, const CUtensorMap* map, uint32_t bar, int c0, int c1, uint16_t mask) {
    asm volatile(
        "cp.async.bulk.tensor.2d.shared::cluster.global.mbarrier::complete_tx::bytes.multicast::cluster [%0], [%1, {%3, %4}], [%2], %5;"
        :: "r"(dst), "l"((uint64_t)map), "r"(bar), "r"(c0), "r"(c1), "h"(mask) : "memory");
}
__device__ __forceinline__ void stmatrix_x4_trans(uint32_t addr, uint32_t r0, uint32_t r1, uint32_t r2, uint32_t r3) {
    asm volatile("stmatrix.sync.aligned.m8n8.x4.trans.shared.b16 [%0], {%1, %2, %3, %4};" :: "r"(addr), "r"(r0), "r"(r1), "r"(r2), "r"(r3) : "memory");
}
__device__ __forceinline__ void stmatrix_x2_trans(uint32_t addr, uint32_t r0, uint32_t r1) {
    asm volatile("stmatrix.sync.aligned.m8n8.x2.trans.shared.b16 [%0], {%1, %2};" :: "r"(addr), "r"(r0), "r"(r1) : "memory");
}
__device__ __forceinline__ uint4 lds128(uint32_t a) {
    uint4 v; asm volatile("ld.shared.v4.u32 {%0, %1, %2, %3}, [%4];" : "=r"(v.x), "=r"(v.y), "=r"(v.z), "=r"(v.w) : "r"(a) : "memory"); return v;
}
__device__ __forceinline__ void sts128(uint32_t a, uint32_t x, uint32_t y, uint32_t z, uint32_t w) {
    asm volatile("st.shared.v4.b32 [%0], {%1, %2, %3, %4};" :: "r"(a), "r"(x), "r"(y), "r"(z), "r"(w) : "memory");
}
__device__ __forceinline__ float2 lds64f(uint32_t a) {
    float2 v; asm volatile("ld.shared.v2.f32 {%0, %1}, [%2];" : "=f"(v.x), "=f"(v.y) : "r"(a) : "memory"); return v;
}
__device__ __forceinline__ void fence_async_smem() { asm volatile("fence.proxy.async.shared::cta;" ::: "memory"); }
#define ACC16(d) "+f"(d[0]), "+f"(d[1]), "+f"(d[2]), "+f"(d[3]), "+f"(d[4]), "+f"(d[5]), "+f"(d[6]), "+f"(d[7]), "+f"(d[8]), "+f"(d[9]), "+f"(d[10]), "+f"(d[11]), "+f"(d[12]), "+f"(d[13]), "+f"(d[14]), "+f"(d[15])
template <int ND>
__device__ __forceinline__ void wgmma_rs_n32(float (&d)[ND], const uint32_t (&a)[4], uint32_t db_lo, int scale_d) {
    asm volatile(
        "{\n.reg .pred p;\n.reg .b64 db;\nsetp.ne.b32 p, %21, 0;\nmov.b64 db, {%20, 0x40000040};\n"
        "wgmma.mma_async.sync.aligned.m64n32k16.f32.bf16.bf16 {%0,%1,%2,%3,%4,%5,%6,%7,%8,%9,%10,%11,%12,%13,%14,%15}, {%16,%17,%18,%19}, db, p, 1, 1, 0;\n}\n"
        : ACC16(d) : "r"(a[0]), "r"(a[1]), "r"(a[2]), "r"(a[3]), "r"(db_lo), "r"(scale_d));
}
template <int ND>
__device__ __forceinline__ void wgmma_ss_n32(float (&d)[ND], uint32_t da_lo, uint32_t db_lo, int scale_d) {
    asm volatile(
        "{\n.reg .pred p;\n.reg .b64 da, db;\nsetp.ne.b32 p, %18, 0;\nmov.b64 da, {%16, 0x40000040};\nmov.b64 db, {%17, 0x40000040};\n"
        "wgmma.mma_async.sync.aligned.m64n32k16.f32.bf16.bf16 {%0,%1,%2,%3,%4,%5,%6,%7,%8,%9,%10,%11,%12,%13,%14,%15}, da, db, p, 1, 1, 1, 0;\n}\n"
        : ACC16(d) : "r"(da_lo), "r"(db_lo), "r"(scale_d));
}
__device__ __forceinline__ void wgmma_ss_n8(float (&d)[4], uint32_t da_lo, uint32_t db_lo, int scale_d) {
    asm volatile(
        "{\n.reg .pred p;\n.reg .b64 da, db;\nsetp.ne.b32 p, %6, 0;\nmov.b64 da, {%4, 0x40000040};\nmov.b64 db, {%5, 0x00000010};\n"
        "wgmma.mma_async.sync.aligned.m64n8k16.f32.bf16.bf16 {%0,%1,%2,%3}, da, db, p, 1, 1, 1, 0;\n}\n"
        : "+f"(d[0]), "+f"(d[1]), "+f"(d[2]), "+f"(d[3]) : "r"(da_lo), "r"(db_lo), "r"(scale_d));
}

#define SCHED_FENCE()
__device__ __forceinline__ void wgmma_ss_n32_p(float (&d)[16], uint32_t da_lo, uint32_t db_lo, int scale_d) {
    asm volatile(
        "{\n.reg .pred p;\n.reg .b64 da, db;\nsetp.ne.b32 p, %18, 0;\nmov.b64 da, {%16, 0x40000040};\nmov.b64 db, {%17, 0x00000030};\n"
        "wgmma.mma_async.sync.aligned.m64n32k16.f32.bf16.bf16 {%0,%1,%2,%3,%4,%5,%6,%7,%8,%9,%10,%11,%12,%13,%14,%15}, da, db, p, 1, 1, 1, 0;\n}\n"
        : ACC16(d) : "r"(da_lo), "r"(db_lo), "r"(scale_d));
}

__device__ __forceinline__ void wgmma_ss_n32_kk(float (&d)[16], uint32_t da_lo, uint32_t db_lo, int scale_d) {
    asm volatile(
        "{\n.reg .pred p;\n.reg .b64 da, db;\nsetp.ne.b32 p, %18, 0;\nmov.b64 da, {%16, 0x40000040};\nmov.b64 db, {%17, 0x40000040};\n"
        "wgmma.mma_async.sync.aligned.m64n32k16.f32.bf16.bf16 {%0,%1,%2,%3,%4,%5,%6,%7,%8,%9,%10,%11,%12,%13,%14,%15}, da, db, p, 1, 1, 0, 0;\n}\n"
        : ACC16(d) : "r"(da_lo), "r"(db_lo), "r"(scale_d));
}

struct ChainParams {
    CUtensorMap mapW[3];
    CUtensorMap mapX;
};
constexpr int CH_BLOCK = 384;
constexpr int CO_WO = 0;
constexpr int CO_XB = 65536;
constexpr int CO_MB = CO_XB + 65536;
constexpr int CO_OB = CO_MB + 8192;
constexpr int CH_TW = 6144, CH_TP = 3 * CH_TW;
constexpr int CO_T = CO_OB + 8192;
constexpr int CO_SC = CO_T + 2 * CH_TP;
constexpr int CO_LS = CO_SC + 2 * 1280;
constexpr int CO_LO = CO_LS + 4 * 1280;
constexpr int CO_P = CO_LO + 4 * 1280;
constexpr int CO_ST = 203776;
#define CH_NSM 3
constexpr int CO_WA = CO_ST + 4096;
constexpr int CO_BAR = CO_WA + CH_TP;
constexpr int CH_SMEM = CO_BAR + 256 + 1024 + DBG_EXTRA;
static_assert(CO_WA >= 3 * 65536 && CO_P + 6144 <= CO_ST && CH_NSM <= 3, "smem layout");
#define CH_POLL_DELAY 0
#define CH_VSPLIT 12
#define CH_CHAINS 4

constexpr float CH_SC = 0.08838834764831845f * 1.4426950408889634f;
__device__ __forceinline__ uint32_t pin(uint32_t v) { return __shfl_sync(0xffffffff, v, threadIdx.x & 31); }

__global__ void __cluster_dims__(8, 1, 1) __launch_bounds__(CH_BLOCK, 1)
chain_kernel(const __grid_constant__ ChainParams P, const bf16* __restrict__ mem0, const bf16* __restrict__ Wo, const bf16* __restrict__ x) {
    extern __shared__ uint8_t smem_raw[];
    const uint32_t sb = (smem_u32(smem_raw) + 1023) & ~1023u;
    const int tid = threadIdx.x, warp = __shfl_sync(0xffffffff, tid >> 5, 0), lane = tid & 31;
    const int rank = (int)cluster_ctarank();
    const int C = blockIdx.x >> 3;
    const int h = C * 4 + (rank >> 1);
    const int qd = lane >> 2, qc = lane & 3;
    const int t4 = warp & 3, wg = warp >> 2;
    pdl_launch_dependents();
    TS_BEGIN(2);
    const uint32_t bar_mem = sb + CO_BAR, bar_o = bar_mem + 32, bar_sc = bar_o + 32, bar_x = bar_sc + 8, bar_l = bar_x + 16, bar_w = bar_l + 8;
    if (tid == 0) {
        for (int j = 0; j < 15; j++) mbar_init(bar_mem + 8 * j, bar_mem + 8 * j == bar_l ? 4 : 1);
        asm volatile("fence.mbarrier_init.release.cluster;" ::: "memory");
    }
    __syncthreads();
    if ((tid & 127) == 0) {
        mbar_expect_tx(bar_w + 8 * wg, 65536);
        for (int i = 0; i < 8; i++)
            tma_load_2d(sb + wg * 65536 + i * 8192, &P.mapW[wg], bar_w + 8 * wg, h * HD + (rank & 1) * 64, i * 64);
    }
    {
        for (int i = tid; i < 512; i += CH_BLOCK) asm volatile("prefetch.global.L2 [%0];" :: "l"(Wo + (size_t)(C * 512 + i) * DM + rank * 64));
        if (tid < 64) asm volatile("prefetch.global.L2 [%0];" :: "l"(x + (size_t)tid * DM + rank * 64));
    }
    auto chunk = [&](int i) { return (uint32_t)((rank - (i >> 1) - 4 * (i & 1)) & 7); };
    const uint32_t wfrag = (((lane >> 4) << 3) + (lane & 7)) * 128 + (((t4 * 2 + ((lane >> 3) & 1)) ^ (lane & 7)) << 4);
    const uint32_t aO = pin(sb + wg * CH_TW + wfrag);
    const uint32_t aM = pin(sb + (lane & 7) * 128 + (((lane >> 3) ^ (lane & 7)) << 4));
    const uint32_t aL = pin(sb + lane * 8);
    uint32_t w[32][4];
    float d[16];
    mbar_wait(bar_w + 8 * wg, 0);
#pragma unroll
    for (int e = CH_NSM; e < 32; e++) ldmatrix_x4_trans(w[e][0], w[e][1], w[e][2], w[e][3], sb + wg * 65536 + wfrag + chunk(e >> 2) * 8192 + (e & 3) * 2048);
#pragma unroll
    for (int e = 0; e < CH_NSM; e++) {
        const uint4 u = lds128(sb + wg * 65536 + chunk(0) * 8192 + e * 2048 + (tid & 127) * 16);
        sts128(sb + CO_WA + wg * CH_TW + e * 2048 + (tid & 127) * 16, u.x, u.y, u.z, u.w);
    }
    fence_async_smem();
    __syncthreads();
    if (tid == 0) {
        fence_async_smem();
        for (int b = 0; b < 2; b++) {
            mbar_expect_tx(bar_x + 8 * b, 32768);
            for (int i = 0; i < 8; i++) tma_load_2d(sb + CO_XB + b * 32768 + i * 4096, &P.mapX, bar_x + 8 * b, i * 64, b * SEGL);
        }
    }
#pragma unroll 2
    for (int i = tid; i < 512 * 4; i += CH_BLOCK) {
        const int r = i >> 2, cg = i & 3, ks = r >> 4, kp = r & 15;
        const int src = (rank - (ks >> 2)) & 7;
        const uint4* p = reinterpret_cast<const uint4*>(Wo + (size_t)(C * 512 + src * 64 + (ks & 3) * 16 + (kp >> 2) * 2 + (kp & 1) + (kp & 2) * 4) * DM + rank * 64 + cg * 16);
        const uint4 u0 = __ldg(p), u1 = __ldg(p + 1);
        const uint32_t a = sb + CO_WO + r * 128;
        sts128(a + (((cg * 2) ^ (r & 7)) << 4), __byte_perm(u0.x, u0.y, 0x5410), __byte_perm(u0.z, u0.w, 0x5410), __byte_perm(u1.x, u1.y, 0x5410), __byte_perm(u1.z, u1.w, 0x5410));
        sts128(a + (((cg * 2 + 1) ^ (r & 7)) << 4), __byte_perm(u0.x, u0.y, 0x7632), __byte_perm(u0.z, u0.w, 0x7632), __byte_perm(u1.x, u1.y, 0x7632), __byte_perm(u1.z, u1.w, 0x7632));
    }
#pragma unroll 1
    for (int i = tid; i < 512; i += CH_BLOCK) {
        const int n = i >> 6, c = i & 63;
        const uint4 u = __ldg(reinterpret_cast<const uint4*>(mem0 + n * DM + chunk(c >> 3) * 64 + (c & 7) * 8));
        sts128(sb + CO_MB + (c >> 3) * 1024 + n * 128 + (((c & 7) ^ n) << 4), u.x, u.y, u.z, u.w);
    }
    if (tid < 128) sts128(sb + CO_T + (tid >> 6) * CH_TP + 2 * CH_TW + 5120 + (tid & 63) * 16, 0u, 0u, 0u, 0u);
    else if (tid < 192) sts128(sb + CO_P + ((tid >> 3) & 7) * 768 + 640 + (tid & 7) * 16, 0u, 0u, 0u, 0u);
    fence_async_smem();
    TS_END(6);
    auto pass32 = [&](int b, int e0 = 0, int e1 = 32) {
        const uint32_t lo = desc_lo(sb + CO_XB + b * 32768, 16);
        wgmma_fence();
#pragma unroll
        for (int e = 0; e < 32; e++) if (e >= e0 && e < e1) {
            const uint32_t db = lo + chunk(e >> 2) * 256 + (e & 3) * 2;
            if (e < CH_NSM) wgmma_ss_n32(d, desc_lo(sb + CO_WA + wg * CH_TW + e * 2048, 16), db, e != 0);
            else wgmma_rs_n32(d, w[e], db, e != 0);
        }
        wgmma_commit();
    };
    auto store32 = [&](uint32_t a) {
        stmatrix_x4_trans(a, pack_bf16(d[0], d[1]), pack_bf16(d[2], d[3]), pack_bf16(d[4], d[5]), pack_bf16(d[6], d[7]));
        stmatrix_x4_trans(a + 2048, pack_bf16(d[8], d[9]), pack_bf16(d[10], d[11]), pack_bf16(d[12], d[13]), pack_bf16(d[14], d[15]));
    };
    auto mem_proj = [&](int s, bool wait) {
        const uint32_t par = s & 1;
        float acc[CH_CHAINS][4];
#pragma unroll
        for (int i = 0; i < CH_CHAINS; i++) acc[i][0] = acc[i][1] = acc[i][2] = acc[i][3] = 0.f;
        const uint32_t aM2 = aM ^ 64;
        uint32_t b[2][8];
        auto load = [&](int c) {
            if (wait && !(c & 1)) mbar_wait_cl(bar_mem + 4 * c, par ^ 1);
            if (c == 0) DBG(11, 0);
            if (c == 6) DBG(13, 0);
            ldmatrix_x4(b[c & 1][0], b[c & 1][1], b[c & 1][2], b[c & 1][3], aM + CO_MB + c * 1024);
            ldmatrix_x4(b[c & 1][4], b[c & 1][5], b[c & 1][6], b[c & 1][7], aM2 + CO_MB + c * 1024);
        };
        load(0);
#pragma unroll
        for (int c = 0; c < 8; c++) {
            if (c < 7) load(c + 1);
            SCHED_FENCE();
#pragma unroll
            for (int i = 0; i < 4; i++) {
                const int e = c * 4 + i;
                mma_16816(acc[i % CH_CHAINS], w[e][0], w[e][1], w[e][2], w[e][3], b[c & 1][i * 2], b[c & 1][i * 2 + 1]);
            }
        }
        if (CH_CHAINS == 4) {
#pragma unroll
            for (int i = 0; i < 4; i++) { acc[0][i] += acc[2 % CH_CHAINS][i]; acc[1][i] += acc[3 % CH_CHAINS][i]; }
        }
        const uint32_t r0 = pack_bf16(acc[0][0] + acc[1][0], acc[0][1] + acc[1][1]);
        const uint32_t r1 = pack_bf16(acc[0][2] + acc[1][2], acc[0][3] + acc[1][3]);
        DBGD(40 + warp, warp, r0 ^ r1);
        stmatrix_x2_trans(aO + par * CH_TP + CO_T + 4096, r0, r1);
    };
    auto load_wa = [&]() {
#pragma unroll
        for (int e = 0; e < CH_NSM; e++) ldmatrix_x4_trans(w[e][0], w[e][1], w[e][2], w[e][3], aO + CO_WA + e * 2048);
    };
    auto remote = [](uint32_t a, uint32_t r) { return mapa_u32(a, r); };
    mbar_wait(bar_x, 0);
    pass32(0);
    wgmma_wait<0>();
    store32(aO + CO_T);
    __syncthreads();
    cluster_sync_all();
    TS_BEGIN(5);

    if (wg < 2) {
        const uint32_t aQ = pin(sb + CO_T + qd * 128 + (((2 * qc) ^ qd) << 4));
        auto local_scores = [&](int s) {
            const uint32_t tb = sb + CO_T + (s & 1) * CH_TP;
            fence_async_smem();
            wgmma_fence();
#pragma unroll
            for (int ks = 0; ks < 4; ks++) wgmma_ss_n32_kk(d, desc_lo(tb + CH_TW, 16) + ks * 2, desc_lo(tb, 16) + ks * 2, ks != 0);
            wgmma_commit();
            wgmma_wait<0>();
            const uint32_t rb = remote(bar_l, rank ^ 1);
            if (t4 < 2) {
                const uint32_t off = 2 * aL - sb + t4 * 512;
#pragma unroll
                for (int j = 0; j < 4; j++) if (j >= 2 || t4 == 0) {
                    st_async_v4(remote(off + CO_LS + j * 1280, rank ^ 1), __float_as_uint(d[4 * j]), __float_as_uint(d[4 * j + 1]), __float_as_uint(d[4 * j + 2]), __float_as_uint(d[4 * j + 3]), rb);
                    sts128(off + CO_LO + j * 1280, __float_as_uint(d[4 * j]), __float_as_uint(d[4 * j + 1]), __float_as_uint(d[4 * j + 2]), __float_as_uint(d[4 * j + 3]));
                }
            } else if (t4 == 2) {
#pragma unroll
                for (int j = 0; j < 4; j++) {
                    st_async_v2(remote(aL + CO_LS + 1024 + j * 1280, rank ^ 1), __float_as_uint(d[4 * j]), __float_as_uint(d[4 * j + 1]), rb);
                    asm volatile("st.shared.v2.f32 [%0], {%1, %2};" :: "r"(aL + CO_LO + 1024 + j * 1280), "f"(d[4 * j]), "f"(d[4 * j + 1]) : "memory");
                }
            }
            __syncwarp();
            if (t4 < 3 && lane == 0) mbar_arrive(bar_l);
            DBG(6, 0);
        };
        auto local_softmax = [&](int s) {
            float v[10];
            mbar_wait_cl(bar_l, s & 1);
            const uint32_t off = 2 * aL - sb + t4 * 1280;
            {
                const uint4 a0 = lds128(off + CO_LS), b0 = lds128(off + CO_LO), a1 = lds128(off + CO_LS + 512), b1 = lds128(off + CO_LO + 512);
                const float2 a2 = lds64f(aL + t4 * 1280 + CO_LS + 1024), b2 = lds64f(aL + t4 * 1280 + CO_LO + 1024);
                auto f = [](uint32_t a, uint32_t b) { return __uint_as_float(a) + __uint_as_float(b); };
                v[0] = f(a0.x, b0.x); v[1] = f(a0.y, b0.y); v[2] = f(a0.z, b0.z); v[3] = f(a0.w, b0.w);
                v[4] = f(a1.x, b1.x); v[5] = f(a1.y, b1.y); v[6] = f(a1.z, b1.z); v[7] = f(a1.w, b1.w);
                v[8] = a2.x + b2.x; v[9] = a2.y + b2.y;
            }
            const int lim = t4 * 8 + 2 * qc - qd;
#pragma unroll
            for (int n = 0; n < 4; n++) {
                if (8 * n > lim) v[2 * n] = -INFINITY;
                if (8 * n > lim + 1) v[2 * n + 1] = -INFINITY;
            }
            float m0 = fmaxf(fmaxf(fmaxf(v[0], v[2]), fmaxf(v[4], v[6])), v[8]), m1 = fmaxf(fmaxf(fmaxf(v[1], v[3]), fmaxf(v[5], v[7])), v[9]);
#pragma unroll
            for (int o = 4; o < 32; o *= 2) { m0 = fmaxf(m0, __shfl_xor_sync(0xffffffff, m0, o)); m1 = fmaxf(m1, __shfl_xor_sync(0xffffffff, m1, o)); }
            m0 *= CH_SC; m1 *= CH_SC;
#pragma unroll
            for (int n = 0; n < 5; n++) { v[2 * n] = ex2f(fmaf(v[2 * n], CH_SC, -m0)); v[2 * n + 1] = ex2f(fmaf(v[2 * n + 1], CH_SC, -m1)); }
            float s0 = ((v[0] + v[2]) + (v[4] + v[6])) + v[8], s1 = ((v[1] + v[3]) + (v[5] + v[7])) + v[9];
#pragma unroll
            for (int o = 4; o < 32; o *= 2) { s0 += __shfl_xor_sync(0xffffffff, s0, o); s1 += __shfl_xor_sync(0xffffffff, s1, o); }
            asm("rcp.approx.ftz.f32 %0, %0;" : "+f"(s0));
            asm("rcp.approx.ftz.f32 %0, %0;" : "+f"(s1));
            const uint32_t pa = 2 * aL - sb + CO_P + t4 * 768;
            stmatrix_x4_trans(pa, pack_bf16(v[0] * s0, v[1] * s1), pack_bf16(v[2] * s0, v[3] * s1), pack_bf16(v[4] * s0, v[5] * s1), pack_bf16(v[6] * s0, v[7] * s1));
            asm volatile("stmatrix.sync.aligned.m8n8.x1.trans.shared.b16 [%0], {%1};" :: "r"(pa + 512), "r"(pack_bf16(v[8] * s0, v[9] * s1)) : "memory");
            fence_async_smem();
            DBG(7, 4);
        };
        auto local_pv = [&](int s) {
            wgmma_fence();
#pragma unroll
            for (int ks = 0; ks < 3; ks++)
                wgmma_ss_n32_p(d, desc_lo(sb + CO_T + (s & 1) * CH_TP + 2 * CH_TW + ks * 2048, 16), desc_lo(sb + CO_P + ks * 256, 128), ks != 0);
            wgmma_commit();
            const int r = ((lane >> 1) & 3) * 2 + ((lane >> 3) & 1) + (lane >> 4) * 8, cc = t4 * 2 + (lane & 1);
            const uint32_t a = sb + CO_ST + r * 128 + ((cc ^ (r & 7)) << 4);
            bf16* go = g_ctxB + ((size_t)h * SEQ + s * SEGL + r) * HD + (rank & 1) * 64 + cc * 8;
            wgmma_wait<0>();
            store32(aO - CH_TW + CO_ST);
            __syncwarp();
            const uint4 o0 = lds128(a), o1 = lds128(a + 2048);
            *reinterpret_cast<uint4*>(go) = o0;
            *reinterpret_cast<uint4*>(go + 16 * HD) = o1;
            DBG(28, 4);
        };
#pragma unroll 1
        for (int s = 0; s < NSEG; s++) {
            const uint32_t par = s & 1;
            load_wa();
            mem_proj(s, s > 0);
            if (s == NSEG - 1) break;
            if (warp < 5) {
                const uint32_t qa_ = aQ + par * CH_TP, ka = qa_ + warp * 1024;
                asm volatile("bar.sync 1, 256;" ::: "memory");
                const uint4 qa = lds128(qa_ + 4096), k0 = lds128(ka + CH_TW), qb = lds128((qa_ ^ 16) + 4096), k1 = lds128((ka ^ 16) + CH_TW);
                DBGD(52 + warp, warp, qa.x ^ qb.x);
                float c[4] = {0.f, 0.f, 0.f, 0.f}, c2[4] = {0.f, 0.f, 0.f, 0.f};
                mma_16816(c, qa.x, 0u, qa.y, 0u, k0.x, k0.y);
                mma_16816(c2, qb.x, 0u, qb.y, 0u, k1.x, k1.y);
                mma_16816(c, qa.z, 0u, qa.w, 0u, k0.z, k0.w);
                mma_16816(c2, qb.z, 0u, qb.w, 0u, k1.z, k1.w);
                c[0] += c2[0]; c[1] += c2[1];
                DBGD(57 + warp, warp, __float_as_uint(c[0]));
                const uint32_t off = aL + CO_SC + warp * 256;
                st_async_v2(remote(off + 1280, rank ^ 1), __float_as_uint(c[0]), __float_as_uint(c[1]), remote(bar_sc, rank ^ 1));
                st_async_v2(off, __float_as_uint(c[0]), __float_as_uint(c[1]), bar_sc);
                asm volatile("bar.arrive 2, 288;" ::: "memory");
                DBG(3, 0);
            } else {
                asm volatile("bar.arrive 1, 256;" ::: "memory");
            }
            if (wg == 0) {
                if (tid == 96) {
                    mbar_expect_tx(bar_sc, 2 * 1280);
                    mbar_expect_tx(bar_l, 4096);
#pragma unroll
                    for (int j = 0; j < 4; j++) { mbar_expect_tx(bar_mem + 8 * j, 2048); mbar_expect_tx(bar_o + 8 * j, 2048); }
                }
                __syncwarp();
                local_scores(s);
                if (tid == 96 && s > 0 && (s & 3) == 0) signal_ctr_generic(CT_CB + ((s - 1) >> 2) * 2 + (h >= O2_HE));
                __syncwarp();
                mbar_wait(bar_x + 8 * (par ^ 1), ((s + 1) >> 1) & 1);
                float c[4];
                const uint32_t alo = desc_lo(sb + CO_WO, 16), blo = desc_lo(sb + CO_OB, 128);
                uint32_t* wp = g_xbuf + (size_t)rank * 2048 + C * 256 + qc * 64 + t4 * 8 + qd;
#pragma unroll
                for (int g = 0; g < 4; g++) {
                    mbar_wait_cl(bar_o + 8 * g, par);
                    if (g == 0) DBG(16, 0);
                    if (g == 3) DBG(18, 0);
                    fence_async_smem();
                    wgmma_fence();
#pragma unroll
                    for (int i = 0; i < 8; i++) wgmma_ss_n8(c, alo + (g * 8 + i) * 128, blo + (g * 8 + i) * 16, (g | i) != 0);
                    wgmma_commit();
                }
                wgmma_wait<0>();
                asm volatile("st.relaxed.gpu.global.u32 [%0], %1;" :: "l"(wp + (s & 3) * 16384), "r"(~pack_bf16(c[0], c[2])) : "memory");
                asm volatile("st.relaxed.gpu.global.u32 [%0], %1;" :: "l"(wp + (s & 3) * 16384 + 32), "r"(~pack_bf16(c[1], c[3])) : "memory");
                asm volatile("bar.arrive 6, 256;" ::: "memory");
                asm volatile("bar.arrive 4, 256;" ::: "memory");
                DBG(8, 0);
                asm volatile("st.relaxed.gpu.global.u32 [%0], %1;" :: "l"(wp + ((s + 2) & 3) * 16384), "r"(0) : "memory");
                asm volatile("st.relaxed.gpu.global.u32 [%0], %1;" :: "l"(wp + ((s + 2) & 3) * 16384 + 32), "r"(0) : "memory");
                if (tid == 0 && s + 2 < NSEG) {
                    mbar_expect_tx(bar_x + 8 * par, 32768);
                    tma_load_2d_mc(sb + CO_XB + par * 32768 + rank * 4096, &P.mapX, bar_x + 8 * par, rank * 64, (s + 2) * SEGL, (uint16_t)0xff);
                }
                __syncwarp();
                asm volatile("bar.sync 8, 256;" ::: "memory");
            } else {
                const uint32_t vaddr = sb + CO_T + par * CH_TP + 2 * CH_TW + (lane & 15) * 128 + (((t4 * 2 + (lane >> 4)) ^ (lane & 7)) << 4);
                const uint32_t dsta = sb + CO_OB + t4 * 256 + (qc >> 1) * 128 + qd * 16 + (qc & 1) * 8;
                mbar_wait_cl(bar_sc, par);
                DBG(4, 4);
                float v[10];
#pragma unroll
                for (int j = 0; j < 5; j++) {
                    const float2 a = lds64f(aL + CO_SC + j * 256), b = lds64f(aL + CO_SC + 1280 + j * 256);
                    v[2 * j] = a.x + b.x; v[2 * j + 1] = a.y + b.y;
                }
                float mx = fmaxf(fmaxf(fmaxf(v[0], v[1]), fmaxf(v[2], v[3])), fmaxf(fmaxf(v[4], v[5]), fmaxf(v[6], v[7])));
                mx = fmaxf(mx, fmaxf(v[8], v[9]));
                mx = fmaxf(mx, __shfl_xor_sync(0xffffffff, mx, 1));
                mx = fmaxf(mx, __shfl_xor_sync(0xffffffff, mx, 2));
                asm volatile("bar.sync 3, 256;" ::: "memory");
                uint32_t vb[3][4];
#pragma unroll
                for (int k = 0; k < 3; k++) ldmatrix_x4_trans(vb[k][0], vb[k][1], vb[k][2], vb[k][3], vaddr + k * 2048);
                DBG(19, 4);
                mx *= CH_SC;
#pragma unroll
                for (int j = 0; j < 10; j++) v[j] = ex2f(fmaf(v[j], CH_SC, -mx));
                float c0[4] = {0.f, 0.f, 0.f, 0.f}, c1[4] = {0.f, 0.f, 0.f, 0.f}, cs[4] = {0.f, 0.f, 0.f, 0.f};
#pragma unroll
                for (int k = 0; k < 3; k++) {
                    const uint32_t p0 = pack_bf16(v[4 * k], v[4 * k + 1]), p1 = k < 2 ? pack_bf16(v[4 * k + 2], v[4 * k + 3]) : 0u;
                    mma_16816(cs, p0, 0u, p1, 0u, 0x3f803f80u, 0x3f803f80u);
                    mma_16816(c0, p0, 0u, p1, 0u, vb[k][0], vb[k][1]);
                    mma_16816(c1, p0, 0u, p1, 0u, vb[k][2], vb[k][3]);
                }
                float inv;
                asm volatile("rcp.approx.ftz.f32 %0, %1;" : "=f"(inv) : "f"(cs[0]));
                const uint32_t b0 = pack_bf16(c0[0] * inv, c0[1] * inv), b1 = pack_bf16(c1[0] * inv, c1[1] * inv);
                DBG(20, 4);
#pragma unroll
                for (int i = 0; i < 8; i++) {
                    const int dr = (rank + i) & 7;
                    st_async_v2(remote(dsta + i * 1024, dr), b0, b1, remote(bar_o + 8 * (i >> 1), dr));
                    if (i == 0) asm volatile("bar.arrive 7, 256;" ::: "memory");
                }
                DBG(5, 4);
                local_softmax(s);
                mbar_wait(bar_x + 8 * (par ^ 1), ((s + 1) >> 1) & 1);
                asm volatile("bar.sync 4, 256;" ::: "memory");
                local_pv(s);
                asm volatile("bar.sync 9, 256;" ::: "memory");
            }
            pass32(par ^ 1);
            DBG(21, 0);
            wgmma_wait<0>();
            store32(aO + (par ^ 1) * CH_TP + CO_T);
            DBG(22, 0);
        }
        asm volatile("bar.sync 1, 256;" ::: "memory");
        if (warp < 5) asm volatile("bar.arrive 2, 288;" ::: "memory");
        if (wg == 0) {
            if (tid == 96) mbar_expect_tx(bar_l, 4096);
            __syncwarp();
            local_scores(NSEG - 1);
            uint32_t* wp = g_xbuf + 16384 + (size_t)rank * 2048 + C * 256 + tid * 2;
            *reinterpret_cast<uint2*>(wp) = make_uint2(0u, 0u);
        } else {
            local_softmax(NSEG - 1);
            asm volatile("bar.sync 3, 256;" ::: "memory");
            fence_async_smem();
            local_pv(NSEG - 1);
            asm volatile("bar.sync 5, 128;" ::: "memory");
            if (tid == 128) signal_ctr_generic(CT_CB + 15 * 2 + (h >= O2_HE));
        }
    } else {
#pragma unroll 1
        for (int s = 0; s < NSEG; s++) {
            const uint32_t par = s & 1;
            load_wa();
            asm volatile("bar.sync 2, 288;" ::: "memory");
            mem_proj(s, false);
            asm volatile("bar.arrive 3, 256;" ::: "memory");
            DBG(24, 8);
            if (s == NSEG - 1) break;
            mbar_wait(bar_x + 8 * (par ^ 1), ((s + 1) >> 1) & 1);
            asm volatile("bar.sync 7, 256;" ::: "memory");
            if (CH_VSPLIT > 0) pass32(par ^ 1, 0, CH_VSPLIT);
            DBG(26, 8);
            asm volatile("bar.sync 6, 256;" ::: "memory");
            pass32(par ^ 1, CH_VSPLIT, 32);
            asm volatile("bar.arrive 8, 256;" ::: "memory");
            asm volatile("bar.arrive 9, 256;" ::: "memory");
            DBG(25, 8);
            wgmma_wait<0>();
            store32(aO + (par ^ 1) * CH_TP + CO_T);
            DBG(27, 8);
            pace(CH_POLL_DELAY);
            auto lo = [](uint32_t u) { return __uint_as_float(~u << 16); };
            auto hi = [](uint32_t u) { return __uint_as_float(~u & 0xffff0000u); };
            const uint4* xb = reinterpret_cast<const uint4*>(g_xbuf + (s & 3) * 16384 + (size_t)rank * 2048 + (lane >> 4) * 1024 + t4 * 64) + (lane & 15);
            uint4 p[4];
#pragma unroll
            for (int k = 0; k < 4; k++)
                asm volatile("ld.relaxed.gpu.global.v4.u32 {%0, %1, %2, %3}, [%4];" : "=r"(p[k].x), "=r"(p[k].y), "=r"(p[k].z), "=r"(p[k].w) : "l"(xb + k * 64) : "memory");
            for (int it = 0; it < WAIT_LIMIT / 4; it++) {
                uint32_t bad = 0;
#pragma unroll
                for (int k = 0; k < 4; k++) bad |= (min(min(p[k].x, p[k].y), min(p[k].z, p[k].w)) == 0u ? 1u : 0u) << k;
                if (__all_sync(0xffffffff, bad == 0u)) break;
#pragma unroll
                for (int k = 0; k < 4; k++)
                    if (bad & (1u << k))
                        asm volatile("ld.relaxed.gpu.global.v4.u32 {%0, %1, %2, %3}, [%4];" : "=r"(p[k].x), "=r"(p[k].y), "=r"(p[k].z), "=r"(p[k].w) : "l"(xb + k * 64) : "memory");
            }
            DBG(9, 8);
            auto sum2 = [&](uint32_t a, uint32_t b, uint32_t c, uint32_t e) {
                float r0 = (lo(a) + lo(b)) + (lo(c) + lo(e)), r1 = (hi(a) + hi(b)) + (hi(c) + hi(e));
                r0 += __shfl_xor_sync(0xffffffff, r0, 16); r1 += __shfl_xor_sync(0xffffffff, r1, 16);
                return pack_bf16(r0, r1);
            };
            const uint32_t m0 = sum2(p[0].x, p[1].x, p[2].x, p[3].x), m1 = sum2(p[0].y, p[1].y, p[2].y, p[3].y);
            const uint32_t m2 = sum2(p[0].z, p[1].z, p[2].z, p[3].z), m3 = sum2(p[0].w, p[1].w, p[2].w, p[3].w);
            const int row = t4 * 2 + ((lane >> 3) & 1);
            const uint32_t dsta = sb + CO_MB + (lane >> 4) * 1024 + row * 128 + (((lane & 7) ^ row) << 4);
#pragma unroll
            for (int i = 0; i < 4; i++) {
                const int dr = (rank + (lane >> 4) * 4 + i) & 7;
                st_async_v4(remote(dsta + i * 2048, dr), m0, m1, m2, m3, remote(bar_mem + 8 * i, dr));
            }
            DBG(10, 8);
        }
    }
    __syncthreads();
    cluster_sync_all();
    TS_END(2);
}

struct Proj2Params {
    CUtensorMap mapA[2];
    CUtensorMap mapW[3];
    bf16* out[3];
};
#define P2T(i)
#define P2_NOMMA 0
#define P2_NOLOAD 0
constexpr int P2_STAGES = 6;
constexpr int P2_SMEM = 131072 + P2_STAGES * 16384 + 1024 + 1024;
constexpr int P2_ITEMS = 168 + 48;

__device__ __forceinline__ int p2_reps(int t) { return t >= 168 ? 1 : 2; }
__device__ __forceinline__ void p2_tile(int t, int w, int& z, int& mp, int& head) {
    if (t >= 168) { w += ((t - 168) & 1) * 2; t = 168 + ((t - 168) >> 1); }
    const int hq = t / 24, v = t % 24;
    mp = v & 7;
    if (v < 16) { head = hq * 4 + (v >> 3) * 2 + (w >> 1); z = 1 + (w & 1); }
    else { head = hq * 4 + w; z = 0; }
}
__device__ __forceinline__ void mbar_arrive_remote(uint32_t bar_cluster_addr) {
    asm volatile("mbarrier.arrive.release.cluster.shared::cluster.b64 _, [%0];" :: "r"(bar_cluster_addr) : "memory");
}
__device__ __forceinline__ void mbar_arrive_cl(uint32_t bar_cluster_addr) {
    asm volatile("mbarrier.arrive.shared::cluster.b64 _, [%0];" :: "r"(bar_cluster_addr) : "memory");
}
__device__ __forceinline__ void mbar_wait_acq_cluster(uint32_t bar, uint32_t parity) {
    asm volatile(
        "{\n"
        ".reg .pred p, q;\n"
        ".reg .u32 c;\n"
        "mov.u32 c, 0;\n"
        "WAIT_LOOP_C:\n"
        "mbarrier.try_wait.parity.acquire.cluster.shared::cta.b64 p, [%0], %1;\n"
        "@p bra WAIT_DONE_C;\n"
        "add.u32 c, c, 1;\n"
        "setp.lt.u32 q, c, 4000000;\n"
        "@q bra WAIT_LOOP_C;\n"
        "WAIT_DONE_C:\n"
        "}\n" :: "r"(bar), "r"(parity) : "memory");
}
__device__ __forceinline__ uint4 quad_transpose(uint32_t p0, uint32_t p1, uint32_t p2, uint32_t p3, int lane) {
    const bool o1 = lane & 1, o2 = lane & 2;
    uint32_t s0 = o1 ? p0 : p1, s1 = o1 ? p2 : p3;
    s0 = __shfl_xor_sync(0xffffffff, s0, 1); s1 = __shfl_xor_sync(0xffffffff, s1, 1);
    const uint32_t a_lo = o1 ? s0 : p0, a_hi = o1 ? p1 : s0, b_lo = o1 ? s1 : p2, b_hi = o1 ? p3 : s1;
    uint32_t t0 = o2 ? a_lo : b_lo, t1 = o2 ? a_hi : b_hi;
    t0 = __shfl_xor_sync(0xffffffff, t0, 2); t1 = __shfl_xor_sync(0xffffffff, t1, 2);
    return o2 ? make_uint4(t0, t1, b_lo, b_hi) : make_uint4(a_lo, a_hi, t0, t1);
}
#define P2_PACE 35
#define P2_PACE2 0
template <bool PERM, int PACE = 0>
__device__ __forceinline__ void store_frag_128(const float (&acc)[64], bf16* obase, int lane) {
#pragma unroll
    for (int rr = 0; rr < 2; rr++)
#pragma unroll
        for (int g = 0; g < 4; g++) {
            const float* a = &acc[g * 16 + rr * 2];
            const uint32_t p0 = pack_bf16(a[0], a[1]), p1 = pack_bf16(a[4], a[5]), p2 = pack_bf16(a[8], a[9]), p3 = pack_bf16(a[12], a[13]);
            *reinterpret_cast<uint4*>(obase + (size_t)(rr * 8) * HD + g * 32) = PERM ? make_uint4(p0, p1, p2, p3) : quad_transpose(p0, p1, p2, p3, lane);
            pace(PACE);
        }
}
__global__ void __cluster_dims__(2, 1, 1) __launch_bounds__(384, 1) proj2_kernel(const __grid_constant__ Proj2Params P) {
    extern __shared__ uint8_t smem_raw[];
    const uint32_t sbase = (smem_u32(smem_raw) + 1023) & ~1023u;
    const uint32_t sA = sbase, sB = sbase + 131072, sC = sB + P2_STAGES * 16384;
    const uint32_t bars = sC;
    const uint32_t a_full = bars, a_empty = bars + 64, b_full = bars + 128, b_empty = b_full + 8 * P2_STAGES;
    const uint32_t item_bar = b_empty + 8 * P2_STAGES, item_in = item_bar + 16, slot = item_in + 16;
    const uint32_t note_bar = slot + 16, note_free = note_bar + 64, note = note_free + 64;
    const int warp = threadIdx.x >> 5, lane = threadIdx.x & 31;
    const uint32_t rank = cluster_ctarank();
    TS_BEGIN(0);
    if (threadIdx.x == 0) {
        for (int i = 0; i < 8; i++) { mbar_init(a_full + 8 * i, 1); mbar_init(a_empty + 8 * i, 2); }
        for (int i = 0; i < P2_STAGES; i++) { mbar_init(b_full + 8 * i, 1); mbar_init(b_empty + 8 * i, 2); }
        mbar_init(item_bar, 1); mbar_init(item_bar + 8, 1); mbar_init(item_in, 2); mbar_init(item_in + 8, 2);
        for (int i = 0; i < 8; i++) { mbar_init(note_bar + 8 * i, 1); mbar_init(note_free + 8 * i, 1); }
        asm volatile("fence.mbarrier_init.release.cluster;" ::: "memory");
    }
    __syncthreads();
    cluster_sync_all();
    pdl_launch_dependents();
    if (warp == 9) {
        if (lane == 0) {
            for (int n = 0;; n++) {
                const int e = (n & 1) * 4 + ((n >> 1) & 3);
                mbar_wait(note_bar + 8 * e, (n >> 3) & 1);
                int m;
                asm volatile("ld.shared.s32 %0, [%1];" : "=r"(m) : "r"(note + e * 4) : "memory");
                mbar_arrive(note_free + 8 * e);
                if (m < 0) break;
                signal_ctr(m);
            }
        }
    } else if (warp == 10) {
        if (lane == 0) {
            auto publish = [&](int ic, int tq) {
                const int t = tq < P2_ITEMS ? tq : -1;
                asm volatile("st.shared.s32 [%0], %1;" :: "r"(slot + (ic & 3) * 4), "r"(t) : "memory");
                mbar_arrive(item_bar + 8 * (ic & 1));
                st_async_b32(mapa_u32(slot + (ic & 3) * 4, 1), (uint32_t)t, mapa_u32(item_bar + 8 * (ic & 1), 1));
            };
            const int npair = (int)(gridDim.x >> 1), pair = (int)(blockIdx.x >> 1);
            if (rank == 0) publish(0, pair);
            for (int ic = 0;; ic++) {
                if (rank == 1) mbar_expect_tx(item_bar + 8 * (ic & 1), 4);
                mbar_wait(item_bar + 8 * (ic & 1), (ic >> 1) & 1);
                int t;
                asm volatile("ld.shared.s32 %0, [%1];" : "=r"(t) : "r"(slot + (ic & 3) * 4) : "memory");
                if (t < 0) break;
                int z0, mp, h0;
                p2_tile(t, 0, z0, mp, h0);
                const int aidx = z0 >= 1 ? 1 : 0;
                const int m0 = (2 * mp + (int)rank) * 128;
                for (int k = 0; k < 8; k++) {
                    mbar_wait(a_empty + 8 * k, (ic & 1) ^ 1);
                    if (P2_NOLOAD) mbar_arrive(a_full + 8 * k); else {
                    mbar_expect_tx(a_full + 8 * k, 16384);
                    tma_load_2d(sA + k * 16384, &P.mapA[aidx], a_full + 8 * k, k * 64, m0); }
                }
                if (rank == 0) {
                    mbar_wait(item_in + 8 * (ic & 1), (ic >> 1) & 1);
                    publish(ic + 1, ic == 0 ? npair + pair : 2 * npair + (int)atomicAdd(&g_ctr[CT_PROJ], 1u));
                }
            }
        }
    } else if (warp == 8 || warp == 11) {
        if (lane == 0) {
            const int par2 = warp == 8 ? 0 : 1;
            int it = 0; uint32_t bph = 0;
            for (int ic = 0;; ic++) {
                mbar_wait(item_bar + 8 * (ic & 1), (ic >> 1) & 1);
                int t;
                asm volatile("ld.shared.s32 %0, [%1];" : "=r"(t) : "r"(slot + (ic & 3) * 4) : "memory");
                if (t < 0) break;
                const int nt = 2 * p2_reps(t);
                for (int w = 0; w < nt; w++) {
                    int z, mp, hd;
                    p2_tile(t, w, z, mp, hd);
                    for (int k = 0; k < 8; k++) {
                        const int s = it; const uint32_t phb = bph;
                        if (++it == P2_STAGES) { it = 0; bph ^= 1; }
                        if ((k & 1) != par2) continue;
                        mbar_wait(b_empty + 8 * s, phb ^ 1);
                        if (P2_NOLOAD) { mbar_arrive(b_full + 8 * s); continue; }
                        mbar_expect_tx(b_full + 8 * s, 16384);
                        tma_load_2d_mc(sB + s * 16384 + rank * 8192, &P.mapW[z], b_full + 8 * s, hd * 128 + (int)rank * 64, k * 64, (uint16_t)3);
                    }
                }
            }
        }
    } else {
        const int wg = warp >> 2;
        float acc[2][64];
        const uint32_t a_lo = desc_lo(sA, 16), b_lo0 = desc_lo(sB, 8192);
        const bool elected = (threadIdx.x & 127) == 0;
        int s = (wg * 8) % P2_STAGES;
        uint32_t ph = ((wg * 8) / P2_STAGES) & 1;
        int nnote = 0;
        if (wg == 1) asm volatile("bar.arrive 3, 256;" ::: "memory");
        for (int ic = 0;; ic++) {
            mbar_wait(item_bar + 8 * (ic & 1), (ic >> 1) & 1);
            int t;
            asm volatile("ld.shared.s32 %0, [%1];" : "=r"(t) : "r"(slot + (ic & 3) * 4) : "memory");
            P2T(7);
            if (wg == 0 && t < 0) {
                if (elected) {
                    const int e = nnote & 3;
                    mbar_wait(note_free + 8 * e, ((nnote >> 2) & 1) ^ 1);
                    asm volatile("st.shared.s32 [%0], %1;" :: "r"(note + e * 4), "r"(-1) : "memory");
                    mbar_arrive(note_bar + 8 * e);
                }
            }
            if (t < 0) break;
            const int reps = p2_reps(t);
#pragma unroll 1
            for (int rp = 0; rp < reps; rp++) {
            const bool first = rp == 0, last = rp == reps - 1;
            int z, mp, head;
            p2_tile(t, rp * 2 + wg, z, mp, head);
            asm volatile("bar.sync %0, 256;" :: "r"(3 + wg) : "memory");
            P2T(0);
            if (wg == 1 && last && elected) mbar_arrive_cl(mapa_u32(item_in + 8 * (ic & 1), 0));
            int sprev = 0;
#pragma unroll
            for (int k = 0; k < 8; k++) {
                if (k == 0) P2T(5);
                if (wg == 0 && first) mbar_wait(a_full + 8 * k, ic & 1);
                if (k == 0) P2T(6);
                mbar_wait(b_full + 8 * s, ph);
                if (k == 7) asm volatile("bar.arrive %0, 256;" :: "r"(4 - wg) : "memory");
                if (k == 0) P2T(1);
                if (k == 7) P2T(2);
                const uint32_t b_lo = b_lo0 + s * 1024;
                wgmma_fence();
#pragma unroll
                for (int kk = 0; kk < (P2_NOMMA ? 1 : 4); kk++) {
                    wgmma_ss_n128_lo<1>(acc[0], a_lo + k * 1024 + kk * 2, b_lo + kk * 128, (k | kk) != 0);
                    wgmma_ss_n128_lo<1>(acc[1], a_lo + k * 1024 + 512 + kk * 2, b_lo + kk * 128, (k | kk) != 0);
                }
                wgmma_commit();
                if (k > 0) {
                    wgmma_wait<1>();
                    if (elected) {
                        const uint32_t e = b_empty + 8 * sprev;
                        mbar_arrive_cl(mapa_u32(e, 0)); mbar_arrive_cl(mapa_u32(e, 1));
                        if (last) mbar_arrive(a_empty + 8 * (k - 1));
                    }
                }
                sprev = s;
                if (++s == P2_STAGES) { s = 0; ph ^= 1; }
            }
            wgmma_wait<0>();
            P2T(3);
            if (elected) {
                const uint32_t e = b_empty + 8 * sprev;
                mbar_arrive_cl(mapa_u32(e, 0)); mbar_arrive_cl(mapa_u32(e, 1));
                if (last) mbar_arrive(a_empty + 8 * 7);
            }
            s += 8 % P2_STAGES; ph ^= (8 / P2_STAGES) & 1;
            if (s >= P2_STAGES) { s -= P2_STAGES; ph ^= 1; }
            const int m0 = (2 * mp + (int)rank) * 128;
            bf16* obase = P.out[z] + ((size_t)head * SEQ + m0 + (warp & 3) * 16 + (lane >> 2)) * HD + (lane & 3) * 8;
            store_frag_128<true, P2_PACE>(acc[0], obase, lane); store_frag_128<true, P2_PACE>(acc[1], obase + (size_t)64 * HD, lane);
            P2T(4);
            {
                asm volatile("bar.sync %0, 128;" :: "r"(1 + wg) : "memory");
                if (elected) {
                    const int e = wg * 4 + (nnote & 3);
                    mbar_wait(note_free + 8 * e, ((nnote >> 2) & 1) ^ 1);
                    asm volatile("st.shared.s32 [%0], %1;" :: "r"(note + e * 4), "r"(CT_AP + (head >> 1)) : "memory");
                    mbar_arrive(note_bar + 8 * e);
                }
                nnote++;
            }
            }
        }
        TS_END(0);
    }
    __syncthreads();
    cluster_sync_all();
}

struct OutParams {
    CUtensorMap mapCtx[2];
    CUtensorMap mapWo[2];
    CUtensorMap mapPart;
};
__device__ float g_part[4 * SEQ * DM];

#define OT(i)
constexpr int O2_STAGES = 4;
constexpr int O2_SMEM = O2_STAGES * 49152 + 1024 + 256;

__global__ void __cluster_dims__(2, 1, 1) __launch_bounds__(352, 1)
out2_kernel(const __grid_constant__ OutParams P, const bf16* __restrict__ x, const bf16* __restrict__ gate_w, bf16* __restrict__ out) {
    extern __shared__ uint8_t smem_raw[];
    const uint32_t sbase = (smem_u32(smem_raw) + 1023) & ~1023u;
    const uint32_t bar_full = sbase + O2_STAGES * 49152, bar_empty = bar_full + 8 * O2_STAGES;
    __shared__ float s_gate[32];
    const int warp = threadIdx.x >> 5, lane = threadIdx.x & 31;
    const uint32_t rank = cluster_ctarank();
    const int cid = blockIdx.x >> 1;
    const int late = cid >> 5, mp = (cid >> 1) & 7, nh = cid & 1;
    const int b = late ? 1 - ((cid >> 4) & 1) : (cid >> 4) & 1, kq = b * 2 + late;
    const int h0 = late ? O2_HE : 0;
    const int KT = late ? 2 * (NH - O2_HE) : 2 * O2_HE;
    const int m0 = (2 * mp + (int)rank) * 128, n0 = nh * 256;
    TS_BEGIN(4);
    OT(0);
    if (threadIdx.x == 0) {
        for (int i = 0; i < O2_STAGES; i++) { mbar_init(bar_full + 8 * i, 1); mbar_init(bar_empty + 8 * i, 4); }
        asm volatile("fence.mbarrier_init.release.cluster;" ::: "memory");
    }
    __syncthreads();
    asm volatile("barrier.cluster.arrive.release.aligned;" ::: "memory");
    if (threadIdx.x == 256) wait_ctr((b == 0 ? CT_CA : CT_CB) + (m0 >> 7) * 2 + late, (unsigned)KT);
    __syncwarp();
    asm volatile("barrier.cluster.wait.acquire.aligned;" ::: "memory");
    if (warp >= 8) {
        if (lane == 0) {
            int s = 0; uint32_t ph = 0;
            for (int i = 0; i < KT; i++) {
                mbar_wait(bar_empty + 8 * s, ph ^ 1);
                const uint32_t sa = sbase + s * 49152;
                const int head = h0 + (i >> 1), dk = (i & 1) * 64;
                if (warp == 8) {
                    mbar_expect_tx(bar_full + 8 * s, 49152);
                    tma_load_2d(sa, &P.mapCtx[b], bar_full + 8 * s, dk, head * SEQ + m0);
                } else {
                    const int j = (int)rank * 2 + (warp - 9);
                    tma_load_2d_mc(sa + 16384 + j * 8192, &P.mapWo[b], bar_full + 8 * s, n0 + j * 64, head * HD + dk, (uint16_t)3);
                }
                if (++s == O2_STAGES) { s = 0; ph ^= 1; }
            }
        }
    } else {
        const int wg = warp >> 2;
        const bool elected = (threadIdx.x & 127) == 0;
        float acc[128];
        {
            const int r = m0 + kq * 32 + (threadIdx.x >> 3);
            float sum = 0.f;
#pragma unroll
            for (int c = 0; c < 8; c++) {
                const int col = c * 64 + (threadIdx.x & 7) * 8;
                const uint4 xv = __ldg(reinterpret_cast<const uint4*>(x + (size_t)r * DM + col));
                const uint4 gv = __ldg(reinterpret_cast<const uint4*>(gate_w + col));
                const bf16* xp = reinterpret_cast<const bf16*>(&xv);
                const bf16* gp = reinterpret_cast<const bf16*>(&gv);
#pragma unroll
                for (int e = 0; e < 8; e++)
                    sum += __bfloat162float(__float2bfloat16(__bfloat162float(xp[e]) * __bfloat162float(gp[e])));
            }
            sum += __shfl_xor_sync(0xffffffff, sum, 1);
            sum += __shfl_xor_sync(0xffffffff, sum, 2);
            sum += __shfl_xor_sync(0xffffffff, sum, 4);
            sum = __bfloat162float(__float2bfloat16(sum));
            if ((threadIdx.x & 7) == 0) s_gate[threadIdx.x >> 3] = __bfloat162float(__float2bfloat16(1.f / (1.f + __expf(-sum))));
        }
        int s = 0, sprev = 0; uint32_t ph = 0;
#pragma unroll 1
        for (int i = 0; i < KT; i++) {
            mbar_wait(bar_full + 8 * s, ph);
            if (i == 0) OT(1);
            if (i == 8) OT(2);
            const uint32_t sa = sbase + s * 49152 + wg * 8192, sb = sbase + s * 49152 + 16384;
            wgmma_fence();
#pragma unroll
            for (int kk = 0; kk < 4; kk++)
                wgmma_ss_n256_tb(acc, make_desc(sa + kk * 32, 16, 1024), make_desc(sb + kk * 2048, 8192, 1024), (i | kk) != 0);
            wgmma_commit();
            if (i > 0) {
                wgmma_wait<1>();
                if (elected) { const uint32_t e = bar_empty + 8 * sprev; mbar_arrive_cl(mapa_u32(e, 0)); mbar_arrive_cl(mapa_u32(e, 1)); }
            }
            sprev = s;
            if (++s == O2_STAGES) { s = 0; ph ^= 1; }
        }
        wgmma_wait<0>();
        OT(3);
        {
            const int r = wg * 64 + (warp & 3) * 16 + (lane >> 2);
            if ((warp >> 1) == kq) {
#pragma unroll
                for (int j = 0; j < 32; j++) {
                    const uint32_t a = sbase + (j >> 2) * 16384 + r * 128 + ((((j & 3) * 2 + ((lane & 3) >> 1)) ^ (r & 7)) << 4) + (lane & 1) * 8;
                    asm volatile("st.shared.v2.f32 [%0], {%1, %2};" :: "r"(a), "f"(acc[j * 4 + 0]), "f"(acc[j * 4 + 1]) : "memory");
                    asm volatile("st.shared.v2.f32 [%0], {%1, %2};" :: "r"(a + 1024), "f"(acc[j * 4 + 2]), "f"(acc[j * 4 + 3]) : "memory");
                }
            } else {
                float* pp = g_part + ((size_t)kq * SEQ + m0 + r) * DM + n0 + (lane & 3) * 2;
#pragma unroll
                for (int j = 0; j < 32; j++) {
                    *reinterpret_cast<float2*>(pp + j * 8) = make_float2(acc[j * 4 + 0], acc[j * 4 + 1]);
                    *reinterpret_cast<float2*>(pp + 8 * DM + j * 8) = make_float2(acc[j * 4 + 2], acc[j * 4 + 3]);
                }
            }
        }
        asm volatile("bar.sync 1, 256;" ::: "memory");
        OT(4);
        unsigned int* ctr = &g_ctr[CT_OP + (2 * mp + (int)rank) * 2 + nh];
        if (threadIdx.x == 0) {
            asm volatile("fence.proxy.async;" ::: "memory");
            __threadfence();
            atomicAdd(ctr, 1u);
            unsigned int v; int it = 0;
            do { asm volatile("ld.acquire.gpu.global.u32 %0, [%1];" : "=r"(v) : "l"(ctr) : "memory"); } while (v < 4u && ++it < WAIT_LIMIT);
        }
        asm volatile("bar.sync 1, 256;" ::: "memory");
        OT(5);
        {
            const int c8 = threadIdx.x & 31, r0 = threadIdx.x >> 5;
            float4 u[4][3][2];
#pragma unroll
            for (int i = 0; i < 4; i++)
#pragma unroll
                for (int q = 1; q < 4; q++) {
                    const float4* p4 = reinterpret_cast<const float4*>(g_part + ((size_t)((kq + q) & 3) * SEQ + m0 + kq * 32 + r0 + i * 8) * DM + n0 + c8 * 8);
                    asm volatile("ld.relaxed.gpu.global.v4.f32 {%0, %1, %2, %3}, [%4];"
                                 : "=f"(u[i][q - 1][0].x), "=f"(u[i][q - 1][0].y), "=f"(u[i][q - 1][0].z), "=f"(u[i][q - 1][0].w) : "l"(p4) : "memory");
                    asm volatile("ld.relaxed.gpu.global.v4.f32 {%0, %1, %2, %3}, [%4];"
                                 : "=f"(u[i][q - 1][1].x), "=f"(u[i][q - 1][1].y), "=f"(u[i][q - 1][1].z), "=f"(u[i][q - 1][1].w) : "l"(p4 + 1) : "memory");
                }
#pragma unroll
            for (int i = 0; i < 4; i++) {
                const int rl = kq * 32 + r0 + i * 8;
                const float ga = s_gate[r0 + i * 8], gb = 1.f - ga;
                float o8[8];
#pragma unroll
                for (int hf = 0; hf < 2; hf++) {
                    float4 own;
                    const uint32_t a = sbase + (c8 >> 2) * 16384 + rl * 128 + ((((c8 & 3) * 2 + hf) ^ (rl & 7)) << 4);
                    asm volatile("ld.shared.v4.f32 {%0, %1, %2, %3}, [%4];" : "=f"(own.x), "=f"(own.y), "=f"(own.z), "=f"(own.w) : "r"(a) : "memory");
                    const int qp = ((kq ^ 1) - kq) & 3;
                    const float4 pa = qp == 1 ? u[i][0][hf] : u[i][2][hf];
                    const float4 o1 = u[i][1][hf];
                    const float4 o2 = qp == 1 ? u[i][2][hf] : u[i][0][hf];
                    const float gm = b == 0 ? ga : gb, go = b == 0 ? gb : ga;
                    o8[hf * 4 + 0] = gm * (own.x + pa.x) + go * (o1.x + o2.x);
                    o8[hf * 4 + 1] = gm * (own.y + pa.y) + go * (o1.y + o2.y);
                    o8[hf * 4 + 2] = gm * (own.z + pa.z) + go * (o1.z + o2.z);
                    o8[hf * 4 + 3] = gm * (own.w + pa.w) + go * (o1.w + o2.w);
                }
                *reinterpret_cast<uint4*>(out + (size_t)(m0 + rl) * DM + n0 + c8 * 8) =
                    make_uint4(pack_bf16(o8[0], o8[1]), pack_bf16(o8[2], o8[3]), pack_bf16(o8[4], o8[5]), pack_bf16(o8[6], o8[7]));
            }
        }
        OT(6);
        if (threadIdx.x == 0) {
            const unsigned int tk = atomicAdd(&g_ctr[CT_FIN], 1u);
            asm volatile("st.shared.u32 [%0], %1;" :: "r"(bar_empty + 8 * O2_STAGES), "r"(tk) : "memory");
        }
        asm volatile("bar.sync 1, 256;" ::: "memory");
        unsigned int tk;
        asm volatile("ld.shared.u32 %0, [%1];" : "=r"(tk) : "r"(bar_empty + 8 * O2_STAGES) : "memory");
        if (tk == gridDim.x - 1 && threadIdx.x < CT_N) g_ctr[threadIdx.x] = 0u;
    }
    __syncthreads();
    cluster_sync_all();
    TS_END(4);
}

typedef CUresult (*PFN_encodeTiled)(CUtensorMap*, CUtensorMapDataType, cuuint32_t, void*, const cuuint64_t*,
                                    const cuuint64_t*, const cuuint32_t*, const cuuint32_t*, CUtensorMapInterleave,
                                    CUtensorMapSwizzle, CUtensorMapL2promotion, CUtensorMapFloatOOBfill);
static PFN_encodeTiled g_encode = nullptr;

static void make_map(CUtensorMap* m, const void* ptr, uint64_t rows, uint64_t cols, uint32_t box_rows, bool sw64 = false) {
    cuuint64_t dims[2] = {cols, rows};
    cuuint64_t strides[1] = {cols * 2};
    cuuint32_t box[2] = {sw64 ? 32u : 64u, box_rows};
    cuuint32_t es[2] = {1, 1};
    g_encode(m, CU_TENSOR_MAP_DATA_TYPE_BFLOAT16, 2, const_cast<void*>(ptr), dims, strides, box, es,
             CU_TENSOR_MAP_INTERLEAVE_NONE, sw64 ? CU_TENSOR_MAP_SWIZZLE_64B : CU_TENSOR_MAP_SWIZZLE_128B, CU_TENSOR_MAP_L2_PROMOTION_L2_256B,
             CU_TENSOR_MAP_FLOAT_OOB_FILL_NONE);
}

template <typename... KArgs, typename... Args>
static void launch_pdl(void (*kernel)(KArgs...), int grid, int block, size_t smem, cudaStream_t st, bool pdl, Args... args) {
    cudaLaunchConfig_t cfg = {};
    cfg.gridDim = dim3(grid); cfg.blockDim = dim3(block); cfg.dynamicSmemBytes = smem; cfg.stream = st;
    cudaLaunchAttribute at[1];
    at[0].id = cudaLaunchAttributeProgrammaticStreamSerialization;
    at[0].val.programmaticStreamSerializationAllowed = 1;
    cfg.attrs = at; cfg.numAttrs = pdl ? 1 : 0;
    cudaLaunchKernelEx(&cfg, kernel, KArgs(args)...);
}

extern "C" void kernel_launch(void* const* d_in, const int* in_sizes, int n_in, void* d_out, int out_size) {
    const bf16* x = (const bf16*)d_in[0];
    const bf16* ckv = (const bf16*)d_in[1];
    const bf16* wq = (const bf16*)d_in[2];
    const bf16* wuk = (const bf16*)d_in[3];
    const bf16* wuv = (const bf16*)d_in[4];
    const bf16* wo = (const bf16*)d_in[5];
    const bf16* mem0 = (const bf16*)d_in[7];
    const bf16* Wq = (const bf16*)d_in[8];
    const bf16* Wk = (const bf16*)d_in[9];
    const bf16* Wv = (const bf16*)d_in[10];
    const bf16* Wo = (const bf16*)d_in[11];
    const bf16* gate_w = (const bf16*)d_in[13];
    bf16* out = (bf16*)d_out;

    static Proj2Params P2;
    static ChainParams CP;
    static AttnParams AP;
    static OutParams OP;
    static bool init = false;
    static const void* last_in[14];
    bool same = init;
    for (int i = 0; i < 14 && same; i++) same = last_in[i] == d_in[i];
    if (!init) {
        cudaDriverEntryPointQueryResult qr;
        cudaGetDriverEntryPoint("cuTensorMapEncodeTiled", (void**)&g_encode, cudaEnableDefault, &qr);
        cudaFuncSetAttribute(proj2_kernel, cudaFuncAttributeMaxDynamicSharedMemorySize, P2_SMEM);
        cudaFuncSetAttribute(attn_kernel, cudaFuncAttributeMaxDynamicSharedMemorySize, FA_SMEM);
        cudaFuncSetAttribute(chain_kernel, cudaFuncAttributeMaxDynamicSharedMemorySize, CH_SMEM);
        cudaFuncSetAttribute(out2_kernel, cudaFuncAttributeMaxDynamicSharedMemorySize, O2_SMEM);
        init = true;
    }
    if (!same) {
        for (int i = 0; i < 14; i++) last_in[i] = d_in[i];
        void *pQA, *pKA, *pVA, *pCA, *pCB;
        cudaGetSymbolAddress(&pQA, g_QA); cudaGetSymbolAddress(&pKA, g_KA); cudaGetSymbolAddress(&pVA, g_VA);
        cudaGetSymbolAddress(&pCA, g_ctxA); cudaGetSymbolAddress(&pCB, g_ctxB);
        make_map(&P2.mapA[0], x, SEQ, DM, 128);
        make_map(&P2.mapA[1], ckv, SEQ, DM, 128);
        const void* ws[3] = {wq, wuk, wuv};
        void* cs[3] = {pQA, pKA, pVA};
        for (int i = 0; i < 3; i++) { make_map(&P2.mapW[i], ws[i], DM, NQ, 64); P2.out[i] = (bf16*)cs[i]; }
        make_map(&CP.mapW[0], Wq, DM, NQ, 64); make_map(&CP.mapW[1], Wk, DM, NQ, 64); make_map(&CP.mapW[2], Wv, DM, NQ, 64);
        make_map(&CP.mapX, x, SEQ, DM, 32);
        make_map(&AP.mapQ, pQA, NH * SEQ, HD, 128);
        make_map(&AP.mapK, pKA, NH * SEQ, HD, 128);
        make_map(&AP.mapV, pVA, NH * SEQ, HD, 128);
        make_map(&AP.mapO, pCA, NH * SEQ, HD, 64);
        make_map(&OP.mapCtx[0], pCA, NH * SEQ, HD, 128);
        make_map(&OP.mapCtx[1], pCB, NH * SEQ, HD, 128);
        make_map(&OP.mapWo[0], wo, NQ, DM, 64);
        make_map(&OP.mapWo[1], Wo, NQ, DM, 64);
        {
            void* pP; cudaGetSymbolAddress(&pP, g_part);
            cuuint64_t dims[2] = {DM, 4 * SEQ}; cuuint64_t strides[1] = {DM * 4}; cuuint32_t box[2] = {32, 32}; cuuint32_t es[2] = {1, 1};
            g_encode(&OP.mapPart, CU_TENSOR_MAP_DATA_TYPE_FLOAT32, 2, pP, dims, strides, box, es, CU_TENSOR_MAP_INTERLEAVE_NONE,
                     CU_TENSOR_MAP_SWIZZLE_128B, CU_TENSOR_MAP_L2_PROMOTION_NONE, CU_TENSOR_MAP_FLOAT_OOB_FILL_NONE);
        }
    }
    cudaStream_t s1 = cudaStreamPerThread;
    const bool pdl = true;
    launch_pdl(chain_kernel, 64, CH_BLOCK, CH_SMEM, s1, false, CP, mem0, Wo, x);
    launch_pdl(proj2_kernel, 68, 384, P2_SMEM, s1, pdl, P2);
    launch_pdl(attn_kernel, FA_GRID, 384, FA_SMEM, s1, pdl, AP, 1000);
    launch_pdl(out2_kernel, 128, 352, O2_SMEM, s1, pdl, OP, x, gate_w, out);
}
```

```cpp
#include <cuda_runtime.h>
#include <cuda_bf16.h>
#include <cuda.h>
#include <stdint.h>
#include <type_traits>

constexpr int SEQ = 2048;
constexpr int DM = 512;
constexpr int NH = 32;
constexpr int HD = 128;
constexpr int NQ = NH * HD;
constexpr int SEGL = 32;
constexpr int NMEM = 8;
constexpr int NSEG = SEQ / SEGL;

typedef __nv_bfloat16 bf16;

__device__ bf16 g_QA[SEQ * NQ];
__device__ bf16 g_KA[SEQ * NQ];
__device__ bf16 g_VA[SEQ * NQ];
__device__ bf16 g_ctxA[SEQ * NQ];
__device__ bf16 g_ctxB[SEQ * NQ];
constexpr int CT_PROJ = 0, CT_ATTN = 1, CT_FIN = 5;
constexpr int CT_AP = 64;
#define O2_HE 18
constexpr int CT_CA = 128;
constexpr int CT_CB = 160;
constexpr int CT_OP = 192;
constexpr int CT_N = 224;
__device__ unsigned int g_ctr[CT_N];
__device__ uint32_t g_xbuf[4 * 8 * 2048];

#define FA_GRID 68

#define TS_BEGIN(id)
#define TS_END(id)
#define WAIT_LIMIT 200000
__device__ __forceinline__ void pdl_launch_dependents() { asm volatile("griddepcontrol.launch_dependents;" ::: "memory"); }
__device__ __forceinline__ void wait_ctr(int idx, unsigned int n) {
    unsigned int v; int it = 0;
    do { asm volatile("ld.acquire.gpu.global.u32 %0, [%1];" : "=r"(v) : "l"(&g_ctr[idx]) : "memory"); } while (v < n && ++it < WAIT_LIMIT);
    asm volatile("fence.proxy.async;" ::: "memory");
}
__device__ __forceinline__ void signal_ctr(int idx) {
    asm volatile("fence.proxy.async;" ::: "memory");
    __threadfence();
    atomicAdd(&g_ctr[idx], 1u);
}
__device__ __forceinline__ void signal_ctr_generic(int idx) {
    asm volatile("red.release.gpu.global.add.u32 [%0], 1;" :: "l"(&g_ctr[idx]) : "memory");
}
__device__ __forceinline__ uint32_t smem_u32(const void* p) {
    return (uint32_t)__cvta_generic_to_shared(p);
}
__device__ __forceinline__ void mbar_init(uint32_t bar, uint32_t count) {
    asm volatile("mbarrier.init.shared::cta.b64 [%0], %1;" :: "r"(bar), "r"(count));
}
__device__ __forceinline__ void mbar_expect_tx(uint32_t bar, uint32_t bytes) {
    asm volatile("mbarrier.arrive.expect_tx.shared::cta.b64 _, [%0], %1;" :: "r"(bar), "r"(bytes) : "memory");
}
__device__ __forceinline__ void mbar_arrive(uint32_t bar) {
    asm volatile("mbarrier.arrive.shared::cta.b64 _, [%0];" :: "r"(bar) : "memory");
}
__device__ __forceinline__ void mbar_wait(uint32_t bar, uint32_t parity) {
    asm volatile(
        "{\n"
        ".reg .pred p, q;\n"
        ".reg .u32 c;\n"
        "mov.u32 c, 0;\n"
        "WAIT_LOOP:\n"
        "mbarrier.try_wait.parity.shared::cta.b64 p, [%0], %1;\n"
        "@p bra WAIT_DONE;\n"
        "add.u32 c, c, 1;\n"
        "setp.lt.u32 q, c, %2;\n"
        "@q bra WAIT_LOOP;\n"
        "WAIT_DONE:\n"
        "}\n" :: "r"(bar), "r"(parity), "n"(WAIT_LIMIT) : "memory");
}
__device__ __forceinline__ void tma_load_2d(uint32_t dst, const CUtensorMap* map, uint32_t bar, int c0, int c1) {
    asm volatile(
        "cp.async.bulk.tensor.2d.shared::cluster.global.mbarrier::complete_tx::bytes [%0], [%1, {%3, %4}], [%2];"
        :: "r"(dst), "l"((uint64_t)map), "r"(bar), "r"(c0), "r"(c1) : "memory");
}
__device__ __forceinline__ void wgmma_fence() { asm volatile("wgmma.fence.sync.aligned;" ::: "memory"); }
__device__ __forceinline__ void wgmma_commit() { asm volatile("wgmma.commit_group.sync.aligned;" ::: "memory"); }
template <int N> __device__ __forceinline__ void wgmma_wait() {
    asm volatile("wgmma.wait_group.sync.aligned %0;" :: "n"(N) : "memory");
}
__device__ __forceinline__ uint64_t make_desc(uint32_t addr, uint32_t lbo, uint32_t sbo) {
    uint64_t d = 0;
    d |= (uint64_t)((addr & 0x3FFFF) >> 4);
    d |= (uint64_t)((lbo >> 4) & 0x3FFF) << 16;
    d |= (uint64_t)((sbo >> 4) & 0x3FFF) << 32;
    d |= (uint64_t)1 << 62;
    return d;
}

#define ACC64(d) \
    "+f"(d[0]), "+f"(d[1]), "+f"(d[2]), "+f"(d[3]), "+f"(d[4]), "+f"(d[5]), "+f"(d[6]), "+f"(d[7]), \
    "+f"(d[8]), "+f"(d[9]), "+f"(d[10]), "+f"(d[11]), "+f"(d[12]), "+f"(d[13]), "+f"(d[14]), "+f"(d[15]), \
    "+f"(d[16]), "+f"(d[17]), "+f"(d[18]), "+f"(d[19]), "+f"(d[20]), "+f"(d[21]), "+f"(d[22]), "+f"(d[23]), \
    "+f"(d[24]), "+f"(d[25]), "+f"(d[26]), "+f"(d[27]), "+f"(d[28]), "+f"(d[29]), "+f"(d[30]), "+f"(d[31]), \
    "+f"(d[32]), "+f"(d[33]), "+f"(d[34]), "+f"(d[35]), "+f"(d[36]), "+f"(d[37]), "+f"(d[38]), "+f"(d[39]), \
    "+f"(d[40]), "+f"(d[41]), "+f"(d[42]), "+f"(d[43]), "+f"(d[44]), "+f"(d[45]), "+f"(d[46]), "+f"(d[47]), \
    "+f"(d[48]), "+f"(d[49]), "+f"(d[50]), "+f"(d[51]), "+f"(d[52]), "+f"(d[53]), "+f"(d[54]), "+f"(d[55]), \
    "+f"(d[56]), "+f"(d[57]), "+f"(d[58]), "+f"(d[59]), "+f"(d[60]), "+f"(d[61]), "+f"(d[62]), "+f"(d[63])
#define ACC64_STR \
    "{%0, %1, %2, %3, %4, %5, %6, %7, %8, %9, %10, %11, %12, %13, %14, %15, " \
    "%16, %17, %18, %19, %20, %21, %22, %23, %24, %25, %26, %27, %28, %29, %30, %31, " \
    "%32, %33, %34, %35, %36, %37, %38, %39, %40, %41, %42, %43, %44, %45, %46, %47, " \
    "%48, %49, %50, %51, %52, %53, %54, %55, %56, %57, %58, %59, %60, %61, %62, %63}"

template <int TB>
__device__ __forceinline__ void wgmma_ss_n128(float (&d)[64], uint64_t da, uint64_t db, int scale_d) {
    asm volatile(
        "{\n.reg .pred p;\nsetp.ne.b32 p, %66, 0;\n"
        "wgmma.mma_async.sync.aligned.m64n128k16.f32.bf16.bf16 " ACC64_STR ", %64, %65, p, 1, 1, 0, %67;\n}\n"
        : ACC64(d) : "l"(da), "l"(db), "r"(scale_d), "n"(TB));
}
__device__ __forceinline__ uint32_t desc_lo(uint32_t addr, uint32_t lbo) { return ((addr & 0x3FFFF) >> 4) | ((lbo >> 4) << 16); }
template <int TB>
__device__ __forceinline__ void wgmma_ss_n128_lo(float (&d)[64], uint32_t da_lo, uint32_t db_lo, int scale_d) {
    asm volatile(
        "{\n.reg .pred p;\n.reg .b64 da, db;\nsetp.ne.b32 p, %66, 0;\n"
        "mov.b64 da, {%64, 0x40000040};\nmov.b64 db, {%65, 0x40000040};\n"
        "wgmma.mma_async.sync.aligned.m64n128k16.f32.bf16.bf16 " ACC64_STR ", da, db, p, 1, 1, 0, %67;\n}\n"
        : ACC64(d) : "r"(da_lo), "r"(db_lo), "r"(scale_d), "n"(TB));
}
__device__ __forceinline__ void wgmma_rs_n128_tb(float (&d)[64], uint32_t a0, uint32_t a1, uint32_t a2, uint32_t a3,
                                                 uint64_t db, int scale_d) {
    asm volatile(
        "{\n.reg .pred p;\nsetp.ne.b32 p, %69, 0;\n"
        "wgmma.mma_async.sync.aligned.m64n128k16.f32.bf16.bf16 " ACC64_STR ", {%64, %65, %66, %67}, %68, p, 1, 1, 1;\n}\n"
        : ACC64(d) : "r"(a0), "r"(a1), "r"(a2), "r"(a3), "l"(db), "r"(scale_d));
}
__device__ __forceinline__ void wgmma_rs_n80(float (&d)[40], const uint32_t (&a)[4], uint32_t db_lo, int scale_d) {
    asm volatile(
        "{\n.reg .pred p;\n.reg .b64 db;\nsetp.ne.b32 p, %45, 0;\nmov.b64 db, {%44, 0x40000040};\n"
        "wgmma.mma_async.sync.aligned.m64n80k16.f32.bf16.bf16 "
        "{%0, %1, %2, %3, %4, %5, %6, %7, %8, %9, %10, %11, %12, %13, %14, %15, %16, %17, %18, %19, %20, %21, %22, %23, %24, %25, %26, %27, %28, %29, %30, %31, %32, %33, %34, %35, %36, %37, %38, %39}, "
        "{%40, %41, %42, %43}, db, p, 1, 1, 0;\n}\n"
        : "+f"(d[0]), "+f"(d[1]), "+f"(d[2]), "+f"(d[3]), "+f"(d[4]), "+f"(d[5]), "+f"(d[6]), "+f"(d[7]), "+f"(d[8]), "+f"(d[9]), "+f"(d[10]), "+f"(d[11]), "+f"(d[12]), "+f"(d[13]), "+f"(d[14]), "+f"(d[15]), "+f"(d[16]), "+f"(d[17]), "+f"(d[18]), "+f"(d[19]), "+f"(d[20]), "+f"(d[21]), "+f"(d[22]), "+f"(d[23]), "+f"(d[24]), "+f"(d[25]), "+f"(d[26]), "+f"(d[27]), "+f"(d[28]), "+f"(d[29]), "+f"(d[30]), "+f"(d[31]), "+f"(d[32]), "+f"(d[33]), "+f"(d[34]), "+f"(d[35]), "+f"(d[36]), "+f"(d[37]), "+f"(d[38]), "+f"(d[39])
        : "r"(a[0]), "r"(a[1]), "r"(a[2]), "r"(a[3]), "r"(db_lo), "r"(scale_d));
}
__device__ __forceinline__ void wgmma_ss_n256_tb(float (&d)[128], uint64_t da, uint64_t db, int scale_d) {
    asm volatile(
        "{\n.reg .pred p;\nsetp.ne.b32 p, %130, 0;\n"
        "wgmma.mma_async.sync.aligned.m64n256k16.f32.bf16.bf16 {%0, %1, %2, %3, %4, %5, %6, %7, %8, %9, %10, %11, %12, %13, %14, %15, %16, %17, %18, %19, %20, %21, %22, %23, %24, %25, %26, %27, %28, %29, %30, %31, %32, %33, %34, %35, %36, %37, %38, %39, %40, %41, %42, %43, %44, %45, %46, %47, %48, %49, %50, %51, %52, %53, %54, %55, %56, %57, %58, %59, %60, %61, %62, %63, %64, %65, %66, %67, %68, %69, %70, %71, %72, %73, %74, %75, %76, %77, %78, %79, %80, %81, %82, %83, %84, %85, %86, %87, %88, %89, %90, %91, %92, %93, %94, %95, %96, %97, %98, %99, %100, %101, %102, %103, %104, %105, %106, %107, %108, %109, %110, %111, %112, %113, %114, %115, %116, %117, %118, %119, %120, %121, %122, %123, %124, %125, %126, %127}, %128, %129, p, 1, 1, 0, 1;\n}\n"
        : "+f"(d[0]), "+f"(d[1]), "+f"(d[2]), "+f"(d[3]), "+f"(d[4]), "+f"(d[5]), "+f"(d[6]), "+f"(d[7]), "+f"(d[8]), "+f"(d[9]), "+f"(d[10]), "+f"(d[11]), "+f"(d[12]), "+f"(d[13]), "+f"(d[14]), "+f"(d[15]), "+f"(d[16]), "+f"(d[17]), "+f"(d[18]), "+f"(d[19]), "+f"(d[20]), "+f"(d[21]), "+f"(d[22]), "+f"(d[23]), "+f"(d[24]), "+f"(d[25]), "+f"(d[26]), "+f"(d[27]), "+f"(d[28]), "+f"(d[29]), "+f"(d[30]), "+f"(d[31]), "+f"(d[32]), "+f"(d[33]), "+f"(d[34]), "+f"(d[35]), "+f"(d[36]), "+f"(d[37]), "+f"(d[38]), "+f"(d[39]), "+f"(d[40]), "+f"(d[41]), "+f"(d[42]), "+f"(d[43]), "+f"(d[44]), "+f"(d[45]), "+f"(d[46]), "+f"(d[47]), "+f"(d[48]), "+f"(d[49]), "+f"(d[50]), "+f"(d[51]), "+f"(d[52]), "+f"(d[53]), "+f"(d[54]), "+f"(d[55]), "+f"(d[56]), "+f"(d[57]), "+f"(d[58]), "+f"(d[59]), "+f"(d[60]), "+f"(d[61]), "+f"(d[62]), "+f"(d[63]), "+f"(d[64]), "+f"(d[65]), "+f"(d[66]), "+f"(d[67]), "+f"(d[68]), "+f"(d[69]), "+f"(d[70]), "+f"(d[71]), "+f"(d[72]), "+f"(d[73]), "+f"(d[74]), "+f"(d[75]), "+f"(d[76]), "+f"(d[77]), "+f"(d[78]), "+f"(d[79]), "+f"(d[80]), "+f"(d[81]), "+f"(d[82]), "+f"(d[83]), "+f"(d[84]), "+f"(d[85]), "+f"(d[86]), "+f"(d[87]), "+f"(d[88]), "+f"(d[89]), "+f"(d[90]), "+f"(d[91]), "+f"(d[92]), "+f"(d[93]), "+f"(d[94]), "+f"(d[95]), "+f"(d[96]), "+f"(d[97]), "+f"(d[98]), "+f"(d[99]), "+f"(d[100]), "+f"(d[101]), "+f"(d[102]), "+f"(d[103]), "+f"(d[104]), "+f"(d[105]), "+f"(d[106]), "+f"(d[107]), "+f"(d[108]), "+f"(d[109]), "+f"(d[110]), "+f"(d[111]), "+f"(d[112]), "+f"(d[113]), "+f"(d[114]), "+f"(d[115]), "+f"(d[116]), "+f"(d[117]), "+f"(d[118]), "+f"(d[119]), "+f"(d[120]), "+f"(d[121]), "+f"(d[122]), "+f"(d[123]), "+f"(d[124]), "+f"(d[125]), "+f"(d[126]), "+f"(d[127])
        : "l"(da), "l"(db), "r"(scale_d));
}
__device__ __forceinline__ void stmatrix_x4(uint32_t addr, uint32_t r0, uint32_t r1, uint32_t r2, uint32_t r3) {
    asm volatile("stmatrix.sync.aligned.m8n8.x4.shared.b16 [%0], {%1, %2, %3, %4};" :: "r"(addr), "r"(r0), "r"(r1), "r"(r2), "r"(r3) : "memory");
}
__device__ __forceinline__ void tma_store_2d(const CUtensorMap* map, uint32_t src, int c0, int c1) {
    asm volatile("cp.async.bulk.tensor.2d.global.shared::cta.bulk_group [%0, {%2, %3}], [%1];"
                 :: "l"((uint64_t)map), "r"(src), "r"(c0), "r"(c1) : "memory");
}
__device__ __forceinline__ float ex2f(float x) { float y; asm("ex2.approx.ftz.f32 %0, %1;" : "=f"(y) : "f"(x)); return y; }
__device__ __forceinline__ uint32_t pack_bf16(float lo, float hi) {
    __nv_bfloat162 v = __floats2bfloat162_rn(lo, hi);
    return *reinterpret_cast<uint32_t*>(&v);
}
__device__ __forceinline__ void mma_16816(float (&c)[4], uint32_t a0, uint32_t a1, uint32_t a2, uint32_t a3,
                                          uint32_t b0, uint32_t b1) {
    asm volatile(
        "mma.sync.aligned.m16n8k16.row.col.f32.bf16.bf16.f32 {%0,%1,%2,%3}, {%4,%5,%6,%7}, {%8,%9}, {%0,%1,%2,%3};"
        : "+f"(c[0]), "+f"(c[1]), "+f"(c[2]), "+f"(c[3])
        : "r"(a0), "r"(a1), "r"(a2), "r"(a3), "r"(b0), "r"(b1));
}
__device__ __forceinline__ void ldmatrix_x4_trans(uint32_t& r0, uint32_t& r1, uint32_t& r2, uint32_t& r3, uint32_t addr) {
    asm volatile("ldmatrix.sync.aligned.m8n8.x4.trans.shared.b16 {%0,%1,%2,%3}, [%4];"
                 : "=r"(r0), "=r"(r1), "=r"(r2), "=r"(r3) : "r"(addr));
}

struct AttnParams {
    CUtensorMap mapQ, mapK, mapV;
    CUtensorMap mapO;
};
constexpr int FA_STAGES = 2;
constexpr int FA_SMEM = 32768 + FA_STAGES * 65536 + 32768 + 1024 + 256;
constexpr int FA_ITEMS = 16 * NH;
#define FA_RETIRE 100000
#define FA_LASTG 8
__device__ __forceinline__ int fa_qt(int t) {
    constexpr int T0 = (32 - FA_LASTG) * 16;
    return t < T0 ? 15 - ((t & 127) >> 3) : 15 - (t - T0) / FA_LASTG;
}
__device__ __forceinline__ int fa_head(int t) {
    constexpr int T0 = (32 - FA_LASTG) * 16;
    return t < T0 ? (t >> 7) * 8 + (t & 7) : (32 - FA_LASTG) + (t - T0) % FA_LASTG;
}

__global__ void __launch_bounds__(384, 1) attn_kernel(const __grid_constant__ AttnParams P, int retire_cta) {
    extern __shared__ uint8_t smem_raw[];
    uint32_t sbase = (smem_u32(smem_raw) + 1023) & ~1023u;
    const uint32_t sQ = sbase;
    const uint32_t sKV = sbase + 32768;
    const uint32_t sO = sKV + FA_STAGES * 65536;
    const uint32_t bars = sO + 32768;
    const uint32_t bar_q = bars, bar_qe = bars + 8, bar_kf = bars + 16, bar_vf = bar_kf + 8 * FA_STAGES, bar_e = bar_vf + 8 * FA_STAGES,
                   bar_ek = bar_e + 8 * FA_STAGES, slot = bar_ek + 8 * FA_STAGES, bar_of = slot + 16, bar_oe = bar_of + 16, oslot = bar_oe + 16;
    const int warp = threadIdx.x >> 5;
    TS_BEGIN(1);
    int tfirst = 0;
    if (threadIdx.x == 256) tfirst = (int)atomicAdd(&g_ctr[CT_ATTN], 1u);
    if (threadIdx.x == 0) {
        mbar_init(bar_q, 1); mbar_init(bar_qe, 8);
        for (int i = 0; i < FA_STAGES; i++) { mbar_init(bar_kf + 8 * i, 1); mbar_init(bar_vf + 8 * i, 1); mbar_init(bar_e + 8 * i, 8); mbar_init(bar_ek + 8 * i, 8); }
        for (int i = 0; i < 2; i++) { mbar_init(bar_of + 8 * i, 1); mbar_init(bar_oe + 8 * i, 1); }
        asm volatile("fence.mbarrier_init.release.cluster;" ::: "memory");
    }
    if (threadIdx.x == 256) asm volatile("st.shared.s32 [%0], %1;" :: "r"(slot + 8), "r"(tfirst) : "memory");
    __syncthreads();
    pdl_launch_dependents();
    if (warp >= 8) {
        asm volatile("setmaxnreg.dec.sync.aligned.u32 40;");
        if (threadIdx.x == 288 || threadIdx.x == 320) {
            const int wg = threadIdx.x == 288 ? 0 : 1;
            const uint32_t stg = sO + wg * 16384;
            for (int n = 0;; n++) {
                mbar_wait(bar_of + 8 * wg, n & 1);
                int t;
                asm volatile("ld.shared.s32 %0, [%1];" : "=r"(t) : "r"(oslot + wg * 4) : "memory");
                if (t < 0) break;
                const int qt = fa_qt(t), h = fa_head(t);
                tma_store_2d(&P.mapO, stg, 0, h * SEQ + qt * 128 + wg * 64);
                tma_store_2d(&P.mapO, stg + 8192, 64, h * SEQ + qt * 128 + wg * 64);
                asm volatile("cp.async.bulk.commit_group;" ::: "memory");
                asm volatile("cp.async.bulk.wait_group.read 0;" ::: "memory");
                mbar_arrive(bar_oe + 8 * wg);
                asm volatile("cp.async.bulk.wait_group 0;" ::: "memory");
                signal_ctr(CT_CA + qt * 2 + (h >= O2_HE));
            }
        }
        if (threadIdx.x == 256) {
            int it = 0, hp_ready = 0;
            for (int item = 0;; item++) {
                int t = tfirst;
                if (item > 0) {
                    bool quit = false;
                    if ((int)blockIdx.x >= retire_cta) {
                        unsigned int v;
                        asm volatile("ld.relaxed.gpu.global.u32 %0, [%1];" : "=r"(v) : "l"(&g_ctr[CT_ATTN]) : "memory");
                        quit = v >= FA_RETIRE;
                    }
                    t = quit ? FA_ITEMS : (int)atomicAdd(&g_ctr[CT_ATTN], 1u);
                }
                const bool valid = t < FA_ITEMS;
                const int qt = fa_qt(t), h = fa_head(t);
                if (valid && !((hp_ready >> (h >> 1)) & 1)) { wait_ctr(CT_AP + (h >> 1), 96u); hp_ready |= 1 << (h >> 1); }
                mbar_wait(bar_qe, (item & 1) ^ 1);
                asm volatile("st.shared.s32 [%0], %1;" :: "r"(slot + (item & 1) * 4), "r"(valid ? t : -1) : "memory");
                if (!valid) { mbar_arrive(bar_q); break; }
                mbar_expect_tx(bar_q, 32768);
                tma_load_2d(sQ, &P.mapQ, bar_q, 0, h * SEQ + qt * 128);
                tma_load_2d(sQ + 16384, &P.mapQ, bar_q, 64, h * SEQ + qt * 128);
                for (int j = 0; j <= qt; j++, it++) {
                    const int s = it % FA_STAGES;
                    mbar_wait(bar_ek + 8 * s, ((it / FA_STAGES) & 1) ^ 1);
                    const uint32_t sk = sKV + s * 65536, sv = sk + 32768;
                    mbar_expect_tx(bar_kf + 8 * s, 32768);
                    tma_load_2d(sk, &P.mapK, bar_kf + 8 * s, 0, h * SEQ + j * 128);
                    tma_load_2d(sk + 16384, &P.mapK, bar_kf + 8 * s, 64, h * SEQ + j * 128);
                    mbar_wait(bar_e + 8 * s, ((it / FA_STAGES) & 1) ^ 1);
                    mbar_expect_tx(bar_vf + 8 * s, 32768);
                    tma_load_2d(sv, &P.mapV, bar_vf + 8 * s, 0, h * SEQ + j * 128);
                    tma_load_2d(sv + 16384, &P.mapV, bar_vf + 8 * s, 64, h * SEQ + j * 128);
                }
            }
        }
    } else {
        asm volatile("setmaxnreg.inc.sync.aligned.u32 232;");
        const int wg = warp >> 2;
        const int lane = threadIdx.x & 31;
        float o[64];
        float mrow0, mrow1, lrow0, lrow1;
        const float sc = 0.08838834764831845f * 1.4426950408889634f;
        const int r0 = wg * 64 + (warp & 3) * 16 + (lane >> 2);
        float sacc[64];
        uint32_t pa[32];
        float a0 = 1.f, a1 = 1.f;
        auto issue_qk = [&](int it) {
            const int s = it % FA_STAGES;
            const uint32_t sk = sKV + s * 65536;
            mbar_wait(bar_kf + 8 * s, (it / FA_STAGES) & 1);
            wgmma_fence();
#pragma unroll
            for (int kk = 0; kk < 8; kk++) {
                uint64_t da = make_desc(sQ + (kk >> 2) * 16384 + wg * 8192 + (kk & 3) * 32, 16, 1024);
                uint64_t db = make_desc(sk + (kk >> 2) * 16384 + (kk & 3) * 32, 16, 1024);
                wgmma_ss_n128<0>(sacc, da, db, kk != 0);
            }
            wgmma_commit();
        };
        auto issue_pv = [&](int it) {
            const int s = it % FA_STAGES;
            const uint32_t sv = sKV + s * 65536 + 32768;
            mbar_wait(bar_vf + 8 * s, (it / FA_STAGES) & 1);
            wgmma_fence();
#pragma unroll
            for (int kk = 0; kk < 8; kk++) {
                uint64_t db = make_desc(sv + kk * 2048, 16384, 1024);
                wgmma_rs_n128_tb(o, pa[kk * 4 + 0], pa[kk * 4 + 1], pa[kk * 4 + 2], pa[kk * 4 + 3], db, 1);
            }
            wgmma_commit();
        };
        auto softmax_stats = [&](bool diag) {
            if (diag) {
#pragma unroll
                for (int i = 0; i < 64; i++) {
                    int col = (i >> 2) * 8 + (lane & 3) * 2 + (i & 1);
                    int row = r0 + ((i & 2) ? 8 : 0);
                    if (col > row) sacc[i] = -INFINITY;
                }
            }
            float mx0 = -INFINITY, mx1 = -INFINITY;
#pragma unroll
            for (int i = 0; i < 16; i++) {
                mx0 = fmaxf(mx0, fmaxf(sacc[i * 4 + 0], sacc[i * 4 + 1]));
                mx1 = fmaxf(mx1, fmaxf(sacc[i * 4 + 2], sacc[i * 4 + 3]));
            }
            mx0 = fmaxf(mx0, __shfl_xor_sync(0xffffffff, mx0, 1));
            mx0 = fmaxf(mx0, __shfl_xor_sync(0xffffffff, mx0, 2));
            mx1 = fmaxf(mx1, __shfl_xor_sync(0xffffffff, mx1, 1));
            mx1 = fmaxf(mx1, __shfl_xor_sync(0xffffffff, mx1, 2));
            const float mn0 = fmaxf(mrow0, mx0), mn1 = fmaxf(mrow1, mx1);
            a0 = ex2f((mrow0 - mn0) * sc); a1 = ex2f((mrow1 - mn1) * sc);
            mrow0 = mn0; mrow1 = mn1;
            const float ms0 = mn0 * sc, ms1 = mn1 * sc;
            float sum0 = 0.f, sum1 = 0.f;
#pragma unroll
            for (int i = 0; i < 16; i++) {
                sacc[i * 4 + 0] = ex2f(fmaf(sacc[i * 4 + 0], sc, -ms0));
                sacc[i * 4 + 1] = ex2f(fmaf(sacc[i * 4 + 1], sc, -ms0));
                sacc[i * 4 + 2] = ex2f(fmaf(sacc[i * 4 + 2], sc, -ms1));
                sacc[i * 4 + 3] = ex2f(fmaf(sacc[i * 4 + 3], sc, -ms1));
                sum0 += sacc[i * 4 + 0] + sacc[i * 4 + 1];
                sum1 += sacc[i * 4 + 2] + sacc[i * 4 + 3];
            }
            lrow0 = lrow0 * a0 + sum0;
            lrow1 = lrow1 * a1 + sum1;
        };
        auto pack_p = [&]() {
#pragma unroll
            for (int i = 0; i < 16; i++) {
                pa[i * 2 + 0] = pack_bf16(sacc[i * 4 + 0], sacc[i * 4 + 1]);
                pa[i * 2 + 1] = pack_bf16(sacc[i * 4 + 2], sacc[i * 4 + 3]);
            }
        };
        int it = 0;
        if (wg == 1) asm volatile("bar.arrive 1, 256;" ::: "memory");
        for (int item = 0;; item++) {
            mbar_wait(bar_q, item & 1);
            int t;
            asm volatile("ld.shared.s32 %0, [%1];" : "=r"(t) : "r"(slot + (item & 1) * 4) : "memory");
            if (t < 0) {
                if ((threadIdx.x & 127) == 0) {
                    mbar_wait(bar_oe + 8 * wg, (item & 1) ^ 1);
                    asm volatile("st.shared.s32 [%0], %1;" :: "r"(oslot + wg * 4), "r"(-1) : "memory");
                    mbar_arrive(bar_of + 8 * wg);
                }
                break;
            }
            const int qt = fa_qt(t);
            const int nkv = qt + 1;
#pragma unroll
            for (int i = 0; i < 64; i++) o[i] = 0.f;
            mrow0 = -INFINITY; mrow1 = -INFINITY; lrow0 = 0.f; lrow1 = 0.f;
            asm volatile("bar.sync %0, 256;" :: "r"(1 + wg) : "memory");
            issue_qk(it);
            asm volatile("bar.arrive %0, 256;" :: "r"(2 - wg) : "memory");
            wgmma_wait<0>();
            if (lane == 0) { mbar_arrive(bar_ek + 8 * (it % FA_STAGES)); if (nkv == 1) mbar_arrive(bar_qe); }
            softmax_stats(nkv == 1);
            pack_p();
#pragma unroll 1
            for (int j = 1; j < nkv; j++) {
                asm volatile("bar.sync %0, 256;" :: "r"(1 + wg) : "memory");
                issue_qk(it + j);
                issue_pv(it + j - 1);
                asm volatile("bar.arrive %0, 256;" :: "r"(2 - wg) : "memory");
                wgmma_wait<1>();
                if (lane == 0) { mbar_arrive(bar_ek + 8 * ((it + j) % FA_STAGES)); if (j == nkv - 1) mbar_arrive(bar_qe); }
                softmax_stats(j == nkv - 1);
                wgmma_wait<0>();
                if (lane == 0) mbar_arrive(bar_e + 8 * ((it + j - 1) % FA_STAGES));
#pragma unroll
                for (int i = 0; i < 16; i++) {
                    o[i * 4 + 0] *= a0; o[i * 4 + 1] *= a0; o[i * 4 + 2] *= a1; o[i * 4 + 3] *= a1;
                }
                pack_p();
            }
            issue_pv(it + nkv - 1);
            wgmma_wait<0>();
            if (lane == 0) mbar_arrive(bar_e + 8 * ((it + nkv - 1) % FA_STAGES));
            it += nkv;
            lrow0 += __shfl_xor_sync(0xffffffff, lrow0, 1);
            lrow0 += __shfl_xor_sync(0xffffffff, lrow0, 2);
            lrow1 += __shfl_xor_sync(0xffffffff, lrow1, 1);
            lrow1 += __shfl_xor_sync(0xffffffff, lrow1, 2);
            const float i0 = 1.f / lrow0, i1 = 1.f / lrow1;
            const uint32_t stg = sO + wg * 16384;
            mbar_wait(bar_oe + 8 * wg, (item & 1) ^ 1);
            {
                const int row = (warp & 3) * 16 + (lane >> 2);
#pragma unroll
                for (int i = 0; i < 4; i++) {
                    const int ch = i * 4 + (lane & 3);
                    const uint32_t a = stg + (ch >> 3) * 8192 + row * 128 + (((ch & 7) ^ (row & 7)) << 4);
                    const float* q = &o[i * 16];
                    asm volatile("st.shared.v4.b32 [%0], {%1, %2, %3, %4};" :: "r"(a), "r"(pack_bf16(q[0] * i0, q[1] * i0)), "r"(pack_bf16(q[4] * i0, q[5] * i0)),
                                 "r"(pack_bf16(q[8] * i0, q[9] * i0)), "r"(pack_bf16(q[12] * i0, q[13] * i0)) : "memory");
                    asm volatile("st.shared.v4.b32 [%0], {%1, %2, %3, %4};" :: "r"(a + 1024), "r"(pack_bf16(q[2] * i1, q[3] * i1)), "r"(pack_bf16(q[6] * i1, q[7] * i1)),
                                 "r"(pack_bf16(q[10] * i1, q[11] * i1)), "r"(pack_bf16(q[14] * i1, q[15] * i1)) : "memory");
                }
            }
            asm volatile("fence.proxy.async.shared::cta;" ::: "memory");
            asm volatile("bar.sync %0, 128;" :: "r"(3 + wg) : "memory");
            if ((threadIdx.x & 127) == 0) {
                asm volatile("st.shared.s32 [%0], %1;" :: "r"(oslot + wg * 4), "r"(t) : "memory");
                mbar_arrive(bar_of + 8 * wg);
            }
        }
        TS_END(1);
    }
}

__device__ __forceinline__ uint32_t cluster_ctarank() {
    uint32_t r; asm volatile("mov.u32 %0, %%cluster_ctarank;" : "=r"(r)); return r;
}
__device__ __forceinline__ uint32_t mapa_u32(uint32_t addr, uint32_t rank) {
    uint32_t r; asm volatile("mapa.shared::cluster.u32 %0, %1, %2;" : "=r"(r) : "r"(addr), "r"(rank)); return r;
}
__device__ __forceinline__ void cluster_sync_all() {
    asm volatile("barrier.cluster.arrive.release.aligned;\nbarrier.cluster.wait.acquire.aligned;" ::: "memory");
}
__device__ __forceinline__ void st_async_v4(uint32_t addr, uint32_t a, uint32_t b, uint32_t c, uint32_t d, uint32_t mbar) {
    asm volatile("st.async.weak.shared::cluster.mbarrier::complete_tx::bytes.v4.b32 [%0], {%1, %2, %3, %4}, [%5];"
                 :: "r"(addr), "r"(a), "r"(b), "r"(c), "r"(d), "r"(mbar) : "memory");
}
__device__ __forceinline__ void st_async_v2(uint32_t addr, uint32_t a, uint32_t b, uint32_t mbar) {
    asm volatile("st.async.weak.shared::cluster.mbarrier::complete_tx::bytes.v2.b32 [%0], {%1, %2}, [%3];"
                 :: "r"(addr), "r"(a), "r"(b), "r"(mbar) : "memory");
}
__device__ __forceinline__ void st_async_b32(uint32_t addr, uint32_t a, uint32_t mbar) {
    asm volatile("st.async.weak.shared::cluster.mbarrier::complete_tx::bytes.b32 [%0], %1, [%2];" :: "r"(addr), "r"(a), "r"(mbar) : "memory");
}
__device__ __forceinline__ void pace(int cycles) {
    if (cycles > 0) {
        uint32_t t0, t;
        asm volatile("mov.u32 %0, %%clock;" : "=r"(t0));
        do { asm volatile("mov.u32 %0, %%clock;" : "=r"(t)); } while (t - t0 < (uint32_t)cycles);
    }
}
__device__ __forceinline__ void mbar_wait_cl(uint32_t bar, uint32_t parity) {
    uint32_t done = 0;
    for (int it = 0; it < WAIT_LIMIT && !done; it++) {
        asm volatile(
            "{\n.reg .pred p;\n"
            "mbarrier.try_wait.parity.shared::cta.b64 p, [%1], %2;\n"
            "selp.u32 %0, 1, 0, p;\n}\n" : "=r"(done) : "r"(bar), "r"(parity) : "memory");
    }
}
__device__ __forceinline__ uint32_t mbar_test(uint32_t bar, uint32_t parity) {
    uint32_t done;
    asm volatile(
        "{\n.reg .pred p;\n"
        "mbarrier.test_wait.parity.shared::cta.b64 p, [%1], %2;\n"
        "selp.u32 %0, 1, 0, p;\n}\n" : "=r"(done) : "r"(bar), "r"(parity) : "memory");
    return done;
}
__device__ __forceinline__ void ldmatrix_x4(uint32_t& r0, uint32_t& r1, uint32_t& r2, uint32_t& r3, uint32_t addr) {
    asm volatile("ldmatrix.sync.aligned.m8n8.x4.shared.b16 {%0,%1,%2,%3}, [%4];"
                 : "=r"(r0), "=r"(r1), "=r"(r2), "=r"(r3) : "r"(addr));
}
__device__ __forceinline__ void cp_async16(uint32_t dst, const void* src) {
    asm volatile("cp.async.cg.shared.global [%0], [%1], 16;" :: "r"(dst), "l"(src) : "memory");
}
__device__ __forceinline__ float bf16r(float x) { return __uint_as_float(pack_bf16(0.f, x) & 0xffff0000u); }

#define DBG(i, w)
#define DBGD(i, w, dep)
#define DBG_EXTRA 0
__device__ __forceinline__ void tma_load_2d_mc(uint32_t dst, const CUtensorMap* map, uint32_t bar, int c0, int c1, uint16_t mask) {
    asm volatile(
        "cp.async.bulk.tensor.2d.shared::cluster.global.mbarrier::complete_tx::bytes.multicast::cluster [%0], [%1, {%3, %4}], [%2], %5;"
        :: "r"(dst), "l"((uint64_t)map), "r"(bar), "r"(c0), "r"(c1), "h"(mask) : "memory");
}
__device__ __forceinline__ void stmatrix_x4_trans(uint32_t addr, uint32_t r0, uint32_t r1, uint32_t r2, uint32_t r3) {
    asm volatile("stmatrix.sync.aligned.m8n8.x4.trans.shared.b16 [%0], {%1, %2, %3, %4};" :: "r"(addr), "r"(r0), "r"(r1), "r"(r2), "r"(r3) : "memory");
}
__device__ __forceinline__ void stmatrix_x2_trans(uint32_t addr, uint32_t r0, uint32_t r1) {
    asm volatile("stmatrix.sync.aligned.m8n8.x2.trans.shared.b16 [%0], {%1, %2};" :: "r"(addr), "r"(r0), "r"(r1) : "memory");
}
__device__ __forceinline__ uint4 lds128(uint32_t a) {
    uint4 v; asm volatile("ld.shared.v4.u32 {%0, %1, %2, %3}, [%4];" : "=r"(v.x), "=r"(v.y), "=r"(v.z), "=r"(v.w) : "r"(a) : "memory"); return v;
}
__device__ __forceinline__ void sts128(uint32_t a, uint32_t x, uint32_t y, uint32_t z, uint32_t w) {
    asm volatile("st.shared.v4.b32 [%0], {%1, %2, %3, %4};" :: "r"(a), "r"(x), "r"(y), "r"(z), "r"(w) : "memory");
}
__device__ __forceinline__ float2 lds64f(uint32_t a) {
    float2 v; asm volatile("ld.shared.v2.f32 {%0, %1}, [%2];" : "=f"(v.x), "=f"(v.y) : "r"(a) : "memory"); return v;
}
__device__ __forceinline__ void fence_async_smem() { asm volatile("fence.proxy.async.shared::cta;" ::: "memory"); }
#define ACC16(d) "+f"(d[0]), "+f"(d[1]), "+f"(d[2]), "+f"(d[3]), "+f"(d[4]), "+f"(d[5]), "+f"(d[6]), "+f"(d[7]), "+f"(d[8]), "+f"(d[9]), "+f"(d[10]), "+f"(d[11]), "+f"(d[12]), "+f"(d[13]), "+f"(d[14]), "+f"(d[15])
template <int ND>
__device__ __forceinline__ void wgmma_rs_n32(float (&d)[ND], const uint32_t (&a)[4], uint32_t db_lo, int scale_d) {
    asm volatile(
        "{\n.reg .pred p;\n.reg .b64 db;\nsetp.ne.b32 p, %21, 0;\nmov.b64 db, {%20, 0x40000040};\n"
        "wgmma.mma_async.sync.aligned.m64n32k16.f32.bf16.bf16 {%0,%1,%2,%3,%4,%5,%6,%7,%8,%9,%10,%11,%12,%13,%14,%15}, {%16,%17,%18,%19}, db, p, 1, 1, 0;\n}\n"
        : ACC16(d) : "r"(a[0]), "r"(a[1]), "r"(a[2]), "r"(a[3]), "r"(db_lo), "r"(scale_d));
}
template <int ND>
__device__ __forceinline__ void wgmma_ss_n32(float (&d)[ND], uint32_t da_lo, uint32_t db_lo, int scale_d) {
    asm volatile(
        "{\n.reg .pred p;\n.reg .b64 da, db;\nsetp.ne.b32 p, %18, 0;\nmov.b64 da, {%16, 0x40000040};\nmov.b64 db, {%17, 0x40000040};\n"
        "wgmma.mma_async.sync.aligned.m64n32k16.f32.bf16.bf16 {%0,%1,%2,%3,%4,%5,%6,%7,%8,%9,%10,%11,%12,%13,%14,%15}, da, db, p, 1, 1, 1, 0;\n}\n"
        : ACC16(d) : "r"(da_lo), "r"(db_lo), "r"(scale_d));
}
__device__ __forceinline__ void wgmma_ss_n8(float (&d)[4], uint32_t da_lo, uint32_t db_lo, int scale_d) {
    asm volatile(
        "{\n.reg .pred p;\n.reg .b64 da, db;\nsetp.ne.b32 p, %6, 0;\nmov.b64 da, {%4, 0x40000040};\nmov.b64 db, {%5, 0x00000010};\n"
        "wgmma.mma_async.sync.aligned.m64n8k16.f32.bf16.bf16 {%0,%1,%2,%3}, da, db, p, 1, 1, 1, 0;\n}\n"
        : "+f"(d[0]), "+f"(d[1]), "+f"(d[2]), "+f"(d[3]) : "r"(da_lo), "r"(db_lo), "r"(scale_d));
}

#define SCHED_FENCE()
__device__ __forceinline__ void wgmma_ss_n32_p(float (&d)[16], uint32_t da_lo, uint32_t db_lo, int scale_d) {
    asm volatile(
        "{\n.reg .pred p;\n.reg .b64 da, db;\nsetp.ne.b32 p, %18, 0;\nmov.b64 da, {%16, 0x40000040};\nmov.b64 db, {%17, 0x00000030};\n"
        "wgmma.mma_async.sync.aligned.m64n32k16.f32.bf16.bf16 {%0,%1,%2,%3,%4,%5,%6,%7,%8,%9,%10,%11,%12,%13,%14,%15}, da, db, p, 1, 1, 1, 0;\n}\n"
        : ACC16(d) : "r"(da_lo), "r"(db_lo), "r"(scale_d));
}

__device__ __forceinline__ void wgmma_ss_n32_kk(float (&d)[16], uint32_t da_lo, uint32_t db_lo, int scale_d) {
    asm volatile(
        "{\n.reg .pred p;\n.reg .b64 da, db;\nsetp.ne.b32 p, %18, 0;\nmov.b64 da, {%16, 0x40000040};\nmov.b64 db, {%17, 0x40000040};\n"
        "wgmma.mma_async.sync.aligned.m64n32k16.f32.bf16.bf16 {%0,%1,%2,%3,%4,%5,%6,%7,%8,%9,%10,%11,%12,%13,%14,%15}, da, db, p, 1, 1, 0, 0;\n}\n"
        : ACC16(d) : "r"(da_lo), "r"(db_lo), "r"(scale_d));
}

struct ChainParams {
    CUtensorMap mapW[3];
    CUtensorMap mapX;
    CUtensorMap mapC;
};
constexpr int CH_BLOCK = 384;
constexpr int CO_WO = 0;
constexpr int CO_XB = 65536;
constexpr int CO_MB = CO_XB + 65536;
constexpr int CO_OB = CO_MB + 8192;
constexpr int CH_TW = 6144, CH_TP = 3 * CH_TW;
constexpr int CO_T = CO_OB + 8192;
constexpr int CO_SC = CO_T + 2 * CH_TP;
constexpr int CO_LS = CO_SC + 2 * 1280;
constexpr int CO_LO = CO_LS + 8 * 1280;
constexpr int CO_P = CO_LO + 4 * 1280;
constexpr int CO_ST = 205824;
#define CH_NSM 3
constexpr int CO_WA = CO_ST + 4096;
constexpr int CO_BAR = CO_WA + CH_TP;
constexpr int CH_SMEM = CO_BAR + 256 + 1024 + DBG_EXTRA;
static_assert(CO_WA >= 3 * 65536 && CO_P + 3072 <= CO_ST && CH_NSM <= 3, "smem layout");
#define CH_POLL_DELAY 0
#define CH_PEARLY 0
#define CH_VPOS 2
#define CH_VST 0
#define CH_V3_DELAY 0
#define CH_V1 0
#define CH_V2 24
#define CH_V3 32
#define CH_OG 2
#define CH_OW 8
#define CH_OF 12
#define CH_CHAINS 4

constexpr float CH_SC = 0.08838834764831845f * 1.4426950408889634f;
__device__ __forceinline__ uint32_t pin(uint32_t v) { return __shfl_sync(0xffffffff, v, threadIdx.x & 31); }

__global__ void __cluster_dims__(8, 1, 1) __launch_bounds__(CH_BLOCK, 1)
chain_kernel(const __grid_constant__ ChainParams P, const bf16* __restrict__ mem0, const bf16* __restrict__ Wo, const bf16* __restrict__ x) {
    extern __shared__ uint8_t smem_raw[];
    const uint32_t sb = (smem_u32(smem_raw) + 1023) & ~1023u;
    const int tid = threadIdx.x, warp = __shfl_sync(0xffffffff, tid >> 5, 0), lane = tid & 31;
    const int rank = (int)cluster_ctarank();
    const int C = blockIdx.x >> 3;
    const int h = C * 4 + (rank >> 1);
    const int qd = lane >> 2, qc = lane & 3;
    const int t4 = warp & 3, wg = warp >> 2;
    pdl_launch_dependents();
    TS_BEGIN(2);
    const uint32_t bar_mem = sb + CO_BAR, bar_o = bar_mem + 32, bar_sc = bar_o + 32, bar_x = bar_sc + 8, bar_l = bar_x + 16, bar_w = bar_l + 8;
    if (tid == 0) {
        for (int j = 0; j < 15; j++) mbar_init(bar_mem + 8 * j, bar_mem + 8 * j == bar_l ? 4 : 1);
        asm volatile("fence.mbarrier_init.release.cluster;" ::: "memory");
    }
    __syncthreads();
    if ((tid & 127) == 0) {
        mbar_expect_tx(bar_w + 8 * wg, 65536);
        for (int i = 0; i < 8; i++)
            tma_load_2d(sb + wg * 65536 + i * 8192, &P.mapW[wg], bar_w + 8 * wg, h * HD + (rank & 1) * 64, i * 64);
    }
    {
        for (int i = tid; i < 512; i += CH_BLOCK) asm volatile("prefetch.global.L2 [%0];" :: "l"(Wo + (size_t)(C * 512 + i) * DM + rank * 64));
        if (tid < 64) asm volatile("prefetch.global.L2 [%0];" :: "l"(x + (size_t)tid * DM + rank * 64));
    }
    auto chunk = [&](int i) { return (uint32_t)((rank - (i >> 1) - 4 * (i & 1)) & 7); };
    const uint32_t wfrag = (((lane >> 4) << 3) + (lane & 7)) * 128 + (((t4 * 2 + ((lane >> 3) & 1)) ^ (lane & 7)) << 4);
    const uint32_t aO = pin(sb + wg * CH_TW + wfrag);
    const uint32_t aM = pin(sb + (lane & 7) * 128 + (((lane >> 3) ^ (lane & 7)) << 4));
    const uint32_t aL = pin(sb + lane * 8);
    uint32_t w[32][4];
    float d[16];
    mbar_wait(bar_w + 8 * wg, 0);
#pragma unroll
    for (int e = CH_NSM; e < 32; e++) ldmatrix_x4_trans(w[e][0], w[e][1], w[e][2], w[e][3], sb + wg * 65536 + wfrag + chunk(e >> 2) * 8192 + (e & 3) * 2048);
#pragma unroll
    for (int e = 0; e < CH_NSM; e++) {
        const uint4 u = lds128(sb + wg * 65536 + chunk(0) * 8192 + e * 2048 + (tid & 127) * 16);
        sts128(sb + CO_WA + wg * CH_TW + e * 2048 + (tid & 127) * 16, u.x, u.y, u.z, u.w);
    }
    fence_async_smem();
    __syncthreads();
    if (tid == 0) {
        fence_async_smem();
        for (int b = 0; b < 2; b++) {
            mbar_expect_tx(bar_x + 8 * b, 32768);
            for (int i = 0; i < 8; i++) tma_load_2d(sb + CO_XB + b * 32768 + i * 4096, &P.mapX, bar_x + 8 * b, i * 64, b * SEGL);
        }
    }
#pragma unroll 2
    for (int i = tid; i < 512 * 4; i += CH_BLOCK) {
        const int r = i >> 2, cg = i & 3, ks = r >> 4, kp = r & 15;
        const int src = (rank - (ks >> 2)) & 7;
        const uint4* p = reinterpret_cast<const uint4*>(Wo + (size_t)(C * 512 + src * 64 + (ks & 3) * 16 + (kp >> 2) * 2 + (kp & 1) + (kp & 2) * 4) * DM + rank * 64 + cg * 16);
        const uint4 u0 = __ldg(p), u1 = __ldg(p + 1);
        const uint32_t a = sb + CO_WO + r * 128;
        sts128(a + (((cg * 2) ^ (r & 7)) << 4), __byte_perm(u0.x, u0.y, 0x5410), __byte_perm(u0.z, u0.w, 0x5410), __byte_perm(u1.x, u1.y, 0x5410), __byte_perm(u1.z, u1.w, 0x5410));
        sts128(a + (((cg * 2 + 1) ^ (r & 7)) << 4), __byte_perm(u0.x, u0.y, 0x7632), __byte_perm(u0.z, u0.w, 0x7632), __byte_perm(u1.x, u1.y, 0x7632), __byte_perm(u1.z, u1.w, 0x7632));
    }
#pragma unroll 1
    for (int i = tid; i < 512; i += CH_BLOCK) {
        const int n = i >> 6, c = i & 63;
        const uint4 u = __ldg(reinterpret_cast<const uint4*>(mem0 + n * DM + chunk(c >> 3) * 64 + (c & 7) * 8));
        sts128(sb + CO_MB + (c >> 3) * 1024 + n * 128 + (((c & 7) ^ n) << 4), u.x, u.y, u.z, u.w);
    }
    if (tid < 128) sts128(sb + CO_T + (tid >> 6) * CH_TP + 2 * CH_TW + 5120 + (tid & 63) * 16, 0u, 0u, 0u, 0u);
    else if (tid < 160) sts128(sb + CO_P + ((tid >> 3) & 3) * 768 + 640 + (tid & 7) * 16, 0u, 0u, 0u, 0u);
    fence_async_smem();
    TS_END(6);
    auto pass32 = [&](int b, int e0 = 0, int e1 = 32) {
        const uint32_t lo = desc_lo(sb + CO_XB + b * 32768, 16);
        wgmma_fence();
#pragma unroll
        for (int e = 0; e < 32; e++) if (e >= e0 && e < e1) {
            const uint32_t db = lo + chunk(e >> 2) * 256 + (e & 3) * 2;
            if (e < CH_NSM) wgmma_ss_n32(d, desc_lo(sb + CO_WA + wg * CH_TW + e * 2048, 16), db, e != 0);
            else wgmma_rs_n32(d, w[e], db, e != 0);
        }
        wgmma_commit();
    };
    auto store32 = [&](uint32_t a) {
        stmatrix_x4_trans(a, pack_bf16(d[0], d[1]), pack_bf16(d[2], d[3]), pack_bf16(d[4], d[5]), pack_bf16(d[6], d[7]));
        stmatrix_x4_trans(a + 2048, pack_bf16(d[8], d[9]), pack_bf16(d[10], d[11]), pack_bf16(d[12], d[13]), pack_bf16(d[14], d[15]));
    };
    auto mem_proj = [&](int s, bool wait, bool arrive = false) {
        const uint32_t par = s & 1;
        float acc[CH_CHAINS][4];
#pragma unroll
        for (int i = 0; i < CH_CHAINS; i++) acc[i][0] = acc[i][1] = acc[i][2] = acc[i][3] = 0.f;
        const uint32_t aM2 = aM ^ 64;
        uint32_t b[2][8];
        auto load = [&](int c) {
            if (wait && !(c & 1)) mbar_wait_cl(bar_mem + 4 * c, par ^ 1);
            if (c == 0) DBG(11, 0);
            if (c == 6) DBG(13, 0);
            ldmatrix_x4(b[c & 1][0], b[c & 1][1], b[c & 1][2], b[c & 1][3], aM + CO_MB + c * 1024);
            ldmatrix_x4(b[c & 1][4], b[c & 1][5], b[c & 1][6], b[c & 1][7], aM2 + CO_MB + c * 1024);
        };
        load(0);
#pragma unroll
        for (int c = 0; c < 8; c++) {
            if (c < 7) load(c + 1);
            SCHED_FENCE();
#pragma unroll
            for (int i = 0; i < 4; i++) {
                const int e = c * 4 + i;
                mma_16816(acc[i % CH_CHAINS], w[e][0], w[e][1], w[e][2], w[e][3], b[c & 1][i * 2], b[c & 1][i * 2 + 1]);
            }
        }
        if (CH_CHAINS == 4) {
#pragma unroll
            for (int i = 0; i < 4; i++) { acc[0][i] += acc[2 % CH_CHAINS][i]; acc[1][i] += acc[3 % CH_CHAINS][i]; }
        }
        const uint32_t r0 = pack_bf16(acc[0][0] + acc[1][0], acc[0][1] + acc[1][1]);
        const uint32_t r1 = pack_bf16(acc[0][2] + acc[1][2], acc[0][3] + acc[1][3]);
        DBGD(40 + warp, warp, r0 ^ r1);
        stmatrix_x2_trans(aO + par * CH_TP + CO_T + 4096, r0, r1);
    };
    auto load_wa = [&]() {
#pragma unroll
        for (int e = 0; e < CH_NSM; e++) ldmatrix_x4_trans(w[e][0], w[e][1], w[e][2], w[e][3], aO + CO_WA + e * 2048);
    };
    auto remote = [](uint32_t a, uint32_t r) { return mapa_u32(a, r); };
    mbar_wait(bar_x, 0);
    pass32(0);
    wgmma_wait<0>();
    store32(aO + CO_T);
    fence_async_smem();
    __syncthreads();
    cluster_sync_all();
    TS_BEGIN(5);

    if (wg < 2) {
        const uint32_t aQ = pin(sb + CO_T + qd * 128 + (((2 * qc) ^ qd) << 4));
        auto local_scores = [&](int s) {
            const uint32_t tb = sb + CO_T + (s & 1) * CH_TP;
            wgmma_fence();
#pragma unroll
            for (int ks = 0; ks < 4; ks++) wgmma_ss_n32_kk(d, desc_lo(tb + CH_TW, 16) + ks * 2, desc_lo(tb, 16) + ks * 2, ks != 0);
            wgmma_commit();
            wgmma_wait<0>();
            const uint32_t rb = remote(bar_l, rank ^ 1);
            if (t4 < 2) {
                const uint32_t off = 2 * aL - sb + t4 * 512;
#pragma unroll
                for (int j = 0; j < 4; j++) if (j >= 2 || t4 == 0) {
                    st_async_v4(remote(off + (s & 1) * 5120 + CO_LS + j * 1280, rank ^ 1), __float_as_uint(d[4 * j]), __float_as_uint(d[4 * j + 1]), __float_as_uint(d[4 * j + 2]), __float_as_uint(d[4 * j + 3]), rb);
                    sts128(off + CO_LO + j * 1280, __float_as_uint(d[4 * j]), __float_as_uint(d[4 * j + 1]), __float_as_uint(d[4 * j + 2]), __float_as_uint(d[4 * j + 3]));
                }
            } else if (t4 == 2) {
#pragma unroll
                for (int j = 0; j < 4; j++) {
                    st_async_v2(remote(aL + (s & 1) * 5120 + CO_LS + 1024 + j * 1280, rank ^ 1), __float_as_uint(d[4 * j]), __float_as_uint(d[4 * j + 1]), rb);
                    asm volatile("st.shared.v2.f32 [%0], {%1, %2};" :: "r"(aL + CO_LO + 1024 + j * 1280), "f"(d[4 * j]), "f"(d[4 * j + 1]) : "memory");
                }
            }
            __syncwarp();
            if (t4 < 3 && lane == 0) mbar_arrive(bar_l);
            DBG(6, 4);
        };
        auto local_pv = [&](int s, bool arrive) {
            wgmma_fence();
#pragma unroll
            for (int ks = 0; ks < 3; ks++)
                wgmma_ss_n32_p(d, desc_lo(sb + CO_T + (s & 1) * CH_TP + 2 * CH_TW + ks * 2048, 16), desc_lo(sb + CO_P + ks * 256, 128), ks != 0);
            wgmma_commit();
            wgmma_wait<0>();
            if (arrive) asm volatile("bar.arrive 9, 256;" ::: "memory");
            store32(aO + CO_ST);
            fence_async_smem();
            if (!arrive) asm volatile("bar.sync 5, 128;" ::: "memory");
        };
        auto store_ctx = [&](int s) {
            tma_store_2d(&P.mapC, sb + CO_ST, (rank & 1) * 64, h * SEQ + s * SEGL);
            asm volatile("cp.async.bulk.commit_group;" ::: "memory");
        };
        auto signal_ctx = [&](int m0, int m1) {
            asm volatile("fence.proxy.async;" ::: "memory");
            __threadfence();
            for (int m = m0; m < m1; m++) asm volatile("red.relaxed.gpu.global.add.u32 [%0], 1;" :: "l"(&g_ctr[CT_CB + m * 2 + (h >= O2_HE)]) : "memory");
        };
#pragma unroll 1
        for (int s = 0; s < NSEG; s++) {
            const uint32_t par = s & 1;
            load_wa();
            mem_proj(s, s > 0);
            if (s == NSEG - 1) break;
            if (warp < 5) {
                const uint32_t qa_ = aQ + par * CH_TP, ka = qa_ + warp * 1024;
                asm volatile("bar.sync 1, 256;" ::: "memory");
                const uint4 qa = lds128(qa_ + 4096), k0 = lds128(ka + CH_TW), qb = lds128((qa_ ^ 16) + 4096), k1 = lds128((ka ^ 16) + CH_TW);
                DBGD(52 + warp, warp, qa.x ^ qb.x);
                float c[4] = {0.f, 0.f, 0.f, 0.f}, c2[4] = {0.f, 0.f, 0.f, 0.f};
                mma_16816(c, qa.x, 0u, qa.y, 0u, k0.x, k0.y);
                mma_16816(c2, qb.x, 0u, qb.y, 0u, k1.x, k1.y);
                mma_16816(c, qa.z, 0u, qa.w, 0u, k0.z, k0.w);
                mma_16816(c2, qb.z, 0u, qb.w, 0u, k1.z, k1.w);
                c[0] += c2[0]; c[1] += c2[1];
                DBGD(57 + warp, warp, __float_as_uint(c[0]));
                const uint32_t off = aL + CO_SC + warp * 256;
                st_async_v2(remote(off + 1280, rank ^ 1), __float_as_uint(c[0]), __float_as_uint(c[1]), remote(bar_sc, rank ^ 1));
                st_async_v2(off, __float_as_uint(c[0]), __float_as_uint(c[1]), bar_sc);
                asm volatile("bar.arrive 2, 288;" ::: "memory");
                DBG(3, 0);
            } else {
                asm volatile("bar.arrive 1, 256;" ::: "memory");
            }
            if (wg == 0) {
                if (tid == 96) {
                    mbar_expect_tx(bar_sc, 2 * 1280);
#pragma unroll
                    for (int j = 0; j < 4; j++) { mbar_expect_tx(bar_mem + 8 * j, 2048); if (j < CH_OG) mbar_expect_tx(bar_o + 8 * j, 8192 / CH_OG); }
                    if (s > 0) mbar_wait(bar_l, par ^ 1);
                    mbar_expect_tx(bar_l, 4096);
                }
                if (tid == 96 && s > 1) {
                    if (s == 34 || s == 50 || s == 58 || s == 62) {
                        asm volatile("cp.async.bulk.wait_group 0;" ::: "memory");
                        signal_ctx(s == 34 ? 0 : (2 * s - 68) >> 2, s >> 2);
                    }
                    store_ctx(s - 2);
                    asm volatile("cp.async.bulk.wait_group.read 0;" ::: "memory");
                }
                __syncwarp();
                mbar_wait(bar_x + 8 * (par ^ 1), ((s + 1) >> 1) & 1);
                asm volatile("bar.sync 5, 128;" ::: "memory");
                float c[4];
                const uint32_t alo = desc_lo(sb + CO_WO, 16), blo = desc_lo(sb + CO_OB, 128);
                uint32_t* wp = g_xbuf + (size_t)rank * 2048 + C * 256 + qc * 64 + t4 * 8 + qd;
                mbar_wait_cl(bar_o, par);
                DBG(16, 0);
                fence_async_smem();
                wgmma_fence();
#pragma unroll
                for (int i = 0; i < 32; i++) {
                    wgmma_ss_n8(c, alo + i * 128, blo + i * 16, i != 0);
                    if (CH_OG == 2 && i == CH_OW) mbar_wait_cl(bar_o + 8, par);
                    if (CH_OG == 2 && i == CH_OF) fence_async_smem();
                }
                wgmma_commit();
                wgmma_wait<0>();
                asm volatile("st.relaxed.gpu.global.u32 [%0], %1;" :: "l"(wp + (s & 3) * 16384), "r"(~pack_bf16(c[0], c[2])) : "memory");
                asm volatile("st.relaxed.gpu.global.u32 [%0], %1;" :: "l"(wp + (s & 3) * 16384 + 32), "r"(~pack_bf16(c[1], c[3])) : "memory");
                asm volatile("bar.arrive 4, 256;" ::: "memory");
                asm volatile("bar.arrive 6, 256;" ::: "memory");
                DBG(8, 0);
                if (s > 0) local_pv(s - 1, true); else asm volatile("bar.arrive 9, 256;" ::: "memory");
                DBG(28, 0);
                asm volatile("st.relaxed.gpu.global.u32 [%0], %1;" :: "l"(wp + ((s + 2) & 3) * 16384), "r"(0) : "memory");
                asm volatile("st.relaxed.gpu.global.u32 [%0], %1;" :: "l"(wp + ((s + 2) & 3) * 16384 + 32), "r"(0) : "memory");
                if (tid == 0 && s + 2 < NSEG) {
                    mbar_expect_tx(bar_x + 8 * par, 32768);
                    tma_load_2d_mc(sb + CO_XB + par * 32768 + rank * 4096, &P.mapX, bar_x + 8 * par, rank * 64, (s + 2) * SEGL, (uint16_t)0xff);
                }
                __syncwarp();
            } else {
                const uint32_t vaddr = pin(sb + CO_T + par * CH_TP + 2 * CH_TW + (lane & 15) * 128 + (((t4 * 2 + (lane >> 4)) ^ (lane & 7)) << 4));
                const uint32_t dsta = pin(sb + CO_OB + t4 * 256 + (qc >> 1) * 128 + qd * 16 + (qc & 1) * 8);
                fence_async_smem();
                uint32_t vb[3][4];
                auto load_v = [&]() {
                    asm volatile("bar.sync 3, 256;" ::: "memory");
#pragma unroll
                    for (int k = 0; k < 3; k++) ldmatrix_x4_trans(vb[k][0], vb[k][1], vb[k][2], vb[k][3], vaddr + k * 2048);
                };
                if (CH_VPOS == 0) load_v();
                mbar_wait_cl(bar_sc, par);
                DBG(4, 4);
                float v[10];
#pragma unroll
                for (int j = 0; j < 5; j++) {
                    const float2 a = lds64f(aL + CO_SC + j * 256), b = lds64f(aL + CO_SC + 1280 + j * 256);
                    v[2 * j] = a.x + b.x; v[2 * j + 1] = a.y + b.y;
                }
                if (CH_VPOS == 1) load_v();
                float mx = fmaxf(fmaxf(fmaxf(v[0], v[1]), fmaxf(v[2], v[3])), fmaxf(fmaxf(v[4], v[5]), fmaxf(v[6], v[7])));
                mx = fmaxf(mx, fmaxf(v[8], v[9]));
                mx = fmaxf(mx, __shfl_xor_sync(0xffffffff, mx, 1));
                mx = fmaxf(mx, __shfl_xor_sync(0xffffffff, mx, 2));
                if (CH_VPOS == 2) load_v();
                DBG(19, 4);
                mx *= CH_SC;
#pragma unroll
                for (int j = 0; j < 10; j++) v[j] = ex2f(fmaf(v[j], CH_SC, -mx));
                float c0[4] = {0.f, 0.f, 0.f, 0.f}, c1[4] = {0.f, 0.f, 0.f, 0.f}, cs[4] = {0.f, 0.f, 0.f, 0.f};
#pragma unroll
                for (int k = 0; k < 3; k++) {
                    const uint32_t p0 = pack_bf16(v[4 * k], v[4 * k + 1]), p1 = k < 2 ? pack_bf16(v[4 * k + 2], v[4 * k + 3]) : 0u;
                    mma_16816(cs, p0, 0u, p1, 0u, 0x3f803f80u, 0x3f803f80u);
                    mma_16816(c0, p0, 0u, p1, 0u, vb[k][0], vb[k][1]);
                    mma_16816(c1, p0, 0u, p1, 0u, vb[k][2], vb[k][3]);
                }
                float inv;
                asm volatile("rcp.approx.ftz.f32 %0, %1;" : "=f"(inv) : "f"(cs[0]));
                const uint32_t b0 = pack_bf16(c0[0] * inv, c0[1] * inv), b1 = pack_bf16(c1[0] * inv, c1[1] * inv);
                DBG(20, 4);
#pragma unroll
                for (int i = 0; i < 8; i++) {
                    const int dr = (rank + i) & 7;
                    st_async_v2(remote(dsta + i * 1024, dr), b0, b1, remote(bar_o + 8 * (i * CH_OG / 8), dr));
                    if (i == 0) asm volatile("bar.arrive 7, 256;" ::: "memory");
                }
                DBG(5, 4);
                mbar_wait(bar_x + 8 * (par ^ 1), ((s + 1) >> 1) & 1);
                asm volatile("bar.sync 4, 256;" ::: "memory");
                local_scores(s);
            }
            pass32(par ^ 1);
            DBG(21, 0);
            wgmma_wait<0>();
            store32(aO + (par ^ 1) * CH_TP + CO_T);
            if (wg == 0) fence_async_smem();
            DBG(22, 0);
        }
        fence_async_smem();
        asm volatile("bar.sync 1, 256;" ::: "memory");
        if (warp < 5) asm volatile("bar.arrive 2, 288;" ::: "memory");
        if (wg == 0) {
            if (tid == 96) { mbar_wait(bar_l, 0); mbar_expect_tx(bar_l, 4096); store_ctx(NSEG - 3); asm volatile("cp.async.bulk.wait_group.read 0;" ::: "memory"); }
            __syncwarp();
            asm volatile("bar.sync 7, 256;" ::: "memory");
            local_pv(NSEG - 2, false);
            asm volatile("bar.arrive 6, 256;" ::: "memory");
            if (tid == 96) { store_ctx(NSEG - 2); asm volatile("cp.async.bulk.wait_group.read 0;" ::: "memory"); }
            __syncwarp();
            asm volatile("bar.sync 8, 256;" ::: "memory");
            local_pv(NSEG - 1, false);
            if (tid == 96) {
                store_ctx(NSEG - 1);
                asm volatile("cp.async.bulk.wait_group 0;" ::: "memory");
                signal_ctx(15, 16);
            }
            uint32_t* wp = g_xbuf + 16384 + (size_t)rank * 2048 + C * 256 + tid * 2;
            *reinterpret_cast<uint2*>(wp) = make_uint2(0u, 0u);
        } else {
            asm volatile("bar.sync 3, 256;" ::: "memory");
            asm volatile("bar.arrive 7, 256;" ::: "memory");
            local_scores(NSEG - 1);
        }
    } else {
        auto local_softmax = [&](int s) {
            float v[10];
            mbar_wait_cl(bar_l, s & 1);
            const uint32_t off = 2 * aL - sb + t4 * 1280;
            {
                const uint4 a0 = lds128(off + (s & 1) * 5120 + CO_LS), b0 = lds128(off + CO_LO), a1 = lds128(off + (s & 1) * 5120 + CO_LS + 512), b1 = lds128(off + CO_LO + 512);
                const float2 a2 = lds64f(aL + t4 * 1280 + (s & 1) * 5120 + CO_LS + 1024), b2 = lds64f(aL + t4 * 1280 + CO_LO + 1024);
                auto f = [](uint32_t a, uint32_t b) { return __uint_as_float(a) + __uint_as_float(b); };
                v[0] = f(a0.x, b0.x); v[1] = f(a0.y, b0.y); v[2] = f(a0.z, b0.z); v[3] = f(a0.w, b0.w);
                v[4] = f(a1.x, b1.x); v[5] = f(a1.y, b1.y); v[6] = f(a1.z, b1.z); v[7] = f(a1.w, b1.w);
                v[8] = a2.x + b2.x; v[9] = a2.y + b2.y;
            }
            const int lim = t4 * 8 + 2 * qc - qd;
#pragma unroll
            for (int n = 0; n < 4; n++) {
                if (8 * n > lim) v[2 * n] = -INFINITY;
                if (8 * n > lim + 1) v[2 * n + 1] = -INFINITY;
            }
            float m0 = fmaxf(fmaxf(fmaxf(v[0], v[2]), fmaxf(v[4], v[6])), v[8]), m1 = fmaxf(fmaxf(fmaxf(v[1], v[3]), fmaxf(v[5], v[7])), v[9]);
#pragma unroll
            for (int o = 4; o < 32; o *= 2) { m0 = fmaxf(m0, __shfl_xor_sync(0xffffffff, m0, o)); m1 = fmaxf(m1, __shfl_xor_sync(0xffffffff, m1, o)); }
            m0 *= CH_SC; m1 *= CH_SC;
#pragma unroll
            for (int n = 0; n < 5; n++) { v[2 * n] = ex2f(fmaf(v[2 * n], CH_SC, -m0)); v[2 * n + 1] = ex2f(fmaf(v[2 * n + 1], CH_SC, -m1)); }
            float s0 = ((v[0] + v[2]) + (v[4] + v[6])) + v[8], s1 = ((v[1] + v[3]) + (v[5] + v[7])) + v[9];
#pragma unroll
            for (int o = 4; o < 32; o *= 2) { s0 += __shfl_xor_sync(0xffffffff, s0, o); s1 += __shfl_xor_sync(0xffffffff, s1, o); }
            asm("rcp.approx.ftz.f32 %0, %0;" : "+f"(s0));
            asm("rcp.approx.ftz.f32 %0, %0;" : "+f"(s1));
            const uint32_t pa = 2 * aL - sb + CO_P + t4 * 768;
            stmatrix_x4_trans(pa, pack_bf16(v[0] * s0, v[1] * s1), pack_bf16(v[2] * s0, v[3] * s1), pack_bf16(v[4] * s0, v[5] * s1), pack_bf16(v[6] * s0, v[7] * s1));
            asm volatile("stmatrix.sync.aligned.m8n8.x1.trans.shared.b16 [%0], {%1};" :: "r"(pa + 512), "r"(pack_bf16(v[8] * s0, v[9] * s1)) : "memory");
            fence_async_smem();
            DBG(7, 8);
        };
#pragma unroll 1
        for (int s = 0; s < NSEG; s++) {
            const uint32_t par = s & 1;
            if (s > 0) local_softmax(s - 1);
            load_wa();
            if (s < NSEG - 1) mbar_wait(bar_x + 8 * (par ^ 1), ((s + 1) >> 1) & 1);
            asm volatile("bar.sync 2, 288;" ::: "memory");
            DBG(23, 8);
            mem_proj(s, false, true);
            asm volatile("bar.arrive 3, 256;" ::: "memory");
            if (s == NSEG - 1) break;
            DBG(24, 8);
            if (CH_V1 > 0) pass32(par ^ 1, 0, CH_V1);
            asm volatile("bar.sync 7, 256;" ::: "memory");
            pass32(par ^ 1, CH_V1, CH_V2);
            DBG(26, 8);
            asm volatile("bar.sync 6, 256;" ::: "memory");
            const uint2* xb = reinterpret_cast<const uint2*>(g_xbuf + (s & 3) * 16384 + (size_t)rank * 2048 + t4 * 64) + lane;
            uint2 p[8];
            auto poll_all = [&]() {
#pragma unroll
                for (int k = 0; k < 8; k++)
                    asm volatile("ld.relaxed.gpu.global.v2.u32 {%0, %1}, [%2];" : "=r"(p[k].x), "=r"(p[k].y) : "l"(xb + k * 128) : "memory");
                DBG(17, 8);
            };
            if (CH_V3 > CH_V2) { pace(CH_V3_DELAY); pass32(par ^ 1, CH_V2, CH_V3); }
            if (CH_VST == 0) {
                asm volatile("bar.sync 9, 256;" ::: "memory");
                wgmma_wait<0>();
                store32(aO + (par ^ 1) * CH_TP + CO_T);
                DBG(27, 8);
            }
            pace(CH_POLL_DELAY);
            auto lo = [](uint32_t u) { return __uint_as_float(~u << 16); };
            auto hi = [](uint32_t u) { return __uint_as_float(~u & 0xffff0000u); };
            poll_all();
            for (int it = 0; it < WAIT_LIMIT / 4; it++) {
                uint32_t bad = 0;
#pragma unroll
                for (int k = 0; k < 8; k++) bad |= (min(p[k].x, p[k].y) == 0u ? 1u : 0u) << k;
                if (__all_sync(0xffffffff, bad == 0u)) break;
                if (it == 0) DBG(12, 8);
                if (it == 1) DBG(14, 8);
                if (it == 2) DBG(15, 8);
#pragma unroll
                for (int k = 0; k < 8; k++)
                    if (bad & (1u << k))
                        asm volatile("ld.relaxed.gpu.global.v2.u32 {%0, %1}, [%2];" : "=r"(p[k].x), "=r"(p[k].y) : "l"(xb + k * 128) : "memory");
            }
            DBG(9, 8);
            const uint32_t m0 = pack_bf16(((lo(p[0].x) + lo(p[1].x)) + (lo(p[2].x) + lo(p[3].x))) + ((lo(p[4].x) + lo(p[5].x)) + (lo(p[6].x) + lo(p[7].x))),
                                          ((hi(p[0].x) + hi(p[1].x)) + (hi(p[2].x) + hi(p[3].x))) + ((hi(p[4].x) + hi(p[5].x)) + (hi(p[6].x) + hi(p[7].x))));
            const uint32_t m1 = pack_bf16(((lo(p[0].y) + lo(p[1].y)) + (lo(p[2].y) + lo(p[3].y))) + ((lo(p[4].y) + lo(p[5].y)) + (lo(p[6].y) + lo(p[7].y))),
                                          ((hi(p[0].y) + hi(p[1].y)) + (hi(p[2].y) + hi(p[3].y))) + ((hi(p[4].y) + hi(p[5].y)) + (hi(p[6].y) + hi(p[7].y))));
            const int row = t4 * 2 + (lane >> 4);
            const uint32_t dsta = sb + CO_MB + row * 128 + ((((lane & 15) >> 1) ^ row) << 4) + (lane & 1) * 8;
#pragma unroll
            for (int i = 0; i < 8; i++) {
                const int dr = (rank + (i & 1) * 4 + (i >> 1)) & 7;
                st_async_v2(remote(dsta + i * 1024, dr), m0, m1, remote(bar_mem + 8 * (i >> 1), dr));
            }
            DBG(10, 8);
            if (CH_VST == 1) {
                if (CH_V3 < 32) pass32(par ^ 1, CH_V3, 32);
                asm volatile("bar.sync 9, 256;" ::: "memory");
                wgmma_wait<0>();
                store32(aO + (par ^ 1) * CH_TP + CO_T);
                DBG(27, 8);
            }
        }
        asm volatile("bar.sync 6, 256;" ::: "memory");
        local_softmax(NSEG - 1);
        asm volatile("bar.arrive 8, 256;" ::: "memory");
    }
    __syncthreads();
    cluster_sync_all();
    TS_END(2);
}

struct Proj2Params {
    CUtensorMap mapA[2];
    CUtensorMap mapW[3];
    bf16* out[3];
};
#define P2T(i)
#define P2_NOMMA 0
#define P2_NOLOAD 0
constexpr int P2_STAGES = 6;
constexpr int P2_SMEM = 131072 + P2_STAGES * 16384 + 1024 + 1024;
constexpr int P2_ITEMS = 168 + 48;

__device__ __forceinline__ int p2_reps(int t) { return t >= 168 ? 1 : 2; }
__device__ __forceinline__ void p2_tile(int t, int w, int& z, int& mp, int& head) {
    if (t >= 168) { w += ((t - 168) & 1) * 2; t = 168 + ((t - 168) >> 1); }
    const int hq = t / 24, v = t % 24;
    mp = v & 7;
    if (v < 16) { head = hq * 4 + (v >> 3) * 2 + (w >> 1); z = 1 + (w & 1); }
    else { head = hq * 4 + w; z = 0; }
}
__device__ __forceinline__ void mbar_arrive_remote(uint32_t bar_cluster_addr) {
    asm volatile("mbarrier.arrive.release.cluster.shared::cluster.b64 _, [%0];" :: "r"(bar_cluster_addr) : "memory");
}
__device__ __forceinline__ void mbar_arrive_cl(uint32_t bar_cluster_addr) {
    asm volatile("mbarrier.arrive.shared::cluster.b64 _, [%0];" :: "r"(bar_cluster_addr) : "memory");
}
__device__ __forceinline__ void mbar_wait_acq_cluster(uint32_t bar, uint32_t parity) {
    asm volatile(
        "{\n"
        ".reg .pred p, q;\n"
        ".reg .u32 c;\n"
        "mov.u32 c, 0;\n"
        "WAIT_LOOP_C:\n"
        "mbarrier.try_wait.parity.acquire.cluster.shared::cta.b64 p, [%0], %1;\n"
        "@p bra WAIT_DONE_C;\n"
        "add.u32 c, c, 1;\n"
        "setp.lt.u32 q, c, 4000000;\n"
        "@q bra WAIT_LOOP_C;\n"
        "WAIT_DONE_C:\n"
        "}\n" :: "r"(bar), "r"(parity) : "memory");
}
__device__ __forceinline__ uint4 quad_transpose(uint32_t p0, uint32_t p1, uint32_t p2, uint32_t p3, int lane) {
    const bool o1 = lane & 1, o2 = lane & 2;
    uint32_t s0 = o1 ? p0 : p1, s1 = o1 ? p2 : p3;
    s0 = __shfl_xor_sync(0xffffffff, s0, 1); s1 = __shfl_xor_sync(0xffffffff, s1, 1);
    const uint32_t a_lo = o1 ? s0 : p0, a_hi = o1 ? p1 : s0, b_lo = o1 ? s1 : p2, b_hi = o1 ? p3 : s1;
    uint32_t t0 = o2 ? a_lo : b_lo, t1 = o2 ? a_hi : b_hi;
    t0 = __shfl_xor_sync(0xffffffff, t0, 2); t1 = __shfl_xor_sync(0xffffffff, t1, 2);
    return o2 ? make_uint4(t0, t1, b_lo, b_hi) : make_uint4(a_lo, a_hi, t0, t1);
}
#define P2_PACE 35
#define P2_PACE2 0
template <bool PERM, int PACE = 0>
__device__ __forceinline__ void store_frag_128(const float (&acc)[64], bf16* obase, int lane) {
#pragma unroll
    for (int rr = 0; rr < 2; rr++)
#pragma unroll
        for (int g = 0; g < 4; g++) {
            const float* a = &acc[g * 16 + rr * 2];
            const uint32_t p0 = pack_bf16(a[0], a[1]), p1 = pack_bf16(a[4], a[5]), p2 = pack_bf16(a[8], a[9]), p3 = pack_bf16(a[12], a[13]);
            *reinterpret_cast<uint4*>(obase + (size_t)(rr * 8) * HD + g * 32) = PERM ? make_uint4(p0, p1, p2, p3) : quad_transpose(p0, p1, p2, p3, lane);
            pace(PACE);
        }
}
__global__ void __cluster_dims__(2, 1, 1) __launch_bounds__(384, 1) proj2_kernel(const __grid_constant__ Proj2Params P) {
    extern __shared__ uint8_t smem_raw[];
    const uint32_t sbase = (smem_u32(smem_raw) + 1023) & ~1023u;
    const uint32_t sA = sbase, sB = sbase + 131072, sC = sB + P2_STAGES * 16384;
    const uint32_t bars = sC;
    const uint32_t a_full = bars, a_empty = bars + 64, b_full = bars + 128, b_empty = b_full + 8 * P2_STAGES;
    const uint32_t item_bar = b_empty + 8 * P2_STAGES, item_in = item_bar + 16, slot = item_in + 16;
    const uint32_t note_bar = slot + 16, note_free = note_bar + 64, note = note_free + 64;
    const int warp = threadIdx.x >> 5, lane = threadIdx.x & 31;
    const uint32_t rank = cluster_ctarank();
    TS_BEGIN(0);
    if (threadIdx.x == 0) {
        for (int i = 0; i < 8; i++) { mbar_init(a_full + 8 * i, 1); mbar_init(a_empty + 8 * i, 2); }
        for (int i = 0; i < P2_STAGES; i++) { mbar_init(b_full + 8 * i, 1); mbar_init(b_empty + 8 * i, 2); }
        mbar_init(item_bar, 1); mbar_init(item_bar + 8, 1); mbar_init(item_in, 2); mbar_init(item_in + 8, 2);
        for (int i = 0; i < 8; i++) { mbar_init(note_bar + 8 * i, 1); mbar_init(note_free + 8 * i, 1); }
        asm volatile("fence.mbarrier_init.release.cluster;" ::: "memory");
    }
    __syncthreads();
    cluster_sync_all();
    pdl_launch_dependents();
    if (warp == 9) {
        if (lane == 0) {
            for (int n = 0;; n++) {
                const int e = (n & 1) * 4 + ((n >> 1) & 3);
                mbar_wait(note_bar + 8 * e, (n >> 3) & 1);
                int m;
                asm volatile("ld.shared.s32 %0, [%1];" : "=r"(m) : "r"(note + e * 4) : "memory");
                mbar_arrive(note_free + 8 * e);
                if (m < 0) break;
                signal_ctr(m);
            }
        }
    } else if (warp == 10) {
        if (lane == 0) {
            auto publish = [&](int ic, int tq) {
                const int t = tq < P2_ITEMS ? tq : -1;
                asm volatile("st.shared.s32 [%0], %1;" :: "r"(slot + (ic & 3) * 4), "r"(t) : "memory");
                mbar_arrive(item_bar + 8 * (ic & 1));
                st_async_b32(mapa_u32(slot + (ic & 3) * 4, 1), (uint32_t)t, mapa_u32(item_bar + 8 * (ic & 1), 1));
            };
            const int npair = (int)(gridDim.x >> 1), pair = (int)(blockIdx.x >> 1);
            if (rank == 0) publish(0, pair);
            for (int ic = 0;; ic++) {
                if (rank == 1) mbar_expect_tx(item_bar + 8 * (ic & 1), 4);
                mbar_wait(item_bar + 8 * (ic & 1), (ic >> 1) & 1);
                int t;
                asm volatile("ld.shared.s32 %0, [%1];" : "=r"(t) : "r"(slot + (ic & 3) * 4) : "memory");
                if (t < 0) break;
                int z0, mp, h0;
                p2_tile(t, 0, z0, mp, h0);
                const int aidx = z0 >= 1 ? 1 : 0;
                const int m0 = (2 * mp + (int)rank) * 128;
                for (int k = 0; k < 8; k++) {
                    mbar_wait(a_empty + 8 * k, (ic & 1) ^ 1);
                    if (P2_NOLOAD) mbar_arrive(a_full + 8 * k); else {
                    mbar_expect_tx(a_full + 8 * k, 16384);
                    tma_load_2d(sA + k * 16384, &P.mapA[aidx], a_full + 8 * k, k * 64, m0); }
                }
                if (rank == 0) {
                    mbar_wait(item_in + 8 * (ic & 1), (ic >> 1) & 1);
                    publish(ic + 1, ic == 0 ? npair + pair : 2 * npair + (int)atomicAdd(&g_ctr[CT_PROJ], 1u));
                }
            }
        }
    } else if (warp == 8 || warp == 11) {
        if (lane == 0) {
            const int par2 = warp == 8 ? 0 : 1;
            int it = 0; uint32_t bph = 0;
            for (int ic = 0;; ic++) {
                mbar_wait(item_bar + 8 * (ic & 1), (ic >> 1) & 1);
                int t;
                asm volatile("ld.shared.s32 %0, [%1];" : "=r"(t) : "r"(slot + (ic & 3) * 4) : "memory");
                if (t < 0) break;
                const int nt = 2 * p2_reps(t);
                for (int w = 0; w < nt; w++) {
                    int z, mp, hd;
                    p2_tile(t, w, z, mp, hd);
                    for (int k = 0; k < 8; k++) {
                        const int s = it; const uint32_t phb = bph;
                        if (++it == P2_STAGES) { it = 0; bph ^= 1; }
                        if ((k & 1) != par2) continue;
                        mbar_wait(b_empty + 8 * s, phb ^ 1);
                        if (P2_NOLOAD) { mbar_arrive(b_full + 8 * s); continue; }
                        mbar_expect_tx(b_full + 8 * s, 16384);
                        tma_load_2d_mc(sB + s * 16384 + rank * 8192, &P.mapW[z], b_full + 8 * s, hd * 128 + (int)rank * 64, k * 64, (uint16_t)3);
                    }
                }
            }
        }
    } else {
        const int wg = warp >> 2;
        float acc[2][64];
        const uint32_t a_lo = desc_lo(sA, 16), b_lo0 = desc_lo(sB, 8192);
        const bool elected = (threadIdx.x & 127) == 0;
        int s = (wg * 8) % P2_STAGES;
        uint32_t ph = ((wg * 8) / P2_STAGES) & 1;
        int nnote = 0;
        if (wg == 1) asm volatile("bar.arrive 3, 256;" ::: "memory");
        for (int ic = 0;; ic++) {
            mbar_wait(item_bar + 8 * (ic & 1), (ic >> 1) & 1);
            int t;
            asm volatile("ld.shared.s32 %0, [%1];" : "=r"(t) : "r"(slot + (ic & 3) * 4) : "memory");
            P2T(7);
            if (wg == 0 && t < 0) {
                if (elected) {
                    const int e = nnote & 3;
                    mbar_wait(note_free + 8 * e, ((nnote >> 2) & 1) ^ 1);
                    asm volatile("st.shared.s32 [%0], %1;" :: "r"(note + e * 4), "r"(-1) : "memory");
                    mbar_arrive(note_bar + 8 * e);
                }
            }
            if (t < 0) break;
            const int reps = p2_reps(t);
#pragma unroll 1
            for (int rp = 0; rp < reps; rp++) {
            const bool first = rp == 0, last = rp == reps - 1;
            int z, mp, head;
            p2_tile(t, rp * 2 + wg, z, mp, head);
            asm volatile("bar.sync %0, 256;" :: "r"(3 + wg) : "memory");
            P2T(0);
            if (wg == 1 && last && elected) mbar_arrive_cl(mapa_u32(item_in + 8 * (ic & 1), 0));
            int sprev = 0;
#pragma unroll
            for (int k = 0; k < 8; k++) {
                if (k == 0) P2T(5);
                if (wg == 0 && first) mbar_wait(a_full + 8 * k, ic & 1);
                if (k == 0) P2T(6);
                mbar_wait(b_full + 8 * s, ph);
                if (k == 7) asm volatile("bar.arrive %0, 256;" :: "r"(4 - wg) : "memory");
                if (k == 0) P2T(1);
                if (k == 7) P2T(2);
                const uint32_t b_lo = b_lo0 + s * 1024;
                wgmma_fence();
#pragma unroll
                for (int kk = 0; kk < (P2_NOMMA ? 1 : 4); kk++) {
                    wgmma_ss_n128_lo<1>(acc[0], a_lo + k * 1024 + kk * 2, b_lo + kk * 128, (k | kk) != 0);
                    wgmma_ss_n128_lo<1>(acc[1], a_lo + k * 1024 + 512 + kk * 2, b_lo + kk * 128, (k | kk) != 0);
                }
                wgmma_commit();
                if (k > 0) {
                    wgmma_wait<1>();
                    if (elected) {
                        const uint32_t e = b_empty + 8 * sprev;
                        mbar_arrive_cl(mapa_u32(e, 0)); mbar_arrive_cl(mapa_u32(e, 1));
                        if (last) mbar_arrive(a_empty + 8 * (k - 1));
                    }
                }
                sprev = s;
                if (++s == P2_STAGES) { s = 0; ph ^= 1; }
            }
            wgmma_wait<0>();
            P2T(3);
            if (elected) {
                const uint32_t e = b_empty + 8 * sprev;
                mbar_arrive_cl(mapa_u32(e, 0)); mbar_arrive_cl(mapa_u32(e, 1));
                if (last) mbar_arrive(a_empty + 8 * 7);
            }
            s += 8 % P2_STAGES; ph ^= (8 / P2_STAGES) & 1;
            if (s >= P2_STAGES) { s -= P2_STAGES; ph ^= 1; }
            const int m0 = (2 * mp + (int)rank) * 128;
            bf16* obase = P.out[z] + ((size_t)head * SEQ + m0 + (warp & 3) * 16 + (lane >> 2)) * HD + (lane & 3) * 8;
            store_frag_128<true, P2_PACE>(acc[0], obase, lane); store_frag_128<true, P2_PACE>(acc[1], obase + (size_t)64 * HD, lane);
            P2T(4);
            {
                asm volatile("bar.sync %0, 128;" :: "r"(1 + wg) : "memory");
                if (elected) {
                    const int e = wg * 4 + (nnote & 3);
                    mbar_wait(note_free + 8 * e, ((nnote >> 2) & 1) ^ 1);
                    asm volatile("st.shared.s32 [%0], %1;" :: "r"(note + e * 4), "r"(CT_AP + (head >> 1)) : "memory");
                    mbar_arrive(note_bar + 8 * e);
                }
                nnote++;
            }
            }
        }
        TS_END(0);
    }
    __syncthreads();
    cluster_sync_all();
}

struct OutParams {
    CUtensorMap mapCtx[2];
    CUtensorMap mapWo[2];
    CUtensorMap mapPart;
};
__device__ float g_part[4 * SEQ * DM];

#define OT(i)
constexpr int O2_STAGES = 4;
constexpr int O2_SMEM = O2_STAGES * 49152 + 1024 + 256;

__global__ void __cluster_dims__(2, 1, 1) __launch_bounds__(352, 1)
out2_kernel(const __grid_constant__ OutParams P, const bf16* __restrict__ x, const bf16* __restrict__ gate_w, bf16* __restrict__ out) {
    extern __shared__ uint8_t smem_raw[];
    const uint32_t sbase = (smem_u32(smem_raw) + 1023) & ~1023u;
    const uint32_t bar_full = sbase + O2_STAGES * 49152, bar_empty = bar_full + 8 * O2_STAGES;
    __shared__ float s_gate[32];
    const int warp = threadIdx.x >> 5, lane = threadIdx.x & 31;
    const uint32_t rank = cluster_ctarank();
    const int cid = blockIdx.x >> 1;
    const int late = cid >> 5, mp = (cid >> 1) & 7, nh = cid & 1;
    const int b = late ? 1 - ((cid >> 4) & 1) : (cid >> 4) & 1, kq = b * 2 + late;
    const int h0 = late ? O2_HE : 0;
    const int KT = late ? 2 * (NH - O2_HE) : 2 * O2_HE;
    const int m0 = (2 * mp + (int)rank) * 128, n0 = nh * 256;
    TS_BEGIN(4);
    OT(0);
    if (threadIdx.x == 0) {
        for (int i = 0; i < O2_STAGES; i++) { mbar_init(bar_full + 8 * i, 1); mbar_init(bar_empty + 8 * i, 4); }
        asm volatile("fence.mbarrier_init.release.cluster;" ::: "memory");
    }
    __syncthreads();
    asm volatile("barrier.cluster.arrive.release.aligned;" ::: "memory");
    if (threadIdx.x == 256) wait_ctr((b == 0 ? CT_CA : CT_CB) + (m0 >> 7) * 2 + late, (unsigned)KT);
    __syncwarp();
    asm volatile("barrier.cluster.wait.acquire.aligned;" ::: "memory");
    if (warp >= 8) {
        if (lane == 0) {
            int s = 0; uint32_t ph = 0;
            for (int i = 0; i < KT; i++) {
                mbar_wait(bar_empty + 8 * s, ph ^ 1);
                const uint32_t sa = sbase + s * 49152;
                const int head = h0 + (i >> 1), dk = (i & 1) * 64;
                if (warp == 8) {
                    mbar_expect_tx(bar_full + 8 * s, 49152);
                    tma_load_2d(sa, &P.mapCtx[b], bar_full + 8 * s, dk, head * SEQ + m0);
                } else {
                    const int j = (int)rank * 2 + (warp - 9);
                    tma_load_2d_mc(sa + 16384 + j * 8192, &P.mapWo[b], bar_full + 8 * s, n0 + j * 64, head * HD + dk, (uint16_t)3);
                }
                if (++s == O2_STAGES) { s = 0; ph ^= 1; }
            }
        }
    } else {
        const int wg = warp >> 2;
        const bool elected = (threadIdx.x & 127) == 0;
        float acc[128];
        {
            const int r = m0 + kq * 32 + (threadIdx.x >> 3);
            float sum = 0.f;
#pragma unroll
            for (int c = 0; c < 8; c++) {
                const int col = c * 64 + (threadIdx.x & 7) * 8;
                const uint4 xv = __ldg(reinterpret_cast<const uint4*>(x + (size_t)r * DM + col));
                const uint4 gv = __ldg(reinterpret_cast<const uint4*>(gate_w + col));
                const bf16* xp = reinterpret_cast<const bf16*>(&xv);
                const bf16* gp = reinterpret_cast<const bf16*>(&gv);
#pragma unroll
                for (int e = 0; e < 8; e++)
                    sum += __bfloat162float(__float2bfloat16(__bfloat162float(xp[e]) * __bfloat162float(gp[e])));
            }
            sum += __shfl_xor_sync(0xffffffff, sum, 1);
            sum += __shfl_xor_sync(0xffffffff, sum, 2);
            sum += __shfl_xor_sync(0xffffffff, sum, 4);
            sum = __bfloat162float(__float2bfloat16(sum));
            if ((threadIdx.x & 7) == 0) s_gate[threadIdx.x >> 3] = __bfloat162float(__float2bfloat16(1.f / (1.f + __expf(-sum))));
        }
        int s = 0, sprev = 0; uint32_t ph = 0;
#pragma unroll 1
        for (int i = 0; i < KT; i++) {
            mbar_wait(bar_full + 8 * s, ph);
            if (i == 0) OT(1);
            if (i == 8) OT(2);
            const uint32_t sa = sbase + s * 49152 + wg * 8192, sb = sbase + s * 49152 + 16384;
            wgmma_fence();
#pragma unroll
            for (int kk = 0; kk < 4; kk++)
                wgmma_ss_n256_tb(acc, make_desc(sa + kk * 32, 16, 1024), make_desc(sb + kk * 2048, 8192, 1024), (i | kk) != 0);
            wgmma_commit();
            if (i > 0) {
                wgmma_wait<1>();
                if (elected) { const uint32_t e = bar_empty + 8 * sprev; mbar_arrive_cl(mapa_u32(e, 0)); mbar_arrive_cl(mapa_u32(e, 1)); }
            }
            sprev = s;
            if (++s == O2_STAGES) { s = 0; ph ^= 1; }
        }
        wgmma_wait<0>();
        OT(3);
        {
            const int r = wg * 64 + (warp & 3) * 16 + (lane >> 2);
            if ((warp >> 1) == kq) {
#pragma unroll
                for (int j = 0; j < 32; j++) {
                    const uint32_t a = sbase + (j >> 2) * 16384 + r * 128 + ((((j & 3) * 2 + ((lane & 3) >> 1)) ^ (r & 7)) << 4) + (lane & 1) * 8;
                    asm volatile("st.shared.v2.f32 [%0], {%1, %2};" :: "r"(a), "f"(acc[j * 4 + 0]), "f"(acc[j * 4 + 1]) : "memory");
                    asm volatile("st.shared.v2.f32 [%0], {%1, %2};" :: "r"(a + 1024), "f"(acc[j * 4 + 2]), "f"(acc[j * 4 + 3]) : "memory");
                }
            } else {
                float* pp = g_part + ((size_t)kq * SEQ + m0 + r) * DM + n0 + (lane & 3) * 2;
#pragma unroll
                for (int j = 0; j < 32; j++) {
                    *reinterpret_cast<float2*>(pp + j * 8) = make_float2(acc[j * 4 + 0], acc[j * 4 + 1]);
                    *reinterpret_cast<float2*>(pp + 8 * DM + j * 8) = make_float2(acc[j * 4 + 2], acc[j * 4 + 3]);
                }
            }
        }
        asm volatile("bar.sync 1, 256;" ::: "memory");
        OT(4);
        unsigned int* ctr = &g_ctr[CT_OP + (2 * mp + (int)rank) * 2 + nh];
        if (threadIdx.x == 0) {
            asm volatile("fence.proxy.async;" ::: "memory");
            __threadfence();
            atomicAdd(ctr, 1u);
            unsigned int v; int it = 0;
            do { asm volatile("ld.acquire.gpu.global.u32 %0, [%1];" : "=r"(v) : "l"(ctr) : "memory"); } while (v < 4u && ++it < WAIT_LIMIT);
        }
        asm volatile("bar.sync 1, 256;" ::: "memory");
        OT(5);
        {
            const int c8 = threadIdx.x & 31, r0 = threadIdx.x >> 5;
            float4 u[4][3][2];
#pragma unroll
            for (int i = 0; i < 4; i++)
#pragma unroll
                for (int q = 1; q < 4; q++) {
                    const float4* p4 = reinterpret_cast<const float4*>(g_part + ((size_t)((kq + q) & 3) * SEQ + m0 + kq * 32 + r0 + i * 8) * DM + n0 + c8 * 8);
                    asm volatile("ld.relaxed.gpu.global.v4.f32 {%0, %1, %2, %3}, [%4];"
                                 : "=f"(u[i][q - 1][0].x), "=f"(u[i][q - 1][0].y), "=f"(u[i][q - 1][0].z), "=f"(u[i][q - 1][0].w) : "l"(p4) : "memory");
                    asm volatile("ld.relaxed.gpu.global.v4.f32 {%0, %1, %2, %3}, [%4];"
                                 : "=f"(u[i][q - 1][1].x), "=f"(u[i][q - 1][1].y), "=f"(u[i][q - 1][1].z), "=f"(u[i][q - 1][1].w) : "l"(p4 + 1) : "memory");
                }
#pragma unroll
            for (int i = 0; i < 4; i++) {
                const int rl = kq * 32 + r0 + i * 8;
                const float ga = s_gate[r0 + i * 8], gb = 1.f - ga;
                float o8[8];
#pragma unroll
                for (int hf = 0; hf < 2; hf++) {
                    float4 own;
                    const uint32_t a = sbase + (c8 >> 2) * 16384 + rl * 128 + ((((c8 & 3) * 2 + hf) ^ (rl & 7)) << 4);
                    asm volatile("ld.shared.v4.f32 {%0, %1, %2, %3}, [%4];" : "=f"(own.x), "=f"(own.y), "=f"(own.z), "=f"(own.w) : "r"(a) : "memory");
                    const int qp = ((kq ^ 1) - kq) & 3;
                    const float4 pa = qp == 1 ? u[i][0][hf] : u[i][2][hf];
                    const float4 o1 = u[i][1][hf];
                    const float4 o2 = qp == 1 ? u[i][2][hf] : u[i][0][hf];
                    const float gm = b == 0 ? ga : gb, go = b == 0 ? gb : ga;
                    o8[hf * 4 + 0] = gm * (own.x + pa.x) + go * (o1.x + o2.x);
                    o8[hf * 4 + 1] = gm * (own.y + pa.y) + go * (o1.y + o2.y);
                    o8[hf * 4 + 2] = gm * (own.z + pa.z) + go * (o1.z + o2.z);
                    o8[hf * 4 + 3] = gm * (own.w + pa.w) + go * (o1.w + o2.w);
                }
                *reinterpret_cast<uint4*>(out + (size_t)(m0 + rl) * DM + n0 + c8 * 8) =
                    make_uint4(pack_bf16(o8[0], o8[1]), pack_bf16(o8[2], o8[3]), pack_bf16(o8[4], o8[5]), pack_bf16(o8[6], o8[7]));
            }
        }
        OT(6);
        if (threadIdx.x == 0) {
            const unsigned int tk = atomicAdd(&g_ctr[CT_FIN], 1u);
            asm volatile("st.shared.u32 [%0], %1;" :: "r"(bar_empty + 8 * O2_STAGES), "r"(tk) : "memory");
        }
        asm volatile("bar.sync 1, 256;" ::: "memory");
        unsigned int tk;
        asm volatile("ld.shared.u32 %0, [%1];" : "=r"(tk) : "r"(bar_empty + 8 * O2_STAGES) : "memory");
        if (tk == gridDim.x - 1 && threadIdx.x < CT_N) g_ctr[threadIdx.x] = 0u;
    }
    __syncthreads();
    cluster_sync_all();
    TS_END(4);
}

typedef CUresult (*PFN_encodeTiled)(CUtensorMap*, CUtensorMapDataType, cuuint32_t, void*, const cuuint64_t*,
                                    const cuuint64_t*, const cuuint32_t*, const cuuint32_t*, CUtensorMapInterleave,
                                    CUtensorMapSwizzle, CUtensorMapL2promotion, CUtensorMapFloatOOBfill);
static PFN_encodeTiled g_encode = nullptr;

static void make_map(CUtensorMap* m, const void* ptr, uint64_t rows, uint64_t cols, uint32_t box_rows, bool sw64 = false) {
    cuuint64_t dims[2] = {cols, rows};
    cuuint64_t strides[1] = {cols * 2};
    cuuint32_t box[2] = {sw64 ? 32u : 64u, box_rows};
    cuuint32_t es[2] = {1, 1};
    g_encode(m, CU_TENSOR_MAP_DATA_TYPE_BFLOAT16, 2, const_cast<void*>(ptr), dims, strides, box, es,
             CU_TENSOR_MAP_INTERLEAVE_NONE, sw64 ? CU_TENSOR_MAP_SWIZZLE_64B : CU_TENSOR_MAP_SWIZZLE_128B, CU_TENSOR_MAP_L2_PROMOTION_L2_256B,
             CU_TENSOR_MAP_FLOAT_OOB_FILL_NONE);
}

template <typename... KArgs, typename... Args>
static void launch_pdl(void (*kernel)(KArgs...), int grid, int block, size_t smem, cudaStream_t st, bool pdl, Args... args) {
    cudaLaunchConfig_t cfg = {};
    cfg.gridDim = dim3(grid); cfg.blockDim = dim3(block); cfg.dynamicSmemBytes = smem; cfg.stream = st;
    cudaLaunchAttribute at[1];
    at[0].id = cudaLaunchAttributeProgrammaticStreamSerialization;
    at[0].val.programmaticStreamSerializationAllowed = 1;
    cfg.attrs = at; cfg.numAttrs = pdl ? 1 : 0;
    cudaLaunchKernelEx(&cfg, kernel, KArgs(args)...);
}

extern "C" void kernel_launch(void* const* d_in, const int* in_sizes, int n_in, void* d_out, int out_size) {
    const bf16* x = (const bf16*)d_in[0];
    const bf16* ckv = (const bf16*)d_in[1];
    const bf16* wq = (const bf16*)d_in[2];
    const bf16* wuk = (const bf16*)d_in[3];
    const bf16* wuv = (const bf16*)d_in[4];
    const bf16* wo = (const bf16*)d_in[5];
    const bf16* mem0 = (const bf16*)d_in[7];
    const bf16* Wq = (const bf16*)d_in[8];
    const bf16* Wk = (const bf16*)d_in[9];
    const bf16* Wv = (const bf16*)d_in[10];
    const bf16* Wo = (const bf16*)d_in[11];
    const bf16* gate_w = (const bf16*)d_in[13];
    bf16* out = (bf16*)d_out;

    static Proj2Params P2;
    static ChainParams CP;
    static AttnParams AP;
    static OutParams OP;
    static bool init = false;
    static const void* last_in[14];
    bool same = init;
    for (int i = 0; i < 14 && same; i++) same = last_in[i] == d_in[i];
    if (!init) {
        cudaDriverEntryPointQueryResult qr;
        cudaGetDriverEntryPoint("cuTensorMapEncodeTiled", (void**)&g_encode, cudaEnableDefault, &qr);
        cudaFuncSetAttribute(proj2_kernel, cudaFuncAttributeMaxDynamicSharedMemorySize, P2_SMEM);
        cudaFuncSetAttribute(attn_kernel, cudaFuncAttributeMaxDynamicSharedMemorySize, FA_SMEM);
        cudaFuncSetAttribute(chain_kernel, cudaFuncAttributeMaxDynamicSharedMemorySize, CH_SMEM);
        cudaFuncSetAttribute(out2_kernel, cudaFuncAttributeMaxDynamicSharedMemorySize, O2_SMEM);
        init = true;
    }
    if (!same) {
        for (int i = 0; i < 14; i++) last_in[i] = d_in[i];
        void *pQA, *pKA, *pVA, *pCA, *pCB;
        cudaGetSymbolAddress(&pQA, g_QA); cudaGetSymbolAddress(&pKA, g_KA); cudaGetSymbolAddress(&pVA, g_VA);
        cudaGetSymbolAddress(&pCA, g_ctxA); cudaGetSymbolAddress(&pCB, g_ctxB);
        make_map(&P2.mapA[0], x, SEQ, DM, 128);
        make_map(&P2.mapA[1], ckv, SEQ, DM, 128);
        const void* ws[3] = {wq, wuk, wuv};
        void* cs[3] = {pQA, pKA, pVA};
        for (int i = 0; i < 3; i++) { make_map(&P2.mapW[i], ws[i], DM, NQ, 64); P2.out[i] = (bf16*)cs[i]; }
        make_map(&CP.mapW[0], Wq, DM, NQ, 64); make_map(&CP.mapW[1], Wk, DM, NQ, 64); make_map(&CP.mapW[2], Wv, DM, NQ, 64);
        make_map(&CP.mapX, x, SEQ, DM, 32);
        make_map(&CP.mapC, pCB, NH * SEQ, HD, 32);
        make_map(&AP.mapQ, pQA, NH * SEQ, HD, 128);
        make_map(&AP.mapK, pKA, NH * SEQ, HD, 128);
        make_map(&AP.mapV, pVA, NH * SEQ, HD, 128);
        make_map(&AP.mapO, pCA, NH * SEQ, HD, 64);
        make_map(&OP.mapCtx[0], pCA, NH * SEQ, HD, 128);
        make_map(&OP.mapCtx[1], pCB, NH * SEQ, HD, 128);
        make_map(&OP.mapWo[0], wo, NQ, DM, 64);
        make_map(&OP.mapWo[1], Wo, NQ, DM, 64);
        {
            void* pP; cudaGetSymbolAddress(&pP, g_part);
            cuuint64_t dims[2] = {DM, 4 * SEQ}; cuuint64_t strides[1] = {DM * 4}; cuuint32_t box[2] = {32, 32}; cuuint32_t es[2] = {1, 1};
            g_encode(&OP.mapPart, CU_TENSOR_MAP_DATA_TYPE_FLOAT32, 2, pP, dims, strides, box, es, CU_TENSOR_MAP_INTERLEAVE_NONE,
                     CU_TENSOR_MAP_SWIZZLE_128B, CU_TENSOR_MAP_L2_PROMOTION_NONE, CU_TENSOR_MAP_FLOAT_OOB_FILL_NONE);
        }
    }
    cudaStream_t s1 = cudaStreamPerThread;
    const bool pdl = true;
    launch_pdl(chain_kernel, 64, CH_BLOCK, CH_SMEM, s1, false, CP, mem0, Wo, x);
    launch_pdl(proj2_kernel, 68, 384, P2_SMEM, s1, pdl, P2);
    launch_pdl(attn_kernel, FA_GRID, 384, FA_SMEM, s1, pdl, AP, 1000);
    launch_pdl(out2_kernel, 128, 352, O2_SMEM, s1, pdl, OP, x, gate_w, out);
}
```

```cpp
#include <cuda_runtime.h>
#include <cuda_bf16.h>
#include <cuda.h>
#include <stdint.h>
#include <type_traits>

constexpr int SEQ = 2048;
constexpr int DM = 512;
constexpr int NH = 32;
constexpr int HD = 128;
constexpr int NQ = NH * HD;
constexpr int SEGL = 32;
constexpr int NMEM = 8;
constexpr int NSEG = SEQ / SEGL;

typedef __nv_bfloat16 bf16;

__device__ bf16 g_QA[SEQ * NQ];
__device__ bf16 g_KA[SEQ * NQ];
__device__ bf16 g_VA[SEQ * NQ];
__device__ bf16 g_ctxA[SEQ * NQ];
__device__ bf16 g_ctxB[SEQ * NQ];
constexpr int CT_PROJ = 0, CT_ATTN = 1, CT_FIN = 5;
constexpr int CT_AP = 64;
#define O2_HE 18
constexpr int CT_CA = 128;
constexpr int CT_CB = 160;
constexpr int CT_OP = 192;
constexpr int CT_N = 224;
__device__ unsigned int g_ctr[CT_N];
__device__ uint32_t g_xbuf[4 * 8 * 2048];

#define FA_GRID 68

#define TS_BEGIN(id)
#define TS_END(id)
#define WAIT_LIMIT 200000
__device__ __forceinline__ void pdl_launch_dependents() { asm volatile("griddepcontrol.launch_dependents;" ::: "memory"); }
__device__ __forceinline__ void wait_ctr(int idx, unsigned int n) {
    unsigned int v; int it = 0;
    do { asm volatile("ld.acquire.gpu.global.u32 %0, [%1];" : "=r"(v) : "l"(&g_ctr[idx]) : "memory"); } while (v < n && ++it < WAIT_LIMIT);
    asm volatile("fence.proxy.async;" ::: "memory");
}
__device__ __forceinline__ void signal_ctr(int idx) {
    asm volatile("fence.proxy.async;" ::: "memory");
    __threadfence();
    atomicAdd(&g_ctr[idx], 1u);
}
__device__ __forceinline__ void signal_ctr_generic(int idx) {
    asm volatile("red.release.gpu.global.add.u32 [%0], 1;" :: "l"(&g_ctr[idx]) : "memory");
}
__device__ __forceinline__ uint32_t smem_u32(const void* p) {
    return (uint32_t)__cvta_generic_to_shared(p);
}
__device__ __forceinline__ void mbar_init(uint32_t bar, uint32_t count) {
    asm volatile("mbarrier.init.shared::cta.b64 [%0], %1;" :: "r"(bar), "r"(count));
}
__device__ __forceinline__ void mbar_expect_tx(uint32_t bar, uint32_t bytes) {
    asm volatile("mbarrier.arrive.expect_tx.shared::cta.b64 _, [%0], %1;" :: "r"(bar), "r"(bytes) : "memory");
}
__device__ __forceinline__ void mbar_arrive(uint32_t bar) {
    asm volatile("mbarrier.arrive.shared::cta.b64 _, [%0];" :: "r"(bar) : "memory");
}
__device__ __forceinline__ void mbar_wait(uint32_t bar, uint32_t parity) {
    asm volatile(
        "{\n"
        ".reg .pred p, q;\n"
        ".reg .u32 c;\n"
        "mov.u32 c, 0;\n"
        "WAIT_LOOP:\n"
        "mbarrier.try_wait.parity.shared::cta.b64 p, [%0], %1;\n"
        "@p bra WAIT_DONE;\n"
        "add.u32 c, c, 1;\n"
        "setp.lt.u32 q, c, %2;\n"
        "@q bra WAIT_LOOP;\n"
        "WAIT_DONE:\n"
        "}\n" :: "r"(bar), "r"(parity), "n"(WAIT_LIMIT) : "memory");
}
__device__ __forceinline__ void tma_load_2d(uint32_t dst, const CUtensorMap* map, uint32_t bar, int c0, int c1) {
    asm volatile(
        "cp.async.bulk.tensor.2d.shared::cluster.global.mbarrier::complete_tx::bytes [%0], [%1, {%3, %4}], [%2];"
        :: "r"(dst), "l"((uint64_t)map), "r"(bar), "r"(c0), "r"(c1) : "memory");
}
__device__ __forceinline__ void wgmma_fence() { asm volatile("wgmma.fence.sync.aligned;" ::: "memory"); }
__device__ __forceinline__ void wgmma_commit() { asm volatile("wgmma.commit_group.sync.aligned;" ::: "memory"); }
template <int N> __device__ __forceinline__ void wgmma_wait() {
    asm volatile("wgmma.wait_group.sync.aligned %0;" :: "n"(N) : "memory");
}
__device__ __forceinline__ uint64_t make_desc(uint32_t addr, uint32_t lbo, uint32_t sbo) {
    uint64_t d = 0;
    d |= (uint64_t)((addr & 0x3FFFF) >> 4);
    d |= (uint64_t)((lbo >> 4) & 0x3FFF) << 16;
    d |= (uint64_t)((sbo >> 4) & 0x3FFF) << 32;
    d |= (uint64_t)1 << 62;
    return d;
}

#define ACC64(d) \
    "+f"(d[0]), "+f"(d[1]), "+f"(d[2]), "+f"(d[3]), "+f"(d[4]), "+f"(d[5]), "+f"(d[6]), "+f"(d[7]), \
    "+f"(d[8]), "+f"(d[9]), "+f"(d[10]), "+f"(d[11]), "+f"(d[12]), "+f"(d[13]), "+f"(d[14]), "+f"(d[15]), \
    "+f"(d[16]), "+f"(d[17]), "+f"(d[18]), "+f"(d[19]), "+f"(d[20]), "+f"(d[21]), "+f"(d[22]), "+f"(d[23]), \
    "+f"(d[24]), "+f"(d[25]), "+f"(d[26]), "+f"(d[27]), "+f"(d[28]), "+f"(d[29]), "+f"(d[30]), "+f"(d[31]), \
    "+f"(d[32]), "+f"(d[33]), "+f"(d[34]), "+f"(d[35]), "+f"(d[36]), "+f"(d[37]), "+f"(d[38]), "+f"(d[39]), \
    "+f"(d[40]), "+f"(d[41]), "+f"(d[42]), "+f"(d[43]), "+f"(d[44]), "+f"(d[45]), "+f"(d[46]), "+f"(d[47]), \
    "+f"(d[48]), "+f"(d[49]), "+f"(d[50]), "+f"(d[51]), "+f"(d[52]), "+f"(d[53]), "+f"(d[54]), "+f"(d[55]), \
    "+f"(d[56]), "+f"(d[57]), "+f"(d[58]), "+f"(d[59]), "+f"(d[60]), "+f"(d[61]), "+f"(d[62]), "+f"(d[63])
#define ACC64_STR \
    "{%0, %1, %2, %3, %4, %5, %6, %7, %8, %9, %10, %11, %12, %13, %14, %15, " \
    "%16, %17, %18, %19, %20, %21, %22, %23, %24, %25, %26, %27, %28, %29, %30, %31, " \
    "%32, %33, %34, %35, %36, %37, %38, %39, %40, %41, %42, %43, %44, %45, %46, %47, " \
    "%48, %49, %50, %51, %52, %53, %54, %55, %56, %57, %58, %59, %60, %61, %62, %63}"

template <int TB>
__device__ __forceinline__ void wgmma_ss_n128(float (&d)[64], uint64_t da, uint64_t db, int scale_d) {
    asm volatile(
        "{\n.reg .pred p;\nsetp.ne.b32 p, %66, 0;\n"
        "wgmma.mma_async.sync.aligned.m64n128k16.f32.bf16.bf16 " ACC64_STR ", %64, %65, p, 1, 1, 0, %67;\n}\n"
        : ACC64(d) : "l"(da), "l"(db), "r"(scale_d), "n"(TB));
}
__device__ __forceinline__ uint32_t desc_lo(uint32_t addr, uint32_t lbo) { return ((addr & 0x3FFFF) >> 4) | ((lbo >> 4) << 16); }
template <int TB>
__device__ __forceinline__ void wgmma_ss_n128_lo(float (&d)[64], uint32_t da_lo, uint32_t db_lo, int scale_d) {
    asm volatile(
        "{\n.reg .pred p;\n.reg .b64 da, db;\nsetp.ne.b32 p, %66, 0;\n"
        "mov.b64 da, {%64, 0x40000040};\nmov.b64 db, {%65, 0x40000040};\n"
        "wgmma.mma_async.sync.aligned.m64n128k16.f32.bf16.bf16 " ACC64_STR ", da, db, p, 1, 1, 0, %67;\n}\n"
        : ACC64(d) : "r"(da_lo), "r"(db_lo), "r"(scale_d), "n"(TB));
}
__device__ __forceinline__ void wgmma_rs_n128_tb(float (&d)[64], uint32_t a0, uint32_t a1, uint32_t a2, uint32_t a3,
                                                 uint64_t db, int scale_d) {
    asm volatile(
        "{\n.reg .pred p;\nsetp.ne.b32 p, %69, 0;\n"
        "wgmma.mma_async.sync.aligned.m64n128k16.f32.bf16.bf16 " ACC64_STR ", {%64, %65, %66, %67}, %68, p, 1, 1, 1;\n}\n"
        : ACC64(d) : "r"(a0), "r"(a1), "r"(a2), "r"(a3), "l"(db), "r"(scale_d));
}
__device__ __forceinline__ void wgmma_rs_n80(float (&d)[40], const uint32_t (&a)[4], uint32_t db_lo, int scale_d) {
    asm volatile(
        "{\n.reg .pred p;\n.reg .b64 db;\nsetp.ne.b32 p, %45, 0;\nmov.b64 db, {%44, 0x40000040};\n"
        "wgmma.mma_async.sync.aligned.m64n80k16.f32.bf16.bf16 "
        "{%0, %1, %2, %3, %4, %5, %6, %7, %8, %9, %10, %11, %12, %13, %14, %15, %16, %17, %18, %19, %20, %21, %22, %23, %24, %25, %26, %27, %28, %29, %30, %31, %32, %33, %34, %35, %36, %37, %38, %39}, "
        "{%40, %41, %42, %43}, db, p, 1, 1, 0;\n}\n"
        : "+f"(d[0]), "+f"(d[1]), "+f"(d[2]), "+f"(d[3]), "+f"(d[4]), "+f"(d[5]), "+f"(d[6]), "+f"(d[7]), "+f"(d[8]), "+f"(d[9]), "+f"(d[10]), "+f"(d[11]), "+f"(d[12]), "+f"(d[13]), "+f"(d[14]), "+f"(d[15]), "+f"(d[16]), "+f"(d[17]), "+f"(d[18]), "+f"(d[19]), "+f"(d[20]), "+f"(d[21]), "+f"(d[22]), "+f"(d[23]), "+f"(d[24]), "+f"(d[25]), "+f"(d[26]), "+f"(d[27]), "+f"(d[28]), "+f"(d[29]), "+f"(d[30]), "+f"(d[31]), "+f"(d[32]), "+f"(d[33]), "+f"(d[34]), "+f"(d[35]), "+f"(d[36]), "+f"(d[37]), "+f"(d[38]), "+f"(d[39])
        : "r"(a[0]), "r"(a[1]), "r"(a[2]), "r"(a[3]), "r"(db_lo), "r"(scale_d));
}
__device__ __forceinline__ void wgmma_ss_n256_tb(float (&d)[128], uint64_t da, uint64_t db, int scale_d) {
    asm volatile(
        "{\n.reg .pred p;\nsetp.ne.b32 p, %130, 0;\n"
        "wgmma.mma_async.sync.aligned.m64n256k16.f32.bf16.bf16 {%0, %1, %2, %3, %4, %5, %6, %7, %8, %9, %10, %11, %12, %13, %14, %15, %16, %17, %18, %19, %20, %21, %22, %23, %24, %25, %26, %27, %28, %29, %30, %31, %32, %33, %34, %35, %36, %37, %38, %39, %40, %41, %42, %43, %44, %45, %46, %47, %48, %49, %50, %51, %52, %53, %54, %55, %56, %57, %58, %59, %60, %61, %62, %63, %64, %65, %66, %67, %68, %69, %70, %71, %72, %73, %74, %75, %76, %77, %78, %79, %80, %81, %82, %83, %84, %85, %86, %87, %88, %89, %90, %91, %92, %93, %94, %95, %96, %97, %98, %99, %100, %101, %102, %103, %104, %105, %106, %107, %108, %109, %110, %111, %112, %113, %114, %115, %116, %117, %118, %119, %120, %121, %122, %123, %124, %125, %126, %127}, %128, %129, p, 1, 1, 0, 1;\n}\n"
        : "+f"(d[0]), "+f"(d[1]), "+f"(d[2]), "+f"(d[3]), "+f"(d[4]), "+f"(d[5]), "+f"(d[6]), "+f"(d[7]), "+f"(d[8]), "+f"(d[9]), "+f"(d[10]), "+f"(d[11]), "+f"(d[12]), "+f"(d[13]), "+f"(d[14]), "+f"(d[15]), "+f"(d[16]), "+f"(d[17]), "+f"(d[18]), "+f"(d[19]), "+f"(d[20]), "+f"(d[21]), "+f"(d[22]), "+f"(d[23]), "+f"(d[24]), "+f"(d[25]), "+f"(d[26]), "+f"(d[27]), "+f"(d[28]), "+f"(d[29]), "+f"(d[30]), "+f"(d[31]), "+f"(d[32]), "+f"(d[33]), "+f"(d[34]), "+f"(d[35]), "+f"(d[36]), "+f"(d[37]), "+f"(d[38]), "+f"(d[39]), "+f"(d[40]), "+f"(d[41]), "+f"(d[42]), "+f"(d[43]), "+f"(d[44]), "+f"(d[45]), "+f"(d[46]), "+f"(d[47]), "+f"(d[48]), "+f"(d[49]), "+f"(d[50]), "+f"(d[51]), "+f"(d[52]), "+f"(d[53]), "+f"(d[54]), "+f"(d[55]), "+f"(d[56]), "+f"(d[57]), "+f"(d[58]), "+f"(d[59]), "+f"(d[60]), "+f"(d[61]), "+f"(d[62]), "+f"(d[63]), "+f"(d[64]), "+f"(d[65]), "+f"(d[66]), "+f"(d[67]), "+f"(d[68]), "+f"(d[69]), "+f"(d[70]), "+f"(d[71]), "+f"(d[72]), "+f"(d[73]), "+f"(d[74]), "+f"(d[75]), "+f"(d[76]), "+f"(d[77]), "+f"(d[78]), "+f"(d[79]), "+f"(d[80]), "+f"(d[81]), "+f"(d[82]), "+f"(d[83]), "+f"(d[84]), "+f"(d[85]), "+f"(d[86]), "+f"(d[87]), "+f"(d[88]), "+f"(d[89]), "+f"(d[90]), "+f"(d[91]), "+f"(d[92]), "+f"(d[93]), "+f"(d[94]), "+f"(d[95]), "+f"(d[96]), "+f"(d[97]), "+f"(d[98]), "+f"(d[99]), "+f"(d[100]), "+f"(d[101]), "+f"(d[102]), "+f"(d[103]), "+f"(d[104]), "+f"(d[105]), "+f"(d[106]), "+f"(d[107]), "+f"(d[108]), "+f"(d[109]), "+f"(d[110]), "+f"(d[111]), "+f"(d[112]), "+f"(d[113]), "+f"(d[114]), "+f"(d[115]), "+f"(d[116]), "+f"(d[117]), "+f"(d[118]), "+f"(d[119]), "+f"(d[120]), "+f"(d[121]), "+f"(d[122]), "+f"(d[123]), "+f"(d[124]), "+f"(d[125]), "+f"(d[126]), "+f"(d[127])
        : "l"(da), "l"(db), "r"(scale_d));
}
__device__ __forceinline__ void stmatrix_x4(uint32_t addr, uint32_t r0, uint32_t r1, uint32_t r2, uint32_t r3) {
    asm volatile("stmatrix.sync.aligned.m8n8.x4.shared.b16 [%0], {%1, %2, %3, %4};" :: "r"(addr), "r"(r0), "r"(r1), "r"(r2), "r"(r3) : "memory");
}
__device__ __forceinline__ void tma_store_2d(const CUtensorMap* map, uint32_t src, int c0, int c1) {
    asm volatile("cp.async.bulk.tensor.2d.global.shared::cta.bulk_group [%0, {%2, %3}], [%1];"
                 :: "l"((uint64_t)map), "r"(src), "r"(c0), "r"(c1) : "memory");
}
__device__ __forceinline__ float ex2f(float x) { float y; asm("ex2.approx.ftz.f32 %0, %1;" : "=f"(y) : "f"(x)); return y; }
__device__ __forceinline__ uint32_t pack_bf16(float lo, float hi) {
    __nv_bfloat162 v = __floats2bfloat162_rn(lo, hi);
    return *reinterpret_cast<uint32_t*>(&v);
}
__device__ __forceinline__ void mma_16816(float (&c)[4], uint32_t a0, uint32_t a1, uint32_t a2, uint32_t a3,
                                          uint32_t b0, uint32_t b1) {
    asm volatile(
        "mma.sync.aligned.m16n8k16.row.col.f32.bf16.bf16.f32 {%0,%1,%2,%3}, {%4,%5,%6,%7}, {%8,%9}, {%0,%1,%2,%3};"
        : "+f"(c[0]), "+f"(c[1]), "+f"(c[2]), "+f"(c[3])
        : "r"(a0), "r"(a1), "r"(a2), "r"(a3), "r"(b0), "r"(b1));
}
__device__ __forceinline__ void ldmatrix_x4_trans(uint32_t& r0, uint32_t& r1, uint32_t& r2, uint32_t& r3, uint32_t addr) {
    asm volatile("ldmatrix.sync.aligned.m8n8.x4.trans.shared.b16 {%0,%1,%2,%3}, [%4];"
                 : "=r"(r0), "=r"(r1), "=r"(r2), "=r"(r3) : "r"(addr));
}

struct AttnParams {
    CUtensorMap mapQ, mapK, mapV;
    CUtensorMap mapO;
};
constexpr int FA_STAGES = 2;
constexpr int FA_SMEM = 32768 + FA_STAGES * 65536 + 32768 + 1024 + 256;
constexpr int FA_ITEMS = 16 * NH;
#define FA_RETIRE 100000
#define FA_LASTG 8
__device__ __forceinline__ int fa_qt(int t) {
    constexpr int T0 = (32 - FA_LASTG) * 16;
    return t < T0 ? 15 - ((t & 127) >> 3) : 15 - (t - T0) / FA_LASTG;
}
__device__ __forceinline__ int fa_head(int t) {
    constexpr int T0 = (32 - FA_LASTG) * 16;
    return t < T0 ? (t >> 7) * 8 + (t & 7) : (32 - FA_LASTG) + (t - T0) % FA_LASTG;
}

__global__ void __launch_bounds__(384, 1) attn_kernel(const __grid_constant__ AttnParams P, int retire_cta) {
    extern __shared__ uint8_t smem_raw[];
    uint32_t sbase = (smem_u32(smem_raw) + 1023) & ~1023u;
    const uint32_t sQ = sbase;
    const uint32_t sKV = sbase + 32768;
    const uint32_t sO = sKV + FA_STAGES * 65536;
    const uint32_t bars = sO + 32768;
    const uint32_t bar_q = bars, bar_qe = bars + 8, bar_kf = bars + 16, bar_vf = bar_kf + 8 * FA_STAGES, bar_e = bar_vf + 8 * FA_STAGES,
                   bar_ek = bar_e + 8 * FA_STAGES, slot = bar_ek + 8 * FA_STAGES, bar_of = slot + 16, bar_oe = bar_of + 16, oslot = bar_oe + 16;
    const int warp = threadIdx.x >> 5;
    TS_BEGIN(1);
    int tfirst = 0;
    if (threadIdx.x == 256) tfirst = (int)atomicAdd(&g_ctr[CT_ATTN], 1u);
    if (threadIdx.x == 0) {
        mbar_init(bar_q, 1); mbar_init(bar_qe, 8);
        for (int i = 0; i < FA_STAGES; i++) { mbar_init(bar_kf + 8 * i, 1); mbar_init(bar_vf + 8 * i, 1); mbar_init(bar_e + 8 * i, 8); mbar_init(bar_ek + 8 * i, 8); }
        for (int i = 0; i < 2; i++) { mbar_init(bar_of + 8 * i, 1); mbar_init(bar_oe + 8 * i, 1); }
        asm volatile("fence.mbarrier_init.release.cluster;" ::: "memory");
    }
    if (threadIdx.x == 256) asm volatile("st.shared.s32 [%0], %1;" :: "r"(slot + 8), "r"(tfirst) : "memory");
    __syncthreads();
    pdl_launch_dependents();
    if (warp >= 8) {
        asm volatile("setmaxnreg.dec.sync.aligned.u32 40;");
        if (threadIdx.x == 288 || threadIdx.x == 320) {
            const int wg = threadIdx.x == 288 ? 0 : 1;
            const uint32_t stg = sO + wg * 16384;
            for (int n = 0;; n++) {
                mbar_wait(bar_of + 8 * wg, n & 1);
                int t;
                asm volatile("ld.shared.s32 %0, [%1];" : "=r"(t) : "r"(oslot + wg * 4) : "memory");
                if (t < 0) break;
                const int qt = fa_qt(t), h = fa_head(t);
                tma_store_2d(&P.mapO, stg, 0, h * SEQ + qt * 128 + wg * 64);
                tma_store_2d(&P.mapO, stg + 8192, 64, h * SEQ + qt * 128 + wg * 64);
                asm volatile("cp.async.bulk.commit_group;" ::: "memory");
                asm volatile("cp.async.bulk.wait_group.read 0;" ::: "memory");
                mbar_arrive(bar_oe + 8 * wg);
                asm volatile("cp.async.bulk.wait_group 0;" ::: "memory");
                signal_ctr(CT_CA + qt * 2 + (h >= O2_HE));
            }
        }
        if (threadIdx.x == 256) {
            int it = 0, hp_ready = 0;
            for (int item = 0;; item++) {
                int t = tfirst;
                if (item > 0) {
                    bool quit = false;
                    if ((int)blockIdx.x >= retire_cta) {
                        unsigned int v;
                        asm volatile("ld.relaxed.gpu.global.u32 %0, [%1];" : "=r"(v) : "l"(&g_ctr[CT_ATTN]) : "memory");
                        quit = v >= FA_RETIRE;
                    }
                    t = quit ? FA_ITEMS : (int)atomicAdd(&g_ctr[CT_ATTN], 1u);
                }
                const bool valid = t < FA_ITEMS;
                const int qt = fa_qt(t), h = fa_head(t);
                if (valid && !((hp_ready >> (h >> 1)) & 1)) { wait_ctr(CT_AP + (h >> 1), 96u); hp_ready |= 1 << (h >> 1); }
                mbar_wait(bar_qe, (item & 1) ^ 1);
                asm volatile("st.shared.s32 [%0], %1;" :: "r"(slot + (item & 1) * 4), "r"(valid ? t : -1) : "memory");
                if (!valid) { mbar_arrive(bar_q); break; }
                mbar_expect_tx(bar_q, 32768);
                tma_load_2d(sQ, &P.mapQ, bar_q, 0, h * SEQ + qt * 128);
                tma_load_2d(sQ + 16384, &P.mapQ, bar_q, 64, h * SEQ + qt * 128);
                for (int j = 0; j <= qt; j++, it++) {
                    const int s = it % FA_STAGES;
                    mbar_wait(bar_ek + 8 * s, ((it / FA_STAGES) & 1) ^ 1);
                    const uint32_t sk = sKV + s * 65536, sv = sk + 32768;
                    mbar_expect_tx(bar_kf + 8 * s, 32768);
                    tma_load_2d(sk, &P.mapK, bar_kf + 8 * s, 0, h * SEQ + j * 128);
                    tma_load_2d(sk + 16384, &P.mapK, bar_kf + 8 * s, 64, h * SEQ + j * 128);
                    mbar_wait(bar_e + 8 * s, ((it / FA_STAGES) & 1) ^ 1);
                    mbar_expect_tx(bar_vf + 8 * s, 32768);
                    tma_load_2d(sv, &P.mapV, bar_vf + 8 * s, 0, h * SEQ + j * 128);
                    tma_load_2d(sv + 16384, &P.mapV, bar_vf + 8 * s, 64, h * SEQ + j * 128);
                }
            }
        }
    } else {
        asm volatile("setmaxnreg.inc.sync.aligned.u32 232;");
        const int wg = warp >> 2;
        const int lane = threadIdx.x & 31;
        float o[64];
        float mrow0, mrow1, lrow0, lrow1;
        const float sc = 0.08838834764831845f * 1.4426950408889634f;
        const int r0 = wg * 64 + (warp & 3) * 16 + (lane >> 2);
        float sacc[64];
        uint32_t pa[32];
        float a0 = 1.f, a1 = 1.f;
        auto issue_qk = [&](int it) {
            const int s = it % FA_STAGES;
            const uint32_t sk = sKV + s * 65536;
            mbar_wait(bar_kf + 8 * s, (it / FA_STAGES) & 1);
            wgmma_fence();
#pragma unroll
            for (int kk = 0; kk < 8; kk++) {
                uint64_t da = make_desc(sQ + (kk >> 2) * 16384 + wg * 8192 + (kk & 3) * 32, 16, 1024);
                uint64_t db = make_desc(sk + (kk >> 2) * 16384 + (kk & 3) * 32, 16, 1024);
                wgmma_ss_n128<0>(sacc, da, db, kk != 0);
            }
            wgmma_commit();
        };
        auto issue_pv = [&](int it) {
            const int s = it % FA_STAGES;
            const uint32_t sv = sKV + s * 65536 + 32768;
            mbar_wait(bar_vf + 8 * s, (it / FA_STAGES) & 1);
            wgmma_fence();
#pragma unroll
            for (int kk = 0; kk < 8; kk++) {
                uint64_t db = make_desc(sv + kk * 2048, 16384, 1024);
                wgmma_rs_n128_tb(o, pa[kk * 4 + 0], pa[kk * 4 + 1], pa[kk * 4 + 2], pa[kk * 4 + 3], db, 1);
            }
            wgmma_commit();
        };
        auto softmax_stats = [&](bool diag) {
            if (diag) {
#pragma unroll
                for (int i = 0; i < 64; i++) {
                    int col = (i >> 2) * 8 + (lane & 3) * 2 + (i & 1);
                    int row = r0 + ((i & 2) ? 8 : 0);
                    if (col > row) sacc[i] = -INFINITY;
                }
            }
            float mx0 = -INFINITY, mx1 = -INFINITY;
#pragma unroll
            for (int i = 0; i < 16; i++) {
                mx0 = fmaxf(mx0, fmaxf(sacc[i * 4 + 0], sacc[i * 4 + 1]));
                mx1 = fmaxf(mx1, fmaxf(sacc[i * 4 + 2], sacc[i * 4 + 3]));
            }
            mx0 = fmaxf(mx0, __shfl_xor_sync(0xffffffff, mx0, 1));
            mx0 = fmaxf(mx0, __shfl_xor_sync(0xffffffff, mx0, 2));
            mx1 = fmaxf(mx1, __shfl_xor_sync(0xffffffff, mx1, 1));
            mx1 = fmaxf(mx1, __shfl_xor_sync(0xffffffff, mx1, 2));
            const float mn0 = fmaxf(mrow0, mx0), mn1 = fmaxf(mrow1, mx1);
            a0 = ex2f((mrow0 - mn0) * sc); a1 = ex2f((mrow1 - mn1) * sc);
            mrow0 = mn0; mrow1 = mn1;
            const float ms0 = mn0 * sc, ms1 = mn1 * sc;
            float sum0 = 0.f, sum1 = 0.f;
#pragma unroll
            for (int i = 0; i < 16; i++) {
                sacc[i * 4 + 0] = ex2f(fmaf(sacc[i * 4 + 0], sc, -ms0));
                sacc[i * 4 + 1] = ex2f(fmaf(sacc[i * 4 + 1], sc, -ms0));
                sacc[i * 4 + 2] = ex2f(fmaf(sacc[i * 4 + 2], sc, -ms1));
                sacc[i * 4 + 3] = ex2f(fmaf(sacc[i * 4 + 3], sc, -ms1));
                sum0 += sacc[i * 4 + 0] + sacc[i * 4 + 1];
                sum1 += sacc[i * 4 + 2] + sacc[i * 4 + 3];
            }
            lrow0 = lrow0 * a0 + sum0;
            lrow1 = lrow1 * a1 + sum1;
        };
        auto pack_p = [&]() {
#pragma unroll
            for (int i = 0; i < 16; i++) {
                pa[i * 2 + 0] = pack_bf16(sacc[i * 4 + 0], sacc[i * 4 + 1]);
                pa[i * 2 + 1] = pack_bf16(sacc[i * 4 + 2], sacc[i * 4 + 3]);
            }
        };
        int it = 0;
        if (wg == 1) asm volatile("bar.arrive 1, 256;" ::: "memory");
        for (int item = 0;; item++) {
            mbar_wait(bar_q, item & 1);
            int t;
            asm volatile("ld.shared.s32 %0, [%1];" : "=r"(t) : "r"(slot + (item & 1) * 4) : "memory");
            if (t < 0) {
                if ((threadIdx.x & 127) == 0) {
                    mbar_wait(bar_oe + 8 * wg, (item & 1) ^ 1);
                    asm volatile("st.shared.s32 [%0], %1;" :: "r"(oslot + wg * 4), "r"(-1) : "memory");
                    mbar_arrive(bar_of + 8 * wg);
                }
                break;
            }
            const int qt = fa_qt(t);
            const int nkv = qt + 1;
#pragma unroll
            for (int i = 0; i < 64; i++) o[i] = 0.f;
            mrow0 = -INFINITY; mrow1 = -INFINITY; lrow0 = 0.f; lrow1 = 0.f;
            asm volatile("bar.sync %0, 256;" :: "r"(1 + wg) : "memory");
            issue_qk(it);
            asm volatile("bar.arrive %0, 256;" :: "r"(2 - wg) : "memory");
            wgmma_wait<0>();
            if (lane == 0) { mbar_arrive(bar_ek + 8 * (it % FA_STAGES)); if (nkv == 1) mbar_arrive(bar_qe); }
            softmax_stats(nkv == 1);
            pack_p();
#pragma unroll 1
            for (int j = 1; j < nkv; j++) {
                asm volatile("bar.sync %0, 256;" :: "r"(1 + wg) : "memory");
                issue_qk(it + j);
                issue_pv(it + j - 1);
                asm volatile("bar.arrive %0, 256;" :: "r"(2 - wg) : "memory");
                wgmma_wait<1>();
                if (lane == 0) { mbar_arrive(bar_ek + 8 * ((it + j) % FA_STAGES)); if (j == nkv - 1) mbar_arrive(bar_qe); }
                softmax_stats(j == nkv - 1);
                wgmma_wait<0>();
                if (lane == 0) mbar_arrive(bar_e + 8 * ((it + j - 1) % FA_STAGES));
#pragma unroll
                for (int i = 0; i < 16; i++) {
                    o[i * 4 + 0] *= a0; o[i * 4 + 1] *= a0; o[i * 4 + 2] *= a1; o[i * 4 + 3] *= a1;
                }
                pack_p();
            }
            issue_pv(it + nkv - 1);
            wgmma_wait<0>();
            if (lane == 0) mbar_arrive(bar_e + 8 * ((it + nkv - 1) % FA_STAGES));
            it += nkv;
            lrow0 += __shfl_xor_sync(0xffffffff, lrow0, 1);
            lrow0 += __shfl_xor_sync(0xffffffff, lrow0, 2);
            lrow1 += __shfl_xor_sync(0xffffffff, lrow1, 1);
            lrow1 += __shfl_xor_sync(0xffffffff, lrow1, 2);
            const float i0 = 1.f / lrow0, i1 = 1.f / lrow1;
            const uint32_t stg = sO + wg * 16384;
            mbar_wait(bar_oe + 8 * wg, (item & 1) ^ 1);
            {
                const int row = (warp & 3) * 16 + (lane >> 2);
#pragma unroll
                for (int i = 0; i < 4; i++) {
                    const int ch = i * 4 + (lane & 3);
                    const uint32_t a = stg + (ch >> 3) * 8192 + row * 128 + (((ch & 7) ^ (row & 7)) << 4);
                    const float* q = &o[i * 16];
                    asm volatile("st.shared.v4.b32 [%0], {%1, %2, %3, %4};" :: "r"(a), "r"(pack_bf16(q[0] * i0, q[1] * i0)), "r"(pack_bf16(q[4] * i0, q[5] * i0)),
                                 "r"(pack_bf16(q[8] * i0, q[9] * i0)), "r"(pack_bf16(q[12] * i0, q[13] * i0)) : "memory");
                    asm volatile("st.shared.v4.b32 [%0], {%1, %2, %3, %4};" :: "r"(a + 1024), "r"(pack_bf16(q[2] * i1, q[3] * i1)), "r"(pack_bf16(q[6] * i1, q[7] * i1)),
                                 "r"(pack_bf16(q[10] * i1, q[11] * i1)), "r"(pack_bf16(q[14] * i1, q[15] * i1)) : "memory");
                }
            }
            asm volatile("fence.proxy.async.shared::cta;" ::: "memory");
            asm volatile("bar.sync %0, 128;" :: "r"(3 + wg) : "memory");
            if ((threadIdx.x & 127) == 0) {
                asm volatile("st.shared.s32 [%0], %1;" :: "r"(oslot + wg * 4), "r"(t) : "memory");
                mbar_arrive(bar_of + 8 * wg);
            }
        }
        TS_END(1);
    }
}

__device__ __forceinline__ uint32_t cluster_ctarank() {
    uint32_t r; asm volatile("mov.u32 %0, %%cluster_ctarank;" : "=r"(r)); return r;
}
__device__ __forceinline__ uint32_t mapa_u32(uint32_t addr, uint32_t rank) {
    uint32_t r; asm volatile("mapa.shared::cluster.u32 %0, %1, %2;" : "=r"(r) : "r"(addr), "r"(rank)); return r;
}
__device__ __forceinline__ void cluster_sync_all() {
    asm volatile("barrier.cluster.arrive.release.aligned;\nbarrier.cluster.wait.acquire.aligned;" ::: "memory");
}
__device__ __forceinline__ void st_async_v4(uint32_t addr, uint32_t a, uint32_t b, uint32_t c, uint32_t d, uint32_t mbar) {
    asm volatile("st.async.weak.shared::cluster.mbarrier::complete_tx::bytes.v4.b32 [%0], {%1, %2, %3, %4}, [%5];"
                 :: "r"(addr), "r"(a), "r"(b), "r"(c), "r"(d), "r"(mbar) : "memory");
}
__device__ __forceinline__ void st_async_v2(uint32_t addr, uint32_t a, uint32_t b, uint32_t mbar) {
    asm volatile("st.async.weak.shared::cluster.mbarrier::complete_tx::bytes.v2.b32 [%0], {%1, %2}, [%3];"
                 :: "r"(addr), "r"(a), "r"(b), "r"(mbar) : "memory");
}
__device__ __forceinline__ void st_async_b32(uint32_t addr, uint32_t a, uint32_t mbar) {
    asm volatile("st.async.weak.shared::cluster.mbarrier::complete_tx::bytes.b32 [%0], %1, [%2];" :: "r"(addr), "r"(a), "r"(mbar) : "memory");
}
__device__ __forceinline__ void pace(int cycles) {
    if (cycles > 0) {
        uint32_t t0, t;
        asm volatile("mov.u32 %0, %%clock;" : "=r"(t0));
        do { asm volatile("mov.u32 %0, %%clock;" : "=r"(t)); } while (t - t0 < (uint32_t)cycles);
    }
}
__device__ __forceinline__ void mbar_wait_cl(uint32_t bar, uint32_t parity) {
    uint32_t done = 0;
    for (int it = 0; it < WAIT_LIMIT && !done; it++) {
        asm volatile(
            "{\n.reg .pred p;\n"
            "mbarrier.try_wait.parity.shared::cta.b64 p, [%1], %2;\n"
            "selp.u32 %0, 1, 0, p;\n}\n" : "=r"(done) : "r"(bar), "r"(parity) : "memory");
    }
}
__device__ __forceinline__ uint32_t mbar_test(uint32_t bar, uint32_t parity) {
    uint32_t done;
    asm volatile(
        "{\n.reg .pred p;\n"
        "mbarrier.test_wait.parity.shared::cta.b64 p, [%1], %2;\n"
        "selp.u32 %0, 1, 0, p;\n}\n" : "=r"(done) : "r"(bar), "r"(parity) : "memory");
    return done;
}
__device__ __forceinline__ void ldmatrix_x4(uint32_t& r0, uint32_t& r1, uint32_t& r2, uint32_t& r3, uint32_t addr) {
    asm volatile("ldmatrix.sync.aligned.m8n8.x4.shared.b16 {%0,%1,%2,%3}, [%4];"
                 : "=r"(r0), "=r"(r1), "=r"(r2), "=r"(r3) : "r"(addr));
}
__device__ __forceinline__ void cp_async16(uint32_t dst, const void* src) {
    asm volatile("cp.async.cg.shared.global [%0], [%1], 16;" :: "r"(dst), "l"(src) : "memory");
}
__device__ __forceinline__ float bf16r(float x) { return __uint_as_float(pack_bf16(0.f, x) & 0xffff0000u); }

#define DBG(i, w)
#define DBGD(i, w, dep)
#define DBG_EXTRA 0
__device__ __forceinline__ void tma_load_2d_mc(uint32_t dst, const CUtensorMap* map, uint32_t bar, int c0, int c1, uint16_t mask) {
    asm volatile(
        "cp.async.bulk.tensor.2d.shared::cluster.global.mbarrier::complete_tx::bytes.multicast::cluster [%0], [%1, {%3, %4}], [%2], %5;"
        :: "r"(dst), "l"((uint64_t)map), "r"(bar), "r"(c0), "r"(c1), "h"(mask) : "memory");
}
__device__ __forceinline__ void stmatrix_x4_trans(uint32_t addr, uint32_t r0, uint32_t r1, uint32_t r2, uint32_t r3) {
    asm volatile("stmatrix.sync.aligned.m8n8.x4.trans.shared.b16 [%0], {%1, %2, %3, %4};" :: "r"(addr), "r"(r0), "r"(r1), "r"(r2), "r"(r3) : "memory");
}
__device__ __forceinline__ void stmatrix_x2_trans(uint32_t addr, uint32_t r0, uint32_t r1) {
    asm volatile("stmatrix.sync.aligned.m8n8.x2.trans.shared.b16 [%0], {%1, %2};" :: "r"(addr), "r"(r0), "r"(r1) : "memory");
}
__device__ __forceinline__ uint4 lds128(uint32_t a) {
    uint4 v; asm volatile("ld.shared.v4.u32 {%0, %1, %2, %3}, [%4];" : "=r"(v.x), "=r"(v.y), "=r"(v.z), "=r"(v.w) : "r"(a) : "memory"); return v;
}
__device__ __forceinline__ void sts128(uint32_t a, uint32_t x, uint32_t y, uint32_t z, uint32_t w) {
    asm volatile("st.shared.v4.b32 [%0], {%1, %2, %3, %4};" :: "r"(a), "r"(x), "r"(y), "r"(z), "r"(w) : "memory");
}
__device__ __forceinline__ float2 lds64f(uint32_t a) {
    float2 v; asm volatile("ld.shared.v2.f32 {%0, %1}, [%2];" : "=f"(v.x), "=f"(v.y) : "r"(a) : "memory"); return v;
}
__device__ __forceinline__ void fence_async_smem() { asm volatile("fence.proxy.async.shared::cta;" ::: "memory"); }
#define ACC16(d) "+f"(d[0]), "+f"(d[1]), "+f"(d[2]), "+f"(d[3]), "+f"(d[4]), "+f"(d[5]), "+f"(d[6]), "+f"(d[7]), "+f"(d[8]), "+f"(d[9]), "+f"(d[10]), "+f"(d[11]), "+f"(d[12]), "+f"(d[13]), "+f"(d[14]), "+f"(d[15])
template <int ND>
__device__ __forceinline__ void wgmma_rs_n32(float (&d)[ND], const uint32_t (&a)[4], uint32_t db_lo, int scale_d) {
    asm volatile(
        "{\n.reg .pred p;\n.reg .b64 db;\nsetp.ne.b32 p, %21, 0;\nmov.b64 db, {%20, 0x40000040};\n"
        "wgmma.mma_async.sync.aligned.m64n32k16.f32.bf16.bf16 {%0,%1,%2,%3,%4,%5,%6,%7,%8,%9,%10,%11,%12,%13,%14,%15}, {%16,%17,%18,%19}, db, p, 1, 1, 0;\n}\n"
        : ACC16(d) : "r"(a[0]), "r"(a[1]), "r"(a[2]), "r"(a[3]), "r"(db_lo), "r"(scale_d));
}
template <int ND>
__device__ __forceinline__ void wgmma_ss_n32(float (&d)[ND], uint32_t da_lo, uint32_t db_lo, int scale_d) {
    asm volatile(
        "{\n.reg .pred p;\n.reg .b64 da, db;\nsetp.ne.b32 p, %18, 0;\nmov.b64 da, {%16, 0x40000040};\nmov.b64 db, {%17, 0x40000040};\n"
        "wgmma.mma_async.sync.aligned.m64n32k16.f32.bf16.bf16 {%0,%1,%2,%3,%4,%5,%6,%7,%8,%9,%10,%11,%12,%13,%14,%15}, da, db, p, 1, 1, 1, 0;\n}\n"
        : ACC16(d) : "r"(da_lo), "r"(db_lo), "r"(scale_d));
}
__device__ __forceinline__ void wgmma_ss_n8(float (&d)[4], uint32_t da_lo, uint32_t db_lo, int scale_d) {
    asm volatile(
        "{\n.reg .pred p;\n.reg .b64 da, db;\nsetp.ne.b32 p, %6, 0;\nmov.b64 da, {%4, 0x40000040};\nmov.b64 db, {%5, 0x00000010};\n"
        "wgmma.mma_async.sync.aligned.m64n8k16.f32.bf16.bf16 {%0,%1,%2,%3}, da, db, p, 1, 1, 1, 0;\n}\n"
        : "+f"(d[0]), "+f"(d[1]), "+f"(d[2]), "+f"(d[3]) : "r"(da_lo), "r"(db_lo), "r"(scale_d));
}

#define SCHED_FENCE()
__device__ __forceinline__ void wgmma_ss_n32_p(float (&d)[16], uint32_t da_lo, uint32_t db_lo, int scale_d) {
    asm volatile(
        "{\n.reg .pred p;\n.reg .b64 da, db;\nsetp.ne.b32 p, %18, 0;\nmov.b64 da, {%16, 0x40000040};\nmov.b64 db, {%17, 0x00000030};\n"
        "wgmma.mma_async.sync.aligned.m64n32k16.f32.bf16.bf16 {%0,%1,%2,%3,%4,%5,%6,%7,%8,%9,%10,%11,%12,%13,%14,%15}, da, db, p, 1, 1, 1, 0;\n}\n"
        : ACC16(d) : "r"(da_lo), "r"(db_lo), "r"(scale_d));
}

__device__ __forceinline__ void wgmma_ss_n32_kk(float (&d)[16], uint32_t da_lo, uint32_t db_lo, int scale_d) {
    asm volatile(
        "{\n.reg .pred p;\n.reg .b64 da, db;\nsetp.ne.b32 p, %18, 0;\nmov.b64 da, {%16, 0x40000040};\nmov.b64 db, {%17, 0x40000040};\n"
        "wgmma.mma_async.sync.aligned.m64n32k16.f32.bf16.bf16 {%0,%1,%2,%3,%4,%5,%6,%7,%8,%9,%10,%11,%12,%13,%14,%15}, da, db, p, 1, 1, 0, 0;\n}\n"
        : ACC16(d) : "r"(da_lo), "r"(db_lo), "r"(scale_d));
}

struct ChainParams {
    CUtensorMap mapW[3];
    CUtensorMap mapX;
    CUtensorMap mapC;
};
constexpr int CH_BLOCK = 384;
constexpr int CO_WO = 0;
constexpr int CO_XB = 65536;
constexpr int CO_MB = CO_XB + 65536;
constexpr int CO_OB = CO_MB + 8192;
constexpr int CH_TW = 6144, CH_TP = 3 * CH_TW;
constexpr int CO_T = CO_OB + 8192;
constexpr int CO_SC = CO_T + 2 * CH_TP;
constexpr int CO_LS = CO_SC + 2 * 1280;
constexpr int CO_LO = CO_LS + 8 * 1280;
constexpr int CO_P = CO_LO + 4 * 1280;
constexpr int CO_ST = 205824;
#define CH_NSM 3
constexpr int CO_WA = CO_ST + 4096;
constexpr int CO_BAR = CO_WA + CH_TP;
constexpr int CH_SMEM = CO_BAR + 256 + 1024 + DBG_EXTRA;
static_assert(CO_WA >= 3 * 65536 && CO_P + 3072 <= CO_ST && CH_NSM <= 3, "smem layout");
#define CH_POLL_DELAY 0
#define CH_PEARLY 0
#define CH_VPOS 2
#define CH_VST 0
#define CH_V3_DELAY 0
#define CH_LSPOS 1
#define CH_V1 0
#define CH_V2 24
#define CH_V3 32
#define CH_OG 2
#define CH_OW 8
#define CH_OF 12
#define CH_CHAINS 4

constexpr float CH_SC = 0.08838834764831845f * 1.4426950408889634f;
__device__ __forceinline__ uint32_t pin(uint32_t v) { return __shfl_sync(0xffffffff, v, threadIdx.x & 31); }

__global__ void __cluster_dims__(8, 1, 1) __launch_bounds__(CH_BLOCK, 1)
chain_kernel(const __grid_constant__ ChainParams P, const bf16* __restrict__ mem0, const bf16* __restrict__ Wo, const bf16* __restrict__ x) {
    extern __shared__ uint8_t smem_raw[];
    const uint32_t sb = (smem_u32(smem_raw) + 1023) & ~1023u;
    const int tid = threadIdx.x, warp = __shfl_sync(0xffffffff, tid >> 5, 0), lane = tid & 31;
    const int rank = (int)cluster_ctarank();
    const int C = blockIdx.x >> 3;
    const int h = C * 4 + (rank >> 1);
    const int qd = lane >> 2, qc = lane & 3;
    const int t4 = warp & 3, wg = warp >> 2;
    pdl_launch_dependents();
    TS_BEGIN(2);
    const uint32_t bar_mem = sb + CO_BAR, bar_o = bar_mem + 32, bar_sc = bar_o + 32, bar_x = bar_sc + 8, bar_l = bar_x + 16, bar_w = bar_l + 8;
    if (tid == 0) {
        for (int j = 0; j < 15; j++) mbar_init(bar_mem + 8 * j, bar_mem + 8 * j == bar_l ? 4 : 1);
        asm volatile("fence.mbarrier_init.release.cluster;" ::: "memory");
    }
    __syncthreads();
    if ((tid & 127) == 0) {
        mbar_expect_tx(bar_w + 8 * wg, 65536);
        for (int i = 0; i < 8; i++)
            tma_load_2d(sb + wg * 65536 + i * 8192, &P.mapW[wg], bar_w + 8 * wg, h * HD + (rank & 1) * 64, i * 64);
    }
    {
        for (int i = tid; i < 512; i += CH_BLOCK) asm volatile("prefetch.global.L2 [%0];" :: "l"(Wo + (size_t)(C * 512 + i) * DM + rank * 64));
        if (tid < 64) asm volatile("prefetch.global.L2 [%0];" :: "l"(x + (size_t)tid * DM + rank * 64));
    }
    auto chunk = [&](int i) { return (uint32_t)((rank - (i >> 1) - 4 * (i & 1)) & 7); };
    const uint32_t wfrag = (((lane >> 4) << 3) + (lane & 7)) * 128 + (((t4 * 2 + ((lane >> 3) & 1)) ^ (lane & 7)) << 4);
    const uint32_t aO = pin(sb + wg * CH_TW + wfrag);
    const uint32_t aM = pin(sb + (lane & 7) * 128 + (((lane >> 3) ^ (lane & 7)) << 4));
    const uint32_t aL = pin(sb + lane * 8);
    uint32_t w[32][4];
    float d[16];
    mbar_wait(bar_w + 8 * wg, 0);
#pragma unroll
    for (int e = CH_NSM; e < 32; e++) ldmatrix_x4_trans(w[e][0], w[e][1], w[e][2], w[e][3], sb + wg * 65536 + wfrag + chunk(e >> 2) * 8192 + (e & 3) * 2048);
#pragma unroll
    for (int e = 0; e < CH_NSM; e++) {
        const uint4 u = lds128(sb + wg * 65536 + chunk(0) * 8192 + e * 2048 + (tid & 127) * 16);
        sts128(sb + CO_WA + wg * CH_TW + e * 2048 + (tid & 127) * 16, u.x, u.y, u.z, u.w);
    }
    fence_async_smem();
    __syncthreads();
    if (tid == 0) {
        fence_async_smem();
        for (int b = 0; b < 2; b++) {
            mbar_expect_tx(bar_x + 8 * b, 32768);
            for (int i = 0; i < 8; i++) tma_load_2d(sb + CO_XB + b * 32768 + i * 4096, &P.mapX, bar_x + 8 * b, i * 64, b * SEGL);
        }
    }
#pragma unroll 2
    for (int i = tid; i < 512 * 4; i += CH_BLOCK) {
        const int r = i >> 2, cg = i & 3, ks = r >> 4, kp = r & 15;
        const int src = (rank - (ks >> 2)) & 7;
        const uint4* p = reinterpret_cast<const uint4*>(Wo + (size_t)(C * 512 + src * 64 + (ks & 3) * 16 + (kp >> 2) * 2 + (kp & 1) + (kp & 2) * 4) * DM + rank * 64 + cg * 16);
        const uint4 u0 = __ldg(p), u1 = __ldg(p + 1);
        const uint32_t a = sb + CO_WO + r * 128;
        sts128(a + (((cg * 2) ^ (r & 7)) << 4), __byte_perm(u0.x, u0.y, 0x5410), __byte_perm(u0.z, u0.w, 0x5410), __byte_perm(u1.x, u1.y, 0x5410), __byte_perm(u1.z, u1.w, 0x5410));
        sts128(a + (((cg * 2 + 1) ^ (r & 7)) << 4), __byte_perm(u0.x, u0.y, 0x7632), __byte_perm(u0.z, u0.w, 0x7632), __byte_perm(u1.x, u1.y, 0x7632), __byte_perm(u1.z, u1.w, 0x7632));
    }
#pragma unroll 1
    for (int i = tid; i < 512; i += CH_BLOCK) {
        const int n = i >> 6, c = i & 63;
        const uint4 u = __ldg(reinterpret_cast<const uint4*>(mem0 + n * DM + chunk(c >> 3) * 64 + (c & 7) * 8));
        sts128(sb + CO_MB + (c >> 3) * 1024 + n * 128 + (((c & 7) ^ n) << 4), u.x, u.y, u.z, u.w);
    }
    if (tid < 128) sts128(sb + CO_T + (tid >> 6) * CH_TP + 2 * CH_TW + 5120 + (tid & 63) * 16, 0u, 0u, 0u, 0u);
    else if (tid < 160) sts128(sb + CO_P + ((tid >> 3) & 3) * 768 + 640 + (tid & 7) * 16, 0u, 0u, 0u, 0u);
    fence_async_smem();
    TS_END(6);
    auto pass32 = [&](int b, int e0 = 0, int e1 = 32) {
        const uint32_t lo = desc_lo(sb + CO_XB + b * 32768, 16);
        wgmma_fence();
#pragma unroll
        for (int e = 0; e < 32; e++) if (e >= e0 && e < e1) {
            const uint32_t db = lo + chunk(e >> 2) * 256 + (e & 3) * 2;
            if (e < CH_NSM) wgmma_ss_n32(d, desc_lo(sb + CO_WA + wg * CH_TW + e * 2048, 16), db, e != 0);
            else wgmma_rs_n32(d, w[e], db, e != 0);
        }
        wgmma_commit();
    };
    auto store32 = [&](uint32_t a) {
        stmatrix_x4_trans(a, pack_bf16(d[0], d[1]), pack_bf16(d[2], d[3]), pack_bf16(d[4], d[5]), pack_bf16(d[6], d[7]));
        stmatrix_x4_trans(a + 2048, pack_bf16(d[8], d[9]), pack_bf16(d[10], d[11]), pack_bf16(d[12], d[13]), pack_bf16(d[14], d[15]));
    };
    auto mem_proj = [&](int s, bool wait, bool arrive = false) {
        const uint32_t par = s & 1;
        float acc[CH_CHAINS][4];
#pragma unroll
        for (int i = 0; i < CH_CHAINS; i++) acc[i][0] = acc[i][1] = acc[i][2] = acc[i][3] = 0.f;
        const uint32_t aM2 = aM ^ 64;
        uint32_t b[2][8];
        auto load = [&](int c) {
            if (wait && !(c & 1)) mbar_wait_cl(bar_mem + 4 * c, par ^ 1);
            if (c == 0) DBG(11, 0);
            if (c == 6) DBG(13, 0);
            ldmatrix_x4(b[c & 1][0], b[c & 1][1], b[c & 1][2], b[c & 1][3], aM + CO_MB + c * 1024);
            ldmatrix_x4(b[c & 1][4], b[c & 1][5], b[c & 1][6], b[c & 1][7], aM2 + CO_MB + c * 1024);
        };
        load(0);
#pragma unroll
        for (int c = 0; c < 8; c++) {
            if (c < 7) load(c + 1);
            SCHED_FENCE();
#pragma unroll
            for (int i = 0; i < 4; i++) {
                const int e = c * 4 + i;
                mma_16816(acc[i % CH_CHAINS], w[e][0], w[e][1], w[e][2], w[e][3], b[c & 1][i * 2], b[c & 1][i * 2 + 1]);
            }
        }
        if (CH_CHAINS == 4) {
#pragma unroll
            for (int i = 0; i < 4; i++) { acc[0][i] += acc[2 % CH_CHAINS][i]; acc[1][i] += acc[3 % CH_CHAINS][i]; }
        }
        const uint32_t r0 = pack_bf16(acc[0][0] + acc[1][0], acc[0][1] + acc[1][1]);
        const uint32_t r1 = pack_bf16(acc[0][2] + acc[1][2], acc[0][3] + acc[1][3]);
        DBGD(40 + warp, warp, r0 ^ r1);
        stmatrix_x2_trans(aO + par * CH_TP + CO_T + 4096, r0, r1);
    };
    auto load_wa = [&]() {
#pragma unroll
        for (int e = 0; e < CH_NSM; e++) ldmatrix_x4_trans(w[e][0], w[e][1], w[e][2], w[e][3], aO + CO_WA + e * 2048);
    };
    auto remote = [](uint32_t a, uint32_t r) { return mapa_u32(a, r); };
    mbar_wait(bar_x, 0);
    pass32(0);
    wgmma_wait<0>();
    store32(aO + CO_T);
    fence_async_smem();
    __syncthreads();
    cluster_sync_all();
    TS_BEGIN(5);

    if (wg < 2) {
        const uint32_t aQ = pin(sb + CO_T + qd * 128 + (((2 * qc) ^ qd) << 4));
        auto local_scores = [&](int s) {
            const uint32_t tb = sb + CO_T + (s & 1) * CH_TP;
            wgmma_fence();
#pragma unroll
            for (int ks = 0; ks < 4; ks++) wgmma_ss_n32_kk(d, desc_lo(tb + CH_TW, 16) + ks * 2, desc_lo(tb, 16) + ks * 2, ks != 0);
            wgmma_commit();
            wgmma_wait<0>();
            const uint32_t rb = remote(bar_l, rank ^ 1);
            if (t4 < 2) {
                const uint32_t off = 2 * aL - sb + t4 * 512;
#pragma unroll
                for (int j = 0; j < 4; j++) if (j >= 2 || t4 == 0) {
                    st_async_v4(remote(off + (s & 1) * 5120 + CO_LS + j * 1280, rank ^ 1), __float_as_uint(d[4 * j]), __float_as_uint(d[4 * j + 1]), __float_as_uint(d[4 * j + 2]), __float_as_uint(d[4 * j + 3]), rb);
                    sts128(off + CO_LO + j * 1280, __float_as_uint(d[4 * j]), __float_as_uint(d[4 * j + 1]), __float_as_uint(d[4 * j + 2]), __float_as_uint(d[4 * j + 3]));
                }
            } else if (t4 == 2) {
#pragma unroll
                for (int j = 0; j < 4; j++) {
                    st_async_v2(remote(aL + (s & 1) * 5120 + CO_LS + 1024 + j * 1280, rank ^ 1), __float_as_uint(d[4 * j]), __float_as_uint(d[4 * j + 1]), rb);
                    asm volatile("st.shared.v2.f32 [%0], {%1, %2};" :: "r"(aL + CO_LO + 1024 + j * 1280), "f"(d[4 * j]), "f"(d[4 * j + 1]) : "memory");
                }
            }
            __syncwarp();
            if (t4 < 3 && lane == 0) mbar_arrive(bar_l);
            DBG(6, 4);
        };
        auto local_pv = [&](int s, bool arrive) {
            wgmma_fence();
#pragma unroll
            for (int ks = 0; ks < 3; ks++)
                wgmma_ss_n32_p(d, desc_lo(sb + CO_T + (s & 1) * CH_TP + 2 * CH_TW + ks * 2048, 16), desc_lo(sb + CO_P + ks * 256, 128), ks != 0);
            wgmma_commit();
            wgmma_wait<0>();
            if (arrive) asm volatile("bar.arrive 9, 256;" ::: "memory");
            store32(aO + CO_ST);
            fence_async_smem();
            if (!arrive) asm volatile("bar.sync 5, 128;" ::: "memory");
        };
        auto store_ctx = [&](int s) {
            tma_store_2d(&P.mapC, sb + CO_ST, (rank & 1) * 64, h * SEQ + s * SEGL);
            asm volatile("cp.async.bulk.commit_group;" ::: "memory");
        };
        auto signal_ctx = [&](int m0, int m1) {
            asm volatile("fence.proxy.async;" ::: "memory");
            __threadfence();
            for (int m = m0; m < m1; m++) asm volatile("red.relaxed.gpu.global.add.u32 [%0], 1;" :: "l"(&g_ctr[CT_CB + m * 2 + (h >= O2_HE)]) : "memory");
        };
#pragma unroll 1
        for (int s = 0; s < NSEG; s++) {
            const uint32_t par = s & 1;
            load_wa();
            mem_proj(s, s > 0);
            if (s == NSEG - 1) break;
            if (warp < 5) {
                const uint32_t qa_ = aQ + par * CH_TP, ka = qa_ + warp * 1024;
                asm volatile("bar.sync 1, 256;" ::: "memory");
                const uint4 qa = lds128(qa_ + 4096), k0 = lds128(ka + CH_TW), qb = lds128((qa_ ^ 16) + 4096), k1 = lds128((ka ^ 16) + CH_TW);
                DBGD(52 + warp, warp, qa.x ^ qb.x);
                float c[4] = {0.f, 0.f, 0.f, 0.f}, c2[4] = {0.f, 0.f, 0.f, 0.f};
                mma_16816(c, qa.x, 0u, qa.y, 0u, k0.x, k0.y);
                mma_16816(c2, qb.x, 0u, qb.y, 0u, k1.x, k1.y);
                mma_16816(c, qa.z, 0u, qa.w, 0u, k0.z, k0.w);
                mma_16816(c2, qb.z, 0u, qb.w, 0u, k1.z, k1.w);
                c[0] += c2[0]; c[1] += c2[1];
                DBGD(57 + warp, warp, __float_as_uint(c[0]));
                const uint32_t off = aL + CO_SC + warp * 256;
                st_async_v2(remote(off + 1280, rank ^ 1), __float_as_uint(c[0]), __float_as_uint(c[1]), remote(bar_sc, rank ^ 1));
                st_async_v2(off, __float_as_uint(c[0]), __float_as_uint(c[1]), bar_sc);
                asm volatile("bar.arrive 2, 288;" ::: "memory");
                DBG(3, 0);
            } else {
                asm volatile("bar.arrive 1, 256;" ::: "memory");
            }
            if (wg == 0) {
                if (tid == 96) {
                    mbar_expect_tx(bar_sc, 2 * 1280);
#pragma unroll
                    for (int j = 0; j < 4; j++) { mbar_expect_tx(bar_mem + 8 * j, 2048); if (j < CH_OG) mbar_expect_tx(bar_o + 8 * j, 8192 / CH_OG); }
                    if (s > 0) mbar_wait(bar_l, par ^ 1);
                    mbar_expect_tx(bar_l, 4096);
                }
                if (tid == 96 && s > 1) {
                    if (s == 34 || s == 50 || s == 58 || s == 62) {
                        asm volatile("cp.async.bulk.wait_group 0;" ::: "memory");
                        signal_ctx(s == 34 ? 0 : (2 * s - 68) >> 2, s >> 2);
                    }
                    store_ctx(s - 2);
                    asm volatile("cp.async.bulk.wait_group.read 0;" ::: "memory");
                }
                __syncwarp();
                mbar_wait(bar_x + 8 * (par ^ 1), ((s + 1) >> 1) & 1);
                asm volatile("bar.sync 5, 128;" ::: "memory");
                float c[4];
                const uint32_t alo = desc_lo(sb + CO_WO, 16), blo = desc_lo(sb + CO_OB, 128);
                uint32_t* wp = g_xbuf + (size_t)rank * 2048 + C * 256 + qc * 64 + t4 * 8 + qd;
                mbar_wait_cl(bar_o, par);
                DBG(16, 0);
                fence_async_smem();
                wgmma_fence();
#pragma unroll
                for (int i = 0; i < 32; i++) {
                    wgmma_ss_n8(c, alo + i * 128, blo + i * 16, i != 0);
                    if (CH_OG == 2 && i == CH_OW) mbar_wait_cl(bar_o + 8, par);
                    if (CH_OG == 2 && i == CH_OF) fence_async_smem();
                }
                wgmma_commit();
                wgmma_wait<0>();
                asm volatile("st.relaxed.gpu.global.u32 [%0], %1;" :: "l"(wp + (s & 3) * 16384), "r"(~pack_bf16(c[0], c[2])) : "memory");
                asm volatile("st.relaxed.gpu.global.u32 [%0], %1;" :: "l"(wp + (s & 3) * 16384 + 32), "r"(~pack_bf16(c[1], c[3])) : "memory");
                asm volatile("bar.arrive 4, 256;" ::: "memory");
                asm volatile("bar.arrive 6, 256;" ::: "memory");
                DBG(8, 0);
                if (s > 0) local_pv(s - 1, true); else asm volatile("bar.arrive 9, 256;" ::: "memory");
                DBG(28, 0);
                asm volatile("st.relaxed.gpu.global.u32 [%0], %1;" :: "l"(wp + ((s + 2) & 3) * 16384), "r"(0) : "memory");
                asm volatile("st.relaxed.gpu.global.u32 [%0], %1;" :: "l"(wp + ((s + 2) & 3) * 16384 + 32), "r"(0) : "memory");
                if (tid == 0 && s + 2 < NSEG) {
                    mbar_expect_tx(bar_x + 8 * par, 32768);
                    tma_load_2d_mc(sb + CO_XB + par * 32768 + rank * 4096, &P.mapX, bar_x + 8 * par, rank * 64, (s + 2) * SEGL, (uint16_t)0xff);
                }
                __syncwarp();
            } else {
                const uint32_t vaddr = pin(sb + CO_T + par * CH_TP + 2 * CH_TW + (lane & 15) * 128 + (((t4 * 2 + (lane >> 4)) ^ (lane & 7)) << 4));
                const uint32_t dsta = pin(sb + CO_OB + t4 * 256 + (qc >> 1) * 128 + qd * 16 + (qc & 1) * 8);
                fence_async_smem();
                uint32_t vb[3][4];
                auto load_v = [&]() {
                    asm volatile("bar.sync 3, 256;" ::: "memory");
#pragma unroll
                    for (int k = 0; k < 3; k++) ldmatrix_x4_trans(vb[k][0], vb[k][1], vb[k][2], vb[k][3], vaddr + k * 2048);
                };
                if (CH_VPOS == 0) load_v();
                mbar_wait_cl(bar_sc, par);
                DBG(4, 4);
                float v[10];
#pragma unroll
                for (int j = 0; j < 5; j++) {
                    const float2 a = lds64f(aL + CO_SC + j * 256), b = lds64f(aL + CO_SC + 1280 + j * 256);
                    v[2 * j] = a.x + b.x; v[2 * j + 1] = a.y + b.y;
                }
                if (CH_VPOS == 1) load_v();
                float mx = fmaxf(fmaxf(fmaxf(v[0], v[1]), fmaxf(v[2], v[3])), fmaxf(fmaxf(v[4], v[5]), fmaxf(v[6], v[7])));
                mx = fmaxf(mx, fmaxf(v[8], v[9]));
                mx = fmaxf(mx, __shfl_xor_sync(0xffffffff, mx, 1));
                mx = fmaxf(mx, __shfl_xor_sync(0xffffffff, mx, 2));
                if (CH_VPOS == 2) load_v();
                DBG(19, 4);
                mx *= CH_SC;
#pragma unroll
                for (int j = 0; j < 10; j++) v[j] = ex2f(fmaf(v[j], CH_SC, -mx));
                float c0[4] = {0.f, 0.f, 0.f, 0.f}, c1[4] = {0.f, 0.f, 0.f, 0.f}, cs[4] = {0.f, 0.f, 0.f, 0.f};
#pragma unroll
                for (int k = 0; k < 3; k++) {
                    const uint32_t p0 = pack_bf16(v[4 * k], v[4 * k + 1]), p1 = k < 2 ? pack_bf16(v[4 * k + 2], v[4 * k + 3]) : 0u;
                    mma_16816(cs, p0, 0u, p1, 0u, 0x3f803f80u, 0x3f803f80u);
                    mma_16816(c0, p0, 0u, p1, 0u, vb[k][0], vb[k][1]);
                    mma_16816(c1, p0, 0u, p1, 0u, vb[k][2], vb[k][3]);
                }
                float inv;
                asm volatile("rcp.approx.ftz.f32 %0, %1;" : "=f"(inv) : "f"(cs[0]));
                const uint32_t b0 = pack_bf16(c0[0] * inv, c0[1] * inv), b1 = pack_bf16(c1[0] * inv, c1[1] * inv);
                DBG(20, 4);
#pragma unroll
                for (int i = 0; i < 8; i++) {
                    const int dr = (rank + i) & 7;
                    st_async_v2(remote(dsta + i * 1024, dr), b0, b1, remote(bar_o + 8 * (i * CH_OG / 8), dr));
                    if (i == 0) asm volatile("bar.arrive 7, 256;" ::: "memory");
                }
                DBG(5, 4);
                mbar_wait(bar_x + 8 * (par ^ 1), ((s + 1) >> 1) & 1);
                asm volatile("bar.sync 4, 256;" ::: "memory");
                if (CH_LSPOS == 0) local_scores(s);
            }
            pass32(par ^ 1);
            DBG(21, 0);
            wgmma_wait<0>();
            store32(aO + (par ^ 1) * CH_TP + CO_T);
            if (wg == 0) fence_async_smem();
            DBG(22, 0);
            DBG(29, 4);
            if (CH_LSPOS == 1 && wg == 1) local_scores(s);
        }
        fence_async_smem();
        asm volatile("bar.sync 1, 256;" ::: "memory");
        if (warp < 5) asm volatile("bar.arrive 2, 288;" ::: "memory");
        if (wg == 0) {
            if (tid == 96) { mbar_wait(bar_l, 0); mbar_expect_tx(bar_l, 4096); store_ctx(NSEG - 3); asm volatile("cp.async.bulk.wait_group.read 0;" ::: "memory"); }
            __syncwarp();
            asm volatile("bar.sync 7, 256;" ::: "memory");
            local_pv(NSEG - 2, false);
            asm volatile("bar.arrive 6, 256;" ::: "memory");
            if (tid == 96) { store_ctx(NSEG - 2); asm volatile("cp.async.bulk.wait_group.read 0;" ::: "memory"); }
            __syncwarp();
            asm volatile("bar.sync 8, 256;" ::: "memory");
            local_pv(NSEG - 1, false);
            if (tid == 96) {
                store_ctx(NSEG - 1);
                asm volatile("cp.async.bulk.wait_group 0;" ::: "memory");
                signal_ctx(15, 16);
            }
            uint32_t* wp = g_xbuf + 16384 + (size_t)rank * 2048 + C * 256 + tid * 2;
            *reinterpret_cast<uint2*>(wp) = make_uint2(0u, 0u);
        } else {
            asm volatile("bar.sync 3, 256;" ::: "memory");
            asm volatile("bar.arrive 7, 256;" ::: "memory");
            local_scores(NSEG - 1);
        }
    } else {
        auto local_softmax = [&](int s) {
            float v[10];
            mbar_wait_cl(bar_l, s & 1);
            const uint32_t off = 2 * aL - sb + t4 * 1280;
            {
                const uint4 a0 = lds128(off + (s & 1) * 5120 + CO_LS), b0 = lds128(off + CO_LO), a1 = lds128(off + (s & 1) * 5120 + CO_LS + 512), b1 = lds128(off + CO_LO + 512);
                const float2 a2 = lds64f(aL + t4 * 1280 + (s & 1) * 5120 + CO_LS + 1024), b2 = lds64f(aL + t4 * 1280 + CO_LO + 1024);
                auto f = [](uint32_t a, uint32_t b) { return __uint_as_float(a) + __uint_as_float(b); };
                v[0] = f(a0.x, b0.x); v[1] = f(a0.y, b0.y); v[2] = f(a0.z, b0.z); v[3] = f(a0.w, b0.w);
                v[4] = f(a1.x, b1.x); v[5] = f(a1.y, b1.y); v[6] = f(a1.z, b1.z); v[7] = f(a1.w, b1.w);
                v[8] = a2.x + b2.x; v[9] = a2.y + b2.y;
            }
            const int lim = t4 * 8 + 2 * qc - qd;
#pragma unroll
            for (int n = 0; n < 4; n++) {
                if (8 * n > lim) v[2 * n] = -INFINITY;
                if (8 * n > lim + 1) v[2 * n + 1] = -INFINITY;
            }
            float m0 = fmaxf(fmaxf(fmaxf(v[0], v[2]), fmaxf(v[4], v[6])), v[8]), m1 = fmaxf(fmaxf(fmaxf(v[1], v[3]), fmaxf(v[5], v[7])), v[9]);
#pragma unroll
            for (int o = 4; o < 32; o *= 2) { m0 = fmaxf(m0, __shfl_xor_sync(0xffffffff, m0, o)); m1 = fmaxf(m1, __shfl_xor_sync(0xffffffff, m1, o)); }
            m0 *= CH_SC; m1 *= CH_SC;
#pragma unroll
            for (int n = 0; n < 5; n++) { v[2 * n] = ex2f(fmaf(v[2 * n], CH_SC, -m0)); v[2 * n + 1] = ex2f(fmaf(v[2 * n + 1], CH_SC, -m1)); }
            float s0 = ((v[0] + v[2]) + (v[4] + v[6])) + v[8], s1 = ((v[1] + v[3]) + (v[5] + v[7])) + v[9];
#pragma unroll
            for (int o = 4; o < 32; o *= 2) { s0 += __shfl_xor_sync(0xffffffff, s0, o); s1 += __shfl_xor_sync(0xffffffff, s1, o); }
            asm("rcp.approx.ftz.f32 %0, %0;" : "+f"(s0));
            asm("rcp.approx.ftz.f32 %0, %0;" : "+f"(s1));
            const uint32_t pa = 2 * aL - sb + CO_P + t4 * 768;
            stmatrix_x4_trans(pa, pack_bf16(v[0] * s0, v[1] * s1), pack_bf16(v[2] * s0, v[3] * s1), pack_bf16(v[4] * s0, v[5] * s1), pack_bf16(v[6] * s0, v[7] * s1));
            asm volatile("stmatrix.sync.aligned.m8n8.x1.trans.shared.b16 [%0], {%1};" :: "r"(pa + 512), "r"(pack_bf16(v[8] * s0, v[9] * s1)) : "memory");
            fence_async_smem();
            DBG(7, 8);
        };
#pragma unroll 1
        for (int s = 0; s < NSEG; s++) {
            const uint32_t par = s & 1;
            if (s > 0) local_softmax(s - 1);
            load_wa();
            if (s < NSEG - 1) mbar_wait(bar_x + 8 * (par ^ 1), ((s + 1) >> 1) & 1);
            asm volatile("bar.sync 2, 288;" ::: "memory");
            DBG(23, 8);
            mem_proj(s, false, true);
            asm volatile("bar.arrive 3, 256;" ::: "memory");
            if (s == NSEG - 1) break;
            DBG(24, 8);
            if (CH_V1 > 0) pass32(par ^ 1, 0, CH_V1);
            asm volatile("bar.sync 7, 256;" ::: "memory");
            pass32(par ^ 1, CH_V1, CH_V2);
            DBG(26, 8);
            asm volatile("bar.sync 6, 256;" ::: "memory");
            const uint2* xb = reinterpret_cast<const uint2*>(g_xbuf + (s & 3) * 16384 + (size_t)rank * 2048 + t4 * 64) + lane;
            uint2 p[8];
            auto poll_all = [&]() {
#pragma unroll
                for (int k = 0; k < 8; k++)
                    asm volatile("ld.relaxed.gpu.global.v2.u32 {%0, %1}, [%2];" : "=r"(p[k].x), "=r"(p[k].y) : "l"(xb + k * 128) : "memory");
                DBG(17, 8);
            };
            if (CH_V3 > CH_V2) { pace(CH_V3_DELAY); pass32(par ^ 1, CH_V2, CH_V3); }
            if (CH_VST == 0) {
                asm volatile("bar.sync 9, 256;" ::: "memory");
                wgmma_wait<0>();
                store32(aO + (par ^ 1) * CH_TP + CO_T);
                DBG(27, 8);
            }
            pace(CH_POLL_DELAY);
            auto lo = [](uint32_t u) { return __uint_as_float(~u << 16); };
            auto hi = [](uint32_t u) { return __uint_as_float(~u & 0xffff0000u); };
            poll_all();
            for (int it = 0; it < WAIT_LIMIT / 4; it++) {
                uint32_t bad = 0;
#pragma unroll
                for (int k = 0; k < 8; k++) bad |= (min(p[k].x, p[k].y) == 0u ? 1u : 0u) << k;
                if (__all_sync(0xffffffff, bad == 0u)) break;
                if (it == 0) DBG(12, 8);
                if (it == 1) DBG(14, 8);
                if (it == 2) DBG(15, 8);
#pragma unroll
                for (int k = 0; k < 8; k++)
                    if (bad & (1u << k))
                        asm volatile("ld.relaxed.gpu.global.v2.u32 {%0, %1}, [%2];" : "=r"(p[k].x), "=r"(p[k].y) : "l"(xb + k * 128) : "memory");
            }
            DBG(9, 8);
            const uint32_t m0 = pack_bf16(((lo(p[0].x) + lo(p[1].x)) + (lo(p[2].x) + lo(p[3].x))) + ((lo(p[4].x) + lo(p[5].x)) + (lo(p[6].x) + lo(p[7].x))),
                                          ((hi(p[0].x) + hi(p[1].x)) + (hi(p[2].x) + hi(p[3].x))) + ((hi(p[4].x) + hi(p[5].x)) + (hi(p[6].x) + hi(p[7].x))));
            const uint32_t m1 = pack_bf16(((lo(p[0].y) + lo(p[1].y)) + (lo(p[2].y) + lo(p[3].y))) + ((lo(p[4].y) + lo(p[5].y)) + (lo(p[6].y) + lo(p[7].y))),
                                          ((hi(p[0].y) + hi(p[1].y)) + (hi(p[2].y) + hi(p[3].y))) + ((hi(p[4].y) + hi(p[5].y)) + (hi(p[6].y) + hi(p[7].y))));
            const int row = t4 * 2 + (lane >> 4);
            const uint32_t dsta = sb + CO_MB + row * 128 + ((((lane & 15) >> 1) ^ row) << 4) + (lane & 1) * 8;
#pragma unroll
            for (int i = 0; i < 8; i++) {
                const int dr = (rank + (i & 1) * 4 + (i >> 1)) & 7;
                st_async_v2(remote(dsta + i * 1024, dr), m0, m1, remote(bar_mem + 8 * (i >> 1), dr));
            }
            DBG(10, 8);
            if (CH_VST == 1) {
                if (CH_V3 < 32) pass32(par ^ 1, CH_V3, 32);
                asm volatile("bar.sync 9, 256;" ::: "memory");
                wgmma_wait<0>();
                store32(aO + (par ^ 1) * CH_TP + CO_T);
                DBG(27, 8);
            }
        }
        asm volatile("bar.sync 6, 256;" ::: "memory");
        local_softmax(NSEG - 1);
        asm volatile("bar.arrive 8, 256;" ::: "memory");
    }
    __syncthreads();
    cluster_sync_all();
    TS_END(2);
}

struct Proj2Params {
    CUtensorMap mapA[2];
    CUtensorMap mapW[3];
    bf16* out[3];
};
#define P2T(i)
#define P2_NOMMA 0
#define P2_NOLOAD 0
constexpr int P2_STAGES = 6;
constexpr int P2_SMEM = 131072 + P2_STAGES * 16384 + 1024 + 1024;
constexpr int P2_ITEMS = 168 + 48;

__device__ __forceinline__ int p2_reps(int t) { return t >= 168 ? 1 : 2; }
__device__ __forceinline__ void p2_tile(int t, int w, int& z, int& mp, int& head) {
    if (t >= 168) { w += ((t - 168) & 1) * 2; t = 168 + ((t - 168) >> 1); }
    const int hq = t / 24, v = t % 24;
    mp = v & 7;
    if (v < 16) { head = hq * 4 + (v >> 3) * 2 + (w >> 1); z = 1 + (w & 1); }
    else { head = hq * 4 + w; z = 0; }
}
__device__ __forceinline__ void mbar_arrive_remote(uint32_t bar_cluster_addr) {
    asm volatile("mbarrier.arrive.release.cluster.shared::cluster.b64 _, [%0];" :: "r"(bar_cluster_addr) : "memory");
}
__device__ __forceinline__ void mbar_arrive_cl(uint32_t bar_cluster_addr) {
    asm volatile("mbarrier.arrive.shared::cluster.b64 _, [%0];" :: "r"(bar_cluster_addr) : "memory");
}
__device__ __forceinline__ void mbar_wait_acq_cluster(uint32_t bar, uint32_t parity) {
    asm volatile(
        "{\n"
        ".reg .pred p, q;\n"
        ".reg .u32 c;\n"
        "mov.u32 c, 0;\n"
        "WAIT_LOOP_C:\n"
        "mbarrier.try_wait.parity.acquire.cluster.shared::cta.b64 p, [%0], %1;\n"
        "@p bra WAIT_DONE_C;\n"
        "add.u32 c, c, 1;\n"
        "setp.lt.u32 q, c, 4000000;\n"
        "@q bra WAIT_LOOP_C;\n"
        "WAIT_DONE_C:\n"
        "}\n" :: "r"(bar), "r"(parity) : "memory");
}
__device__ __forceinline__ uint4 quad_transpose(uint32_t p0, uint32_t p1, uint32_t p2, uint32_t p3, int lane) {
    const bool o1 = lane & 1, o2 = lane & 2;
    uint32_t s0 = o1 ? p0 : p1, s1 = o1 ? p2 : p3;
    s0 = __shfl_xor_sync(0xffffffff, s0, 1); s1 = __shfl_xor_sync(0xffffffff, s1, 1);
    const uint32_t a_lo = o1 ? s0 : p0, a_hi = o1 ? p1 : s0, b_lo = o1 ? s1 : p2, b_hi = o1 ? p3 : s1;
    uint32_t t0 = o2 ? a_lo : b_lo, t1 = o2 ? a_hi : b_hi;
    t0 = __shfl_xor_sync(0xffffffff, t0, 2); t1 = __shfl_xor_sync(0xffffffff, t1, 2);
    return o2 ? make_uint4(t0, t1, b_lo, b_hi) : make_uint4(a_lo, a_hi, t0, t1);
}
#define P2_PACE 35
#define P2_PACE2 0
template <bool PERM, int PACE = 0>
__device__ __forceinline__ void store_frag_128(const float (&acc)[64], bf16* obase, int lane) {
#pragma unroll
    for (int rr = 0; rr < 2; rr++)
#pragma unroll
        for (int g = 0; g < 4; g++) {
            const float* a = &acc[g * 16 + rr * 2];
            const uint32_t p0 = pack_bf16(a[0], a[1]), p1 = pack_bf16(a[4], a[5]), p2 = pack_bf16(a[8], a[9]), p3 = pack_bf16(a[12], a[13]);
            *reinterpret_cast<uint4*>(obase + (size_t)(rr * 8) * HD + g * 32) = PERM ? make_uint4(p0, p1, p2, p3) : quad_transpose(p0, p1, p2, p3, lane);
            pace(PACE);
        }
}
__global__ void __cluster_dims__(2, 1, 1) __launch_bounds__(384, 1) proj2_kernel(const __grid_constant__ Proj2Params P) {
    extern __shared__ uint8_t smem_raw[];
    const uint32_t sbase = (smem_u32(smem_raw) + 1023) & ~1023u;
    const uint32_t sA = sbase, sB = sbase + 131072, sC = sB + P2_STAGES * 16384;
    const uint32_t bars = sC;
    const uint32_t a_full = bars, a_empty = bars + 64, b_full = bars + 128, b_empty = b_full + 8 * P2_STAGES;
    const uint32_t item_bar = b_empty + 8 * P2_STAGES, item_in = item_bar + 16, slot = item_in + 16;
    const uint32_t note_bar = slot + 16, note_free = note_bar + 64, note = note_free + 64;
    const int warp = threadIdx.x >> 5, lane = threadIdx.x & 31;
    const uint32_t rank = cluster_ctarank();
    TS_BEGIN(0);
    if (threadIdx.x == 0) {
        for (int i = 0; i < 8; i++) { mbar_init(a_full + 8 * i, 1); mbar_init(a_empty + 8 * i, 2); }
        for (int i = 0; i < P2_STAGES; i++) { mbar_init(b_full + 8 * i, 1); mbar_init(b_empty + 8 * i, 2); }
        mbar_init(item_bar, 1); mbar_init(item_bar + 8, 1); mbar_init(item_in, 2); mbar_init(item_in + 8, 2);
        for (int i = 0; i < 8; i++) { mbar_init(note_bar + 8 * i, 1); mbar_init(note_free + 8 * i, 1); }
        asm volatile("fence.mbarrier_init.release.cluster;" ::: "memory");
    }
    __syncthreads();
    cluster_sync_all();
    pdl_launch_dependents();
    if (warp == 9) {
        if (lane == 0) {
            for (int n = 0;; n++) {
                const int e = (n & 1) * 4 + ((n >> 1) & 3);
                mbar_wait(note_bar + 8 * e, (n >> 3) & 1);
                int m;
                asm volatile("ld.shared.s32 %0, [%1];" : "=r"(m) : "r"(note + e * 4) : "memory");
                mbar_arrive(note_free + 8 * e);
                if (m < 0) break;
                signal_ctr(m);
            }
        }
    } else if (warp == 10) {
        if (lane == 0) {
            auto publish = [&](int ic, int tq) {
                const int t = tq < P2_ITEMS ? tq : -1;
                asm volatile("st.shared.s32 [%0], %1;" :: "r"(slot + (ic & 3) * 4), "r"(t) : "memory");
                mbar_arrive(item_bar + 8 * (ic & 1));
                st_async_b32(mapa_u32(slot + (ic & 3) * 4, 1), (uint32_t)t, mapa_u32(item_bar + 8 * (ic & 1), 1));
            };
            const int npair = (int)(gridDim.x >> 1), pair = (int)(blockIdx.x >> 1);
            if (rank == 0) publish(0, pair);
            for (int ic = 0;; ic++) {
                if (rank == 1) mbar_expect_tx(item_bar + 8 * (ic & 1), 4);
                mbar_wait(item_bar + 8 * (ic & 1), (ic >> 1) & 1);
                int t;
                asm volatile("ld.shared.s32 %0, [%1];" : "=r"(t) : "r"(slot + (ic & 3) * 4) : "memory");
                if (t < 0) break;
                int z0, mp, h0;
                p2_tile(t, 0, z0, mp, h0);
                const int aidx = z0 >= 1 ? 1 : 0;
                const int m0 = (2 * mp + (int)rank) * 128;
                for (int k = 0; k < 8; k++) {
                    mbar_wait(a_empty + 8 * k, (ic & 1) ^ 1);
                    if (P2_NOLOAD) mbar_arrive(a_full + 8 * k); else {
                    mbar_expect_tx(a_full + 8 * k, 16384);
                    tma_load_2d(sA + k * 16384, &P.mapA[aidx], a_full + 8 * k, k * 64, m0); }
                }
                if (rank == 0) {
                    mbar_wait(item_in + 8 * (ic & 1), (ic >> 1) & 1);
                    publish(ic + 1, ic == 0 ? npair + pair : 2 * npair + (int)atomicAdd(&g_ctr[CT_PROJ], 1u));
                }
            }
        }
    } else if (warp == 8 || warp == 11) {
        if (lane == 0) {
            const int par2 = warp == 8 ? 0 : 1;
            int it = 0; uint32_t bph = 0;
            for (int ic = 0;; ic++) {
                mbar_wait(item_bar + 8 * (ic & 1), (ic >> 1) & 1);
                int t;
                asm volatile("ld.shared.s32 %0, [%1];" : "=r"(t) : "r"(slot + (ic & 3) * 4) : "memory");
                if (t < 0) break;
                const int nt = 2 * p2_reps(t);
                for (int w = 0; w < nt; w++) {
                    int z, mp, hd;
                    p2_tile(t, w, z, mp, hd);
                    for (int k = 0; k < 8; k++) {
                        const int s = it; const uint32_t phb = bph;
                        if (++it == P2_STAGES) { it = 0; bph ^= 1; }
                        if ((k & 1) != par2) continue;
                        mbar_wait(b_empty + 8 * s, phb ^ 1);
                        if (P2_NOLOAD) { mbar_arrive(b_full + 8 * s); continue; }
                        mbar_expect_tx(b_full + 8 * s, 16384);
                        tma_load_2d_mc(sB + s * 16384 + rank * 8192, &P.mapW[z], b_full + 8 * s, hd * 128 + (int)rank * 64, k * 64, (uint16_t)3);
                    }
                }
            }
        }
    } else {
        const int wg = warp >> 2;
        float acc[2][64];
        const uint32_t a_lo = desc_lo(sA, 16), b_lo0 = desc_lo(sB, 8192);
        const bool elected = (threadIdx.x & 127) == 0;
        int s = (wg * 8) % P2_STAGES;
        uint32_t ph = ((wg * 8) / P2_STAGES) & 1;
        int nnote = 0;
        if (wg == 1) asm volatile("bar.arrive 3, 256;" ::: "memory");
        for (int ic = 0;; ic++) {
            mbar_wait(item_bar + 8 * (ic & 1), (ic >> 1) & 1);
            int t;
            asm volatile("ld.shared.s32 %0, [%1];" : "=r"(t) : "r"(slot + (ic & 3) * 4) : "memory");
            P2T(7);
            if (wg == 0 && t < 0) {
                if (elected) {
                    const int e = nnote & 3;
                    mbar_wait(note_free + 8 * e, ((nnote >> 2) & 1) ^ 1);
                    asm volatile("st.shared.s32 [%0], %1;" :: "r"(note + e * 4), "r"(-1) : "memory");
                    mbar_arrive(note_bar + 8 * e);
                }
            }
            if (t < 0) break;
            const int reps = p2_reps(t);
#pragma unroll 1
            for (int rp = 0; rp < reps; rp++) {
            const bool first = rp == 0, last = rp == reps - 1;
            int z, mp, head;
            p2_tile(t, rp * 2 + wg, z, mp, head);
            asm volatile("bar.sync %0, 256;" :: "r"(3 + wg) : "memory");
            P2T(0);
            if (wg == 1 && last && elected) mbar_arrive_cl(mapa_u32(item_in + 8 * (ic & 1), 0));
            int sprev = 0;
#pragma unroll
            for (int k = 0; k < 8; k++) {
                if (k == 0) P2T(5);
                if (wg == 0 && first) mbar_wait(a_full + 8 * k, ic & 1);
                if (k == 0) P2T(6);
                mbar_wait(b_full + 8 * s, ph);
                if (k == 7) asm volatile("bar.arrive %0, 256;" :: "r"(4 - wg) : "memory");
                if (k == 0) P2T(1);
                if (k == 7) P2T(2);
                const uint32_t b_lo = b_lo0 + s * 1024;
                wgmma_fence();
#pragma unroll
                for (int kk = 0; kk < (P2_NOMMA ? 1 : 4); kk++) {
                    wgmma_ss_n128_lo<1>(acc[0], a_lo + k * 1024 + kk * 2, b_lo + kk * 128, (k | kk) != 0);
                    wgmma_ss_n128_lo<1>(acc[1], a_lo + k * 1024 + 512 + kk * 2, b_lo + kk * 128, (k | kk) != 0);
                }
                wgmma_commit();
                if (k > 0) {
                    wgmma_wait<1>();
                    if (elected) {
                        const uint32_t e = b_empty + 8 * sprev;
                        mbar_arrive_cl(mapa_u32(e, 0)); mbar_arrive_cl(mapa_u32(e, 1));
                        if (last) mbar_arrive(a_empty + 8 * (k - 1));
                    }
                }
                sprev = s;
                if (++s == P2_STAGES) { s = 0; ph ^= 1; }
            }
            wgmma_wait<0>();
            P2T(3);
            if (elected) {
                const uint32_t e = b_empty + 8 * sprev;
                mbar_arrive_cl(mapa_u32(e, 0)); mbar_arrive_cl(mapa_u32(e, 1));
                if (last) mbar_arrive(a_empty + 8 * 7);
            }
            s += 8 % P2_STAGES; ph ^= (8 / P2_STAGES) & 1;
            if (s >= P2_STAGES) { s -= P2_STAGES; ph ^= 1; }
            const int m0 = (2 * mp + (int)rank) * 128;
            bf16* obase = P.out[z] + ((size_t)head * SEQ + m0 + (warp & 3) * 16 + (lane >> 2)) * HD + (lane & 3) * 8;
            store_frag_128<true, P2_PACE>(acc[0], obase, lane); store_frag_128<true, P2_PACE>(acc[1], obase + (size_t)64 * HD, lane);
            P2T(4);
            {
                asm volatile("bar.sync %0, 128;" :: "r"(1 + wg) : "memory");
                if (elected) {
                    const int e = wg * 4 + (nnote & 3);
                    mbar_wait(note_free + 8 * e, ((nnote >> 2) & 1) ^ 1);
                    asm volatile("st.shared.s32 [%0], %1;" :: "r"(note + e * 4), "r"(CT_AP + (head >> 1)) : "memory");
                    mbar_arrive(note_bar + 8 * e);
                }
                nnote++;
            }
            }
        }
        TS_END(0);
    }
    __syncthreads();
    cluster_sync_all();
}

struct OutParams {
    CUtensorMap mapCtx[2];
    CUtensorMap mapWo[2];
    CUtensorMap mapPart;
};
__device__ float g_part[4 * SEQ * DM];

#define OT(i)
constexpr int O2_STAGES = 4;
constexpr int O2_SMEM = O2_STAGES * 49152 + 1024 + 256;

__global__ void __cluster_dims__(2, 1, 1) __launch_bounds__(352, 1)
out2_kernel(const __grid_constant__ OutParams P, const bf16* __restrict__ x, const bf16* __restrict__ gate_w, bf16* __restrict__ out) {
    extern __shared__ uint8_t smem_raw[];
    const uint32_t sbase = (smem_u32(smem_raw) + 1023) & ~1023u;
    const uint32_t bar_full = sbase + O2_STAGES * 49152, bar_empty = bar_full + 8 * O2_STAGES;
    __shared__ float s_gate[32];
    const int warp = threadIdx.x >> 5, lane = threadIdx.x & 31;
    const uint32_t rank = cluster_ctarank();
    const int cid = blockIdx.x >> 1;
    const int late = cid >> 5, mp = (cid >> 1) & 7, nh = cid & 1;
    const int b = late ? 1 - ((cid >> 4) & 1) : (cid >> 4) & 1, kq = b * 2 + late;
    const int h0 = late ? O2_HE : 0;
    const int KT = late ? 2 * (NH - O2_HE) : 2 * O2_HE;
    const int m0 = (2 * mp + (int)rank) * 128, n0 = nh * 256;
    TS_BEGIN(4);
    OT(0);
    if (threadIdx.x == 0) {
        for (int i = 0; i < O2_STAGES; i++) { mbar_init(bar_full + 8 * i, 1); mbar_init(bar_empty + 8 * i, 4); }
        asm volatile("fence.mbarrier_init.release.cluster;" ::: "memory");
    }
    __syncthreads();
    asm volatile("barrier.cluster.arrive.release.aligned;" ::: "memory");
    if (threadIdx.x == 256) wait_ctr((b == 0 ? CT_CA : CT_CB) + (m0 >> 7) * 2 + late, (unsigned)KT);
    __syncwarp();
    asm volatile("barrier.cluster.wait.acquire.aligned;" ::: "memory");
    if (warp >= 8) {
        if (lane == 0) {
            int s = 0; uint32_t ph = 0;
            for (int i = 0; i < KT; i++) {
                mbar_wait(bar_empty + 8 * s, ph ^ 1);
                const uint32_t sa = sbase + s * 49152;
                const int head = h0 + (i >> 1), dk = (i & 1) * 64;
                if (warp == 8) {
                    mbar_expect_tx(bar_full + 8 * s, 49152);
                    tma_load_2d(sa, &P.mapCtx[b], bar_full + 8 * s, dk, head * SEQ + m0);
                } else {
                    const int j = (int)rank * 2 + (warp - 9);
                    tma_load_2d_mc(sa + 16384 + j * 8192, &P.mapWo[b], bar_full + 8 * s, n0 + j * 64, head * HD + dk, (uint16_t)3);
                }
                if (++s == O2_STAGES) { s = 0; ph ^= 1; }
            }
        }
    } else {
        const int wg = warp >> 2;
        const bool elected = (threadIdx.x & 127) == 0;
        float acc[128];
        {
            const int r = m0 + kq * 32 + (threadIdx.x >> 3);
            float sum = 0.f;
#pragma unroll
            for (int c = 0; c < 8; c++) {
                const int col = c * 64 + (threadIdx.x & 7) * 8;
                const uint4 xv = __ldg(reinterpret_cast<const uint4*>(x + (size_t)r * DM + col));
                const uint4 gv = __ldg(reinterpret_cast<const uint4*>(gate_w + col));
                const bf16* xp = reinterpret_cast<const bf16*>(&xv);
                const bf16* gp = reinterpret_cast<const bf16*>(&gv);
#pragma unroll
                for (int e = 0; e < 8; e++)
                    sum += __bfloat162float(__float2bfloat16(__bfloat162float(xp[e]) * __bfloat162float(gp[e])));
            }
            sum += __shfl_xor_sync(0xffffffff, sum, 1);
            sum += __shfl_xor_sync(0xffffffff, sum, 2);
            sum += __shfl_xor_sync(0xffffffff, sum, 4);
            sum = __bfloat162float(__float2bfloat16(sum));
            if ((threadIdx.x & 7) == 0) s_gate[threadIdx.x >> 3] = __bfloat162float(__float2bfloat16(1.f / (1.f + __expf(-sum))));
        }
        int s = 0, sprev = 0; uint32_t ph = 0;
#pragma unroll 1
        for (int i = 0; i < KT; i++) {
            mbar_wait(bar_full + 8 * s, ph);
            if (i == 0) OT(1);
            if (i == 8) OT(2);
            const uint32_t sa = sbase + s * 49152 + wg * 8192, sb = sbase + s * 49152 + 16384;
            wgmma_fence();
#pragma unroll
            for (int kk = 0; kk < 4; kk++)
                wgmma_ss_n256_tb(acc, make_desc(sa + kk * 32, 16, 1024), make_desc(sb + kk * 2048, 8192, 1024), (i | kk) != 0);
            wgmma_commit();
            if (i > 0) {
                wgmma_wait<1>();
                if (elected) { const uint32_t e = bar_empty + 8 * sprev; mbar_arrive_cl(mapa_u32(e, 0)); mbar_arrive_cl(mapa_u32(e, 1)); }
            }
            sprev = s;
            if (++s == O2_STAGES) { s = 0; ph ^= 1; }
        }
        wgmma_wait<0>();
        OT(3);
        {
            const int r = wg * 64 + (warp & 3) * 16 + (lane >> 2);
            if ((warp >> 1) == kq) {
#pragma unroll
                for (int j = 0; j < 32; j++) {
                    const uint32_t a = sbase + (j >> 2) * 16384 + r * 128 + ((((j & 3) * 2 + ((lane & 3) >> 1)) ^ (r & 7)) << 4) + (lane & 1) * 8;
                    asm volatile("st.shared.v2.f32 [%0], {%1, %2};" :: "r"(a), "f"(acc[j * 4 + 0]), "f"(acc[j * 4 + 1]) : "memory");
                    asm volatile("st.shared.v2.f32 [%0], {%1, %2};" :: "r"(a + 1024), "f"(acc[j * 4 + 2]), "f"(acc[j * 4 + 3]) : "memory");
                }
            } else {
                float* pp = g_part + ((size_t)kq * SEQ + m0 + r) * DM + n0 + (lane & 3) * 2;
#pragma unroll
                for (int j = 0; j < 32; j++) {
                    *reinterpret_cast<float2*>(pp + j * 8) = make_float2(acc[j * 4 + 0], acc[j * 4 + 1]);
                    *reinterpret_cast<float2*>(pp + 8 * DM + j * 8) = make_float2(acc[j * 4 + 2], acc[j * 4 + 3]);
                }
            }
        }
        asm volatile("bar.sync 1, 256;" ::: "memory");
        OT(4);
        unsigned int* ctr = &g_ctr[CT_OP + (2 * mp + (int)rank) * 2 + nh];
        if (threadIdx.x == 0) {
            asm volatile("fence.proxy.async;" ::: "memory");
            __threadfence();
            atomicAdd(ctr, 1u);
            unsigned int v; int it = 0;
            do { asm volatile("ld.acquire.gpu.global.u32 %0, [%1];" : "=r"(v) : "l"(ctr) : "memory"); } while (v < 4u && ++it < WAIT_LIMIT);
        }
        asm volatile("bar.sync 1, 256;" ::: "memory");
        OT(5);
        {
            const int c8 = threadIdx.x & 31, r0 = threadIdx.x >> 5;
            float4 u[4][3][2];
#pragma unroll
            for (int i = 0; i < 4; i++)
#pragma unroll
                for (int q = 1; q < 4; q++) {
                    const float4* p4 = reinterpret_cast<const float4*>(g_part + ((size_t)((kq + q) & 3) * SEQ + m0 + kq * 32 + r0 + i * 8) * DM + n0 + c8 * 8);
                    asm volatile("ld.relaxed.gpu.global.v4.f32 {%0, %1, %2, %3}, [%4];"
                                 : "=f"(u[i][q - 1][0].x), "=f"(u[i][q - 1][0].y), "=f"(u[i][q - 1][0].z), "=f"(u[i][q - 1][0].w) : "l"(p4) : "memory");
                    asm volatile("ld.relaxed.gpu.global.v4.f32 {%0, %1, %2, %3}, [%4];"
                                 : "=f"(u[i][q - 1][1].x), "=f"(u[i][q - 1][1].y), "=f"(u[i][q - 1][1].z), "=f"(u[i][q - 1][1].w) : "l"(p4 + 1) : "memory");
                }
#pragma unroll
            for (int i = 0; i < 4; i++) {
                const int rl = kq * 32 + r0 + i * 8;
                const float ga = s_gate[r0 + i * 8], gb = 1.f - ga;
                float o8[8];
#pragma unroll
                for (int hf = 0; hf < 2; hf++) {
                    float4 own;
                    const uint32_t a = sbase + (c8 >> 2) * 16384 + rl * 128 + ((((c8 & 3) * 2 + hf) ^ (rl & 7)) << 4);
                    asm volatile("ld.shared.v4.f32 {%0, %1, %2, %3}, [%4];" : "=f"(own.x), "=f"(own.y), "=f"(own.z), "=f"(own.w) : "r"(a) : "memory");
                    const int qp = ((kq ^ 1) - kq) & 3;
                    const float4 pa = qp == 1 ? u[i][0][hf] : u[i][2][hf];
                    const float4 o1 = u[i][1][hf];
                    const float4 o2 = qp == 1 ? u[i][2][hf] : u[i][0][hf];
                    const float gm = b == 0 ? ga : gb, go = b == 0 ? gb : ga;
                    o8[hf * 4 + 0] = gm * (own.x + pa.x) + go * (o1.x + o2.x);
                    o8[hf * 4 + 1] = gm * (own.y + pa.y) + go * (o1.y + o2.y);
                    o8[hf * 4 + 2] = gm * (own.z + pa.z) + go * (o1.z + o2.z);
                    o8[hf * 4 + 3] = gm * (own.w + pa.w) + go * (o1.w + o2.w);
                }
                *reinterpret_cast<uint4*>(out + (size_t)(m0 + rl) * DM + n0 + c8 * 8) =
                    make_uint4(pack_bf16(o8[0], o8[1]), pack_bf16(o8[2], o8[3]), pack_bf16(o8[4], o8[5]), pack_bf16(o8[6], o8[7]));
            }
        }
        OT(6);
        if (threadIdx.x == 0) {
            const unsigned int tk = atomicAdd(&g_ctr[CT_FIN], 1u);
            asm volatile("st.shared.u32 [%0], %1;" :: "r"(bar_empty + 8 * O2_STAGES), "r"(tk) : "memory");
        }
        asm volatile("bar.sync 1, 256;" ::: "memory");
        unsigned int tk;
        asm volatile("ld.shared.u32 %0, [%1];" : "=r"(tk) : "r"(bar_empty + 8 * O2_STAGES) : "memory");
        if (tk == gridDim.x - 1 && threadIdx.x < CT_N) g_ctr[threadIdx.x] = 0u;
    }
    __syncthreads();
    cluster_sync_all();
    TS_END(4);
}

typedef CUresult (*PFN_encodeTiled)(CUtensorMap*, CUtensorMapDataType, cuuint32_t, void*, const cuuint64_t*,
                                    const cuuint64_t*, const cuuint32_t*, const cuuint32_t*, CUtensorMapInterleave,
                                    CUtensorMapSwizzle, CUtensorMapL2promotion, CUtensorMapFloatOOBfill);
static PFN_encodeTiled g_encode = nullptr;

static void make_map(CUtensorMap* m, const void* ptr, uint64_t rows, uint64_t cols, uint32_t box_rows, bool sw64 = false) {
    cuuint64_t dims[2] = {cols, rows};
    cuuint64_t strides[1] = {cols * 2};
    cuuint32_t box[2] = {sw64 ? 32u : 64u, box_rows};
    cuuint32_t es[2] = {1, 1};
    g_encode(m, CU_TENSOR_MAP_DATA_TYPE_BFLOAT16, 2, const_cast<void*>(ptr), dims, strides, box, es,
             CU_TENSOR_MAP_INTERLEAVE_NONE, sw64 ? CU_TENSOR_MAP_SWIZZLE_64B : CU_TENSOR_MAP_SWIZZLE_128B, CU_TENSOR_MAP_L2_PROMOTION_L2_256B,
             CU_TENSOR_MAP_FLOAT_OOB_FILL_NONE);
}

template <typename... KArgs, typename... Args>
static void launch_pdl(void (*kernel)(KArgs...), int grid, int block, size_t smem, cudaStream_t st, bool pdl, Args... args) {
    cudaLaunchConfig_t cfg = {};
    cfg.gridDim = dim3(grid); cfg.blockDim = dim3(block); cfg.dynamicSmemBytes = smem; cfg.stream = st;
    cudaLaunchAttribute at[1];
    at[0].id = cudaLaunchAttributeProgrammaticStreamSerialization;
    at[0].val.programmaticStreamSerializationAllowed = 1;
    cfg.attrs = at; cfg.numAttrs = pdl ? 1 : 0;
    cudaLaunchKernelEx(&cfg, kernel, KArgs(args)...);
}

extern "C" void kernel_launch(void* const* d_in, const int* in_sizes, int n_in, void* d_out, int out_size) {
    const bf16* x = (const bf16*)d_in[0];
    const bf16* ckv = (const bf16*)d_in[1];
    const bf16* wq = (const bf16*)d_in[2];
    const bf16* wuk = (const bf16*)d_in[3];
    const bf16* wuv = (const bf16*)d_in[4];
    const bf16* wo = (const bf16*)d_in[5];
    const bf16* mem0 = (const bf16*)d_in[7];
    const bf16* Wq = (const bf16*)d_in[8];
    const bf16* Wk = (const bf16*)d_in[9];
    const bf16* Wv = (const bf16*)d_in[10];
    const bf16* Wo = (const bf16*)d_in[11];
    const bf16* gate_w = (const bf16*)d_in[13];
    bf16* out = (bf16*)d_out;

    static Proj2Params P2;
    static ChainParams CP;
    static AttnParams AP;
    static OutParams OP;
    static bool init = false;
    static const void* last_in[14];
    bool same = init;
    for (int i = 0; i < 14 && same; i++) same = last_in[i] == d_in[i];
    if (!init) {
        cudaDriverEntryPointQueryResult qr;
        cudaGetDriverEntryPoint("cuTensorMapEncodeTiled", (void**)&g_encode, cudaEnableDefault, &qr);
        cudaFuncSetAttribute(proj2_kernel, cudaFuncAttributeMaxDynamicSharedMemorySize, P2_SMEM);
        cudaFuncSetAttribute(attn_kernel, cudaFuncAttributeMaxDynamicSharedMemorySize, FA_SMEM);
        cudaFuncSetAttribute(chain_kernel, cudaFuncAttributeMaxDynamicSharedMemorySize, CH_SMEM);
        cudaFuncSetAttribute(out2_kernel, cudaFuncAttributeMaxDynamicSharedMemorySize, O2_SMEM);
        init = true;
    }
    if (!same) {
        for (int i = 0; i < 14; i++) last_in[i] = d_in[i];
        void *pQA, *pKA, *pVA, *pCA, *pCB;
        cudaGetSymbolAddress(&pQA, g_QA); cudaGetSymbolAddress(&pKA, g_KA); cudaGetSymbolAddress(&pVA, g_VA);
        cudaGetSymbolAddress(&pCA, g_ctxA); cudaGetSymbolAddress(&pCB, g_ctxB);
        make_map(&P2.mapA[0], x, SEQ, DM, 128);
        make_map(&P2.mapA[1], ckv, SEQ, DM, 128);
        const void* ws[3] = {wq, wuk, wuv};
        void* cs[3] = {pQA, pKA, pVA};
        for (int i = 0; i < 3; i++) { make_map(&P2.mapW[i], ws[i], DM, NQ, 64); P2.out[i] = (bf16*)cs[i]; }
        make_map(&CP.mapW[0], Wq, DM, NQ, 64); make_map(&CP.mapW[1], Wk, DM, NQ, 64); make_map(&CP.mapW[2], Wv, DM, NQ, 64);
        make_map(&CP.mapX, x, SEQ, DM, 32);
        make_map(&CP.mapC, pCB, NH * SEQ, HD, 32);
        make_map(&AP.mapQ, pQA, NH * SEQ, HD, 128);
        make_map(&AP.mapK, pKA, NH * SEQ, HD, 128);
        make_map(&AP.mapV, pVA, NH * SEQ, HD, 128);
        make_map(&AP.mapO, pCA, NH * SEQ, HD, 64);
        make_map(&OP.mapCtx[0], pCA, NH * SEQ, HD, 128);
        make_map(&OP.mapCtx[1], pCB, NH * SEQ, HD, 128);
        make_map(&OP.mapWo[0], wo, NQ, DM, 64);
        make_map(&OP.mapWo[1], Wo, NQ, DM, 64);
        {
            void* pP; cudaGetSymbolAddress(&pP, g_part);
            cuuint64_t dims[2] = {DM, 4 * SEQ}; cuuint64_t strides[1] = {DM * 4}; cuuint32_t box[2] = {32, 32}; cuuint32_t es[2] = {1, 1};
            g_encode(&OP.mapPart, CU_TENSOR_MAP_DATA_TYPE_FLOAT32, 2, pP, dims, strides, box, es, CU_TENSOR_MAP_INTERLEAVE_NONE,
                     CU_TENSOR_MAP_SWIZZLE_128B, CU_TENSOR_MAP_L2_PROMOTION_NONE, CU_TENSOR_MAP_FLOAT_OOB_FILL_NONE);
        }
    }
    cudaStream_t s1 = cudaStreamPerThread;
    const bool pdl = true;
    launch_pdl(chain_kernel, 64, CH_BLOCK, CH_SMEM, s1, false, CP, mem0, Wo, x);
    launch_pdl(proj2_kernel, 68, 384, P2_SMEM, s1, pdl, P2);
    launch_pdl(attn_kernel, FA_GRID, 384, FA_SMEM, s1, pdl, AP, 1000);
    launch_pdl(out2_kernel, 128, 352, O2_SMEM, s1, pdl, OP, x, gate_w, out);
}
```

```cpp
#include <cuda_runtime.h>
#include <cuda_bf16.h>
#include <cuda.h>
#include <stdint.h>
#include <type_traits>

constexpr int SEQ = 2048;
constexpr int DM = 512;
constexpr int NH = 32;
constexpr int HD = 128;
constexpr int NQ = NH * HD;
constexpr int SEGL = 32;
constexpr int NMEM = 8;
constexpr int NSEG = SEQ / SEGL;

typedef __nv_bfloat16 bf16;

__device__ bf16 g_QA[SEQ * NQ];
__device__ bf16 g_KA[SEQ * NQ];
__device__ bf16 g_VA[SEQ * NQ];
__device__ bf16 g_ctxA[SEQ * NQ];
__device__ bf16 g_ctxB[SEQ * NQ];
constexpr int CT_PROJ = 0, CT_ATTN = 1, CT_FIN = 5;
constexpr int CT_AP = 64;
constexpr int CT_GATE = 96;
constexpr int CT_CA = 128;
constexpr int CT_CB = 192;
constexpr int CT_OT = 208;
constexpr int CT_N = 224;
__device__ unsigned int g_ctr[CT_N];
__device__ float g_gate[SEQ];
__device__ uint32_t g_xbuf[4 * 8 * 2048];

#define FA_GRID 68

#define TS_BEGIN(id)
#define TS_END(id)
#define WAIT_LIMIT 200000
__device__ __forceinline__ void pdl_launch_dependents() { asm volatile("griddepcontrol.launch_dependents;" ::: "memory"); }
__device__ __forceinline__ void wait_ctr(int idx, unsigned int n) {
    unsigned int v; int it = 0;
    do { asm volatile("ld.acquire.gpu.global.u32 %0, [%1];" : "=r"(v) : "l"(&g_ctr[idx]) : "memory"); } while (v < n && ++it < WAIT_LIMIT);
    asm volatile("fence.proxy.async;" ::: "memory");
}
__device__ __forceinline__ void signal_ctr(int idx) {
    asm volatile("fence.proxy.async;" ::: "memory");
    __threadfence();
    atomicAdd(&g_ctr[idx], 1u);
}
__device__ __forceinline__ void signal_ctr_generic(int idx) {
    asm volatile("red.release.gpu.global.add.u32 [%0], 1;" :: "l"(&g_ctr[idx]) : "memory");
}
__device__ __forceinline__ uint32_t smem_u32(const void* p) {
    return (uint32_t)__cvta_generic_to_shared(p);
}
__device__ __forceinline__ void mbar_init(uint32_t bar, uint32_t count) {
    asm volatile("mbarrier.init.shared::cta.b64 [%0], %1;" :: "r"(bar), "r"(count));
}
__device__ __forceinline__ void mbar_expect_tx(uint32_t bar, uint32_t bytes) {
    asm volatile("mbarrier.arrive.expect_tx.shared::cta.b64 _, [%0], %1;" :: "r"(bar), "r"(bytes) : "memory");
}
__device__ __forceinline__ void mbar_arrive(uint32_t bar) {
    asm volatile("mbarrier.arrive.shared::cta.b64 _, [%0];" :: "r"(bar) : "memory");
}
__device__ __forceinline__ void mbar_wait(uint32_t bar, uint32_t parity) {
    asm volatile(
        "{\n"
        ".reg .pred p, q;\n"
        ".reg .u32 c;\n"
        "mov.u32 c, 0;\n"
        "WAIT_LOOP:\n"
        "mbarrier.try_wait.parity.shared::cta.b64 p, [%0], %1;\n"
        "@p bra WAIT_DONE;\n"
        "add.u32 c, c, 1;\n"
        "setp.lt.u32 q, c, %2;\n"
        "@q bra WAIT_LOOP;\n"
        "WAIT_DONE:\n"
        "}\n" :: "r"(bar), "r"(parity), "n"(WAIT_LIMIT) : "memory");
}
__device__ __forceinline__ void tma_load_2d(uint32_t dst, const CUtensorMap* map, uint32_t bar, int c0, int c1) {
    asm volatile(
        "cp.async.bulk.tensor.2d.shared::cluster.global.mbarrier::complete_tx::bytes [%0], [%1, {%3, %4}], [%2];"
        :: "r"(dst), "l"((uint64_t)map), "r"(bar), "r"(c0), "r"(c1) : "memory");
}
__device__ __forceinline__ void wgmma_fence() { asm volatile("wgmma.fence.sync.aligned;" ::: "memory"); }
__device__ __forceinline__ void wgmma_commit() { asm volatile("wgmma.commit_group.sync.aligned;" ::: "memory"); }
template <int N> __device__ __forceinline__ void wgmma_wait() {
    asm volatile("wgmma.wait_group.sync.aligned %0;" :: "n"(N) : "memory");
}
__device__ __forceinline__ uint64_t make_desc(uint32_t addr, uint32_t lbo, uint32_t sbo) {
    uint64_t d = 0;
    d |= (uint64_t)((addr & 0x3FFFF) >> 4);
    d |= (uint64_t)((lbo >> 4) & 0x3FFF) << 16;
    d |= (uint64_t)((sbo >> 4) & 0x3FFF) << 32;
    d |= (uint64_t)1 << 62;
    return d;
}

#define ACC64(d) \
    "+f"(d[0]), "+f"(d[1]), "+f"(d[2]), "+f"(d[3]), "+f"(d[4]), "+f"(d[5]), "+f"(d[6]), "+f"(d[7]), \
    "+f"(d[8]), "+f"(d[9]), "+f"(d[10]), "+f"(d[11]), "+f"(d[12]), "+f"(d[13]), "+f"(d[14]), "+f"(d[15]), \
    "+f"(d[16]), "+f"(d[17]), "+f"(d[18]), "+f"(d[19]), "+f"(d[20]), "+f"(d[21]), "+f"(d[22]), "+f"(d[23]), \
    "+f"(d[24]), "+f"(d[25]), "+f"(d[26]), "+f"(d[27]), "+f"(d[28]), "+f"(d[29]), "+f"(d[30]), "+f"(d[31]), \
    "+f"(d[32]), "+f"(d[33]), "+f"(d[34]), "+f"(d[35]), "+f"(d[36]), "+f"(d[37]), "+f"(d[38]), "+f"(d[39]), \
    "+f"(d[40]), "+f"(d[41]), "+f"(d[42]), "+f"(d[43]), "+f"(d[44]), "+f"(d[45]), "+f"(d[46]), "+f"(d[47]), \
    "+f"(d[48]), "+f"(d[49]), "+f"(d[50]), "+f"(d[51]), "+f"(d[52]), "+f"(d[53]), "+f"(d[54]), "+f"(d[55]), \
    "+f"(d[56]), "+f"(d[57]), "+f"(d[58]), "+f"(d[59]), "+f"(d[60]), "+f"(d[61]), "+f"(d[62]), "+f"(d[63])
#define ACC64_STR \
    "{%0, %1, %2, %3, %4, %5, %6, %7, %8, %9, %10, %11, %12, %13, %14, %15, " \
    "%16, %17, %18, %19, %20, %21, %22, %23, %24, %25, %26, %27, %28, %29, %30, %31, " \
    "%32, %33, %34, %35, %36, %37, %38, %39, %40, %41, %42, %43, %44, %45, %46, %47, " \
    "%48, %49, %50, %51, %52, %53, %54, %55, %56, %57, %58, %59, %60, %61, %62, %63}"

template <int TB>
__device__ __forceinline__ void wgmma_ss_n128(float (&d)[64], uint64_t da, uint64_t db, int scale_d) {
    asm volatile(
        "{\n.reg .pred p;\nsetp.ne.b32 p, %66, 0;\n"
        "wgmma.mma_async.sync.aligned.m64n128k16.f32.bf16.bf16 " ACC64_STR ", %64, %65, p, 1, 1, 0, %67;\n}\n"
        : ACC64(d) : "l"(da), "l"(db), "r"(scale_d), "n"(TB));
}
__device__ __forceinline__ uint32_t desc_lo(uint32_t addr, uint32_t lbo) { return ((addr & 0x3FFFF) >> 4) | ((lbo >> 4) << 16); }
template <int TB>
__device__ __forceinline__ void wgmma_ss_n128_lo(float (&d)[64], uint32_t da_lo, uint32_t db_lo, int scale_d) {
    asm volatile(
        "{\n.reg .pred p;\n.reg .b64 da, db;\nsetp.ne.b32 p, %66, 0;\n"
        "mov.b64 da, {%64, 0x40000040};\nmov.b64 db, {%65, 0x40000040};\n"
        "wgmma.mma_async.sync.aligned.m64n128k16.f32.bf16.bf16 " ACC64_STR ", da, db, p, 1, 1, 0, %67;\n}\n"
        : ACC64(d) : "r"(da_lo), "r"(db_lo), "r"(scale_d), "n"(TB));
}
__device__ __forceinline__ void wgmma_rs_n128_tb(float (&d)[64], uint32_t a0, uint32_t a1, uint32_t a2, uint32_t a3,
                                                 uint64_t db, int scale_d) {
    asm volatile(
        "{\n.reg .pred p;\nsetp.ne.b32 p, %69, 0;\n"
        "wgmma.mma_async.sync.aligned.m64n128k16.f32.bf16.bf16 " ACC64_STR ", {%64, %65, %66, %67}, %68, p, 1, 1, 1;\n}\n"
        : ACC64(d) : "r"(a0), "r"(a1), "r"(a2), "r"(a3), "l"(db), "r"(scale_d));
}
__device__ __forceinline__ void wgmma_rs_n80(float (&d)[40], const uint32_t (&a)[4], uint32_t db_lo, int scale_d) {
    asm volatile(
        "{\n.reg .pred p;\n.reg .b64 db;\nsetp.ne.b32 p, %45, 0;\nmov.b64 db, {%44, 0x40000040};\n"
        "wgmma.mma_async.sync.aligned.m64n80k16.f32.bf16.bf16 "
        "{%0, %1, %2, %3, %4, %5, %6, %7, %8, %9, %10, %11, %12, %13, %14, %15, %16, %17, %18, %19, %20, %21, %22, %23, %24, %25, %26, %27, %28, %29, %30, %31, %32, %33, %34, %35, %36, %37, %38, %39}, "
        "{%40, %41, %42, %43}, db, p, 1, 1, 0;\n}\n"
        : "+f"(d[0]), "+f"(d[1]), "+f"(d[2]), "+f"(d[3]), "+f"(d[4]), "+f"(d[5]), "+f"(d[6]), "+f"(d[7]), "+f"(d[8]), "+f"(d[9]), "+f"(d[10]), "+f"(d[11]), "+f"(d[12]), "+f"(d[13]), "+f"(d[14]), "+f"(d[15]), "+f"(d[16]), "+f"(d[17]), "+f"(d[18]), "+f"(d[19]), "+f"(d[20]), "+f"(d[21]), "+f"(d[22]), "+f"(d[23]), "+f"(d[24]), "+f"(d[25]), "+f"(d[26]), "+f"(d[27]), "+f"(d[28]), "+f"(d[29]), "+f"(d[30]), "+f"(d[31]), "+f"(d[32]), "+f"(d[33]), "+f"(d[34]), "+f"(d[35]), "+f"(d[36]), "+f"(d[37]), "+f"(d[38]), "+f"(d[39])
        : "r"(a[0]), "r"(a[1]), "r"(a[2]), "r"(a[3]), "r"(db_lo), "r"(scale_d));
}
__device__ __forceinline__ void wgmma_ss_n256_tb(float (&d)[128], uint64_t da, uint64_t db, int scale_d) {
    asm volatile(
        "{\n.reg .pred p;\nsetp.ne.b32 p, %130, 0;\n"
        "wgmma.mma_async.sync.aligned.m64n256k16.f32.bf16.bf16 {%0, %1, %2, %3, %4, %5, %6, %7, %8, %9, %10, %11, %12, %13, %14, %15, %16, %17, %18, %19, %20, %21, %22, %23, %24, %25, %26, %27, %28, %29, %30, %31, %32, %33, %34, %35, %36, %37, %38, %39, %40, %41, %42, %43, %44, %45, %46, %47, %48, %49, %50, %51, %52, %53, %54, %55, %56, %57, %58, %59, %60, %61, %62, %63, %64, %65, %66, %67, %68, %69, %70, %71, %72, %73, %74, %75, %76, %77, %78, %79, %80, %81, %82, %83, %84, %85, %86, %87, %88, %89, %90, %91, %92, %93, %94, %95, %96, %97, %98, %99, %100, %101, %102, %103, %104, %105, %106, %107, %108, %109, %110, %111, %112, %113, %114, %115, %116, %117, %118, %119, %120, %121, %122, %123, %124, %125, %126, %127}, %128, %129, p, 1, 1, 0, 1;\n}\n"
        : "+f"(d[0]), "+f"(d[1]), "+f"(d[2]), "+f"(d[3]), "+f"(d[4]), "+f"(d[5]), "+f"(d[6]), "+f"(d[7]), "+f"(d[8]), "+f"(d[9]), "+f"(d[10]), "+f"(d[11]), "+f"(d[12]), "+f"(d[13]), "+f"(d[14]), "+f"(d[15]), "+f"(d[16]), "+f"(d[17]), "+f"(d[18]), "+f"(d[19]), "+f"(d[20]), "+f"(d[21]), "+f"(d[22]), "+f"(d[23]), "+f"(d[24]), "+f"(d[25]), "+f"(d[26]), "+f"(d[27]), "+f"(d[28]), "+f"(d[29]), "+f"(d[30]), "+f"(d[31]), "+f"(d[32]), "+f"(d[33]), "+f"(d[34]), "+f"(d[35]), "+f"(d[36]), "+f"(d[37]), "+f"(d[38]), "+f"(d[39]), "+f"(d[40]), "+f"(d[41]), "+f"(d[42]), "+f"(d[43]), "+f"(d[44]), "+f"(d[45]), "+f"(d[46]), "+f"(d[47]), "+f"(d[48]), "+f"(d[49]), "+f"(d[50]), "+f"(d[51]), "+f"(d[52]), "+f"(d[53]), "+f"(d[54]), "+f"(d[55]), "+f"(d[56]), "+f"(d[57]), "+f"(d[58]), "+f"(d[59]), "+f"(d[60]), "+f"(d[61]), "+f"(d[62]), "+f"(d[63]), "+f"(d[64]), "+f"(d[65]), "+f"(d[66]), "+f"(d[67]), "+f"(d[68]), "+f"(d[69]), "+f"(d[70]), "+f"(d[71]), "+f"(d[72]), "+f"(d[73]), "+f"(d[74]), "+f"(d[75]), "+f"(d[76]), "+f"(d[77]), "+f"(d[78]), "+f"(d[79]), "+f"(d[80]), "+f"(d[81]), "+f"(d[82]), "+f"(d[83]), "+f"(d[84]), "+f"(d[85]), "+f"(d[86]), "+f"(d[87]), "+f"(d[88]), "+f"(d[89]), "+f"(d[90]), "+f"(d[91]), "+f"(d[92]), "+f"(d[93]), "+f"(d[94]), "+f"(d[95]), "+f"(d[96]), "+f"(d[97]), "+f"(d[98]), "+f"(d[99]), "+f"(d[100]), "+f"(d[101]), "+f"(d[102]), "+f"(d[103]), "+f"(d[104]), "+f"(d[105]), "+f"(d[106]), "+f"(d[107]), "+f"(d[108]), "+f"(d[109]), "+f"(d[110]), "+f"(d[111]), "+f"(d[112]), "+f"(d[113]), "+f"(d[114]), "+f"(d[115]), "+f"(d[116]), "+f"(d[117]), "+f"(d[118]), "+f"(d[119]), "+f"(d[120]), "+f"(d[121]), "+f"(d[122]), "+f"(d[123]), "+f"(d[124]), "+f"(d[125]), "+f"(d[126]), "+f"(d[127])
        : "l"(da), "l"(db), "r"(scale_d));
}
__device__ __forceinline__ void stmatrix_x4(uint32_t addr, uint32_t r0, uint32_t r1, uint32_t r2, uint32_t r3) {
    asm volatile("stmatrix.sync.aligned.m8n8.x4.shared.b16 [%0], {%1, %2, %3, %4};" :: "r"(addr), "r"(r0), "r"(r1), "r"(r2), "r"(r3) : "memory");
}
__device__ __forceinline__ void tma_store_2d(const CUtensorMap* map, uint32_t src, int c0, int c1) {
    asm volatile("cp.async.bulk.tensor.2d.global.shared::cta.bulk_group [%0, {%2, %3}], [%1];"
                 :: "l"((uint64_t)map), "r"(src), "r"(c0), "r"(c1) : "memory");
}
__device__ __forceinline__ float ex2f(float x) { float y; asm("ex2.approx.ftz.f32 %0, %1;" : "=f"(y) : "f"(x)); return y; }
__device__ __forceinline__ uint32_t pack_bf16(float lo, float hi) {
    __nv_bfloat162 v = __floats2bfloat162_rn(lo, hi);
    return *reinterpret_cast<uint32_t*>(&v);
}
__device__ __forceinline__ void mma_16816(float (&c)[4], uint32_t a0, uint32_t a1, uint32_t a2, uint32_t a3,
                                          uint32_t b0, uint32_t b1) {
    asm volatile(
        "mma.sync.aligned.m16n8k16.row.col.f32.bf16.bf16.f32 {%0,%1,%2,%3}, {%4,%5,%6,%7}, {%8,%9}, {%0,%1,%2,%3};"
        : "+f"(c[0]), "+f"(c[1]), "+f"(c[2]), "+f"(c[3])
        : "r"(a0), "r"(a1), "r"(a2), "r"(a3), "r"(b0), "r"(b1));
}
__device__ __forceinline__ void ldmatrix_x4_trans(uint32_t& r0, uint32_t& r1, uint32_t& r2, uint32_t& r3, uint32_t addr) {
    asm volatile("ldmatrix.sync.aligned.m8n8.x4.trans.shared.b16 {%0,%1,%2,%3}, [%4];"
                 : "=r"(r0), "=r"(r1), "=r"(r2), "=r"(r3) : "r"(addr));
}

struct AttnParams {
    CUtensorMap mapQ, mapK, mapV;
    CUtensorMap mapO;
};
constexpr int FA_STAGES = 2;
constexpr int FA_SMEM = 32768 + FA_STAGES * 65536 + 32768 + 1024 + 256;
constexpr int FA_ITEMS = 16 * NH;
#define FA_RETIRE 100000
#define FA_LASTG 8
__device__ __forceinline__ int fa_qt(int t) {
    constexpr int T0 = (32 - FA_LASTG) * 16;
    return t < T0 ? 15 - ((t & 127) >> 3) : 15 - (t - T0) / FA_LASTG;
}
__device__ __forceinline__ int fa_head(int t) {
    constexpr int T0 = (32 - FA_LASTG) * 16;
    return t < T0 ? (t >> 7) * 8 + (t & 7) : (32 - FA_LASTG) + (t - T0) % FA_LASTG;
}

__global__ void __launch_bounds__(384, 1) attn_kernel(const __grid_constant__ AttnParams P, int retire_cta) {
    extern __shared__ uint8_t smem_raw[];
    uint32_t sbase = (smem_u32(smem_raw) + 1023) & ~1023u;
    const uint32_t sQ = sbase;
    const uint32_t sKV = sbase + 32768;
    const uint32_t sO = sKV + FA_STAGES * 65536;
    const uint32_t bars = sO + 32768;
    const uint32_t bar_q = bars, bar_qe = bars + 8, bar_kf = bars + 16, bar_vf = bar_kf + 8 * FA_STAGES, bar_e = bar_vf + 8 * FA_STAGES,
                   bar_ek = bar_e + 8 * FA_STAGES, slot = bar_ek + 8 * FA_STAGES, bar_of = slot + 16, bar_oe = bar_of + 16, oslot = bar_oe + 16;
    const int warp = threadIdx.x >> 5;
    TS_BEGIN(1);
    int tfirst = 0;
    if (threadIdx.x == 256) tfirst = (int)atomicAdd(&g_ctr[CT_ATTN], 1u);
    if (threadIdx.x == 0) {
        mbar_init(bar_q, 1); mbar_init(bar_qe, 8);
        for (int i = 0; i < FA_STAGES; i++) { mbar_init(bar_kf + 8 * i, 1); mbar_init(bar_vf + 8 * i, 1); mbar_init(bar_e + 8 * i, 8); mbar_init(bar_ek + 8 * i, 8); }
        for (int i = 0; i < 2; i++) { mbar_init(bar_of + 8 * i, 1); mbar_init(bar_oe + 8 * i, 1); }
        asm volatile("fence.mbarrier_init.release.cluster;" ::: "memory");
    }
    if (threadIdx.x == 256) asm volatile("st.shared.s32 [%0], %1;" :: "r"(slot + 8), "r"(tfirst) : "memory");
    __syncthreads();
    pdl_launch_dependents();
    if (warp >= 8) {
        asm volatile("setmaxnreg.dec.sync.aligned.u32 40;");
        if (threadIdx.x == 288 || threadIdx.x == 320) {
            const int wg = threadIdx.x == 288 ? 0 : 1;
            const uint32_t stg = sO + wg * 16384;
            for (int n = 0;; n++) {
                mbar_wait(bar_of + 8 * wg, n & 1);
                int t;
                asm volatile("ld.shared.s32 %0, [%1];" : "=r"(t) : "r"(oslot + wg * 4) : "memory");
                if (t < 0) break;
                const int qt = fa_qt(t), h = fa_head(t);
                tma_store_2d(&P.mapO, stg, 0, h * SEQ + qt * 128 + wg * 64);
                tma_store_2d(&P.mapO, stg + 8192, 64, h * SEQ + qt * 128 + wg * 64);
                asm volatile("cp.async.bulk.commit_group;" ::: "memory");
                asm volatile("cp.async.bulk.wait_group.read 0;" ::: "memory");
                mbar_arrive(bar_oe + 8 * wg);
                asm volatile("cp.async.bulk.wait_group 0;" ::: "memory");
                signal_ctr(CT_CA + qt * 4 + (h >> 3));
            }
        }
        if (threadIdx.x == 256) {
            int it = 0, hp_ready = 0;
            wait_ctr(CT_GATE, 64u);
            for (int item = 0;; item++) {
                int t = tfirst;
                if (item > 0) {
                    bool quit = false;
                    if ((int)blockIdx.x >= retire_cta) {
                        unsigned int v;
                        asm volatile("ld.relaxed.gpu.global.u32 %0, [%1];" : "=r"(v) : "l"(&g_ctr[CT_ATTN]) : "memory");
                        quit = v >= FA_RETIRE;
                    }
                    t = quit ? FA_ITEMS : (int)atomicAdd(&g_ctr[CT_ATTN], 1u);
                }
                const bool valid = t < FA_ITEMS;
                const int qt = fa_qt(t), h = fa_head(t);
                if (valid && !((hp_ready >> (h >> 1)) & 1)) { wait_ctr(CT_AP + (h >> 1), 96u); hp_ready |= 1 << (h >> 1); }
                mbar_wait(bar_qe, (item & 1) ^ 1);
                asm volatile("st.shared.s32 [%0], %1;" :: "r"(slot + (item & 1) * 4), "r"(valid ? t : -1) : "memory");
                if (!valid) { mbar_arrive(bar_q); break; }
                mbar_expect_tx(bar_q, 32768);
                tma_load_2d(sQ, &P.mapQ, bar_q, 0, h * SEQ + qt * 128);
                tma_load_2d(sQ + 16384, &P.mapQ, bar_q, 64, h * SEQ + qt * 128);
                for (int j = 0; j <= qt; j++, it++) {
                    const int s = it % FA_STAGES;
                    mbar_wait(bar_ek + 8 * s, ((it / FA_STAGES) & 1) ^ 1);
                    const uint32_t sk = sKV + s * 65536, sv = sk + 32768;
                    mbar_expect_tx(bar_kf + 8 * s, 32768);
                    tma_load_2d(sk, &P.mapK, bar_kf + 8 * s, 0, h * SEQ + j * 128);
                    tma_load_2d(sk + 16384, &P.mapK, bar_kf + 8 * s, 64, h * SEQ + j * 128);
                    mbar_wait(bar_e + 8 * s, ((it / FA_STAGES) & 1) ^ 1);
                    mbar_expect_tx(bar_vf + 8 * s, 32768);
                    tma_load_2d(sv, &P.mapV, bar_vf + 8 * s, 0, h * SEQ + j * 128);
                    tma_load_2d(sv + 16384, &P.mapV, bar_vf + 8 * s, 64, h * SEQ + j * 128);
                }
            }
        }
    } else {
        asm volatile("setmaxnreg.inc.sync.aligned.u32 232;");
        const int wg = warp >> 2;
        const int lane = threadIdx.x & 31;
        float o[64];
        float mrow0, mrow1, lrow0, lrow1;
        const float sc = 0.08838834764831845f * 1.4426950408889634f;
        const int r0 = wg * 64 + (warp & 3) * 16 + (lane >> 2);
        float sacc[64];
        uint32_t pa[32];
        float a0 = 1.f, a1 = 1.f;
        auto issue_qk = [&](int it) {
            const int s = it % FA_STAGES;
            const uint32_t sk = sKV + s * 65536;
            mbar_wait(bar_kf + 8 * s, (it / FA_STAGES) & 1);
            wgmma_fence();
#pragma unroll
            for (int kk = 0; kk < 8; kk++) {
                uint64_t da = make_desc(sQ + (kk >> 2) * 16384 + wg * 8192 + (kk & 3) * 32, 16, 1024);
                uint64_t db = make_desc(sk + (kk >> 2) * 16384 + (kk & 3) * 32, 16, 1024);
                wgmma_ss_n128<0>(sacc, da, db, kk != 0);
            }
            wgmma_commit();
        };
        auto issue_pv = [&](int it) {
            const int s = it % FA_STAGES;
            const uint32_t sv = sKV + s * 65536 + 32768;
            mbar_wait(bar_vf + 8 * s, (it / FA_STAGES) & 1);
            wgmma_fence();
#pragma unroll
            for (int kk = 0; kk < 8; kk++) {
                uint64_t db = make_desc(sv + kk * 2048, 16384, 1024);
                wgmma_rs_n128_tb(o, pa[kk * 4 + 0], pa[kk * 4 + 1], pa[kk * 4 + 2], pa[kk * 4 + 3], db, 1);
            }
            wgmma_commit();
        };
        auto softmax_stats = [&](bool diag) {
            if (diag) {
#pragma unroll
                for (int i = 0; i < 64; i++) {
                    int col = (i >> 2) * 8 + (lane & 3) * 2 + (i & 1);
                    int row = r0 + ((i & 2) ? 8 : 0);
                    if (col > row) sacc[i] = -INFINITY;
                }
            }
            float mx0 = -INFINITY, mx1 = -INFINITY;
#pragma unroll
            for (int i = 0; i < 16; i++) {
                mx0 = fmaxf(mx0, fmaxf(sacc[i * 4 + 0], sacc[i * 4 + 1]));
                mx1 = fmaxf(mx1, fmaxf(sacc[i * 4 + 2], sacc[i * 4 + 3]));
            }
            mx0 = fmaxf(mx0, __shfl_xor_sync(0xffffffff, mx0, 1));
            mx0 = fmaxf(mx0, __shfl_xor_sync(0xffffffff, mx0, 2));
            mx1 = fmaxf(mx1, __shfl_xor_sync(0xffffffff, mx1, 1));
            mx1 = fmaxf(mx1, __shfl_xor_sync(0xffffffff, mx1, 2));
            const float mn0 = fmaxf(mrow0, mx0), mn1 = fmaxf(mrow1, mx1);
            a0 = ex2f((mrow0 - mn0) * sc); a1 = ex2f((mrow1 - mn1) * sc);
            mrow0 = mn0; mrow1 = mn1;
            const float ms0 = mn0 * sc, ms1 = mn1 * sc;
            float sum0 = 0.f, sum1 = 0.f;
#pragma unroll
            for (int i = 0; i < 16; i++) {
                sacc[i * 4 + 0] = ex2f(fmaf(sacc[i * 4 + 0], sc, -ms0));
                sacc[i * 4 + 1] = ex2f(fmaf(sacc[i * 4 + 1], sc, -ms0));
                sacc[i * 4 + 2] = ex2f(fmaf(sacc[i * 4 + 2], sc, -ms1));
                sacc[i * 4 + 3] = ex2f(fmaf(sacc[i * 4 + 3], sc, -ms1));
                sum0 += sacc[i * 4 + 0] + sacc[i * 4 + 1];
                sum1 += sacc[i * 4 + 2] + sacc[i * 4 + 3];
            }
            lrow0 = lrow0 * a0 + sum0;
            lrow1 = lrow1 * a1 + sum1;
        };
        auto pack_p = [&]() {
#pragma unroll
            for (int i = 0; i < 16; i++) {
                pa[i * 2 + 0] = pack_bf16(sacc[i * 4 + 0], sacc[i * 4 + 1]);
                pa[i * 2 + 1] = pack_bf16(sacc[i * 4 + 2], sacc[i * 4 + 3]);
            }
        };
        int it = 0;
        if (wg == 1) asm volatile("bar.arrive 1, 256;" ::: "memory");
        for (int item = 0;; item++) {
            mbar_wait(bar_q, item & 1);
            int t;
            asm volatile("ld.shared.s32 %0, [%1];" : "=r"(t) : "r"(slot + (item & 1) * 4) : "memory");
            if (t < 0) {
                if ((threadIdx.x & 127) == 0) {
                    mbar_wait(bar_oe + 8 * wg, (item & 1) ^ 1);
                    asm volatile("st.shared.s32 [%0], %1;" :: "r"(oslot + wg * 4), "r"(-1) : "memory");
                    mbar_arrive(bar_of + 8 * wg);
                }
                break;
            }
            const int qt = fa_qt(t);
            const int nkv = qt + 1;
#pragma unroll
            for (int i = 0; i < 64; i++) o[i] = 0.f;
            mrow0 = -INFINITY; mrow1 = -INFINITY; lrow0 = 0.f; lrow1 = 0.f;
            asm volatile("bar.sync %0, 256;" :: "r"(1 + wg) : "memory");
            issue_qk(it);
            asm volatile("bar.arrive %0, 256;" :: "r"(2 - wg) : "memory");
            wgmma_wait<0>();
            if (lane == 0) { mbar_arrive(bar_ek + 8 * (it % FA_STAGES)); if (nkv == 1) mbar_arrive(bar_qe); }
            softmax_stats(nkv == 1);
            pack_p();
#pragma unroll 1
            for (int j = 1; j < nkv; j++) {
                asm volatile("bar.sync %0, 256;" :: "r"(1 + wg) : "memory");
                issue_qk(it + j);
                issue_pv(it + j - 1);
                asm volatile("bar.arrive %0, 256;" :: "r"(2 - wg) : "memory");
                wgmma_wait<1>();
                if (lane == 0) { mbar_arrive(bar_ek + 8 * ((it + j) % FA_STAGES)); if (j == nkv - 1) mbar_arrive(bar_qe); }
                softmax_stats(j == nkv - 1);
                wgmma_wait<0>();
                if (lane == 0) mbar_arrive(bar_e + 8 * ((it + j - 1) % FA_STAGES));
#pragma unroll
                for (int i = 0; i < 16; i++) {
                    o[i * 4 + 0] *= a0; o[i * 4 + 1] *= a0; o[i * 4 + 2] *= a1; o[i * 4 + 3] *= a1;
                }
                pack_p();
            }
            issue_pv(it + nkv - 1);
            wgmma_wait<0>();
            if (lane == 0) mbar_arrive(bar_e + 8 * ((it + nkv - 1) % FA_STAGES));
            it += nkv;
            lrow0 += __shfl_xor_sync(0xffffffff, lrow0, 1);
            lrow0 += __shfl_xor_sync(0xffffffff, lrow0, 2);
            lrow1 += __shfl_xor_sync(0xffffffff, lrow1, 1);
            lrow1 += __shfl_xor_sync(0xffffffff, lrow1, 2);
            const float i0 = __ldcg(g_gate + qt * 128 + r0) / lrow0, i1 = __ldcg(g_gate + qt * 128 + r0 + 8) / lrow1;
            const uint32_t stg = sO + wg * 16384;
            mbar_wait(bar_oe + 8 * wg, (item & 1) ^ 1);
            {
                const int row = (warp & 3) * 16 + (lane >> 2);
#pragma unroll
                for (int i = 0; i < 4; i++) {
                    const int ch = i * 4 + (lane & 3);
                    const uint32_t a = stg + (ch >> 3) * 8192 + row * 128 + (((ch & 7) ^ (row & 7)) << 4);
                    const float* q = &o[i * 16];
                    asm volatile("st.shared.v4.b32 [%0], {%1, %2, %3, %4};" :: "r"(a), "r"(pack_bf16(q[0] * i0, q[1] * i0)), "r"(pack_bf16(q[4] * i0, q[5] * i0)),
                                 "r"(pack_bf16(q[8] * i0, q[9] * i0)), "r"(pack_bf16(q[12] * i0, q[13] * i0)) : "memory");
                    asm volatile("st.shared.v4.b32 [%0], {%1, %2, %3, %4};" :: "r"(a + 1024), "r"(pack_bf16(q[2] * i1, q[3] * i1)), "r"(pack_bf16(q[6] * i1, q[7] * i1)),
                                 "r"(pack_bf16(q[10] * i1, q[11] * i1)), "r"(pack_bf16(q[14] * i1, q[15] * i1)) : "memory");
                }
            }
            asm volatile("fence.proxy.async.shared::cta;" ::: "memory");
            asm volatile("bar.sync %0, 128;" :: "r"(3 + wg) : "memory");
            if ((threadIdx.x & 127) == 0) {
                asm volatile("st.shared.s32 [%0], %1;" :: "r"(oslot + wg * 4), "r"(t) : "memory");
                mbar_arrive(bar_of + 8 * wg);
            }
        }
        TS_END(1);
    }
}

__device__ __forceinline__ uint32_t cluster_ctarank() {
    uint32_t r; asm volatile("mov.u32 %0, %%cluster_ctarank;" : "=r"(r)); return r;
}
__device__ __forceinline__ uint32_t mapa_u32(uint32_t addr, uint32_t rank) {
    uint32_t r; asm volatile("mapa.shared::cluster.u32 %0, %1, %2;" : "=r"(r) : "r"(addr), "r"(rank)); return r;
}
__device__ __forceinline__ void cluster_sync_all() {
    asm volatile("barrier.cluster.arrive.release.aligned;\nbarrier.cluster.wait.acquire.aligned;" ::: "memory");
}
__device__ __forceinline__ void st_async_v4(uint32_t addr, uint32_t a, uint32_t b, uint32_t c, uint32_t d, uint32_t mbar) {
    asm volatile("st.async.weak.shared::cluster.mbarrier::complete_tx::bytes.v4.b32 [%0], {%1, %2, %3, %4}, [%5];"
                 :: "r"(addr), "r"(a), "r"(b), "r"(c), "r"(d), "r"(mbar) : "memory");
}
__device__ __forceinline__ void st_async_v2(uint32_t addr, uint32_t a, uint32_t b, uint32_t mbar) {
    asm volatile("st.async.weak.shared::cluster.mbarrier::complete_tx::bytes.v2.b32 [%0], {%1, %2}, [%3];"
                 :: "r"(addr), "r"(a), "r"(b), "r"(mbar) : "memory");
}
__device__ __forceinline__ void st_async_b32(uint32_t addr, uint32_t a, uint32_t mbar) {
    asm volatile("st.async.weak.shared::cluster.mbarrier::complete_tx::bytes.b32 [%0], %1, [%2];" :: "r"(addr), "r"(a), "r"(mbar) : "memory");
}
__device__ __forceinline__ void pace(int cycles) {
    if (cycles > 0) {
        uint32_t t0, t;
        asm volatile("mov.u32 %0, %%clock;" : "=r"(t0));
        do { asm volatile("mov.u32 %0, %%clock;" : "=r"(t)); } while (t - t0 < (uint32_t)cycles);
    }
}
__device__ __forceinline__ void mbar_wait_cl(uint32_t bar, uint32_t parity) {
    uint32_t done = 0;
    for (int it = 0; it < WAIT_LIMIT && !done; it++) {
        asm volatile(
            "{\n.reg .pred p;\n"
            "mbarrier.try_wait.parity.shared::cta.b64 p, [%1], %2;\n"
            "selp.u32 %0, 1, 0, p;\n}\n" : "=r"(done) : "r"(bar), "r"(parity) : "memory");
    }
}
__device__ __forceinline__ uint32_t mbar_test(uint32_t bar, uint32_t parity) {
    uint32_t done;
    asm volatile(
        "{\n.reg .pred p;\n"
        "mbarrier.test_wait.parity.shared::cta.b64 p, [%1], %2;\n"
        "selp.u32 %0, 1, 0, p;\n}\n" : "=r"(done) : "r"(bar), "r"(parity) : "memory");
    return done;
}
__device__ __forceinline__ void ldmatrix_x4(uint32_t& r0, uint32_t& r1, uint32_t& r2, uint32_t& r3, uint32_t addr) {
    asm volatile("ldmatrix.sync.aligned.m8n8.x4.shared.b16 {%0,%1,%2,%3}, [%4];"
                 : "=r"(r0), "=r"(r1), "=r"(r2), "=r"(r3) : "r"(addr));
}
__device__ __forceinline__ void cp_async16(uint32_t dst, const void* src) {
    asm volatile("cp.async.cg.shared.global [%0], [%1], 16;" :: "r"(dst), "l"(src) : "memory");
}
__device__ __forceinline__ float bf16r(float x) { return __uint_as_float(pack_bf16(0.f, x) & 0xffff0000u); }

#define DBG(i, w)
#define DBGD(i, w, dep)
#define DBG_EXTRA 0
__device__ __forceinline__ void tma_load_2d_mc(uint32_t dst, const CUtensorMap* map, uint32_t bar, int c0, int c1, uint16_t mask) {
    asm volatile(
        "cp.async.bulk.tensor.2d.shared::cluster.global.mbarrier::complete_tx::bytes.multicast::cluster [%0], [%1, {%3, %4}], [%2], %5;"
        :: "r"(dst), "l"((uint64_t)map), "r"(bar), "r"(c0), "r"(c1), "h"(mask) : "memory");
}
__device__ __forceinline__ void stmatrix_x4_trans(uint32_t addr, uint32_t r0, uint32_t r1, uint32_t r2, uint32_t r3) {
    asm volatile("stmatrix.sync.aligned.m8n8.x4.trans.shared.b16 [%0], {%1, %2, %3, %4};" :: "r"(addr), "r"(r0), "r"(r1), "r"(r2), "r"(r3) : "memory");
}
__device__ __forceinline__ void stmatrix_x2_trans(uint32_t addr, uint32_t r0, uint32_t r1) {
    asm volatile("stmatrix.sync.aligned.m8n8.x2.trans.shared.b16 [%0], {%1, %2};" :: "r"(addr), "r"(r0), "r"(r1) : "memory");
}
__device__ __forceinline__ uint4 lds128(uint32_t a) {
    uint4 v; asm volatile("ld.shared.v4.u32 {%0, %1, %2, %3}, [%4];" : "=r"(v.x), "=r"(v.y), "=r"(v.z), "=r"(v.w) : "r"(a) : "memory"); return v;
}
__device__ __forceinline__ void sts128(uint32_t a, uint32_t x, uint32_t y, uint32_t z, uint32_t w) {
    asm volatile("st.shared.v4.b32 [%0], {%1, %2, %3, %4};" :: "r"(a), "r"(x), "r"(y), "r"(z), "r"(w) : "memory");
}
__device__ __forceinline__ float2 lds64f(uint32_t a) {
    float2 v; asm volatile("ld.shared.v2.f32 {%0, %1}, [%2];" : "=f"(v.x), "=f"(v.y) : "r"(a) : "memory"); return v;
}
__device__ __forceinline__ void fence_async_smem() { asm volatile("fence.proxy.async.shared::cta;" ::: "memory"); }
#define ACC16(d) "+f"(d[0]), "+f"(d[1]), "+f"(d[2]), "+f"(d[3]), "+f"(d[4]), "+f"(d[5]), "+f"(d[6]), "+f"(d[7]), "+f"(d[8]), "+f"(d[9]), "+f"(d[10]), "+f"(d[11]), "+f"(d[12]), "+f"(d[13]), "+f"(d[14]), "+f"(d[15])
template <int ND>
__device__ __forceinline__ void wgmma_rs_n32(float (&d)[ND], const uint32_t (&a)[4], uint32_t db_lo, int scale_d) {
    asm volatile(
        "{\n.reg .pred p;\n.reg .b64 db;\nsetp.ne.b32 p, %21, 0;\nmov.b64 db, {%20, 0x40000040};\n"
        "wgmma.mma_async.sync.aligned.m64n32k16.f32.bf16.bf16 {%0,%1,%2,%3,%4,%5,%6,%7,%8,%9,%10,%11,%12,%13,%14,%15}, {%16,%17,%18,%19}, db, p, 1, 1, 0;\n}\n"
        : ACC16(d) : "r"(a[0]), "r"(a[1]), "r"(a[2]), "r"(a[3]), "r"(db_lo), "r"(scale_d));
}
template <int ND>
__device__ __forceinline__ void wgmma_ss_n32(float (&d)[ND], uint32_t da_lo, uint32_t db_lo, int scale_d) {
    asm volatile(
        "{\n.reg .pred p;\n.reg .b64 da, db;\nsetp.ne.b32 p, %18, 0;\nmov.b64 da, {%16, 0x40000040};\nmov.b64 db, {%17, 0x40000040};\n"
        "wgmma.mma_async.sync.aligned.m64n32k16.f32.bf16.bf16 {%0,%1,%2,%3,%4,%5,%6,%7,%8,%9,%10,%11,%12,%13,%14,%15}, da, db, p, 1, 1, 1, 0;\n}\n"
        : ACC16(d) : "r"(da_lo), "r"(db_lo), "r"(scale_d));
}
__device__ __forceinline__ void wgmma_ss_n8(float (&d)[4], uint32_t da_lo, uint32_t db_lo, int scale_d) {
    asm volatile(
        "{\n.reg .pred p;\n.reg .b64 da, db;\nsetp.ne.b32 p, %6, 0;\nmov.b64 da, {%4, 0x40000040};\nmov.b64 db, {%5, 0x00000010};\n"
        "wgmma.mma_async.sync.aligned.m64n8k16.f32.bf16.bf16 {%0,%1,%2,%3}, da, db, p, 1, 1, 1, 0;\n}\n"
        : "+f"(d[0]), "+f"(d[1]), "+f"(d[2]), "+f"(d[3]) : "r"(da_lo), "r"(db_lo), "r"(scale_d));
}

#define SCHED_FENCE()
__device__ __forceinline__ void wgmma_ss_n32_p(float (&d)[16], uint32_t da_lo, uint32_t db_lo, int scale_d) {
    asm volatile(
        "{\n.reg .pred p;\n.reg .b64 da, db;\nsetp.ne.b32 p, %18, 0;\nmov.b64 da, {%16, 0x40000040};\nmov.b64 db, {%17, 0x00000030};\n"
        "wgmma.mma_async.sync.aligned.m64n32k16.f32.bf16.bf16 {%0,%1,%2,%3,%4,%5,%6,%7,%8,%9,%10,%11,%12,%13,%14,%15}, da, db, p, 1, 1, 1, 0;\n}\n"
        : ACC16(d) : "r"(da_lo), "r"(db_lo), "r"(scale_d));
}

__device__ __forceinline__ void wgmma_ss_n32_kk(float (&d)[16], uint32_t da_lo, uint32_t db_lo, int scale_d) {
    asm volatile(
        "{\n.reg .pred p;\n.reg .b64 da, db;\nsetp.ne.b32 p, %18, 0;\nmov.b64 da, {%16, 0x40000040};\nmov.b64 db, {%17, 0x40000040};\n"
        "wgmma.mma_async.sync.aligned.m64n32k16.f32.bf16.bf16 {%0,%1,%2,%3,%4,%5,%6,%7,%8,%9,%10,%11,%12,%13,%14,%15}, da, db, p, 1, 1, 0, 0;\n}\n"
        : ACC16(d) : "r"(da_lo), "r"(db_lo), "r"(scale_d));
}

struct ChainParams {
    CUtensorMap mapW[3];
    CUtensorMap mapX;
    CUtensorMap mapC;
};
constexpr int CH_BLOCK = 384;
constexpr int CO_WO = 0;
constexpr int CO_XB = 65536;
constexpr int CO_MB = CO_XB + 65536;
constexpr int CO_OB = CO_MB + 8192;
constexpr int CH_TW = 6144, CH_TP = 3 * CH_TW;
constexpr int CO_T = CO_OB + 8192;
constexpr int CO_SC = CO_T + 2 * CH_TP;
constexpr int CO_LS = CO_SC + 2 * 1280;
constexpr int CO_LO = CO_LS + 8 * 1280;
constexpr int CO_P = CO_LO + 4 * 1280;
constexpr int CO_ST = 205824;
#define CH_NSM 3
constexpr int CO_WA = CO_ST + 4096;
constexpr int CO_BAR = CO_WA + CH_TP;
constexpr int CH_SMEM = CO_BAR + 256 + 1024 + DBG_EXTRA;
static_assert(CO_WA >= 3 * 65536 && CO_P + 3072 <= CO_ST && CH_NSM <= 3, "smem layout");
#define CH_POLL_DELAY 0
#define CH_PEARLY 0
#define CH_VPOS 2
#define CH_VST 0
#define CH_V3_DELAY 0
#define CH_LSPOS 1
#define CH_V1 0
#define CH_V2 24
#define CH_V3 32
#define CH_OG 2
#define CH_OW 8
#define CH_OF 12
#define CH_CHAINS 4

constexpr float CH_SC = 0.08838834764831845f * 1.4426950408889634f;
__device__ __forceinline__ uint32_t pin(uint32_t v) { return __shfl_sync(0xffffffff, v, threadIdx.x & 31); }

__global__ void __cluster_dims__(8, 1, 1) __launch_bounds__(CH_BLOCK, 1)
chain_kernel(const __grid_constant__ ChainParams P, const bf16* __restrict__ mem0, const bf16* __restrict__ Wo, const bf16* __restrict__ x,
             const bf16* __restrict__ gate_w) {
    extern __shared__ uint8_t smem_raw[];
    const uint32_t sb = (smem_u32(smem_raw) + 1023) & ~1023u;
    const int tid = threadIdx.x, warp = __shfl_sync(0xffffffff, tid >> 5, 0), lane = tid & 31;
    const int rank = (int)cluster_ctarank();
    const int C = blockIdx.x >> 3;
    const int h = C * 4 + (rank >> 1);
    const int qd = lane >> 2, qc = lane & 3;
    const int t4 = warp & 3, wg = warp >> 2;
    pdl_launch_dependents();
    TS_BEGIN(2);
    const uint32_t bar_mem = sb + CO_BAR, bar_o = bar_mem + 32, bar_sc = bar_o + 32, bar_x = bar_sc + 8, bar_l = bar_x + 16, bar_w = bar_l + 8;
    if (tid == 0) {
        for (int j = 0; j < 15; j++) mbar_init(bar_mem + 8 * j, bar_mem + 8 * j == bar_l ? 4 : 1);
        asm volatile("fence.mbarrier_init.release.cluster;" ::: "memory");
    }
    __syncthreads();
    if ((tid & 127) == 0) {
        mbar_expect_tx(bar_w + 8 * wg, 65536);
        for (int i = 0; i < 8; i++)
            tma_load_2d(sb + wg * 65536 + i * 8192, &P.mapW[wg], bar_w + 8 * wg, h * HD + (rank & 1) * 64, i * 64);
    }
    {
        for (int i = tid; i < 512; i += CH_BLOCK) asm volatile("prefetch.global.L2 [%0];" :: "l"(Wo + (size_t)(C * 512 + i) * DM + rank * 64));
        if (tid < 64) asm volatile("prefetch.global.L2 [%0];" :: "l"(x + (size_t)tid * DM + rank * 64));
    }
    if (tid < 256) {
        const int r = blockIdx.x * 32 + (tid >> 3);
        float sum = 0.f;
#pragma unroll
        for (int c = 0; c < 8; c++) {
            const int col = c * 64 + (tid & 7) * 8;
            const uint4 xv = __ldg(reinterpret_cast<const uint4*>(x + (size_t)r * DM + col));
            const uint4 gv = __ldg(reinterpret_cast<const uint4*>(gate_w + col));
            const bf16* xp = reinterpret_cast<const bf16*>(&xv);
            const bf16* gp = reinterpret_cast<const bf16*>(&gv);
#pragma unroll
            for (int e = 0; e < 8; e++) sum += bf16r(__bfloat162float(xp[e]) * __bfloat162float(gp[e]));
        }
        sum += __shfl_xor_sync(0xffffffff, sum, 1);
        sum += __shfl_xor_sync(0xffffffff, sum, 2);
        sum += __shfl_xor_sync(0xffffffff, sum, 4);
        if ((tid & 7) == 0) g_gate[r] = bf16r(1.f / (1.f + __expf(-bf16r(sum))));
        asm volatile("bar.sync 1, 256;" ::: "memory");
        if (tid == 32) signal_ctr_generic(CT_GATE);
    }
    auto chunk = [&](int i) { return (uint32_t)((rank - (i >> 1) - 4 * (i & 1)) & 7); };
    const uint32_t wfrag = (((lane >> 4) << 3) + (lane & 7)) * 128 + (((t4 * 2 + ((lane >> 3) & 1)) ^ (lane & 7)) << 4);
    const uint32_t aO = pin(sb + wg * CH_TW + wfrag);
    const uint32_t aM = pin(sb + (lane & 7) * 128 + (((lane >> 3) ^ (lane & 7)) << 4));
    const uint32_t aL = pin(sb + lane * 8);
    uint32_t w[32][4];
    float d[16];
    mbar_wait(bar_w + 8 * wg, 0);
#pragma unroll
    for (int e = CH_NSM; e < 32; e++) ldmatrix_x4_trans(w[e][0], w[e][1], w[e][2], w[e][3], sb + wg * 65536 + wfrag + chunk(e >> 2) * 8192 + (e & 3) * 2048);
#pragma unroll
    for (int e = 0; e < CH_NSM; e++) {
        const uint4 u = lds128(sb + wg * 65536 + chunk(0) * 8192 + e * 2048 + (tid & 127) * 16);
        sts128(sb + CO_WA + wg * CH_TW + e * 2048 + (tid & 127) * 16, u.x, u.y, u.z, u.w);
    }
    fence_async_smem();
    __syncthreads();
    if (tid == 0) {
        fence_async_smem();
        for (int b = 0; b < 2; b++) {
            mbar_expect_tx(bar_x + 8 * b, 32768);
            for (int i = 0; i < 8; i++) tma_load_2d(sb + CO_XB + b * 32768 + i * 4096, &P.mapX, bar_x + 8 * b, i * 64, b * SEGL);
        }
    }
#pragma unroll 2
    for (int i = tid; i < 512 * 4; i += CH_BLOCK) {
        const int r = i >> 2, cg = i & 3, ks = r >> 4, kp = r & 15;
        const int src = (rank - (ks >> 2)) & 7;
        const uint4* p = reinterpret_cast<const uint4*>(Wo + (size_t)(C * 512 + src * 64 + (ks & 3) * 16 + (kp >> 2) * 2 + (kp & 1) + (kp & 2) * 4) * DM + rank * 64 + cg * 16);
        const uint4 u0 = __ldg(p), u1 = __ldg(p + 1);
        const uint32_t a = sb + CO_WO + r * 128;
        sts128(a + (((cg * 2) ^ (r & 7)) << 4), __byte_perm(u0.x, u0.y, 0x5410), __byte_perm(u0.z, u0.w, 0x5410), __byte_perm(u1.x, u1.y, 0x5410), __byte_perm(u1.z, u1.w, 0x5410));
        sts128(a + (((cg * 2 + 1) ^ (r & 7)) << 4), __byte_perm(u0.x, u0.y, 0x7632), __byte_perm(u0.z, u0.w, 0x7632), __byte_perm(u1.x, u1.y, 0x7632), __byte_perm(u1.z, u1.w, 0x7632));
    }
#pragma unroll 1
    for (int i = tid; i < 512; i += CH_BLOCK) {
        const int n = i >> 6, c = i & 63;
        const uint4 u = __ldg(reinterpret_cast<const uint4*>(mem0 + n * DM + chunk(c >> 3) * 64 + (c & 7) * 8));
        sts128(sb + CO_MB + (c >> 3) * 1024 + n * 128 + (((c & 7) ^ n) << 4), u.x, u.y, u.z, u.w);
    }
    if (tid < 128) sts128(sb + CO_T + (tid >> 6) * CH_TP + 2 * CH_TW + 5120 + (tid & 63) * 16, 0u, 0u, 0u, 0u);
    else if (tid < 160) sts128(sb + CO_P + ((tid >> 3) & 3) * 768 + 640 + (tid & 7) * 16, 0u, 0u, 0u, 0u);
    fence_async_smem();
    TS_END(6);
    auto pass32 = [&](int b, int e0 = 0, int e1 = 32) {
        const uint32_t lo = desc_lo(sb + CO_XB + b * 32768, 16);
        wgmma_fence();
#pragma unroll
        for (int e = 0; e < 32; e++) if (e >= e0 && e < e1) {
            const uint32_t db = lo + chunk(e >> 2) * 256 + (e & 3) * 2;
            if (e < CH_NSM) wgmma_ss_n32(d, desc_lo(sb + CO_WA + wg * CH_TW + e * 2048, 16), db, e != 0);
            else wgmma_rs_n32(d, w[e], db, e != 0);
        }
        wgmma_commit();
    };
    auto store32 = [&](uint32_t a) {
        stmatrix_x4_trans(a, pack_bf16(d[0], d[1]), pack_bf16(d[2], d[3]), pack_bf16(d[4], d[5]), pack_bf16(d[6], d[7]));
        stmatrix_x4_trans(a + 2048, pack_bf16(d[8], d[9]), pack_bf16(d[10], d[11]), pack_bf16(d[12], d[13]), pack_bf16(d[14], d[15]));
    };
    auto mem_proj = [&](int s, bool wait, bool arrive = false) {
        const uint32_t par = s & 1;
        float acc[CH_CHAINS][4];
#pragma unroll
        for (int i = 0; i < CH_CHAINS; i++) acc[i][0] = acc[i][1] = acc[i][2] = acc[i][3] = 0.f;
        const uint32_t aM2 = aM ^ 64;
        uint32_t b[2][8];
        auto load = [&](int c) {
            if (wait && !(c & 1)) mbar_wait_cl(bar_mem + 4 * c, par ^ 1);
            if (c == 0) DBG(11, 0);
            if (c == 6) DBG(13, 0);
            ldmatrix_x4(b[c & 1][0], b[c & 1][1], b[c & 1][2], b[c & 1][3], aM + CO_MB + c * 1024);
            ldmatrix_x4(b[c & 1][4], b[c & 1][5], b[c & 1][6], b[c & 1][7], aM2 + CO_MB + c * 1024);
        };
        load(0);
#pragma unroll
        for (int c = 0; c < 8; c++) {
            if (c < 7) load(c + 1);
            SCHED_FENCE();
#pragma unroll
            for (int i = 0; i < 4; i++) {
                const int e = c * 4 + i;
                mma_16816(acc[i % CH_CHAINS], w[e][0], w[e][1], w[e][2], w[e][3], b[c & 1][i * 2], b[c & 1][i * 2 + 1]);
            }
        }
        if (CH_CHAINS == 4) {
#pragma unroll
            for (int i = 0; i < 4; i++) { acc[0][i] += acc[2 % CH_CHAINS][i]; acc[1][i] += acc[3 % CH_CHAINS][i]; }
        }
        const uint32_t r0 = pack_bf16(acc[0][0] + acc[1][0], acc[0][1] + acc[1][1]);
        const uint32_t r1 = pack_bf16(acc[0][2] + acc[1][2], acc[0][3] + acc[1][3]);
        DBGD(40 + warp, warp, r0 ^ r1);
        stmatrix_x2_trans(aO + par * CH_TP + CO_T + 4096, r0, r1);
    };
    auto load_wa = [&]() {
#pragma unroll
        for (int e = 0; e < CH_NSM; e++) ldmatrix_x4_trans(w[e][0], w[e][1], w[e][2], w[e][3], aO + CO_WA + e * 2048);
    };
    auto remote = [](uint32_t a, uint32_t r) { return mapa_u32(a, r); };
    mbar_wait(bar_x, 0);
    pass32(0);
    wgmma_wait<0>();
    store32(aO + CO_T);
    fence_async_smem();
    __syncthreads();
    cluster_sync_all();
    TS_BEGIN(5);

    if (wg < 2) {
        const uint32_t aQ = pin(sb + CO_T + qd * 128 + (((2 * qc) ^ qd) << 4));
        auto local_scores = [&](int s) {
            const uint32_t tb = sb + CO_T + (s & 1) * CH_TP;
            wgmma_fence();
#pragma unroll
            for (int ks = 0; ks < 4; ks++) wgmma_ss_n32_kk(d, desc_lo(tb + CH_TW, 16) + ks * 2, desc_lo(tb, 16) + ks * 2, ks != 0);
            wgmma_commit();
            wgmma_wait<0>();
            const uint32_t rb = remote(bar_l, rank ^ 1);
            if (t4 < 2) {
                const uint32_t off = 2 * aL - sb + t4 * 512;
#pragma unroll
                for (int j = 0; j < 4; j++) if (j >= 2 || t4 == 0) {
                    st_async_v4(remote(off + (s & 1) * 5120 + CO_LS + j * 1280, rank ^ 1), __float_as_uint(d[4 * j]), __float_as_uint(d[4 * j + 1]), __float_as_uint(d[4 * j + 2]), __float_as_uint(d[4 * j + 3]), rb);
                    sts128(off + CO_LO + j * 1280, __float_as_uint(d[4 * j]), __float_as_uint(d[4 * j + 1]), __float_as_uint(d[4 * j + 2]), __float_as_uint(d[4 * j + 3]));
                }
            } else if (t4 == 2) {
#pragma unroll
                for (int j = 0; j < 4; j++) {
                    st_async_v2(remote(aL + (s & 1) * 5120 + CO_LS + 1024 + j * 1280, rank ^ 1), __float_as_uint(d[4 * j]), __float_as_uint(d[4 * j + 1]), rb);
                    asm volatile("st.shared.v2.f32 [%0], {%1, %2};" :: "r"(aL + CO_LO + 1024 + j * 1280), "f"(d[4 * j]), "f"(d[4 * j + 1]) : "memory");
                }
            }
            __syncwarp();
            if (t4 < 3 && lane == 0) mbar_arrive(bar_l);
            DBG(6, 4);
        };
        auto local_pv = [&](int s, bool arrive) {
            wgmma_fence();
#pragma unroll
            for (int ks = 0; ks < 3; ks++)
                wgmma_ss_n32_p(d, desc_lo(sb + CO_T + (s & 1) * CH_TP + 2 * CH_TW + ks * 2048, 16), desc_lo(sb + CO_P + ks * 256, 128), ks != 0);
            wgmma_commit();
            wgmma_wait<0>();
            if (arrive) asm volatile("bar.arrive 9, 256;" ::: "memory");
            store32(aO + CO_ST);
            fence_async_smem();
            if (!arrive) asm volatile("bar.sync 5, 128;" ::: "memory");
        };
        auto store_ctx = [&](int s) {
            tma_store_2d(&P.mapC, sb + CO_ST, (rank & 1) * 64, h * SEQ + s * SEGL);
            asm volatile("cp.async.bulk.commit_group;" ::: "memory");
        };
        auto signal_ctx = [&](int m0, int m1) {
            asm volatile("fence.proxy.async;" ::: "memory");
            __threadfence();
            for (int m = m0; m < m1; m++) asm volatile("red.relaxed.gpu.global.add.u32 [%0], 1;" :: "l"(&g_ctr[CT_CB + m]) : "memory");
        };
#pragma unroll 1
        for (int s = 0; s < NSEG; s++) {
            const uint32_t par = s & 1;
            load_wa();
            mem_proj(s, s > 0);
            if (s == NSEG - 1) break;
            if (warp < 5) {
                const uint32_t qa_ = aQ + par * CH_TP, ka = qa_ + warp * 1024;
                asm volatile("bar.sync 1, 256;" ::: "memory");
                const uint4 qa = lds128(qa_ + 4096), k0 = lds128(ka + CH_TW), qb = lds128((qa_ ^ 16) + 4096), k1 = lds128((ka ^ 16) + CH_TW);
                DBGD(52 + warp, warp, qa.x ^ qb.x);
                float c[4] = {0.f, 0.f, 0.f, 0.f}, c2[4] = {0.f, 0.f, 0.f, 0.f};
                mma_16816(c, qa.x, 0u, qa.y, 0u, k0.x, k0.y);
                mma_16816(c2, qb.x, 0u, qb.y, 0u, k1.x, k1.y);
                mma_16816(c, qa.z, 0u, qa.w, 0u, k0.z, k0.w);
                mma_16816(c2, qb.z, 0u, qb.w, 0u, k1.z, k1.w);
                c[0] += c2[0]; c[1] += c2[1];
                DBGD(57 + warp, warp, __float_as_uint(c[0]));
                const uint32_t off = aL + CO_SC + warp * 256;
                st_async_v2(remote(off + 1280, rank ^ 1), __float_as_uint(c[0]), __float_as_uint(c[1]), remote(bar_sc, rank ^ 1));
                st_async_v2(off, __float_as_uint(c[0]), __float_as_uint(c[1]), bar_sc);
                asm volatile("bar.arrive 2, 288;" ::: "memory");
                DBG(3, 0);
            } else {
                asm volatile("bar.arrive 1, 256;" ::: "memory");
            }
            if (wg == 0) {
                if (tid == 96) {
                    mbar_expect_tx(bar_sc, 2 * 1280);
#pragma unroll
                    for (int j = 0; j < 4; j++) { mbar_expect_tx(bar_mem + 8 * j, 2048); if (j < CH_OG) mbar_expect_tx(bar_o + 8 * j, 8192 / CH_OG); }
                    if (s > 0) mbar_wait(bar_l, par ^ 1);
                    mbar_expect_tx(bar_l, 4096);
                }
                if (tid == 96 && s > 1) {
                    if (s == 34 || s == 50 || s == 58 || s == 62) {
                        asm volatile("cp.async.bulk.wait_group 0;" ::: "memory");
                        signal_ctx(s == 34 ? 0 : (2 * s - 68) >> 2, s >> 2);
                    }
                    store_ctx(s - 2);
                    asm volatile("cp.async.bulk.wait_group.read 0;" ::: "memory");
                }
                __syncwarp();
                mbar_wait(bar_x + 8 * (par ^ 1), ((s + 1) >> 1) & 1);
                asm volatile("bar.sync 5, 128;" ::: "memory");
                float c[4];
                const uint32_t alo = desc_lo(sb + CO_WO, 16), blo = desc_lo(sb + CO_OB, 128);
                uint32_t* wp = g_xbuf + (size_t)rank * 2048 + C * 256 + qc * 64 + t4 * 8 + qd;
                mbar_wait_cl(bar_o, par);
                DBG(16, 0);
                fence_async_smem();
                wgmma_fence();
#pragma unroll
                for (int i = 0; i < 32; i++) {
                    wgmma_ss_n8(c, alo + i * 128, blo + i * 16, i != 0);
                    if (CH_OG == 2 && i == CH_OW) mbar_wait_cl(bar_o + 8, par);
                    if (CH_OG == 2 && i == CH_OF) fence_async_smem();
                }
                wgmma_commit();
                wgmma_wait<0>();
                asm volatile("st.relaxed.gpu.global.u32 [%0], %1;" :: "l"(wp + (s & 3) * 16384), "r"(~pack_bf16(c[0], c[2])) : "memory");
                asm volatile("st.relaxed.gpu.global.u32 [%0], %1;" :: "l"(wp + (s & 3) * 16384 + 32), "r"(~pack_bf16(c[1], c[3])) : "memory");
                asm volatile("bar.arrive 4, 256;" ::: "memory");
                asm volatile("bar.arrive 6, 256;" ::: "memory");
                DBG(8, 0);
                if (s > 0) local_pv(s - 1, true); else asm volatile("bar.arrive 9, 256;" ::: "memory");
                DBG(28, 0);
                asm volatile("st.relaxed.gpu.global.u32 [%0], %1;" :: "l"(wp + ((s + 2) & 3) * 16384), "r"(0) : "memory");
                asm volatile("st.relaxed.gpu.global.u32 [%0], %1;" :: "l"(wp + ((s + 2) & 3) * 16384 + 32), "r"(0) : "memory");
                if (tid == 0 && s + 2 < NSEG) {
                    mbar_expect_tx(bar_x + 8 * par, 32768);
                    tma_load_2d_mc(sb + CO_XB + par * 32768 + rank * 4096, &P.mapX, bar_x + 8 * par, rank * 64, (s + 2) * SEGL, (uint16_t)0xff);
                }
                __syncwarp();
            } else {
                const uint32_t vaddr = pin(sb + CO_T + par * CH_TP + 2 * CH_TW + (lane & 15) * 128 + (((t4 * 2 + (lane >> 4)) ^ (lane & 7)) << 4));
                const uint32_t dsta = pin(sb + CO_OB + t4 * 256 + (qc >> 1) * 128 + qd * 16 + (qc & 1) * 8);
                fence_async_smem();
                uint32_t vb[3][4];
                auto load_v = [&]() {
                    asm volatile("bar.sync 3, 256;" ::: "memory");
#pragma unroll
                    for (int k = 0; k < 3; k++) ldmatrix_x4_trans(vb[k][0], vb[k][1], vb[k][2], vb[k][3], vaddr + k * 2048);
                };
                if (CH_VPOS == 0) load_v();
                mbar_wait_cl(bar_sc, par);
                DBG(4, 4);
                float v[10];
#pragma unroll
                for (int j = 0; j < 5; j++) {
                    const float2 a = lds64f(aL + CO_SC + j * 256), b = lds64f(aL + CO_SC + 1280 + j * 256);
                    v[2 * j] = a.x + b.x; v[2 * j + 1] = a.y + b.y;
                }
                if (CH_VPOS == 1) load_v();
                float mx = fmaxf(fmaxf(fmaxf(v[0], v[1]), fmaxf(v[2], v[3])), fmaxf(fmaxf(v[4], v[5]), fmaxf(v[6], v[7])));
                mx = fmaxf(mx, fmaxf(v[8], v[9]));
                mx = fmaxf(mx, __shfl_xor_sync(0xffffffff, mx, 1));
                mx = fmaxf(mx, __shfl_xor_sync(0xffffffff, mx, 2));
                if (CH_VPOS == 2) load_v();
                DBG(19, 4);
                mx *= CH_SC;
#pragma unroll
                for (int j = 0; j < 10; j++) v[j] = ex2f(fmaf(v[j], CH_SC, -mx));
                float c0[4] = {0.f, 0.f, 0.f, 0.f}, c1[4] = {0.f, 0.f, 0.f, 0.f}, cs[4] = {0.f, 0.f, 0.f, 0.f};
#pragma unroll
                for (int k = 0; k < 3; k++) {
                    const uint32_t p0 = pack_bf16(v[4 * k], v[4 * k + 1]), p1 = k < 2 ? pack_bf16(v[4 * k + 2], v[4 * k + 3]) : 0u;
                    mma_16816(cs, p0, 0u, p1, 0u, 0x3f803f80u, 0x3f803f80u);
                    mma_16816(c0, p0, 0u, p1, 0u, vb[k][0], vb[k][1]);
                    mma_16816(c1, p0, 0u, p1, 0u, vb[k][2], vb[k][3]);
                }
                float inv;
                asm volatile("rcp.approx.ftz.f32 %0, %1;" : "=f"(inv) : "f"(cs[0]));
                const uint32_t b0 = pack_bf16(c0[0] * inv, c0[1] * inv), b1 = pack_bf16(c1[0] * inv, c1[1] * inv);
                DBG(20, 4);
#pragma unroll
                for (int i = 0; i < 8; i++) {
                    const int dr = (rank + i) & 7;
                    st_async_v2(remote(dsta + i * 1024, dr), b0, b1, remote(bar_o + 8 * (i * CH_OG / 8), dr));
                    if (i == 0) asm volatile("bar.arrive 7, 256;" ::: "memory");
                }
                DBG(5, 4);
                mbar_wait(bar_x + 8 * (par ^ 1), ((s + 1) >> 1) & 1);
                asm volatile("bar.sync 4, 256;" ::: "memory");
                if (CH_LSPOS == 0) local_scores(s);
            }
            pass32(par ^ 1);
            DBG(21, 0);
            wgmma_wait<0>();
            store32(aO + (par ^ 1) * CH_TP + CO_T);
            if (wg == 0) fence_async_smem();
            DBG(22, 0);
            DBG(29, 4);
            if (CH_LSPOS == 1 && wg == 1) local_scores(s);
        }
        fence_async_smem();
        asm volatile("bar.sync 1, 256;" ::: "memory");
        if (warp < 5) asm volatile("bar.arrive 2, 288;" ::: "memory");
        if (wg == 0) {
            if (tid == 96) { mbar_wait(bar_l, 0); mbar_expect_tx(bar_l, 4096); store_ctx(NSEG - 3); asm volatile("cp.async.bulk.wait_group.read 0;" ::: "memory"); }
            __syncwarp();
            asm volatile("bar.sync 7, 256;" ::: "memory");
            local_pv(NSEG - 2, false);
            asm volatile("bar.arrive 6, 256;" ::: "memory");
            if (tid == 96) { store_ctx(NSEG - 2); asm volatile("cp.async.bulk.wait_group.read 0;" ::: "memory"); }
            __syncwarp();
            asm volatile("bar.sync 8, 256;" ::: "memory");
            local_pv(NSEG - 1, false);
            if (tid == 96) {
                store_ctx(NSEG - 1);
                asm volatile("cp.async.bulk.wait_group 0;" ::: "memory");
                signal_ctx(15, 16);
            }
            uint32_t* wp = g_xbuf + 16384 + (size_t)rank * 2048 + C * 256 + tid * 2;
            *reinterpret_cast<uint2*>(wp) = make_uint2(0u, 0u);
        } else {
            asm volatile("bar.sync 3, 256;" ::: "memory");
            asm volatile("bar.arrive 7, 256;" ::: "memory");
            local_scores(NSEG - 1);
        }
    } else {
        auto local_softmax = [&](int s) {
            float v[10];
            const float2 g = __ldcg(reinterpret_cast<const float2*>(g_gate + s * SEGL + t4 * 8 + 2 * qc));
            mbar_wait_cl(bar_l, s & 1);
            const uint32_t off = 2 * aL - sb + t4 * 1280;
            {
                const uint4 a0 = lds128(off + (s & 1) * 5120 + CO_LS), b0 = lds128(off + CO_LO), a1 = lds128(off + (s & 1) * 5120 + CO_LS + 512), b1 = lds128(off + CO_LO + 512);
                const float2 a2 = lds64f(aL + t4 * 1280 + (s & 1) * 5120 + CO_LS + 1024), b2 = lds64f(aL + t4 * 1280 + CO_LO + 1024);
                auto f = [](uint32_t a, uint32_t b) { return __uint_as_float(a) + __uint_as_float(b); };
                v[0] = f(a0.x, b0.x); v[1] = f(a0.y, b0.y); v[2] = f(a0.z, b0.z); v[3] = f(a0.w, b0.w);
                v[4] = f(a1.x, b1.x); v[5] = f(a1.y, b1.y); v[6] = f(a1.z, b1.z); v[7] = f(a1.w, b1.w);
                v[8] = a2.x + b2.x; v[9] = a2.y + b2.y;
            }
            const int lim = t4 * 8 + 2 * qc - qd;
#pragma unroll
            for (int n = 0; n < 4; n++) {
                if (8 * n > lim) v[2 * n] = -INFINITY;
                if (8 * n > lim + 1) v[2 * n + 1] = -INFINITY;
            }
            float m0 = fmaxf(fmaxf(fmaxf(v[0], v[2]), fmaxf(v[4], v[6])), v[8]), m1 = fmaxf(fmaxf(fmaxf(v[1], v[3]), fmaxf(v[5], v[7])), v[9]);
#pragma unroll
            for (int o = 4; o < 32; o *= 2) { m0 = fmaxf(m0, __shfl_xor_sync(0xffffffff, m0, o)); m1 = fmaxf(m1, __shfl_xor_sync(0xffffffff, m1, o)); }
            m0 *= CH_SC; m1 *= CH_SC;
#pragma unroll
            for (int n = 0; n < 5; n++) { v[2 * n] = ex2f(fmaf(v[2 * n], CH_SC, -m0)); v[2 * n + 1] = ex2f(fmaf(v[2 * n + 1], CH_SC, -m1)); }
            float s0 = ((v[0] + v[2]) + (v[4] + v[6])) + v[8], s1 = ((v[1] + v[3]) + (v[5] + v[7])) + v[9];
#pragma unroll
            for (int o = 4; o < 32; o *= 2) { s0 += __shfl_xor_sync(0xffffffff, s0, o); s1 += __shfl_xor_sync(0xffffffff, s1, o); }
            asm("rcp.approx.ftz.f32 %0, %0;" : "+f"(s0));
            asm("rcp.approx.ftz.f32 %0, %0;" : "+f"(s1));
            s0 *= 1.f - g.x; s1 *= 1.f - g.y;
            const uint32_t pa = 2 * aL - sb + CO_P + t4 * 768;
            stmatrix_x4_trans(pa, pack_bf16(v[0] * s0, v[1] * s1), pack_bf16(v[2] * s0, v[3] * s1), pack_bf16(v[4] * s0, v[5] * s1), pack_bf16(v[6] * s0, v[7] * s1));
            asm volatile("stmatrix.sync.aligned.m8n8.x1.trans.shared.b16 [%0], {%1};" :: "r"(pa + 512), "r"(pack_bf16(v[8] * s0, v[9] * s1)) : "memory");
            fence_async_smem();
            DBG(7, 8);
        };
        wait_ctr(CT_GATE, 64u);
#pragma unroll 1
        for (int s = 0; s < NSEG; s++) {
            const uint32_t par = s & 1;
            if (s > 0) local_softmax(s - 1);
            load_wa();
            if (s < NSEG - 1) mbar_wait(bar_x + 8 * (par ^ 1), ((s + 1) >> 1) & 1);
            asm volatile("bar.sync 2, 288;" ::: "memory");
            DBG(23, 8);
            mem_proj(s, false, true);
            asm volatile("bar.arrive 3, 256;" ::: "memory");
            if (s == NSEG - 1) break;
            DBG(24, 8);
            if (CH_V1 > 0) pass32(par ^ 1, 0, CH_V1);
            asm volatile("bar.sync 7, 256;" ::: "memory");
            pass32(par ^ 1, CH_V1, CH_V2);
            DBG(26, 8);
            asm volatile("bar.sync 6, 256;" ::: "memory");
            const uint2* xb = reinterpret_cast<const uint2*>(g_xbuf + (s & 3) * 16384 + (size_t)rank * 2048 + t4 * 64) + lane;
            uint2 p[8];
            auto poll_all = [&]() {
#pragma unroll
                for (int k = 0; k < 8; k++)
                    asm volatile("ld.relaxed.gpu.global.v2.u32 {%0, %1}, [%2];" : "=r"(p[k].x), "=r"(p[k].y) : "l"(xb + k * 128) : "memory");
                DBG(17, 8);
            };
            if (CH_V3 > CH_V2) { pace(CH_V3_DELAY); pass32(par ^ 1, CH_V2, CH_V3); }
            if (CH_VST == 0) {
                asm volatile("bar.sync 9, 256;" ::: "memory");
                wgmma_wait<0>();
                store32(aO + (par ^ 1) * CH_TP + CO_T);
                DBG(27, 8);
            }
            pace(CH_POLL_DELAY);
            auto lo = [](uint32_t u) { return __uint_as_float(~u << 16); };
            auto hi = [](uint32_t u) { return __uint_as_float(~u & 0xffff0000u); };
            poll_all();
            for (int it = 0; it < WAIT_LIMIT / 4; it++) {
                uint32_t bad = 0;
#pragma unroll
                for (int k = 0; k < 8; k++) bad |= (min(p[k].x, p[k].y) == 0u ? 1u : 0u) << k;
                if (__all_sync(0xffffffff, bad == 0u)) break;
                if (it == 0) DBG(12, 8);
                if (it == 1) DBG(14, 8);
                if (it == 2) DBG(15, 8);
#pragma unroll
                for (int k = 0; k < 8; k++)
                    if (bad & (1u << k))
                        asm volatile("ld.relaxed.gpu.global.v2.u32 {%0, %1}, [%2];" : "=r"(p[k].x), "=r"(p[k].y) : "l"(xb + k * 128) : "memory");
            }
            DBG(9, 8);
            const uint32_t m0 = pack_bf16(((lo(p[0].x) + lo(p[1].x)) + (lo(p[2].x) + lo(p[3].x))) + ((lo(p[4].x) + lo(p[5].x)) + (lo(p[6].x) + lo(p[7].x))),
                                          ((hi(p[0].x) + hi(p[1].x)) + (hi(p[2].x) + hi(p[3].x))) + ((hi(p[4].x) + hi(p[5].x)) + (hi(p[6].x) + hi(p[7].x))));
            const uint32_t m1 = pack_bf16(((lo(p[0].y) + lo(p[1].y)) + (lo(p[2].y) + lo(p[3].y))) + ((lo(p[4].y) + lo(p[5].y)) + (lo(p[6].y) + lo(p[7].y))),
                                          ((hi(p[0].y) + hi(p[1].y)) + (hi(p[2].y) + hi(p[3].y))) + ((hi(p[4].y) + hi(p[5].y)) + (hi(p[6].y) + hi(p[7].y))));
            const int row = t4 * 2 + (lane >> 4);
            const uint32_t dsta = sb + CO_MB + row * 128 + ((((lane & 15) >> 1) ^ row) << 4) + (lane & 1) * 8;
#pragma unroll
            for (int i = 0; i < 8; i++) {
                const int dr = (rank + (i & 1) * 4 + (i >> 1)) & 7;
                st_async_v2(remote(dsta + i * 1024, dr), m0, m1, remote(bar_mem + 8 * (i >> 1), dr));
            }
            DBG(10, 8);
            if (CH_VST == 1) {
                if (CH_V3 < 32) pass32(par ^ 1, CH_V3, 32);
                asm volatile("bar.sync 9, 256;" ::: "memory");
                wgmma_wait<0>();
                store32(aO + (par ^ 1) * CH_TP + CO_T);
                DBG(27, 8);
            }
        }
        asm volatile("bar.sync 6, 256;" ::: "memory");
        local_softmax(NSEG - 1);
        asm volatile("bar.arrive 8, 256;" ::: "memory");
    }
    __syncthreads();
    cluster_sync_all();
    TS_END(2);
}

struct Proj2Params {
    CUtensorMap mapA[2];
    CUtensorMap mapW[3];
    bf16* out[3];
};
#define P2T(i)
#define P2_NOMMA 0
#define P2_NOLOAD 0
constexpr int P2_STAGES = 6;
constexpr int P2_SMEM = 131072 + P2_STAGES * 16384 + 1024 + 1024;
constexpr int P2_ITEMS = 168 + 48;

__device__ __forceinline__ int p2_reps(int t) { return t >= 168 ? 1 : 2; }
__device__ __forceinline__ void p2_tile(int t, int w, int& z, int& mp, int& head) {
    if (t >= 168) { w += ((t - 168) & 1) * 2; t = 168 + ((t - 168) >> 1); }
    const int hq = t / 24, v = t % 24;
    mp = v & 7;
    if (v < 16) { head = hq * 4 + (v >> 3) * 2 + (w >> 1); z = 1 + (w & 1); }
    else { head = hq * 4 + w; z = 0; }
}
__device__ __forceinline__ void mbar_arrive_remote(uint32_t bar_cluster_addr) {
    asm volatile("mbarrier.arrive.release.cluster.shared::cluster.b64 _, [%0];" :: "r"(bar_cluster_addr) : "memory");
}
__device__ __forceinline__ void mbar_arrive_cl(uint32_t bar_cluster_addr) {
    asm volatile("mbarrier.arrive.shared::cluster.b64 _, [%0];" :: "r"(bar_cluster_addr) : "memory");
}
__device__ __forceinline__ void mbar_wait_acq_cluster(uint32_t bar, uint32_t parity) {
    asm volatile(
        "{\n"
        ".reg .pred p, q;\n"
        ".reg .u32 c;\n"
        "mov.u32 c, 0;\n"
        "WAIT_LOOP_C:\n"
        "mbarrier.try_wait.parity.acquire.cluster.shared::cta.b64 p, [%0], %1;\n"
        "@p bra WAIT_DONE_C;\n"
        "add.u32 c, c, 1;\n"
        "setp.lt.u32 q, c, 4000000;\n"
        "@q bra WAIT_LOOP_C;\n"
        "WAIT_DONE_C:\n"
        "}\n" :: "r"(bar), "r"(parity) : "memory");
}
__device__ __forceinline__ uint4 quad_transpose(uint32_t p0, uint32_t p1, uint32_t p2, uint32_t p3, int lane) {
    const bool o1 = lane & 1, o2 = lane & 2;
    uint32_t s0 = o1 ? p0 : p1, s1 = o1 ? p2 : p3;
    s0 = __shfl_xor_sync(0xffffffff, s0, 1); s1 = __shfl_xor_sync(0xffffffff, s1, 1);
    const uint32_t a_lo = o1 ? s0 : p0, a_hi = o1 ? p1 : s0, b_lo = o1 ? s1 : p2, b_hi = o1 ? p3 : s1;
    uint32_t t0 = o2 ? a_lo : b_lo, t1 = o2 ? a_hi : b_hi;
    t0 = __shfl_xor_sync(0xffffffff, t0, 2); t1 = __shfl_xor_sync(0xffffffff, t1, 2);
    return o2 ? make_uint4(t0, t1, b_lo, b_hi) : make_uint4(a_lo, a_hi, t0, t1);
}
#define P2_PACE 35
#define P2_PACE2 0
template <bool PERM, int PACE = 0>
__device__ __forceinline__ void store_frag_128(const float (&acc)[64], bf16* obase, int lane) {
#pragma unroll
    for (int rr = 0; rr < 2; rr++)
#pragma unroll
        for (int g = 0; g < 4; g++) {
            const float* a = &acc[g * 16 + rr * 2];
            const uint32_t p0 = pack_bf16(a[0], a[1]), p1 = pack_bf16(a[4], a[5]), p2 = pack_bf16(a[8], a[9]), p3 = pack_bf16(a[12], a[13]);
            *reinterpret_cast<uint4*>(obase + (size_t)(rr * 8) * HD + g * 32) = PERM ? make_uint4(p0, p1, p2, p3) : quad_transpose(p0, p1, p2, p3, lane);
            pace(PACE);
        }
}
__global__ void __cluster_dims__(2, 1, 1) __launch_bounds__(384, 1) proj2_kernel(const __grid_constant__ Proj2Params P) {
    extern __shared__ uint8_t smem_raw[];
    const uint32_t sbase = (smem_u32(smem_raw) + 1023) & ~1023u;
    const uint32_t sA = sbase, sB = sbase + 131072, sC = sB + P2_STAGES * 16384;
    const uint32_t bars = sC;
    const uint32_t a_full = bars, a_empty = bars + 64, b_full = bars + 128, b_empty = b_full + 8 * P2_STAGES;
    const uint32_t item_bar = b_empty + 8 * P2_STAGES, item_in = item_bar + 16, slot = item_in + 16;
    const uint32_t note_bar = slot + 16, note_free = note_bar + 64, note = note_free + 64;
    const int warp = threadIdx.x >> 5, lane = threadIdx.x & 31;
    const uint32_t rank = cluster_ctarank();
    TS_BEGIN(0);
    if (threadIdx.x == 0) {
        for (int i = 0; i < 8; i++) { mbar_init(a_full + 8 * i, 1); mbar_init(a_empty + 8 * i, 2); }
        for (int i = 0; i < P2_STAGES; i++) { mbar_init(b_full + 8 * i, 1); mbar_init(b_empty + 8 * i, 2); }
        mbar_init(item_bar, 1); mbar_init(item_bar + 8, 1); mbar_init(item_in, 2); mbar_init(item_in + 8, 2);
        for (int i = 0; i < 8; i++) { mbar_init(note_bar + 8 * i, 1); mbar_init(note_free + 8 * i, 1); }
        asm volatile("fence.mbarrier_init.release.cluster;" ::: "memory");
    }
    __syncthreads();
    cluster_sync_all();
    pdl_launch_dependents();
    if (warp == 9) {
        if (lane == 0) {
            for (int n = 0;; n++) {
                const int e = (n & 1) * 4 + ((n >> 1) & 3);
                mbar_wait(note_bar + 8 * e, (n >> 3) & 1);
                int m;
                asm volatile("ld.shared.s32 %0, [%1];" : "=r"(m) : "r"(note + e * 4) : "memory");
                mbar_arrive(note_free + 8 * e);
                if (m < 0) break;
                signal_ctr(m);
            }
        }
    } else if (warp == 10) {
        if (lane == 0) {
            auto publish = [&](int ic, int tq) {
                const int t = tq < P2_ITEMS ? tq : -1;
                asm volatile("st.shared.s32 [%0], %1;" :: "r"(slot + (ic & 3) * 4), "r"(t) : "memory");
                mbar_arrive(item_bar + 8 * (ic & 1));
                st_async_b32(mapa_u32(slot + (ic & 3) * 4, 1), (uint32_t)t, mapa_u32(item_bar + 8 * (ic & 1), 1));
            };
            const int npair = (int)(gridDim.x >> 1), pair = (int)(blockIdx.x >> 1);
            if (rank == 0) publish(0, pair);
            for (int ic = 0;; ic++) {
                if (rank == 1) mbar_expect_tx(item_bar + 8 * (ic & 1), 4);
                mbar_wait(item_bar + 8 * (ic & 1), (ic >> 1) & 1);
                int t;
                asm volatile("ld.shared.s32 %0, [%1];" : "=r"(t) : "r"(slot + (ic & 3) * 4) : "memory");
                if (t < 0) break;
                int z0, mp, h0;
                p2_tile(t, 0, z0, mp, h0);
                const int aidx = z0 >= 1 ? 1 : 0;
                const int m0 = (2 * mp + (int)rank) * 128;
                for (int k = 0; k < 8; k++) {
                    mbar_wait(a_empty + 8 * k, (ic & 1) ^ 1);
                    if (P2_NOLOAD) mbar_arrive(a_full + 8 * k); else {
                    mbar_expect_tx(a_full + 8 * k, 16384);
                    tma_load_2d(sA + k * 16384, &P.mapA[aidx], a_full + 8 * k, k * 64, m0); }
                }
                if (rank == 0) {
                    mbar_wait(item_in + 8 * (ic & 1), (ic >> 1) & 1);
                    publish(ic + 1, ic == 0 ? npair + pair : 2 * npair + (int)atomicAdd(&g_ctr[CT_PROJ], 1u));
                }
            }
        }
    } else if (warp == 8 || warp == 11) {
        if (lane == 0) {
            const int par2 = warp == 8 ? 0 : 1;
            int it = 0; uint32_t bph = 0;
            for (int ic = 0;; ic++) {
                mbar_wait(item_bar + 8 * (ic & 1), (ic >> 1) & 1);
                int t;
                asm volatile("ld.shared.s32 %0, [%1];" : "=r"(t) : "r"(slot + (ic & 3) * 4) : "memory");
                if (t < 0) break;
                const int nt = 2 * p2_reps(t);
                for (int w = 0; w < nt; w++) {
                    int z, mp, hd;
                    p2_tile(t, w, z, mp, hd);
                    for (int k = 0; k < 8; k++) {
                        const int s = it; const uint32_t phb = bph;
                        if (++it == P2_STAGES) { it = 0; bph ^= 1; }
                        if ((k & 1) != par2) continue;
                        mbar_wait(b_empty + 8 * s, phb ^ 1);
                        if (P2_NOLOAD) { mbar_arrive(b_full + 8 * s); continue; }
                        mbar_expect_tx(b_full + 8 * s, 16384);
                        tma_load_2d_mc(sB + s * 16384 + rank * 8192, &P.mapW[z], b_full + 8 * s, hd * 128 + (int)rank * 64, k * 64, (uint16_t)3);
                    }
                }
            }
        }
    } else {
        const int wg = warp >> 2;
        float acc[2][64];
        const uint32_t a_lo = desc_lo(sA, 16), b_lo0 = desc_lo(sB, 8192);
        const bool elected = (threadIdx.x & 127) == 0;
        int s = (wg * 8) % P2_STAGES;
        uint32_t ph = ((wg * 8) / P2_STAGES) & 1;
        int nnote = 0;
        if (wg == 1) asm volatile("bar.arrive 3, 256;" ::: "memory");
        for (int ic = 0;; ic++) {
            mbar_wait(item_bar + 8 * (ic & 1), (ic >> 1) & 1);
            int t;
            asm volatile("ld.shared.s32 %0, [%1];" : "=r"(t) : "r"(slot + (ic & 3) * 4) : "memory");
            P2T(7);
            if (wg == 0 && t < 0) {
                if (elected) {
                    const int e = nnote & 3;
                    mbar_wait(note_free + 8 * e, ((nnote >> 2) & 1) ^ 1);
                    asm volatile("st.shared.s32 [%0], %1;" :: "r"(note + e * 4), "r"(-1) : "memory");
                    mbar_arrive(note_bar + 8 * e);
                }
            }
            if (t < 0) break;
            const int reps = p2_reps(t);
#pragma unroll 1
            for (int rp = 0; rp < reps; rp++) {
            const bool first = rp == 0, last = rp == reps - 1;
            int z, mp, head;
            p2_tile(t, rp * 2 + wg, z, mp, head);
            asm volatile("bar.sync %0, 256;" :: "r"(3 + wg) : "memory");
            P2T(0);
            if (wg == 1 && last && elected) mbar_arrive_cl(mapa_u32(item_in + 8 * (ic & 1), 0));
            int sprev = 0;
#pragma unroll
            for (int k = 0; k < 8; k++) {
                if (k == 0) P2T(5);
                if (wg == 0 && first) mbar_wait(a_full + 8 * k, ic & 1);
                if (k == 0) P2T(6);
                mbar_wait(b_full + 8 * s, ph);
                if (k == 7) asm volatile("bar.arrive %0, 256;" :: "r"(4 - wg) : "memory");
                if (k == 0) P2T(1);
                if (k == 7) P2T(2);
                const uint32_t b_lo = b_lo0 + s * 1024;
                wgmma_fence();
#pragma unroll
                for (int kk = 0; kk < (P2_NOMMA ? 1 : 4); kk++) {
                    wgmma_ss_n128_lo<1>(acc[0], a_lo + k * 1024 + kk * 2, b_lo + kk * 128, (k | kk) != 0);
                    wgmma_ss_n128_lo<1>(acc[1], a_lo + k * 1024 + 512 + kk * 2, b_lo + kk * 128, (k | kk) != 0);
                }
                wgmma_commit();
                if (k > 0) {
                    wgmma_wait<1>();
                    if (elected) {
                        const uint32_t e = b_empty + 8 * sprev;
                        mbar_arrive_cl(mapa_u32(e, 0)); mbar_arrive_cl(mapa_u32(e, 1));
                        if (last) mbar_arrive(a_empty + 8 * (k - 1));
                    }
                }
                sprev = s;
                if (++s == P2_STAGES) { s = 0; ph ^= 1; }
            }
            wgmma_wait<0>();
            P2T(3);
            if (elected) {
                const uint32_t e = b_empty + 8 * sprev;
                mbar_arrive_cl(mapa_u32(e, 0)); mbar_arrive_cl(mapa_u32(e, 1));
                if (last) mbar_arrive(a_empty + 8 * 7);
            }
            s += 8 % P2_STAGES; ph ^= (8 / P2_STAGES) & 1;
            if (s >= P2_STAGES) { s -= P2_STAGES; ph ^= 1; }
            const int m0 = (2 * mp + (int)rank) * 128;
            bf16* obase = P.out[z] + ((size_t)head * SEQ + m0 + (warp & 3) * 16 + (lane >> 2)) * HD + (lane & 3) * 8;
            store_frag_128<true, P2_PACE>(acc[0], obase, lane); store_frag_128<true, P2_PACE>(acc[1], obase + (size_t)64 * HD, lane);
            P2T(4);
            {
                asm volatile("bar.sync %0, 128;" :: "r"(1 + wg) : "memory");
                if (elected) {
                    const int e = wg * 4 + (nnote & 3);
                    mbar_wait(note_free + 8 * e, ((nnote >> 2) & 1) ^ 1);
                    asm volatile("st.shared.s32 [%0], %1;" :: "r"(note + e * 4), "r"(CT_AP + (head >> 1)) : "memory");
                    mbar_arrive(note_bar + 8 * e);
                }
                nnote++;
            }
            }
        }
        TS_END(0);
    }
    __syncthreads();
    cluster_sync_all();
}

struct OutParams {
    CUtensorMap mapCtx[2];
    CUtensorMap mapWo[2];
};
__device__ uint4 g_part[32 * 5 * 8 * 2 * 256];

#define OT(i)
constexpr int O2_STAGES = 4;
constexpr int O2_SMEM = O2_STAGES * 49152 + 1024 + 256;
constexpr int O2_GRID = 132;

__global__ void __cluster_dims__(2, 1, 1) __launch_bounds__(352, 1)
out2_kernel(const __grid_constant__ OutParams P, bf16* __restrict__ out) {
    extern __shared__ uint8_t smem_raw[];
    const uint32_t sbase = (smem_u32(smem_raw) + 1023) & ~1023u;
    const uint32_t bar_full = sbase + O2_STAGES * 49152, bar_empty = bar_full + 8 * O2_STAGES, bar_item = bar_empty + 8 * O2_STAGES;
    const uint32_t slot = bar_item + 32, stop = slot + 16, fin = stop + 16;
    const int warp = threadIdx.x >> 5, lane = threadIdx.x & 31;
    const uint32_t rank = cluster_ctarank();
    const int cid = blockIdx.x >> 1;
    int pt, cj;
    if (cid < 28) { pt = cid < 14 ? cid : 27 - cid; cj = cid >= 14; }
    else if (cid < 34) { pt = 14 + (cid & 1); cj = (cid - 28) >> 1; }
    else { pt = 15 - ((cid - 34) & 15); cj = (pt >= 14 ? 3 : 2) + ((cid - 34) >> 4); }
    const int nc = pt >= 14 ? 5 : 4;
    const int mt = (pt >> 1) * 2 + (int)rank, m0 = mt * 128, n0 = (pt & 1) * 256;
    TS_BEGIN(4);
    OT(0);
    int t0 = 0;
    if (threadIdx.x == 256 && rank == 0) t0 = (int)atomicAdd(&g_ctr[CT_OT + pt], 1u);
    if (threadIdx.x == 0) {
        for (int i = 0; i < O2_STAGES; i++) { mbar_init(bar_full + 8 * i, 1); mbar_init(bar_empty + 8 * i, 4); mbar_init(bar_item + 8 * i, 1); }
        sts128(stop, 0u, 0u, 0u, 0u);
        asm volatile("fence.mbarrier_init.release.cluster;" ::: "memory");
    }
    __syncthreads();
    cluster_sync_all();
    if (warp >= 8) {
        if (lane == 0) {
            auto publish = [&](int ic, int t) {
                asm volatile("st.shared.s32 [%0], %1;" :: "r"(slot + (ic & 3) * 4), "r"(t) : "memory");
                mbar_arrive(bar_item + 8 * (ic & 3));
                st_async_b32(mapa_u32(slot + (ic & 3) * 4, 1), (uint32_t)t, mapa_u32(bar_item + 8 * (ic & 3), 1));
            };
            if (warp == 8 && rank == 0) publish(0, t0);
            int s = 0, ready = 0; uint32_t ph = 0;
            for (int ic = 0;; ic++) {
                if (warp == 8 && rank == 1) mbar_expect_tx(bar_item + 8 * (ic & 3), 4);
                mbar_wait(bar_item + 8 * (ic & 3), (ic >> 2) & 1);
                int t;
                asm volatile("ld.shared.s32 %0, [%1];" : "=r"(t) : "r"(slot + (ic & 3) * 4) : "memory");
                if (t >= 2 * NH) {
                    if (warp == 8) {
                        mbar_wait(bar_empty + 8 * s, ph ^ 1);
                        asm volatile("st.shared.s32 [%0], %1;" :: "r"(stop + s * 4), "r"(1) : "memory");
                        mbar_arrive(bar_full + 8 * s);
                    }
                    break;
                }
                const int b = t >> 5, head = t & 31;
                for (int dk = 0; dk < HD; dk += 64) {
                    mbar_wait(bar_empty + 8 * s, ph ^ 1);
                    const uint32_t sa = sbase + s * 49152;
                    if (warp == 8) {
                        const int f = b ? 4 : head >> 3;
                        const bool need = !((ready >> f) & 1);
                        if (need && dk == 0 && rank == 0) publish(ic + 1, (int)atomicAdd(&g_ctr[CT_OT + pt], 1u));
                        if (need) { wait_ctr(b ? CT_CB + mt : CT_CA + mt * 4 + f, b ? 64u : 16u); ready |= 1 << f; }
                        mbar_expect_tx(bar_full + 8 * s, 49152);
                        tma_load_2d(sa, &P.mapCtx[b], bar_full + 8 * s, dk, head * SEQ + m0);
                        if (!need && dk == 0 && rank == 0) publish(ic + 1, (int)atomicAdd(&g_ctr[CT_OT + pt], 1u));
                    } else {
                        const int j = (int)rank * 2 + (warp - 9);
                        tma_load_2d_mc(sa + 16384 + j * 8192, &P.mapWo[b], bar_full + 8 * s, n0 + j * 64, head * HD + dk, (uint16_t)3);
                    }
                    if (++s == O2_STAGES) { s = 0; ph ^= 1; }
                }
            }
        }
    } else {
        const int wg = warp >> 2;
        const bool elected = (threadIdx.x & 127) == 0;
        float acc[128];
#pragma unroll
        for (int i = 0; i < 128; i++) acc[i] = 0.f;
        int s = 0, sprev = 0; uint32_t ph = 0;
#pragma unroll 1
        for (int i = 0;; i++) {
            mbar_wait(bar_full + 8 * s, ph);
            int st;
            asm volatile("ld.shared.s32 %0, [%1];" : "=r"(st) : "r"(stop + s * 4) : "memory");
            if (st) break;
            if (i == 0) OT(1);
            const uint32_t sa = sbase + s * 49152 + wg * 8192, sb = sbase + s * 49152 + 16384;
            wgmma_fence();
#pragma unroll
            for (int kk = 0; kk < 4; kk++)
                wgmma_ss_n256_tb(acc, make_desc(sa + kk * 32, 16, 1024), make_desc(sb + kk * 2048, 8192, 1024), 1);
            wgmma_commit();
            if (i > 0) {
                wgmma_wait<1>();
                if (elected) { const uint32_t e = bar_empty + 8 * sprev; mbar_arrive_cl(mapa_u32(e, 0)); mbar_arrive_cl(mapa_u32(e, 1)); }
            }
            sprev = s;
            if (++s == O2_STAGES) { s = 0; ph ^= 1; }
        }
        wgmma_wait<0>();
        OT(3);
        const int u0 = cj * 8 / nc, u1 = (cj + 1) * 8 / nc;
        uint4* pb = g_part + (size_t)(mt * 2 + (pt & 1)) * (5 * 4096) + threadIdx.x;
        float own[2][16];
#pragma unroll
        for (int i = 0; i < 16; i++) own[1][i] = 0.f;
#pragma unroll
        for (int u = 0; u < 8; u++) {
            const float* a = &acc[u * 16];
            if (u == u0) {
#pragma unroll
                for (int i = 0; i < 16; i++) own[0][i] = a[i];
            } else if (u > u0 && u < u1) {
#pragma unroll
                for (int i = 0; i < 16; i++) own[1][i] = a[i];
            } else {
#pragma unroll
                for (int rr = 0; rr < 2; rr++)
                    asm volatile("st.relaxed.gpu.global.v4.u32 [%0], {%1, %2, %3, %4};" :: "l"(pb + cj * 4096 + u * 512 + rr * 256),
                                 "r"(~pack_bf16(a[rr * 2], a[rr * 2 + 1])), "r"(~pack_bf16(a[rr * 2 + 4], a[rr * 2 + 5])),
                                 "r"(~pack_bf16(a[rr * 2 + 8], a[rr * 2 + 9])), "r"(~pack_bf16(a[rr * 2 + 12], a[rr * 2 + 13])) : "memory");
            }
        }
        OT(4);
        uint4 v[16];
        uint32_t bad = 0;
#pragma unroll
        for (int k = 0; k < 16; k++) {
            v[k] = make_uint4(~0u, ~0u, ~0u, ~0u);
            if ((k >> 2) + 1 < nc && u0 + ((k >> 1) & 1) < u1) bad |= 1u << k;
        }
        const uint32_t mine = bad;
        auto addr = [&](int k) { int c = cj + 1 + (k >> 2); if (c >= nc) c -= nc; return pb + c * 4096 + u0 * 512 + (k & 3) * 256; };
        for (int it = 0; it < WAIT_LIMIT && bad; it++) {
#pragma unroll
            for (int k = 0; k < 16; k++)
                if (bad & (1u << k))
                    asm volatile("ld.relaxed.gpu.global.v4.u32 {%0, %1, %2, %3}, [%4];" : "=r"(v[k].x), "=r"(v[k].y), "=r"(v[k].z), "=r"(v[k].w) : "l"(addr(k)) : "memory");
            bad = 0;
#pragma unroll
            for (int k = 0; k < 16; k++) bad |= (min(min(v[k].x, v[k].y), min(v[k].z, v[k].w)) == 0u ? 1u : 0u) << k;
        }
        __syncwarp();
        OT(5);
        bf16* obase = out + (size_t)(m0 + wg * 64 + (warp & 3) * 16 + (lane >> 2)) * DM + n0 + u0 * 32 + (lane & 3) * 8;
#pragma unroll
        for (int k = 0; k < 4; k++) {
            const float* a = &own[k >> 1][(k & 1) * 2];
            auto sum = [&](float x0, float x1, uint32_t p0, uint32_t p1, uint32_t p2, uint32_t p3) {
                x0 += (__uint_as_float(~p0 << 16) + __uint_as_float(~p1 << 16)) + (__uint_as_float(~p2 << 16) + __uint_as_float(~p3 << 16));
                x1 += (__uint_as_float(~p0 & 0xffff0000u) + __uint_as_float(~p1 & 0xffff0000u)) + (__uint_as_float(~p2 & 0xffff0000u) + __uint_as_float(~p3 & 0xffff0000u));
                return pack_bf16(x0, x1);
            };
            const uint4 o = quad_transpose(sum(a[0], a[1], v[k].x, v[k + 4].x, v[k + 8].x, v[k + 12].x), sum(a[4], a[5], v[k].y, v[k + 4].y, v[k + 8].y, v[k + 12].y),
                                           sum(a[8], a[9], v[k].z, v[k + 4].z, v[k + 8].z, v[k + 12].z), sum(a[12], a[13], v[k].w, v[k + 4].w, v[k + 8].w, v[k + 12].w), lane);
            if (u0 + (k >> 1) < u1) *reinterpret_cast<uint4*>(obase + (k & 1) * 8 * DM + (k >> 1) * 32) = o;
        }
#pragma unroll
        for (int k = 0; k < 16; k++) if (mine & (1u << k)) *addr(k) = make_uint4(0u, 0u, 0u, 0u);
        OT(6);
        if (threadIdx.x == 0) {
            const unsigned int tk = atomicAdd(&g_ctr[CT_FIN], 1u);
            asm volatile("st.shared.u32 [%0], %1;" :: "r"(fin), "r"(tk) : "memory");
        }
        asm volatile("bar.sync 1, 256;" ::: "memory");
        unsigned int tk;
        asm volatile("ld.shared.u32 %0, [%1];" : "=r"(tk) : "r"(fin) : "memory");
        if (tk == gridDim.x - 1 && threadIdx.x < CT_N) g_ctr[threadIdx.x] = 0u;
    }
    __syncthreads();
    cluster_sync_all();
    TS_END(4);
}

typedef CUresult (*PFN_encodeTiled)(CUtensorMap*, CUtensorMapDataType, cuuint32_t, void*, const cuuint64_t*,
                                    const cuuint64_t*, const cuuint32_t*, const cuuint32_t*, CUtensorMapInterleave,
                                    CUtensorMapSwizzle, CUtensorMapL2promotion, CUtensorMapFloatOOBfill);
static PFN_encodeTiled g_encode = nullptr;

static void make_map(CUtensorMap* m, const void* ptr, uint64_t rows, uint64_t cols, uint32_t box_rows, bool sw64 = false) {
    cuuint64_t dims[2] = {cols, rows};
    cuuint64_t strides[1] = {cols * 2};
    cuuint32_t box[2] = {sw64 ? 32u : 64u, box_rows};
    cuuint32_t es[2] = {1, 1};
    g_encode(m, CU_TENSOR_MAP_DATA_TYPE_BFLOAT16, 2, const_cast<void*>(ptr), dims, strides, box, es,
             CU_TENSOR_MAP_INTERLEAVE_NONE, sw64 ? CU_TENSOR_MAP_SWIZZLE_64B : CU_TENSOR_MAP_SWIZZLE_128B, CU_TENSOR_MAP_L2_PROMOTION_L2_256B,
             CU_TENSOR_MAP_FLOAT_OOB_FILL_NONE);
}

template <typename... KArgs, typename... Args>
static void launch_pdl(void (*kernel)(KArgs...), int grid, int block, size_t smem, cudaStream_t st, bool pdl, Args... args) {
    cudaLaunchConfig_t cfg = {};
    cfg.gridDim = dim3(grid); cfg.blockDim = dim3(block); cfg.dynamicSmemBytes = smem; cfg.stream = st;
    cudaLaunchAttribute at[1];
    at[0].id = cudaLaunchAttributeProgrammaticStreamSerialization;
    at[0].val.programmaticStreamSerializationAllowed = 1;
    cfg.attrs = at; cfg.numAttrs = pdl ? 1 : 0;
    cudaLaunchKernelEx(&cfg, kernel, KArgs(args)...);
}

extern "C" void kernel_launch(void* const* d_in, const int* in_sizes, int n_in, void* d_out, int out_size) {
    const bf16* x = (const bf16*)d_in[0];
    const bf16* ckv = (const bf16*)d_in[1];
    const bf16* wq = (const bf16*)d_in[2];
    const bf16* wuk = (const bf16*)d_in[3];
    const bf16* wuv = (const bf16*)d_in[4];
    const bf16* wo = (const bf16*)d_in[5];
    const bf16* mem0 = (const bf16*)d_in[7];
    const bf16* Wq = (const bf16*)d_in[8];
    const bf16* Wk = (const bf16*)d_in[9];
    const bf16* Wv = (const bf16*)d_in[10];
    const bf16* Wo = (const bf16*)d_in[11];
    const bf16* gate_w = (const bf16*)d_in[13];
    bf16* out = (bf16*)d_out;

    static Proj2Params P2;
    static ChainParams CP;
    static AttnParams AP;
    static OutParams OP;
    static bool init = false;
    static const void* last_in[14];
    bool same = init;
    for (int i = 0; i < 14 && same; i++) same = last_in[i] == d_in[i];
    if (!init) {
        cudaDriverEntryPointQueryResult qr;
        cudaGetDriverEntryPoint("cuTensorMapEncodeTiled", (void**)&g_encode, cudaEnableDefault, &qr);
        cudaFuncSetAttribute(proj2_kernel, cudaFuncAttributeMaxDynamicSharedMemorySize, P2_SMEM);
        cudaFuncSetAttribute(attn_kernel, cudaFuncAttributeMaxDynamicSharedMemorySize, FA_SMEM);
        cudaFuncSetAttribute(chain_kernel, cudaFuncAttributeMaxDynamicSharedMemorySize, CH_SMEM);
        cudaFuncSetAttribute(out2_kernel, cudaFuncAttributeMaxDynamicSharedMemorySize, O2_SMEM);
        init = true;
    }
    if (!same) {
        for (int i = 0; i < 14; i++) last_in[i] = d_in[i];
        void *pQA, *pKA, *pVA, *pCA, *pCB;
        cudaGetSymbolAddress(&pQA, g_QA); cudaGetSymbolAddress(&pKA, g_KA); cudaGetSymbolAddress(&pVA, g_VA);
        cudaGetSymbolAddress(&pCA, g_ctxA); cudaGetSymbolAddress(&pCB, g_ctxB);
        make_map(&P2.mapA[0], x, SEQ, DM, 128);
        make_map(&P2.mapA[1], ckv, SEQ, DM, 128);
        const void* ws[3] = {wq, wuk, wuv};
        void* cs[3] = {pQA, pKA, pVA};
        for (int i = 0; i < 3; i++) { make_map(&P2.mapW[i], ws[i], DM, NQ, 64); P2.out[i] = (bf16*)cs[i]; }
        make_map(&CP.mapW[0], Wq, DM, NQ, 64); make_map(&CP.mapW[1], Wk, DM, NQ, 64); make_map(&CP.mapW[2], Wv, DM, NQ, 64);
        make_map(&CP.mapX, x, SEQ, DM, 32);
        make_map(&CP.mapC, pCB, NH * SEQ, HD, 32);
        make_map(&AP.mapQ, pQA, NH * SEQ, HD, 128);
        make_map(&AP.mapK, pKA, NH * SEQ, HD, 128);
        make_map(&AP.mapV, pVA, NH * SEQ, HD, 128);
        make_map(&AP.mapO, pCA, NH * SEQ, HD, 64);
        make_map(&OP.mapCtx[0], pCA, NH * SEQ, HD, 128);
        make_map(&OP.mapCtx[1], pCB, NH * SEQ, HD, 128);
        make_map(&OP.mapWo[0], wo, NQ, DM, 64);
        make_map(&OP.mapWo[1], Wo, NQ, DM, 64);
    }
    cudaStream_t s1 = cudaStreamPerThread;
    const bool pdl = true;
    launch_pdl(chain_kernel, 64, CH_BLOCK, CH_SMEM, s1, false, CP, mem0, Wo, x, gate_w);
    launch_pdl(proj2_kernel, 68, 384, P2_SMEM, s1, pdl, P2);
    launch_pdl(attn_kernel, FA_GRID, 384, FA_SMEM, s1, pdl, AP, 1000);
    launch_pdl(out2_kernel, O2_GRID, 352, O2_SMEM, s1, pdl, OP, out);
}
```

```cpp
#include <cuda_runtime.h>
#include <cuda_bf16.h>
#include <cuda.h>
#include <stdint.h>
#include <type_traits>

constexpr int SEQ = 2048;
constexpr int DM = 512;
constexpr int NH = 32;
constexpr int HD = 128;
constexpr int NQ = NH * HD;
constexpr int SEGL = 32;
constexpr int NMEM = 8;
constexpr int NSEG = SEQ / SEGL;

typedef __nv_bfloat16 bf16;

__device__ bf16 g_QA[SEQ * NQ];
__device__ bf16 g_KA[SEQ * NQ];
__device__ bf16 g_VA[SEQ * NQ];
__device__ bf16 g_ctxA[SEQ * NQ];
__device__ bf16 g_ctxB[SEQ * NQ];
constexpr int CT_PROJ = 0, CT_ATTN = 1, CT_FIN = 5;
constexpr int CT_AP = 64;
constexpr int CT_GATE = 96;
constexpr int CT_CA = 128;
constexpr int CT_CB = 192;
constexpr int CT_OT = 208;
constexpr int CT_N = 224;
__device__ __align__(16) unsigned int g_ctr[CT_N];
__device__ float g_gate[SEQ];
__device__ uint32_t g_xbuf[4 * 8 * 2048];

#define FA_GRID 68

#define TS_BEGIN(id)
#define TS_END(id)
#define WAIT_LIMIT 200000
__device__ __forceinline__ void pdl_launch_dependents() { asm volatile("griddepcontrol.launch_dependents;" ::: "memory"); }
__device__ __forceinline__ void wait_ctr(int idx, unsigned int n) {
    unsigned int v; int it = 0;
    do { asm volatile("ld.acquire.gpu.global.u32 %0, [%1];" : "=r"(v) : "l"(&g_ctr[idx]) : "memory"); } while (v < n && ++it < WAIT_LIMIT);
    asm volatile("fence.proxy.async.shared::cta;" ::: "memory");
}
__device__ __forceinline__ int take_ticket(int idx) {
    int v;
    asm volatile("atom.relaxed.gpu.global.inc.u32 %0, [%1], 0x7fffffff;" : "=r"(v) : "l"(&g_ctr[idx]) : "memory");
    return v;
}
__device__ __forceinline__ void signal_ctr(int idx) {
    asm volatile("fence.proxy.async;" ::: "memory");
    __threadfence();
    atomicAdd(&g_ctr[idx], 1u);
}
__device__ __forceinline__ void signal_ctr_generic(int idx) {
    asm volatile("red.release.gpu.global.add.u32 [%0], 1;" :: "l"(&g_ctr[idx]) : "memory");
}
__device__ __forceinline__ uint32_t smem_u32(const void* p) {
    return (uint32_t)__cvta_generic_to_shared(p);
}
__device__ __forceinline__ void mbar_init(uint32_t bar, uint32_t count) {
    asm volatile("mbarrier.init.shared::cta.b64 [%0], %1;" :: "r"(bar), "r"(count));
}
__device__ __forceinline__ void mbar_expect_tx(uint32_t bar, uint32_t bytes) {
    asm volatile("mbarrier.arrive.expect_tx.shared::cta.b64 _, [%0], %1;" :: "r"(bar), "r"(bytes) : "memory");
}
__device__ __forceinline__ void mbar_arrive(uint32_t bar) {
    asm volatile("mbarrier.arrive.shared::cta.b64 _, [%0];" :: "r"(bar) : "memory");
}
__device__ __forceinline__ void mbar_wait(uint32_t bar, uint32_t parity) {
    asm volatile(
        "{\n"
        ".reg .pred p, q;\n"
        ".reg .u32 c;\n"
        "mov.u32 c, 0;\n"
        "WAIT_LOOP:\n"
        "mbarrier.try_wait.parity.shared::cta.b64 p, [%0], %1;\n"
        "@p bra WAIT_DONE;\n"
        "add.u32 c, c, 1;\n"
        "setp.lt.u32 q, c, %2;\n"
        "@q bra WAIT_LOOP;\n"
        "WAIT_DONE:\n"
        "}\n" :: "r"(bar), "r"(parity), "n"(WAIT_LIMIT) : "memory");
}
__device__ __forceinline__ void tma_load_2d(uint32_t dst, const CUtensorMap* map, uint32_t bar, int c0, int c1) {
    asm volatile(
        "cp.async.bulk.tensor.2d.shared::cluster.global.mbarrier::complete_tx::bytes [%0], [%1, {%3, %4}], [%2];"
        :: "r"(dst), "l"((uint64_t)map), "r"(bar), "r"(c0), "r"(c1) : "memory");
}
__device__ __forceinline__ void wgmma_fence() { asm volatile("wgmma.fence.sync.aligned;" ::: "memory"); }
__device__ __forceinline__ void wgmma_commit() { asm volatile("wgmma.commit_group.sync.aligned;" ::: "memory"); }
template <int N> __device__ __forceinline__ void wgmma_wait() {
    asm volatile("wgmma.wait_group.sync.aligned %0;" :: "n"(N) : "memory");
}
__device__ __forceinline__ uint64_t make_desc(uint32_t addr, uint32_t lbo, uint32_t sbo) {
    uint64_t d = 0;
    d |= (uint64_t)((addr & 0x3FFFF) >> 4);
    d |= (uint64_t)((lbo >> 4) & 0x3FFF) << 16;
    d |= (uint64_t)((sbo >> 4) & 0x3FFF) << 32;
    d |= (uint64_t)1 << 62;
    return d;
}

#define ACC64(d) \
    "+f"(d[0]), "+f"(d[1]), "+f"(d[2]), "+f"(d[3]), "+f"(d[4]), "+f"(d[5]), "+f"(d[6]), "+f"(d[7]), \
    "+f"(d[8]), "+f"(d[9]), "+f"(d[10]), "+f"(d[11]), "+f"(d[12]), "+f"(d[13]), "+f"(d[14]), "+f"(d[15]), \
    "+f"(d[16]), "+f"(d[17]), "+f"(d[18]), "+f"(d[19]), "+f"(d[20]), "+f"(d[21]), "+f"(d[22]), "+f"(d[23]), \
    "+f"(d[24]), "+f"(d[25]), "+f"(d[26]), "+f"(d[27]), "+f"(d[28]), "+f"(d[29]), "+f"(d[30]), "+f"(d[31]), \
    "+f"(d[32]), "+f"(d[33]), "+f"(d[34]), "+f"(d[35]), "+f"(d[36]), "+f"(d[37]), "+f"(d[38]), "+f"(d[39]), \
    "+f"(d[40]), "+f"(d[41]), "+f"(d[42]), "+f"(d[43]), "+f"(d[44]), "+f"(d[45]), "+f"(d[46]), "+f"(d[47]), \
    "+f"(d[48]), "+f"(d[49]), "+f"(d[50]), "+f"(d[51]), "+f"(d[52]), "+f"(d[53]), "+f"(d[54]), "+f"(d[55]), \
    "+f"(d[56]), "+f"(d[57]), "+f"(d[58]), "+f"(d[59]), "+f"(d[60]), "+f"(d[61]), "+f"(d[62]), "+f"(d[63])
#define ACC64_STR \
    "{%0, %1, %2, %3, %4, %5, %6, %7, %8, %9, %10, %11, %12, %13, %14, %15, " \
    "%16, %17, %18, %19, %20, %21, %22, %23, %24, %25, %26, %27, %28, %29, %30, %31, " \
    "%32, %33, %34, %35, %36, %37, %38, %39, %40, %41, %42, %43, %44, %45, %46, %47, " \
    "%48, %49, %50, %51, %52, %53, %54, %55, %56, %57, %58, %59, %60, %61, %62, %63}"

template <int TB>
__device__ __forceinline__ void wgmma_ss_n128(float (&d)[64], uint64_t da, uint64_t db, int scale_d) {
    asm volatile(
        "{\n.reg .pred p;\nsetp.ne.b32 p, %66, 0;\n"
        "wgmma.mma_async.sync.aligned.m64n128k16.f32.bf16.bf16 " ACC64_STR ", %64, %65, p, 1, 1, 0, %67;\n}\n"
        : ACC64(d) : "l"(da), "l"(db), "r"(scale_d), "n"(TB));
}
__device__ __forceinline__ uint32_t desc_lo(uint32_t addr, uint32_t lbo) { return ((addr & 0x3FFFF) >> 4) | ((lbo >> 4) << 16); }
template <int TB>
__device__ __forceinline__ void wgmma_ss_n128_lo(float (&d)[64], uint32_t da_lo, uint32_t db_lo, int scale_d) {
    asm volatile(
        "{\n.reg .pred p;\n.reg .b64 da, db;\nsetp.ne.b32 p, %66, 0;\n"
        "mov.b64 da, {%64, 0x40000040};\nmov.b64 db, {%65, 0x40000040};\n"
        "wgmma.mma_async.sync.aligned.m64n128k16.f32.bf16.bf16 " ACC64_STR ", da, db, p, 1, 1, 0, %67;\n}\n"
        : ACC64(d) : "r"(da_lo), "r"(db_lo), "r"(scale_d), "n"(TB));
}
__device__ __forceinline__ void wgmma_rs_n128_tb(float (&d)[64], uint32_t a0, uint32_t a1, uint32_t a2, uint32_t a3,
                                                 uint64_t db, int scale_d) {
    asm volatile(
        "{\n.reg .pred p;\nsetp.ne.b32 p, %69, 0;\n"
        "wgmma.mma_async.sync.aligned.m64n128k16.f32.bf16.bf16 " ACC64_STR ", {%64, %65, %66, %67}, %68, p, 1, 1, 1;\n}\n"
        : ACC64(d) : "r"(a0), "r"(a1), "r"(a2), "r"(a3), "l"(db), "r"(scale_d));
}
__device__ __forceinline__ void wgmma_rs_n80(float (&d)[40], const uint32_t (&a)[4], uint32_t db_lo, int scale_d) {
    asm volatile(
        "{\n.reg .pred p;\n.reg .b64 db;\nsetp.ne.b32 p, %45, 0;\nmov.b64 db, {%44, 0x40000040};\n"
        "wgmma.mma_async.sync.aligned.m64n80k16.f32.bf16.bf16 "
        "{%0, %1, %2, %3, %4, %5, %6, %7, %8, %9, %10, %11, %12, %13, %14, %15, %16, %17, %18, %19, %20, %21, %22, %23, %24, %25, %26, %27, %28, %29, %30, %31, %32, %33, %34, %35, %36, %37, %38, %39}, "
        "{%40, %41, %42, %43}, db, p, 1, 1, 0;\n}\n"
        : "+f"(d[0]), "+f"(d[1]), "+f"(d[2]), "+f"(d[3]), "+f"(d[4]), "+f"(d[5]), "+f"(d[6]), "+f"(d[7]), "+f"(d[8]), "+f"(d[9]), "+f"(d[10]), "+f"(d[11]), "+f"(d[12]), "+f"(d[13]), "+f"(d[14]), "+f"(d[15]), "+f"(d[16]), "+f"(d[17]), "+f"(d[18]), "+f"(d[19]), "+f"(d[20]), "+f"(d[21]), "+f"(d[22]), "+f"(d[23]), "+f"(d[24]), "+f"(d[25]), "+f"(d[26]), "+f"(d[27]), "+f"(d[28]), "+f"(d[29]), "+f"(d[30]), "+f"(d[31]), "+f"(d[32]), "+f"(d[33]), "+f"(d[34]), "+f"(d[35]), "+f"(d[36]), "+f"(d[37]), "+f"(d[38]), "+f"(d[39])
        : "r"(a[0]), "r"(a[1]), "r"(a[2]), "r"(a[3]), "r"(db_lo), "r"(scale_d));
}
__device__ __forceinline__ void wgmma_ss_n256_tb(float (&d)[128], uint64_t da, uint64_t db, int scale_d) {
    asm volatile(
        "{\n.reg .pred p;\nsetp.ne.b32 p, %130, 0;\n"
        "wgmma.mma_async.sync.aligned.m64n256k16.f32.bf16.bf16 {%0, %1, %2, %3, %4, %5, %6, %7, %8, %9, %10, %11, %12, %13, %14, %15, %16, %17, %18, %19, %20, %21, %22, %23, %24, %25, %26, %27, %28, %29, %30, %31, %32, %33, %34, %35, %36, %37, %38, %39, %40, %41, %42, %43, %44, %45, %46, %47, %48, %49, %50, %51, %52, %53, %54, %55, %56, %57, %58, %59, %60, %61, %62, %63, %64, %65, %66, %67, %68, %69, %70, %71, %72, %73, %74, %75, %76, %77, %78, %79, %80, %81, %82, %83, %84, %85, %86, %87, %88, %89, %90, %91, %92, %93, %94, %95, %96, %97, %98, %99, %100, %101, %102, %103, %104, %105, %106, %107, %108, %109, %110, %111, %112, %113, %114, %115, %116, %117, %118, %119, %120, %121, %122, %123, %124, %125, %126, %127}, %128, %129, p, 1, 1, 0, 1;\n}\n"
        : "+f"(d[0]), "+f"(d[1]), "+f"(d[2]), "+f"(d[3]), "+f"(d[4]), "+f"(d[5]), "+f"(d[6]), "+f"(d[7]), "+f"(d[8]), "+f"(d[9]), "+f"(d[10]), "+f"(d[11]), "+f"(d[12]), "+f"(d[13]), "+f"(d[14]), "+f"(d[15]), "+f"(d[16]), "+f"(d[17]), "+f"(d[18]), "+f"(d[19]), "+f"(d[20]), "+f"(d[21]), "+f"(d[22]), "+f"(d[23]), "+f"(d[24]), "+f"(d[25]), "+f"(d[26]), "+f"(d[27]), "+f"(d[28]), "+f"(d[29]), "+f"(d[30]), "+f"(d[31]), "+f"(d[32]), "+f"(d[33]), "+f"(d[34]), "+f"(d[35]), "+f"(d[36]), "+f"(d[37]), "+f"(d[38]), "+f"(d[39]), "+f"(d[40]), "+f"(d[41]), "+f"(d[42]), "+f"(d[43]), "+f"(d[44]), "+f"(d[45]), "+f"(d[46]), "+f"(d[47]), "+f"(d[48]), "+f"(d[49]), "+f"(d[50]), "+f"(d[51]), "+f"(d[52]), "+f"(d[53]), "+f"(d[54]), "+f"(d[55]), "+f"(d[56]), "+f"(d[57]), "+f"(d[58]), "+f"(d[59]), "+f"(d[60]), "+f"(d[61]), "+f"(d[62]), "+f"(d[63]), "+f"(d[64]), "+f"(d[65]), "+f"(d[66]), "+f"(d[67]), "+f"(d[68]), "+f"(d[69]), "+f"(d[70]), "+f"(d[71]), "+f"(d[72]), "+f"(d[73]), "+f"(d[74]), "+f"(d[75]), "+f"(d[76]), "+f"(d[77]), "+f"(d[78]), "+f"(d[79]), "+f"(d[80]), "+f"(d[81]), "+f"(d[82]), "+f"(d[83]), "+f"(d[84]), "+f"(d[85]), "+f"(d[86]), "+f"(d[87]), "+f"(d[88]), "+f"(d[89]), "+f"(d[90]), "+f"(d[91]), "+f"(d[92]), "+f"(d[93]), "+f"(d[94]), "+f"(d[95]), "+f"(d[96]), "+f"(d[97]), "+f"(d[98]), "+f"(d[99]), "+f"(d[100]), "+f"(d[101]), "+f"(d[102]), "+f"(d[103]), "+f"(d[104]), "+f"(d[105]), "+f"(d[106]), "+f"(d[107]), "+f"(d[108]), "+f"(d[109]), "+f"(d[110]), "+f"(d[111]), "+f"(d[112]), "+f"(d[113]), "+f"(d[114]), "+f"(d[115]), "+f"(d[116]), "+f"(d[117]), "+f"(d[118]), "+f"(d[119]), "+f"(d[120]), "+f"(d[121]), "+f"(d[122]), "+f"(d[123]), "+f"(d[124]), "+f"(d[125]), "+f"(d[126]), "+f"(d[127])
        : "l"(da), "l"(db), "r"(scale_d));
}
__device__ __forceinline__ void stmatrix_x4(uint32_t addr, uint32_t r0, uint32_t r1, uint32_t r2, uint32_t r3) {
    asm volatile("stmatrix.sync.aligned.m8n8.x4.shared.b16 [%0], {%1, %2, %3, %4};" :: "r"(addr), "r"(r0), "r"(r1), "r"(r2), "r"(r3) : "memory");
}
__device__ __forceinline__ void tma_store_2d(const CUtensorMap* map, uint32_t src, int c0, int c1) {
    asm volatile("cp.async.bulk.tensor.2d.global.shared::cta.bulk_group [%0, {%2, %3}], [%1];"
                 :: "l"((uint64_t)map), "r"(src), "r"(c0), "r"(c1) : "memory");
}
__device__ __forceinline__ float ex2f(float x) { float y; asm("ex2.approx.ftz.f32 %0, %1;" : "=f"(y) : "f"(x)); return y; }
__device__ __forceinline__ uint32_t pack_bf16(float lo, float hi) {
    __nv_bfloat162 v = __floats2bfloat162_rn(lo, hi);
    return *reinterpret_cast<uint32_t*>(&v);
}
__device__ __forceinline__ void mma_16816(float (&c)[4], uint32_t a0, uint32_t a1, uint32_t a2, uint32_t a3,
                                          uint32_t b0, uint32_t b1) {
    asm volatile(
        "mma.sync.aligned.m16n8k16.row.col.f32.bf16.bf16.f32 {%0,%1,%2,%3}, {%4,%5,%6,%7}, {%8,%9}, {%0,%1,%2,%3};"
        : "+f"(c[0]), "+f"(c[1]), "+f"(c[2]), "+f"(c[3])
        : "r"(a0), "r"(a1), "r"(a2), "r"(a3), "r"(b0), "r"(b1));
}
__device__ __forceinline__ void ldmatrix_x4_trans(uint32_t& r0, uint32_t& r1, uint32_t& r2, uint32_t& r3, uint32_t addr) {
    asm volatile("ldmatrix.sync.aligned.m8n8.x4.trans.shared.b16 {%0,%1,%2,%3}, [%4];"
                 : "=r"(r0), "=r"(r1), "=r"(r2), "=r"(r3) : "r"(addr));
}

struct AttnParams {
    CUtensorMap mapQ, mapK, mapV;
    CUtensorMap mapO;
    bf16* out;
};
constexpr int FA_STAGES = 2;
constexpr int FA_SMEM = 32768 + FA_STAGES * 65536 + 32768 + 1024 + 256;
constexpr int FA_ITEMS = 16 * NH;
#define FA_RETIRE 100000
#define FA_LASTG 8
__device__ __forceinline__ int fa_qt(int t) {
    constexpr int T0 = (32 - FA_LASTG) * 16;
    return t < T0 ? 15 - ((t & 127) >> 3) : 15 - (t - T0) / FA_LASTG;
}
__device__ __forceinline__ int fa_head(int t) {
    constexpr int T0 = (32 - FA_LASTG) * 16;
    return t < T0 ? (t >> 7) * 8 + (t & 7) : (32 - FA_LASTG) + (t - T0) % FA_LASTG;
}

__global__ void __launch_bounds__(384, 1) attn_kernel(const __grid_constant__ AttnParams P, int retire_cta) {
    extern __shared__ uint8_t smem_raw[];
    uint32_t sbase = (smem_u32(smem_raw) + 1023) & ~1023u;
    const uint32_t sQ = sbase;
    const uint32_t sKV = sbase + 32768;
    const uint32_t sO = sKV + FA_STAGES * 65536;
    const uint32_t bars = sO + 32768;
    const uint32_t bar_q = bars, bar_qe = bars + 8, bar_kf = bars + 16, bar_vf = bar_kf + 8 * FA_STAGES, bar_e = bar_vf + 8 * FA_STAGES,
                   bar_ek = bar_e + 8 * FA_STAGES, slot = bar_ek + 8 * FA_STAGES, bar_of = slot + 16, bar_oe = bar_of + 16, oslot = bar_oe + 16;
    const int warp = threadIdx.x >> 5;
    TS_BEGIN(1);
    int tfirst = 0;
    if (threadIdx.x == 256) tfirst = (int)atomicAdd(&g_ctr[CT_ATTN], 1u);
    if (threadIdx.x == 0) {
        mbar_init(bar_q, 1); mbar_init(bar_qe, 8);
        for (int i = 0; i < FA_STAGES; i++) { mbar_init(bar_kf + 8 * i, 1); mbar_init(bar_vf + 8 * i, 1); mbar_init(bar_e + 8 * i, 8); mbar_init(bar_ek + 8 * i, 8); }
        for (int i = 0; i < 2; i++) { mbar_init(bar_of + 8 * i, 1); mbar_init(bar_oe + 8 * i, 1); }
        asm volatile("fence.mbarrier_init.release.cluster;" ::: "memory");
    }
    if (threadIdx.x == 256) asm volatile("st.shared.s32 [%0], %1;" :: "r"(slot + 8), "r"(tfirst) : "memory");
    __syncthreads();
    pdl_launch_dependents();
    if (warp >= 8) {
        asm volatile("setmaxnreg.dec.sync.aligned.u32 40;");
        if (threadIdx.x == 288 || threadIdx.x == 320) {
            const int wg = threadIdx.x == 288 ? 0 : 1;
            const uint32_t stg = sO + wg * 16384;
            for (int n = 0;; n++) {
                mbar_wait(bar_of + 8 * wg, n & 1);
                int t;
                asm volatile("ld.shared.s32 %0, [%1];" : "=r"(t) : "r"(oslot + wg * 4) : "memory");
                if (t < 0) break;
                const int qt = fa_qt(t), h = fa_head(t);
                tma_store_2d(&P.mapO, stg, 0, h * SEQ + qt * 128 + wg * 64);
                tma_store_2d(&P.mapO, stg + 8192, 64, h * SEQ + qt * 128 + wg * 64);
                asm volatile("cp.async.bulk.commit_group;" ::: "memory");
                asm volatile("cp.async.bulk.wait_group.read 0;" ::: "memory");
                mbar_arrive(bar_oe + 8 * wg);
                asm volatile("cp.async.bulk.wait_group 0;" ::: "memory");
                signal_ctr(CT_CA + qt * 4 + (h >> 3));
            }
        }
        if (threadIdx.x == 256) {
            int it = 0, hp_ready = 0;
            wait_ctr(CT_GATE, 64u);
            for (int item = 0;; item++) {
                int t = tfirst;
                if (item > 0) {
                    bool quit = false;
                    if ((int)blockIdx.x >= retire_cta) {
                        unsigned int v;
                        asm volatile("ld.relaxed.gpu.global.u32 %0, [%1];" : "=r"(v) : "l"(&g_ctr[CT_ATTN]) : "memory");
                        quit = v >= FA_RETIRE;
                    }
                    t = quit ? FA_ITEMS : (int)atomicAdd(&g_ctr[CT_ATTN], 1u);
                }
                const bool valid = t < FA_ITEMS;
                const int qt = fa_qt(t), h = fa_head(t);
                if (valid && !((hp_ready >> (h >> 1)) & 1)) { wait_ctr(CT_AP + (h >> 1), 96u); hp_ready |= 1 << (h >> 1); }
                mbar_wait(bar_qe, (item & 1) ^ 1);
                asm volatile("st.shared.s32 [%0], %1;" :: "r"(slot + (item & 1) * 4), "r"(valid ? t : -1) : "memory");
                if (!valid) { mbar_arrive(bar_q); break; }
                mbar_expect_tx(bar_q, 32768);
                tma_load_2d(sQ, &P.mapQ, bar_q, 0, h * SEQ + qt * 128);
                tma_load_2d(sQ + 16384, &P.mapQ, bar_q, 64, h * SEQ + qt * 128);
                for (int j = 0; j <= qt; j++, it++) {
                    const int s = it % FA_STAGES;
                    mbar_wait(bar_ek + 8 * s, ((it / FA_STAGES) & 1) ^ 1);
                    const uint32_t sk = sKV + s * 65536, sv = sk + 32768;
                    mbar_expect_tx(bar_kf + 8 * s, 32768);
                    tma_load_2d(sk, &P.mapK, bar_kf + 8 * s, 0, h * SEQ + j * 128);
                    tma_load_2d(sk + 16384, &P.mapK, bar_kf + 8 * s, 64, h * SEQ + j * 128);
                    mbar_wait(bar_e + 8 * s, ((it / FA_STAGES) & 1) ^ 1);
                    mbar_expect_tx(bar_vf + 8 * s, 32768);
                    tma_load_2d(sv, &P.mapV, bar_vf + 8 * s, 0, h * SEQ + j * 128);
                    tma_load_2d(sv + 16384, &P.mapV, bar_vf + 8 * s, 64, h * SEQ + j * 128);
                }
            }
        }
    } else {
        asm volatile("setmaxnreg.inc.sync.aligned.u32 232;");
        const int wg = warp >> 2;
        const int lane = threadIdx.x & 31;
        float o[64];
        float mrow0, mrow1, lrow0, lrow1;
        const float sc = 0.08838834764831845f * 1.4426950408889634f;
        const int r0 = wg * 64 + (warp & 3) * 16 + (lane >> 2);
        float sacc[64];
        uint32_t pa[32];
        float a0 = 1.f, a1 = 1.f;
        auto issue_qk = [&](int it) {
            const int s = it % FA_STAGES;
            const uint32_t sk = sKV + s * 65536;
            mbar_wait(bar_kf + 8 * s, (it / FA_STAGES) & 1);
            wgmma_fence();
#pragma unroll
            for (int kk = 0; kk < 8; kk++) {
                uint64_t da = make_desc(sQ + (kk >> 2) * 16384 + wg * 8192 + (kk & 3) * 32, 16, 1024);
                uint64_t db = make_desc(sk + (kk >> 2) * 16384 + (kk & 3) * 32, 16, 1024);
                wgmma_ss_n128<0>(sacc, da, db, kk != 0);
            }
            wgmma_commit();
        };
        auto issue_pv = [&](int it) {
            const int s = it % FA_STAGES;
            const uint32_t sv = sKV + s * 65536 + 32768;
            mbar_wait(bar_vf + 8 * s, (it / FA_STAGES) & 1);
            wgmma_fence();
#pragma unroll
            for (int kk = 0; kk < 8; kk++) {
                uint64_t db = make_desc(sv + kk * 2048, 16384, 1024);
                wgmma_rs_n128_tb(o, pa[kk * 4 + 0], pa[kk * 4 + 1], pa[kk * 4 + 2], pa[kk * 4 + 3], db, 1);
            }
            wgmma_commit();
        };
        auto softmax_stats = [&](bool diag) {
            if (diag) {
#pragma unroll
                for (int i = 0; i < 64; i++) {
                    int col = (i >> 2) * 8 + (lane & 3) * 2 + (i & 1);
                    int row = r0 + ((i & 2) ? 8 : 0);
                    if (col > row) sacc[i] = -INFINITY;
                }
            }
            float mx0 = -INFINITY, mx1 = -INFINITY;
#pragma unroll
            for (int i = 0; i < 16; i++) {
                mx0 = fmaxf(mx0, fmaxf(sacc[i * 4 + 0], sacc[i * 4 + 1]));
                mx1 = fmaxf(mx1, fmaxf(sacc[i * 4 + 2], sacc[i * 4 + 3]));
            }
            mx0 = fmaxf(mx0, __shfl_xor_sync(0xffffffff, mx0, 1));
            mx0 = fmaxf(mx0, __shfl_xor_sync(0xffffffff, mx0, 2));
            mx1 = fmaxf(mx1, __shfl_xor_sync(0xffffffff, mx1, 1));
            mx1 = fmaxf(mx1, __shfl_xor_sync(0xffffffff, mx1, 2));
            const float mn0 = fmaxf(mrow0, mx0), mn1 = fmaxf(mrow1, mx1);
            a0 = ex2f((mrow0 - mn0) * sc); a1 = ex2f((mrow1 - mn1) * sc);
            mrow0 = mn0; mrow1 = mn1;
            const float ms0 = mn0 * sc, ms1 = mn1 * sc;
            float sum0 = 0.f, sum1 = 0.f;
#pragma unroll
            for (int i = 0; i < 16; i++) {
                sacc[i * 4 + 0] = ex2f(fmaf(sacc[i * 4 + 0], sc, -ms0));
                sacc[i * 4 + 1] = ex2f(fmaf(sacc[i * 4 + 1], sc, -ms0));
                sacc[i * 4 + 2] = ex2f(fmaf(sacc[i * 4 + 2], sc, -ms1));
                sacc[i * 4 + 3] = ex2f(fmaf(sacc[i * 4 + 3], sc, -ms1));
                sum0 += sacc[i * 4 + 0] + sacc[i * 4 + 1];
                sum1 += sacc[i * 4 + 2] + sacc[i * 4 + 3];
            }
            lrow0 = lrow0 * a0 + sum0;
            lrow1 = lrow1 * a1 + sum1;
        };
        auto pack_p = [&]() {
#pragma unroll
            for (int i = 0; i < 16; i++) {
                pa[i * 2 + 0] = pack_bf16(sacc[i * 4 + 0], sacc[i * 4 + 1]);
                pa[i * 2 + 1] = pack_bf16(sacc[i * 4 + 2], sacc[i * 4 + 3]);
            }
        };
        int it = 0;
        if (wg == 1) asm volatile("bar.arrive 1, 256;" ::: "memory");
        for (int item = 0;; item++) {
            mbar_wait(bar_q, item & 1);
            int t;
            asm volatile("ld.shared.s32 %0, [%1];" : "=r"(t) : "r"(slot + (item & 1) * 4) : "memory");
            if (t < 0) {
                if ((threadIdx.x & 127) == 0) {
                    mbar_wait(bar_oe + 8 * wg, (item & 1) ^ 1);
                    asm volatile("st.shared.s32 [%0], %1;" :: "r"(oslot + wg * 4), "r"(-1) : "memory");
                    mbar_arrive(bar_of + 8 * wg);
                }
                break;
            }
            const int qt = fa_qt(t);
            const int nkv = qt + 1;
#pragma unroll
            for (int i = 0; i < 64; i++) o[i] = 0.f;
            mrow0 = -INFINITY; mrow1 = -INFINITY; lrow0 = 0.f; lrow1 = 0.f;
            asm volatile("bar.sync %0, 256;" :: "r"(1 + wg) : "memory");
            issue_qk(it);
            asm volatile("bar.arrive %0, 256;" :: "r"(2 - wg) : "memory");
            wgmma_wait<0>();
            if (lane == 0) { mbar_arrive(bar_ek + 8 * (it % FA_STAGES)); if (nkv == 1) mbar_arrive(bar_qe); }
            softmax_stats(nkv == 1);
            pack_p();
#pragma unroll 1
            for (int j = 1; j < nkv; j++) {
                asm volatile("bar.sync %0, 256;" :: "r"(1 + wg) : "memory");
                issue_qk(it + j);
                issue_pv(it + j - 1);
                asm volatile("bar.arrive %0, 256;" :: "r"(2 - wg) : "memory");
                wgmma_wait<1>();
                if (lane == 0) { mbar_arrive(bar_ek + 8 * ((it + j) % FA_STAGES)); if (j == nkv - 1) mbar_arrive(bar_qe); }
                softmax_stats(j == nkv - 1);
                wgmma_wait<0>();
                if (lane == 0) mbar_arrive(bar_e + 8 * ((it + j - 1) % FA_STAGES));
#pragma unroll
                for (int i = 0; i < 16; i++) {
                    o[i * 4 + 0] *= a0; o[i * 4 + 1] *= a0; o[i * 4 + 2] *= a1; o[i * 4 + 3] *= a1;
                }
                pack_p();
            }
            issue_pv(it + nkv - 1);
            wgmma_wait<0>();
            if (lane == 0) mbar_arrive(bar_e + 8 * ((it + nkv - 1) % FA_STAGES));
            it += nkv;
            lrow0 += __shfl_xor_sync(0xffffffff, lrow0, 1);
            lrow0 += __shfl_xor_sync(0xffffffff, lrow0, 2);
            lrow1 += __shfl_xor_sync(0xffffffff, lrow1, 1);
            lrow1 += __shfl_xor_sync(0xffffffff, lrow1, 2);
            const float i0 = __ldcg(g_gate + qt * 128 + r0) / lrow0, i1 = __ldcg(g_gate + qt * 128 + r0 + 8) / lrow1;
            const uint32_t stg = sO + wg * 16384;
            mbar_wait(bar_oe + 8 * wg, (item & 1) ^ 1);
            {
                const int row = (warp & 3) * 16 + (lane >> 2);
#pragma unroll
                for (int i = 0; i < 4; i++) {
                    const int ch = i * 4 + (lane & 3);
                    const uint32_t a = stg + (ch >> 3) * 8192 + row * 128 + (((ch & 7) ^ (row & 7)) << 4);
                    const float* q = &o[i * 16];
                    asm volatile("st.shared.v4.b32 [%0], {%1, %2, %3, %4};" :: "r"(a), "r"(pack_bf16(q[0] * i0, q[1] * i0)), "r"(pack_bf16(q[4] * i0, q[5] * i0)),
                                 "r"(pack_bf16(q[8] * i0, q[9] * i0)), "r"(pack_bf16(q[12] * i0, q[13] * i0)) : "memory");
                    asm volatile("st.shared.v4.b32 [%0], {%1, %2, %3, %4};" :: "r"(a + 1024), "r"(pack_bf16(q[2] * i1, q[3] * i1)), "r"(pack_bf16(q[6] * i1, q[7] * i1)),
                                 "r"(pack_bf16(q[10] * i1, q[11] * i1)), "r"(pack_bf16(q[14] * i1, q[15] * i1)) : "memory");
                }
            }
            if (fa_head(t) >= 24) {
                bf16* z = P.out + (size_t)(qt * 128 + wg * 64 + ((threadIdx.x & 127) >> 3)) * DM + (fa_head(t) - 24) * 64 + (lane & 7) * 8;
#pragma unroll
                for (int i = 0; i < 4; i++) *reinterpret_cast<uint4*>(z + i * 16 * DM) = make_uint4(0u, 0u, 0u, 0u);
            }
            asm volatile("fence.proxy.async.shared::cta;" ::: "memory");
            asm volatile("bar.sync %0, 128;" :: "r"(3 + wg) : "memory");
            if ((threadIdx.x & 127) == 0) {
                asm volatile("st.shared.s32 [%0], %1;" :: "r"(oslot + wg * 4), "r"(t) : "memory");
                mbar_arrive(bar_of + 8 * wg);
            }
        }
        TS_END(1);
    }
}

__device__ __forceinline__ uint32_t cluster_ctarank() {
    uint32_t r; asm volatile("mov.u32 %0, %%cluster_ctarank;" : "=r"(r)); return r;
}
__device__ __forceinline__ uint32_t mapa_u32(uint32_t addr, uint32_t rank) {
    uint32_t r; asm volatile("mapa.shared::cluster.u32 %0, %1, %2;" : "=r"(r) : "r"(addr), "r"(rank)); return r;
}
__device__ __forceinline__ void cluster_sync_all() {
    asm volatile("barrier.cluster.arrive.release.aligned;\nbarrier.cluster.wait.acquire.aligned;" ::: "memory");
}
__device__ __forceinline__ void st_async_v4(uint32_t addr, uint32_t a, uint32_t b, uint32_t c, uint32_t d, uint32_t mbar) {
    asm volatile("st.async.weak.shared::cluster.mbarrier::complete_tx::bytes.v4.b32 [%0], {%1, %2, %3, %4}, [%5];"
                 :: "r"(addr), "r"(a), "r"(b), "r"(c), "r"(d), "r"(mbar) : "memory");
}
__device__ __forceinline__ void st_async_v2(uint32_t addr, uint32_t a, uint32_t b, uint32_t mbar) {
    asm volatile("st.async.weak.shared::cluster.mbarrier::complete_tx::bytes.v2.b32 [%0], {%1, %2}, [%3];"
                 :: "r"(addr), "r"(a), "r"(b), "r"(mbar) : "memory");
}
__device__ __forceinline__ void st_async_b32(uint32_t addr, uint32_t a, uint32_t mbar) {
    asm volatile("st.async.weak.shared::cluster.mbarrier::complete_tx::bytes.b32 [%0], %1, [%2];" :: "r"(addr), "r"(a), "r"(mbar) : "memory");
}
__device__ __forceinline__ void pace(int cycles) {
    if (cycles > 0) {
        uint32_t t0, t;
        asm volatile("mov.u32 %0, %%clock;" : "=r"(t0));
        do { asm volatile("mov.u32 %0, %%clock;" : "=r"(t)); } while (t - t0 < (uint32_t)cycles);
    }
}
__device__ __forceinline__ void mbar_wait_cl(uint32_t bar, uint32_t parity) {
    uint32_t done = 0;
    for (int it = 0; it < WAIT_LIMIT && !done; it++) {
        asm volatile(
            "{\n.reg .pred p;\n"
            "mbarrier.try_wait.parity.shared::cta.b64 p, [%1], %2;\n"
            "selp.u32 %0, 1, 0, p;\n}\n" : "=r"(done) : "r"(bar), "r"(parity) : "memory");
    }
}
__device__ __forceinline__ uint32_t mbar_test(uint32_t bar, uint32_t parity) {
    uint32_t done;
    asm volatile(
        "{\n.reg .pred p;\n"
        "mbarrier.test_wait.parity.shared::cta.b64 p, [%1], %2;\n"
        "selp.u32 %0, 1, 0, p;\n}\n" : "=r"(done) : "r"(bar), "r"(parity) : "memory");
    return done;
}
__device__ __forceinline__ void ldmatrix_x4(uint32_t& r0, uint32_t& r1, uint32_t& r2, uint32_t& r3, uint32_t addr) {
    asm volatile("ldmatrix.sync.aligned.m8n8.x4.shared.b16 {%0,%1,%2,%3}, [%4];"
                 : "=r"(r0), "=r"(r1), "=r"(r2), "=r"(r3) : "r"(addr));
}
__device__ __forceinline__ void cp_async16(uint32_t dst, const void* src) {
    asm volatile("cp.async.cg.shared.global [%0], [%1], 16;" :: "r"(dst), "l"(src) : "memory");
}
__device__ __forceinline__ float bf16r(float x) { return __uint_as_float(pack_bf16(0.f, x) & 0xffff0000u); }

#define DBG(i, w)
#define DBGD(i, w, dep)
#define DBG_EXTRA 0
__device__ __forceinline__ void tma_load_2d_mc(uint32_t dst, const CUtensorMap* map, uint32_t bar, int c0, int c1, uint16_t mask) {
    asm volatile(
        "cp.async.bulk.tensor.2d.shared::cluster.global.mbarrier::complete_tx::bytes.multicast::cluster [%0], [%1, {%3, %4}], [%2], %5;"
        :: "r"(dst), "l"((uint64_t)map), "r"(bar), "r"(c0), "r"(c1), "h"(mask) : "memory");
}
__device__ __forceinline__ void stmatrix_x4_trans(uint32_t addr, uint32_t r0, uint32_t r1, uint32_t r2, uint32_t r3) {
    asm volatile("stmatrix.sync.aligned.m8n8.x4.trans.shared.b16 [%0], {%1, %2, %3, %4};" :: "r"(addr), "r"(r0), "r"(r1), "r"(r2), "r"(r3) : "memory");
}
__device__ __forceinline__ void stmatrix_x2_trans(uint32_t addr, uint32_t r0, uint32_t r1) {
    asm volatile("stmatrix.sync.aligned.m8n8.x2.trans.shared.b16 [%0], {%1, %2};" :: "r"(addr), "r"(r0), "r"(r1) : "memory");
}
__device__ __forceinline__ uint4 lds128(uint32_t a) {
    uint4 v; asm volatile("ld.shared.v4.u32 {%0, %1, %2, %3}, [%4];" : "=r"(v.x), "=r"(v.y), "=r"(v.z), "=r"(v.w) : "r"(a) : "memory"); return v;
}
__device__ __forceinline__ void sts128(uint32_t a, uint32_t x, uint32_t y, uint32_t z, uint32_t w) {
    asm volatile("st.shared.v4.b32 [%0], {%1, %2, %3, %4};" :: "r"(a), "r"(x), "r"(y), "r"(z), "r"(w) : "memory");
}
__device__ __forceinline__ float2 lds64f(uint32_t a) {
    float2 v; asm volatile("ld.shared.v2.f32 {%0, %1}, [%2];" : "=f"(v.x), "=f"(v.y) : "r"(a) : "memory"); return v;
}
__device__ __forceinline__ void fence_async_smem() { asm volatile("fence.proxy.async.shared::cta;" ::: "memory"); }
#define ACC16(d) "+f"(d[0]), "+f"(d[1]), "+f"(d[2]), "+f"(d[3]), "+f"(d[4]), "+f"(d[5]), "+f"(d[6]), "+f"(d[7]), "+f"(d[8]), "+f"(d[9]), "+f"(d[10]), "+f"(d[11]), "+f"(d[12]), "+f"(d[13]), "+f"(d[14]), "+f"(d[15])
template <int ND>
__device__ __forceinline__ void wgmma_rs_n32(float (&d)[ND], const uint32_t (&a)[4], uint32_t db_lo, int scale_d) {
    asm volatile(
        "{\n.reg .pred p;\n.reg .b64 db;\nsetp.ne.b32 p, %21, 0;\nmov.b64 db, {%20, 0x40000040};\n"
        "wgmma.mma_async.sync.aligned.m64n32k16.f32.bf16.bf16 {%0,%1,%2,%3,%4,%5,%6,%7,%8,%9,%10,%11,%12,%13,%14,%15}, {%16,%17,%18,%19}, db, p, 1, 1, 0;\n}\n"
        : ACC16(d) : "r"(a[0]), "r"(a[1]), "r"(a[2]), "r"(a[3]), "r"(db_lo), "r"(scale_d));
}
template <int ND>
__device__ __forceinline__ void wgmma_ss_n32(float (&d)[ND], uint32_t da_lo, uint32_t db_lo, int scale_d) {
    asm volatile(
        "{\n.reg .pred p;\n.reg .b64 da, db;\nsetp.ne.b32 p, %18, 0;\nmov.b64 da, {%16, 0x40000040};\nmov.b64 db, {%17, 0x40000040};\n"
        "wgmma.mma_async.sync.aligned.m64n32k16.f32.bf16.bf16 {%0,%1,%2,%3,%4,%5,%6,%7,%8,%9,%10,%11,%12,%13,%14,%15}, da, db, p, 1, 1, 1, 0;\n}\n"
        : ACC16(d) : "r"(da_lo), "r"(db_lo), "r"(scale_d));
}
__device__ __forceinline__ void wgmma_ss_n8(float (&d)[4], uint32_t da_lo, uint32_t db_lo, int scale_d) {
    asm volatile(
        "{\n.reg .pred p;\n.reg .b64 da, db;\nsetp.ne.b32 p, %6, 0;\nmov.b64 da, {%4, 0x40000040};\nmov.b64 db, {%5, 0x00000010};\n"
        "wgmma.mma_async.sync.aligned.m64n8k16.f32.bf16.bf16 {%0,%1,%2,%3}, da, db, p, 1, 1, 1, 0;\n}\n"
        : "+f"(d[0]), "+f"(d[1]), "+f"(d[2]), "+f"(d[3]) : "r"(da_lo), "r"(db_lo), "r"(scale_d));
}

#define SCHED_FENCE()
__device__ __forceinline__ void wgmma_ss_n32_p(float (&d)[16], uint32_t da_lo, uint32_t db_lo, int scale_d) {
    asm volatile(
        "{\n.reg .pred p;\n.reg .b64 da, db;\nsetp.ne.b32 p, %18, 0;\nmov.b64 da, {%16, 0x40000040};\nmov.b64 db, {%17, 0x00000030};\n"
        "wgmma.mma_async.sync.aligned.m64n32k16.f32.bf16.bf16 {%0,%1,%2,%3,%4,%5,%6,%7,%8,%9,%10,%11,%12,%13,%14,%15}, da, db, p, 1, 1, 1, 0;\n}\n"
        : ACC16(d) : "r"(da_lo), "r"(db_lo), "r"(scale_d));
}

__device__ __forceinline__ void wgmma_ss_n32_kk(float (&d)[16], uint32_t da_lo, uint32_t db_lo, int scale_d) {
    asm volatile(
        "{\n.reg .pred p;\n.reg .b64 da, db;\nsetp.ne.b32 p, %18, 0;\nmov.b64 da, {%16, 0x40000040};\nmov.b64 db, {%17, 0x40000040};\n"
        "wgmma.mma_async.sync.aligned.m64n32k16.f32.bf16.bf16 {%0,%1,%2,%3,%4,%5,%6,%7,%8,%9,%10,%11,%12,%13,%14,%15}, da, db, p, 1, 1, 0, 0;\n}\n"
        : ACC16(d) : "r"(da_lo), "r"(db_lo), "r"(scale_d));
}

struct ChainParams {
    CUtensorMap mapW[3];
    CUtensorMap mapX;
    CUtensorMap mapC;
};
constexpr int CH_BLOCK = 384;
constexpr int CO_WO = 0;
constexpr int CO_XB = 65536;
constexpr int CO_MB = CO_XB + 65536;
constexpr int CO_OB = CO_MB + 8192;
constexpr int CH_TW = 6144, CH_TP = 3 * CH_TW;
constexpr int CO_T = CO_OB + 8192;
constexpr int CO_SC = CO_T + 2 * CH_TP;
constexpr int CO_LS = CO_SC + 2 * 1280;
constexpr int CO_LO = CO_LS + 8 * 1280;
constexpr int CO_P = CO_LO + 4 * 1280;
constexpr int CO_ST = 205824;
#define CH_NSM 3
constexpr int CO_WA = CO_ST + 4096;
constexpr int CO_BAR = CO_WA + CH_TP;
constexpr int CH_SMEM = CO_BAR + 256 + 1024 + DBG_EXTRA;
static_assert(CO_WA >= 3 * 65536 && CO_P + 3072 <= CO_ST && CH_NSM <= 3, "smem layout");
#define CH_POLL_DELAY 0
#define CH_PEARLY 0
#define CH_VPOS 2
#define CH_VST 0
#define CH_V3_DELAY 0
#define CH_LSPOS 1
#define CH_V1 0
#define CH_V2 24
#define CH_V3 32
#define CH_OG 2
#define CH_OW 8
#define CH_OF 12
#define CH_CHAINS 4

constexpr float CH_SC = 0.08838834764831845f * 1.4426950408889634f;
__device__ __forceinline__ uint32_t pin(uint32_t v) { return __shfl_sync(0xffffffff, v, threadIdx.x & 31); }

__global__ void __cluster_dims__(8, 1, 1) __launch_bounds__(CH_BLOCK, 1)
chain_kernel(const __grid_constant__ ChainParams P, const bf16* __restrict__ mem0, const bf16* __restrict__ Wo, const bf16* __restrict__ x,
             const bf16* __restrict__ gate_w) {
    extern __shared__ uint8_t smem_raw[];
    const uint32_t sb = (smem_u32(smem_raw) + 1023) & ~1023u;
    const int tid = threadIdx.x, warp = __shfl_sync(0xffffffff, tid >> 5, 0), lane = tid & 31;
    const int rank = (int)cluster_ctarank();
    const int C = blockIdx.x >> 3;
    const int h = C * 4 + (rank >> 1);
    const int qd = lane >> 2, qc = lane & 3;
    const int t4 = warp & 3, wg = warp >> 2;
    pdl_launch_dependents();
    TS_BEGIN(2);
    const uint32_t bar_mem = sb + CO_BAR, bar_o = bar_mem + 32, bar_sc = bar_o + 32, bar_x = bar_sc + 8, bar_l = bar_x + 16, bar_w = bar_l + 8;
    if (tid == 0) {
        for (int j = 0; j < 15; j++) mbar_init(bar_mem + 8 * j, bar_mem + 8 * j == bar_l ? 4 : 1);
        asm volatile("fence.mbarrier_init.release.cluster;" ::: "memory");
    }
    __syncthreads();
    if ((tid & 127) == 0) {
        mbar_expect_tx(bar_w + 8 * wg, 65536);
        for (int i = 0; i < 8; i++)
            tma_load_2d(sb + wg * 65536 + i * 8192, &P.mapW[wg], bar_w + 8 * wg, h * HD + (rank & 1) * 64, i * 64);
    }
    {
        for (int i = tid; i < 512; i += CH_BLOCK) asm volatile("prefetch.global.L2 [%0];" :: "l"(Wo + (size_t)(C * 512 + i) * DM + rank * 64));
        if (tid < 64) asm volatile("prefetch.global.L2 [%0];" :: "l"(x + (size_t)tid * DM + rank * 64));
    }
    if (tid < 256) {
        const int r = blockIdx.x * 32 + (tid >> 3);
        float sum = 0.f;
#pragma unroll
        for (int c = 0; c < 8; c++) {
            const int col = c * 64 + (tid & 7) * 8;
            const uint4 xv = __ldg(reinterpret_cast<const uint4*>(x + (size_t)r * DM + col));
            const uint4 gv = __ldg(reinterpret_cast<const uint4*>(gate_w + col));
            const bf16* xp = reinterpret_cast<const bf16*>(&xv);
            const bf16* gp = reinterpret_cast<const bf16*>(&gv);
#pragma unroll
            for (int e = 0; e < 8; e++) sum += bf16r(__bfloat162float(xp[e]) * __bfloat162float(gp[e]));
        }
        sum += __shfl_xor_sync(0xffffffff, sum, 1);
        sum += __shfl_xor_sync(0xffffffff, sum, 2);
        sum += __shfl_xor_sync(0xffffffff, sum, 4);
        if ((tid & 7) == 0) g_gate[r] = bf16r(1.f / (1.f + __expf(-bf16r(sum))));
        asm volatile("bar.sync 1, 256;" ::: "memory");
        if (tid == 32) signal_ctr_generic(CT_GATE);
    }
    auto chunk = [&](int i) { return (uint32_t)((rank - (i >> 1) - 4 * (i & 1)) & 7); };
    const uint32_t wfrag = (((lane >> 4) << 3) + (lane & 7)) * 128 + (((t4 * 2 + ((lane >> 3) & 1)) ^ (lane & 7)) << 4);
    const uint32_t aO = pin(sb + wg * CH_TW + wfrag);
    const uint32_t aM = pin(sb + (lane & 7) * 128 + (((lane >> 3) ^ (lane & 7)) << 4));
    const uint32_t aL = pin(sb + lane * 8);
    uint32_t w[32][4];
    float d[16];
    mbar_wait(bar_w + 8 * wg, 0);
#pragma unroll
    for (int e = CH_NSM; e < 32; e++) ldmatrix_x4_trans(w[e][0], w[e][1], w[e][2], w[e][3], sb + wg * 65536 + wfrag + chunk(e >> 2) * 8192 + (e & 3) * 2048);
#pragma unroll
    for (int e = 0; e < CH_NSM; e++) {
        const uint4 u = lds128(sb + wg * 65536 + chunk(0) * 8192 + e * 2048 + (tid & 127) * 16);
        sts128(sb + CO_WA + wg * CH_TW + e * 2048 + (tid & 127) * 16, u.x, u.y, u.z, u.w);
    }
    fence_async_smem();
    __syncthreads();
    if (tid == 0) {
        fence_async_smem();
        for (int b = 0; b < 2; b++) {
            mbar_expect_tx(bar_x + 8 * b, 32768);
            for (int i = 0; i < 8; i++) tma_load_2d(sb + CO_XB + b * 32768 + i * 4096, &P.mapX, bar_x + 8 * b, i * 64, b * SEGL);
        }
    }
#pragma unroll 2
    for (int i = tid; i < 512 * 4; i += CH_BLOCK) {
        const int r = i >> 2, cg = i & 3, ks = r >> 4, kp = r & 15;
        const int src = (rank - (ks >> 2)) & 7;
        const uint4* p = reinterpret_cast<const uint4*>(Wo + (size_t)(C * 512 + src * 64 + (ks & 3) * 16 + (kp >> 2) * 2 + (kp & 1) + (kp & 2) * 4) * DM + rank * 64 + cg * 16);
        const uint4 u0 = __ldg(p), u1 = __ldg(p + 1);
        const uint32_t a = sb + CO_WO + r * 128;
        sts128(a + (((cg * 2) ^ (r & 7)) << 4), __byte_perm(u0.x, u0.y, 0x5410), __byte_perm(u0.z, u0.w, 0x5410), __byte_perm(u1.x, u1.y, 0x5410), __byte_perm(u1.z, u1.w, 0x5410));
        sts128(a + (((cg * 2 + 1) ^ (r & 7)) << 4), __byte_perm(u0.x, u0.y, 0x7632), __byte_perm(u0.z, u0.w, 0x7632), __byte_perm(u1.x, u1.y, 0x7632), __byte_perm(u1.z, u1.w, 0x7632));
    }
#pragma unroll 1
    for (int i = tid; i < 512; i += CH_BLOCK) {
        const int n = i >> 6, c = i & 63;
        const uint4 u = __ldg(reinterpret_cast<const uint4*>(mem0 + n * DM + chunk(c >> 3) * 64 + (c & 7) * 8));
        sts128(sb + CO_MB + (c >> 3) * 1024 + n * 128 + (((c & 7) ^ n) << 4), u.x, u.y, u.z, u.w);
    }
    if (tid < 128) sts128(sb + CO_T + (tid >> 6) * CH_TP + 2 * CH_TW + 5120 + (tid & 63) * 16, 0u, 0u, 0u, 0u);
    else if (tid < 160) sts128(sb + CO_P + ((tid >> 3) & 3) * 768 + 640 + (tid & 7) * 16, 0u, 0u, 0u, 0u);
    fence_async_smem();
    TS_END(6);
    auto pass32 = [&](int b, int e0 = 0, int e1 = 32) {
        const uint32_t lo = desc_lo(sb + CO_XB + b * 32768, 16);
        wgmma_fence();
#pragma unroll
        for (int e = 0; e < 32; e++) if (e >= e0 && e < e1) {
            const uint32_t db = lo + chunk(e >> 2) * 256 + (e & 3) * 2;
            if (e < CH_NSM) wgmma_ss_n32(d, desc_lo(sb + CO_WA + wg * CH_TW + e * 2048, 16), db, e != 0);
            else wgmma_rs_n32(d, w[e], db, e != 0);
        }
        wgmma_commit();
    };
    auto store32 = [&](uint32_t a) {
        stmatrix_x4_trans(a, pack_bf16(d[0], d[1]), pack_bf16(d[2], d[3]), pack_bf16(d[4], d[5]), pack_bf16(d[6], d[7]));
        stmatrix_x4_trans(a + 2048, pack_bf16(d[8], d[9]), pack_bf16(d[10], d[11]), pack_bf16(d[12], d[13]), pack_bf16(d[14], d[15]));
    };
    auto mem_proj = [&](int s, bool wait, bool arrive = false) {
        const uint32_t par = s & 1;
        float acc[CH_CHAINS][4];
#pragma unroll
        for (int i = 0; i < CH_CHAINS; i++) acc[i][0] = acc[i][1] = acc[i][2] = acc[i][3] = 0.f;
        const uint32_t aM2 = aM ^ 64;
        uint32_t b[2][8];
        auto load = [&](int c) {
            if (wait && !(c & 1)) mbar_wait_cl(bar_mem + 4 * c, par ^ 1);
            if (c == 0) DBG(11, 0);
            if (c == 6) DBG(13, 0);
            ldmatrix_x4(b[c & 1][0], b[c & 1][1], b[c & 1][2], b[c & 1][3], aM + CO_MB + c * 1024);
            ldmatrix_x4(b[c & 1][4], b[c & 1][5], b[c & 1][6], b[c & 1][7], aM2 + CO_MB + c * 1024);
        };
        load(0);
#pragma unroll
        for (int c = 0; c < 8; c++) {
            if (c < 7) load(c + 1);
            SCHED_FENCE();
#pragma unroll
            for (int i = 0; i < 4; i++) {
                const int e = c * 4 + i;
                mma_16816(acc[i % CH_CHAINS], w[e][0], w[e][1], w[e][2], w[e][3], b[c & 1][i * 2], b[c & 1][i * 2 + 1]);
            }
        }
        if (CH_CHAINS == 4) {
#pragma unroll
            for (int i = 0; i < 4; i++) { acc[0][i] += acc[2 % CH_CHAINS][i]; acc[1][i] += acc[3 % CH_CHAINS][i]; }
        }
        const uint32_t r0 = pack_bf16(acc[0][0] + acc[1][0], acc[0][1] + acc[1][1]);
        const uint32_t r1 = pack_bf16(acc[0][2] + acc[1][2], acc[0][3] + acc[1][3]);
        DBGD(40 + warp, warp, r0 ^ r1);
        stmatrix_x2_trans(aO + par * CH_TP + CO_T + 4096, r0, r1);
    };
    auto load_wa = [&]() {
#pragma unroll
        for (int e = 0; e < CH_NSM; e++) ldmatrix_x4_trans(w[e][0], w[e][1], w[e][2], w[e][3], aO + CO_WA + e * 2048);
    };
    auto remote = [](uint32_t a, uint32_t r) { return mapa_u32(a, r); };
    mbar_wait(bar_x, 0);
    pass32(0);
    wgmma_wait<0>();
    store32(aO + CO_T);
    fence_async_smem();
    __syncthreads();
    cluster_sync_all();
    TS_BEGIN(5);

    if (wg < 2) {
        const uint32_t aQ = pin(sb + CO_T + qd * 128 + (((2 * qc) ^ qd) << 4));
        auto local_scores = [&](int s) {
            const uint32_t tb = sb + CO_T + (s & 1) * CH_TP;
            wgmma_fence();
#pragma unroll
            for (int ks = 0; ks < 4; ks++) wgmma_ss_n32_kk(d, desc_lo(tb + CH_TW, 16) + ks * 2, desc_lo(tb, 16) + ks * 2, ks != 0);
            wgmma_commit();
            wgmma_wait<0>();
            const uint32_t rb = remote(bar_l, rank ^ 1);
            if (t4 < 2) {
                const uint32_t off = 2 * aL - sb + t4 * 512;
#pragma unroll
                for (int j = 0; j < 4; j++) if (j >= 2 || t4 == 0) {
                    st_async_v4(remote(off + (s & 1) * 5120 + CO_LS + j * 1280, rank ^ 1), __float_as_uint(d[4 * j]), __float_as_uint(d[4 * j + 1]), __float_as_uint(d[4 * j + 2]), __float_as_uint(d[4 * j + 3]), rb);
                    sts128(off + CO_LO + j * 1280, __float_as_uint(d[4 * j]), __float_as_uint(d[4 * j + 1]), __float_as_uint(d[4 * j + 2]), __float_as_uint(d[4 * j + 3]));
                }
            } else if (t4 == 2) {
#pragma unroll
                for (int j = 0; j < 4; j++) {
                    st_async_v2(remote(aL + (s & 1) * 5120 + CO_LS + 1024 + j * 1280, rank ^ 1), __float_as_uint(d[4 * j]), __float_as_uint(d[4 * j + 1]), rb);
                    asm volatile("st.shared.v2.f32 [%0], {%1, %2};" :: "r"(aL + CO_LO + 1024 + j * 1280), "f"(d[4 * j]), "f"(d[4 * j + 1]) : "memory");
                }
            }
            __syncwarp();
            if (t4 < 3 && lane == 0) mbar_arrive(bar_l);
            DBG(6, 4);
        };
        auto local_pv = [&](int s, bool arrive) {
            wgmma_fence();
#pragma unroll
            for (int ks = 0; ks < 3; ks++)
                wgmma_ss_n32_p(d, desc_lo(sb + CO_T + (s & 1) * CH_TP + 2 * CH_TW + ks * 2048, 16), desc_lo(sb + CO_P + ks * 256, 128), ks != 0);
            wgmma_commit();
            wgmma_wait<0>();
            if (arrive) asm volatile("bar.arrive 9, 256;" ::: "memory");
            store32(aO + CO_ST);
            fence_async_smem();
            if (!arrive) asm volatile("bar.sync 5, 128;" ::: "memory");
        };
        auto store_ctx = [&](int s) {
            tma_store_2d(&P.mapC, sb + CO_ST, (rank & 1) * 64, h * SEQ + s * SEGL);
            asm volatile("cp.async.bulk.commit_group;" ::: "memory");
        };
        auto signal_ctx = [&](int m0, int m1) {
            asm volatile("fence.proxy.async;" ::: "memory");
            __threadfence();
            for (int m = m0; m < m1; m++) asm volatile("red.relaxed.gpu.global.add.u32 [%0], 1;" :: "l"(&g_ctr[CT_CB + m]) : "memory");
        };
#pragma unroll 1
        for (int s = 0; s < NSEG; s++) {
            const uint32_t par = s & 1;
            load_wa();
            mem_proj(s, s > 0);
            if (s == NSEG - 1) break;
            if (warp < 5) {
                const uint32_t qa_ = aQ + par * CH_TP, ka = qa_ + warp * 1024;
                asm volatile("bar.sync 1, 256;" ::: "memory");
                const uint4 qa = lds128(qa_ + 4096), k0 = lds128(ka + CH_TW), qb = lds128((qa_ ^ 16) + 4096), k1 = lds128((ka ^ 16) + CH_TW);
                DBGD(52 + warp, warp, qa.x ^ qb.x);
                float c[4] = {0.f, 0.f, 0.f, 0.f}, c2[4] = {0.f, 0.f, 0.f, 0.f};
                mma_16816(c, qa.x, 0u, qa.y, 0u, k0.x, k0.y);
                mma_16816(c2, qb.x, 0u, qb.y, 0u, k1.x, k1.y);
                mma_16816(c, qa.z, 0u, qa.w, 0u, k0.z, k0.w);
                mma_16816(c2, qb.z, 0u, qb.w, 0u, k1.z, k1.w);
                c[0] += c2[0]; c[1] += c2[1];
                DBGD(57 + warp, warp, __float_as_uint(c[0]));
                const uint32_t off = aL + CO_SC + warp * 256;
                st_async_v2(remote(off + 1280, rank ^ 1), __float_as_uint(c[0]), __float_as_uint(c[1]), remote(bar_sc, rank ^ 1));
                st_async_v2(off, __float_as_uint(c[0]), __float_as_uint(c[1]), bar_sc);
                asm volatile("bar.arrive 2, 288;" ::: "memory");
                DBG(3, 0);
            } else {
                asm volatile("bar.arrive 1, 256;" ::: "memory");
            }
            if (wg == 0) {
                if (tid == 96) {
                    mbar_expect_tx(bar_sc, 2 * 1280);
#pragma unroll
                    for (int j = 0; j < 4; j++) { mbar_expect_tx(bar_mem + 8 * j, 2048); if (j < CH_OG) mbar_expect_tx(bar_o + 8 * j, 8192 / CH_OG); }
                    if (s > 0) mbar_wait(bar_l, par ^ 1);
                    mbar_expect_tx(bar_l, 4096);
                }
                if (tid == 96 && s > 1) {
                    if (s == 34 || s == 50 || s == 58 || s == 62) {
                        asm volatile("cp.async.bulk.wait_group 0;" ::: "memory");
                        signal_ctx(s == 34 ? 0 : (2 * s - 68) >> 2, s >> 2);
                    }
                    store_ctx(s - 2);
                    asm volatile("cp.async.bulk.wait_group.read 0;" ::: "memory");
                }
                __syncwarp();
                mbar_wait(bar_x + 8 * (par ^ 1), ((s + 1) >> 1) & 1);
                asm volatile("bar.sync 5, 128;" ::: "memory");
                float c[4];
                const uint32_t alo = desc_lo(sb + CO_WO, 16), blo = desc_lo(sb + CO_OB, 128);
                uint32_t* wp = g_xbuf + (size_t)rank * 2048 + C * 256 + qc * 64 + t4 * 8 + qd;
                mbar_wait_cl(bar_o, par);
                DBG(16, 0);
                fence_async_smem();
                wgmma_fence();
#pragma unroll
                for (int i = 0; i < 32; i++) {
                    wgmma_ss_n8(c, alo + i * 128, blo + i * 16, i != 0);
                    if (CH_OG == 2 && i == CH_OW) mbar_wait_cl(bar_o + 8, par);
                    if (CH_OG == 2 && i == CH_OF) fence_async_smem();
                }
                wgmma_commit();
                wgmma_wait<0>();
                asm volatile("st.relaxed.gpu.global.u32 [%0], %1;" :: "l"(wp + (s & 3) * 16384), "r"(~pack_bf16(c[0], c[2])) : "memory");
                asm volatile("st.relaxed.gpu.global.u32 [%0], %1;" :: "l"(wp + (s & 3) * 16384 + 32), "r"(~pack_bf16(c[1], c[3])) : "memory");
                asm volatile("bar.arrive 4, 256;" ::: "memory");
                asm volatile("bar.arrive 6, 256;" ::: "memory");
                DBG(8, 0);
                if (s > 0) local_pv(s - 1, true); else asm volatile("bar.arrive 9, 256;" ::: "memory");
                DBG(28, 0);
                asm volatile("st.relaxed.gpu.global.u32 [%0], %1;" :: "l"(wp + ((s + 2) & 3) * 16384), "r"(0) : "memory");
                asm volatile("st.relaxed.gpu.global.u32 [%0], %1;" :: "l"(wp + ((s + 2) & 3) * 16384 + 32), "r"(0) : "memory");
                if (tid == 0 && s + 2 < NSEG) {
                    mbar_expect_tx(bar_x + 8 * par, 32768);
                    tma_load_2d_mc(sb + CO_XB + par * 32768 + rank * 4096, &P.mapX, bar_x + 8 * par, rank * 64, (s + 2) * SEGL, (uint16_t)0xff);
                }
                __syncwarp();
            } else {
                const uint32_t vaddr = pin(sb + CO_T + par * CH_TP + 2 * CH_TW + (lane & 15) * 128 + (((t4 * 2 + (lane >> 4)) ^ (lane & 7)) << 4));
                const uint32_t dsta = pin(sb + CO_OB + t4 * 256 + (qc >> 1) * 128 + qd * 16 + (qc & 1) * 8);
                fence_async_smem();
                uint32_t vb[3][4];
                auto load_v = [&]() {
                    asm volatile("bar.sync 3, 256;" ::: "memory");
#pragma unroll
                    for (int k = 0; k < 3; k++) ldmatrix_x4_trans(vb[k][0], vb[k][1], vb[k][2], vb[k][3], vaddr + k * 2048);
                };
                if (CH_VPOS == 0) load_v();
                mbar_wait_cl(bar_sc, par);
                DBG(4, 4);
                float v[10];
#pragma unroll
                for (int j = 0; j < 5; j++) {
                    const float2 a = lds64f(aL + CO_SC + j * 256), b = lds64f(aL + CO_SC + 1280 + j * 256);
                    v[2 * j] = a.x + b.x; v[2 * j + 1] = a.y + b.y;
                }
                if (CH_VPOS == 1) load_v();
                float mx = fmaxf(fmaxf(fmaxf(v[0], v[1]), fmaxf(v[2], v[3])), fmaxf(fmaxf(v[4], v[5]), fmaxf(v[6], v[7])));
                mx = fmaxf(mx, fmaxf(v[8], v[9]));
                mx = fmaxf(mx, __shfl_xor_sync(0xffffffff, mx, 1));
                mx = fmaxf(mx, __shfl_xor_sync(0xffffffff, mx, 2));
                if (CH_VPOS == 2) load_v();
                DBG(19, 4);
                mx *= CH_SC;
#pragma unroll
                for (int j = 0; j < 10; j++) v[j] = ex2f(fmaf(v[j], CH_SC, -mx));
                float c0[4] = {0.f, 0.f, 0.f, 0.f}, c1[4] = {0.f, 0.f, 0.f, 0.f}, cs[4] = {0.f, 0.f, 0.f, 0.f};
#pragma unroll
                for (int k = 0; k < 3; k++) {
                    const uint32_t p0 = pack_bf16(v[4 * k], v[4 * k + 1]), p1 = k < 2 ? pack_bf16(v[4 * k + 2], v[4 * k + 3]) : 0u;
                    mma_16816(cs, p0, 0u, p1, 0u, 0x3f803f80u, 0x3f803f80u);
                    mma_16816(c0, p0, 0u, p1, 0u, vb[k][0], vb[k][1]);
                    mma_16816(c1, p0, 0u, p1, 0u, vb[k][2], vb[k][3]);
                }
                float inv;
                asm volatile("rcp.approx.ftz.f32 %0, %1;" : "=f"(inv) : "f"(cs[0]));
                const uint32_t b0 = pack_bf16(c0[0] * inv, c0[1] * inv), b1 = pack_bf16(c1[0] * inv, c1[1] * inv);
                DBG(20, 4);
#pragma unroll
                for (int i = 0; i < 8; i++) {
                    const int dr = (rank + i) & 7;
                    st_async_v2(remote(dsta + i * 1024, dr), b0, b1, remote(bar_o + 8 * (i * CH_OG / 8), dr));
                    if (i == 0) asm volatile("bar.arrive 7, 256;" ::: "memory");
                }
                DBG(5, 4);
                mbar_wait(bar_x + 8 * (par ^ 1), ((s + 1) >> 1) & 1);
                asm volatile("bar.sync 4, 256;" ::: "memory");
                if (CH_LSPOS == 0) local_scores(s);
            }
            pass32(par ^ 1);
            DBG(21, 0);
            wgmma_wait<0>();
            store32(aO + (par ^ 1) * CH_TP + CO_T);
            if (wg == 0) fence_async_smem();
            DBG(22, 0);
            DBG(29, 4);
            if (CH_LSPOS == 1 && wg == 1) local_scores(s);
        }
        fence_async_smem();
        asm volatile("bar.sync 1, 256;" ::: "memory");
        if (warp < 5) asm volatile("bar.arrive 2, 288;" ::: "memory");
        if (wg == 0) {
            if (tid == 96) { mbar_wait(bar_l, 0); mbar_expect_tx(bar_l, 4096); store_ctx(NSEG - 3); asm volatile("cp.async.bulk.wait_group.read 0;" ::: "memory"); }
            __syncwarp();
            asm volatile("bar.sync 7, 256;" ::: "memory");
            local_pv(NSEG - 2, false);
            asm volatile("bar.arrive 6, 256;" ::: "memory");
            if (tid == 96) { store_ctx(NSEG - 2); asm volatile("cp.async.bulk.wait_group.read 0;" ::: "memory"); }
            __syncwarp();
            asm volatile("bar.sync 8, 256;" ::: "memory");
            local_pv(NSEG - 1, false);
            if (tid == 96) {
                store_ctx(NSEG - 1);
                asm volatile("cp.async.bulk.wait_group 0;" ::: "memory");
                signal_ctx(15, 16);
            }
            uint32_t* wp = g_xbuf + 16384 + (size_t)rank * 2048 + C * 256 + tid * 2;
            *reinterpret_cast<uint2*>(wp) = make_uint2(0u, 0u);
        } else {
            asm volatile("bar.sync 3, 256;" ::: "memory");
            asm volatile("bar.arrive 7, 256;" ::: "memory");
            local_scores(NSEG - 1);
        }
    } else {
        auto local_softmax = [&](int s) {
            float v[10];
            const float2 g = __ldcg(reinterpret_cast<const float2*>(g_gate + s * SEGL + t4 * 8 + 2 * qc));
            mbar_wait_cl(bar_l, s & 1);
            const uint32_t off = 2 * aL - sb + t4 * 1280;
            {
                const uint4 a0 = lds128(off + (s & 1) * 5120 + CO_LS), b0 = lds128(off + CO_LO), a1 = lds128(off + (s & 1) * 5120 + CO_LS + 512), b1 = lds128(off + CO_LO + 512);
                const float2 a2 = lds64f(aL + t4 * 1280 + (s & 1) * 5120 + CO_LS + 1024), b2 = lds64f(aL + t4 * 1280 + CO_LO + 1024);
                auto f = [](uint32_t a, uint32_t b) { return __uint_as_float(a) + __uint_as_float(b); };
                v[0] = f(a0.x, b0.x); v[1] = f(a0.y, b0.y); v[2] = f(a0.z, b0.z); v[3] = f(a0.w, b0.w);
                v[4] = f(a1.x, b1.x); v[5] = f(a1.y, b1.y); v[6] = f(a1.z, b1.z); v[7] = f(a1.w, b1.w);
                v[8] = a2.x + b2.x; v[9] = a2.y + b2.y;
            }
            const int lim = t4 * 8 + 2 * qc - qd;
#pragma unroll
            for (int n = 0; n < 4; n++) {
                if (8 * n > lim) v[2 * n] = -INFINITY;
                if (8 * n > lim + 1) v[2 * n + 1] = -INFINITY;
            }
            float m0 = fmaxf(fmaxf(fmaxf(v[0], v[2]), fmaxf(v[4], v[6])), v[8]), m1 = fmaxf(fmaxf(fmaxf(v[1], v[3]), fmaxf(v[5], v[7])), v[9]);
#pragma unroll
            for (int o = 4; o < 32; o *= 2) { m0 = fmaxf(m0, __shfl_xor_sync(0xffffffff, m0, o)); m1 = fmaxf(m1, __shfl_xor_sync(0xffffffff, m1, o)); }
            m0 *= CH_SC; m1 *= CH_SC;
#pragma unroll
            for (int n = 0; n < 5; n++) { v[2 * n] = ex2f(fmaf(v[2 * n], CH_SC, -m0)); v[2 * n + 1] = ex2f(fmaf(v[2 * n + 1], CH_SC, -m1)); }
            float s0 = ((v[0] + v[2]) + (v[4] + v[6])) + v[8], s1 = ((v[1] + v[3]) + (v[5] + v[7])) + v[9];
#pragma unroll
            for (int o = 4; o < 32; o *= 2) { s0 += __shfl_xor_sync(0xffffffff, s0, o); s1 += __shfl_xor_sync(0xffffffff, s1, o); }
            asm("rcp.approx.ftz.f32 %0, %0;" : "+f"(s0));
            asm("rcp.approx.ftz.f32 %0, %0;" : "+f"(s1));
            s0 *= 1.f - g.x; s1 *= 1.f - g.y;
            const uint32_t pa = 2 * aL - sb + CO_P + t4 * 768;
            stmatrix_x4_trans(pa, pack_bf16(v[0] * s0, v[1] * s1), pack_bf16(v[2] * s0, v[3] * s1), pack_bf16(v[4] * s0, v[5] * s1), pack_bf16(v[6] * s0, v[7] * s1));
            asm volatile("stmatrix.sync.aligned.m8n8.x1.trans.shared.b16 [%0], {%1};" :: "r"(pa + 512), "r"(pack_bf16(v[8] * s0, v[9] * s1)) : "memory");
            fence_async_smem();
            DBG(7, 8);
        };
        wait_ctr(CT_GATE, 64u);
#pragma unroll 1
        for (int s = 0; s < NSEG; s++) {
            const uint32_t par = s & 1;
            if (s > 0) local_softmax(s - 1);
            load_wa();
            if (s < NSEG - 1) mbar_wait(bar_x + 8 * (par ^ 1), ((s + 1) >> 1) & 1);
            asm volatile("bar.sync 2, 288;" ::: "memory");
            DBG(23, 8);
            mem_proj(s, false, true);
            asm volatile("bar.arrive 3, 256;" ::: "memory");
            if (s == NSEG - 1) break;
            DBG(24, 8);
            if (CH_V1 > 0) pass32(par ^ 1, 0, CH_V1);
            asm volatile("bar.sync 7, 256;" ::: "memory");
            pass32(par ^ 1, CH_V1, CH_V2);
            DBG(26, 8);
            asm volatile("bar.sync 6, 256;" ::: "memory");
            const uint2* xb = reinterpret_cast<const uint2*>(g_xbuf + (s & 3) * 16384 + (size_t)rank * 2048 + t4 * 64) + lane;
            uint2 p[8];
            auto poll_all = [&]() {
#pragma unroll
                for (int k = 0; k < 8; k++)
                    asm volatile("ld.relaxed.gpu.global.v2.u32 {%0, %1}, [%2];" : "=r"(p[k].x), "=r"(p[k].y) : "l"(xb + k * 128) : "memory");
                DBG(17, 8);
            };
            if (CH_V3 > CH_V2) { pace(CH_V3_DELAY); pass32(par ^ 1, CH_V2, CH_V3); }
            if (CH_VST == 0) {
                asm volatile("bar.sync 9, 256;" ::: "memory");
                wgmma_wait<0>();
                store32(aO + (par ^ 1) * CH_TP + CO_T);
                DBG(27, 8);
            }
            pace(CH_POLL_DELAY);
            auto lo = [](uint32_t u) { return __uint_as_float(~u << 16); };
            auto hi = [](uint32_t u) { return __uint_as_float(~u & 0xffff0000u); };
            poll_all();
            for (int it = 0; it < WAIT_LIMIT / 4; it++) {
                uint32_t bad = 0;
#pragma unroll
                for (int k = 0; k < 8; k++) bad |= (min(p[k].x, p[k].y) == 0u ? 1u : 0u) << k;
                if (__all_sync(0xffffffff, bad == 0u)) break;
                if (it == 0) DBG(12, 8);
                if (it == 1) DBG(14, 8);
                if (it == 2) DBG(15, 8);
#pragma unroll
                for (int k = 0; k < 8; k++)
                    if (bad & (1u << k))
                        asm volatile("ld.relaxed.gpu.global.v2.u32 {%0, %1}, [%2];" : "=r"(p[k].x), "=r"(p[k].y) : "l"(xb + k * 128) : "memory");
            }
            DBG(9, 8);
            const uint32_t m0 = pack_bf16(((lo(p[0].x) + lo(p[1].x)) + (lo(p[2].x) + lo(p[3].x))) + ((lo(p[4].x) + lo(p[5].x)) + (lo(p[6].x) + lo(p[7].x))),
                                          ((hi(p[0].x) + hi(p[1].x)) + (hi(p[2].x) + hi(p[3].x))) + ((hi(p[4].x) + hi(p[5].x)) + (hi(p[6].x) + hi(p[7].x))));
            const uint32_t m1 = pack_bf16(((lo(p[0].y) + lo(p[1].y)) + (lo(p[2].y) + lo(p[3].y))) + ((lo(p[4].y) + lo(p[5].y)) + (lo(p[6].y) + lo(p[7].y))),
                                          ((hi(p[0].y) + hi(p[1].y)) + (hi(p[2].y) + hi(p[3].y))) + ((hi(p[4].y) + hi(p[5].y)) + (hi(p[6].y) + hi(p[7].y))));
            const int row = t4 * 2 + (lane >> 4);
            const uint32_t dsta = sb + CO_MB + row * 128 + ((((lane & 15) >> 1) ^ row) << 4) + (lane & 1) * 8;
#pragma unroll
            for (int i = 0; i < 8; i++) {
                const int dr = (rank + (i & 1) * 4 + (i >> 1)) & 7;
                st_async_v2(remote(dsta + i * 1024, dr), m0, m1, remote(bar_mem + 8 * (i >> 1), dr));
            }
            DBG(10, 8);
            if (CH_VST == 1) {
                if (CH_V3 < 32) pass32(par ^ 1, CH_V3, 32);
                asm volatile("bar.sync 9, 256;" ::: "memory");
                wgmma_wait<0>();
                store32(aO + (par ^ 1) * CH_TP + CO_T);
                DBG(27, 8);
            }
        }
        asm volatile("bar.sync 6, 256;" ::: "memory");
        local_softmax(NSEG - 1);
        asm volatile("bar.arrive 8, 256;" ::: "memory");
    }
    __syncthreads();
    cluster_sync_all();
    TS_END(2);
}

struct Proj2Params {
    CUtensorMap mapA[2];
    CUtensorMap mapW[3];
    bf16* out[3];
};
#define P2T(i)
#define P2_NOMMA 0
#define P2_NOLOAD 0
constexpr int P2_STAGES = 6;
constexpr int P2_SMEM = 131072 + P2_STAGES * 16384 + 1024 + 1024;
constexpr int P2_ITEMS = 168 + 48;

__device__ __forceinline__ int p2_reps(int t) { return t >= 168 ? 1 : 2; }
__device__ __forceinline__ void p2_tile(int t, int w, int& z, int& mp, int& head) {
    if (t >= 168) { w += ((t - 168) & 1) * 2; t = 168 + ((t - 168) >> 1); }
    const int hq = t / 24, v = t % 24;
    mp = v & 7;
    if (v < 16) { head = hq * 4 + (v >> 3) * 2 + (w >> 1); z = 1 + (w & 1); }
    else { head = hq * 4 + w; z = 0; }
}
__device__ __forceinline__ void mbar_arrive_remote(uint32_t bar_cluster_addr) {
    asm volatile("mbarrier.arrive.release.cluster.shared::cluster.b64 _, [%0];" :: "r"(bar_cluster_addr) : "memory");
}
__device__ __forceinline__ void mbar_arrive_cl(uint32_t bar_cluster_addr) {
    asm volatile("mbarrier.arrive.shared::cluster.b64 _, [%0];" :: "r"(bar_cluster_addr) : "memory");
}
__device__ __forceinline__ void mbar_wait_acq_cluster(uint32_t bar, uint32_t parity) {
    asm volatile(
        "{\n"
        ".reg .pred p, q;\n"
        ".reg .u32 c;\n"
        "mov.u32 c, 0;\n"
        "WAIT_LOOP_C:\n"
        "mbarrier.try_wait.parity.acquire.cluster.shared::cta.b64 p, [%0], %1;\n"
        "@p bra WAIT_DONE_C;\n"
        "add.u32 c, c, 1;\n"
        "setp.lt.u32 q, c, 4000000;\n"
        "@q bra WAIT_LOOP_C;\n"
        "WAIT_DONE_C:\n"
        "}\n" :: "r"(bar), "r"(parity) : "memory");
}
__device__ __forceinline__ uint4 quad_transpose(uint32_t p0, uint32_t p1, uint32_t p2, uint32_t p3, int lane) {
    const bool o1 = lane & 1, o2 = lane & 2;
    uint32_t s0 = o1 ? p0 : p1, s1 = o1 ? p2 : p3;
    s0 = __shfl_xor_sync(0xffffffff, s0, 1); s1 = __shfl_xor_sync(0xffffffff, s1, 1);
    const uint32_t a_lo = o1 ? s0 : p0, a_hi = o1 ? p1 : s0, b_lo = o1 ? s1 : p2, b_hi = o1 ? p3 : s1;
    uint32_t t0 = o2 ? a_lo : b_lo, t1 = o2 ? a_hi : b_hi;
    t0 = __shfl_xor_sync(0xffffffff, t0, 2); t1 = __shfl_xor_sync(0xffffffff, t1, 2);
    return o2 ? make_uint4(t0, t1, b_lo, b_hi) : make_uint4(a_lo, a_hi, t0, t1);
}
#define P2_PACE 35
#define P2_PACE2 0
template <bool PERM, int PACE = 0>
__device__ __forceinline__ void store_frag_128(const float (&acc)[64], bf16* obase, int lane) {
#pragma unroll
    for (int rr = 0; rr < 2; rr++)
#pragma unroll
        for (int g = 0; g < 4; g++) {
            const float* a = &acc[g * 16 + rr * 2];
            const uint32_t p0 = pack_bf16(a[0], a[1]), p1 = pack_bf16(a[4], a[5]), p2 = pack_bf16(a[8], a[9]), p3 = pack_bf16(a[12], a[13]);
            *reinterpret_cast<uint4*>(obase + (size_t)(rr * 8) * HD + g * 32) = PERM ? make_uint4(p0, p1, p2, p3) : quad_transpose(p0, p1, p2, p3, lane);
            pace(PACE);
        }
}
__global__ void __cluster_dims__(2, 1, 1) __launch_bounds__(384, 1) proj2_kernel(const __grid_constant__ Proj2Params P) {
    extern __shared__ uint8_t smem_raw[];
    const uint32_t sbase = (smem_u32(smem_raw) + 1023) & ~1023u;
    const uint32_t sA = sbase, sB = sbase + 131072, sC = sB + P2_STAGES * 16384;
    const uint32_t bars = sC;
    const uint32_t a_full = bars, a_empty = bars + 64, b_full = bars + 128, b_empty = b_full + 8 * P2_STAGES;
    const uint32_t item_bar = b_empty + 8 * P2_STAGES, item_in = item_bar + 16, slot = item_in + 16;
    const uint32_t note_bar = slot + 16, note_free = note_bar + 64, note = note_free + 64;
    const int warp = threadIdx.x >> 5, lane = threadIdx.x & 31;
    const uint32_t rank = cluster_ctarank();
    TS_BEGIN(0);
    if (threadIdx.x == 0) {
        for (int i = 0; i < 8; i++) { mbar_init(a_full + 8 * i, 1); mbar_init(a_empty + 8 * i, 2); }
        for (int i = 0; i < P2_STAGES; i++) { mbar_init(b_full + 8 * i, 1); mbar_init(b_empty + 8 * i, 2); }
        mbar_init(item_bar, 1); mbar_init(item_bar + 8, 1); mbar_init(item_in, 2); mbar_init(item_in + 8, 2);
        for (int i = 0; i < 8; i++) { mbar_init(note_bar + 8 * i, 1); mbar_init(note_free + 8 * i, 1); }
        asm volatile("fence.mbarrier_init.release.cluster;" ::: "memory");
    }
    __syncthreads();
    cluster_sync_all();
    pdl_launch_dependents();
    if (warp == 9) {
        if (lane == 0) {
            for (int n = 0;; n++) {
                const int e = (n & 1) * 4 + ((n >> 1) & 3);
                mbar_wait(note_bar + 8 * e, (n >> 3) & 1);
                int m;
                asm volatile("ld.shared.s32 %0, [%1];" : "=r"(m) : "r"(note + e * 4) : "memory");
                mbar_arrive(note_free + 8 * e);
                if (m < 0) break;
                signal_ctr(m);
            }
        }
    } else if (warp == 10) {
        if (lane == 0) {
            auto publish = [&](int ic, int tq) {
                const int t = tq < P2_ITEMS ? tq : -1;
                asm volatile("st.shared.s32 [%0], %1;" :: "r"(slot + (ic & 3) * 4), "r"(t) : "memory");
                mbar_arrive(item_bar + 8 * (ic & 1));
                st_async_b32(mapa_u32(slot + (ic & 3) * 4, 1), (uint32_t)t, mapa_u32(item_bar + 8 * (ic & 1), 1));
            };
            const int npair = (int)(gridDim.x >> 1), pair = (int)(blockIdx.x >> 1);
            if (rank == 0) publish(0, pair);
            for (int ic = 0;; ic++) {
                if (rank == 1) mbar_expect_tx(item_bar + 8 * (ic & 1), 4);
                mbar_wait(item_bar + 8 * (ic & 1), (ic >> 1) & 1);
                int t;
                asm volatile("ld.shared.s32 %0, [%1];" : "=r"(t) : "r"(slot + (ic & 3) * 4) : "memory");
                if (t < 0) break;
                int z0, mp, h0;
                p2_tile(t, 0, z0, mp, h0);
                const int aidx = z0 >= 1 ? 1 : 0;
                const int m0 = (2 * mp + (int)rank) * 128;
                for (int k = 0; k < 8; k++) {
                    mbar_wait(a_empty + 8 * k, (ic & 1) ^ 1);
                    if (P2_NOLOAD) mbar_arrive(a_full + 8 * k); else {
                    mbar_expect_tx(a_full + 8 * k, 16384);
                    tma_load_2d(sA + k * 16384, &P.mapA[aidx], a_full + 8 * k, k * 64, m0); }
                }
                if (rank == 0) {
                    mbar_wait(item_in + 8 * (ic & 1), (ic >> 1) & 1);
                    publish(ic + 1, ic == 0 ? npair + pair : 2 * npair + (int)atomicAdd(&g_ctr[CT_PROJ], 1u));
                }
            }
        }
    } else if (warp == 8 || warp == 11) {
        if (lane == 0) {
            const int par2 = warp == 8 ? 0 : 1;
            int it = 0; uint32_t bph = 0;
            for (int ic = 0;; ic++) {
                mbar_wait(item_bar + 8 * (ic & 1), (ic >> 1) & 1);
                int t;
                asm volatile("ld.shared.s32 %0, [%1];" : "=r"(t) : "r"(slot + (ic & 3) * 4) : "memory");
                if (t < 0) break;
                const int nt = 2 * p2_reps(t);
                for (int w = 0; w < nt; w++) {
                    int z, mp, hd;
                    p2_tile(t, w, z, mp, hd);
                    for (int k = 0; k < 8; k++) {
                        const int s = it; const uint32_t phb = bph;
                        if (++it == P2_STAGES) { it = 0; bph ^= 1; }
                        if ((k & 1) != par2) continue;
                        mbar_wait(b_empty + 8 * s, phb ^ 1);
                        if (P2_NOLOAD) { mbar_arrive(b_full + 8 * s); continue; }
                        mbar_expect_tx(b_full + 8 * s, 16384);
                        tma_load_2d_mc(sB + s * 16384 + rank * 8192, &P.mapW[z], b_full + 8 * s, hd * 128 + (int)rank * 64, k * 64, (uint16_t)3);
                    }
                }
            }
        }
    } else {
        const int wg = warp >> 2;
        float acc[2][64];
        const uint32_t a_lo = desc_lo(sA, 16), b_lo0 = desc_lo(sB, 8192);
        const bool elected = (threadIdx.x & 127) == 0;
        int s = (wg * 8) % P2_STAGES;
        uint32_t ph = ((wg * 8) / P2_STAGES) & 1;
        int nnote = 0;
        if (wg == 1) asm volatile("bar.arrive 3, 256;" ::: "memory");
        for (int ic = 0;; ic++) {
            mbar_wait(item_bar + 8 * (ic & 1), (ic >> 1) & 1);
            int t;
            asm volatile("ld.shared.s32 %0, [%1];" : "=r"(t) : "r"(slot + (ic & 3) * 4) : "memory");
            P2T(7);
            if (wg == 0 && t < 0) {
                if (elected) {
                    const int e = nnote & 3;
                    mbar_wait(note_free + 8 * e, ((nnote >> 2) & 1) ^ 1);
                    asm volatile("st.shared.s32 [%0], %1;" :: "r"(note + e * 4), "r"(-1) : "memory");
                    mbar_arrive(note_bar + 8 * e);
                }
            }
            if (t < 0) break;
            const int reps = p2_reps(t);
#pragma unroll 1
            for (int rp = 0; rp < reps; rp++) {
            const bool first = rp == 0, last = rp == reps - 1;
            int z, mp, head;
            p2_tile(t, rp * 2 + wg, z, mp, head);
            asm volatile("bar.sync %0, 256;" :: "r"(3 + wg) : "memory");
            P2T(0);
            if (wg == 1 && last && elected) mbar_arrive_cl(mapa_u32(item_in + 8 * (ic & 1), 0));
            int sprev = 0;
#pragma unroll
            for (int k = 0; k < 8; k++) {
                if (k == 0) P2T(5);
                if (wg == 0 && first) mbar_wait(a_full + 8 * k, ic & 1);
                if (k == 0) P2T(6);
                mbar_wait(b_full + 8 * s, ph);
                if (k == 7) asm volatile("bar.arrive %0, 256;" :: "r"(4 - wg) : "memory");
                if (k == 0) P2T(1);
                if (k == 7) P2T(2);
                const uint32_t b_lo = b_lo0 + s * 1024;
                wgmma_fence();
#pragma unroll
                for (int kk = 0; kk < (P2_NOMMA ? 1 : 4); kk++) {
                    wgmma_ss_n128_lo<1>(acc[0], a_lo + k * 1024 + kk * 2, b_lo + kk * 128, (k | kk) != 0);
                    wgmma_ss_n128_lo<1>(acc[1], a_lo + k * 1024 + 512 + kk * 2, b_lo + kk * 128, (k | kk) != 0);
                }
                wgmma_commit();
                if (k > 0) {
                    wgmma_wait<1>();
                    if (elected) {
                        const uint32_t e = b_empty + 8 * sprev;
                        mbar_arrive_cl(mapa_u32(e, 0)); mbar_arrive_cl(mapa_u32(e, 1));
                        if (last) mbar_arrive(a_empty + 8 * (k - 1));
                    }
                }
                sprev = s;
                if (++s == P2_STAGES) { s = 0; ph ^= 1; }
            }
            wgmma_wait<0>();
            P2T(3);
            if (elected) {
                const uint32_t e = b_empty + 8 * sprev;
                mbar_arrive_cl(mapa_u32(e, 0)); mbar_arrive_cl(mapa_u32(e, 1));
                if (last) mbar_arrive(a_empty + 8 * 7);
            }
            s += 8 % P2_STAGES; ph ^= (8 / P2_STAGES) & 1;
            if (s >= P2_STAGES) { s -= P2_STAGES; ph ^= 1; }
            const int m0 = (2 * mp + (int)rank) * 128;
            bf16* obase = P.out[z] + ((size_t)head * SEQ + m0 + (warp & 3) * 16 + (lane >> 2)) * HD + (lane & 3) * 8;
            store_frag_128<true, P2_PACE>(acc[0], obase, lane); store_frag_128<true, P2_PACE>(acc[1], obase + (size_t)64 * HD, lane);
            P2T(4);
            {
                asm volatile("bar.sync %0, 128;" :: "r"(1 + wg) : "memory");
                if (elected) {
                    const int e = wg * 4 + (nnote & 3);
                    mbar_wait(note_free + 8 * e, ((nnote >> 2) & 1) ^ 1);
                    asm volatile("st.shared.s32 [%0], %1;" :: "r"(note + e * 4), "r"(CT_AP + (head >> 1)) : "memory");
                    mbar_arrive(note_bar + 8 * e);
                }
                nnote++;
            }
            }
        }
        TS_END(0);
    }
    __syncthreads();
    cluster_sync_all();
}

struct OutParams {
    CUtensorMap mapCtx[2];
    CUtensorMap mapWo[2];
    CUtensorMap mapOut;
};

#define OT(i)
#define OTP(i, th)
constexpr int O2_STAGES = 4;
constexpr int O2_SMEM = O2_STAGES * 49152 + 1024 + 256;
constexpr int O2_GRID = 132;
#define O2_FINE 8

__global__ void __cluster_dims__(2, 1, 1) __launch_bounds__(352, 1)
out2_kernel(const __grid_constant__ OutParams P) {
    extern __shared__ uint8_t smem_raw[];
    const uint32_t sbase = (smem_u32(smem_raw) + 1023) & ~1023u;
    const uint32_t bar_full = sbase + O2_STAGES * 49152, bar_empty = bar_full + 8 * O2_STAGES, bar_item = bar_empty + 8 * O2_STAGES;
    const uint32_t slot = bar_item + 64, stop = slot + 32;
    const int warp = threadIdx.x >> 5, lane = threadIdx.x & 31;
    const uint32_t rank = cluster_ctarank();
    const int cid = blockIdx.x >> 1;
    int pt, cj;
    if (cid < 20) { pt = 2 + (cid < 10 ? cid : 19 - cid); cj = cid >= 10; }
    else if (cid < 28) { pt = 12 + (cid < 24 ? cid - 20 : 27 - cid); cj = cid >= 24; }
    else if (cid < 34) { pt = cid & 1; cj = (cid - 28) >> 1; }
    else { pt = 15 - (cid - 34) % 14; cj = 2 + (cid - 34) / 14; }
    const int nc = pt >= 12 ? 5 : pt >= 2 ? 4 : 3;
    const int mt = (pt >> 1) * 2 + (int)rank, m0 = mt * 128, n0 = (pt & 1) * 256;
    TS_BEGIN(4);
    OT(0);
    int tnext = 0;
    if (threadIdx.x == 256) {
        if (rank == 0) tnext = take_ticket(CT_OT + pt);
        for (int i = 0; i < O2_STAGES; i++) { mbar_init(bar_full + 8 * i, 1); mbar_init(bar_empty + 8 * i, 4); mbar_init(bar_item + 16 * i, 1); mbar_init(bar_item + 16 * i + 8, 1); }
        sts128(stop, 0u, 0u, 0u, 0u);
        asm volatile("fence.mbarrier_init.release.cluster;" ::: "memory");
    }
    __syncwarp();
    asm volatile("barrier.cluster.arrive.relaxed.aligned;" ::: "memory");
    if (threadIdx.x == 256) {
        asm volatile("prefetch.tensormap [%0];" :: "l"(&P.mapCtx[0]) : "memory");
        wait_ctr(CT_CA + mt * 4, 16u);
        OTP(8, 256);
        for (int i = 0; i < 2; i++) {
            mbar_expect_tx(bar_full + 8 * i, 49152);
            tma_load_2d(sbase + i * 49152, &P.mapCtx[0], bar_full + 8 * i, i * 64, cj * SEQ + m0);
        }
        OTP(11, 256);
    }
    if (threadIdx.x == 288) asm volatile("prefetch.tensormap [%0];" :: "l"(&P.mapWo[0]) : "memory");
    __syncwarp();
    asm volatile("barrier.cluster.wait.aligned;" ::: "memory");
    OTP(10, 288);
    if (warp >= 8) {
        if (lane == 0) {
            int s = 0, ready = 1, q = cj * 2, qe = q + 2; uint32_t ph = 0;
            for (int ic = 0;; ic++) {
                if (warp == 8 && rank == 0) {
                    const int t = tnext + nc;
                    asm volatile("st.shared.s32 [%0], %1;" :: "r"(slot + (ic & 7) * 4), "r"(t) : "memory");
                    mbar_arrive(bar_item + 8 * (ic & 7));
                    st_async_b32(mapa_u32(slot + (ic & 7) * 4, 1), (uint32_t)t, mapa_u32(bar_item + 8 * (ic & 7), 1));
                    if (t < 64 + O2_FINE) tnext = take_ticket(CT_OT + pt);
                }
#pragma unroll 1
                for (; q < qe; q++) {
                    const int b = q >> 6, head = (q >> 1) & 31, dk = (q & 1) * 64;
                    mbar_wait(bar_empty + 8 * s, ph ^ 1);
                    const uint32_t sa = sbase + s * 49152;
                    if (warp == 8) {
                        const int f = b ? 4 : head >> 3;
                        if (!((ready >> f) & 1)) {
                            if (b && !(ready & 8)) { wait_ctr(CT_CA + mt * 4 + 3, 16u); ready |= 8; }
                            wait_ctr(b ? CT_CB + mt : CT_CA + mt * 4 + f, b ? 64u : 16u); ready |= 1 << f;
                        }
                        if (ic > 0) {
                            mbar_expect_tx(bar_full + 8 * s, 49152);
                            tma_load_2d(sa, &P.mapCtx[b], bar_full + 8 * s, dk, head * SEQ + m0);
                        }
                    } else {
                        const int j = (int)rank * 2 + (warp - 9);
                        tma_load_2d_mc(sa + 16384 + j * 8192, &P.mapWo[b], bar_full + 8 * s, n0 + j * 64, head * HD + dk, (uint16_t)3);
                    }
                    if (ic == 0 && s == 0) OTP(12, 288);
                    if (++s == O2_STAGES) { s = 0; ph ^= 1; }
                }
                if (warp == 8 && rank == 1) mbar_expect_tx(bar_item + 8 * (ic & 7), 4);
                mbar_wait(bar_item + 8 * (ic & 7), (ic >> 3) & 1);
                int t;
                asm volatile("ld.shared.s32 %0, [%1];" : "=r"(t) : "r"(slot + (ic & 7) * 4) : "memory");
                if (t >= 64 + O2_FINE) break;
                if (t < 64 - O2_FINE) { q = 2 * t; qe = q + 2; } else { q = 64 - O2_FINE + t; qe = q + 1; }
            }
            if (warp == 8) {
                asm volatile("prefetch.tensormap [%0];" :: "l"(&P.mapOut) : "memory");
                if (!(ready & 8)) wait_ctr(CT_CA + mt * 4 + 3, 16u);
                mbar_wait(bar_empty + 8 * s, ph ^ 1);
                asm volatile("st.shared.s32 [%0], %1;" :: "r"(stop + s * 4), "r"(1) : "memory");
                mbar_arrive(bar_full + 8 * s);
                if (atomicAdd(&g_ctr[CT_FIN], 1u) == gridDim.x - 1)
                    for (int i = 0; i < CT_N / 4; i++) reinterpret_cast<uint4*>(g_ctr)[i] = make_uint4(0u, 0u, 0u, 0u);
            }
        }
        __syncwarp();
        asm volatile("barrier.cluster.arrive.relaxed.aligned;" ::: "memory");
    } else {
        const int wg = warp >> 2;
        const bool elected = (threadIdx.x & 127) == 0;
        float acc[128];
#pragma unroll
        for (int i = 0; i < 128; i++) acc[i] = 0.f;
        int s = 0, sprev = 0; uint32_t ph = 0;
#pragma unroll 1
        for (int i = 0;; i++) {
            mbar_wait(bar_full + 8 * s, ph);
            int st;
            asm volatile("ld.shared.s32 %0, [%1];" : "=r"(st) : "r"(stop + s * 4) : "memory");
            if (st) break;
            if (i == 0) OT(1);
            const uint32_t sa = sbase + s * 49152 + wg * 8192, sb = sbase + s * 49152 + 16384;
            wgmma_fence();
#pragma unroll
            for (int kk = 0; kk < 4; kk++)
                wgmma_ss_n256_tb(acc, make_desc(sa + kk * 32, 16, 1024), make_desc(sb + kk * 2048, 8192, 1024), 1);
            wgmma_commit();
            if (i > 0) {
                wgmma_wait<1>();
                if (elected) { const uint32_t e = bar_empty + 8 * sprev; mbar_arrive_cl(mapa_u32(e, 0)); mbar_arrive_cl(mapa_u32(e, 1)); }
            }
            sprev = s;
            if (++s == O2_STAGES) { s = 0; ph ^= 1; }
        }
        asm volatile("barrier.cluster.arrive.relaxed.aligned;" ::: "memory");
        wgmma_wait<0>();
        asm volatile("bar.sync %0, 128;" :: "r"(1 + wg) : "memory");
        OT(3);
        const int row = (lane & 7) + ((lane >> 3) & 1) * 8;
#pragma unroll
        for (int bx = 0; bx < 4; bx++) {
            const uint32_t stg = sbase + bx * 49152 + warp * 2048;
#pragma unroll
            for (int j = 0; j < 8; j += 2) {
                const float* a = &acc[bx * 32 + j * 4];
                stmatrix_x4(stg + row * 128 + (((j + (lane >> 4)) ^ (row & 7)) << 4), pack_bf16(a[0], a[1]), pack_bf16(a[2], a[3]), pack_bf16(a[4], a[5]), pack_bf16(a[6], a[7]));
            }
            asm volatile("fence.proxy.async.shared::cta;" ::: "memory");
            __syncwarp();
            if (lane == 0)
                asm volatile("cp.reduce.async.bulk.tensor.2d.global.shared::cta.add.tile.bulk_group [%0, {%2, %3}], [%1];"
                             :: "l"((uint64_t)&P.mapOut), "r"(stg), "r"(n0 + bx * 64), "r"(m0 + warp * 16) : "memory");
        }
        OT(4);
        if (lane == 0) {
            asm volatile("cp.async.bulk.commit_group;" ::: "memory");
            asm volatile("cp.async.bulk.wait_group.read 0;" ::: "memory");
        }
        __syncwarp();
    }
    asm volatile("barrier.cluster.wait.aligned;" ::: "memory");
    TS_END(4);
}

typedef CUresult (*PFN_encodeTiled)(CUtensorMap*, CUtensorMapDataType, cuuint32_t, void*, const cuuint64_t*,
                                    const cuuint64_t*, const cuuint32_t*, const cuuint32_t*, CUtensorMapInterleave,
                                    CUtensorMapSwizzle, CUtensorMapL2promotion, CUtensorMapFloatOOBfill);
static PFN_encodeTiled g_encode = nullptr;

static void make_map(CUtensorMap* m, const void* ptr, uint64_t rows, uint64_t cols, uint32_t box_rows, bool sw64 = false) {
    cuuint64_t dims[2] = {cols, rows};
    cuuint64_t strides[1] = {cols * 2};
    cuuint32_t box[2] = {sw64 ? 32u : 64u, box_rows};
    cuuint32_t es[2] = {1, 1};
    g_encode(m, CU_TENSOR_MAP_DATA_TYPE_BFLOAT16, 2, const_cast<void*>(ptr), dims, strides, box, es,
             CU_TENSOR_MAP_INTERLEAVE_NONE, sw64 ? CU_TENSOR_MAP_SWIZZLE_64B : CU_TENSOR_MAP_SWIZZLE_128B, CU_TENSOR_MAP_L2_PROMOTION_L2_256B,
             CU_TENSOR_MAP_FLOAT_OOB_FILL_NONE);
}

template <typename... KArgs, typename... Args>
static void launch_pdl(void (*kernel)(KArgs...), int grid, int block, size_t smem, cudaStream_t st, bool pdl, Args... args) {
    cudaLaunchConfig_t cfg = {};
    cfg.gridDim = dim3(grid); cfg.blockDim = dim3(block); cfg.dynamicSmemBytes = smem; cfg.stream = st;
    cudaLaunchAttribute at[1];
    at[0].id = cudaLaunchAttributeProgrammaticStreamSerialization;
    at[0].val.programmaticStreamSerializationAllowed = 1;
    cfg.attrs = at; cfg.numAttrs = pdl ? 1 : 0;
    cudaLaunchKernelEx(&cfg, kernel, KArgs(args)...);
}

extern "C" void kernel_launch(void* const* d_in, const int* in_sizes, int n_in, void* d_out, int out_size) {
    const bf16* x = (const bf16*)d_in[0];
    const bf16* ckv = (const bf16*)d_in[1];
    const bf16* wq = (const bf16*)d_in[2];
    const bf16* wuk = (const bf16*)d_in[3];
    const bf16* wuv = (const bf16*)d_in[4];
    const bf16* wo = (const bf16*)d_in[5];
    const bf16* mem0 = (const bf16*)d_in[7];
    const bf16* Wq = (const bf16*)d_in[8];
    const bf16* Wk = (const bf16*)d_in[9];
    const bf16* Wv = (const bf16*)d_in[10];
    const bf16* Wo = (const bf16*)d_in[11];
    const bf16* gate_w = (const bf16*)d_in[13];
    bf16* out = (bf16*)d_out;

    static Proj2Params P2;
    static ChainParams CP;
    static AttnParams AP;
    static OutParams OP;
    static bool init = false;
    static const void* last_in[14];
    static const void* last_out;
    bool same = init && last_out == d_out;
    for (int i = 0; i < 14 && same; i++) same = last_in[i] == d_in[i];
    if (!init) {
        cudaDriverEntryPointQueryResult qr;
        cudaGetDriverEntryPoint("cuTensorMapEncodeTiled", (void**)&g_encode, cudaEnableDefault, &qr);
        cudaFuncSetAttribute(proj2_kernel, cudaFuncAttributeMaxDynamicSharedMemorySize, P2_SMEM);
        cudaFuncSetAttribute(attn_kernel, cudaFuncAttributeMaxDynamicSharedMemorySize, FA_SMEM);
        cudaFuncSetAttribute(chain_kernel, cudaFuncAttributeMaxDynamicSharedMemorySize, CH_SMEM);
        cudaFuncSetAttribute(out2_kernel, cudaFuncAttributeMaxDynamicSharedMemorySize, O2_SMEM);
        init = true;
    }
    if (!same) {
        for (int i = 0; i < 14; i++) last_in[i] = d_in[i];
        last_out = d_out;
        void *pQA, *pKA, *pVA, *pCA, *pCB;
        cudaGetSymbolAddress(&pQA, g_QA); cudaGetSymbolAddress(&pKA, g_KA); cudaGetSymbolAddress(&pVA, g_VA);
        cudaGetSymbolAddress(&pCA, g_ctxA); cudaGetSymbolAddress(&pCB, g_ctxB);
        make_map(&P2.mapA[0], x, SEQ, DM, 128);
        make_map(&P2.mapA[1], ckv, SEQ, DM, 128);
        const void* ws[3] = {wq, wuk, wuv};
        void* cs[3] = {pQA, pKA, pVA};
        for (int i = 0; i < 3; i++) { make_map(&P2.mapW[i], ws[i], DM, NQ, 64); P2.out[i] = (bf16*)cs[i]; }
        make_map(&CP.mapW[0], Wq, DM, NQ, 64); make_map(&CP.mapW[1], Wk, DM, NQ, 64); make_map(&CP.mapW[2], Wv, DM, NQ, 64);
        make_map(&CP.mapX, x, SEQ, DM, 32);
        make_map(&CP.mapC, pCB, NH * SEQ, HD, 32);
        make_map(&AP.mapQ, pQA, NH * SEQ, HD, 128);
        make_map(&AP.mapK, pKA, NH * SEQ, HD, 128);
        make_map(&AP.mapV, pVA, NH * SEQ, HD, 128);
        make_map(&AP.mapO, pCA, NH * SEQ, HD, 64);
        make_map(&OP.mapCtx[0], pCA, NH * SEQ, HD, 128);
        make_map(&OP.mapCtx[1], pCB, NH * SEQ, HD, 128);
        make_map(&OP.mapWo[0], wo, NQ, DM, 64);
        make_map(&OP.mapWo[1], Wo, NQ, DM, 64);
        make_map(&OP.mapOut, out, SEQ, DM, 16);
        AP.out = out;
    }
    cudaStream_t s1 = cudaStreamPerThread;
    const bool pdl = true;
    launch_pdl(chain_kernel, 64, CH_BLOCK, CH_SMEM, s1, false, CP, mem0, Wo, x, gate_w);
    launch_pdl(proj2_kernel, 68, 384, P2_SMEM, s1, pdl, P2);
    launch_pdl(attn_kernel, FA_GRID, 384, FA_SMEM, s1, pdl, AP, 1000);
    launch_pdl(out2_kernel, O2_GRID, 352, O2_SMEM, s1, pdl, OP);
}
```

```cpp
#include <cuda_runtime.h>
#include <cuda_bf16.h>
#include <cuda.h>
#include <stdint.h>
#include <type_traits>

constexpr int SEQ = 2048;
constexpr int DM = 512;
constexpr int NH = 32;
constexpr int HD = 128;
constexpr int NQ = NH * HD;
constexpr int SEGL = 32;
constexpr int NMEM = 8;
constexpr int NSEG = SEQ / SEGL;

typedef __nv_bfloat16 bf16;

__device__ bf16 g_QA[SEQ * NQ];
__device__ bf16 g_KA[SEQ * NQ];
__device__ bf16 g_VA[SEQ * NQ];
__device__ bf16 g_ctxA[SEQ * NQ];
__device__ bf16 g_ctxB[SEQ * NQ];
constexpr int CT_PROJ = 0, CT_ATTN = 1, CT_FIN = 5;
constexpr int CT_AP = 64;
constexpr int CT_GATE = 96;
constexpr int CT_CA = 128;
constexpr int CT_CB = 192;
constexpr int CT_OT = 208;
constexpr int CT_N = 224;
__device__ __align__(16) unsigned int g_ctr[CT_N];
__device__ float g_gate[SEQ];
__device__ uint32_t g_xbuf[4 * 8 * 2048];

#define FA_GRID 68

#define TS_BEGIN(id)
#define TS_END(id)
#define WAIT_LIMIT 200000
__device__ __forceinline__ void pdl_launch_dependents() { asm volatile("griddepcontrol.launch_dependents;" ::: "memory"); }
__device__ __forceinline__ void wait_ctr(int idx, unsigned int n) {
    unsigned int v; int it = 0;
    do { asm volatile("ld.acquire.gpu.global.u32 %0, [%1];" : "=r"(v) : "l"(&g_ctr[idx]) : "memory"); } while (v < n && ++it < WAIT_LIMIT);
    asm volatile("fence.proxy.async.shared::cta;" ::: "memory");
}
__device__ __forceinline__ int take_ticket(int idx) {
    int v;
    asm volatile("atom.relaxed.gpu.global.inc.u32 %0, [%1], 0x7fffffff;" : "=r"(v) : "l"(&g_ctr[idx]) : "memory");
    return v;
}
__device__ __forceinline__ void signal_ctr(int idx) {
    asm volatile("fence.proxy.async;" ::: "memory");
    __threadfence();
    atomicAdd(&g_ctr[idx], 1u);
}
__device__ __forceinline__ void signal_ctr_generic(int idx) {
    asm volatile("red.release.gpu.global.add.u32 [%0], 1;" :: "l"(&g_ctr[idx]) : "memory");
}
__device__ __forceinline__ uint32_t smem_u32(const void* p) {
    return (uint32_t)__cvta_generic_to_shared(p);
}
__device__ __forceinline__ void mbar_init(uint32_t bar, uint32_t count) {
    asm volatile("mbarrier.init.shared::cta.b64 [%0], %1;" :: "r"(bar), "r"(count));
}
__device__ __forceinline__ void mbar_expect_tx(uint32_t bar, uint32_t bytes) {
    asm volatile("mbarrier.arrive.expect_tx.shared::cta.b64 _, [%0], %1;" :: "r"(bar), "r"(bytes) : "memory");
}
__device__ __forceinline__ void mbar_arrive(uint32_t bar) {
    asm volatile("mbarrier.arrive.shared::cta.b64 _, [%0];" :: "r"(bar) : "memory");
}
__device__ __forceinline__ void mbar_wait(uint32_t bar, uint32_t parity) {
    asm volatile(
        "{\n"
        ".reg .pred p, q;\n"
        ".reg .u32 c;\n"
        "mov.u32 c, 0;\n"
        "WAIT_LOOP:\n"
        "mbarrier.try_wait.parity.shared::cta.b64 p, [%0], %1;\n"
        "@p bra WAIT_DONE;\n"
        "add.u32 c, c, 1;\n"
        "setp.lt.u32 q, c, %2;\n"
        "@q bra WAIT_LOOP;\n"
        "WAIT_DONE:\n"
        "}\n" :: "r"(bar), "r"(parity), "n"(WAIT_LIMIT) : "memory");
}
__device__ __forceinline__ void tma_load_2d(uint32_t dst, const CUtensorMap* map, uint32_t bar, int c0, int c1) {
    asm volatile(
        "cp.async.bulk.tensor.2d.shared::cluster.global.mbarrier::complete_tx::bytes [%0], [%1, {%3, %4}], [%2];"
        :: "r"(dst), "l"((uint64_t)map), "r"(bar), "r"(c0), "r"(c1) : "memory");
}
__device__ __forceinline__ void wgmma_fence() { asm volatile("wgmma.fence.sync.aligned;" ::: "memory"); }
__device__ __forceinline__ void wgmma_commit() { asm volatile("wgmma.commit_group.sync.aligned;" ::: "memory"); }
template <int N> __device__ __forceinline__ void wgmma_wait() {
    asm volatile("wgmma.wait_group.sync.aligned %0;" :: "n"(N) : "memory");
}
__device__ __forceinline__ uint64_t make_desc(uint32_t addr, uint32_t lbo, uint32_t sbo) {
    uint64_t d = 0;
    d |= (uint64_t)((addr & 0x3FFFF) >> 4);
    d |= (uint64_t)((lbo >> 4) & 0x3FFF) << 16;
    d |= (uint64_t)((sbo >> 4) & 0x3FFF) << 32;
    d |= (uint64_t)1 << 62;
    return d;
}

#define ACC64(d) \
    "+f"(d[0]), "+f"(d[1]), "+f"(d[2]), "+f"(d[3]), "+f"(d[4]), "+f"(d[5]), "+f"(d[6]), "+f"(d[7]), \
    "+f"(d[8]), "+f"(d[9]), "+f"(d[10]), "+f"(d[11]), "+f"(d[12]), "+f"(d[13]), "+f"(d[14]), "+f"(d[15]), \
    "+f"(d[16]), "+f"(d[17]), "+f"(d[18]), "+f"(d[19]), "+f"(d[20]), "+f"(d[21]), "+f"(d[22]), "+f"(d[23]), \
    "+f"(d[24]), "+f"(d[25]), "+f"(d[26]), "+f"(d[27]), "+f"(d[28]), "+f"(d[29]), "+f"(d[30]), "+f"(d[31]), \
    "+f"(d[32]), "+f"(d[33]), "+f"(d[34]), "+f"(d[35]), "+f"(d[36]), "+f"(d[37]), "+f"(d[38]), "+f"(d[39]), \
    "+f"(d[40]), "+f"(d[41]), "+f"(d[42]), "+f"(d[43]), "+f"(d[44]), "+f"(d[45]), "+f"(d[46]), "+f"(d[47]), \
    "+f"(d[48]), "+f"(d[49]), "+f"(d[50]), "+f"(d[51]), "+f"(d[52]), "+f"(d[53]), "+f"(d[54]), "+f"(d[55]), \
    "+f"(d[56]), "+f"(d[57]), "+f"(d[58]), "+f"(d[59]), "+f"(d[60]), "+f"(d[61]), "+f"(d[62]), "+f"(d[63])
#define ACC64_STR \
    "{%0, %1, %2, %3, %4, %5, %6, %7, %8, %9, %10, %11, %12, %13, %14, %15, " \
    "%16, %17, %18, %19, %20, %21, %22, %23, %24, %25, %26, %27, %28, %29, %30, %31, " \
    "%32, %33, %34, %35, %36, %37, %38, %39, %40, %41, %42, %43, %44, %45, %46, %47, " \
    "%48, %49, %50, %51, %52, %53, %54, %55, %56, %57, %58, %59, %60, %61, %62, %63}"

template <int TB>
__device__ __forceinline__ void wgmma_ss_n128(float (&d)[64], uint64_t da, uint64_t db, int scale_d) {
    asm volatile(
        "{\n.reg .pred p;\nsetp.ne.b32 p, %66, 0;\n"
        "wgmma.mma_async.sync.aligned.m64n128k16.f32.bf16.bf16 " ACC64_STR ", %64, %65, p, 1, 1, 0, %67;\n}\n"
        : ACC64(d) : "l"(da), "l"(db), "r"(scale_d), "n"(TB));
}
__device__ __forceinline__ uint32_t desc_lo(uint32_t addr, uint32_t lbo) { return ((addr & 0x3FFFF) >> 4) | ((lbo >> 4) << 16); }
template <int TB>
__device__ __forceinline__ void wgmma_ss_n128_lo(float (&d)[64], uint32_t da_lo, uint32_t db_lo, int scale_d) {
    asm volatile(
        "{\n.reg .pred p;\n.reg .b64 da, db;\nsetp.ne.b32 p, %66, 0;\n"
        "mov.b64 da, {%64, 0x40000040};\nmov.b64 db, {%65, 0x40000040};\n"
        "wgmma.mma_async.sync.aligned.m64n128k16.f32.bf16.bf16 " ACC64_STR ", da, db, p, 1, 1, 0, %67;\n}\n"
        : ACC64(d) : "r"(da_lo), "r"(db_lo), "r"(scale_d), "n"(TB));
}
__device__ __forceinline__ void wgmma_rs_n128_tb(float (&d)[64], uint32_t a0, uint32_t a1, uint32_t a2, uint32_t a3,
                                                 uint64_t db, int scale_d) {
    asm volatile(
        "{\n.reg .pred p;\nsetp.ne.b32 p, %69, 0;\n"
        "wgmma.mma_async.sync.aligned.m64n128k16.f32.bf16.bf16 " ACC64_STR ", {%64, %65, %66, %67}, %68, p, 1, 1, 1;\n}\n"
        : ACC64(d) : "r"(a0), "r"(a1), "r"(a2), "r"(a3), "l"(db), "r"(scale_d));
}
__device__ __forceinline__ void wgmma_rs_n80(float (&d)[40], const uint32_t (&a)[4], uint32_t db_lo, int scale_d) {
    asm volatile(
        "{\n.reg .pred p;\n.reg .b64 db;\nsetp.ne.b32 p, %45, 0;\nmov.b64 db, {%44, 0x40000040};\n"
        "wgmma.mma_async.sync.aligned.m64n80k16.f32.bf16.bf16 "
        "{%0, %1, %2, %3, %4, %5, %6, %7, %8, %9, %10, %11, %12, %13, %14, %15, %16, %17, %18, %19, %20, %21, %22, %23, %24, %25, %26, %27, %28, %29, %30, %31, %32, %33, %34, %35, %36, %37, %38, %39}, "
        "{%40, %41, %42, %43}, db, p, 1, 1, 0;\n}\n"
        : "+f"(d[0]), "+f"(d[1]), "+f"(d[2]), "+f"(d[3]), "+f"(d[4]), "+f"(d[5]), "+f"(d[6]), "+f"(d[7]), "+f"(d[8]), "+f"(d[9]), "+f"(d[10]), "+f"(d[11]), "+f"(d[12]), "+f"(d[13]), "+f"(d[14]), "+f"(d[15]), "+f"(d[16]), "+f"(d[17]), "+f"(d[18]), "+f"(d[19]), "+f"(d[20]), "+f"(d[21]), "+f"(d[22]), "+f"(d[23]), "+f"(d[24]), "+f"(d[25]), "+f"(d[26]), "+f"(d[27]), "+f"(d[28]), "+f"(d[29]), "+f"(d[30]), "+f"(d[31]), "+f"(d[32]), "+f"(d[33]), "+f"(d[34]), "+f"(d[35]), "+f"(d[36]), "+f"(d[37]), "+f"(d[38]), "+f"(d[39])
        : "r"(a[0]), "r"(a[1]), "r"(a[2]), "r"(a[3]), "r"(db_lo), "r"(scale_d));
}
__device__ __forceinline__ void wgmma_ss_n256_tb(float (&d)[128], uint64_t da, uint64_t db, int scale_d) {
    asm volatile(
        "{\n.reg .pred p;\nsetp.ne.b32 p, %130, 0;\n"
        "wgmma.mma_async.sync.aligned.m64n256k16.f32.bf16.bf16 {%0, %1, %2, %3, %4, %5, %6, %7, %8, %9, %10, %11, %12, %13, %14, %15, %16, %17, %18, %19, %20, %21, %22, %23, %24, %25, %26, %27, %28, %29, %30, %31, %32, %33, %34, %35, %36, %37, %38, %39, %40, %41, %42, %43, %44, %45, %46, %47, %48, %49, %50, %51, %52, %53, %54, %55, %56, %57, %58, %59, %60, %61, %62, %63, %64, %65, %66, %67, %68, %69, %70, %71, %72, %73, %74, %75, %76, %77, %78, %79, %80, %81, %82, %83, %84, %85, %86, %87, %88, %89, %90, %91, %92, %93, %94, %95, %96, %97, %98, %99, %100, %101, %102, %103, %104, %105, %106, %107, %108, %109, %110, %111, %112, %113, %114, %115, %116, %117, %118, %119, %120, %121, %122, %123, %124, %125, %126, %127}, %128, %129, p, 1, 1, 0, 1;\n}\n"
        : "+f"(d[0]), "+f"(d[1]), "+f"(d[2]), "+f"(d[3]), "+f"(d[4]), "+f"(d[5]), "+f"(d[6]), "+f"(d[7]), "+f"(d[8]), "+f"(d[9]), "+f"(d[10]), "+f"(d[11]), "+f"(d[12]), "+f"(d[13]), "+f"(d[14]), "+f"(d[15]), "+f"(d[16]), "+f"(d[17]), "+f"(d[18]), "+f"(d[19]), "+f"(d[20]), "+f"(d[21]), "+f"(d[22]), "+f"(d[23]), "+f"(d[24]), "+f"(d[25]), "+f"(d[26]), "+f"(d[27]), "+f"(d[28]), "+f"(d[29]), "+f"(d[30]), "+f"(d[31]), "+f"(d[32]), "+f"(d[33]), "+f"(d[34]), "+f"(d[35]), "+f"(d[36]), "+f"(d[37]), "+f"(d[38]), "+f"(d[39]), "+f"(d[40]), "+f"(d[41]), "+f"(d[42]), "+f"(d[43]), "+f"(d[44]), "+f"(d[45]), "+f"(d[46]), "+f"(d[47]), "+f"(d[48]), "+f"(d[49]), "+f"(d[50]), "+f"(d[51]), "+f"(d[52]), "+f"(d[53]), "+f"(d[54]), "+f"(d[55]), "+f"(d[56]), "+f"(d[57]), "+f"(d[58]), "+f"(d[59]), "+f"(d[60]), "+f"(d[61]), "+f"(d[62]), "+f"(d[63]), "+f"(d[64]), "+f"(d[65]), "+f"(d[66]), "+f"(d[67]), "+f"(d[68]), "+f"(d[69]), "+f"(d[70]), "+f"(d[71]), "+f"(d[72]), "+f"(d[73]), "+f"(d[74]), "+f"(d[75]), "+f"(d[76]), "+f"(d[77]), "+f"(d[78]), "+f"(d[79]), "+f"(d[80]), "+f"(d[81]), "+f"(d[82]), "+f"(d[83]), "+f"(d[84]), "+f"(d[85]), "+f"(d[86]), "+f"(d[87]), "+f"(d[88]), "+f"(d[89]), "+f"(d[90]), "+f"(d[91]), "+f"(d[92]), "+f"(d[93]), "+f"(d[94]), "+f"(d[95]), "+f"(d[96]), "+f"(d[97]), "+f"(d[98]), "+f"(d[99]), "+f"(d[100]), "+f"(d[101]), "+f"(d[102]), "+f"(d[103]), "+f"(d[104]), "+f"(d[105]), "+f"(d[106]), "+f"(d[107]), "+f"(d[108]), "+f"(d[109]), "+f"(d[110]), "+f"(d[111]), "+f"(d[112]), "+f"(d[113]), "+f"(d[114]), "+f"(d[115]), "+f"(d[116]), "+f"(d[117]), "+f"(d[118]), "+f"(d[119]), "+f"(d[120]), "+f"(d[121]), "+f"(d[122]), "+f"(d[123]), "+f"(d[124]), "+f"(d[125]), "+f"(d[126]), "+f"(d[127])
        : "l"(da), "l"(db), "r"(scale_d));
}
__device__ __forceinline__ void stmatrix_x4(uint32_t addr, uint32_t r0, uint32_t r1, uint32_t r2, uint32_t r3) {
    asm volatile("stmatrix.sync.aligned.m8n8.x4.shared.b16 [%0], {%1, %2, %3, %4};" :: "r"(addr), "r"(r0), "r"(r1), "r"(r2), "r"(r3) : "memory");
}
__device__ __forceinline__ void tma_store_2d(const CUtensorMap* map, uint32_t src, int c0, int c1) {
    asm volatile("cp.async.bulk.tensor.2d.global.shared::cta.bulk_group [%0, {%2, %3}], [%1];"
                 :: "l"((uint64_t)map), "r"(src), "r"(c0), "r"(c1) : "memory");
}
__device__ __forceinline__ float ex2f(float x) { float y; asm("ex2.approx.ftz.f32 %0, %1;" : "=f"(y) : "f"(x)); return y; }
__device__ __forceinline__ uint32_t pack_bf16(float lo, float hi) {
    __nv_bfloat162 v = __floats2bfloat162_rn(lo, hi);
    return *reinterpret_cast<uint32_t*>(&v);
}
__device__ __forceinline__ void mma_16816(float (&c)[4], uint32_t a0, uint32_t a1, uint32_t a2, uint32_t a3,
                                          uint32_t b0, uint32_t b1) {
    asm volatile(
        "mma.sync.aligned.m16n8k16.row.col.f32.bf16.bf16.f32 {%0,%1,%2,%3}, {%4,%5,%6,%7}, {%8,%9}, {%0,%1,%2,%3};"
        : "+f"(c[0]), "+f"(c[1]), "+f"(c[2]), "+f"(c[3])
        : "r"(a0), "r"(a1), "r"(a2), "r"(a3), "r"(b0), "r"(b1));
}
__device__ __forceinline__ void ldmatrix_x4_trans(uint32_t& r0, uint32_t& r1, uint32_t& r2, uint32_t& r3, uint32_t addr) {
    asm volatile("ldmatrix.sync.aligned.m8n8.x4.trans.shared.b16 {%0,%1,%2,%3}, [%4];"
                 : "=r"(r0), "=r"(r1), "=r"(r2), "=r"(r3) : "r"(addr));
}

struct AttnParams {
    CUtensorMap mapQ, mapK, mapV;
    CUtensorMap mapO;
    bf16* out;
};
constexpr int FA_SMEM = 2 * 32768 + 2 * 65536 + 32768 + 1024 + 256;
constexpr int FA_ITEMS = 16 * NH;
__device__ __forceinline__ int fa_qt(int t) { return 15 - ((t & 127) >> 3); }
__device__ __forceinline__ int fa_head(int t) { return (t >> 7) * 8 + (t & 7); }
#define FA_TKA 2
#define FA_SPLIT 8

#define FAT(b, i)
__device__ __forceinline__ void mbar_arrive_if(uint32_t bar, bool c) {
    asm volatile("{\n.reg .pred p;\nsetp.ne.b32 p, %1, 0;\n@p mbarrier.arrive.shared::cta.b64 _, [%0];\n}" :: "r"(bar), "r"((int)c) : "memory");
}
__device__ __forceinline__ float ex2v(float x) { float y; asm volatile("ex2.approx.ftz.f32 %0, %1;" : "=f"(y) : "f"(x)); return y; }
__device__ __forceinline__ void wgmma_rs_n128_tb_lo(float (&d)[64], const uint32_t* a, uint32_t db_lo, int scale_d) {
    asm volatile(
        "{\n.reg .pred p;\n.reg .b64 db;\nsetp.ne.b32 p, %69, 0;\nmov.b64 db, {%68, 0x40000040};\n"
        "wgmma.mma_async.sync.aligned.m64n128k16.f32.bf16.bf16 " ACC64_STR ", {%64, %65, %66, %67}, db, p, 1, 1, 1;\n}\n"
        : ACC64(d) : "r"(a[0]), "r"(a[1]), "r"(a[2]), "r"(a[3]), "r"(db_lo), "r"(scale_d));
}

__global__ void __launch_bounds__(384, 1) attn_kernel(const __grid_constant__ AttnParams P) {
    extern __shared__ uint8_t smem_raw[];
    uint32_t sbase = (smem_u32(smem_raw) + 1023) & ~1023u;
    const uint32_t sQ = sbase;
    const uint32_t sKV = sbase + 65536;
    const uint32_t sO = sKV + 2 * 65536;
    const uint32_t bars = sO + 32768;
    const uint32_t bar_qf = bars, bar_qe = bars + 16, bar_kf = bars + 32, bar_vf = bars + 48, bar_ke = bars + 64, bar_ve = bars + 80,
                   bar_of = bars + 96, bar_oe = bars + 112, slot = bars + 128, oslot = bars + 136;
    const int warp = threadIdx.x >> 5;
    TS_BEGIN(1);
    if (threadIdx.x == 256) {
        asm volatile("prefetch.tensormap [%0];" :: "l"(&P.mapQ) : "memory");
        asm volatile("prefetch.tensormap [%0];" :: "l"(&P.mapK) : "memory");
        for (int i = 0; i < 2; i++) {
            mbar_init(bar_qf + 8 * i, 1); mbar_init(bar_qe + 8 * i, 8); mbar_init(bar_kf + 8 * i, 1); mbar_init(bar_vf + 8 * i, 1);
            mbar_init(bar_ke + 8 * i, 8); mbar_init(bar_ve + 8 * i, 8); mbar_init(bar_of + 8 * i, 1); mbar_init(bar_oe + 8 * i, 1);
        }
        asm volatile("fence.mbarrier_init.release.cluster;" ::: "memory");
    }
    __syncthreads();
    pdl_launch_dependents();
    if (warp >= 8) {
        asm volatile("setmaxnreg.dec.sync.aligned.u32 40;");
        if (threadIdx.x == 288 || threadIdx.x == 320) {
            const int wg = threadIdx.x == 288 ? 0 : 1;
            const uint32_t stg = sO + wg * 16384;
            for (int n = 0;; n++) {
                mbar_wait(bar_of + 8 * wg, n & 1);
                int t;
                asm volatile("ld.shared.s32 %0, [%1];" : "=r"(t) : "r"(oslot + wg * 4) : "memory");
                const int qt = fa_qt(t), h = fa_head(t & 1023);
                tma_store_2d(&P.mapO, stg, 0, h * SEQ + qt * 128 + wg * 64);
                tma_store_2d(&P.mapO, stg + 8192, 64, h * SEQ + qt * 128 + wg * 64);
                asm volatile("cp.async.bulk.commit_group;" ::: "memory");
                asm volatile("cp.async.bulk.wait_group.read 0;" ::: "memory");
                mbar_arrive(bar_oe + 8 * wg);
                asm volatile("cp.async.bulk.wait_group 0;" ::: "memory");
                signal_ctr(CT_CA + qt * 4 + (h >> 3));
                if (t >= 1024) break;
            }
        }
        if (threadIdx.x == 256) {
            int b = 0, hp_ready = 0, vrow = 0, t = blockIdx.x;
            auto load_v = [&](int i) {
                const uint32_t sv = sKV + (i & 1) * 65536 + 32768, bar = bar_vf + 8 * (i & 1);
                mbar_wait(bar_ve + 8 * (i & 1), ((i >> 1) & 1) ^ 1);
                mbar_expect_tx(bar, 32768);
                tma_load_2d(sv, &P.mapV, bar, 0, vrow);
                tma_load_2d(sv + 16384, &P.mapV, bar, 64, vrow);
            };
            for (int item = 0;; item++) {
                const bool valid = t < FA_ITEMS;
                const int qt = fa_qt(t), h = fa_head(t);
                if (valid && !((hp_ready >> (h >> 1)) & 1)) { wait_ctr(CT_AP + (h >> 1), 96u); hp_ready |= 1 << (h >> 1); }
                const uint32_t bq = bar_qf + 8 * (item & 1);
                mbar_wait(bar_qe + 8 * (item & 1), ((item >> 1) & 1) ^ 1);
                asm volatile("st.shared.s32 [%0], %1;" :: "r"(slot + (item & 1) * 4), "r"(valid ? t : -1) : "memory");
                if (!valid) { mbar_arrive(bq); break; }
                mbar_expect_tx(bq, 32768);
                tma_load_2d(sQ + (item & 1) * 32768, &P.mapQ, bq, 0, h * SEQ + qt * 128);
                tma_load_2d(sQ + (item & 1) * 32768 + 16384, &P.mapQ, bq, 64, h * SEQ + qt * 128);
#pragma unroll 1
                for (int j = 0; j <= qt; j++, b++) {
                    const uint32_t sk = sKV + (b & 1) * 65536, bar = bar_kf + 8 * (b & 1);
                    mbar_wait(bar_ke + 8 * (b & 1), ((b >> 1) & 1) ^ 1);
                    mbar_expect_tx(bar, 32768);
                    tma_load_2d(sk, &P.mapK, bar, 0, h * SEQ + j * 128);
                    tma_load_2d(sk + 16384, &P.mapK, bar, 64, h * SEQ + j * 128);
                    if (j == max(qt - FA_TKA, 0)) t = take_ticket(CT_ATTN);
                    if (b > 0) load_v(b - 1);
                    vrow = h * SEQ + j * 128;
                }
                if (item == 0) wait_ctr(CT_GATE, 64u);
                t += gridDim.x;
            }
            load_v(b - 1);
        }
    } else {
        asm volatile("setmaxnreg.inc.sync.aligned.u32 232;");
        const int wg = warp >> 2;
        const int lane = threadIdx.x & 31;
        const float sc = 0.08838834764831845f * 1.4426950408889634f;
        const int r0 = wg * 64 + (warp & 3) * 16 + (lane >> 2);
        float o[64], s[64];
        uint32_t pa[32];
        float m0, m1, l0 = 0.f, l1 = 0.f, a0, a1, i0 = 0.f, i1 = 0.f;
        const uint32_t q_lo = desc_lo(sQ + wg * 8192, 16), k_lo = desc_lo(sKV, 16), v_lo = desc_lo(sKV + 32768, 16384);
        auto issue_qk = [&](int b, int item) {
            const uint32_t qd = q_lo + (item & 1) * 2048, kd = k_lo + (b & 1) * 4096;
            mbar_wait(bar_kf + 8 * (b & 1), (b >> 1) & 1);
            wgmma_fence();
#pragma unroll
            for (int kk = 0; kk < 8; kk++) wgmma_ss_n128_lo<0>(s, qd + (kk >> 2) * 1024 + (kk & 3) * 2, kd + (kk >> 2) * 1024 + (kk & 3) * 2, kk != 0);
            wgmma_commit();
        };
        auto issue_pv = [&](int b, bool acc) {
            const uint32_t vd = v_lo + (b & 1) * 4096;
            mbar_wait(bar_vf + 8 * (b & 1), (b >> 1) & 1);
            wgmma_fence();
#pragma unroll
            for (int kk = 0; kk < 8; kk++) wgmma_rs_n128_tb_lo(o, &pa[kk * 4], vd + kk * 128, kk ? 1 : (int)acc);
            wgmma_commit();
        };
        auto row_max = [&](bool diag) {
            if (diag) {
                const int lim = r0 - (lane & 3) * 2;
#pragma unroll
                for (int i = 0; i < 64; i++)
                    if ((i >> 2) * 8 + (i & 1) - ((i & 2) ? 8 : 0) > lim) s[i] = -INFINITY;
            }
            float x[8];
#pragma unroll
            for (int i = 0; i < 8; i++) x[i] = fmaxf(s[i * 2], s[i * 2 + 1]);
#pragma unroll
            for (int i = 8; i < 32; i++) x[i & 7] = fmaxf(x[i & 7], fmaxf(s[i * 2], s[i * 2 + 1]));
            float x0 = fmaxf(fmaxf(x[0], x[2]), fmaxf(x[4], x[6])), x1 = fmaxf(fmaxf(x[1], x[3]), fmaxf(x[5], x[7]));
            x0 = fmaxf(x0, __shfl_xor_sync(0xffffffff, x0, 1)); x1 = fmaxf(x1, __shfl_xor_sync(0xffffffff, x1, 1));
            x0 = fmaxf(x0, __shfl_xor_sync(0xffffffff, x0, 2)); x1 = fmaxf(x1, __shfl_xor_sync(0xffffffff, x1, 2));
            x0 = fmaxf(m0, x0 * sc); x1 = fmaxf(m1, x1 * sc);
            a0 = ex2f(m0 - x0); a1 = ex2f(m1 - x1);
            m0 = x0; m1 = x1;
            l0 *= a0; l1 *= a1;
        };
        auto exps = [&](auto g0, auto g1) {
            float u0 = 0.f, u1 = 0.f;
#pragma unroll
            for (int i = decltype(g0)::value; i < decltype(g1)::value; i++) {
                s[i * 4 + 0] = ex2v(fmaf(s[i * 4 + 0], sc, -m0));
                s[i * 4 + 1] = ex2v(fmaf(s[i * 4 + 1], sc, -m0));
                s[i * 4 + 2] = ex2v(fmaf(s[i * 4 + 2], sc, -m1));
                s[i * 4 + 3] = ex2v(fmaf(s[i * 4 + 3], sc, -m1));
                l0 += s[i * 4 + 0]; u0 += s[i * 4 + 1];
                l1 += s[i * 4 + 2]; u1 += s[i * 4 + 3];
            }
            l0 += u0; l1 += u1;
        };
        auto pack_p = [&]() {
#pragma unroll
            for (int i = 0; i < 32; i++) pa[i] = pack_bf16(s[i * 2], s[i * 2 + 1]);
        };
        auto finish_rows = [&](int t) {
            const float g0 = __ldcg(g_gate + fa_qt(t) * 128 + r0), g1 = __ldcg(g_gate + fa_qt(t) * 128 + r0 + 8);
            l0 += __shfl_xor_sync(0xffffffff, l0, 1); l1 += __shfl_xor_sync(0xffffffff, l1, 1);
            l0 += __shfl_xor_sync(0xffffffff, l0, 2); l1 += __shfl_xor_sync(0xffffffff, l1, 2);
            i0 = __fdividef(g0, l0); i1 = __fdividef(g1, l1);
        };
        auto store_o = [&](int t, int n) {
            const uint32_t stg = sO + wg * 16384;
            mbar_wait(bar_oe + 8 * wg, (n & 1) ^ 1);
            const int row = (warp & 3) * 16 + (lane >> 2);
#pragma unroll
            for (int i = 0; i < 4; i++) {
                const int ch = i * 4 + (lane & 3);
                const uint32_t a = stg + (ch >> 3) * 8192 + row * 128 + (((ch & 7) ^ (row & 7)) << 4);
                const float* q = &o[i * 16];
                asm volatile("st.shared.v4.b32 [%0], {%1, %2, %3, %4};" :: "r"(a), "r"(pack_bf16(q[0] * i0, q[1] * i0)), "r"(pack_bf16(q[4] * i0, q[5] * i0)),
                             "r"(pack_bf16(q[8] * i0, q[9] * i0)), "r"(pack_bf16(q[12] * i0, q[13] * i0)) : "memory");
                asm volatile("st.shared.v4.b32 [%0], {%1, %2, %3, %4};" :: "r"(a + 1024), "r"(pack_bf16(q[2] * i1, q[3] * i1)), "r"(pack_bf16(q[6] * i1, q[7] * i1)),
                             "r"(pack_bf16(q[10] * i1, q[11] * i1)), "r"(pack_bf16(q[14] * i1, q[15] * i1)) : "memory");
            }
            if ((t & 1023) >= 384) {
                bf16* z = P.out + (size_t)(fa_qt(t) * 128 + wg * 64 + ((threadIdx.x & 127) >> 3)) * DM + (t & 7) * 64 + (lane & 7) * 8;
#pragma unroll
                for (int i = 0; i < 4; i++) *reinterpret_cast<uint4*>(z + i * 16 * DM) = make_uint4(0u, 0u, 0u, 0u);
            }
            asm volatile("fence.proxy.async.shared::cta;" ::: "memory");
            asm volatile("bar.sync %0, 128;" :: "r"(3 + wg) : "memory");
            if ((threadIdx.x & 127) == 0) {
                asm volatile("st.shared.s32 [%0], %1;" :: "r"(oslot + wg * 4), "r"(t) : "memory");
                mbar_arrive(bar_of + 8 * wg);
            }
            __syncwarp();
        };
        using std::integral_constant;
        int t = blockIdx.x, item = 0, left = fa_qt(t), tdone = -1, b = 1, nout = 0;
        bool first = true;
        if (wg == 1) asm volatile("bar.arrive 1, 256;" ::: "memory");
        mbar_wait(bar_qf, 0);
        asm volatile("bar.sync %0, 256;" :: "r"(1 + wg) : "memory");
        issue_qk(0, 0);
        asm volatile("bar.arrive %0, 256;" :: "r"(2 - wg) : "memory");
        m0 = m1 = -INFINITY;
        wgmma_wait<0>();
        mbar_arrive_if(bar_ke, lane == 0);
        mbar_arrive_if(bar_qe, lane == 0 && left == 0);
        row_max(left == 0);
        exps(integral_constant<int, 0>(), integral_constant<int, 16>());
        pack_p();
#pragma unroll 1
        for (;; b++) {
            const bool fresh = left == 0;
            const int tprev = t;
            if (fresh) {
                item++;
                mbar_wait(bar_qf + 8 * (item & 1), (item >> 1) & 1);
                asm volatile("ld.shared.s32 %0, [%1];" : "=r"(t) : "r"(slot + (item & 1) * 4) : "memory");
                if (t < 0) { t = tprev; break; }
                left = fa_qt(t) + 1;
            }
            left--;
            asm volatile("bar.sync %0, 256;" :: "r"(1 + wg) : "memory");
            FAT(b, 0);
            issue_qk(b, item);
            if (tdone >= 0) {
                asm volatile("bar.arrive %0, 256;" :: "r"(2 - wg) : "memory");
                store_o(tdone, nout++);
            }
            issue_pv(b - 1, !first);
            if (tdone < 0) asm volatile("bar.arrive %0, 256;" :: "r"(2 - wg) : "memory");
            tdone = -1;
            if (fresh) { finish_rows(tprev); tdone = tprev; m0 = m1 = -INFINITY; }
            first = fresh;
            wgmma_wait<1>();
            FAT(b, 1);
            mbar_arrive_if(bar_ke + 8 * (b & 1), lane == 0);
            mbar_arrive_if(bar_qe + 8 * (item & 1), lane == 0 && left == 0);
            row_max(left == 0);
            exps(integral_constant<int, 0>(), integral_constant<int, FA_SPLIT>());
            FAT(b, 2);
            mbar_wait(bar_vf + 8 * ((b - 1) & 1), ((b - 1) >> 1) & 1);
            wgmma_wait<0>();
            FAT(b - 1, 3);
            mbar_arrive_if(bar_ve + 8 * ((b - 1) & 1), lane == 0);
            if (fresh) a0 = a1 = 1.f;
#pragma unroll
            for (int i = 0; i < 16; i++) { o[i * 4 + 0] *= a0; o[i * 4 + 1] *= a0; o[i * 4 + 2] *= a1; o[i * 4 + 3] *= a1; }
            exps(integral_constant<int, FA_SPLIT>(), integral_constant<int, 16>());
            pack_p();
        }
        if (tdone >= 0) store_o(tdone, nout++);
        issue_pv(b - 1, !first);
        finish_rows(t);
        wgmma_wait<0>();
        store_o(t + 1024, nout);
        TS_END(1);
    }
}

__device__ __forceinline__ uint32_t cluster_ctarank() {
    uint32_t r; asm volatile("mov.u32 %0, %%cluster_ctarank;" : "=r"(r)); return r;
}
__device__ __forceinline__ uint32_t mapa_u32(uint32_t addr, uint32_t rank) {
    uint32_t r; asm volatile("mapa.shared::cluster.u32 %0, %1, %2;" : "=r"(r) : "r"(addr), "r"(rank)); return r;
}
__device__ __forceinline__ void cluster_sync_all() {
    asm volatile("barrier.cluster.arrive.release.aligned;\nbarrier.cluster.wait.acquire.aligned;" ::: "memory");
}
__device__ __forceinline__ void st_async_v4(uint32_t addr, uint32_t a, uint32_t b, uint32_t c, uint32_t d, uint32_t mbar) {
    asm volatile("st.async.weak.shared::cluster.mbarrier::complete_tx::bytes.v4.b32 [%0], {%1, %2, %3, %4}, [%5];"
                 :: "r"(addr), "r"(a), "r"(b), "r"(c), "r"(d), "r"(mbar) : "memory");
}
__device__ __forceinline__ void st_async_v2(uint32_t addr, uint32_t a, uint32_t b, uint32_t mbar) {
    asm volatile("st.async.weak.shared::cluster.mbarrier::complete_tx::bytes.v2.b32 [%0], {%1, %2}, [%3];"
                 :: "r"(addr), "r"(a), "r"(b), "r"(mbar) : "memory");
}
__device__ __forceinline__ void st_async_b32(uint32_t addr, uint32_t a, uint32_t mbar) {
    asm volatile("st.async.weak.shared::cluster.mbarrier::complete_tx::bytes.b32 [%0], %1, [%2];" :: "r"(addr), "r"(a), "r"(mbar) : "memory");
}
__device__ __forceinline__ void pace(int cycles) {
    if (cycles > 0) {
        uint32_t t0, t;
        asm volatile("mov.u32 %0, %%clock;" : "=r"(t0));
        do { asm volatile("mov.u32 %0, %%clock;" : "=r"(t)); } while (t - t0 < (uint32_t)cycles);
    }
}
__device__ __forceinline__ void mbar_wait_cl(uint32_t bar, uint32_t parity) {
    uint32_t done = 0;
    for (int it = 0; it < WAIT_LIMIT && !done; it++) {
        asm volatile(
            "{\n.reg .pred p;\n"
            "mbarrier.try_wait.parity.shared::cta.b64 p, [%1], %2;\n"
            "selp.u32 %0, 1, 0, p;\n}\n" : "=r"(done) : "r"(bar), "r"(parity) : "memory");
    }
}
__device__ __forceinline__ uint32_t mbar_test(uint32_t bar, uint32_t parity) {
    uint32_t done;
    asm volatile(
        "{\n.reg .pred p;\n"
        "mbarrier.test_wait.parity.shared::cta.b64 p, [%1], %2;\n"
        "selp.u32 %0, 1, 0, p;\n}\n" : "=r"(done) : "r"(bar), "r"(parity) : "memory");
    return done;
}
__device__ __forceinline__ void ldmatrix_x4(uint32_t& r0, uint32_t& r1, uint32_t& r2, uint32_t& r3, uint32_t addr) {
    asm volatile("ldmatrix.sync.aligned.m8n8.x4.shared.b16 {%0,%1,%2,%3}, [%4];"
                 : "=r"(r0), "=r"(r1), "=r"(r2), "=r"(r3) : "r"(addr));
}
__device__ __forceinline__ void cp_async16(uint32_t dst, const void* src) {
    asm volatile("cp.async.cg.shared.global [%0], [%1], 16;" :: "r"(dst), "l"(src) : "memory");
}
__device__ __forceinline__ float bf16r(float x) { return __uint_as_float(pack_bf16(0.f, x) & 0xffff0000u); }

#define DBG(i, w)
#define DBGD(i, w, dep)
#define DBG_EXTRA 0
__device__ __forceinline__ void tma_load_2d_mc(uint32_t dst, const CUtensorMap* map, uint32_t bar, int c0, int c1, uint16_t mask) {
    asm volatile(
        "cp.async.bulk.tensor.2d.shared::cluster.global.mbarrier::complete_tx::bytes.multicast::cluster [%0], [%1, {%3, %4}], [%2], %5;"
        :: "r"(dst), "l"((uint64_t)map), "r"(bar), "r"(c0), "r"(c1), "h"(mask) : "memory");
}
__device__ __forceinline__ void stmatrix_x4_trans(uint32_t addr, uint32_t r0, uint32_t r1, uint32_t r2, uint32_t r3) {
    asm volatile("stmatrix.sync.aligned.m8n8.x4.trans.shared.b16 [%0], {%1, %2, %3, %4};" :: "r"(addr), "r"(r0), "r"(r1), "r"(r2), "r"(r3) : "memory");
}
__device__ __forceinline__ void stmatrix_x2_trans(uint32_t addr, uint32_t r0, uint32_t r1) {
    asm volatile("stmatrix.sync.aligned.m8n8.x2.trans.shared.b16 [%0], {%1, %2};" :: "r"(addr), "r"(r0), "r"(r1) : "memory");
}
__device__ __forceinline__ uint4 lds128(uint32_t a) {
    uint4 v; asm volatile("ld.shared.v4.u32 {%0, %1, %2, %3}, [%4];" : "=r"(v.x), "=r"(v.y), "=r"(v.z), "=r"(v.w) : "r"(a) : "memory"); return v;
}
__device__ __forceinline__ void sts128(uint32_t a, uint32_t x, uint32_t y, uint32_t z, uint32_t w) {
    asm volatile("st.shared.v4.b32 [%0], {%1, %2, %3, %4};" :: "r"(a), "r"(x), "r"(y), "r"(z), "r"(w) : "memory");
}
__device__ __forceinline__ float2 lds64f(uint32_t a) {
    float2 v; asm volatile("ld.shared.v2.f32 {%0, %1}, [%2];" : "=f"(v.x), "=f"(v.y) : "r"(a) : "memory"); return v;
}
__device__ __forceinline__ void fence_async_smem() { asm volatile("fence.proxy.async.shared::cta;" ::: "memory"); }
#define ACC16(d) "+f"(d[0]), "+f"(d[1]), "+f"(d[2]), "+f"(d[3]), "+f"(d[4]), "+f"(d[5]), "+f"(d[6]), "+f"(d[7]), "+f"(d[8]), "+f"(d[9]), "+f"(d[10]), "+f"(d[11]), "+f"(d[12]), "+f"(d[13]), "+f"(d[14]), "+f"(d[15])
template <int ND>
__device__ __forceinline__ void wgmma_rs_n32(float (&d)[ND], const uint32_t (&a)[4], uint32_t db_lo, int scale_d) {
    asm volatile(
        "{\n.reg .pred p;\n.reg .b64 db;\nsetp.ne.b32 p, %21, 0;\nmov.b64 db, {%20, 0x40000040};\n"
        "wgmma.mma_async.sync.aligned.m64n32k16.f32.bf16.bf16 {%0,%1,%2,%3,%4,%5,%6,%7,%8,%9,%10,%11,%12,%13,%14,%15}, {%16,%17,%18,%19}, db, p, 1, 1, 0;\n}\n"
        : ACC16(d) : "r"(a[0]), "r"(a[1]), "r"(a[2]), "r"(a[3]), "r"(db_lo), "r"(scale_d));
}
template <int ND>
__device__ __forceinline__ void wgmma_ss_n32(float (&d)[ND], uint32_t da_lo, uint32_t db_lo, int scale_d) {
    asm volatile(
        "{\n.reg .pred p;\n.reg .b64 da, db;\nsetp.ne.b32 p, %18, 0;\nmov.b64 da, {%16, 0x40000040};\nmov.b64 db, {%17, 0x40000040};\n"
        "wgmma.mma_async.sync.aligned.m64n32k16.f32.bf16.bf16 {%0,%1,%2,%3,%4,%5,%6,%7,%8,%9,%10,%11,%12,%13,%14,%15}, da, db, p, 1, 1, 1, 0;\n}\n"
        : ACC16(d) : "r"(da_lo), "r"(db_lo), "r"(scale_d));
}
__device__ __forceinline__ void wgmma_ss_n8(float (&d)[4], uint32_t da_lo, uint32_t db_lo, int scale_d) {
    asm volatile(
        "{\n.reg .pred p;\n.reg .b64 da, db;\nsetp.ne.b32 p, %6, 0;\nmov.b64 da, {%4, 0x40000040};\nmov.b64 db, {%5, 0x00000010};\n"
        "wgmma.mma_async.sync.aligned.m64n8k16.f32.bf16.bf16 {%0,%1,%2,%3}, da, db, p, 1, 1, 1, 0;\n}\n"
        : "+f"(d[0]), "+f"(d[1]), "+f"(d[2]), "+f"(d[3]) : "r"(da_lo), "r"(db_lo), "r"(scale_d));
}

#define SCHED_FENCE()
__device__ __forceinline__ void wgmma_ss_n32_p(float (&d)[16], uint32_t da_lo, uint32_t db_lo, int scale_d) {
    asm volatile(
        "{\n.reg .pred p;\n.reg .b64 da, db;\nsetp.ne.b32 p, %18, 0;\nmov.b64 da, {%16, 0x40000040};\nmov.b64 db, {%17, 0x00000030};\n"
        "wgmma.mma_async.sync.aligned.m64n32k16.f32.bf16.bf16 {%0,%1,%2,%3,%4,%5,%6,%7,%8,%9,%10,%11,%12,%13,%14,%15}, da, db, p, 1, 1, 1, 0;\n}\n"
        : ACC16(d) : "r"(da_lo), "r"(db_lo), "r"(scale_d));
}

__device__ __forceinline__ void wgmma_ss_n32_kk(float (&d)[16], uint32_t da_lo, uint32_t db_lo, int scale_d) {
    asm volatile(
        "{\n.reg .pred p;\n.reg .b64 da, db;\nsetp.ne.b32 p, %18, 0;\nmov.b64 da, {%16, 0x40000040};\nmov.b64 db, {%17, 0x40000040};\n"
        "wgmma.mma_async.sync.aligned.m64n32k16.f32.bf16.bf16 {%0,%1,%2,%3,%4,%5,%6,%7,%8,%9,%10,%11,%12,%13,%14,%15}, da, db, p, 1, 1, 0, 0;\n}\n"
        : ACC16(d) : "r"(da_lo), "r"(db_lo), "r"(scale_d));
}

struct ChainParams {
    CUtensorMap mapW[3];
    CUtensorMap mapX;
    CUtensorMap mapC;
};
constexpr int CH_BLOCK = 384;
constexpr int CO_WO = 0;
constexpr int CO_XB = 65536;
constexpr int CO_MB = CO_XB + 65536;
constexpr int CO_OB = CO_MB + 8192;
constexpr int CH_TW = 6144, CH_TP = 3 * CH_TW;
constexpr int CO_T = CO_OB + 8192;
constexpr int CO_SC = CO_T + 2 * CH_TP;
constexpr int CO_LS = CO_SC + 2 * 1280;
constexpr int CO_LO = CO_LS + 8 * 1280;
constexpr int CO_P = CO_LO + 4 * 1280;
constexpr int CO_ST = 205824;
#define CH_NSM 3
constexpr int CO_WA = CO_ST + 4096;
constexpr int CO_BAR = CO_WA + CH_TP;
constexpr int CH_SMEM = CO_BAR + 256 + 1024 + DBG_EXTRA;
static_assert(CO_WA >= 3 * 65536 && CO_P + 3072 <= CO_ST && CH_NSM <= 3, "smem layout");
#define CH_POLL_DELAY 0
#define CH_PEARLY 0
#define CH_VPOS 2
#define CH_VST 0
#define CH_V3_DELAY 0
#define CH_LSPOS 1
#define CH_V1 0
#define CH_V2 24
#define CH_V3 32
#define CH_OG 2
#define CH_OW 8
#define CH_OF 12
#define CH_CHAINS 4

constexpr float CH_SC = 0.08838834764831845f * 1.4426950408889634f;
__device__ __forceinline__ uint32_t pin(uint32_t v) { return __shfl_sync(0xffffffff, v, threadIdx.x & 31); }

__global__ void __cluster_dims__(8, 1, 1) __launch_bounds__(CH_BLOCK, 1)
chain_kernel(const __grid_constant__ ChainParams P, const bf16* __restrict__ mem0, const bf16* __restrict__ Wo, const bf16* __restrict__ x,
             const bf16* __restrict__ gate_w) {
    extern __shared__ uint8_t smem_raw[];
    const uint32_t sb = (smem_u32(smem_raw) + 1023) & ~1023u;
    const int tid = threadIdx.x, warp = __shfl_sync(0xffffffff, tid >> 5, 0), lane = tid & 31;
    const int rank = (int)cluster_ctarank();
    const int C = blockIdx.x >> 3;
    const int h = C * 4 + (rank >> 1);
    const int qd = lane >> 2, qc = lane & 3;
    const int t4 = warp & 3, wg = warp >> 2;
    pdl_launch_dependents();
    TS_BEGIN(2);
    const uint32_t bar_mem = sb + CO_BAR, bar_o = bar_mem + 32, bar_sc = bar_o + 32, bar_x = bar_sc + 8, bar_l = bar_x + 16, bar_w = bar_l + 8;
    if (tid == 0) {
        for (int j = 0; j < 15; j++) mbar_init(bar_mem + 8 * j, bar_mem + 8 * j == bar_l ? 4 : 1);
        asm volatile("fence.mbarrier_init.release.cluster;" ::: "memory");
    }
    __syncthreads();
    if ((tid & 127) == 0) {
        mbar_expect_tx(bar_w + 8 * wg, 65536);
        for (int i = 0; i < 8; i++)
            tma_load_2d(sb + wg * 65536 + i * 8192, &P.mapW[wg], bar_w + 8 * wg, h * HD + (rank & 1) * 64, i * 64);
    }
    {
        for (int i = tid; i < 512; i += CH_BLOCK) asm volatile("prefetch.global.L2 [%0];" :: "l"(Wo + (size_t)(C * 512 + i) * DM + rank * 64));
        if (tid < 64) asm volatile("prefetch.global.L2 [%0];" :: "l"(x + (size_t)tid * DM + rank * 64));
    }
    if (tid < 256) {
        const int r = blockIdx.x * 32 + (tid >> 3);
        float sum = 0.f;
#pragma unroll
        for (int c = 0; c < 8; c++) {
            const int col = c * 64 + (tid & 7) * 8;
            const uint4 xv = __ldg(reinterpret_cast<const uint4*>(x + (size_t)r * DM + col));
            const uint4 gv = __ldg(reinterpret_cast<const uint4*>(gate_w + col));
            const bf16* xp = reinterpret_cast<const bf16*>(&xv);
            const bf16* gp = reinterpret_cast<const bf16*>(&gv);
#pragma unroll
            for (int e = 0; e < 8; e++) sum += bf16r(__bfloat162float(xp[e]) * __bfloat162float(gp[e]));
        }
        sum += __shfl_xor_sync(0xffffffff, sum, 1);
        sum += __shfl_xor_sync(0xffffffff, sum, 2);
        sum += __shfl_xor_sync(0xffffffff, sum, 4);
        if ((tid & 7) == 0) g_gate[r] = bf16r(1.f / (1.f + __expf(-bf16r(sum))));
        asm volatile("bar.sync 1, 256;" ::: "memory");
        if (tid == 32) signal_ctr_generic(CT_GATE);
    }
    auto chunk = [&](int i) { return (uint32_t)((rank - (i >> 1) - 4 * (i & 1)) & 7); };
    const uint32_t wfrag = (((lane >> 4) << 3) + (lane & 7)) * 128 + (((t4 * 2 + ((lane >> 3) & 1)) ^ (lane & 7)) << 4);
    const uint32_t aO = pin(sb + wg * CH_TW + wfrag);
    const uint32_t aM = pin(sb + (lane & 7) * 128 + (((lane >> 3) ^ (lane & 7)) << 4));
    const uint32_t aL = pin(sb + lane * 8);
    uint32_t w[32][4];
    float d[16];
    mbar_wait(bar_w + 8 * wg, 0);
#pragma unroll
    for (int e = CH_NSM; e < 32; e++) ldmatrix_x4_trans(w[e][0], w[e][1], w[e][2], w[e][3], sb + wg * 65536 + wfrag + chunk(e >> 2) * 8192 + (e & 3) * 2048);
#pragma unroll
    for (int e = 0; e < CH_NSM; e++) {
        const uint4 u = lds128(sb + wg * 65536 + chunk(0) * 8192 + e * 2048 + (tid & 127) * 16);
        sts128(sb + CO_WA + wg * CH_TW + e * 2048 + (tid & 127) * 16, u.x, u.y, u.z, u.w);
    }
    fence_async_smem();
    __syncthreads();
    if (tid == 0) {
        fence_async_smem();
        for (int b = 0; b < 2; b++) {
            mbar_expect_tx(bar_x + 8 * b, 32768);
            for (int i = 0; i < 8; i++) tma_load_2d(sb + CO_XB + b * 32768 + i * 4096, &P.mapX, bar_x + 8 * b, i * 64, b * SEGL);
        }
    }
#pragma unroll 2
    for (int i = tid; i < 512 * 4; i += CH_BLOCK) {
        const int r = i >> 2, cg = i & 3, ks = r >> 4, kp = r & 15;
        const int src = (rank - (ks >> 2)) & 7;
        const uint4* p = reinterpret_cast<const uint4*>(Wo + (size_t)(C * 512 + src * 64 + (ks & 3) * 16 + (kp >> 2) * 2 + (kp & 1) + (kp & 2) * 4) * DM + rank * 64 + cg * 16);
        const uint4 u0 = __ldg(p), u1 = __ldg(p + 1);
        const uint32_t a = sb + CO_WO + r * 128;
        sts128(a + (((cg * 2) ^ (r & 7)) << 4), __byte_perm(u0.x, u0.y, 0x5410), __byte_perm(u0.z, u0.w, 0x5410), __byte_perm(u1.x, u1.y, 0x5410), __byte_perm(u1.z, u1.w, 0x5410));
        sts128(a + (((cg * 2 + 1) ^ (r & 7)) << 4), __byte_perm(u0.x, u0.y, 0x7632), __byte_perm(u0.z, u0.w, 0x7632), __byte_perm(u1.x, u1.y, 0x7632), __byte_perm(u1.z, u1.w, 0x7632));
    }
#pragma unroll 1
    for (int i = tid; i < 512; i += CH_BLOCK) {
        const int n = i >> 6, c = i & 63;
        const uint4 u = __ldg(reinterpret_cast<const uint4*>(mem0 + n * DM + chunk(c >> 3) * 64 + (c & 7) * 8));
        sts128(sb + CO_MB + (c >> 3) * 1024 + n * 128 + (((c & 7) ^ n) << 4), u.x, u.y, u.z, u.w);
    }
    if (tid < 128) sts128(sb + CO_T + (tid >> 6) * CH_TP + 2 * CH_TW + 5120 + (tid & 63) * 16, 0u, 0u, 0u, 0u);
    else if (tid < 160) sts128(sb + CO_P + ((tid >> 3) & 3) * 768 + 640 + (tid & 7) * 16, 0u, 0u, 0u, 0u);
    fence_async_smem();
    TS_END(6);
    auto pass32 = [&](int b, int e0 = 0, int e1 = 32) {
        const uint32_t lo = desc_lo(sb + CO_XB + b * 32768, 16);
        wgmma_fence();
#pragma unroll
        for (int e = 0; e < 32; e++) if (e >= e0 && e < e1) {
            const uint32_t db = lo + chunk(e >> 2) * 256 + (e & 3) * 2;
            if (e < CH_NSM) wgmma_ss_n32(d, desc_lo(sb + CO_WA + wg * CH_TW + e * 2048, 16), db, e != 0);
            else wgmma_rs_n32(d, w[e], db, e != 0);
        }
        wgmma_commit();
    };
    auto store32 = [&](uint32_t a) {
        stmatrix_x4_trans(a, pack_bf16(d[0], d[1]), pack_bf16(d[2], d[3]), pack_bf16(d[4], d[5]), pack_bf16(d[6], d[7]));
        stmatrix_x4_trans(a + 2048, pack_bf16(d[8], d[9]), pack_bf16(d[10], d[11]), pack_bf16(d[12], d[13]), pack_bf16(d[14], d[15]));
    };
    auto mem_proj = [&](int s, bool wait, bool arrive = false) {
        const uint32_t par = s & 1;
        float acc[CH_CHAINS][4];
#pragma unroll
        for (int i = 0; i < CH_CHAINS; i++) acc[i][0] = acc[i][1] = acc[i][2] = acc[i][3] = 0.f;
        const uint32_t aM2 = aM ^ 64;
        uint32_t b[2][8];
        auto load = [&](int c) {
            if (wait && !(c & 1)) mbar_wait_cl(bar_mem + 4 * c, par ^ 1);
            if (c == 0) DBG(11, 0);
            if (c == 6) DBG(13, 0);
            ldmatrix_x4(b[c & 1][0], b[c & 1][1], b[c & 1][2], b[c & 1][3], aM + CO_MB + c * 1024);
            ldmatrix_x4(b[c & 1][4], b[c & 1][5], b[c & 1][6], b[c & 1][7], aM2 + CO_MB + c * 1024);
        };
        load(0);
#pragma unroll
        for (int c = 0; c < 8; c++) {
            if (c < 7) load(c + 1);
            SCHED_FENCE();
#pragma unroll
            for (int i = 0; i < 4; i++) {
                const int e = c * 4 + i;
                mma_16816(acc[i % CH_CHAINS], w[e][0], w[e][1], w[e][2], w[e][3], b[c & 1][i * 2], b[c & 1][i * 2 + 1]);
            }
        }
        if (CH_CHAINS == 4) {
#pragma unroll
            for (int i = 0; i < 4; i++) { acc[0][i] += acc[2 % CH_CHAINS][i]; acc[1][i] += acc[3 % CH_CHAINS][i]; }
        }
        const uint32_t r0 = pack_bf16(acc[0][0] + acc[1][0], acc[0][1] + acc[1][1]);
        const uint32_t r1 = pack_bf16(acc[0][2] + acc[1][2], acc[0][3] + acc[1][3]);
        DBGD(40 + warp, warp, r0 ^ r1);
        stmatrix_x2_trans(aO + par * CH_TP + CO_T + 4096, r0, r1);
    };
    auto load_wa = [&]() {
#pragma unroll
        for (int e = 0; e < CH_NSM; e++) ldmatrix_x4_trans(w[e][0], w[e][1], w[e][2], w[e][3], aO + CO_WA + e * 2048);
    };
    auto remote = [](uint32_t a, uint32_t r) { return mapa_u32(a, r); };
    mbar_wait(bar_x, 0);
    pass32(0);
    wgmma_wait<0>();
    store32(aO + CO_T);
    fence_async_smem();
    __syncthreads();
    cluster_sync_all();
    TS_BEGIN(5);

    if (wg < 2) {
        const uint32_t aQ = pin(sb + CO_T + qd * 128 + (((2 * qc) ^ qd) << 4));
        auto local_scores = [&](int s) {
            const uint32_t tb = sb + CO_T + (s & 1) * CH_TP;
            wgmma_fence();
#pragma unroll
            for (int ks = 0; ks < 4; ks++) wgmma_ss_n32_kk(d, desc_lo(tb + CH_TW, 16) + ks * 2, desc_lo(tb, 16) + ks * 2, ks != 0);
            wgmma_commit();
            wgmma_wait<0>();
            const uint32_t rb = remote(bar_l, rank ^ 1);
            if (t4 < 2) {
                const uint32_t off = 2 * aL - sb + t4 * 512;
#pragma unroll
                for (int j = 0; j < 4; j++) if (j >= 2 || t4 == 0) {
                    st_async_v4(remote(off + (s & 1) * 5120 + CO_LS + j * 1280, rank ^ 1), __float_as_uint(d[4 * j]), __float_as_uint(d[4 * j + 1]), __float_as_uint(d[4 * j + 2]), __float_as_uint(d[4 * j + 3]), rb);
                    sts128(off + CO_LO + j * 1280, __float_as_uint(d[4 * j]), __float_as_uint(d[4 * j + 1]), __float_as_uint(d[4 * j + 2]), __float_as_uint(d[4 * j + 3]));
                }
            } else if (t4 == 2) {
#pragma unroll
                for (int j = 0; j < 4; j++) {
                    st_async_v2(remote(aL + (s & 1) * 5120 + CO_LS + 1024 + j * 1280, rank ^ 1), __float_as_uint(d[4 * j]), __float_as_uint(d[4 * j + 1]), rb);
                    asm volatile("st.shared.v2.f32 [%0], {%1, %2};" :: "r"(aL + CO_LO + 1024 + j * 1280), "f"(d[4 * j]), "f"(d[4 * j + 1]) : "memory");
                }
            }
            __syncwarp();
            if (t4 < 3 && lane == 0) mbar_arrive(bar_l);
            DBG(6, 4);
        };
        auto local_pv = [&](int s, bool arrive) {
            wgmma_fence();
#pragma unroll
            for (int ks = 0; ks < 3; ks++)
                wgmma_ss_n32_p(d, desc_lo(sb + CO_T + (s & 1) * CH_TP + 2 * CH_TW + ks * 2048, 16), desc_lo(sb + CO_P + ks * 256, 128), ks != 0);
            wgmma_commit();
            wgmma_wait<0>();
            if (arrive) asm volatile("bar.arrive 9, 256;" ::: "memory");
            store32(aO + CO_ST);
            fence_async_smem();
            if (!arrive) asm volatile("bar.sync 5, 128;" ::: "memory");
        };
        auto store_ctx = [&](int s) {
            tma_store_2d(&P.mapC, sb + CO_ST, (rank & 1) * 64, h * SEQ + s * SEGL);
            asm volatile("cp.async.bulk.commit_group;" ::: "memory");
        };
        auto signal_ctx = [&](int m0, int m1) {
            asm volatile("fence.proxy.async;" ::: "memory");
            __threadfence();
            for (int m = m0; m < m1; m++) asm volatile("red.relaxed.gpu.global.add.u32 [%0], 1;" :: "l"(&g_ctr[CT_CB + m]) : "memory");
        };
#pragma unroll 1
        for (int s = 0; s < NSEG; s++) {
            const uint32_t par = s & 1;
            load_wa();
            mem_proj(s, s > 0);
            if (s == NSEG - 1) break;
            if (warp < 5) {
                const uint32_t qa_ = aQ + par * CH_TP, ka = qa_ + warp * 1024;
                asm volatile("bar.sync 1, 256;" ::: "memory");
                const uint4 qa = lds128(qa_ + 4096), k0 = lds128(ka + CH_TW), qb = lds128((qa_ ^ 16) + 4096), k1 = lds128((ka ^ 16) + CH_TW);
                DBGD(52 + warp, warp, qa.x ^ qb.x);
                float c[4] = {0.f, 0.f, 0.f, 0.f}, c2[4] = {0.f, 0.f, 0.f, 0.f};
                mma_16816(c, qa.x, 0u, qa.y, 0u, k0.x, k0.y);
                mma_16816(c2, qb.x, 0u, qb.y, 0u, k1.x, k1.y);
                mma_16816(c, qa.z, 0u, qa.w, 0u, k0.z, k0.w);
                mma_16816(c2, qb.z, 0u, qb.w, 0u, k1.z, k1.w);
                c[0] += c2[0]; c[1] += c2[1];
                DBGD(57 + warp, warp, __float_as_uint(c[0]));
                const uint32_t off = aL + CO_SC + warp * 256;
                st_async_v2(remote(off + 1280, rank ^ 1), __float_as_uint(c[0]), __float_as_uint(c[1]), remote(bar_sc, rank ^ 1));
                st_async_v2(off, __float_as_uint(c[0]), __float_as_uint(c[1]), bar_sc);
                asm volatile("bar.arrive 2, 288;" ::: "memory");
                DBG(3, 0);
            } else {
                asm volatile("bar.arrive 1, 256;" ::: "memory");
            }
            if (wg == 0) {
                if (tid == 96) {
                    mbar_expect_tx(bar_sc, 2 * 1280);
#pragma unroll
                    for (int j = 0; j < 4; j++) { mbar_expect_tx(bar_mem + 8 * j, 2048); if (j < CH_OG) mbar_expect_tx(bar_o + 8 * j, 8192 / CH_OG); }
                    if (s > 0) mbar_wait(bar_l, par ^ 1);
                    mbar_expect_tx(bar_l, 4096);
                }
                if (tid == 96 && s > 1) {
                    if (s == 34 || s == 50 || s == 58 || s == 62) {
                        asm volatile("cp.async.bulk.wait_group 0;" ::: "memory");
                        signal_ctx(s == 34 ? 0 : (2 * s - 68) >> 2, s >> 2);
                    }
                    store_ctx(s - 2);
                    asm volatile("cp.async.bulk.wait_group.read 0;" ::: "memory");
                }
                __syncwarp();
                mbar_wait(bar_x + 8 * (par ^ 1), ((s + 1) >> 1) & 1);
                asm volatile("bar.sync 5, 128;" ::: "memory");
                float c[4];
                const uint32_t alo = desc_lo(sb + CO_WO, 16), blo = desc_lo(sb + CO_OB, 128);
                uint32_t* wp = g_xbuf + (size_t)rank * 2048 + C * 256 + qc * 64 + t4 * 8 + qd;
                mbar_wait_cl(bar_o, par);
                DBG(16, 0);
                fence_async_smem();
                wgmma_fence();
#pragma unroll
                for (int i = 0; i < 32; i++) {
                    wgmma_ss_n8(c, alo + i * 128, blo + i * 16, i != 0);
                    if (CH_OG == 2 && i == CH_OW) mbar_wait_cl(bar_o + 8, par);
                    if (CH_OG == 2 && i == CH_OF) fence_async_smem();
                }
                wgmma_commit();
                wgmma_wait<0>();
                asm volatile("st.relaxed.gpu.global.u32 [%0], %1;" :: "l"(wp + (s & 3) * 16384), "r"(~pack_bf16(c[0], c[2])) : "memory");
                asm volatile("st.relaxed.gpu.global.u32 [%0], %1;" :: "l"(wp + (s & 3) * 16384 + 32), "r"(~pack_bf16(c[1], c[3])) : "memory");
                asm volatile("bar.arrive 4, 256;" ::: "memory");
                asm volatile("bar.arrive 6, 256;" ::: "memory");
                DBG(8, 0);
                if (s > 0) local_pv(s - 1, true); else asm volatile("bar.arrive 9, 256;" ::: "memory");
                DBG(28, 0);
                asm volatile("st.relaxed.gpu.global.u32 [%0], %1;" :: "l"(wp + ((s + 2) & 3) * 16384), "r"(0) : "memory");
                asm volatile("st.relaxed.gpu.global.u32 [%0], %1;" :: "l"(wp + ((s + 2) & 3) * 16384 + 32), "r"(0) : "memory");
                if (tid == 0 && s + 2 < NSEG) {
                    mbar_expect_tx(bar_x + 8 * par, 32768);
                    tma_load_2d_mc(sb + CO_XB + par * 32768 + rank * 4096, &P.mapX, bar_x + 8 * par, rank * 64, (s + 2) * SEGL, (uint16_t)0xff);
                }
                __syncwarp();
            } else {
                const uint32_t vaddr = pin(sb + CO_T + par * CH_TP + 2 * CH_TW + (lane & 15) * 128 + (((t4 * 2 + (lane >> 4)) ^ (lane & 7)) << 4));
                const uint32_t dsta = pin(sb + CO_OB + t4 * 256 + (qc >> 1) * 128 + qd * 16 + (qc & 1) * 8);
                fence_async_smem();
                uint32_t vb[3][4];
                auto load_v = [&]() {
                    asm volatile("bar.sync 3, 256;" ::: "memory");
#pragma unroll
                    for (int k = 0; k < 3; k++) ldmatrix_x4_trans(vb[k][0], vb[k][1], vb[k][2], vb[k][3], vaddr + k * 2048);
                };
                if (CH_VPOS == 0) load_v();
                mbar_wait_cl(bar_sc, par);
                DBG(4, 4);
                float v[10];
#pragma unroll
                for (int j = 0; j < 5; j++) {
                    const float2 a = lds64f(aL + CO_SC + j * 256), b = lds64f(aL + CO_SC + 1280 + j * 256);
                    v[2 * j] = a.x + b.x; v[2 * j + 1] = a.y + b.y;
                }
                if (CH_VPOS == 1) load_v();
                float mx = fmaxf(fmaxf(fmaxf(v[0], v[1]), fmaxf(v[2], v[3])), fmaxf(fmaxf(v[4], v[5]), fmaxf(v[6], v[7])));
                mx = fmaxf(mx, fmaxf(v[8], v[9]));
                mx = fmaxf(mx, __shfl_xor_sync(0xffffffff, mx, 1));
                mx = fmaxf(mx, __shfl_xor_sync(0xffffffff, mx, 2));
                if (CH_VPOS == 2) load_v();
                DBG(19, 4);
                mx *= CH_SC;
#pragma unroll
                for (int j = 0; j < 10; j++) v[j] = ex2f(fmaf(v[j], CH_SC, -mx));
                float c0[4] = {0.f, 0.f, 0.f, 0.f}, c1[4] = {0.f, 0.f, 0.f, 0.f}, cs[4] = {0.f, 0.f, 0.f, 0.f};
#pragma unroll
                for (int k = 0; k < 3; k++) {
                    const uint32_t p0 = pack_bf16(v[4 * k], v[4 * k + 1]), p1 = k < 2 ? pack_bf16(v[4 * k + 2], v[4 * k + 3]) : 0u;
                    mma_16816(cs, p0, 0u, p1, 0u, 0x3f803f80u, 0x3f803f80u);
                    mma_16816(c0, p0, 0u, p1, 0u, vb[k][0], vb[k][1]);
                    mma_16816(c1, p0, 0u, p1, 0u, vb[k][2], vb[k][3]);
                }
                float inv;
                asm volatile("rcp.approx.ftz.f32 %0, %1;" : "=f"(inv) : "f"(cs[0]));
                const uint32_t b0 = pack_bf16(c0[0] * inv, c0[1] * inv), b1 = pack_bf16(c1[0] * inv, c1[1] * inv);
                DBG(20, 4);
#pragma unroll
                for (int i = 0; i < 8; i++) {
                    const int dr = (rank + i) & 7;
                    st_async_v2(remote(dsta + i * 1024, dr), b0, b1, remote(bar_o + 8 * (i * CH_OG / 8), dr));
                    if (i == 0) asm volatile("bar.arrive 7, 256;" ::: "memory");
                }
                DBG(5, 4);
                mbar_wait(bar_x + 8 * (par ^ 1), ((s + 1) >> 1) & 1);
                asm volatile("bar.sync 4, 256;" ::: "memory");
                if (CH_LSPOS == 0) local_scores(s);
            }
            pass32(par ^ 1);
            DBG(21, 0);
            wgmma_wait<0>();
            store32(aO + (par ^ 1) * CH_TP + CO_T);
            if (wg == 0) fence_async_smem();
            DBG(22, 0);
            DBG(29, 4);
            if (CH_LSPOS == 1 && wg == 1) local_scores(s);
        }
        fence_async_smem();
        asm volatile("bar.sync 1, 256;" ::: "memory");
        if (warp < 5) asm volatile("bar.arrive 2, 288;" ::: "memory");
        if (wg == 0) {
            if (tid == 96) { mbar_wait(bar_l, 0); mbar_expect_tx(bar_l, 4096); store_ctx(NSEG - 3); asm volatile("cp.async.bulk.wait_group.read 0;" ::: "memory"); }
            __syncwarp();
            asm volatile("bar.sync 7, 256;" ::: "memory");
            local_pv(NSEG - 2, false);
            asm volatile("bar.arrive 6, 256;" ::: "memory");
            if (tid == 96) { store_ctx(NSEG - 2); asm volatile("cp.async.bulk.wait_group.read 0;" ::: "memory"); }
            __syncwarp();
            asm volatile("bar.sync 8, 256;" ::: "memory");
            local_pv(NSEG - 1, false);
            if (tid == 96) {
                store_ctx(NSEG - 1);
                asm volatile("cp.async.bulk.wait_group 0;" ::: "memory");
                signal_ctx(15, 16);
            }
            uint32_t* wp = g_xbuf + 16384 + (size_t)rank * 2048 + C * 256 + tid * 2;
            *reinterpret_cast<uint2*>(wp) = make_uint2(0u, 0u);
        } else {
            asm volatile("bar.sync 3, 256;" ::: "memory");
            asm volatile("bar.arrive 7, 256;" ::: "memory");
            local_scores(NSEG - 1);
        }
    } else {
        auto local_softmax = [&](int s) {
            float v[10];
            const float2 g = __ldcg(reinterpret_cast<const float2*>(g_gate + s * SEGL + t4 * 8 + 2 * qc));
            mbar_wait_cl(bar_l, s & 1);
            const uint32_t off = 2 * aL - sb + t4 * 1280;
            {
                const uint4 a0 = lds128(off + (s & 1) * 5120 + CO_LS), b0 = lds128(off + CO_LO), a1 = lds128(off + (s & 1) * 5120 + CO_LS + 512), b1 = lds128(off + CO_LO + 512);
                const float2 a2 = lds64f(aL + t4 * 1280 + (s & 1) * 5120 + CO_LS + 1024), b2 = lds64f(aL + t4 * 1280 + CO_LO + 1024);
                auto f = [](uint32_t a, uint32_t b) { return __uint_as_float(a) + __uint_as_float(b); };
                v[0] = f(a0.x, b0.x); v[1] = f(a0.y, b0.y); v[2] = f(a0.z, b0.z); v[3] = f(a0.w, b0.w);
                v[4] = f(a1.x, b1.x); v[5] = f(a1.y, b1.y); v[6] = f(a1.z, b1.z); v[7] = f(a1.w, b1.w);
                v[8] = a2.x + b2.x; v[9] = a2.y + b2.y;
            }
            const int lim = t4 * 8 + 2 * qc - qd;
#pragma unroll
            for (int n = 0; n < 4; n++) {
                if (8 * n > lim) v[2 * n] = -INFINITY;
                if (8 * n > lim + 1) v[2 * n + 1] = -INFINITY;
            }
            float m0 = fmaxf(fmaxf(fmaxf(v[0], v[2]), fmaxf(v[4], v[6])), v[8]), m1 = fmaxf(fmaxf(fmaxf(v[1], v[3]), fmaxf(v[5], v[7])), v[9]);
#pragma unroll
            for (int o = 4; o < 32; o *= 2) { m0 = fmaxf(m0, __shfl_xor_sync(0xffffffff, m0, o)); m1 = fmaxf(m1, __shfl_xor_sync(0xffffffff, m1, o)); }
            m0 *= CH_SC; m1 *= CH_SC;
#pragma unroll
            for (int n = 0; n < 5; n++) { v[2 * n] = ex2f(fmaf(v[2 * n], CH_SC, -m0)); v[2 * n + 1] = ex2f(fmaf(v[2 * n + 1], CH_SC, -m1)); }
            float s0 = ((v[0] + v[2]) + (v[4] + v[6])) + v[8], s1 = ((v[1] + v[3]) + (v[5] + v[7])) + v[9];
#pragma unroll
            for (int o = 4; o < 32; o *= 2) { s0 += __shfl_xor_sync(0xffffffff, s0, o); s1 += __shfl_xor_sync(0xffffffff, s1, o); }
            asm("rcp.approx.ftz.f32 %0, %0;" : "+f"(s0));
            asm("rcp.approx.ftz.f32 %0, %0;" : "+f"(s1));
            s0 *= 1.f - g.x; s1 *= 1.f - g.y;
            const uint32_t pa = 2 * aL - sb + CO_P + t4 * 768;
            stmatrix_x4_trans(pa, pack_bf16(v[0] * s0, v[1] * s1), pack_bf16(v[2] * s0, v[3] * s1), pack_bf16(v[4] * s0, v[5] * s1), pack_bf16(v[6] * s0, v[7] * s1));
            asm volatile("stmatrix.sync.aligned.m8n8.x1.trans.shared.b16 [%0], {%1};" :: "r"(pa + 512), "r"(pack_bf16(v[8] * s0, v[9] * s1)) : "memory");
            fence_async_smem();
            DBG(7, 8);
        };
        wait_ctr(CT_GATE, 64u);
#pragma unroll 1
        for (int s = 0; s < NSEG; s++) {
            const uint32_t par = s & 1;
            if (s > 0) local_softmax(s - 1);
            load_wa();
            if (s < NSEG - 1) mbar_wait(bar_x + 8 * (par ^ 1), ((s + 1) >> 1) & 1);
            asm volatile("bar.sync 2, 288;" ::: "memory");
            DBG(23, 8);
            mem_proj(s, false, true);
            asm volatile("bar.arrive 3, 256;" ::: "memory");
            if (s == NSEG - 1) break;
            DBG(24, 8);
            if (CH_V1 > 0) pass32(par ^ 1, 0, CH_V1);
            asm volatile("bar.sync 7, 256;" ::: "memory");
            pass32(par ^ 1, CH_V1, CH_V2);
            DBG(26, 8);
            asm volatile("bar.sync 6, 256;" ::: "memory");
            const uint2* xb = reinterpret_cast<const uint2*>(g_xbuf + (s & 3) * 16384 + (size_t)rank * 2048 + t4 * 64) + lane;
            uint2 p[8];
            auto poll_all = [&]() {
#pragma unroll
                for (int k = 0; k < 8; k++)
                    asm volatile("ld.relaxed.gpu.global.v2.u32 {%0, %1}, [%2];" : "=r"(p[k].x), "=r"(p[k].y) : "l"(xb + k * 128) : "memory");
                DBG(17, 8);
            };
            if (CH_V3 > CH_V2) { pace(CH_V3_DELAY); pass32(par ^ 1, CH_V2, CH_V3); }
            if (CH_VST == 0) {
                asm volatile("bar.sync 9, 256;" ::: "memory");
                wgmma_wait<0>();
                store32(aO + (par ^ 1) * CH_TP + CO_T);
                DBG(27, 8);
            }
            pace(CH_POLL_DELAY);
            auto lo = [](uint32_t u) { return __uint_as_float(~u << 16); };
            auto hi = [](uint32_t u) { return __uint_as_float(~u & 0xffff0000u); };
            poll_all();
            for (int it = 0; it < WAIT_LIMIT / 4; it++) {
                uint32_t bad = 0;
#pragma unroll
                for (int k = 0; k < 8; k++) bad |= (min(p[k].x, p[k].y) == 0u ? 1u : 0u) << k;
                if (__all_sync(0xffffffff, bad == 0u)) break;
                if (it == 0) DBG(12, 8);
                if (it == 1) DBG(14, 8);
                if (it == 2) DBG(15, 8);
#pragma unroll
                for (int k = 0; k < 8; k++)
                    if (bad & (1u << k))
                        asm volatile("ld.relaxed.gpu.global.v2.u32 {%0, %1}, [%2];" : "=r"(p[k].x), "=r"(p[k].y) : "l"(xb + k * 128) : "memory");
            }
            DBG(9, 8);
            const uint32_t m0 = pack_bf16(((lo(p[0].x) + lo(p[1].x)) + (lo(p[2].x) + lo(p[3].x))) + ((lo(p[4].x) + lo(p[5].x)) + (lo(p[6].x) + lo(p[7].x))),
                                          ((hi(p[0].x) + hi(p[1].x)) + (hi(p[2].x) + hi(p[3].x))) + ((hi(p[4].x) + hi(p[5].x)) + (hi(p[6].x) + hi(p[7].x))));
            const uint32_t m1 = pack_bf16(((lo(p[0].y) + lo(p[1].y)) + (lo(p[2].y) + lo(p[3].y))) + ((lo(p[4].y) + lo(p[5].y)) + (lo(p[6].y) + lo(p[7].y))),
                                          ((hi(p[0].y) + hi(p[1].y)) + (hi(p[2].y) + hi(p[3].y))) + ((hi(p[4].y) + hi(p[5].y)) + (hi(p[6].y) + hi(p[7].y))));
            const int row = t4 * 2 + (lane >> 4);
            const uint32_t dsta = sb + CO_MB + row * 128 + ((((lane & 15) >> 1) ^ row) << 4) + (lane & 1) * 8;
#pragma unroll
            for (int i = 0; i < 8; i++) {
                const int dr = (rank + (i & 1) * 4 + (i >> 1)) & 7;
                st_async_v2(remote(dsta + i * 1024, dr), m0, m1, remote(bar_mem + 8 * (i >> 1), dr));
            }
            DBG(10, 8);
            if (CH_VST == 1) {
                if (CH_V3 < 32) pass32(par ^ 1, CH_V3, 32);
                asm volatile("bar.sync 9, 256;" ::: "memory");
                wgmma_wait<0>();
                store32(aO + (par ^ 1) * CH_TP + CO_T);
                DBG(27, 8);
            }
        }
        asm volatile("bar.sync 6, 256;" ::: "memory");
        local_softmax(NSEG - 1);
        asm volatile("bar.arrive 8, 256;" ::: "memory");
    }
    __syncthreads();
    cluster_sync_all();
    TS_END(2);
}

struct Proj2Params {
    CUtensorMap mapA[2];
    CUtensorMap mapW[3];
    bf16* out[3];
};
#define P2T(i)
#define P2_NOMMA 0
#define P2_NOLOAD 0
constexpr int P2_STAGES = 6;
constexpr int P2_SMEM = 131072 + P2_STAGES * 16384 + 1024 + 1024;
constexpr int P2_ITEMS = 168 + 48;

__device__ __forceinline__ int p2_reps(int t) { return t >= 168 ? 1 : 2; }
__device__ __forceinline__ void p2_tile(int t, int w, int& z, int& mp, int& head) {
    if (t >= 168) { w += ((t - 168) & 1) * 2; t = 168 + ((t - 168) >> 1); }
    const int hq = t / 24, v = t % 24;
    mp = v & 7;
    if (v < 16) { head = hq * 4 + (v >> 3) * 2 + (w >> 1); z = 1 + (w & 1); }
    else { head = hq * 4 + w; z = 0; }
}
__device__ __forceinline__ void mbar_arrive_remote(uint32_t bar_cluster_addr) {
    asm volatile("mbarrier.arrive.release.cluster.shared::cluster.b64 _, [%0];" :: "r"(bar_cluster_addr) : "memory");
}
__device__ __forceinline__ void mbar_arrive_cl(uint32_t bar_cluster_addr) {
    asm volatile("mbarrier.arrive.shared::cluster.b64 _, [%0];" :: "r"(bar_cluster_addr) : "memory");
}
__device__ __forceinline__ void mbar_wait_acq_cluster(uint32_t bar, uint32_t parity) {
    asm volatile(
        "{\n"
        ".reg .pred p, q;\n"
        ".reg .u32 c;\n"
        "mov.u32 c, 0;\n"
        "WAIT_LOOP_C:\n"
        "mbarrier.try_wait.parity.acquire.cluster.shared::cta.b64 p, [%0], %1;\n"
        "@p bra WAIT_DONE_C;\n"
        "add.u32 c, c, 1;\n"
        "setp.lt.u32 q, c, 4000000;\n"
        "@q bra WAIT_LOOP_C;\n"
        "WAIT_DONE_C:\n"
        "}\n" :: "r"(bar), "r"(parity) : "memory");
}
__device__ __forceinline__ uint4 quad_transpose(uint32_t p0, uint32_t p1, uint32_t p2, uint32_t p3, int lane) {
    const bool o1 = lane & 1, o2 = lane & 2;
    uint32_t s0 = o1 ? p0 : p1, s1 = o1 ? p2 : p3;
    s0 = __shfl_xor_sync(0xffffffff, s0, 1); s1 = __shfl_xor_sync(0xffffffff, s1, 1);
    const uint32_t a_lo = o1 ? s0 : p0, a_hi = o1 ? p1 : s0, b_lo = o1 ? s1 : p2, b_hi = o1 ? p3 : s1;
    uint32_t t0 = o2 ? a_lo : b_lo, t1 = o2 ? a_hi : b_hi;
    t0 = __shfl_xor_sync(0xffffffff, t0, 2); t1 = __shfl_xor_sync(0xffffffff, t1, 2);
    return o2 ? make_uint4(t0, t1, b_lo, b_hi) : make_uint4(a_lo, a_hi, t0, t1);
}
#define P2_PACE 35
#define P2_PACE2 0
template <bool PERM, int PACE = 0>
__device__ __forceinline__ void store_frag_128(const float (&acc)[64], bf16* obase, int lane) {
#pragma unroll
    for (int rr = 0; rr < 2; rr++)
#pragma unroll
        for (int g = 0; g < 4; g++) {
            const float* a = &acc[g * 16 + rr * 2];
            const uint32_t p0 = pack_bf16(a[0], a[1]), p1 = pack_bf16(a[4], a[5]), p2 = pack_bf16(a[8], a[9]), p3 = pack_bf16(a[12], a[13]);
            *reinterpret_cast<uint4*>(obase + (size_t)(rr * 8) * HD + g * 32) = PERM ? make_uint4(p0, p1, p2, p3) : quad_transpose(p0, p1, p2, p3, lane);
            pace(PACE);
        }
}
__global__ void __cluster_dims__(2, 1, 1) __launch_bounds__(384, 1) proj2_kernel(const __grid_constant__ Proj2Params P) {
    extern __shared__ uint8_t smem_raw[];
    const uint32_t sbase = (smem_u32(smem_raw) + 1023) & ~1023u;
    const uint32_t sA = sbase, sB = sbase + 131072, sC = sB + P2_STAGES * 16384;
    const uint32_t bars = sC;
    const uint32_t a_full = bars, a_empty = bars + 64, b_full = bars + 128, b_empty = b_full + 8 * P2_STAGES;
    const uint32_t item_bar = b_empty + 8 * P2_STAGES, item_in = item_bar + 16, slot = item_in + 16;
    const uint32_t note_bar = slot + 16, note_free = note_bar + 64, note = note_free + 64;
    const int warp = threadIdx.x >> 5, lane = threadIdx.x & 31;
    const uint32_t rank = cluster_ctarank();
    TS_BEGIN(0);
    if (threadIdx.x == 0) {
        for (int i = 0; i < 8; i++) { mbar_init(a_full + 8 * i, 1); mbar_init(a_empty + 8 * i, 2); }
        for (int i = 0; i < P2_STAGES; i++) { mbar_init(b_full + 8 * i, 1); mbar_init(b_empty + 8 * i, 2); }
        mbar_init(item_bar, 1); mbar_init(item_bar + 8, 1); mbar_init(item_in, 2); mbar_init(item_in + 8, 2);
        for (int i = 0; i < 8; i++) { mbar_init(note_bar + 8 * i, 1); mbar_init(note_free + 8 * i, 1); }
        asm volatile("fence.mbarrier_init.release.cluster;" ::: "memory");
    }
    __syncthreads();
    cluster_sync_all();
    pdl_launch_dependents();
    if (warp == 9) {
        if (lane == 0) {
            for (int n = 0;; n++) {
                const int e = (n & 1) * 4 + ((n >> 1) & 3);
                mbar_wait(note_bar + 8 * e, (n >> 3) & 1);
                int m;
                asm volatile("ld.shared.s32 %0, [%1];" : "=r"(m) : "r"(note + e * 4) : "memory");
                mbar_arrive(note_free + 8 * e);
                if (m < 0) break;
                signal_ctr(m);
            }
        }
    } else if (warp == 10) {
        if (lane == 0) {
            auto publish = [&](int ic, int tq) {
                const int t = tq < P2_ITEMS ? tq : -1;
                asm volatile("st.shared.s32 [%0], %1;" :: "r"(slot + (ic & 3) * 4), "r"(t) : "memory");
                mbar_arrive(item_bar + 8 * (ic & 1));
                st_async_b32(mapa_u32(slot + (ic & 3) * 4, 1), (uint32_t)t, mapa_u32(item_bar + 8 * (ic & 1), 1));
            };
            const int npair = (int)(gridDim.x >> 1), pair = (int)(blockIdx.x >> 1);
            if (rank == 0) publish(0, pair);
            for (int ic = 0;; ic++) {
                if (rank == 1) mbar_expect_tx(item_bar + 8 * (ic & 1), 4);
                mbar_wait(item_bar + 8 * (ic & 1), (ic >> 1) & 1);
                int t;
                asm volatile("ld.shared.s32 %0, [%1];" : "=r"(t) : "r"(slot + (ic & 3) * 4) : "memory");
                if (t < 0) break;
                int z0, mp, h0;
                p2_tile(t, 0, z0, mp, h0);
                const int aidx = z0 >= 1 ? 1 : 0;
                const int m0 = (2 * mp + (int)rank) * 128;
                for (int k = 0; k < 8; k++) {
                    mbar_wait(a_empty + 8 * k, (ic & 1) ^ 1);
                    if (P2_NOLOAD) mbar_arrive(a_full + 8 * k); else {
                    mbar_expect_tx(a_full + 8 * k, 16384);
                    tma_load_2d(sA + k * 16384, &P.mapA[aidx], a_full + 8 * k, k * 64, m0); }
                }
                if (rank == 0) {
                    mbar_wait(item_in + 8 * (ic & 1), (ic >> 1) & 1);
                    publish(ic + 1, ic == 0 ? npair + pair : 2 * npair + (int)atomicAdd(&g_ctr[CT_PROJ], 1u));
                }
            }
        }
    } else if (warp == 8 || warp == 11) {
        if (lane == 0) {
            const int par2 = warp == 8 ? 0 : 1;
            int it = 0; uint32_t bph = 0;
            for (int ic = 0;; ic++) {
                mbar_wait(item_bar + 8 * (ic & 1), (ic >> 1) & 1);
                int t;
                asm volatile("ld.shared.s32 %0, [%1];" : "=r"(t) : "r"(slot + (ic & 3) * 4) : "memory");
                if (t < 0) break;
                const int nt = 2 * p2_reps(t);
                for (int w = 0; w < nt; w++) {
                    int z, mp, hd;
                    p2_tile(t, w, z, mp, hd);
                    for (int k = 0; k < 8; k++) {
                        const int s = it; const uint32_t phb = bph;
                        if (++it == P2_STAGES) { it = 0; bph ^= 1; }
                        if ((k & 1) != par2) continue;
                        mbar_wait(b_empty + 8 * s, phb ^ 1);
                        if (P2_NOLOAD) { mbar_arrive(b_full + 8 * s); continue; }
                        mbar_expect_tx(b_full + 8 * s, 16384);
                        tma_load_2d_mc(sB + s * 16384 + rank * 8192, &P.mapW[z], b_full + 8 * s, hd * 128 + (int)rank * 64, k * 64, (uint16_t)3);
                    }
                }
            }
        }
    } else {
        const int wg = warp >> 2;
        float acc[2][64];
        const uint32_t a_lo = desc_lo(sA, 16), b_lo0 = desc_lo(sB, 8192);
        const bool elected = (threadIdx.x & 127) == 0;
        int s = (wg * 8) % P2_STAGES;
        uint32_t ph = ((wg * 8) / P2_STAGES) & 1;
        int nnote = 0;
        if (wg == 1) asm volatile("bar.arrive 3, 256;" ::: "memory");
        for (int ic = 0;; ic++) {
            mbar_wait(item_bar + 8 * (ic & 1), (ic >> 1) & 1);
            int t;
            asm volatile("ld.shared.s32 %0, [%1];" : "=r"(t) : "r"(slot + (ic & 3) * 4) : "memory");
            P2T(7);
            if (wg == 0 && t < 0) {
                if (elected) {
                    const int e = nnote & 3;
                    mbar_wait(note_free + 8 * e, ((nnote >> 2) & 1) ^ 1);
                    asm volatile("st.shared.s32 [%0], %1;" :: "r"(note + e * 4), "r"(-1) : "memory");
                    mbar_arrive(note_bar + 8 * e);
                }
            }
            if (t < 0) break;
            const int reps = p2_reps(t);
#pragma unroll 1
            for (int rp = 0; rp < reps; rp++) {
            const bool first = rp == 0, last = rp == reps - 1;
            int z, mp, head;
            p2_tile(t, rp * 2 + wg, z, mp, head);
            asm volatile("bar.sync %0, 256;" :: "r"(3 + wg) : "memory");
            P2T(0);
            if (wg == 1 && last && elected) mbar_arrive_cl(mapa_u32(item_in + 8 * (ic & 1), 0));
            int sprev = 0;
#pragma unroll
            for (int k = 0; k < 8; k++) {
                if (k == 0) P2T(5);
                if (wg == 0 && first) mbar_wait(a_full + 8 * k, ic & 1);
                if (k == 0) P2T(6);
                mbar_wait(b_full + 8 * s, ph);
                if (k == 7) asm volatile("bar.arrive %0, 256;" :: "r"(4 - wg) : "memory");
                if (k == 0) P2T(1);
                if (k == 7) P2T(2);
                const uint32_t b_lo = b_lo0 + s * 1024;
                wgmma_fence();
#pragma unroll
                for (int kk = 0; kk < (P2_NOMMA ? 1 : 4); kk++) {
                    wgmma_ss_n128_lo<1>(acc[0], a_lo + k * 1024 + kk * 2, b_lo + kk * 128, (k | kk) != 0);
                    wgmma_ss_n128_lo<1>(acc[1], a_lo + k * 1024 + 512 + kk * 2, b_lo + kk * 128, (k | kk) != 0);
                }
                wgmma_commit();
                if (k > 0) {
                    wgmma_wait<1>();
                    if (elected) {
                        const uint32_t e = b_empty + 8 * sprev;
                        mbar_arrive_cl(mapa_u32(e, 0)); mbar_arrive_cl(mapa_u32(e, 1));
                        if (last) mbar_arrive(a_empty + 8 * (k - 1));
                    }
                }
                sprev = s;
                if (++s == P2_STAGES) { s = 0; ph ^= 1; }
            }
            wgmma_wait<0>();
            P2T(3);
            if (elected) {
                const uint32_t e = b_empty + 8 * sprev;
                mbar_arrive_cl(mapa_u32(e, 0)); mbar_arrive_cl(mapa_u32(e, 1));
                if (last) mbar_arrive(a_empty + 8 * 7);
            }
            s += 8 % P2_STAGES; ph ^= (8 / P2_STAGES) & 1;
            if (s >= P2_STAGES) { s -= P2_STAGES; ph ^= 1; }
            const int m0 = (2 * mp + (int)rank) * 128;
            bf16* obase = P.out[z] + ((size_t)head * SEQ + m0 + (warp & 3) * 16 + (lane >> 2)) * HD + (lane & 3) * 8;
            store_frag_128<true, P2_PACE>(acc[0], obase, lane); store_frag_128<true, P2_PACE>(acc[1], obase + (size_t)64 * HD, lane);
            P2T(4);
            {
                asm volatile("bar.sync %0, 128;" :: "r"(1 + wg) : "memory");
                if (elected) {
                    const int e = wg * 4 + (nnote & 3);
                    mbar_wait(note_free + 8 * e, ((nnote >> 2) & 1) ^ 1);
                    asm volatile("st.shared.s32 [%0], %1;" :: "r"(note + e * 4), "r"(CT_AP + (head >> 1)) : "memory");
                    mbar_arrive(note_bar + 8 * e);
                }
                nnote++;
            }
            }
        }
        TS_END(0);
    }
    __syncthreads();
    cluster_sync_all();
}

struct OutParams {
    CUtensorMap mapCtx[2];
    CUtensorMap mapWo[2];
    CUtensorMap mapOut;
};

#define OT(i)
#define OTP(i, th)
constexpr int O2_STAGES = 4;
constexpr int O2_SMEM = O2_STAGES * 49152 + 1024 + 256;
constexpr int O2_GRID = 132;
#define O2_FINE 8

__global__ void __cluster_dims__(2, 1, 1) __launch_bounds__(352, 1)
out2_kernel(const __grid_constant__ OutParams P) {
    extern __shared__ uint8_t smem_raw[];
    const uint32_t sbase = (smem_u32(smem_raw) + 1023) & ~1023u;
    const uint32_t bar_full = sbase + O2_STAGES * 49152, bar_empty = bar_full + 8 * O2_STAGES, bar_item = bar_empty + 8 * O2_STAGES;
    const uint32_t slot = bar_item + 64, stop = slot + 32;
    const int warp = threadIdx.x >> 5, lane = threadIdx.x & 31;
    const uint32_t rank = cluster_ctarank();
    const int cid = blockIdx.x >> 1;
    int pt, cj;
    if (cid < 20) { pt = 2 + (cid < 10 ? cid : 19 - cid); cj = cid >= 10; }
    else if (cid < 28) { pt = 12 + (cid < 24 ? cid - 20 : 27 - cid); cj = cid >= 24; }
    else if (cid < 34) { pt = cid & 1; cj = (cid - 28) >> 1; }
    else { pt = 15 - (cid - 34) % 14; cj = 2 + (cid - 34) / 14; }
    const int nc = pt >= 12 ? 5 : pt >= 2 ? 4 : 3;
    const int mt = (pt >> 1) * 2 + (int)rank, m0 = mt * 128, n0 = (pt & 1) * 256;
    TS_BEGIN(4);
    OT(0);
    int tnext = 0;
    if (threadIdx.x == 256) {
        if (rank == 0) tnext = take_ticket(CT_OT + pt);
        for (int i = 0; i < O2_STAGES; i++) { mbar_init(bar_full + 8 * i, 1); mbar_init(bar_empty + 8 * i, 4); mbar_init(bar_item + 16 * i, 1); mbar_init(bar_item + 16 * i + 8, 1); }
        sts128(stop, 0u, 0u, 0u, 0u);
        asm volatile("fence.mbarrier_init.release.cluster;" ::: "memory");
    }
    __syncwarp();
    asm volatile("barrier.cluster.arrive.relaxed.aligned;" ::: "memory");
    if (threadIdx.x == 256) {
        asm volatile("prefetch.tensormap [%0];" :: "l"(&P.mapCtx[0]) : "memory");
        wait_ctr(CT_CA + mt * 4, 16u);
        OTP(8, 256);
        for (int i = 0; i < 2; i++) {
            mbar_expect_tx(bar_full + 8 * i, 49152);
            tma_load_2d(sbase + i * 49152, &P.mapCtx[0], bar_full + 8 * i, i * 64, cj * SEQ + m0);
        }
        OTP(11, 256);
    }
    if (threadIdx.x == 288) asm volatile("prefetch.tensormap [%0];" :: "l"(&P.mapWo[0]) : "memory");
    __syncwarp();
    asm volatile("barrier.cluster.wait.aligned;" ::: "memory");
    OTP(10, 288);
    if (warp >= 8) {
        if (lane == 0) {
            int s = 0, ready = 1, q = cj * 2, qe = q + 2; uint32_t ph = 0;
            for (int ic = 0;; ic++) {
                if (warp == 8 && rank == 0) {
                    const int t = tnext + nc;
                    asm volatile("st.shared.s32 [%0], %1;" :: "r"(slot + (ic & 7) * 4), "r"(t) : "memory");
                    mbar_arrive(bar_item + 8 * (ic & 7));
                    st_async_b32(mapa_u32(slot + (ic & 7) * 4, 1), (uint32_t)t, mapa_u32(bar_item + 8 * (ic & 7), 1));
                    if (t < 64 + O2_FINE) tnext = take_ticket(CT_OT + pt);
                }
#pragma unroll 1
                for (; q < qe; q++) {
                    const int b = q >> 6, head = (q >> 1) & 31, dk = (q & 1) * 64;
                    mbar_wait(bar_empty + 8 * s, ph ^ 1);
                    const uint32_t sa = sbase + s * 49152;
                    if (warp == 8) {
                        const int f = b ? 4 : head >> 3;
                        if (!((ready >> f) & 1)) {
                            if (b && !(ready & 8)) { wait_ctr(CT_CA + mt * 4 + 3, 16u); ready |= 8; }
                            wait_ctr(b ? CT_CB + mt : CT_CA + mt * 4 + f, b ? 64u : 16u); ready |= 1 << f;
                        }
                        if (ic > 0) {
                            mbar_expect_tx(bar_full + 8 * s, 49152);
                            tma_load_2d(sa, &P.mapCtx[b], bar_full + 8 * s, dk, head * SEQ + m0);
                        }
                    } else {
                        const int j = (int)rank * 2 + (warp - 9);
                        tma_load_2d_mc(sa + 16384 + j * 8192, &P.mapWo[b], bar_full + 8 * s, n0 + j * 64, head * HD + dk, (uint16_t)3);
                    }
                    if (ic == 0 && s == 0) OTP(12, 288);
                    if (++s == O2_STAGES) { s = 0; ph ^= 1; }
                }
                if (warp == 8 && rank == 1) mbar_expect_tx(bar_item + 8 * (ic & 7), 4);
                mbar_wait(bar_item + 8 * (ic & 7), (ic >> 3) & 1);
                int t;
                asm volatile("ld.shared.s32 %0, [%1];" : "=r"(t) : "r"(slot + (ic & 7) * 4) : "memory");
                if (t >= 64 + O2_FINE) break;
                if (t < 64 - O2_FINE) { q = 2 * t; qe = q + 2; } else { q = 64 - O2_FINE + t; qe = q + 1; }
            }
            if (warp == 8) {
                asm volatile("prefetch.tensormap [%0];" :: "l"(&P.mapOut) : "memory");
                if (!(ready & 8)) wait_ctr(CT_CA + mt * 4 + 3, 16u);
                mbar_wait(bar_empty + 8 * s, ph ^ 1);
                asm volatile("st.shared.s32 [%0], %1;" :: "r"(stop + s * 4), "r"(1) : "memory");
                mbar_arrive(bar_full + 8 * s);
                if (atomicAdd(&g_ctr[CT_FIN], 1u) == gridDim.x - 1)
                    for (int i = 0; i < CT_N / 4; i++) reinterpret_cast<uint4*>(g_ctr)[i] = make_uint4(0u, 0u, 0u, 0u);
            }
        }
        __syncwarp();
        asm volatile("barrier.cluster.arrive.relaxed.aligned;" ::: "memory");
    } else {
        const int wg = warp >> 2;
        const bool elected = (threadIdx.x & 127) == 0;
        float acc[128];
#pragma unroll
        for (int i = 0; i < 128; i++) acc[i] = 0.f;
        int s = 0, sprev = 0; uint32_t ph = 0;
#pragma unroll 1
        for (int i = 0;; i++) {
            mbar_wait(bar_full + 8 * s, ph);
            int st;
            asm volatile("ld.shared.s32 %0, [%1];" : "=r"(st) : "r"(stop + s * 4) : "memory");
            if (st) break;
            if (i == 0) OT(1);
            const uint32_t sa = sbase + s * 49152 + wg * 8192, sb = sbase + s * 49152 + 16384;
            wgmma_fence();
#pragma unroll
            for (int kk = 0; kk < 4; kk++)
                wgmma_ss_n256_tb(acc, make_desc(sa + kk * 32, 16, 1024), make_desc(sb + kk * 2048, 8192, 1024), 1);
            wgmma_commit();
            if (i > 0) {
                wgmma_wait<1>();
                if (elected) { const uint32_t e = bar_empty + 8 * sprev; mbar_arrive_cl(mapa_u32(e, 0)); mbar_arrive_cl(mapa_u32(e, 1)); }
            }
            sprev = s;
            if (++s == O2_STAGES) { s = 0; ph ^= 1; }
        }
        asm volatile("barrier.cluster.arrive.relaxed.aligned;" ::: "memory");
        wgmma_wait<0>();
        asm volatile("bar.sync %0, 128;" :: "r"(1 + wg) : "memory");
        OT(3);
        const int row = (lane & 7) + ((lane >> 3) & 1) * 8;
#pragma unroll
        for (int bx = 0; bx < 4; bx++) {
            const uint32_t stg = sbase + bx * 49152 + warp * 2048;
#pragma unroll
            for (int j = 0; j < 8; j += 2) {
                const float* a = &acc[bx * 32 + j * 4];
                stmatrix_x4(stg + row * 128 + (((j + (lane >> 4)) ^ (row & 7)) << 4), pack_bf16(a[0], a[1]), pack_bf16(a[2], a[3]), pack_bf16(a[4], a[5]), pack_bf16(a[6], a[7]));
            }
            asm volatile("fence.proxy.async.shared::cta;" ::: "memory");
            __syncwarp();
            if (lane == 0)
                asm volatile("cp.reduce.async.bulk.tensor.2d.global.shared::cta.add.tile.bulk_group [%0, {%2, %3}], [%1];"
                             :: "l"((uint64_t)&P.mapOut), "r"(stg), "r"(n0 + bx * 64), "r"(m0 + warp * 16) : "memory");
        }
        OT(4);
        if (lane == 0) {
            asm volatile("cp.async.bulk.commit_group;" ::: "memory");
            asm volatile("cp.async.bulk.wait_group.read 0;" ::: "memory");
        }
        __syncwarp();
    }
    asm volatile("barrier.cluster.wait.aligned;" ::: "memory");
    TS_END(4);
}

typedef CUresult (*PFN_encodeTiled)(CUtensorMap*, CUtensorMapDataType, cuuint32_t, void*, const cuuint64_t*,
                                    const cuuint64_t*, const cuuint32_t*, const cuuint32_t*, CUtensorMapInterleave,
                                    CUtensorMapSwizzle, CUtensorMapL2promotion, CUtensorMapFloatOOBfill);
static PFN_encodeTiled g_encode = nullptr;

static void make_map(CUtensorMap* m, const void* ptr, uint64_t rows, uint64_t cols, uint32_t box_rows, bool sw64 = false) {
    cuuint64_t dims[2] = {cols, rows};
    cuuint64_t strides[1] = {cols * 2};
    cuuint32_t box[2] = {sw64 ? 32u : 64u, box_rows};
    cuuint32_t es[2] = {1, 1};
    g_encode(m, CU_TENSOR_MAP_DATA_TYPE_BFLOAT16, 2, const_cast<void*>(ptr), dims, strides, box, es,
             CU_TENSOR_MAP_INTERLEAVE_NONE, sw64 ? CU_TENSOR_MAP_SWIZZLE_64B : CU_TENSOR_MAP_SWIZZLE_128B, CU_TENSOR_MAP_L2_PROMOTION_L2_256B,
             CU_TENSOR_MAP_FLOAT_OOB_FILL_NONE);
}

template <typename... KArgs, typename... Args>
static void launch_pdl(void (*kernel)(KArgs...), int grid, int block, size_t smem, cudaStream_t st, bool pdl, Args... args) {
    cudaLaunchConfig_t cfg = {};
    cfg.gridDim = dim3(grid); cfg.blockDim = dim3(block); cfg.dynamicSmemBytes = smem; cfg.stream = st;
    cudaLaunchAttribute at[1];
    at[0].id = cudaLaunchAttributeProgrammaticStreamSerialization;
    at[0].val.programmaticStreamSerializationAllowed = 1;
    cfg.attrs = at; cfg.numAttrs = pdl ? 1 : 0;
    cudaLaunchKernelEx(&cfg, kernel, KArgs(args)...);
}

extern "C" void kernel_launch(void* const* d_in, const int* in_sizes, int n_in, void* d_out, int out_size) {
    const bf16* x = (const bf16*)d_in[0];
    const bf16* ckv = (const bf16*)d_in[1];
    const bf16* wq = (const bf16*)d_in[2];
    const bf16* wuk = (const bf16*)d_in[3];
    const bf16* wuv = (const bf16*)d_in[4];
    const bf16* wo = (const bf16*)d_in[5];
    const bf16* mem0 = (const bf16*)d_in[7];
    const bf16* Wq = (const bf16*)d_in[8];
    const bf16* Wk = (const bf16*)d_in[9];
    const bf16* Wv = (const bf16*)d_in[10];
    const bf16* Wo = (const bf16*)d_in[11];
    const bf16* gate_w = (const bf16*)d_in[13];
    bf16* out = (bf16*)d_out;

    static Proj2Params P2;
    static ChainParams CP;
    static AttnParams AP;
    static OutParams OP;
    static bool init = false;
    static const void* last_in[14];
    static const void* last_out;
    bool same = init && last_out == d_out;
    for (int i = 0; i < 14 && same; i++) same = last_in[i] == d_in[i];
    if (!init) {
        cudaDriverEntryPointQueryResult qr;
        cudaGetDriverEntryPoint("cuTensorMapEncodeTiled", (void**)&g_encode, cudaEnableDefault, &qr);
        cudaFuncSetAttribute(proj2_kernel, cudaFuncAttributeMaxDynamicSharedMemorySize, P2_SMEM);
        cudaFuncSetAttribute(attn_kernel, cudaFuncAttributeMaxDynamicSharedMemorySize, FA_SMEM);
        cudaFuncSetAttribute(chain_kernel, cudaFuncAttributeMaxDynamicSharedMemorySize, CH_SMEM);
        cudaFuncSetAttribute(out2_kernel, cudaFuncAttributeMaxDynamicSharedMemorySize, O2_SMEM);
        init = true;
    }
    if (!same) {
        for (int i = 0; i < 14; i++) last_in[i] = d_in[i];
        last_out = d_out;
        void *pQA, *pKA, *pVA, *pCA, *pCB;
        cudaGetSymbolAddress(&pQA, g_QA); cudaGetSymbolAddress(&pKA, g_KA); cudaGetSymbolAddress(&pVA, g_VA);
        cudaGetSymbolAddress(&pCA, g_ctxA); cudaGetSymbolAddress(&pCB, g_ctxB);
        make_map(&P2.mapA[0], x, SEQ, DM, 128);
        make_map(&P2.mapA[1], ckv, SEQ, DM, 128);
        const void* ws[3] = {wq, wuk, wuv};
        void* cs[3] = {pQA, pKA, pVA};
        for (int i = 0; i < 3; i++) { make_map(&P2.mapW[i], ws[i], DM, NQ, 64); P2.out[i] = (bf16*)cs[i]; }
        make_map(&CP.mapW[0], Wq, DM, NQ, 64); make_map(&CP.mapW[1], Wk, DM, NQ, 64); make_map(&CP.mapW[2], Wv, DM, NQ, 64);
        make_map(&CP.mapX, x, SEQ, DM, 32);
        make_map(&CP.mapC, pCB, NH * SEQ, HD, 32);
        make_map(&AP.mapQ, pQA, NH * SEQ, HD, 128);
        make_map(&AP.mapK, pKA, NH * SEQ, HD, 128);
        make_map(&AP.mapV, pVA, NH * SEQ, HD, 128);
        make_map(&AP.mapO, pCA, NH * SEQ, HD, 64);
        make_map(&OP.mapCtx[0], pCA, NH * SEQ, HD, 128);
        make_map(&OP.mapCtx[1], pCB, NH * SEQ, HD, 128);
        make_map(&OP.mapWo[0], wo, NQ, DM, 64);
        make_map(&OP.mapWo[1], Wo, NQ, DM, 64);
        make_map(&OP.mapOut, out, SEQ, DM, 16);
        AP.out = out;
    }
    cudaStream_t s1 = cudaStreamPerThread;
    const bool pdl = true;
    launch_pdl(chain_kernel, 64, CH_BLOCK, CH_SMEM, s1, false, CP, mem0, Wo, x, gate_w);
    launch_pdl(proj2_kernel, 68, 384, P2_SMEM, s1, pdl, P2);
    launch_pdl(attn_kernel, FA_GRID, 384, FA_SMEM, s1, pdl, AP);
    launch_pdl(out2_kernel, O2_GRID, 352, O2_SMEM, s1, pdl, OP);
}
```

```cpp
#include <cuda_runtime.h>
#include <cuda_bf16.h>
#include <cuda.h>
#include <stdint.h>
#include <type_traits>

constexpr int SEQ = 2048;
constexpr int DM = 512;
constexpr int NH = 32;
constexpr int HD = 128;
constexpr int NQ = NH * HD;
constexpr int SEGL = 32;
constexpr int NMEM = 8;
constexpr int NSEG = SEQ / SEGL;

typedef __nv_bfloat16 bf16;

__device__ bf16 g_QA[SEQ * NQ];
__device__ bf16 g_KA[SEQ * NQ];
__device__ bf16 g_VA[SEQ * NQ];
__device__ bf16 g_ctxA[SEQ * NQ];
__device__ bf16 g_ctxB[SEQ * NQ];
constexpr int CT_PROJ = 0, CT_ATTN = 1, CT_FIN = 5;
constexpr int CT_AP = 64;
constexpr int CT_GATE = 96;
constexpr int CT_CA = 128;
constexpr int CT_CB = 192;
constexpr int CT_OT = 208;
constexpr int CT_N = 224;
__device__ __align__(16) unsigned int g_ctr[CT_N];
__device__ float g_gate[SEQ];
__device__ uint32_t g_xbuf[4 * 8 * 2048];

#define FA_GRID 68

#define TS_BEGIN(id)
#define TS_END(id)
#define WAIT_LIMIT 200000
__device__ __forceinline__ void pdl_launch_dependents() { asm volatile("griddepcontrol.launch_dependents;" ::: "memory"); }
__device__ __forceinline__ void wait_ctr(int idx, unsigned int n) {
    unsigned int v; int it = 0;
    do { asm volatile("ld.acquire.gpu.global.u32 %0, [%1];" : "=r"(v) : "l"(&g_ctr[idx]) : "memory"); } while (v < n && ++it < WAIT_LIMIT);
    asm volatile("fence.proxy.async.shared::cta;" ::: "memory");
}
__device__ __forceinline__ int take_ticket(int idx) {
    int v;
    asm volatile("atom.relaxed.gpu.global.inc.u32 %0, [%1], 0x7fffffff;" : "=r"(v) : "l"(&g_ctr[idx]) : "memory");
    return v;
}
__device__ __forceinline__ void signal_ctr(int idx) {
    asm volatile("fence.proxy.async;" ::: "memory");
    __threadfence();
    atomicAdd(&g_ctr[idx], 1u);
}
__device__ __forceinline__ void signal_ctr_generic(int idx) {
    asm volatile("red.release.gpu.global.add.u32 [%0], 1;" :: "l"(&g_ctr[idx]) : "memory");
}
__device__ __forceinline__ uint32_t smem_u32(const void* p) {
    return (uint32_t)__cvta_generic_to_shared(p);
}
__device__ __forceinline__ void mbar_init(uint32_t bar, uint32_t count) {
    asm volatile("mbarrier.init.shared::cta.b64 [%0], %1;" :: "r"(bar), "r"(count));
}
__device__ __forceinline__ void mbar_expect_tx(uint32_t bar, uint32_t bytes) {
    asm volatile("mbarrier.arrive.expect_tx.shared::cta.b64 _, [%0], %1;" :: "r"(bar), "r"(bytes) : "memory");
}
__device__ __forceinline__ void mbar_arrive(uint32_t bar) {
    asm volatile("mbarrier.arrive.shared::cta.b64 _, [%0];" :: "r"(bar) : "memory");
}
__device__ __forceinline__ void mbar_wait(uint32_t bar, uint32_t parity) {
    asm volatile(
        "{\n"
        ".reg .pred p, q;\n"
        ".reg .u32 c;\n"
        "mov.u32 c, 0;\n"
        "WAIT_LOOP:\n"
        "mbarrier.try_wait.parity.shared::cta.b64 p, [%0], %1;\n"
        "@p bra WAIT_DONE;\n"
        "add.u32 c, c, 1;\n"
        "setp.lt.u32 q, c, %2;\n"
        "@q bra WAIT_LOOP;\n"
        "WAIT_DONE:\n"
        "}\n" :: "r"(bar), "r"(parity), "n"(WAIT_LIMIT) : "memory");
}
__device__ __forceinline__ void tma_load_2d(uint32_t dst, const CUtensorMap* map, uint32_t bar, int c0, int c1) {
    asm volatile(
        "cp.async.bulk.tensor.2d.shared::cluster.global.mbarrier::complete_tx::bytes [%0], [%1, {%3, %4}], [%2];"
        :: "r"(dst), "l"((uint64_t)map), "r"(bar), "r"(c0), "r"(c1) : "memory");
}
__device__ __forceinline__ void wgmma_fence() { asm volatile("wgmma.fence.sync.aligned;" ::: "memory"); }
__device__ __forceinline__ void wgmma_commit() { asm volatile("wgmma.commit_group.sync.aligned;" ::: "memory"); }
template <int N> __device__ __forceinline__ void wgmma_wait() {
    asm volatile("wgmma.wait_group.sync.aligned %0;" :: "n"(N) : "memory");
}
__device__ __forceinline__ uint64_t make_desc(uint32_t addr, uint32_t lbo, uint32_t sbo) {
    uint64_t d = 0;
    d |= (uint64_t)((addr & 0x3FFFF) >> 4);
    d |= (uint64_t)((lbo >> 4) & 0x3FFF) << 16;
    d |= (uint64_t)((sbo >> 4) & 0x3FFF) << 32;
    d |= (uint64_t)1 << 62;
    return d;
}

#define ACC64(d) \
    "+f"(d[0]), "+f"(d[1]), "+f"(d[2]), "+f"(d[3]), "+f"(d[4]), "+f"(d[5]), "+f"(d[6]), "+f"(d[7]), \
    "+f"(d[8]), "+f"(d[9]), "+f"(d[10]), "+f"(d[11]), "+f"(d[12]), "+f"(d[13]), "+f"(d[14]), "+f"(d[15]), \
    "+f"(d[16]), "+f"(d[17]), "+f"(d[18]), "+f"(d[19]), "+f"(d[20]), "+f"(d[21]), "+f"(d[22]), "+f"(d[23]), \
    "+f"(d[24]), "+f"(d[25]), "+f"(d[26]), "+f"(d[27]), "+f"(d[28]), "+f"(d[29]), "+f"(d[30]), "+f"(d[31]), \
    "+f"(d[32]), "+f"(d[33]), "+f"(d[34]), "+f"(d[35]), "+f"(d[36]), "+f"(d[37]), "+f"(d[38]), "+f"(d[39]), \
    "+f"(d[40]), "+f"(d[41]), "+f"(d[42]), "+f"(d[43]), "+f"(d[44]), "+f"(d[45]), "+f"(d[46]), "+f"(d[47]), \
    "+f"(d[48]), "+f"(d[49]), "+f"(d[50]), "+f"(d[51]), "+f"(d[52]), "+f"(d[53]), "+f"(d[54]), "+f"(d[55]), \
    "+f"(d[56]), "+f"(d[57]), "+f"(d[58]), "+f"(d[59]), "+f"(d[60]), "+f"(d[61]), "+f"(d[62]), "+f"(d[63])
#define ACC64_STR \
    "{%0, %1, %2, %3, %4, %5, %6, %7, %8, %9, %10, %11, %12, %13, %14, %15, " \
    "%16, %17, %18, %19, %20, %21, %22, %23, %24, %25, %26, %27, %28, %29, %30, %31, " \
    "%32, %33, %34, %35, %36, %37, %38, %39, %40, %41, %42, %43, %44, %45, %46, %47, " \
    "%48, %49, %50, %51, %52, %53, %54, %55, %56, %57, %58, %59, %60, %61, %62, %63}"

template <int TB>
__device__ __forceinline__ void wgmma_ss_n128(float (&d)[64], uint64_t da, uint64_t db, int scale_d) {
    asm volatile(
        "{\n.reg .pred p;\nsetp.ne.b32 p, %66, 0;\n"
        "wgmma.mma_async.sync.aligned.m64n128k16.f32.bf16.bf16 " ACC64_STR ", %64, %65, p, 1, 1, 0, %67;\n}\n"
        : ACC64(d) : "l"(da), "l"(db), "r"(scale_d), "n"(TB));
}
__device__ __forceinline__ uint32_t desc_lo(uint32_t addr, uint32_t lbo) { return ((addr & 0x3FFFF) >> 4) | ((lbo >> 4) << 16); }
template <int TB>
__device__ __forceinline__ void wgmma_ss_n128_lo(float (&d)[64], uint32_t da_lo, uint32_t db_lo, int scale_d) {
    asm volatile(
        "{\n.reg .pred p;\n.reg .b64 da, db;\nsetp.ne.b32 p, %66, 0;\n"
        "mov.b64 da, {%64, 0x40000040};\nmov.b64 db, {%65, 0x40000040};\n"
        "wgmma.mma_async.sync.aligned.m64n128k16.f32.bf16.bf16 " ACC64_STR ", da, db, p, 1, 1, 0, %67;\n}\n"
        : ACC64(d) : "r"(da_lo), "r"(db_lo), "r"(scale_d), "n"(TB));
}
__device__ __forceinline__ void wgmma_rs_n128_tb(float (&d)[64], uint32_t a0, uint32_t a1, uint32_t a2, uint32_t a3,
                                                 uint64_t db, int scale_d) {
    asm volatile(
        "{\n.reg .pred p;\nsetp.ne.b32 p, %69, 0;\n"
        "wgmma.mma_async.sync.aligned.m64n128k16.f32.bf16.bf16 " ACC64_STR ", {%64, %65, %66, %67}, %68, p, 1, 1, 1;\n}\n"
        : ACC64(d) : "r"(a0), "r"(a1), "r"(a2), "r"(a3), "l"(db), "r"(scale_d));
}
__device__ __forceinline__ void wgmma_rs_n80(float (&d)[40], const uint32_t (&a)[4], uint32_t db_lo, int scale_d) {
    asm volatile(
        "{\n.reg .pred p;\n.reg .b64 db;\nsetp.ne.b32 p, %45, 0;\nmov.b64 db, {%44, 0x40000040};\n"
        "wgmma.mma_async.sync.aligned.m64n80k16.f32.bf16.bf16 "
        "{%0, %1, %2, %3, %4, %5, %6, %7, %8, %9, %10, %11, %12, %13, %14, %15, %16, %17, %18, %19, %20, %21, %22, %23, %24, %25, %26, %27, %28, %29, %30, %31, %32, %33, %34, %35, %36, %37, %38, %39}, "
        "{%40, %41, %42, %43}, db, p, 1, 1, 0;\n}\n"
        : "+f"(d[0]), "+f"(d[1]), "+f"(d[2]), "+f"(d[3]), "+f"(d[4]), "+f"(d[5]), "+f"(d[6]), "+f"(d[7]), "+f"(d[8]), "+f"(d[9]), "+f"(d[10]), "+f"(d[11]), "+f"(d[12]), "+f"(d[13]), "+f"(d[14]), "+f"(d[15]), "+f"(d[16]), "+f"(d[17]), "+f"(d[18]), "+f"(d[19]), "+f"(d[20]), "+f"(d[21]), "+f"(d[22]), "+f"(d[23]), "+f"(d[24]), "+f"(d[25]), "+f"(d[26]), "+f"(d[27]), "+f"(d[28]), "+f"(d[29]), "+f"(d[30]), "+f"(d[31]), "+f"(d[32]), "+f"(d[33]), "+f"(d[34]), "+f"(d[35]), "+f"(d[36]), "+f"(d[37]), "+f"(d[38]), "+f"(d[39])
        : "r"(a[0]), "r"(a[1]), "r"(a[2]), "r"(a[3]), "r"(db_lo), "r"(scale_d));
}
__device__ __forceinline__ void wgmma_ss_n256_tb(float (&d)[128], uint64_t da, uint64_t db, int scale_d) {
    asm volatile(
        "{\n.reg .pred p;\nsetp.ne.b32 p, %130, 0;\n"
        "wgmma.mma_async.sync.aligned.m64n256k16.f32.bf16.bf16 {%0, %1, %2, %3, %4, %5, %6, %7, %8, %9, %10, %11, %12, %13, %14, %15, %16, %17, %18, %19, %20, %21, %22, %23, %24, %25, %26, %27, %28, %29, %30, %31, %32, %33, %34, %35, %36, %37, %38, %39, %40, %41, %42, %43, %44, %45, %46, %47, %48, %49, %50, %51, %52, %53, %54, %55, %56, %57, %58, %59, %60, %61, %62, %63, %64, %65, %66, %67, %68, %69, %70, %71, %72, %73, %74, %75, %76, %77, %78, %79, %80, %81, %82, %83, %84, %85, %86, %87, %88, %89, %90, %91, %92, %93, %94, %95, %96, %97, %98, %99, %100, %101, %102, %103, %104, %105, %106, %107, %108, %109, %110, %111, %112, %113, %114, %115, %116, %117, %118, %119, %120, %121, %122, %123, %124, %125, %126, %127}, %128, %129, p, 1, 1, 0, 1;\n}\n"
        : "+f"(d[0]), "+f"(d[1]), "+f"(d[2]), "+f"(d[3]), "+f"(d[4]), "+f"(d[5]), "+f"(d[6]), "+f"(d[7]), "+f"(d[8]), "+f"(d[9]), "+f"(d[10]), "+f"(d[11]), "+f"(d[12]), "+f"(d[13]), "+f"(d[14]), "+f"(d[15]), "+f"(d[16]), "+f"(d[17]), "+f"(d[18]), "+f"(d[19]), "+f"(d[20]), "+f"(d[21]), "+f"(d[22]), "+f"(d[23]), "+f"(d[24]), "+f"(d[25]), "+f"(d[26]), "+f"(d[27]), "+f"(d[28]), "+f"(d[29]), "+f"(d[30]), "+f"(d[31]), "+f"(d[32]), "+f"(d[33]), "+f"(d[34]), "+f"(d[35]), "+f"(d[36]), "+f"(d[37]), "+f"(d[38]), "+f"(d[39]), "+f"(d[40]), "+f"(d[41]), "+f"(d[42]), "+f"(d[43]), "+f"(d[44]), "+f"(d[45]), "+f"(d[46]), "+f"(d[47]), "+f"(d[48]), "+f"(d[49]), "+f"(d[50]), "+f"(d[51]), "+f"(d[52]), "+f"(d[53]), "+f"(d[54]), "+f"(d[55]), "+f"(d[56]), "+f"(d[57]), "+f"(d[58]), "+f"(d[59]), "+f"(d[60]), "+f"(d[61]), "+f"(d[62]), "+f"(d[63]), "+f"(d[64]), "+f"(d[65]), "+f"(d[66]), "+f"(d[67]), "+f"(d[68]), "+f"(d[69]), "+f"(d[70]), "+f"(d[71]), "+f"(d[72]), "+f"(d[73]), "+f"(d[74]), "+f"(d[75]), "+f"(d[76]), "+f"(d[77]), "+f"(d[78]), "+f"(d[79]), "+f"(d[80]), "+f"(d[81]), "+f"(d[82]), "+f"(d[83]), "+f"(d[84]), "+f"(d[85]), "+f"(d[86]), "+f"(d[87]), "+f"(d[88]), "+f"(d[89]), "+f"(d[90]), "+f"(d[91]), "+f"(d[92]), "+f"(d[93]), "+f"(d[94]), "+f"(d[95]), "+f"(d[96]), "+f"(d[97]), "+f"(d[98]), "+f"(d[99]), "+f"(d[100]), "+f"(d[101]), "+f"(d[102]), "+f"(d[103]), "+f"(d[104]), "+f"(d[105]), "+f"(d[106]), "+f"(d[107]), "+f"(d[108]), "+f"(d[109]), "+f"(d[110]), "+f"(d[111]), "+f"(d[112]), "+f"(d[113]), "+f"(d[114]), "+f"(d[115]), "+f"(d[116]), "+f"(d[117]), "+f"(d[118]), "+f"(d[119]), "+f"(d[120]), "+f"(d[121]), "+f"(d[122]), "+f"(d[123]), "+f"(d[124]), "+f"(d[125]), "+f"(d[126]), "+f"(d[127])
        : "l"(da), "l"(db), "r"(scale_d));
}
__device__ __forceinline__ void stmatrix_x4(uint32_t addr, uint32_t r0, uint32_t r1, uint32_t r2, uint32_t r3) {
    asm volatile("stmatrix.sync.aligned.m8n8.x4.shared.b16 [%0], {%1, %2, %3, %4};" :: "r"(addr), "r"(r0), "r"(r1), "r"(r2), "r"(r3) : "memory");
}
__device__ __forceinline__ void tma_store_2d(const CUtensorMap* map, uint32_t src, int c0, int c1) {
    asm volatile("cp.async.bulk.tensor.2d.global.shared::cta.bulk_group [%0, {%2, %3}], [%1];"
                 :: "l"((uint64_t)map), "r"(src), "r"(c0), "r"(c1) : "memory");
}
__device__ __forceinline__ float ex2f(float x) { float y; asm("ex2.approx.ftz.f32 %0, %1;" : "=f"(y) : "f"(x)); return y; }
__device__ __forceinline__ uint32_t pack_bf16(float lo, float hi) {
    __nv_bfloat162 v = __floats2bfloat162_rn(lo, hi);
    return *reinterpret_cast<uint32_t*>(&v);
}
__device__ __forceinline__ void mma_16816(float (&c)[4], uint32_t a0, uint32_t a1, uint32_t a2, uint32_t a3,
                                          uint32_t b0, uint32_t b1) {
    asm volatile(
        "mma.sync.aligned.m16n8k16.row.col.f32.bf16.bf16.f32 {%0,%1,%2,%3}, {%4,%5,%6,%7}, {%8,%9}, {%0,%1,%2,%3};"
        : "+f"(c[0]), "+f"(c[1]), "+f"(c[2]), "+f"(c[3])
        : "r"(a0), "r"(a1), "r"(a2), "r"(a3), "r"(b0), "r"(b1));
}
__device__ __forceinline__ void ldmatrix_x4_trans(uint32_t& r0, uint32_t& r1, uint32_t& r2, uint32_t& r3, uint32_t addr) {
    asm volatile("ldmatrix.sync.aligned.m8n8.x4.trans.shared.b16 {%0,%1,%2,%3}, [%4];"
                 : "=r"(r0), "=r"(r1), "=r"(r2), "=r"(r3) : "r"(addr));
}

struct AttnParams {
    CUtensorMap mapQ, mapK, mapV;
    CUtensorMap mapO;
    bf16* out;
};
constexpr int FA_SMEM = 2 * 32768 + 2 * 65536 + 32768 + 1024 + 256;
constexpr int FA_ITEMS = 16 * NH;
__device__ __forceinline__ int fa_qt(int t) { return 15 - ((t & 127) >> 3); }
__device__ __forceinline__ int fa_head(int t) { return (t >> 7) * 8 + (t & 7); }
#define FA_TKA 2
#define FA_SPLIT 8

constexpr float FA_MARGIN = 16.f;
#define FAT(b, i)
__device__ __forceinline__ void mbar_arrive_if(uint32_t bar, bool c) {
    asm volatile("{\n.reg .pred p;\nsetp.ne.b32 p, %1, 0;\n@p mbarrier.arrive.shared::cta.b64 _, [%0];\n}" :: "r"(bar), "r"((int)c) : "memory");
}
__device__ __forceinline__ float ex2v(float x) { float y; asm volatile("ex2.approx.ftz.f32 %0, %1;" : "=f"(y) : "f"(x)); return y; }
__device__ __forceinline__ void wgmma_rs_n128_tb_lo(float (&d)[64], const uint32_t* a, uint32_t db_lo, int scale_d) {
    asm volatile(
        "{\n.reg .pred p;\n.reg .b64 db;\nsetp.ne.b32 p, %69, 0;\nmov.b64 db, {%68, 0x40000040};\n"
        "wgmma.mma_async.sync.aligned.m64n128k16.f32.bf16.bf16 " ACC64_STR ", {%64, %65, %66, %67}, db, p, 1, 1, 1;\n}\n"
        : ACC64(d) : "r"(a[0]), "r"(a[1]), "r"(a[2]), "r"(a[3]), "r"(db_lo), "r"(scale_d));
}

__global__ void __launch_bounds__(384, 1) attn_kernel(const __grid_constant__ AttnParams P) {
    extern __shared__ uint8_t smem_raw[];
    uint32_t sbase = (smem_u32(smem_raw) + 1023) & ~1023u;
    const uint32_t sQ = sbase;
    const uint32_t sKV = sbase + 65536;
    const uint32_t sO = sKV + 2 * 65536;
    const uint32_t bars = sO + 32768;
    const uint32_t bar_qf = bars, bar_qe = bars + 16, bar_kf = bars + 32, bar_vf = bars + 48, bar_ke = bars + 64, bar_ve = bars + 80,
                   bar_of = bars + 96, bar_oe = bars + 112, slot = bars + 128, oslot = bars + 136, bar_dummy = bars + 144;
    const int warp = threadIdx.x >> 5;
    TS_BEGIN(1);
    if (threadIdx.x == 256) {
        asm volatile("prefetch.tensormap [%0];" :: "l"(&P.mapQ) : "memory");
        asm volatile("prefetch.tensormap [%0];" :: "l"(&P.mapK) : "memory");
        for (int i = 0; i < 2; i++) {
            mbar_init(bar_qf + 8 * i, 1); mbar_init(bar_qe + 8 * i, 8); mbar_init(bar_kf + 8 * i, 1); mbar_init(bar_vf + 8 * i, 1);
            mbar_init(bar_ke + 8 * i, 8); mbar_init(bar_ve + 8 * i, 8); mbar_init(bar_of + 8 * i, 1); mbar_init(bar_oe + 8 * i, 1);
        }
        mbar_init(bar_dummy, 1);
        asm volatile("fence.mbarrier_init.release.cluster;" ::: "memory");
    }
    __syncthreads();
    pdl_launch_dependents();
    if (warp >= 8) {
        asm volatile("setmaxnreg.dec.sync.aligned.u32 40;");
        if (threadIdx.x == 288 || threadIdx.x == 320) {
            const int wg = threadIdx.x == 288 ? 0 : 1;
            const uint32_t stg = sO + wg * 16384;
            for (int n = 0;; n++) {
                mbar_wait(bar_of + 8 * wg, n & 1);
                int t;
                asm volatile("ld.shared.s32 %0, [%1];" : "=r"(t) : "r"(oslot + wg * 4) : "memory");
                const int qt = fa_qt(t), h = fa_head(t & 1023);
                tma_store_2d(&P.mapO, stg, 0, h * SEQ + qt * 128 + wg * 64);
                tma_store_2d(&P.mapO, stg + 8192, 64, h * SEQ + qt * 128 + wg * 64);
                asm volatile("cp.async.bulk.commit_group;" ::: "memory");
                asm volatile("cp.async.bulk.wait_group.read 0;" ::: "memory");
                mbar_arrive(bar_oe + 8 * wg);
                asm volatile("cp.async.bulk.wait_group 0;" ::: "memory");
                signal_ctr(CT_CA + qt * 4 + (h >> 3));
                if (t >= 1024) break;
            }
        }
        if (threadIdx.x == 256) {
            int b = 0, hp_ready = 0, vrow = 0, t = blockIdx.x;
            auto load_v = [&](int i) {
                const uint32_t sv = sKV + (i & 1) * 65536 + 32768, bar = bar_vf + 8 * (i & 1);
                mbar_wait(bar_ve + 8 * (i & 1), ((i >> 1) & 1) ^ 1);
                mbar_expect_tx(bar, 32768);
                tma_load_2d(sv, &P.mapV, bar, 0, vrow);
                tma_load_2d(sv + 16384, &P.mapV, bar, 64, vrow);
            };
            for (int item = 0;; item++) {
                const bool valid = t < FA_ITEMS;
                const int qt = fa_qt(t), h = fa_head(t);
                if (valid && !((hp_ready >> (h >> 1)) & 1)) { wait_ctr(CT_AP + (h >> 1), 96u); hp_ready |= 1 << (h >> 1); }
                const uint32_t bq = bar_qf + 8 * (item & 1);
                mbar_wait(bar_qe + 8 * (item & 1), ((item >> 1) & 1) ^ 1);
                asm volatile("st.shared.s32 [%0], %1;" :: "r"(slot + (item & 1) * 4), "r"(valid ? t : -1) : "memory");
                if (!valid) { mbar_arrive(bq); break; }
                mbar_expect_tx(bq, 32768);
                tma_load_2d(sQ + (item & 1) * 32768, &P.mapQ, bq, 0, h * SEQ + qt * 128);
                tma_load_2d(sQ + (item & 1) * 32768 + 16384, &P.mapQ, bq, 64, h * SEQ + qt * 128);
#pragma unroll 1
                for (int j = 0; j <= qt; j++, b++) {
                    const uint32_t sk = sKV + (b & 1) * 65536, bar = bar_kf + 8 * (b & 1);
                    mbar_wait(bar_ke + 8 * (b & 1), ((b >> 1) & 1) ^ 1);
                    mbar_expect_tx(bar, 32768);
                    tma_load_2d(sk, &P.mapK, bar, 0, h * SEQ + j * 128);
                    tma_load_2d(sk + 16384, &P.mapK, bar, 64, h * SEQ + j * 128);
                    if (j == max(qt - FA_TKA, 0)) t = take_ticket(CT_ATTN);
                    if (b > 0) load_v(b - 1);
                    vrow = h * SEQ + j * 128;
                }
                if (item == 0) wait_ctr(CT_GATE, 64u);
                t += gridDim.x;
            }
            load_v(b - 1);
        }
    } else {
        asm volatile("setmaxnreg.inc.sync.aligned.u32 232;");
        const int wg = warp >> 2;
        const int lane = threadIdx.x & 31;
        const float sc = 0.08838834764831845f * 1.4426950408889634f;
        const int r0 = wg * 64 + (warp & 3) * 16 + (lane >> 2);
        float o[64], s[64];
        uint32_t pa[32];
        float m0 = 0.f, m1 = 0.f, l0 = 0.f, l1 = 0.f, i0 = 0.f, i1 = 0.f;
        const uint32_t q_lo = desc_lo(sQ + wg * 8192, 16), k_lo = desc_lo(sKV, 16), v_lo = desc_lo(sKV + 32768, 16384);
        auto issue_qk = [&](int b, int item) {
            const uint32_t qd = q_lo + (item & 1) * 2048, kd = k_lo + (b & 1) * 4096;
            mbar_wait(bar_kf + 8 * (b & 1), (b >> 1) & 1);
            wgmma_fence();
#pragma unroll
            for (int kk = 0; kk < 8; kk++) wgmma_ss_n128_lo<0>(s, qd + (kk >> 2) * 1024 + (kk & 3) * 2, kd + (kk >> 2) * 1024 + (kk & 3) * 2, kk != 0);
            wgmma_commit();
        };
        auto issue_pv = [&](int b, bool acc) {
            const uint32_t vd = v_lo + (b & 1) * 4096;
            mbar_wait(bar_vf + 8 * (b & 1), (b >> 1) & 1);
            wgmma_fence();
#pragma unroll
            for (int kk = 0; kk < 8; kk++) wgmma_rs_n128_tb_lo(o, &pa[kk * 4], vd + kk * 128, kk ? 1 : (int)acc);
            wgmma_commit();
        };
        auto mask_diag = [&]() {
            const int lim = r0 - (lane & 3) * 2;
#pragma unroll
            for (int i = 0; i < 64; i++)
                if ((i >> 2) * 8 + (i & 1) - ((i & 2) ? 8 : 0) > lim) s[i] = -INFINITY;
        };
        auto softmax = [&](bool fresh, int b) {
            bool refresh = fresh;
#pragma unroll 1
            for (;;) {
                if (refresh) {
                    float x[8];
#pragma unroll
                    for (int i = 0; i < 8; i++) x[i] = fmaxf(s[i * 2], s[i * 2 + 1]);
#pragma unroll
                    for (int i = 8; i < 32; i++) x[i & 7] = fmaxf(x[i & 7], fmaxf(s[i * 2], s[i * 2 + 1]));
                    float x0 = fmaxf(fmaxf(x[0], x[2]), fmaxf(x[4], x[6])), x1 = fmaxf(fmaxf(x[1], x[3]), fmaxf(x[5], x[7]));
                    x0 = fmaxf(x0, __shfl_xor_sync(0xffffffff, x0, 1)); x1 = fmaxf(x1, __shfl_xor_sync(0xffffffff, x1, 1));
                    x0 = fmaxf(x0, __shfl_xor_sync(0xffffffff, x0, 2)); x1 = fmaxf(x1, __shfl_xor_sync(0xffffffff, x1, 2));
                    x0 = fmaf(x0, sc, FA_MARGIN); x1 = fmaf(x1, sc, FA_MARGIN);
                    if (!fresh) {
                        x0 = fmaxf(x0, m0); x1 = fmaxf(x1, m1);
                        const float a0 = ex2f(m0 - x0), a1 = ex2f(m1 - x1);
                        l0 *= a0; l1 *= a1;
                        wgmma_wait<0>();
#pragma unroll
                        for (int i = 0; i < 16; i++) { o[i * 4 + 0] *= a0; o[i * 4 + 1] *= a0; o[i * 4 + 2] *= a1; o[i * 4 + 3] *= a1; }
                    }
                    m0 = x0; m1 = x1;
                }
                float p[64], u[4] = {0.f, 0.f, 0.f, 0.f};
#pragma unroll
                for (int i = 0; i < 64; i++) {
                    if (i == FA_SPLIT * 4) {
                        FAT(b, 2);
                        mbar_wait(bar_dummy, 1);
                        wgmma_wait<0>();
                        FAT(b - 1, 3);
                        mbar_arrive_if(bar_ve + 8 * ((b - 1) & 1), lane == 0 && refresh == fresh && b > 0);
                    }
                    p[i] = ex2v(fmaf(s[i], sc, (i & 2) ? -m1 : -m0));
                    u[i & 3] += p[i];
                }
#pragma unroll
                for (int i = 0; i < 32; i++) pa[i] = pack_bf16(p[i * 2], p[i * 2 + 1]);
                u[0] += u[1]; u[2] += u[3];
                if (refresh || !__any_sync(0xffffffff, !(u[0] + u[2] < 1.f))) { l0 += u[0]; l1 += u[2]; break; }
                refresh = true;
            }
        };
        auto finish_rows = [&](int t) {
            const float g0 = __ldcg(g_gate + fa_qt(t) * 128 + r0), g1 = __ldcg(g_gate + fa_qt(t) * 128 + r0 + 8);
            l0 += __shfl_xor_sync(0xffffffff, l0, 1); l1 += __shfl_xor_sync(0xffffffff, l1, 1);
            l0 += __shfl_xor_sync(0xffffffff, l0, 2); l1 += __shfl_xor_sync(0xffffffff, l1, 2);
            i0 = __fdividef(g0, l0); i1 = __fdividef(g1, l1);
        };
        auto store_o = [&](int t, int n) {
            const uint32_t stg = sO + wg * 16384;
            mbar_wait(bar_oe + 8 * wg, (n & 1) ^ 1);
            const int row = (warp & 3) * 16 + (lane >> 2);
#pragma unroll
            for (int i = 0; i < 4; i++) {
                const int ch = i * 4 + (lane & 3);
                const uint32_t a = stg + (ch >> 3) * 8192 + row * 128 + (((ch & 7) ^ (row & 7)) << 4);
                const float* q = &o[i * 16];
                asm volatile("st.shared.v4.b32 [%0], {%1, %2, %3, %4};" :: "r"(a), "r"(pack_bf16(q[0] * i0, q[1] * i0)), "r"(pack_bf16(q[4] * i0, q[5] * i0)),
                             "r"(pack_bf16(q[8] * i0, q[9] * i0)), "r"(pack_bf16(q[12] * i0, q[13] * i0)) : "memory");
                asm volatile("st.shared.v4.b32 [%0], {%1, %2, %3, %4};" :: "r"(a + 1024), "r"(pack_bf16(q[2] * i1, q[3] * i1)), "r"(pack_bf16(q[6] * i1, q[7] * i1)),
                             "r"(pack_bf16(q[10] * i1, q[11] * i1)), "r"(pack_bf16(q[14] * i1, q[15] * i1)) : "memory");
            }
            if ((t & 1023) >= 384) {
                bf16* z = P.out + (size_t)(fa_qt(t) * 128 + wg * 64 + ((threadIdx.x & 127) >> 3)) * DM + (t & 7) * 64 + (lane & 7) * 8;
#pragma unroll
                for (int i = 0; i < 4; i++) *reinterpret_cast<uint4*>(z + i * 16 * DM) = make_uint4(0u, 0u, 0u, 0u);
            }
            asm volatile("fence.proxy.async.shared::cta;" ::: "memory");
            asm volatile("bar.sync %0, 128;" :: "r"(3 + wg) : "memory");
            if ((threadIdx.x & 127) == 0) {
                asm volatile("st.shared.s32 [%0], %1;" :: "r"(oslot + wg * 4), "r"(t) : "memory");
                mbar_arrive(bar_of + 8 * wg);
            }
            __syncwarp();
        };
        int t = blockIdx.x, item = 0, left = fa_qt(t), tdone = -1, b = 1, nout = 0;
        bool first = true;
        if (wg == 1) asm volatile("bar.arrive 1, 256;" ::: "memory");
        mbar_wait(bar_qf, 0);
        asm volatile("bar.sync %0, 256;" :: "r"(1 + wg) : "memory");
        issue_qk(0, 0);
        asm volatile("bar.arrive %0, 256;" :: "r"(2 - wg) : "memory");
        wgmma_wait<0>();
        mbar_arrive_if(bar_ke, lane == 0);
        mbar_arrive_if(bar_qe, lane == 0 && left == 0);
        if (left == 0) mask_diag();
        softmax(true, 0);
#pragma unroll 1
        for (;; b++) {
            const bool fresh = left == 0;
            const int tprev = t;
            if (fresh) {
                item++;
                mbar_wait(bar_qf + 8 * (item & 1), (item >> 1) & 1);
                asm volatile("ld.shared.s32 %0, [%1];" : "=r"(t) : "r"(slot + (item & 1) * 4) : "memory");
                if (t < 0) { t = tprev; break; }
                left = fa_qt(t) + 1;
            }
            left--;
            asm volatile("bar.sync %0, 256;" :: "r"(1 + wg) : "memory");
            FAT(b, 0);
            issue_qk(b, item);
            if (tdone >= 0) {
                asm volatile("bar.arrive %0, 256;" :: "r"(2 - wg) : "memory");
                store_o(tdone, nout++);
            }
            issue_pv(b - 1, !first);
            if (tdone < 0) asm volatile("bar.arrive %0, 256;" :: "r"(2 - wg) : "memory");
            tdone = -1;
            if (fresh) { finish_rows(tprev); tdone = tprev; l0 = l1 = 0.f; }
            first = fresh;
            wgmma_wait<1>();
            FAT(b, 1);
            mbar_arrive_if(bar_ke + 8 * (b & 1), lane == 0);
            mbar_arrive_if(bar_qe + 8 * (item & 1), lane == 0 && left == 0);
            if (left == 0) mask_diag();
            softmax(fresh, b);
        }
        if (tdone >= 0) store_o(tdone, nout++);
        issue_pv(b - 1, !first);
        finish_rows(t);
        wgmma_wait<0>();
        store_o(t + 1024, nout);
        TS_END(1);
    }
}

__device__ __forceinline__ uint32_t cluster_ctarank() {
    uint32_t r; asm volatile("mov.u32 %0, %%cluster_ctarank;" : "=r"(r)); return r;
}
__device__ __forceinline__ uint32_t mapa_u32(uint32_t addr, uint32_t rank) {
    uint32_t r; asm volatile("mapa.shared::cluster.u32 %0, %1, %2;" : "=r"(r) : "r"(addr), "r"(rank)); return r;
}
__device__ __forceinline__ void cluster_sync_all() {
    asm volatile("barrier.cluster.arrive.release.aligned;\nbarrier.cluster.wait.acquire.aligned;" ::: "memory");
}
__device__ __forceinline__ void st_async_v4(uint32_t addr, uint32_t a, uint32_t b, uint32_t c, uint32_t d, uint32_t mbar) {
    asm volatile("st.async.weak.shared::cluster.mbarrier::complete_tx::bytes.v4.b32 [%0], {%1, %2, %3, %4}, [%5];"
                 :: "r"(addr), "r"(a), "r"(b), "r"(c), "r"(d), "r"(mbar) : "memory");
}
__device__ __forceinline__ void st_async_v2(uint32_t addr, uint32_t a, uint32_t b, uint32_t mbar) {
    asm volatile("st.async.weak.shared::cluster.mbarrier::complete_tx::bytes.v2.b32 [%0], {%1, %2}, [%3];"
                 :: "r"(addr), "r"(a), "r"(b), "r"(mbar) : "memory");
}
__device__ __forceinline__ void st_async_b32(uint32_t addr, uint32_t a, uint32_t mbar) {
    asm volatile("st.async.weak.shared::cluster.mbarrier::complete_tx::bytes.b32 [%0], %1, [%2];" :: "r"(addr), "r"(a), "r"(mbar) : "memory");
}
__device__ __forceinline__ void pace(int cycles) {
    if (cycles > 0) {
        uint32_t t0, t;
        asm volatile("mov.u32 %0, %%clock;" : "=r"(t0));
        do { asm volatile("mov.u32 %0, %%clock;" : "=r"(t)); } while (t - t0 < (uint32_t)cycles);
    }
}
__device__ __forceinline__ void mbar_wait_cl(uint32_t bar, uint32_t parity) {
    uint32_t done = 0;
    for (int it = 0; it < WAIT_LIMIT && !done; it++) {
        asm volatile(
            "{\n.reg .pred p;\n"
            "mbarrier.try_wait.parity.shared::cta.b64 p, [%1], %2;\n"
            "selp.u32 %0, 1, 0, p;\n}\n" : "=r"(done) : "r"(bar), "r"(parity) : "memory");
    }
}
__device__ __forceinline__ uint32_t mbar_test(uint32_t bar, uint32_t parity) {
    uint32_t done;
    asm volatile(
        "{\n.reg .pred p;\n"
        "mbarrier.test_wait.parity.shared::cta.b64 p, [%1], %2;\n"
        "selp.u32 %0, 1, 0, p;\n}\n" : "=r"(done) : "r"(bar), "r"(parity) : "memory");
    return done;
}
__device__ __forceinline__ void ldmatrix_x4(uint32_t& r0, uint32_t& r1, uint32_t& r2, uint32_t& r3, uint32_t addr) {
    asm volatile("ldmatrix.sync.aligned.m8n8.x4.shared.b16 {%0,%1,%2,%3}, [%4];"
                 : "=r"(r0), "=r"(r1), "=r"(r2), "=r"(r3) : "r"(addr));
}
__device__ __forceinline__ void cp_async16(uint32_t dst, const void* src) {
    asm volatile("cp.async.cg.shared.global [%0], [%1], 16;" :: "r"(dst), "l"(src) : "memory");
}
__device__ __forceinline__ float bf16r(float x) { return __uint_as_float(pack_bf16(0.f, x) & 0xffff0000u); }

#define DBG(i, w)
#define DBGD(i, w, dep)
#define DBG_EXTRA 0
__device__ __forceinline__ void tma_load_2d_mc(uint32_t dst, const CUtensorMap* map, uint32_t bar, int c0, int c1, uint16_t mask) {
    asm volatile(
        "cp.async.bulk.tensor.2d.shared::cluster.global.mbarrier::complete_tx::bytes.multicast::cluster [%0], [%1, {%3, %4}], [%2], %5;"
        :: "r"(dst), "l"((uint64_t)map), "r"(bar), "r"(c0), "r"(c1), "h"(mask) : "memory");
}
__device__ __forceinline__ void stmatrix_x4_trans(uint32_t addr, uint32_t r0, uint32_t r1, uint32_t r2, uint32_t r3) {
    asm volatile("stmatrix.sync.aligned.m8n8.x4.trans.shared.b16 [%0], {%1, %2, %3, %4};" :: "r"(addr), "r"(r0), "r"(r1), "r"(r2), "r"(r3) : "memory");
}
__device__ __forceinline__ void stmatrix_x2_trans(uint32_t addr, uint32_t r0, uint32_t r1) {
    asm volatile("stmatrix.sync.aligned.m8n8.x2.trans.shared.b16 [%0], {%1, %2};" :: "r"(addr), "r"(r0), "r"(r1) : "memory");
}
__device__ __forceinline__ uint4 lds128(uint32_t a) {
    uint4 v; asm volatile("ld.shared.v4.u32 {%0, %1, %2, %3}, [%4];" : "=r"(v.x), "=r"(v.y), "=r"(v.z), "=r"(v.w) : "r"(a) : "memory"); return v;
}
__device__ __forceinline__ void sts128(uint32_t a, uint32_t x, uint32_t y, uint32_t z, uint32_t w) {
    asm volatile("st.shared.v4.b32 [%0], {%1, %2, %3, %4};" :: "r"(a), "r"(x), "r"(y), "r"(z), "r"(w) : "memory");
}
__device__ __forceinline__ float2 lds64f(uint32_t a) {
    float2 v; asm volatile("ld.shared.v2.f32 {%0, %1}, [%2];" : "=f"(v.x), "=f"(v.y) : "r"(a) : "memory"); return v;
}
__device__ __forceinline__ void fence_async_smem() { asm volatile("fence.proxy.async.shared::cta;" ::: "memory"); }
#define ACC16(d) "+f"(d[0]), "+f"(d[1]), "+f"(d[2]), "+f"(d[3]), "+f"(d[4]), "+f"(d[5]), "+f"(d[6]), "+f"(d[7]), "+f"(d[8]), "+f"(d[9]), "+f"(d[10]), "+f"(d[11]), "+f"(d[12]), "+f"(d[13]), "+f"(d[14]), "+f"(d[15])
template <int ND>
__device__ __forceinline__ void wgmma_rs_n32(float (&d)[ND], const uint32_t (&a)[4], uint32_t db_lo, int scale_d) {
    asm volatile(
        "{\n.reg .pred p;\n.reg .b64 db;\nsetp.ne.b32 p, %21, 0;\nmov.b64 db, {%20, 0x40000040};\n"
        "wgmma.mma_async.sync.aligned.m64n32k16.f32.bf16.bf16 {%0,%1,%2,%3,%4,%5,%6,%7,%8,%9,%10,%11,%12,%13,%14,%15}, {%16,%17,%18,%19}, db, p, 1, 1, 0;\n}\n"
        : ACC16(d) : "r"(a[0]), "r"(a[1]), "r"(a[2]), "r"(a[3]), "r"(db_lo), "r"(scale_d));
}
template <int ND>
__device__ __forceinline__ void wgmma_ss_n32(float (&d)[ND], uint32_t da_lo, uint32_t db_lo, int scale_d) {
    asm volatile(
        "{\n.reg .pred p;\n.reg .b64 da, db;\nsetp.ne.b32 p, %18, 0;\nmov.b64 da, {%16, 0x40000040};\nmov.b64 db, {%17, 0x40000040};\n"
        "wgmma.mma_async.sync.aligned.m64n32k16.f32.bf16.bf16 {%0,%1,%2,%3,%4,%5,%6,%7,%8,%9,%10,%11,%12,%13,%14,%15}, da, db, p, 1, 1, 1, 0;\n}\n"
        : ACC16(d) : "r"(da_lo), "r"(db_lo), "r"(scale_d));
}
__device__ __forceinline__ void wgmma_ss_n8(float (&d)[4], uint32_t da_lo, uint32_t db_lo, int scale_d) {
    asm volatile(
        "{\n.reg .pred p;\n.reg .b64 da, db;\nsetp.ne.b32 p, %6, 0;\nmov.b64 da, {%4, 0x40000040};\nmov.b64 db, {%5, 0x00000010};\n"
        "wgmma.mma_async.sync.aligned.m64n8k16.f32.bf16.bf16 {%0,%1,%2,%3}, da, db, p, 1, 1, 1, 0;\n}\n"
        : "+f"(d[0]), "+f"(d[1]), "+f"(d[2]), "+f"(d[3]) : "r"(da_lo), "r"(db_lo), "r"(scale_d));
}

#define SCHED_FENCE()
__device__ __forceinline__ void wgmma_ss_n32_p(float (&d)[16], uint32_t da_lo, uint32_t db_lo, int scale_d) {
    asm volatile(
        "{\n.reg .pred p;\n.reg .b64 da, db;\nsetp.ne.b32 p, %18, 0;\nmov.b64 da, {%16, 0x40000040};\nmov.b64 db, {%17, 0x00000030};\n"
        "wgmma.mma_async.sync.aligned.m64n32k16.f32.bf16.bf16 {%0,%1,%2,%3,%4,%5,%6,%7,%8,%9,%10,%11,%12,%13,%14,%15}, da, db, p, 1, 1, 1, 0;\n}\n"
        : ACC16(d) : "r"(da_lo), "r"(db_lo), "r"(scale_d));
}

__device__ __forceinline__ void wgmma_ss_n32_kk(float (&d)[16], uint32_t da_lo, uint32_t db_lo, int scale_d) {
    asm volatile(
        "{\n.reg .pred p;\n.reg .b64 da, db;\nsetp.ne.b32 p, %18, 0;\nmov.b64 da, {%16, 0x40000040};\nmov.b64 db, {%17, 0x40000040};\n"
        "wgmma.mma_async.sync.aligned.m64n32k16.f32.bf16.bf16 {%0,%1,%2,%3,%4,%5,%6,%7,%8,%9,%10,%11,%12,%13,%14,%15}, da, db, p, 1, 1, 0, 0;\n}\n"
        : ACC16(d) : "r"(da_lo), "r"(db_lo), "r"(scale_d));
}

struct ChainParams {
    CUtensorMap mapW[3];
    CUtensorMap mapX;
    CUtensorMap mapC;
};
constexpr int CH_BLOCK = 384;
constexpr int CO_WO = 0;
constexpr int CO_XB = 65536;
constexpr int CO_MB = CO_XB + 65536;
constexpr int CO_OB = CO_MB + 8192;
constexpr int CH_TW = 6144, CH_TP = 3 * CH_TW;
constexpr int CO_T = CO_OB + 8192;
constexpr int CO_SC = CO_T + 2 * CH_TP;
constexpr int CO_LS = CO_SC + 2 * 1280;
constexpr int CO_LO = CO_LS + 8 * 1280;
constexpr int CO_P = CO_LO + 4 * 1280;
constexpr int CO_ST = 205824;
#define CH_NSM 3
constexpr int CO_WA = CO_ST + 4096;
constexpr int CO_BAR = CO_WA + CH_TP;
constexpr int CH_SMEM = CO_BAR + 256 + 1024 + DBG_EXTRA;
static_assert(CO_WA >= 3 * 65536 && CO_P + 3072 <= CO_ST && CH_NSM <= 3, "smem layout");
#define CH_POLL_DELAY 0
#define CH_PEARLY 0
#define CH_VPOS 2
#define CH_VST 0
#define CH_V3_DELAY 0
#define CH_LSPOS 1
#define CH_V1 0
#define CH_V2 24
#define CH_V3 32
#define CH_OG 2
#define CH_OW 8
#define CH_OF 12
#define CH_CHAINS 4

constexpr float CH_SC = 0.08838834764831845f * 1.4426950408889634f;
__device__ __forceinline__ uint32_t pin(uint32_t v) { return __shfl_sync(0xffffffff, v, threadIdx.x & 31); }

__global__ void __cluster_dims__(8, 1, 1) __launch_bounds__(CH_BLOCK, 1)
chain_kernel(const __grid_constant__ ChainParams P, const bf16* __restrict__ mem0, const bf16* __restrict__ Wo, const bf16* __restrict__ x,
             const bf16* __restrict__ gate_w) {
    extern __shared__ uint8_t smem_raw[];
    const uint32_t sb = (smem_u32(smem_raw) + 1023) & ~1023u;
    const int tid = threadIdx.x, warp = __shfl_sync(0xffffffff, tid >> 5, 0), lane = tid & 31;
    const int rank = (int)cluster_ctarank();
    const int C = blockIdx.x >> 3;
    const int h = C * 4 + (rank >> 1);
    const int qd = lane >> 2, qc = lane & 3;
    const int t4 = warp & 3, wg = warp >> 2;
    pdl_launch_dependents();
    TS_BEGIN(2);
    const uint32_t bar_mem = sb + CO_BAR, bar_o = bar_mem + 32, bar_sc = bar_o + 32, bar_x = bar_sc + 8, bar_l = bar_x + 16, bar_w = bar_l + 8;
    if (tid == 0) {
        for (int j = 0; j < 15; j++) mbar_init(bar_mem + 8 * j, bar_mem + 8 * j == bar_l ? 4 : 1);
        asm volatile("fence.mbarrier_init.release.cluster;" ::: "memory");
    }
    __syncthreads();
    if ((tid & 127) == 0) {
        mbar_expect_tx(bar_w + 8 * wg, 65536);
        for (int i = 0; i < 8; i++)
            tma_load_2d(sb + wg * 65536 + i * 8192, &P.mapW[wg], bar_w + 8 * wg, h * HD + (rank & 1) * 64, i * 64);
    }
    {
        for (int i = tid; i < 512; i += CH_BLOCK) asm volatile("prefetch.global.L2 [%0];" :: "l"(Wo + (size_t)(C * 512 + i) * DM + rank * 64));
        if (tid < 64) asm volatile("prefetch.global.L2 [%0];" :: "l"(x + (size_t)tid * DM + rank * 64));
    }
    if (tid < 256) {
        const int r = blockIdx.x * 32 + (tid >> 3);
        float sum = 0.f;
#pragma unroll
        for (int c = 0; c < 8; c++) {
            const int col = c * 64 + (tid & 7) * 8;
            const uint4 xv = __ldg(reinterpret_cast<const uint4*>(x + (size_t)r * DM + col));
            const uint4 gv = __ldg(reinterpret_cast<const uint4*>(gate_w + col));
            const bf16* xp = reinterpret_cast<const bf16*>(&xv);
            const bf16* gp = reinterpret_cast<const bf16*>(&gv);
#pragma unroll
            for (int e = 0; e < 8; e++) sum += bf16r(__bfloat162float(xp[e]) * __bfloat162float(gp[e]));
        }
        sum += __shfl_xor_sync(0xffffffff, sum, 1);
        sum += __shfl_xor_sync(0xffffffff, sum, 2);
        sum += __shfl_xor_sync(0xffffffff, sum, 4);
        if ((tid & 7) == 0) g_gate[r] = bf16r(1.f / (1.f + __expf(-bf16r(sum))));
        asm volatile("bar.sync 1, 256;" ::: "memory");
        if (tid == 32) signal_ctr_generic(CT_GATE);
    }
    auto chunk = [&](int i) { return (uint32_t)((rank - (i >> 1) - 4 * (i & 1)) & 7); };
    const uint32_t wfrag = (((lane >> 4) << 3) + (lane & 7)) * 128 + (((t4 * 2 + ((lane >> 3) & 1)) ^ (lane & 7)) << 4);
    const uint32_t aO = pin(sb + wg * CH_TW + wfrag);
    const uint32_t aM = pin(sb + (lane & 7) * 128 + (((lane >> 3) ^ (lane & 7)) << 4));
    const uint32_t aL = pin(sb + lane * 8);
    uint32_t w[32][4];
    float d[16];
    mbar_wait(bar_w + 8 * wg, 0);
#pragma unroll
    for (int e = CH_NSM; e < 32; e++) ldmatrix_x4_trans(w[e][0], w[e][1], w[e][2], w[e][3], sb + wg * 65536 + wfrag + chunk(e >> 2) * 8192 + (e & 3) * 2048);
#pragma unroll
    for (int e = 0; e < CH_NSM; e++) {
        const uint4 u = lds128(sb + wg * 65536 + chunk(0) * 8192 + e * 2048 + (tid & 127) * 16);
        sts128(sb + CO_WA + wg * CH_TW + e * 2048 + (tid & 127) * 16, u.x, u.y, u.z, u.w);
    }
    fence_async_smem();
    __syncthreads();
    if (tid == 0) {
        fence_async_smem();
        for (int b = 0; b < 2; b++) {
            mbar_expect_tx(bar_x + 8 * b, 32768);
            for (int i = 0; i < 8; i++) tma_load_2d(sb + CO_XB + b * 32768 + i * 4096, &P.mapX, bar_x + 8 * b, i * 64, b * SEGL);
        }
    }
#pragma unroll 2
    for (int i = tid; i < 512 * 4; i += CH_BLOCK) {
        const int r = i >> 2, cg = i & 3, ks = r >> 4, kp = r & 15;
        const int src = (rank - (ks >> 2)) & 7;
        const uint4* p = reinterpret_cast<const uint4*>(Wo + (size_t)(C * 512 + src * 64 + (ks & 3) * 16 + (kp >> 2) * 2 + (kp & 1) + (kp & 2) * 4) * DM + rank * 64 + cg * 16);
        const uint4 u0 = __ldg(p), u1 = __ldg(p + 1);
        const uint32_t a = sb + CO_WO + r * 128;
        sts128(a + (((cg * 2) ^ (r & 7)) << 4), __byte_perm(u0.x, u0.y, 0x5410), __byte_perm(u0.z, u0.w, 0x5410), __byte_perm(u1.x, u1.y, 0x5410), __byte_perm(u1.z, u1.w, 0x5410));
        sts128(a + (((cg * 2 + 1) ^ (r & 7)) << 4), __byte_perm(u0.x, u0.y, 0x7632), __byte_perm(u0.z, u0.w, 0x7632), __byte_perm(u1.x, u1.y, 0x7632), __byte_perm(u1.z, u1.w, 0x7632));
    }
#pragma unroll 1
    for (int i = tid; i < 512; i += CH_BLOCK) {
        const int n = i >> 6, c = i & 63;
        const uint4 u = __ldg(reinterpret_cast<const uint4*>(mem0 + n * DM + chunk(c >> 3) * 64 + (c & 7) * 8));
        sts128(sb + CO_MB + (c >> 3) * 1024 + n * 128 + (((c & 7) ^ n) << 4), u.x, u.y, u.z, u.w);
    }
    if (tid < 128) sts128(sb + CO_T + (tid >> 6) * CH_TP + 2 * CH_TW + 5120 + (tid & 63) * 16, 0u, 0u, 0u, 0u);
    else if (tid < 160) sts128(sb + CO_P + ((tid >> 3) & 3) * 768 + 640 + (tid & 7) * 16, 0u, 0u, 0u, 0u);
    fence_async_smem();
    TS_END(6);
    auto pass32 = [&](int b, int e0 = 0, int e1 = 32) {
        const uint32_t lo = desc_lo(sb + CO_XB + b * 32768, 16);
        wgmma_fence();
#pragma unroll
        for (int e = 0; e < 32; e++) if (e >= e0 && e < e1) {
            const uint32_t db = lo + chunk(e >> 2) * 256 + (e & 3) * 2;
            if (e < CH_NSM) wgmma_ss_n32(d, desc_lo(sb + CO_WA + wg * CH_TW + e * 2048, 16), db, e != 0);
            else wgmma_rs_n32(d, w[e], db, e != 0);
        }
        wgmma_commit();
    };
    auto store32 = [&](uint32_t a) {
        stmatrix_x4_trans(a, pack_bf16(d[0], d[1]), pack_bf16(d[2], d[3]), pack_bf16(d[4], d[5]), pack_bf16(d[6], d[7]));
        stmatrix_x4_trans(a + 2048, pack_bf16(d[8], d[9]), pack_bf16(d[10], d[11]), pack_bf16(d[12], d[13]), pack_bf16(d[14], d[15]));
    };
    auto mem_proj = [&](int s, bool wait, bool arrive = false) {
        const uint32_t par = s & 1;
        float acc[CH_CHAINS][4];
#pragma unroll
        for (int i = 0; i < CH_CHAINS; i++) acc[i][0] = acc[i][1] = acc[i][2] = acc[i][3] = 0.f;
        const uint32_t aM2 = aM ^ 64;
        uint32_t b[2][8];
        auto load = [&](int c) {
            if (wait && !(c & 1)) mbar_wait_cl(bar_mem + 4 * c, par ^ 1);
            if (c == 0) DBG(11, 0);
            if (c == 6) DBG(13, 0);
            ldmatrix_x4(b[c & 1][0], b[c & 1][1], b[c & 1][2], b[c & 1][3], aM + CO_MB + c * 1024);
            ldmatrix_x4(b[c & 1][4], b[c & 1][5], b[c & 1][6], b[c & 1][7], aM2 + CO_MB + c * 1024);
        };
        load(0);
#pragma unroll
        for (int c = 0; c < 8; c++) {
            if (c < 7) load(c + 1);
            SCHED_FENCE();
#pragma unroll
            for (int i = 0; i < 4; i++) {
                const int e = c * 4 + i;
                mma_16816(acc[i % CH_CHAINS], w[e][0], w[e][1], w[e][2], w[e][3], b[c & 1][i * 2], b[c & 1][i * 2 + 1]);
            }
        }
        if (CH_CHAINS == 4) {
#pragma unroll
            for (int i = 0; i < 4; i++) { acc[0][i] += acc[2 % CH_CHAINS][i]; acc[1][i] += acc[3 % CH_CHAINS][i]; }
        }
        const uint32_t r0 = pack_bf16(acc[0][0] + acc[1][0], acc[0][1] + acc[1][1]);
        const uint32_t r1 = pack_bf16(acc[0][2] + acc[1][2], acc[0][3] + acc[1][3]);
        DBGD(40 + warp, warp, r0 ^ r1);
        stmatrix_x2_trans(aO + par * CH_TP + CO_T + 4096, r0, r1);
    };
    auto load_wa = [&]() {
#pragma unroll
        for (int e = 0; e < CH_NSM; e++) ldmatrix_x4_trans(w[e][0], w[e][1], w[e][2], w[e][3], aO + CO_WA + e * 2048);
    };
    auto remote = [](uint32_t a, uint32_t r) { return mapa_u32(a, r); };
    mbar_wait(bar_x, 0);
    pass32(0);
    wgmma_wait<0>();
    store32(aO + CO_T);
    fence_async_smem();
    __syncthreads();
    cluster_sync_all();
    TS_BEGIN(5);

    if (wg < 2) {
        const uint32_t aQ = pin(sb + CO_T + qd * 128 + (((2 * qc) ^ qd) << 4));
        auto local_scores = [&](int s) {
            const uint32_t tb = sb + CO_T + (s & 1) * CH_TP;
            wgmma_fence();
#pragma unroll
            for (int ks = 0; ks < 4; ks++) wgmma_ss_n32_kk(d, desc_lo(tb + CH_TW, 16) + ks * 2, desc_lo(tb, 16) + ks * 2, ks != 0);
            wgmma_commit();
            wgmma_wait<0>();
            const uint32_t rb = remote(bar_l, rank ^ 1);
            if (t4 < 2) {
                const uint32_t off = 2 * aL - sb + t4 * 512;
#pragma unroll
                for (int j = 0; j < 4; j++) if (j >= 2 || t4 == 0) {
                    st_async_v4(remote(off + (s & 1) * 5120 + CO_LS + j * 1280, rank ^ 1), __float_as_uint(d[4 * j]), __float_as_uint(d[4 * j + 1]), __float_as_uint(d[4 * j + 2]), __float_as_uint(d[4 * j + 3]), rb);
                    sts128(off + CO_LO + j * 1280, __float_as_uint(d[4 * j]), __float_as_uint(d[4 * j + 1]), __float_as_uint(d[4 * j + 2]), __float_as_uint(d[4 * j + 3]));
                }
            } else if (t4 == 2) {
#pragma unroll
                for (int j = 0; j < 4; j++) {
                    st_async_v2(remote(aL + (s & 1) * 5120 + CO_LS + 1024 + j * 1280, rank ^ 1), __float_as_uint(d[4 * j]), __float_as_uint(d[4 * j + 1]), rb);
                    asm volatile("st.shared.v2.f32 [%0], {%1, %2};" :: "r"(aL + CO_LO + 1024 + j * 1280), "f"(d[4 * j]), "f"(d[4 * j + 1]) : "memory");
                }
            }
            __syncwarp();
            if (t4 < 3 && lane == 0) mbar_arrive(bar_l);
            DBG(6, 4);
        };
        auto local_pv = [&](int s, bool arrive) {
            wgmma_fence();
#pragma unroll
            for (int ks = 0; ks < 3; ks++)
                wgmma_ss_n32_p(d, desc_lo(sb + CO_T + (s & 1) * CH_TP + 2 * CH_TW + ks * 2048, 16), desc_lo(sb + CO_P + ks * 256, 128), ks != 0);
            wgmma_commit();
            wgmma_wait<0>();
            if (arrive) asm volatile("bar.arrive 9, 256;" ::: "memory");
            store32(aO + CO_ST);
            fence_async_smem();
            if (!arrive) asm volatile("bar.sync 5, 128;" ::: "memory");
        };
        auto store_ctx = [&](int s) {
            tma_store_2d(&P.mapC, sb + CO_ST, (rank & 1) * 64, h * SEQ + s * SEGL);
            asm volatile("cp.async.bulk.commit_group;" ::: "memory");
        };
        auto signal_ctx = [&](int m0, int m1) {
            asm volatile("fence.proxy.async;" ::: "memory");
            __threadfence();
            for (int m = m0; m < m1; m++) asm volatile("red.relaxed.gpu.global.add.u32 [%0], 1;" :: "l"(&g_ctr[CT_CB + m]) : "memory");
        };
#pragma unroll 1
        for (int s = 0; s < NSEG; s++) {
            const uint32_t par = s & 1;
            load_wa();
            mem_proj(s, s > 0);
            if (s == NSEG - 1) break;
            if (warp < 5) {
                const uint32_t qa_ = aQ + par * CH_TP, ka = qa_ + warp * 1024;
                asm volatile("bar.sync 1, 256;" ::: "memory");
                const uint4 qa = lds128(qa_ + 4096), k0 = lds128(ka + CH_TW), qb = lds128((qa_ ^ 16) + 4096), k1 = lds128((ka ^ 16) + CH_TW);
                DBGD(52 + warp, warp, qa.x ^ qb.x);
                float c[4] = {0.f, 0.f, 0.f, 0.f}, c2[4] = {0.f, 0.f, 0.f, 0.f};
                mma_16816(c, qa.x, 0u, qa.y, 0u, k0.x, k0.y);
                mma_16816(c2, qb.x, 0u, qb.y, 0u, k1.x, k1.y);
                mma_16816(c, qa.z, 0u, qa.w, 0u, k0.z, k0.w);
                mma_16816(c2, qb.z, 0u, qb.w, 0u, k1.z, k1.w);
                c[0] += c2[0]; c[1] += c2[1];
                DBGD(57 + warp, warp, __float_as_uint(c[0]));
                const uint32_t off = aL + CO_SC + warp * 256;
                st_async_v2(remote(off + 1280, rank ^ 1), __float_as_uint(c[0]), __float_as_uint(c[1]), remote(bar_sc, rank ^ 1));
                st_async_v2(off, __float_as_uint(c[0]), __float_as_uint(c[1]), bar_sc);
                asm volatile("bar.arrive 2, 288;" ::: "memory");
                DBG(3, 0);
            } else {
                asm volatile("bar.arrive 1, 256;" ::: "memory");
            }
            if (wg == 0) {
                if (tid == 96) {
                    mbar_expect_tx(bar_sc, 2 * 1280);
#pragma unroll
                    for (int j = 0; j < 4; j++) { mbar_expect_tx(bar_mem + 8 * j, 2048); if (j < CH_OG) mbar_expect_tx(bar_o + 8 * j, 8192 / CH_OG); }
                    if (s > 0) mbar_wait(bar_l, par ^ 1);
                    mbar_expect_tx(bar_l, 4096);
                }
                if (tid == 96 && s > 1) {
                    if (s == 34 || s == 50 || s == 58 || s == 62) {
                        asm volatile("cp.async.bulk.wait_group 0;" ::: "memory");
                        signal_ctx(s == 34 ? 0 : (2 * s - 68) >> 2, s >> 2);
                    }
                    store_ctx(s - 2);
                    asm volatile("cp.async.bulk.wait_group.read 0;" ::: "memory");
                }
                __syncwarp();
                mbar_wait(bar_x + 8 * (par ^ 1), ((s + 1) >> 1) & 1);
                asm volatile("bar.sync 5, 128;" ::: "memory");
                float c[4];
                const uint32_t alo = desc_lo(sb + CO_WO, 16), blo = desc_lo(sb + CO_OB, 128);
                uint32_t* wp = g_xbuf + (size_t)rank * 2048 + C * 256 + qc * 64 + t4 * 8 + qd;
                mbar_wait_cl(bar_o, par);
                DBG(16, 0);
                fence_async_smem();
                wgmma_fence();
#pragma unroll
                for (int i = 0; i < 32; i++) {
                    wgmma_ss_n8(c, alo + i * 128, blo + i * 16, i != 0);
                    if (CH_OG == 2 && i == CH_OW) mbar_wait_cl(bar_o + 8, par);
                    if (CH_OG == 2 && i == CH_OF) fence_async_smem();
                }
                wgmma_commit();
                wgmma_wait<0>();
                asm volatile("st.relaxed.gpu.global.u32 [%0], %1;" :: "l"(wp + (s & 3) * 16384), "r"(~pack_bf16(c[0], c[2])) : "memory");
                asm volatile("st.relaxed.gpu.global.u32 [%0], %1;" :: "l"(wp + (s & 3) * 16384 + 32), "r"(~pack_bf16(c[1], c[3])) : "memory");
                asm volatile("bar.arrive 4, 256;" ::: "memory");
                asm volatile("bar.arrive 6, 256;" ::: "memory");
                DBG(8, 0);
                if (s > 0) local_pv(s - 1, true); else asm volatile("bar.arrive 9, 256;" ::: "memory");
                DBG(28, 0);
                asm volatile("st.relaxed.gpu.global.u32 [%0], %1;" :: "l"(wp + ((s + 2) & 3) * 16384), "r"(0) : "memory");
                asm volatile("st.relaxed.gpu.global.u32 [%0], %1;" :: "l"(wp + ((s + 2) & 3) * 16384 + 32), "r"(0) : "memory");
                if (tid == 0 && s + 2 < NSEG) {
                    mbar_expect_tx(bar_x + 8 * par, 32768);
                    tma_load_2d_mc(sb + CO_XB + par * 32768 + rank * 4096, &P.mapX, bar_x + 8 * par, rank * 64, (s + 2) * SEGL, (uint16_t)0xff);
                }
                __syncwarp();
            } else {
                const uint32_t vaddr = pin(sb + CO_T + par * CH_TP + 2 * CH_TW + (lane & 15) * 128 + (((t4 * 2 + (lane >> 4)) ^ (lane & 7)) << 4));
                const uint32_t dsta = pin(sb + CO_OB + t4 * 256 + (qc >> 1) * 128 + qd * 16 + (qc & 1) * 8);
                fence_async_smem();
                uint32_t vb[3][4];
                auto load_v = [&]() {
                    asm volatile("bar.sync 3, 256;" ::: "memory");
#pragma unroll
                    for (int k = 0; k < 3; k++) ldmatrix_x4_trans(vb[k][0], vb[k][1], vb[k][2], vb[k][3], vaddr + k * 2048);
                };
                if (CH_VPOS == 0) load_v();
                mbar_wait_cl(bar_sc, par);
                DBG(4, 4);
                float v[10];
#pragma unroll
                for (int j = 0; j < 5; j++) {
                    const float2 a = lds64f(aL + CO_SC + j * 256), b = lds64f(aL + CO_SC + 1280 + j * 256);
                    v[2 * j] = a.x + b.x; v[2 * j + 1] = a.y + b.y;
                }
                if (CH_VPOS == 1) load_v();
                float mx = fmaxf(fmaxf(fmaxf(v[0], v[1]), fmaxf(v[2], v[3])), fmaxf(fmaxf(v[4], v[5]), fmaxf(v[6], v[7])));
                mx = fmaxf(mx, fmaxf(v[8], v[9]));
                mx = fmaxf(mx, __shfl_xor_sync(0xffffffff, mx, 1));
                mx = fmaxf(mx, __shfl_xor_sync(0xffffffff, mx, 2));
                if (CH_VPOS == 2) load_v();
                DBG(19, 4);
                mx *= CH_SC;
#pragma unroll
                for (int j = 0; j < 10; j++) v[j] = ex2f(fmaf(v[j], CH_SC, -mx));
                float c0[4] = {0.f, 0.f, 0.f, 0.f}, c1[4] = {0.f, 0.f, 0.f, 0.f}, cs[4] = {0.f, 0.f, 0.f, 0.f};
#pragma unroll
                for (int k = 0; k < 3; k++) {
                    const uint32_t p0 = pack_bf16(v[4 * k], v[4 * k + 1]), p1 = k < 2 ? pack_bf16(v[4 * k + 2], v[4 * k + 3]) : 0u;
                    mma_16816(cs, p0, 0u, p1, 0u, 0x3f803f80u, 0x3f803f80u);
                    mma_16816(c0, p0, 0u, p1, 0u, vb[k][0], vb[k][1]);
                    mma_16816(c1, p0, 0u, p1, 0u, vb[k][2], vb[k][3]);
                }
                float inv;
                asm volatile("rcp.approx.ftz.f32 %0, %1;" : "=f"(inv) : "f"(cs[0]));
                const uint32_t b0 = pack_bf16(c0[0] * inv, c0[1] * inv), b1 = pack_bf16(c1[0] * inv, c1[1] * inv);
                DBG(20, 4);
#pragma unroll
                for (int i = 0; i < 8; i++) {
                    const int dr = (rank + i) & 7;
                    st_async_v2(remote(dsta + i * 1024, dr), b0, b1, remote(bar_o + 8 * (i * CH_OG / 8), dr));
                    if (i == 0) asm volatile("bar.arrive 7, 256;" ::: "memory");
                }
                DBG(5, 4);
                mbar_wait(bar_x + 8 * (par ^ 1), ((s + 1) >> 1) & 1);
                asm volatile("bar.sync 4, 256;" ::: "memory");
                if (CH_LSPOS == 0) local_scores(s);
            }
            pass32(par ^ 1);
            DBG(21, 0);
            wgmma_wait<0>();
            store32(aO + (par ^ 1) * CH_TP + CO_T);
            if (wg == 0) fence_async_smem();
            DBG(22, 0);
            DBG(29, 4);
            if (CH_LSPOS == 1 && wg == 1) local_scores(s);
        }
        fence_async_smem();
        asm volatile("bar.sync 1, 256;" ::: "memory");
        if (warp < 5) asm volatile("bar.arrive 2, 288;" ::: "memory");
        if (wg == 0) {
            if (tid == 96) { mbar_wait(bar_l, 0); mbar_expect_tx(bar_l, 4096); store_ctx(NSEG - 3); asm volatile("cp.async.bulk.wait_group.read 0;" ::: "memory"); }
            __syncwarp();
            asm volatile("bar.sync 7, 256;" ::: "memory");
            local_pv(NSEG - 2, false);
            asm volatile("bar.arrive 6, 256;" ::: "memory");
            if (tid == 96) { store_ctx(NSEG - 2); asm volatile("cp.async.bulk.wait_group.read 0;" ::: "memory"); }
            __syncwarp();
            asm volatile("bar.sync 8, 256;" ::: "memory");
            local_pv(NSEG - 1, false);
            if (tid == 96) {
                store_ctx(NSEG - 1);
                asm volatile("cp.async.bulk.wait_group 0;" ::: "memory");
                signal_ctx(15, 16);
            }
            uint32_t* wp = g_xbuf + 16384 + (size_t)rank * 2048 + C * 256 + tid * 2;
            *reinterpret_cast<uint2*>(wp) = make_uint2(0u, 0u);
        } else {
            asm volatile("bar.sync 3, 256;" ::: "memory");
            asm volatile("bar.arrive 7, 256;" ::: "memory");
            local_scores(NSEG - 1);
        }
    } else {
        auto local_softmax = [&](int s) {
            float v[10];
            const float2 g = __ldcg(reinterpret_cast<const float2*>(g_gate + s * SEGL + t4 * 8 + 2 * qc));
            mbar_wait_cl(bar_l, s & 1);
            const uint32_t off = 2 * aL - sb + t4 * 1280;
            {
                const uint4 a0 = lds128(off + (s & 1) * 5120 + CO_LS), b0 = lds128(off + CO_LO), a1 = lds128(off + (s & 1) * 5120 + CO_LS + 512), b1 = lds128(off + CO_LO + 512);
                const float2 a2 = lds64f(aL + t4 * 1280 + (s & 1) * 5120 + CO_LS + 1024), b2 = lds64f(aL + t4 * 1280 + CO_LO + 1024);
                auto f = [](uint32_t a, uint32_t b) { return __uint_as_float(a) + __uint_as_float(b); };
                v[0] = f(a0.x, b0.x); v[1] = f(a0.y, b0.y); v[2] = f(a0.z, b0.z); v[3] = f(a0.w, b0.w);
                v[4] = f(a1.x, b1.x); v[5] = f(a1.y, b1.y); v[6] = f(a1.z, b1.z); v[7] = f(a1.w, b1.w);
                v[8] = a2.x + b2.x; v[9] = a2.y + b2.y;
            }
            const int lim = t4 * 8 + 2 * qc - qd;
#pragma unroll
            for (int n = 0; n < 4; n++) {
                if (8 * n > lim) v[2 * n] = -INFINITY;
                if (8 * n > lim + 1) v[2 * n + 1] = -INFINITY;
            }
            float m0 = fmaxf(fmaxf(fmaxf(v[0], v[2]), fmaxf(v[4], v[6])), v[8]), m1 = fmaxf(fmaxf(fmaxf(v[1], v[3]), fmaxf(v[5], v[7])), v[9]);
#pragma unroll
            for (int o = 4; o < 32; o *= 2) { m0 = fmaxf(m0, __shfl_xor_sync(0xffffffff, m0, o)); m1 = fmaxf(m1, __shfl_xor_sync(0xffffffff, m1, o)); }
            m0 *= CH_SC; m1 *= CH_SC;
#pragma unroll
            for (int n = 0; n < 5; n++) { v[2 * n] = ex2f(fmaf(v[2 * n], CH_SC, -m0)); v[2 * n + 1] = ex2f(fmaf(v[2 * n + 1], CH_SC, -m1)); }
            float s0 = ((v[0] + v[2]) + (v[4] + v[6])) + v[8], s1 = ((v[1] + v[3]) + (v[5] + v[7])) + v[9];
#pragma unroll
            for (int o = 4; o < 32; o *= 2) { s0 += __shfl_xor_sync(0xffffffff, s0, o); s1 += __shfl_xor_sync(0xffffffff, s1, o); }
            asm("rcp.approx.ftz.f32 %0, %0;" : "+f"(s0));
            asm("rcp.approx.ftz.f32 %0, %0;" : "+f"(s1));
            s0 *= 1.f - g.x; s1 *= 1.f - g.y;
            const uint32_t pa = 2 * aL - sb + CO_P + t4 * 768;
            stmatrix_x4_trans(pa, pack_bf16(v[0] * s0, v[1] * s1), pack_bf16(v[2] * s0, v[3] * s1), pack_bf16(v[4] * s0, v[5] * s1), pack_bf16(v[6] * s0, v[7] * s1));
            asm volatile("stmatrix.sync.aligned.m8n8.x1.trans.shared.b16 [%0], {%1};" :: "r"(pa + 512), "r"(pack_bf16(v[8] * s0, v[9] * s1)) : "memory");
            fence_async_smem();
            DBG(7, 8);
        };
        wait_ctr(CT_GATE, 64u);
#pragma unroll 1
        for (int s = 0; s < NSEG; s++) {
            const uint32_t par = s & 1;
            if (s > 0) local_softmax(s - 1);
            load_wa();
            if (s < NSEG - 1) mbar_wait(bar_x + 8 * (par ^ 1), ((s + 1) >> 1) & 1);
            asm volatile("bar.sync 2, 288;" ::: "memory");
            DBG(23, 8);
            mem_proj(s, false, true);
            asm volatile("bar.arrive 3, 256;" ::: "memory");
            if (s == NSEG - 1) break;
            DBG(24, 8);
            if (CH_V1 > 0) pass32(par ^ 1, 0, CH_V1);
            asm volatile("bar.sync 7, 256;" ::: "memory");
            pass32(par ^ 1, CH_V1, CH_V2);
            DBG(26, 8);
            asm volatile("bar.sync 6, 256;" ::: "memory");
            const uint2* xb = reinterpret_cast<const uint2*>(g_xbuf + (s & 3) * 16384 + (size_t)rank * 2048 + t4 * 64) + lane;
            uint2 p[8];
            auto poll_all = [&]() {
#pragma unroll
                for (int k = 0; k < 8; k++)
                    asm volatile("ld.relaxed.gpu.global.v2.u32 {%0, %1}, [%2];" : "=r"(p[k].x), "=r"(p[k].y) : "l"(xb + k * 128) : "memory");
                DBG(17, 8);
            };
            if (CH_V3 > CH_V2) { pace(CH_V3_DELAY); pass32(par ^ 1, CH_V2, CH_V3); }
            if (CH_VST == 0) {
                asm volatile("bar.sync 9, 256;" ::: "memory");
                wgmma_wait<0>();
                store32(aO + (par ^ 1) * CH_TP + CO_T);
                DBG(27, 8);
            }
            pace(CH_POLL_DELAY);
            auto lo = [](uint32_t u) { return __uint_as_float(~u << 16); };
            auto hi = [](uint32_t u) { return __uint_as_float(~u & 0xffff0000u); };
            poll_all();
            for (int it = 0; it < WAIT_LIMIT / 4; it++) {
                uint32_t bad = 0;
#pragma unroll
                for (int k = 0; k < 8; k++) bad |= (min(p[k].x, p[k].y) == 0u ? 1u : 0u) << k;
                if (__all_sync(0xffffffff, bad == 0u)) break;
                if (it == 0) DBG(12, 8);
                if (it == 1) DBG(14, 8);
                if (it == 2) DBG(15, 8);
#pragma unroll
                for (int k = 0; k < 8; k++)
                    if (bad & (1u << k))
                        asm volatile("ld.relaxed.gpu.global.v2.u32 {%0, %1}, [%2];" : "=r"(p[k].x), "=r"(p[k].y) : "l"(xb + k * 128) : "memory");
            }
            DBG(9, 8);
            const uint32_t m0 = pack_bf16(((lo(p[0].x) + lo(p[1].x)) + (lo(p[2].x) + lo(p[3].x))) + ((lo(p[4].x) + lo(p[5].x)) + (lo(p[6].x) + lo(p[7].x))),
                                          ((hi(p[0].x) + hi(p[1].x)) + (hi(p[2].x) + hi(p[3].x))) + ((hi(p[4].x) + hi(p[5].x)) + (hi(p[6].x) + hi(p[7].x))));
            const uint32_t m1 = pack_bf16(((lo(p[0].y) + lo(p[1].y)) + (lo(p[2].y) + lo(p[3].y))) + ((lo(p[4].y) + lo(p[5].y)) + (lo(p[6].y) + lo(p[7].y))),
                                          ((hi(p[0].y) + hi(p[1].y)) + (hi(p[2].y) + hi(p[3].y))) + ((hi(p[4].y) + hi(p[5].y)) + (hi(p[6].y) + hi(p[7].y))));
            const int row = t4 * 2 + (lane >> 4);
            const uint32_t dsta = sb + CO_MB + row * 128 + ((((lane & 15) >> 1) ^ row) << 4) + (lane & 1) * 8;
#pragma unroll
            for (int i = 0; i < 8; i++) {
                const int dr = (rank + (i & 1) * 4 + (i >> 1)) & 7;
                st_async_v2(remote(dsta + i * 1024, dr), m0, m1, remote(bar_mem + 8 * (i >> 1), dr));
            }
            DBG(10, 8);
            if (CH_VST == 1) {
                if (CH_V3 < 32) pass32(par ^ 1, CH_V3, 32);
                asm volatile("bar.sync 9, 256;" ::: "memory");
                wgmma_wait<0>();
                store32(aO + (par ^ 1) * CH_TP + CO_T);
                DBG(27, 8);
            }
        }
        asm volatile("bar.sync 6, 256;" ::: "memory");
        local_softmax(NSEG - 1);
        asm volatile("bar.arrive 8, 256;" ::: "memory");
    }
    __syncthreads();
    cluster_sync_all();
    TS_END(2);
}

struct Proj2Params {
    CUtensorMap mapA[2];
    CUtensorMap mapW[3];
    bf16* out[3];
};
#define P2T(i)
#define P2_NOMMA 0
#define P2_NOLOAD 0
constexpr int P2_STAGES = 6;
constexpr int P2_SMEM = 131072 + P2_STAGES * 16384 + 1024 + 1024;
constexpr int P2_ITEMS = 168 + 48;

__device__ __forceinline__ int p2_reps(int t) { return t >= 168 ? 1 : 2; }
__device__ __forceinline__ void p2_tile(int t, int w, int& z, int& mp, int& head) {
    if (t >= 168) { w += ((t - 168) & 1) * 2; t = 168 + ((t - 168) >> 1); }
    const int hq = t / 24, v = t % 24;
    mp = v & 7;
    if (v < 16) { head = hq * 4 + (v >> 3) * 2 + (w >> 1); z = 1 + (w & 1); }
    else { head = hq * 4 + w; z = 0; }
}
__device__ __forceinline__ void mbar_arrive_remote(uint32_t bar_cluster_addr) {
    asm volatile("mbarrier.arrive.release.cluster.shared::cluster.b64 _, [%0];" :: "r"(bar_cluster_addr) : "memory");
}
__device__ __forceinline__ void mbar_arrive_cl(uint32_t bar_cluster_addr) {
    asm volatile("mbarrier.arrive.shared::cluster.b64 _, [%0];" :: "r"(bar_cluster_addr) : "memory");
}
__device__ __forceinline__ void mbar_wait_acq_cluster(uint32_t bar, uint32_t parity) {
    asm volatile(
        "{\n"
        ".reg .pred p, q;\n"
        ".reg .u32 c;\n"
        "mov.u32 c, 0;\n"
        "WAIT_LOOP_C:\n"
        "mbarrier.try_wait.parity.acquire.cluster.shared::cta.b64 p, [%0], %1;\n"
        "@p bra WAIT_DONE_C;\n"
        "add.u32 c, c, 1;\n"
        "setp.lt.u32 q, c, 4000000;\n"
        "@q bra WAIT_LOOP_C;\n"
        "WAIT_DONE_C:\n"
        "}\n" :: "r"(bar), "r"(parity) : "memory");
}
__device__ __forceinline__ uint4 quad_transpose(uint32_t p0, uint32_t p1, uint32_t p2, uint32_t p3, int lane) {
    const bool o1 = lane & 1, o2 = lane & 2;
    uint32_t s0 = o1 ? p0 : p1, s1 = o1 ? p2 : p3;
    s0 = __shfl_xor_sync(0xffffffff, s0, 1); s1 = __shfl_xor_sync(0xffffffff, s1, 1);
    const uint32_t a_lo = o1 ? s0 : p0, a_hi = o1 ? p1 : s0, b_lo = o1 ? s1 : p2, b_hi = o1 ? p3 : s1;
    uint32_t t0 = o2 ? a_lo : b_lo, t1 = o2 ? a_hi : b_hi;
    t0 = __shfl_xor_sync(0xffffffff, t0, 2); t1 = __shfl_xor_sync(0xffffffff, t1, 2);
    return o2 ? make_uint4(t0, t1, b_lo, b_hi) : make_uint4(a_lo, a_hi, t0, t1);
}
#define P2_PACE 35
#define P2_PACE2 0
template <bool PERM, int PACE = 0>
__device__ __forceinline__ void store_frag_128(const float (&acc)[64], bf16* obase, int lane) {
#pragma unroll
    for (int rr = 0; rr < 2; rr++)
#pragma unroll
        for (int g = 0; g < 4; g++) {
            const float* a = &acc[g * 16 + rr * 2];
            const uint32_t p0 = pack_bf16(a[0], a[1]), p1 = pack_bf16(a[4], a[5]), p2 = pack_bf16(a[8], a[9]), p3 = pack_bf16(a[12], a[13]);
            *reinterpret_cast<uint4*>(obase + (size_t)(rr * 8) * HD + g * 32) = PERM ? make_uint4(p0, p1, p2, p3) : quad_transpose(p0, p1, p2, p3, lane);
            pace(PACE);
        }
}
__global__ void __cluster_dims__(2, 1, 1) __launch_bounds__(384, 1) proj2_kernel(const __grid_constant__ Proj2Params P) {
    extern __shared__ uint8_t smem_raw[];
    const uint32_t sbase = (smem_u32(smem_raw) + 1023) & ~1023u;
    const uint32_t sA = sbase, sB = sbase + 131072, sC = sB + P2_STAGES * 16384;
    const uint32_t bars = sC;
    const uint32_t a_full = bars, a_empty = bars + 64, b_full = bars + 128, b_empty = b_full + 8 * P2_STAGES;
    const uint32_t item_bar = b_empty + 8 * P2_STAGES, item_in = item_bar + 16, slot = item_in + 16;
    const uint32_t note_bar = slot + 16, note_free = note_bar + 64, note = note_free + 64;
    const int warp = threadIdx.x >> 5, lane = threadIdx.x & 31;
    const uint32_t rank = cluster_ctarank();
    TS_BEGIN(0);
    if (threadIdx.x == 0) {
        for (int i = 0; i < 8; i++) { mbar_init(a_full + 8 * i, 1); mbar_init(a_empty + 8 * i, 2); }
        for (int i = 0; i < P2_STAGES; i++) { mbar_init(b_full + 8 * i, 1); mbar_init(b_empty + 8 * i, 2); }
        mbar_init(item_bar, 1); mbar_init(item_bar + 8, 1); mbar_init(item_in, 2); mbar_init(item_in + 8, 2);
        for (int i = 0; i < 8; i++) { mbar_init(note_bar + 8 * i, 1); mbar_init(note_free + 8 * i, 1); }
        asm volatile("fence.mbarrier_init.release.cluster;" ::: "memory");
    }
    __syncthreads();
    cluster_sync_all();
    pdl_launch_dependents();
    if (warp == 9) {
        if (lane == 0) {
            for (int n = 0;; n++) {
                const int e = (n & 1) * 4 + ((n >> 1) & 3);
                mbar_wait(note_bar + 8 * e, (n >> 3) & 1);
                int m;
                asm volatile("ld.shared.s32 %0, [%1];" : "=r"(m) : "r"(note + e * 4) : "memory");
                mbar_arrive(note_free + 8 * e);
                if (m < 0) break;
                signal_ctr(m);
            }
        }
    } else if (warp == 10) {
        if (lane == 0) {
            auto publish = [&](int ic, int tq) {
                const int t = tq < P2_ITEMS ? tq : -1;
                asm volatile("st.shared.s32 [%0], %1;" :: "r"(slot + (ic & 3) * 4), "r"(t) : "memory");
                mbar_arrive(item_bar + 8 * (ic & 1));
                st_async_b32(mapa_u32(slot + (ic & 3) * 4, 1), (uint32_t)t, mapa_u32(item_bar + 8 * (ic & 1), 1));
            };
            const int npair = (int)(gridDim.x >> 1), pair = (int)(blockIdx.x >> 1);
            if (rank == 0) publish(0, pair);
            for (int ic = 0;; ic++) {
                if (rank == 1) mbar_expect_tx(item_bar + 8 * (ic & 1), 4);
                mbar_wait(item_bar + 8 * (ic & 1), (ic >> 1) & 1);
                int t;
                asm volatile("ld.shared.s32 %0, [%1];" : "=r"(t) : "r"(slot + (ic & 3) * 4) : "memory");
                if (t < 0) break;
                int z0, mp, h0;
                p2_tile(t, 0, z0, mp, h0);
                const int aidx = z0 >= 1 ? 1 : 0;
                const int m0 = (2 * mp + (int)rank) * 128;
                for (int k = 0; k < 8; k++) {
                    mbar_wait(a_empty + 8 * k, (ic & 1) ^ 1);
                    if (P2_NOLOAD) mbar_arrive(a_full + 8 * k); else {
                    mbar_expect_tx(a_full + 8 * k, 16384);
                    tma_load_2d(sA + k * 16384, &P.mapA[aidx], a_full + 8 * k, k * 64, m0); }
                }
                if (rank == 0) {
                    mbar_wait(item_in + 8 * (ic & 1), (ic >> 1) & 1);
                    publish(ic + 1, ic == 0 ? npair + pair : 2 * npair + (int)atomicAdd(&g_ctr[CT_PROJ], 1u));
                }
            }
        }
    } else if (warp == 8 || warp == 11) {
        if (lane == 0) {
            const int par2 = warp == 8 ? 0 : 1;
            int it = 0; uint32_t bph = 0;
            for (int ic = 0;; ic++) {
                mbar_wait(item_bar + 8 * (ic & 1), (ic >> 1) & 1);
                int t;
                asm volatile("ld.shared.s32 %0, [%1];" : "=r"(t) : "r"(slot + (ic & 3) * 4) : "memory");
                if (t < 0) break;
                const int nt = 2 * p2_reps(t);
                for (int w = 0; w < nt; w++) {
                    int z, mp, hd;
                    p2_tile(t, w, z, mp, hd);
                    for (int k = 0; k < 8; k++) {
                        const int s = it; const uint32_t phb = bph;
                        if (++it == P2_STAGES) { it = 0; bph ^= 1; }
                        if ((k & 1) != par2) continue;
                        mbar_wait(b_empty + 8 * s, phb ^ 1);
                        if (P2_NOLOAD) { mbar_arrive(b_full + 8 * s); continue; }
                        mbar_expect_tx(b_full + 8 * s, 16384);
                        tma_load_2d_mc(sB + s * 16384 + rank * 8192, &P.mapW[z], b_full + 8 * s, hd * 128 + (int)rank * 64, k * 64, (uint16_t)3);
                    }
                }
            }
        }
    } else {
        const int wg = warp >> 2;
        float acc[2][64];
        const uint32_t a_lo = desc_lo(sA, 16), b_lo0 = desc_lo(sB, 8192);
        const bool elected = (threadIdx.x & 127) == 0;
        int s = (wg * 8) % P2_STAGES;
        uint32_t ph = ((wg * 8) / P2_STAGES) & 1;
        int nnote = 0;
        if (wg == 1) asm volatile("bar.arrive 3, 256;" ::: "memory");
        for (int ic = 0;; ic++) {
            mbar_wait(item_bar + 8 * (ic & 1), (ic >> 1) & 1);
            int t;
            asm volatile("ld.shared.s32 %0, [%1];" : "=r"(t) : "r"(slot + (ic & 3) * 4) : "memory");
            P2T(7);
            if (wg == 0 && t < 0) {
                if (elected) {
                    const int e = nnote & 3;
                    mbar_wait(note_free + 8 * e, ((nnote >> 2) & 1) ^ 1);
                    asm volatile("st.shared.s32 [%0], %1;" :: "r"(note + e * 4), "r"(-1) : "memory");
                    mbar_arrive(note_bar + 8 * e);
                }
            }
            if (t < 0) break;
            const int reps = p2_reps(t);
#pragma unroll 1
            for (int rp = 0; rp < reps; rp++) {
            const bool first = rp == 0, last = rp == reps - 1;
            int z, mp, head;
            p2_tile(t, rp * 2 + wg, z, mp, head);
            asm volatile("bar.sync %0, 256;" :: "r"(3 + wg) : "memory");
            P2T(0);
            if (wg == 1 && last && elected) mbar_arrive_cl(mapa_u32(item_in + 8 * (ic & 1), 0));
            int sprev = 0;
#pragma unroll
            for (int k = 0; k < 8; k++) {
                if (k == 0) P2T(5);
                if (wg == 0 && first) mbar_wait(a_full + 8 * k, ic & 1);
                if (k == 0) P2T(6);
                mbar_wait(b_full + 8 * s, ph);
                if (k == 7) asm volatile("bar.arrive %0, 256;" :: "r"(4 - wg) : "memory");
                if (k == 0) P2T(1);
                if (k == 7) P2T(2);
                const uint32_t b_lo = b_lo0 + s * 1024;
                wgmma_fence();
#pragma unroll
                for (int kk = 0; kk < (P2_NOMMA ? 1 : 4); kk++) {
                    wgmma_ss_n128_lo<1>(acc[0], a_lo + k * 1024 + kk * 2, b_lo + kk * 128, (k | kk) != 0);
                    wgmma_ss_n128_lo<1>(acc[1], a_lo + k * 1024 + 512 + kk * 2, b_lo + kk * 128, (k | kk) != 0);
                }
                wgmma_commit();
                if (k > 0) {
                    wgmma_wait<1>();
                    if (elected) {
                        const uint32_t e = b_empty + 8 * sprev;
                        mbar_arrive_cl(mapa_u32(e, 0)); mbar_arrive_cl(mapa_u32(e, 1));
                        if (last) mbar_arrive(a_empty + 8 * (k - 1));
                    }
                }
                sprev = s;
                if (++s == P2_STAGES) { s = 0; ph ^= 1; }
            }
            wgmma_wait<0>();
            P2T(3);
            if (elected) {
                const uint32_t e = b_empty + 8 * sprev;
                mbar_arrive_cl(mapa_u32(e, 0)); mbar_arrive_cl(mapa_u32(e, 1));
                if (last) mbar_arrive(a_empty + 8 * 7);
            }
            s += 8 % P2_STAGES; ph ^= (8 / P2_STAGES) & 1;
            if (s >= P2_STAGES) { s -= P2_STAGES; ph ^= 1; }
            const int m0 = (2 * mp + (int)rank) * 128;
            bf16* obase = P.out[z] + ((size_t)head * SEQ + m0 + (warp & 3) * 16 + (lane >> 2)) * HD + (lane & 3) * 8;
            store_frag_128<true, P2_PACE>(acc[0], obase, lane); store_frag_128<true, P2_PACE>(acc[1], obase + (size_t)64 * HD, lane);
            P2T(4);
            {
                asm volatile("bar.sync %0, 128;" :: "r"(1 + wg) : "memory");
                if (elected) {
                    const int e = wg * 4 + (nnote & 3);
                    mbar_wait(note_free + 8 * e, ((nnote >> 2) & 1) ^ 1);
                    asm volatile("st.shared.s32 [%0], %1;" :: "r"(note + e * 4), "r"(CT_AP + (head >> 1)) : "memory");
                    mbar_arrive(note_bar + 8 * e);
                }
                nnote++;
            }
            }
        }
        TS_END(0);
    }
    __syncthreads();
    cluster_sync_all();
}

struct OutParams {
    CUtensorMap mapCtx[2];
    CUtensorMap mapWo[2];
    CUtensorMap mapOut;
};

#define OT(i)
#define OTP(i, th)
constexpr int O2_STAGES = 4;
constexpr int O2_SMEM = O2_STAGES * 49152 + 1024 + 256;
constexpr int O2_GRID = 132;
#define O2_NL 8
#define O2_FINE 8

__global__ void __cluster_dims__(2, 1, 1) __launch_bounds__(352, 1)
out2_kernel(const __grid_constant__ OutParams P) {
    extern __shared__ uint8_t smem_raw[];
    const uint32_t sbase = (smem_u32(smem_raw) + 1023) & ~1023u;
    const uint32_t bar_full = sbase + O2_STAGES * 49152, bar_empty = bar_full + 8 * O2_STAGES, bar_item = bar_empty + 8 * O2_STAGES;
    const uint32_t slot = bar_item + 64, stop = slot + 32;
    const int warp = threadIdx.x >> 5, lane = threadIdx.x & 31;
    const uint32_t rank = cluster_ctarank();
    const int cid = blockIdx.x >> 1;
    int pt, h0;
    if (cid < 32) { pt = cid < 16 ? cid : 31 - cid; h0 = cid >= 16; }
    else if (cid < 34) { pt = 12 + (cid & 1); h0 = 2; }
    else { pt = 14 + (cid & 1); h0 = 63 - ((cid - 34) >> 1); }
    const int ne = (pt >> 1) == 6 ? 3 : 2, nh = pt >= 14 ? 64 - O2_NL : 64;
    if (cid >= 34 + 2 * O2_NL) {
        if (threadIdx.x == 0 && atomicAdd(&g_ctr[CT_FIN], 1u) == gridDim.x - 1)
            for (int i = 0; i < CT_N / 4; i++) reinterpret_cast<uint4*>(g_ctr)[i] = make_uint4(0u, 0u, 0u, 0u);
        return;
    }
    const int mt = (pt >> 1) * 2 + (int)rank, m0 = mt * 128, n0 = (pt & 1) * 256;
    TS_BEGIN(4);
    OT(0);
    int tnext = 0;
    if (threadIdx.x == 256) {
        if (rank == 0) tnext = take_ticket(CT_OT + pt);
        for (int i = 0; i < O2_STAGES; i++) { mbar_init(bar_full + 8 * i, 1); mbar_init(bar_empty + 8 * i, 4); mbar_init(bar_item + 16 * i, 1); mbar_init(bar_item + 16 * i + 8, 1); }
        sts128(stop, 0u, 0u, 0u, 0u);
        asm volatile("fence.mbarrier_init.release.cluster;" ::: "memory");
    }
    __syncwarp();
    asm volatile("barrier.cluster.arrive.relaxed.aligned;" ::: "memory");
    if (threadIdx.x == 256) {
        asm volatile("prefetch.tensormap [%0];" :: "l"(&P.mapCtx[h0 >> 5]) : "memory");
        wait_ctr(h0 < 32 ? CT_CA + mt * 4 : CT_CB + mt, h0 < 32 ? 16u : 64u);
        OTP(8, 256);
        for (int i = 0; i < 2; i++) {
            mbar_expect_tx(bar_full + 8 * i, 49152);
            tma_load_2d(sbase + i * 49152, &P.mapCtx[h0 >> 5], bar_full + 8 * i, i * 64, (h0 & 31) * SEQ + m0);
        }
        OTP(11, 256);
    }
    if (threadIdx.x == 288) asm volatile("prefetch.tensormap [%0];" :: "l"(&P.mapWo[h0 >> 5]) : "memory");
    __syncwarp();
    asm volatile("barrier.cluster.wait.aligned;" ::: "memory");
    OTP(10, 288);
    if (warp >= 8) {
        if (lane == 0) {
            int s = 0, ready = h0 < 32 ? 1 : 16, q = h0 * 2, qe = q + 2; uint32_t ph = 0;
            for (int ic = 0;; ic++) {
                if (warp == 8 && rank == 0) {
                    const int t = tnext + ne;
                    asm volatile("st.shared.s32 [%0], %1;" :: "r"(slot + (ic & 7) * 4), "r"(t) : "memory");
                    mbar_arrive(bar_item + 8 * (ic & 7));
                    st_async_b32(mapa_u32(slot + (ic & 7) * 4, 1), (uint32_t)t, mapa_u32(bar_item + 8 * (ic & 7), 1));
                    if (t < nh + O2_FINE) tnext = take_ticket(CT_OT + pt);
                }
#pragma unroll 1
                for (; q < qe; q++) {
                    const int b = q >> 6, head = (q >> 1) & 31, dk = (q & 1) * 64;
                    mbar_wait(bar_empty + 8 * s, ph ^ 1);
                    const uint32_t sa = sbase + s * 49152;
                    if (warp == 8) {
                        const int f = b ? 4 : head >> 3;
                        if (!((ready >> f) & 1)) {
                            if (b && !(ready & 8)) { wait_ctr(CT_CA + mt * 4 + 3, 16u); ready |= 8; }
                            wait_ctr(b ? CT_CB + mt : CT_CA + mt * 4 + f, b ? 64u : 16u); ready |= 1 << f;
                        }
                        if (ic > 0) {
                            mbar_expect_tx(bar_full + 8 * s, 49152);
                            tma_load_2d(sa, &P.mapCtx[b], bar_full + 8 * s, dk, head * SEQ + m0);
                        }
                    } else {
                        const int j = (int)rank * 2 + (warp - 9);
                        tma_load_2d_mc(sa + 16384 + j * 8192, &P.mapWo[b], bar_full + 8 * s, n0 + j * 64, head * HD + dk, (uint16_t)3);
                    }
                    if (ic == 0 && s == 0) OTP(12, 288);
                    if (++s == O2_STAGES) { s = 0; ph ^= 1; }
                }
                if (warp == 8 && rank == 1) mbar_expect_tx(bar_item + 8 * (ic & 7), 4);
                mbar_wait(bar_item + 8 * (ic & 7), (ic >> 3) & 1);
                int t;
                asm volatile("ld.shared.s32 %0, [%1];" : "=r"(t) : "r"(slot + (ic & 7) * 4) : "memory");
                if (t >= nh + O2_FINE) break;
                if (t < nh - O2_FINE) { q = 2 * t; qe = q + 2; } else { q = nh - O2_FINE + t; qe = q + 1; }
            }
            if (warp == 8) {
                asm volatile("prefetch.tensormap [%0];" :: "l"(&P.mapOut) : "memory");
                if (!(ready & 8)) wait_ctr(CT_CA + mt * 4 + 3, 16u);
                mbar_wait(bar_empty + 8 * s, ph ^ 1);
                asm volatile("st.shared.s32 [%0], %1;" :: "r"(stop + s * 4), "r"(1) : "memory");
                mbar_arrive(bar_full + 8 * s);
                if (atomicAdd(&g_ctr[CT_FIN], 1u) == gridDim.x - 1)
                    for (int i = 0; i < CT_N / 4; i++) reinterpret_cast<uint4*>(g_ctr)[i] = make_uint4(0u, 0u, 0u, 0u);
                for (int i = 1; i < O2_STAGES; i++) {
                    if (++s == O2_STAGES) { s = 0; ph ^= 1; }
                    mbar_wait(bar_empty + 8 * s, ph ^ 1);
                }
            }
        }
    } else {
        const int wg = warp >> 2;
        const bool elected = (threadIdx.x & 127) == 0;
        float acc[128];
#pragma unroll
        for (int i = 0; i < 128; i++) acc[i] = 0.f;
        int s = 0, sprev = 0; uint32_t ph = 0;
#pragma unroll 1
        for (int i = 0;; i++) {
            mbar_wait(bar_full + 8 * s, ph);
            int st;
            asm volatile("ld.shared.s32 %0, [%1];" : "=r"(st) : "r"(stop + s * 4) : "memory");
            if (st) break;
            if (i == 0) OT(1);
            const uint32_t sa = sbase + s * 49152 + wg * 8192, sb = sbase + s * 49152 + 16384;
            wgmma_fence();
#pragma unroll
            for (int kk = 0; kk < 4; kk++)
                wgmma_ss_n256_tb(acc, make_desc(sa + kk * 32, 16, 1024), make_desc(sb + kk * 2048, 8192, 1024), 1);
            wgmma_commit();
            if (i > 0) {
                wgmma_wait<1>();
                if (elected) { const uint32_t e = bar_empty + 8 * sprev; mbar_arrive_cl(mapa_u32(e, 0)); mbar_arrive_cl(mapa_u32(e, 1)); }
            }
            sprev = s;
            if (++s == O2_STAGES) { s = 0; ph ^= 1; }
        }
        wgmma_wait<0>();
        if (elected) { const uint32_t e = bar_empty + 8 * sprev; mbar_arrive_cl(mapa_u32(e, 0)); mbar_arrive_cl(mapa_u32(e, 1)); }
        asm volatile("bar.sync %0, 128;" :: "r"(1 + wg) : "memory");
        OT(3);
        const int row = (lane & 7) + ((lane >> 3) & 1) * 8;
#pragma unroll
        for (int bx = 0; bx < 4; bx++) {
            const uint32_t stg = sbase + bx * 49152 + warp * 2048;
#pragma unroll
            for (int j = 0; j < 8; j += 2) {
                const float* a = &acc[bx * 32 + j * 4];
                stmatrix_x4(stg + row * 128 + (((j + (lane >> 4)) ^ (row & 7)) << 4), pack_bf16(a[0], a[1]), pack_bf16(a[2], a[3]), pack_bf16(a[4], a[5]), pack_bf16(a[6], a[7]));
            }
            asm volatile("fence.proxy.async.shared::cta;" ::: "memory");
            __syncwarp();
            if (lane == 0)
                asm volatile("cp.reduce.async.bulk.tensor.2d.global.shared::cta.add.tile.bulk_group [%0, {%2, %3}], [%1];"
                             :: "l"((uint64_t)&P.mapOut), "r"(stg), "r"(n0 + bx * 64), "r"(m0 + warp * 16) : "memory");
        }
        OT(4);
        if (lane == 0) {
            asm volatile("cp.async.bulk.commit_group;" ::: "memory");
            asm volatile("cp.async.bulk.wait_group.read 0;" ::: "memory");
        }
        TS_END(4);
    }
}

typedef CUresult (*PFN_encodeTiled)(CUtensorMap*, CUtensorMapDataType, cuuint32_t, void*, const cuuint64_t*,
                                    const cuuint64_t*, const cuuint32_t*, const cuuint32_t*, CUtensorMapInterleave,
                                    CUtensorMapSwizzle, CUtensorMapL2promotion, CUtensorMapFloatOOBfill);
static PFN_encodeTiled g_encode = nullptr;

static void make_map(CUtensorMap* m, const void* ptr, uint64_t rows, uint64_t cols, uint32_t box_rows, bool sw64 = false) {
    cuuint64_t dims[2] = {cols, rows};
    cuuint64_t strides[1] = {cols * 2};
    cuuint32_t box[2] = {sw64 ? 32u : 64u, box_rows};
    cuuint32_t es[2] = {1, 1};
    g_encode(m, CU_TENSOR_MAP_DATA_TYPE_BFLOAT16, 2, const_cast<void*>(ptr), dims, strides, box, es,
             CU_TENSOR_MAP_INTERLEAVE_NONE, sw64 ? CU_TENSOR_MAP_SWIZZLE_64B : CU_TENSOR_MAP_SWIZZLE_128B, CU_TENSOR_MAP_L2_PROMOTION_L2_256B,
             CU_TENSOR_MAP_FLOAT_OOB_FILL_NONE);
}

template <typename... KArgs, typename... Args>
static void launch_pdl(void (*kernel)(KArgs...), int grid, int block, size_t smem, cudaStream_t st, bool pdl, Args... args) {
    cudaLaunchConfig_t cfg = {};
    cfg.gridDim = dim3(grid); cfg.blockDim = dim3(block); cfg.dynamicSmemBytes = smem; cfg.stream = st;
    cudaLaunchAttribute at[1];
    at[0].id = cudaLaunchAttributeProgrammaticStreamSerialization;
    at[0].val.programmaticStreamSerializationAllowed = 1;
    cfg.attrs = at; cfg.numAttrs = pdl ? 1 : 0;
    cudaLaunchKernelEx(&cfg, kernel, KArgs(args)...);
}

extern "C" void kernel_launch(void* const* d_in, const int* in_sizes, int n_in, void* d_out, int out_size) {
    const bf16* x = (const bf16*)d_in[0];
    const bf16* ckv = (const bf16*)d_in[1];
    const bf16* wq = (const bf16*)d_in[2];
    const bf16* wuk = (const bf16*)d_in[3];
    const bf16* wuv = (const bf16*)d_in[4];
    const bf16* wo = (const bf16*)d_in[5];
    const bf16* mem0 = (const bf16*)d_in[7];
    const bf16* Wq = (const bf16*)d_in[8];
    const bf16* Wk = (const bf16*)d_in[9];
    const bf16* Wv = (const bf16*)d_in[10];
    const bf16* Wo = (const bf16*)d_in[11];
    const bf16* gate_w = (const bf16*)d_in[13];
    bf16* out = (bf16*)d_out;

    static Proj2Params P2;
    static ChainParams CP;
    static AttnParams AP;
    static OutParams OP;
    static bool init = false;
    static const void* last_in[14];
    static const void* last_out;
    bool same = init && last_out == d_out;
    for (int i = 0; i < 14 && same; i++) same = last_in[i] == d_in[i];
    if (!init) {
        cudaDriverEntryPointQueryResult qr;
        cudaGetDriverEntryPoint("cuTensorMapEncodeTiled", (void**)&g_encode, cudaEnableDefault, &qr);
        cudaFuncSetAttribute(proj2_kernel, cudaFuncAttributeMaxDynamicSharedMemorySize, P2_SMEM);
        cudaFuncSetAttribute(attn_kernel, cudaFuncAttributeMaxDynamicSharedMemorySize, FA_SMEM);
        cudaFuncSetAttribute(chain_kernel, cudaFuncAttributeMaxDynamicSharedMemorySize, CH_SMEM);
        cudaFuncSetAttribute(out2_kernel, cudaFuncAttributeMaxDynamicSharedMemorySize, O2_SMEM);
        init = true;
    }
    if (!same) {
        for (int i = 0; i < 14; i++) last_in[i] = d_in[i];
        last_out = d_out;
        void *pQA, *pKA, *pVA, *pCA, *pCB;
        cudaGetSymbolAddress(&pQA, g_QA); cudaGetSymbolAddress(&pKA, g_KA); cudaGetSymbolAddress(&pVA, g_VA);
        cudaGetSymbolAddress(&pCA, g_ctxA); cudaGetSymbolAddress(&pCB, g_ctxB);
        make_map(&P2.mapA[0], x, SEQ, DM, 128);
        make_map(&P2.mapA[1], ckv, SEQ, DM, 128);
        const void* ws[3] = {wq, wuk, wuv};
        void* cs[3] = {pQA, pKA, pVA};
        for (int i = 0; i < 3; i++) { make_map(&P2.mapW[i], ws[i], DM, NQ, 64); P2.out[i] = (bf16*)cs[i]; }
        make_map(&CP.mapW[0], Wq, DM, NQ, 64); make_map(&CP.mapW[1], Wk, DM, NQ, 64); make_map(&CP.mapW[2], Wv, DM, NQ, 64);
        make_map(&CP.mapX, x, SEQ, DM, 32);
        make_map(&CP.mapC, pCB, NH * SEQ, HD, 32);
        make_map(&AP.mapQ, pQA, NH * SEQ, HD, 128);
        make_map(&AP.mapK, pKA, NH * SEQ, HD, 128);
        make_map(&AP.mapV, pVA, NH * SEQ, HD, 128);
        make_map(&AP.mapO, pCA, NH * SEQ, HD, 64);
        make_map(&OP.mapCtx[0], pCA, NH * SEQ, HD, 128);
        make_map(&OP.mapCtx[1], pCB, NH * SEQ, HD, 128);
        make_map(&OP.mapWo[0], wo, NQ, DM, 64);
        make_map(&OP.mapWo[1], Wo, NQ, DM, 64);
        make_map(&OP.mapOut, out, SEQ, DM, 16);
        AP.out = out;
    }
    cudaStream_t s1 = cudaStreamPerThread;
    const bool pdl = true;
    launch_pdl(chain_kernel, 64, CH_BLOCK, CH_SMEM, s1, false, CP, mem0, Wo, x, gate_w);
    launch_pdl(proj2_kernel, 68, 384, P2_SMEM, s1, pdl, P2);
    launch_pdl(attn_kernel, FA_GRID, 384, FA_SMEM, s1, pdl, AP);
    launch_pdl(out2_kernel, O2_GRID, 352, O2_SMEM, s1, pdl, OP);
}
```

```cpp
#include <cuda_runtime.h>
#include <cuda_bf16.h>
#include <cuda.h>
#include <stdint.h>
#include <type_traits>

constexpr int SEQ = 2048;
constexpr int DM = 512;
constexpr int NH = 32;
constexpr int HD = 128;
constexpr int NQ = NH * HD;
constexpr int SEGL = 32;
constexpr int NMEM = 8;
constexpr int NSEG = SEQ / SEGL;

typedef __nv_bfloat16 bf16;

__device__ bf16 g_QA[SEQ * NQ];
__device__ bf16 g_KA[SEQ * NQ];
__device__ bf16 g_VA[SEQ * NQ];
__device__ bf16 g_ctxA[SEQ * NQ];
__device__ bf16 g_ctxB[SEQ * NQ];
constexpr int CT_PROJ = 0, CT_ATTN = 1, CT_FIN = 5;
constexpr int CT_AP = 64;
constexpr int CT_GATE = 96;
constexpr int CT_CA = 128;
constexpr int CT_CB = 192;
constexpr int CT_OT = 208;
constexpr int CT_N = 224;
__device__ __align__(16) unsigned int g_ctr[CT_N];
__device__ float g_gate[SEQ];
__device__ uint32_t g_xbuf[4 * 8 * 2048];

#define FA_GRID 68

#define TS_BEGIN(id)
#define TS_END(id)
#define WAIT_LIMIT 200000
__device__ __forceinline__ void pdl_launch_dependents() { asm volatile("griddepcontrol.launch_dependents;" ::: "memory"); }
__device__ __forceinline__ void wait_ctr(int idx, unsigned int n) {
    unsigned int v; int it = 0;
    do { asm volatile("ld.acquire.gpu.global.u32 %0, [%1];" : "=r"(v) : "l"(&g_ctr[idx]) : "memory"); } while (v < n && ++it < WAIT_LIMIT);
    asm volatile("fence.proxy.async.shared::cta;" ::: "memory");
}
__device__ __forceinline__ int take_ticket(int idx) {
    int v;
    asm volatile("atom.relaxed.gpu.global.inc.u32 %0, [%1], 0x7fffffff;" : "=r"(v) : "l"(&g_ctr[idx]) : "memory");
    return v;
}
__device__ __forceinline__ void signal_ctr(int idx) {
    asm volatile("fence.proxy.async;" ::: "memory");
    __threadfence();
    atomicAdd(&g_ctr[idx], 1u);
}
__device__ __forceinline__ void signal_ctr_generic(int idx) {
    asm volatile("red.release.gpu.global.add.u32 [%0], 1;" :: "l"(&g_ctr[idx]) : "memory");
}
__device__ __forceinline__ uint32_t smem_u32(const void* p) {
    return (uint32_t)__cvta_generic_to_shared(p);
}
__device__ __forceinline__ void mbar_init(uint32_t bar, uint32_t count) {
    asm volatile("mbarrier.init.shared::cta.b64 [%0], %1;" :: "r"(bar), "r"(count));
}
__device__ __forceinline__ void mbar_expect_tx(uint32_t bar, uint32_t bytes) {
    asm volatile("mbarrier.arrive.expect_tx.shared::cta.b64 _, [%0], %1;" :: "r"(bar), "r"(bytes) : "memory");
}
__device__ __forceinline__ void mbar_arrive(uint32_t bar) {
    asm volatile("mbarrier.arrive.shared::cta.b64 _, [%0];" :: "r"(bar) : "memory");
}
__device__ __forceinline__ void mbar_wait(uint32_t bar, uint32_t parity) {
    asm volatile(
        "{\n"
        ".reg .pred p, q;\n"
        ".reg .u32 c;\n"
        "mov.u32 c, 0;\n"
        "WAIT_LOOP:\n"
        "mbarrier.try_wait.parity.shared::cta.b64 p, [%0], %1;\n"
        "@p bra WAIT_DONE;\n"
        "add.u32 c, c, 1;\n"
        "setp.lt.u32 q, c, %2;\n"
        "@q bra WAIT_LOOP;\n"
        "WAIT_DONE:\n"
        "}\n" :: "r"(bar), "r"(parity), "n"(WAIT_LIMIT) : "memory");
}
__device__ __forceinline__ uint32_t mbar_test(uint32_t bar, uint32_t parity) {
    uint32_t done;
    asm volatile(
        "{\n.reg .pred p;\n"
        "mbarrier.test_wait.parity.shared::cta.b64 p, [%1], %2;\n"
        "selp.u32 %0, 1, 0, p;\n}\n" : "=r"(done) : "r"(bar), "r"(parity) : "memory");
    return done;
}
__device__ __forceinline__ void tma_load_2d(uint32_t dst, const CUtensorMap* map, uint32_t bar, int c0, int c1) {
    asm volatile(
        "cp.async.bulk.tensor.2d.shared::cluster.global.mbarrier::complete_tx::bytes [%0], [%1, {%3, %4}], [%2];"
        :: "r"(dst), "l"((uint64_t)map), "r"(bar), "r"(c0), "r"(c1) : "memory");
}
__device__ __forceinline__ void wgmma_fence() { asm volatile("wgmma.fence.sync.aligned;" ::: "memory"); }
__device__ __forceinline__ void wgmma_commit() { asm volatile("wgmma.commit_group.sync.aligned;" ::: "memory"); }
template <int N> __device__ __forceinline__ void wgmma_wait() {
    asm volatile("wgmma.wait_group.sync.aligned %0;" :: "n"(N) : "memory");
}
__device__ __forceinline__ uint64_t make_desc(uint32_t addr, uint32_t lbo, uint32_t sbo) {
    uint64_t d = 0;
    d |= (uint64_t)((addr & 0x3FFFF) >> 4);
    d |= (uint64_t)((lbo >> 4) & 0x3FFF) << 16;
    d |= (uint64_t)((sbo >> 4) & 0x3FFF) << 32;
    d |= (uint64_t)1 << 62;
    return d;
}

#define ACC64(d) \
    "+f"(d[0]), "+f"(d[1]), "+f"(d[2]), "+f"(d[3]), "+f"(d[4]), "+f"(d[5]), "+f"(d[6]), "+f"(d[7]), \
    "+f"(d[8]), "+f"(d[9]), "+f"(d[10]), "+f"(d[11]), "+f"(d[12]), "+f"(d[13]), "+f"(d[14]), "+f"(d[15]), \
    "+f"(d[16]), "+f"(d[17]), "+f"(d[18]), "+f"(d[19]), "+f"(d[20]), "+f"(d[21]), "+f"(d[22]), "+f"(d[23]), \
    "+f"(d[24]), "+f"(d[25]), "+f"(d[26]), "+f"(d[27]), "+f"(d[28]), "+f"(d[29]), "+f"(d[30]), "+f"(d[31]), \
    "+f"(d[32]), "+f"(d[33]), "+f"(d[34]), "+f"(d[35]), "+f"(d[36]), "+f"(d[37]), "+f"(d[38]), "+f"(d[39]), \
    "+f"(d[40]), "+f"(d[41]), "+f"(d[42]), "+f"(d[43]), "+f"(d[44]), "+f"(d[45]), "+f"(d[46]), "+f"(d[47]), \
    "+f"(d[48]), "+f"(d[49]), "+f"(d[50]), "+f"(d[51]), "+f"(d[52]), "+f"(d[53]), "+f"(d[54]), "+f"(d[55]), \
    "+f"(d[56]), "+f"(d[57]), "+f"(d[58]), "+f"(d[59]), "+f"(d[60]), "+f"(d[61]), "+f"(d[62]), "+f"(d[63])
#define ACC64_STR \
    "{%0, %1, %2, %3, %4, %5, %6, %7, %8, %9, %10, %11, %12, %13, %14, %15, " \
    "%16, %17, %18, %19, %20, %21, %22, %23, %24, %25, %26, %27, %28, %29, %30, %31, " \
    "%32, %33, %34, %35, %36, %37, %38, %39, %40, %41, %42, %43, %44, %45, %46, %47, " \
    "%48, %49, %50, %51, %52, %53, %54, %55, %56, %57, %58, %59, %60, %61, %62, %63}"

template <int TB>
__device__ __forceinline__ void wgmma_ss_n128(float (&d)[64], uint64_t da, uint64_t db, int scale_d) {
    asm volatile(
        "{\n.reg .pred p;\nsetp.ne.b32 p, %66, 0;\n"
        "wgmma.mma_async.sync.aligned.m64n128k16.f32.bf16.bf16 " ACC64_STR ", %64, %65, p, 1, 1, 0, %67;\n}\n"
        : ACC64(d) : "l"(da), "l"(db), "r"(scale_d), "n"(TB));
}
__device__ __forceinline__ uint32_t desc_lo(uint32_t addr, uint32_t lbo) { return ((addr & 0x3FFFF) >> 4) | ((lbo >> 4) << 16); }
template <int TB>
__device__ __forceinline__ void wgmma_ss_n128_lo(float (&d)[64], uint32_t da_lo, uint32_t db_lo, int scale_d) {
    asm volatile(
        "{\n.reg .pred p;\n.reg .b64 da, db;\nsetp.ne.b32 p, %66, 0;\n"
        "mov.b64 da, {%64, 0x40000040};\nmov.b64 db, {%65, 0x40000040};\n"
        "wgmma.mma_async.sync.aligned.m64n128k16.f32.bf16.bf16 " ACC64_STR ", da, db, p, 1, 1, 0, %67;\n}\n"
        : ACC64(d) : "r"(da_lo), "r"(db_lo), "r"(scale_d), "n"(TB));
}
__device__ __forceinline__ void wgmma_rs_n128_tb(float (&d)[64], uint32_t a0, uint32_t a1, uint32_t a2, uint32_t a3,
                                                 uint64_t db, int scale_d) {
    asm volatile(
        "{\n.reg .pred p;\nsetp.ne.b32 p, %69, 0;\n"
        "wgmma.mma_async.sync.aligned.m64n128k16.f32.bf16.bf16 " ACC64_STR ", {%64, %65, %66, %67}, %68, p, 1, 1, 1;\n}\n"
        : ACC64(d) : "r"(a0), "r"(a1), "r"(a2), "r"(a3), "l"(db), "r"(scale_d));
}
__device__ __forceinline__ void wgmma_rs_n80(float (&d)[40], const uint32_t (&a)[4], uint32_t db_lo, int scale_d) {
    asm volatile(
        "{\n.reg .pred p;\n.reg .b64 db;\nsetp.ne.b32 p, %45, 0;\nmov.b64 db, {%44, 0x40000040};\n"
        "wgmma.mma_async.sync.aligned.m64n80k16.f32.bf16.bf16 "
        "{%0, %1, %2, %3, %4, %5, %6, %7, %8, %9, %10, %11, %12, %13, %14, %15, %16, %17, %18, %19, %20, %21, %22, %23, %24, %25, %26, %27, %28, %29, %30, %31, %32, %33, %34, %35, %36, %37, %38, %39}, "
        "{%40, %41, %42, %43}, db, p, 1, 1, 0;\n}\n"
        : "+f"(d[0]), "+f"(d[1]), "+f"(d[2]), "+f"(d[3]), "+f"(d[4]), "+f"(d[5]), "+f"(d[6]), "+f"(d[7]), "+f"(d[8]), "+f"(d[9]), "+f"(d[10]), "+f"(d[11]), "+f"(d[12]), "+f"(d[13]), "+f"(d[14]), "+f"(d[15]), "+f"(d[16]), "+f"(d[17]), "+f"(d[18]), "+f"(d[19]), "+f"(d[20]), "+f"(d[21]), "+f"(d[22]), "+f"(d[23]), "+f"(d[24]), "+f"(d[25]), "+f"(d[26]), "+f"(d[27]), "+f"(d[28]), "+f"(d[29]), "+f"(d[30]), "+f"(d[31]), "+f"(d[32]), "+f"(d[33]), "+f"(d[34]), "+f"(d[35]), "+f"(d[36]), "+f"(d[37]), "+f"(d[38]), "+f"(d[39])
        : "r"(a[0]), "r"(a[1]), "r"(a[2]), "r"(a[3]), "r"(db_lo), "r"(scale_d));
}
__device__ __forceinline__ void wgmma_ss_n256_tb(float (&d)[128], uint64_t da, uint64_t db, int scale_d) {
    asm volatile(
        "{\n.reg .pred p;\nsetp.ne.b32 p, %130, 0;\n"
        "wgmma.mma_async.sync.aligned.m64n256k16.f32.bf16.bf16 {%0, %1, %2, %3, %4, %5, %6, %7, %8, %9, %10, %11, %12, %13, %14, %15, %16, %17, %18, %19, %20, %21, %22, %23, %24, %25, %26, %27, %28, %29, %30, %31, %32, %33, %34, %35, %36, %37, %38, %39, %40, %41, %42, %43, %44, %45, %46, %47, %48, %49, %50, %51, %52, %53, %54, %55, %56, %57, %58, %59, %60, %61, %62, %63, %64, %65, %66, %67, %68, %69, %70, %71, %72, %73, %74, %75, %76, %77, %78, %79, %80, %81, %82, %83, %84, %85, %86, %87, %88, %89, %90, %91, %92, %93, %94, %95, %96, %97, %98, %99, %100, %101, %102, %103, %104, %105, %106, %107, %108, %109, %110, %111, %112, %113, %114, %115, %116, %117, %118, %119, %120, %121, %122, %123, %124, %125, %126, %127}, %128, %129, p, 1, 1, 0, 1;\n}\n"
        : "+f"(d[0]), "+f"(d[1]), "+f"(d[2]), "+f"(d[3]), "+f"(d[4]), "+f"(d[5]), "+f"(d[6]), "+f"(d[7]), "+f"(d[8]), "+f"(d[9]), "+f"(d[10]), "+f"(d[11]), "+f"(d[12]), "+f"(d[13]), "+f"(d[14]), "+f"(d[15]), "+f"(d[16]), "+f"(d[17]), "+f"(d[18]), "+f"(d[19]), "+f"(d[20]), "+f"(d[21]), "+f"(d[22]), "+f"(d[23]), "+f"(d[24]), "+f"(d[25]), "+f"(d[26]), "+f"(d[27]), "+f"(d[28]), "+f"(d[29]), "+f"(d[30]), "+f"(d[31]), "+f"(d[32]), "+f"(d[33]), "+f"(d[34]), "+f"(d[35]), "+f"(d[36]), "+f"(d[37]), "+f"(d[38]), "+f"(d[39]), "+f"(d[40]), "+f"(d[41]), "+f"(d[42]), "+f"(d[43]), "+f"(d[44]), "+f"(d[45]), "+f"(d[46]), "+f"(d[47]), "+f"(d[48]), "+f"(d[49]), "+f"(d[50]), "+f"(d[51]), "+f"(d[52]), "+f"(d[53]), "+f"(d[54]), "+f"(d[55]), "+f"(d[56]), "+f"(d[57]), "+f"(d[58]), "+f"(d[59]), "+f"(d[60]), "+f"(d[61]), "+f"(d[62]), "+f"(d[63]), "+f"(d[64]), "+f"(d[65]), "+f"(d[66]), "+f"(d[67]), "+f"(d[68]), "+f"(d[69]), "+f"(d[70]), "+f"(d[71]), "+f"(d[72]), "+f"(d[73]), "+f"(d[74]), "+f"(d[75]), "+f"(d[76]), "+f"(d[77]), "+f"(d[78]), "+f"(d[79]), "+f"(d[80]), "+f"(d[81]), "+f"(d[82]), "+f"(d[83]), "+f"(d[84]), "+f"(d[85]), "+f"(d[86]), "+f"(d[87]), "+f"(d[88]), "+f"(d[89]), "+f"(d[90]), "+f"(d[91]), "+f"(d[92]), "+f"(d[93]), "+f"(d[94]), "+f"(d[95]), "+f"(d[96]), "+f"(d[97]), "+f"(d[98]), "+f"(d[99]), "+f"(d[100]), "+f"(d[101]), "+f"(d[102]), "+f"(d[103]), "+f"(d[104]), "+f"(d[105]), "+f"(d[106]), "+f"(d[107]), "+f"(d[108]), "+f"(d[109]), "+f"(d[110]), "+f"(d[111]), "+f"(d[112]), "+f"(d[113]), "+f"(d[114]), "+f"(d[115]), "+f"(d[116]), "+f"(d[117]), "+f"(d[118]), "+f"(d[119]), "+f"(d[120]), "+f"(d[121]), "+f"(d[122]), "+f"(d[123]), "+f"(d[124]), "+f"(d[125]), "+f"(d[126]), "+f"(d[127])
        : "l"(da), "l"(db), "r"(scale_d));
}
__device__ __forceinline__ void stmatrix_x4(uint32_t addr, uint32_t r0, uint32_t r1, uint32_t r2, uint32_t r3) {
    asm volatile("stmatrix.sync.aligned.m8n8.x4.shared.b16 [%0], {%1, %2, %3, %4};" :: "r"(addr), "r"(r0), "r"(r1), "r"(r2), "r"(r3) : "memory");
}
__device__ __forceinline__ void tma_store_2d(const CUtensorMap* map, uint32_t src, int c0, int c1) {
    asm volatile("cp.async.bulk.tensor.2d.global.shared::cta.bulk_group [%0, {%2, %3}], [%1];"
                 :: "l"((uint64_t)map), "r"(src), "r"(c0), "r"(c1) : "memory");
}
__device__ __forceinline__ float ex2f(float x) { float y; asm("ex2.approx.ftz.f32 %0, %1;" : "=f"(y) : "f"(x)); return y; }
__device__ __forceinline__ uint32_t pack_bf16(float lo, float hi) {
    __nv_bfloat162 v = __floats2bfloat162_rn(lo, hi);
    return *reinterpret_cast<uint32_t*>(&v);
}
__device__ __forceinline__ void mma_16816(float (&c)[4], uint32_t a0, uint32_t a1, uint32_t a2, uint32_t a3,
                                          uint32_t b0, uint32_t b1) {
    asm volatile(
        "mma.sync.aligned.m16n8k16.row.col.f32.bf16.bf16.f32 {%0,%1,%2,%3}, {%4,%5,%6,%7}, {%8,%9}, {%0,%1,%2,%3};"
        : "+f"(c[0]), "+f"(c[1]), "+f"(c[2]), "+f"(c[3])
        : "r"(a0), "r"(a1), "r"(a2), "r"(a3), "r"(b0), "r"(b1));
}
__device__ __forceinline__ void ldmatrix_x4_trans(uint32_t& r0, uint32_t& r1, uint32_t& r2, uint32_t& r3, uint32_t addr) {
    asm volatile("ldmatrix.sync.aligned.m8n8.x4.trans.shared.b16 {%0,%1,%2,%3}, [%4];"
                 : "=r"(r0), "=r"(r1), "=r"(r2), "=r"(r3) : "r"(addr));
}

struct AttnParams {
    CUtensorMap mapQ, mapK, mapV;
    CUtensorMap mapO;
    bf16* out;
};
constexpr int FA_SMEM = 2 * 32768 + 2 * 65536 + 32768 + 1024 + 256;
constexpr int FA_ITEMS = 16 * NH;
__device__ __forceinline__ int fa_qt(int t) { return 15 - ((t & 127) >> 3); }
__device__ __forceinline__ int fa_head(int t) { return (t >> 7) * 8 + (t & 7); }
#define FA_TKA 2
#define FA_SPLIT 11

#define FA_P0 3
#define FA_HO 7
#define FA_LAG 2
#define FA_PK 3
#define FA_ST 4
#define FA_TG 16
#define FA_EARLY 0
#define FA_I0 0
static_assert(FA_GRID <= 104 && FA_HO >= FA_P0 && FA_P0 >= 1, "");
constexpr float FA_MARGIN = 16.f;
#define FAT(b, i)
__device__ __forceinline__ void mbar_arrive_if(uint32_t bar, bool c) {
    asm volatile("{\n.reg .pred p;\nsetp.ne.b32 p, %1, 0;\n@p mbarrier.arrive.shared::cta.b64 _, [%0];\n}" :: "r"(bar), "r"((int)c) : "memory");
}
__device__ __forceinline__ void sched_fence(int v, int id, const float* a, const float* b, const float* c) {
    asm volatile("{\n.reg .pred p;\nsetp.ne.s32 p, %0, %1;\n@p bra SF_SKIP;\nwgmma.wait_group.sync.aligned 0;\n"
                 "st.volatile.shared.f32 [%0], %2;\nst.volatile.shared.f32 [%0], %3;\nst.volatile.shared.f32 [%0], %4;\nst.volatile.shared.f32 [%0], %5;\n"
                 "st.volatile.shared.f32 [%0], %6;\nst.volatile.shared.f32 [%0], %7;\nst.volatile.shared.f32 [%0], %8;\nst.volatile.shared.f32 [%0], %9;\n"
                 "st.volatile.shared.f32 [%0], %10;\nst.volatile.shared.f32 [%0], %11;\nst.volatile.shared.f32 [%0], %12;\nst.volatile.shared.f32 [%0], %13;\n"
                 "exit;\nSF_SKIP:\n}" :: "r"(v), "r"(1000000 + id), "f"(a[0]), "f"(a[1]), "f"(a[2]), "f"(a[3]), "f"(b[0]), "f"(b[1]), "f"(b[2]), "f"(b[3]),
                 "f"(c[0]), "f"(c[1]), "f"(c[2]), "f"(c[3]) : "memory");
}
__device__ __forceinline__ float ex2v(float x) { float y; asm volatile("ex2.approx.ftz.f32 %0, %1;" : "=f"(y) : "f"(x)); return y; }
__device__ __forceinline__ void wgmma_rs_n128_tb_lo(float (&d)[64], const uint32_t* a, uint32_t db_lo, int scale_d) {
    asm volatile(
        "{\n.reg .pred p;\n.reg .b64 db;\nsetp.ne.b32 p, %69, 0;\nmov.b64 db, {%68, 0x40000040};\n"
        "wgmma.mma_async.sync.aligned.m64n128k16.f32.bf16.bf16 " ACC64_STR ", {%64, %65, %66, %67}, db, p, 1, 1, 1;\n}\n"
        : ACC64(d) : "r"(a[0]), "r"(a[1]), "r"(a[2]), "r"(a[3]), "r"(db_lo), "r"(scale_d));
}

__global__ void __launch_bounds__(384, 1) attn_kernel(const __grid_constant__ AttnParams P) {
    extern __shared__ uint8_t smem_raw[];
    constexpr uint32_t sbase = 1024;
    if (smem_u32(smem_raw) > sbase) __trap();
    constexpr uint32_t sQ = sbase;
    constexpr uint32_t sKV = sbase + 65536;
    constexpr uint32_t sO = sKV + 2 * 65536;
    constexpr uint32_t bars = sO + 32768;
    constexpr uint32_t bar_qf = bars, bar_qe = bars + 16, bar_kf = bars + 32, bar_vf = bars + 48, bar_ke = bars + 64, bar_ve = bars + 80,
                   bar_of = bars + 96, bar_oe = bars + 112, slot = bars + 128, oslot = bars + 136;
    const int warp = __shfl_sync(0xffffffff, threadIdx.x >> 5, 0);
    TS_BEGIN(1);
    if (threadIdx.x == 256) {
        asm volatile("prefetch.tensormap [%0];" :: "l"(&P.mapQ) : "memory");
        asm volatile("prefetch.tensormap [%0];" :: "l"(&P.mapK) : "memory");
        for (int i = 0; i < 2; i++) {
            mbar_init(bar_qf + 8 * i, 1); mbar_init(bar_qe + 8 * i, 8); mbar_init(bar_kf + 8 * i, 1); mbar_init(bar_vf + 8 * i, 1);
            mbar_init(bar_ke + 8 * i, 8); mbar_init(bar_ve + 8 * i, 8); mbar_init(bar_of + 8 * i, 4); mbar_init(bar_oe + 8 * i, 1);
        }
        asm volatile("fence.mbarrier_init.release.cluster;" ::: "memory");
    }
    __syncthreads();
    pdl_launch_dependents();
    if (warp >= 8) {
        asm volatile("setmaxnreg.dec.sync.aligned.u32 40;");
        if (threadIdx.x == 288 || threadIdx.x == 320) {
            const int wg = threadIdx.x == 288 ? 0 : 1;
            const uint32_t stg = sO + wg * 16384;
            for (int n = 0;; n++) {
                mbar_wait(bar_of + 8 * wg, n & 1);
                int t;
                asm volatile("ld.shared.s32 %0, [%1];" : "=r"(t) : "r"(oslot + wg * 4) : "memory");
                const int qt = fa_qt(t), h = fa_head(t & 1023);
                tma_store_2d(&P.mapO, stg, 0, h * SEQ + qt * 128 + wg * 64);
                tma_store_2d(&P.mapO, stg + 8192, 64, h * SEQ + qt * 128 + wg * 64);
                asm volatile("cp.async.bulk.commit_group;" ::: "memory");
                asm volatile("cp.async.bulk.wait_group.read 0;" ::: "memory");
                mbar_arrive(bar_oe + 8 * wg);
                asm volatile("cp.async.bulk.wait_group 0;" ::: "memory");
                signal_ctr(CT_CA + qt * 4 + (h >> 3));
                if (t >= 1024) break;
            }
        }
        if (threadIdx.x == 256) {
            int b = 0, hp_ready = 0, vrow = 0, t = blockIdx.x;
            auto load_v = [&](int i) {
                const uint32_t sv = sKV + (i & 1) * 65536 + 32768, bar = bar_vf + 8 * (i & 1);
                mbar_wait(bar_ve + 8 * (i & 1), ((i >> 1) & 1) ^ 1);
                mbar_expect_tx(bar, 32768);
                tma_load_2d(sv, &P.mapV, bar, 0, vrow);
                tma_load_2d(sv + 16384, &P.mapV, bar, 64, vrow);
            };
            for (int item = 0;; item++) {
                const bool valid = t < FA_ITEMS;
                const int qt = fa_qt(t), h = fa_head(t);
                if (valid && !((hp_ready >> (h >> 1)) & 1)) { wait_ctr(CT_AP + (h >> 1), 96u); hp_ready |= 1 << (h >> 1); }
                const uint32_t bq = bar_qf + 8 * (item & 1);
                mbar_wait(bar_qe + 8 * (item & 1), ((item >> 1) & 1) ^ 1);
                asm volatile("st.shared.s32 [%0], %1;" :: "r"(slot + (item & 1) * 4), "r"(valid ? t : -1) : "memory");
                if (!valid) { mbar_arrive(bq); break; }
                mbar_expect_tx(bq, 32768);
                tma_load_2d(sQ + (item & 1) * 32768, &P.mapQ, bq, 0, h * SEQ + qt * 128);
                tma_load_2d(sQ + (item & 1) * 32768 + 16384, &P.mapQ, bq, 64, h * SEQ + qt * 128);
#pragma unroll 1
                for (int j = 0; j <= qt; j++, b++) {
                    const uint32_t sk = sKV + (b & 1) * 65536, bar = bar_kf + 8 * (b & 1);
                    mbar_wait(bar_ke + 8 * (b & 1), ((b >> 1) & 1) ^ 1);
                    if (b == 2) wait_ctr(CT_GATE, 64u);
                    mbar_expect_tx(bar, 32768);
                    tma_load_2d(sk, &P.mapK, bar, 0, h * SEQ + j * 128);
                    tma_load_2d(sk + 16384, &P.mapK, bar, 64, h * SEQ + j * 128);
                    if (j == max(qt - FA_TKA, 0)) t = take_ticket(CT_ATTN);
                    if (b > 0) load_v(b - 1);
                    vrow = h * SEQ + j * 128;
                }
                t += gridDim.x;
            }
            load_v(b - 1);
        }
    } else {
        asm volatile("setmaxnreg.inc.sync.aligned.u32 232;");
        const int wg = warp >> 2;
        const int lane = threadIdx.x & 31;
        const float sc = 0.08838834764831845f * 1.4426950408889634f;
        const int r0 = wg * 64 + (warp & 3) * 16 + (lane >> 2);
        float o[64], s[64];
        uint32_t pa[32];
        float m0 = 0.f, m1 = 0.f, l0 = 0.f, l1 = 0.f, i0 = 0.f, i1 = 0.f, g0 = 0.f, g1 = 0.f;
        const uint32_t q_lo = desc_lo(sQ + wg * 8192, 16), k_lo = desc_lo(sKV, 16), v_lo = desc_lo(sKV + 32768, 16384);
        auto issue_qk = [&](int b, int item) {
            const uint32_t qd = q_lo + (item & 1) * 2048, kd = k_lo + (b & 1) * 4096;
            wgmma_fence();
#pragma unroll
            for (int kk = 0; kk < 8; kk++) wgmma_ss_n128_lo<0>(s, qd + (kk >> 2) * 1024 + (kk & 3) * 2, kd + (kk >> 2) * 1024 + (kk & 3) * 2, kk != 0);
            wgmma_commit();
        };
        auto issue_pv = [&](int b, bool acc, int n) {
            const uint32_t vd = v_lo + (b & 1) * 4096;
            mbar_wait(bar_vf + 8 * (b & 1), (b >> 1) & 1);
            wgmma_fence();
#pragma unroll
            for (int kk = 0; kk < 8; kk++) if (kk < n) wgmma_rs_n128_tb_lo(o, &pa[kk * 4], vd + kk * 128, kk ? 1 : (int)acc);
            wgmma_commit();
        };
        const int lim = r0 - (lane & 3) * 2;
        int item = -1, tnext = 0;
        uint32_t k_ready = 0, q_ready = 0;
        auto mask = [&](int i) { if ((i >> 2) * 8 + (i & 1) - ((i & 2) ? 8 : 0) > lim) s[i] = -INFINITY; };
        auto exps = [&](auto mode, int b, bool hand_over, float& u0, float& u1) {
            constexpr int MODE = decltype(mode)::value;
            float p[64], u[4] = {0.f, 0.f, 0.f, 0.f};
            const uint32_t vd = v_lo + ((b - 1) & 1) * 4096;
#pragma unroll
            for (int i = 0; i < 4; i++) p[i] = fmaf(s[i], sc, (i & 2) ? -m1 : -m0);
#pragma unroll
            for (int g = 0; g < 16 + FA_LAG; g++) {
                if (MODE && g >= FA_I0 && g - FA_I0 < 8 - FA_P0) {
                    const int kk = FA_P0 + g - FA_I0;
                    wgmma_fence();
                    wgmma_rs_n128_tb_lo(o, &pa[kk * 4], vd + kk * 128, 1);
                    wgmma_commit();
                    if (kk == FA_HO) asm volatile("{\n.reg .pred p;\nsetp.ne.b32 p, %1, 0;\n@p bar.arrive %0, 256;\n}" :: "r"(2 - wg), "r"((int)hand_over) : "memory");
                }
                if (MODE && g == FA_SPLIT) {
                    FAT(b, 2);
                    wgmma_wait<0>();
                    FAT(b - 1, 3);
                    mbar_arrive_if(bar_ve + 8 * ((b - 1) & 1), lane == 0);
                }
                if (MODE && g == FA_TG) {
                    k_ready = mbar_test(bar_kf + 8 * (~b & 1), ((b + 1) >> 1) & 1);
                    if (MODE == 2) {
                        q_ready = mbar_test(bar_qf + 8 * (~item & 1), ((item + 1) >> 1) & 1);
                        asm volatile("ld.shared.s32 %0, [%1];" : "=r"(tnext) : "r"(slot + (~item & 1) * 4) : "memory");
                    }
                }
#pragma unroll
                for (int j = 0; j < 4; j++) {
                    const int i = g * 4 + j;
                    if (g < 16) p[i] = ex2v(p[i]);
                    if (g < 15) {
                        if (MODE == 2) mask(i + 4);
                        p[i + 4] = fmaf(s[i + 4], sc, (i & 2) ? -m1 : -m0);
                    }
                    if (g >= FA_LAG) u[j] += p[i - FA_LAG * 4];
                }
#pragma unroll
                for (int gg = 0; gg < 16; gg++) {
                    const int at = MODE && gg + FA_LAG < FA_SPLIT + gg / FA_PK ? FA_SPLIT + gg / FA_PK : gg + FA_LAG;
                    if (at == g) { pa[gg * 2] = pack_bf16(p[gg * 4], p[gg * 4 + 1]); pa[gg * 2 + 1] = pack_bf16(p[gg * 4 + 2], p[gg * 4 + 3]); }
                }
                if (MODE && g < 16) sched_fence(b, g + MODE * 32, &p[g * 4], &p[(g < 15 ? g + 1 : g) * 4], u);
            }
            u0 = u[0] + u[1]; u1 = u[2] + u[3];
        };
        auto quad_max = [&](float& x0, float& x1) {
            x0 = fmaxf(x0, __shfl_xor_sync(0xffffffff, x0, 1)); x1 = fmaxf(x1, __shfl_xor_sync(0xffffffff, x1, 1));
            x0 = fmaxf(x0, __shfl_xor_sync(0xffffffff, x0, 2)); x1 = fmaxf(x1, __shfl_xor_sync(0xffffffff, x1, 2));
            x0 = fmaf(x0, sc, FA_MARGIN); x1 = fmaf(x1, sc, FA_MARGIN);
        };
        auto softmax_exact = [&](bool fresh, int b) {
            wgmma_wait<0>();
            float x[8];
#pragma unroll
            for (int i = 0; i < 8; i++) x[i] = fmaxf(s[i * 2], s[i * 2 + 1]);
#pragma unroll
            for (int i = 8; i < 32; i++) x[i & 7] = fmaxf(x[i & 7], fmaxf(s[i * 2], s[i * 2 + 1]));
            float x0 = fmaxf(fmaxf(x[0], x[2]), fmaxf(x[4], x[6])), x1 = fmaxf(fmaxf(x[1], x[3]), fmaxf(x[5], x[7]));
            quad_max(x0, x1);
            if (!fresh) {
                x0 = fmaxf(x0, m0); x1 = fmaxf(x1, m1);
                const float a0 = ex2f(m0 - x0), a1 = ex2f(m1 - x1);
                l0 *= a0; l1 *= a1;
#pragma unroll
                for (int i = 0; i < 16; i++) { o[i * 4 + 0] *= a0; o[i * 4 + 1] *= a0; o[i * 4 + 2] *= a1; o[i * 4 + 3] *= a1; }
            }
            m0 = x0; m1 = x1;
            float u0, u1;
            exps(std::integral_constant<int, 0>(), b, false, u0, u1);
            l0 += u0; l1 += u1;
        };
        auto finish_rows = [&]() {
            l0 += __shfl_xor_sync(0xffffffff, l0, 1); l1 += __shfl_xor_sync(0xffffffff, l1, 1);
            l0 += __shfl_xor_sync(0xffffffff, l0, 2); l1 += __shfl_xor_sync(0xffffffff, l1, 2);
            i0 = __fdividef(g0, l0); i1 = __fdividef(g1, l1);
        };
        auto clear_out = [&](int t) {
            if (t >= 384) {
                bf16* z = P.out + (size_t)(fa_qt(t) * 128 + wg * 64 + ((threadIdx.x & 127) >> 3)) * DM + (t & 7) * 64 + (lane & 7) * 8;
#pragma unroll
                for (int i = 0; i < 4; i++) *reinterpret_cast<uint4*>(z + i * 16 * DM) = make_uint4(0u, 0u, 0u, 0u);
            }
        };
        auto store_o = [&](int t, int n, int c0, int c1) {
            const uint32_t stg = sO + wg * 16384;
            if (c0 == 0) {
                mbar_wait(bar_oe + 8 * wg, (n & 1) ^ 1);
                asm volatile("st.shared.s32 [%0], %1;" :: "r"(oslot + wg * 4), "r"(t) : "memory");
            }
            const int row = (warp & 3) * 16 + (lane >> 2);
#pragma unroll
            for (int i = c0; i < c1; i++) {
                const int ch = i * 4 + (lane & 3);
                const uint32_t a = stg + (ch >> 3) * 8192 + row * 128 + (((ch & 7) ^ (row & 7)) << 4);
                const float* q = &o[i * 16];
                asm volatile("st.shared.v4.b32 [%0], {%1, %2, %3, %4};" :: "r"(a), "r"(pack_bf16(q[0] * i0, q[1] * i0)), "r"(pack_bf16(q[4] * i0, q[5] * i0)),
                             "r"(pack_bf16(q[8] * i0, q[9] * i0)), "r"(pack_bf16(q[12] * i0, q[13] * i0)) : "memory");
                asm volatile("st.shared.v4.b32 [%0], {%1, %2, %3, %4};" :: "r"(a + 1024), "r"(pack_bf16(q[2] * i1, q[3] * i1)), "r"(pack_bf16(q[6] * i1, q[7] * i1)),
                             "r"(pack_bf16(q[10] * i1, q[11] * i1)), "r"(pack_bf16(q[14] * i1, q[15] * i1)) : "memory");
            }
        };
        auto publish_o = [&]() {
            asm volatile("fence.proxy.async.shared::cta;" ::: "memory");
            __syncwarp();
            mbar_arrive_if(bar_of + 8 * wg, lane == 0);
        };
        int t = 0, left = 0, tdone = -1, b = 0, nout = 0;
        bool first = true, staged = false;
        if (wg == 1) asm volatile("bar.arrive 1, 256;" ::: "memory");
#pragma unroll 1
        for (;; b++) {
            const bool fresh = left == 0;
            const int tprev = t;
            FAT(b, 4);
            if (staged) { publish_o(); staged = false; }
            if (fresh) {
                item++;
                if (!q_ready) {
                    mbar_wait(bar_qf + 8 * (item & 1), (item >> 1) & 1);
                    asm volatile("ld.shared.s32 %0, [%1];" : "=r"(tnext) : "r"(slot + (item & 1) * 4) : "memory");
                }
                if (tnext < 0) break;
                t = tnext;
                left = fa_qt(t) + 1;
            }
            left--;
            if (tdone >= 0) store_o(tdone, nout, 0, FA_ST);
            FAT(b, 5);
            if (!k_ready) mbar_wait(bar_kf + 8 * (b & 1), (b >> 1) & 1);
            FAT(b, 6);
            asm volatile("bar.sync %0, 256;" :: "r"(1 + wg) : "memory");
            FAT(b, 0);
            issue_qk(b, item);
            bool early = false;
            if (!fresh && !first && left != 0) {
                issue_pv(b - 1, true, FA_P0);
                wgmma_wait<1>();
                FAT(b, 1);
                mbar_arrive_if(bar_ke + 8 * (b & 1), lane == 0);
            } else {
                early = (FA_EARLY && tdone >= 0) || b == 0;
                if (early) asm volatile("bar.arrive %0, 256;" :: "r"(2 - wg) : "memory");
                if (tdone >= 0) { wgmma_wait<1>(); store_o(tdone, nout++, FA_ST, 4); staged = true; }
                tdone = -1;
                if (fresh && b > 0) { finish_rows(); tdone = tprev; l0 = l1 = 0.f; }
                if (left == 0) { g0 = __ldcg(g_gate + fa_qt(t) * 128 + r0); g1 = __ldcg(g_gate + fa_qt(t) * 128 + r0 + 8); clear_out(t); }
                if (b > 0) issue_pv(b - 1, !first, FA_P0); else wgmma_commit();
                first = fresh;
                wgmma_wait<1>();
                FAT(b, 1);
                mbar_arrive_if(bar_ke + 8 * (b & 1), lane == 0);
                mbar_arrive_if(bar_qe + 8 * (item & 1), lane == 0 && left == 0);
                if (left == 0) { mask(0); mask(1); }
                if (fresh) { m0 = fmaxf(s[0], s[1]); m1 = fmaxf(s[2], s[3]); quad_max(m0, m1); }
            }
            if (b > 0) {
                float u0, u1;
                if (left == 0) exps(std::integral_constant<int, 2>(), b, !early, u0, u1);
                else exps(std::integral_constant<int, 1>(), b, !early, u0, u1);
                if (!__any_sync(0xffffffff, !(u0 + u1 < 1.f))) { l0 += u0; l1 += u1; continue; }
            }
            softmax_exact(fresh, b);
        }
        if (tdone >= 0) { store_o(tdone, nout++, 0, 4); publish_o(); }
        issue_pv(b - 1, !first, 8);
        finish_rows();
        wgmma_wait<0>();
        store_o(t + 1024, nout, 0, 4);
        publish_o();
        TS_END(1);
    }
}

__device__ __forceinline__ uint32_t cluster_ctarank() {
    uint32_t r; asm volatile("mov.u32 %0, %%cluster_ctarank;" : "=r"(r)); return r;
}
__device__ __forceinline__ uint32_t mapa_u32(uint32_t addr, uint32_t rank) {
    uint32_t r; asm volatile("mapa.shared::cluster.u32 %0, %1, %2;" : "=r"(r) : "r"(addr), "r"(rank)); return r;
}
__device__ __forceinline__ void cluster_sync_all() {
    asm volatile("barrier.cluster.arrive.release.aligned;\nbarrier.cluster.wait.acquire.aligned;" ::: "memory");
}
__device__ __forceinline__ void st_async_v4(uint32_t addr, uint32_t a, uint32_t b, uint32_t c, uint32_t d, uint32_t mbar) {
    asm volatile("st.async.weak.shared::cluster.mbarrier::complete_tx::bytes.v4.b32 [%0], {%1, %2, %3, %4}, [%5];"
                 :: "r"(addr), "r"(a), "r"(b), "r"(c), "r"(d), "r"(mbar) : "memory");
}
__device__ __forceinline__ void st_async_v2(uint32_t addr, uint32_t a, uint32_t b, uint32_t mbar) {
    asm volatile("st.async.weak.shared::cluster.mbarrier::complete_tx::bytes.v2.b32 [%0], {%1, %2}, [%3];"
                 :: "r"(addr), "r"(a), "r"(b), "r"(mbar) : "memory");
}
__device__ __forceinline__ void st_async_b32(uint32_t addr, uint32_t a, uint32_t mbar) {
    asm volatile("st.async.weak.shared::cluster.mbarrier::complete_tx::bytes.b32 [%0], %1, [%2];" :: "r"(addr), "r"(a), "r"(mbar) : "memory");
}
__device__ __forceinline__ void pace(int cycles) {
    if (cycles > 0) {
        uint32_t t0, t;
        asm volatile("mov.u32 %0, %%clock;" : "=r"(t0));
        do { asm volatile("mov.u32 %0, %%clock;" : "=r"(t)); } while (t - t0 < (uint32_t)cycles);
    }
}
__device__ __forceinline__ void mbar_wait_cl(uint32_t bar, uint32_t parity) {
    uint32_t done = 0;
    for (int it = 0; it < WAIT_LIMIT && !done; it++) {
        asm volatile(
            "{\n.reg .pred p;\n"
            "mbarrier.try_wait.parity.shared::cta.b64 p, [%1], %2;\n"
            "selp.u32 %0, 1, 0, p;\n}\n" : "=r"(done) : "r"(bar), "r"(parity) : "memory");
    }
}
__device__ __forceinline__ void ldmatrix_x4(uint32_t& r0, uint32_t& r1, uint32_t& r2, uint32_t& r3, uint32_t addr) {
    asm volatile("ldmatrix.sync.aligned.m8n8.x4.shared.b16 {%0,%1,%2,%3}, [%4];"
                 : "=r"(r0), "=r"(r1), "=r"(r2), "=r"(r3) : "r"(addr));
}
__device__ __forceinline__ void cp_async16(uint32_t dst, const void* src) {
    asm volatile("cp.async.cg.shared.global [%0], [%1], 16;" :: "r"(dst), "l"(src) : "memory");
}
__device__ __forceinline__ float bf16r(float x) { return __uint_as_float(pack_bf16(0.f, x) & 0xffff0000u); }

#define DBG(i, w)
#define DBGD(i, w, dep)
#define DBG_EXTRA 0
__device__ __forceinline__ void tma_load_2d_mc(uint32_t dst, const CUtensorMap* map, uint32_t bar, int c0, int c1, uint16_t mask) {
    asm volatile(
        "cp.async.bulk.tensor.2d.shared::cluster.global.mbarrier::complete_tx::bytes.multicast::cluster [%0], [%1, {%3, %4}], [%2], %5;"
        :: "r"(dst), "l"((uint64_t)map), "r"(bar), "r"(c0), "r"(c1), "h"(mask) : "memory");
}
__device__ __forceinline__ void stmatrix_x4_trans(uint32_t addr, uint32_t r0, uint32_t r1, uint32_t r2, uint32_t r3) {
    asm volatile("stmatrix.sync.aligned.m8n8.x4.trans.shared.b16 [%0], {%1, %2, %3, %4};" :: "r"(addr), "r"(r0), "r"(r1), "r"(r2), "r"(r3) : "memory");
}
__device__ __forceinline__ void stmatrix_x2_trans(uint32_t addr, uint32_t r0, uint32_t r1) {
    asm volatile("stmatrix.sync.aligned.m8n8.x2.trans.shared.b16 [%0], {%1, %2};" :: "r"(addr), "r"(r0), "r"(r1) : "memory");
}
__device__ __forceinline__ uint4 lds128(uint32_t a) {
    uint4 v; asm volatile("ld.shared.v4.u32 {%0, %1, %2, %3}, [%4];" : "=r"(v.x), "=r"(v.y), "=r"(v.z), "=r"(v.w) : "r"(a) : "memory"); return v;
}
__device__ __forceinline__ void sts128(uint32_t a, uint32_t x, uint32_t y, uint32_t z, uint32_t w) {
    asm volatile("st.shared.v4.b32 [%0], {%1, %2, %3, %4};" :: "r"(a), "r"(x), "r"(y), "r"(z), "r"(w) : "memory");
}
__device__ __forceinline__ float2 lds64f(uint32_t a) {
    float2 v; asm volatile("ld.shared.v2.f32 {%0, %1}, [%2];" : "=f"(v.x), "=f"(v.y) : "r"(a) : "memory"); return v;
}
__device__ __forceinline__ void fence_async_smem() { asm volatile("fence.proxy.async.shared::cta;" ::: "memory"); }
#define ACC16(d) "+f"(d[0]), "+f"(d[1]), "+f"(d[2]), "+f"(d[3]), "+f"(d[4]), "+f"(d[5]), "+f"(d[6]), "+f"(d[7]), "+f"(d[8]), "+f"(d[9]), "+f"(d[10]), "+f"(d[11]), "+f"(d[12]), "+f"(d[13]), "+f"(d[14]), "+f"(d[15])
template <int ND>
__device__ __forceinline__ void wgmma_rs_n32(float (&d)[ND], const uint32_t (&a)[4], uint32_t db_lo, int scale_d) {
    asm volatile(
        "{\n.reg .pred p;\n.reg .b64 db;\nsetp.ne.b32 p, %21, 0;\nmov.b64 db, {%20, 0x40000040};\n"
        "wgmma.mma_async.sync.aligned.m64n32k16.f32.bf16.bf16 {%0,%1,%2,%3,%4,%5,%6,%7,%8,%9,%10,%11,%12,%13,%14,%15}, {%16,%17,%18,%19}, db, p, 1, 1, 0;\n}\n"
        : ACC16(d) : "r"(a[0]), "r"(a[1]), "r"(a[2]), "r"(a[3]), "r"(db_lo), "r"(scale_d));
}
template <int ND>
__device__ __forceinline__ void wgmma_ss_n32(float (&d)[ND], uint32_t da_lo, uint32_t db_lo, int scale_d) {
    asm volatile(
        "{\n.reg .pred p;\n.reg .b64 da, db;\nsetp.ne.b32 p, %18, 0;\nmov.b64 da, {%16, 0x40000040};\nmov.b64 db, {%17, 0x40000040};\n"
        "wgmma.mma_async.sync.aligned.m64n32k16.f32.bf16.bf16 {%0,%1,%2,%3,%4,%5,%6,%7,%8,%9,%10,%11,%12,%13,%14,%15}, da, db, p, 1, 1, 1, 0;\n}\n"
        : ACC16(d) : "r"(da_lo), "r"(db_lo), "r"(scale_d));
}
__device__ __forceinline__ void wgmma_ss_n8(float (&d)[4], uint32_t da_lo, uint32_t db_lo, int scale_d) {
    asm volatile(
        "{\n.reg .pred p;\n.reg .b64 da, db;\nsetp.ne.b32 p, %6, 0;\nmov.b64 da, {%4, 0x40000040};\nmov.b64 db, {%5, 0x00000010};\n"
        "wgmma.mma_async.sync.aligned.m64n8k16.f32.bf16.bf16 {%0,%1,%2,%3}, da, db, p, 1, 1, 1, 0;\n}\n"
        : "+f"(d[0]), "+f"(d[1]), "+f"(d[2]), "+f"(d[3]) : "r"(da_lo), "r"(db_lo), "r"(scale_d));
}

#define SCHED_FENCE()
__device__ __forceinline__ void wgmma_ss_n32_p(float (&d)[16], uint32_t da_lo, uint32_t db_lo, int scale_d) {
    asm volatile(
        "{\n.reg .pred p;\n.reg .b64 da, db;\nsetp.ne.b32 p, %18, 0;\nmov.b64 da, {%16, 0x40000040};\nmov.b64 db, {%17, 0x00000030};\n"
        "wgmma.mma_async.sync.aligned.m64n32k16.f32.bf16.bf16 {%0,%1,%2,%3,%4,%5,%6,%7,%8,%9,%10,%11,%12,%13,%14,%15}, da, db, p, 1, 1, 1, 0;\n}\n"
        : ACC16(d) : "r"(da_lo), "r"(db_lo), "r"(scale_d));
}

__device__ __forceinline__ void wgmma_ss_n32_kk(float (&d)[16], uint32_t da_lo, uint32_t db_lo, int scale_d) {
    asm volatile(
        "{\n.reg .pred p;\n.reg .b64 da, db;\nsetp.ne.b32 p, %18, 0;\nmov.b64 da, {%16, 0x40000040};\nmov.b64 db, {%17, 0x40000040};\n"
        "wgmma.mma_async.sync.aligned.m64n32k16.f32.bf16.bf16 {%0,%1,%2,%3,%4,%5,%6,%7,%8,%9,%10,%11,%12,%13,%14,%15}, da, db, p, 1, 1, 0, 0;\n}\n"
        : ACC16(d) : "r"(da_lo), "r"(db_lo), "r"(scale_d));
}

#define PT(i, th)
struct ChainParams {
    CUtensorMap mapW[3];
    CUtensorMap mapX;
    CUtensorMap mapC;
};
constexpr int CH_BLOCK = 384;
constexpr int CO_WO = 0;
constexpr int CO_XB = 65536;
constexpr int CO_MB = CO_XB + 65536;
constexpr int CO_OB = CO_MB + 8192;
constexpr int CH_TW = 6144, CH_TP = 3 * CH_TW;
constexpr int CO_T = CO_OB + 8192;
constexpr int CO_SC = CO_T + 2 * CH_TP;
constexpr int CO_LS = CO_SC + 2 * 1280;
constexpr int CO_LO = CO_LS + 8 * 1280;
constexpr int CO_P = CO_LO + 4 * 1280;
constexpr int CO_ST = 205824;
#define CH_NSM 3
constexpr int CO_WA = CO_ST + 4096;
constexpr int CO_BAR = CO_WA + CH_TP;
constexpr int CH_SMEM = CO_BAR + 256 + 1024 + DBG_EXTRA;
static_assert(CO_WA >= 3 * 65536 && CO_P + 3072 <= CO_ST && CH_NSM <= 3, "smem layout");
#define CH_POLL_DELAY 0
#define CH_VPOS 2
#define CH_VST 0
#define CH_V3_DELAY 0
#define CH_LSPOS 1
#define CH_V1 0
#define CH_V2 24
#define CH_V3 32
#define CH_OG 2
#define CH_OW 8
#define CH_OF 12
#define CH_CHAINS 4

constexpr float CH_SC = 0.08838834764831845f * 1.4426950408889634f;
__device__ __forceinline__ uint32_t pin(uint32_t v) { return __shfl_sync(0xffffffff, v, threadIdx.x & 31); }

__global__ void __cluster_dims__(8, 1, 1) __launch_bounds__(CH_BLOCK, 1)
chain_kernel(const __grid_constant__ ChainParams P, const bf16* __restrict__ mem0, const bf16* __restrict__ Wo, const bf16* __restrict__ x,
             const bf16* __restrict__ gate_w) {
    extern __shared__ uint8_t smem_raw[];
    const uint32_t sb = (smem_u32(smem_raw) + 1023) & ~1023u;
    const int tid = threadIdx.x, warp = __shfl_sync(0xffffffff, tid >> 5, 0), lane = tid & 31;
    const int rank = (int)cluster_ctarank();
    const int C = blockIdx.x >> 3;
    const int h = C * 4 + (rank >> 1);
    const int qd = lane >> 2, qc = lane & 3;
    const int t4 = warp & 3, wg = warp >> 2;
    pdl_launch_dependents();
    TS_BEGIN(2);
    PT(0, 0);
    const uint32_t bar_mem = sb + CO_BAR, bar_o = bar_mem + 32, bar_sc = bar_o + 32, bar_x = bar_sc + 8, bar_l = bar_x + 16, bar_w = bar_l + 8;
    if (tid == 0) {
        for (int j = 0; j < 15; j++) mbar_init(bar_mem + 8 * j, bar_mem + 8 * j == bar_l ? 4 : 1);
        asm volatile("fence.mbarrier_init.release.cluster;" ::: "memory");
    }
    __syncthreads();
    if ((tid & 127) == 0) {
        mbar_expect_tx(bar_w + 8 * wg, 65536);
        for (int i = 0; i < 8; i++)
            tma_load_2d(sb + wg * 65536 + i * 8192, &P.mapW[wg], bar_w + 8 * wg, h * HD + (rank & 1) * 64, i * 64);
    }
    PT(1, 0);
    {
        for (int i = tid; i < 512; i += CH_BLOCK) asm volatile("prefetch.global.L2 [%0];" :: "l"(Wo + (size_t)(C * 512 + i) * DM + rank * 64));
        if (tid < 64) asm volatile("prefetch.global.L2 [%0];" :: "l"(x + (size_t)tid * DM + rank * 64));
    }
    if (tid < 256) {
        const int r = blockIdx.x * 32 + (tid >> 3);
        float sum = 0.f;
#pragma unroll
        for (int c = 0; c < 8; c++) {
            const int col = c * 64 + (tid & 7) * 8;
            const uint4 xv = __ldg(reinterpret_cast<const uint4*>(x + (size_t)r * DM + col));
            const uint4 gv = __ldg(reinterpret_cast<const uint4*>(gate_w + col));
            const bf16* xp = reinterpret_cast<const bf16*>(&xv);
            const bf16* gp = reinterpret_cast<const bf16*>(&gv);
#pragma unroll
            for (int e = 0; e < 8; e++) sum += bf16r(__bfloat162float(xp[e]) * __bfloat162float(gp[e]));
        }
        sum += __shfl_xor_sync(0xffffffff, sum, 1);
        sum += __shfl_xor_sync(0xffffffff, sum, 2);
        sum += __shfl_xor_sync(0xffffffff, sum, 4);
        if ((tid & 7) == 0) g_gate[r] = bf16r(1.f / (1.f + __expf(-bf16r(sum))));
        asm volatile("bar.sync 1, 256;" ::: "memory");
        if (tid == 32) signal_ctr_generic(CT_GATE);
    }
    auto chunk = [&](int i) { return (uint32_t)((rank - (i >> 1) - 4 * (i & 1)) & 7); };
    const uint32_t wfrag = (((lane >> 4) << 3) + (lane & 7)) * 128 + (((t4 * 2 + ((lane >> 3) & 1)) ^ (lane & 7)) << 4);
    const uint32_t aO = pin(sb + wg * CH_TW + wfrag);
    const uint32_t aM = pin(sb + (lane & 7) * 128 + (((lane >> 3) ^ (lane & 7)) << 4));
    const uint32_t aL = pin(sb + lane * 8);
    uint32_t w[32][4];
    float d[16];
    PT(2, 0);
    mbar_wait(bar_w + 8 * wg, 0);
    PT(3, 0); PT(4, 256);
#pragma unroll
    for (int e = CH_NSM; e < 32; e++) ldmatrix_x4_trans(w[e][0], w[e][1], w[e][2], w[e][3], sb + wg * 65536 + wfrag + chunk(e >> 2) * 8192 + (e & 3) * 2048);
#pragma unroll
    for (int e = 0; e < CH_NSM; e++) {
        const uint4 u = lds128(sb + wg * 65536 + chunk(0) * 8192 + e * 2048 + (tid & 127) * 16);
        sts128(sb + CO_WA + wg * CH_TW + e * 2048 + (tid & 127) * 16, u.x, u.y, u.z, u.w);
    }
    fence_async_smem();
    __syncthreads();
    PT(5, 0);
    if (tid == 0) {
        fence_async_smem();
        for (int b = 0; b < 2; b++) {
            mbar_expect_tx(bar_x + 8 * b, 32768);
            for (int i = 0; i < 8; i++) tma_load_2d(sb + CO_XB + b * 32768 + i * 4096, &P.mapX, bar_x + 8 * b, i * 64, b * SEGL);
        }
    }
#pragma unroll 2
    for (int i = tid; i < 512 * 4; i += CH_BLOCK) {
        const int r = i >> 2, cg = i & 3, ks = r >> 4, kp = r & 15;
        const int src = (rank - (ks >> 2)) & 7;
        const uint4* p = reinterpret_cast<const uint4*>(Wo + (size_t)(C * 512 + src * 64 + (ks & 3) * 16 + (kp >> 2) * 2 + (kp & 1) + (kp & 2) * 4) * DM + rank * 64 + cg * 16);
        const uint4 u0 = __ldg(p), u1 = __ldg(p + 1);
        const uint32_t a = sb + CO_WO + r * 128;
        sts128(a + (((cg * 2) ^ (r & 7)) << 4), __byte_perm(u0.x, u0.y, 0x5410), __byte_perm(u0.z, u0.w, 0x5410), __byte_perm(u1.x, u1.y, 0x5410), __byte_perm(u1.z, u1.w, 0x5410));
        sts128(a + (((cg * 2 + 1) ^ (r & 7)) << 4), __byte_perm(u0.x, u0.y, 0x7632), __byte_perm(u0.z, u0.w, 0x7632), __byte_perm(u1.x, u1.y, 0x7632), __byte_perm(u1.z, u1.w, 0x7632));
    }
#pragma unroll 1
    for (int i = tid; i < 512; i += CH_BLOCK) {
        const int n = i >> 6, c = i & 63;
        const uint4 u = __ldg(reinterpret_cast<const uint4*>(mem0 + n * DM + chunk(c >> 3) * 64 + (c & 7) * 8));
        sts128(sb + CO_MB + (c >> 3) * 1024 + n * 128 + (((c & 7) ^ n) << 4), u.x, u.y, u.z, u.w);
    }
    if (tid < 128) sts128(sb + CO_T + (tid >> 6) * CH_TP + 2 * CH_TW + 5120 + (tid & 63) * 16, 0u, 0u, 0u, 0u);
    else if (tid < 160) sts128(sb + CO_P + ((tid >> 3) & 3) * 768 + 640 + (tid & 7) * 16, 0u, 0u, 0u, 0u);
    fence_async_smem();
    TS_END(6);
    PT(6, 0);
    auto pass32 = [&](int b, int e0 = 0, int e1 = 32) {
        const uint32_t lo = desc_lo(sb + CO_XB + b * 32768, 16);
        wgmma_fence();
#pragma unroll
        for (int e = 0; e < 32; e++) if (e >= e0 && e < e1) {
            const uint32_t db = lo + chunk(e >> 2) * 256 + (e & 3) * 2;
            if (e < CH_NSM) wgmma_ss_n32(d, desc_lo(sb + CO_WA + wg * CH_TW + e * 2048, 16), db, e != 0);
            else wgmma_rs_n32(d, w[e], db, e != 0);
        }
        wgmma_commit();
    };
    auto store32 = [&](uint32_t a) {
        stmatrix_x4_trans(a, pack_bf16(d[0], d[1]), pack_bf16(d[2], d[3]), pack_bf16(d[4], d[5]), pack_bf16(d[6], d[7]));
        stmatrix_x4_trans(a + 2048, pack_bf16(d[8], d[9]), pack_bf16(d[10], d[11]), pack_bf16(d[12], d[13]), pack_bf16(d[14], d[15]));
    };
    auto mem_proj = [&](int s, bool wait, bool arrive = false) {
        const uint32_t par = s & 1;
        float acc[CH_CHAINS][4];
#pragma unroll
        for (int i = 0; i < CH_CHAINS; i++) acc[i][0] = acc[i][1] = acc[i][2] = acc[i][3] = 0.f;
        const uint32_t aM2 = aM ^ 64;
        uint32_t b[2][8];
        auto load = [&](int c) {
            if (wait && !(c & 1)) mbar_wait_cl(bar_mem + 4 * c, par ^ 1);
            if (c == 0) DBG(11, 0);
            if (c == 6) DBG(13, 0);
            ldmatrix_x4(b[c & 1][0], b[c & 1][1], b[c & 1][2], b[c & 1][3], aM + CO_MB + c * 1024);
            ldmatrix_x4(b[c & 1][4], b[c & 1][5], b[c & 1][6], b[c & 1][7], aM2 + CO_MB + c * 1024);
        };
        load(0);
#pragma unroll
        for (int c = 0; c < 8; c++) {
            if (c < 7) load(c + 1);
            SCHED_FENCE();
#pragma unroll
            for (int i = 0; i < 4; i++) {
                const int e = c * 4 + i;
                mma_16816(acc[i % CH_CHAINS], w[e][0], w[e][1], w[e][2], w[e][3], b[c & 1][i * 2], b[c & 1][i * 2 + 1]);
            }
        }
        if (CH_CHAINS == 4) {
#pragma unroll
            for (int i = 0; i < 4; i++) { acc[0][i] += acc[2 % CH_CHAINS][i]; acc[1][i] += acc[3 % CH_CHAINS][i]; }
        }
        const uint32_t r0 = pack_bf16(acc[0][0] + acc[1][0], acc[0][1] + acc[1][1]);
        const uint32_t r1 = pack_bf16(acc[0][2] + acc[1][2], acc[0][3] + acc[1][3]);
        DBGD(40 + warp, warp, r0 ^ r1);
        stmatrix_x2_trans(aO + par * CH_TP + CO_T + 4096, r0, r1);
    };
    auto load_wa = [&]() {
#pragma unroll
        for (int e = 0; e < CH_NSM; e++) ldmatrix_x4_trans(w[e][0], w[e][1], w[e][2], w[e][3], aO + CO_WA + e * 2048);
    };
    auto remote = [](uint32_t a, uint32_t r) { return mapa_u32(a, r); };
    mbar_wait(bar_x, 0);
    PT(7, 0);
    pass32(0);
    wgmma_wait<0>();
    store32(aO + CO_T);
    fence_async_smem();
    __syncthreads();
    PT(8, 0);
    cluster_sync_all();
    TS_BEGIN(5);
    PT(9, 0);

    if (wg < 2) {
        const uint32_t aQ = pin(sb + CO_T + qd * 128 + (((2 * qc) ^ qd) << 4));
        auto local_scores = [&](int s) {
            const uint32_t tb = sb + CO_T + (s & 1) * CH_TP;
            wgmma_fence();
#pragma unroll
            for (int ks = 0; ks < 4; ks++) wgmma_ss_n32_kk(d, desc_lo(tb + CH_TW, 16) + ks * 2, desc_lo(tb, 16) + ks * 2, ks != 0);
            wgmma_commit();
            DBG(30, 4);
            wgmma_wait<0>();
            DBG(31, 4);
            const uint32_t rb = remote(bar_l, rank ^ 1);
            if (t4 < 2) {
                const uint32_t off = 2 * aL - sb + t4 * 512;
#pragma unroll
                for (int j = 0; j < 4; j++) if (j >= 2 || t4 == 0) {
                    st_async_v4(remote(off + (s & 1) * 5120 + CO_LS + j * 1280, rank ^ 1), __float_as_uint(d[4 * j]), __float_as_uint(d[4 * j + 1]), __float_as_uint(d[4 * j + 2]), __float_as_uint(d[4 * j + 3]), rb);
                    sts128(off + CO_LO + j * 1280, __float_as_uint(d[4 * j]), __float_as_uint(d[4 * j + 1]), __float_as_uint(d[4 * j + 2]), __float_as_uint(d[4 * j + 3]));
                }
            } else if (t4 == 2) {
#pragma unroll
                for (int j = 0; j < 4; j++) {
                    st_async_v2(remote(aL + (s & 1) * 5120 + CO_LS + 1024 + j * 1280, rank ^ 1), __float_as_uint(d[4 * j]), __float_as_uint(d[4 * j + 1]), rb);
                    asm volatile("st.shared.v2.f32 [%0], {%1, %2};" :: "r"(aL + CO_LO + 1024 + j * 1280), "f"(d[4 * j]), "f"(d[4 * j + 1]) : "memory");
                }
            }
            __syncwarp();
            if (t4 < 3 && lane == 0) mbar_arrive(bar_l);
            DBG(6, 4);
        };
        auto local_pv = [&](int s, bool arrive) {
            wgmma_fence();
#pragma unroll
            for (int ks = 0; ks < 3; ks++)
                wgmma_ss_n32_p(d, desc_lo(sb + CO_T + (s & 1) * CH_TP + 2 * CH_TW + ks * 2048, 16), desc_lo(sb + CO_P + ks * 256, 128), ks != 0);
            wgmma_commit();
            wgmma_wait<0>();
            if (arrive) asm volatile("bar.arrive 9, 256;" ::: "memory");
            store32(aO + CO_ST);
            fence_async_smem();
            if (!arrive) asm volatile("bar.sync 5, 128;" ::: "memory");
        };
        auto store_ctx = [&](int s) {
            tma_store_2d(&P.mapC, sb + CO_ST, (rank & 1) * 64, h * SEQ + s * SEGL);
            asm volatile("cp.async.bulk.commit_group;" ::: "memory");
        };
        auto signal_ctx = [&](int m0, int m1) {
            asm volatile("fence.proxy.async;" ::: "memory");
            __threadfence();
            for (int m = m0; m < m1; m++) asm volatile("red.relaxed.gpu.global.add.u32 [%0], 1;" :: "l"(&g_ctr[CT_CB + m]) : "memory");
        };
#pragma unroll 1
        for (int s = 0; s < NSEG; s++) {
            const uint32_t par = s & 1;
            load_wa();
            mem_proj(s, s > 0);
            if (s == NSEG - 1) break;
            if (warp < 5) {
                const uint32_t qa_ = aQ + par * CH_TP, ka = qa_ + warp * 1024;
                asm volatile("bar.sync 1, 256;" ::: "memory");
                const uint4 qa = lds128(qa_ + 4096), k0 = lds128(ka + CH_TW), qb = lds128((qa_ ^ 16) + 4096), k1 = lds128((ka ^ 16) + CH_TW);
                DBGD(52 + warp, warp, qa.x ^ qb.x);
                float c[4] = {0.f, 0.f, 0.f, 0.f}, c2[4] = {0.f, 0.f, 0.f, 0.f};
                mma_16816(c, qa.x, 0u, qa.y, 0u, k0.x, k0.y);
                mma_16816(c2, qb.x, 0u, qb.y, 0u, k1.x, k1.y);
                mma_16816(c, qa.z, 0u, qa.w, 0u, k0.z, k0.w);
                mma_16816(c2, qb.z, 0u, qb.w, 0u, k1.z, k1.w);
                c[0] += c2[0]; c[1] += c2[1];
                DBGD(57 + warp, warp, __float_as_uint(c[0]));
                const uint32_t off = aL + CO_SC + warp * 256;
                st_async_v2(remote(off + 1280, rank ^ 1), __float_as_uint(c[0]), __float_as_uint(c[1]), remote(bar_sc, rank ^ 1));
                st_async_v2(off, __float_as_uint(c[0]), __float_as_uint(c[1]), bar_sc);
                asm volatile("bar.arrive 2, 288;" ::: "memory");
                DBG(3, 0);
            } else {
                asm volatile("bar.arrive 1, 256;" ::: "memory");
            }
            if (wg == 0) {
                if (tid == 96) {
                    mbar_expect_tx(bar_sc, 2 * 1280);
#pragma unroll
                    for (int j = 0; j < 4; j++) { mbar_expect_tx(bar_mem + 8 * j, 2048); if (j < CH_OG) mbar_expect_tx(bar_o + 8 * j, 8192 / CH_OG); }
                    if (s > 0) mbar_wait(bar_l, par ^ 1);
                    mbar_expect_tx(bar_l, 4096);
                }
                if (tid == 96 && s > 1) {
                    if (s == 34 || s == 50 || s == 58 || s == 62) {
                        asm volatile("cp.async.bulk.wait_group 0;" ::: "memory");
                        signal_ctx(s == 34 ? 0 : (2 * s - 68) >> 2, s >> 2);
                    }
                    store_ctx(s - 2);
                    asm volatile("cp.async.bulk.wait_group.read 0;" ::: "memory");
                }
                __syncwarp();
                mbar_wait(bar_x + 8 * (par ^ 1), ((s + 1) >> 1) & 1);
                asm volatile("bar.sync 5, 128;" ::: "memory");
                float c[4];
                const uint32_t alo = desc_lo(sb + CO_WO, 16), blo = desc_lo(sb + CO_OB, 128);
                uint32_t* wp = g_xbuf + (size_t)rank * 2048 + C * 256 + qc * 64 + t4 * 8 + qd;
                mbar_wait_cl(bar_o, par);
                DBG(16, 0);
                fence_async_smem();
                wgmma_fence();
#pragma unroll
                for (int i = 0; i < 32; i++) {
                    wgmma_ss_n8(c, alo + i * 128, blo + i * 16, i != 0);
                    if (CH_OG == 2 && i == CH_OW) mbar_wait_cl(bar_o + 8, par);
                    if (CH_OG == 2 && i == CH_OF) fence_async_smem();
                }
                wgmma_commit();
                wgmma_wait<0>();
                asm volatile("st.relaxed.gpu.global.u32 [%0], %1;" :: "l"(wp + (s & 3) * 16384), "r"(~pack_bf16(c[0], c[2])) : "memory");
                asm volatile("st.relaxed.gpu.global.u32 [%0], %1;" :: "l"(wp + (s & 3) * 16384 + 32), "r"(~pack_bf16(c[1], c[3])) : "memory");
                asm volatile("bar.arrive 4, 256;" ::: "memory");
                asm volatile("bar.arrive 6, 256;" ::: "memory");
                DBG(8, 0);
                if (s > 0) local_pv(s - 1, true); else asm volatile("bar.arrive 9, 256;" ::: "memory");
                DBG(28, 0);
                asm volatile("st.relaxed.gpu.global.u32 [%0], %1;" :: "l"(wp + ((s + 2) & 3) * 16384), "r"(0) : "memory");
                asm volatile("st.relaxed.gpu.global.u32 [%0], %1;" :: "l"(wp + ((s + 2) & 3) * 16384 + 32), "r"(0) : "memory");
                if (tid == 0 && s + 2 < NSEG) {
                    mbar_expect_tx(bar_x + 8 * par, 32768);
                    tma_load_2d_mc(sb + CO_XB + par * 32768 + rank * 4096, &P.mapX, bar_x + 8 * par, rank * 64, (s + 2) * SEGL, (uint16_t)0xff);
                }
                __syncwarp();
            } else {
                const uint32_t vaddr = pin(sb + CO_T + par * CH_TP + 2 * CH_TW + (lane & 15) * 128 + (((t4 * 2 + (lane >> 4)) ^ (lane & 7)) << 4));
                const uint32_t dsta = pin(sb + CO_OB + t4 * 256 + (qc >> 1) * 128 + qd * 16 + (qc & 1) * 8);
                fence_async_smem();
                uint32_t vb[3][4];
                auto load_v = [&]() {
                    asm volatile("bar.sync 3, 256;" ::: "memory");
#pragma unroll
                    for (int k = 0; k < 3; k++) ldmatrix_x4_trans(vb[k][0], vb[k][1], vb[k][2], vb[k][3], vaddr + k * 2048);
                };
                if (CH_VPOS == 0) load_v();
                mbar_wait_cl(bar_sc, par);
                DBG(4, 4);
                float v[10];
#pragma unroll
                for (int j = 0; j < 5; j++) {
                    const float2 a = lds64f(aL + CO_SC + j * 256), b = lds64f(aL + CO_SC + 1280 + j * 256);
                    v[2 * j] = a.x + b.x; v[2 * j + 1] = a.y + b.y;
                }
                if (CH_VPOS == 1) load_v();
                float mx = fmaxf(fmaxf(fmaxf(v[0], v[1]), fmaxf(v[2], v[3])), fmaxf(fmaxf(v[4], v[5]), fmaxf(v[6], v[7])));
                mx = fmaxf(mx, fmaxf(v[8], v[9]));
                mx = fmaxf(mx, __shfl_xor_sync(0xffffffff, mx, 1));
                mx = fmaxf(mx, __shfl_xor_sync(0xffffffff, mx, 2));
                if (CH_VPOS == 2) load_v();
                DBG(19, 4);
                mx *= CH_SC;
#pragma unroll
                for (int j = 0; j < 10; j++) v[j] = ex2f(fmaf(v[j], CH_SC, -mx));
                float c0[4] = {0.f, 0.f, 0.f, 0.f}, c1[4] = {0.f, 0.f, 0.f, 0.f}, cs[4] = {0.f, 0.f, 0.f, 0.f};
#pragma unroll
                for (int k = 0; k < 3; k++) {
                    const uint32_t p0 = pack_bf16(v[4 * k], v[4 * k + 1]), p1 = k < 2 ? pack_bf16(v[4 * k + 2], v[4 * k + 3]) : 0u;
                    mma_16816(cs, p0, 0u, p1, 0u, 0x3f803f80u, 0x3f803f80u);
                    mma_16816(c0, p0, 0u, p1, 0u, vb[k][0], vb[k][1]);
                    mma_16816(c1, p0, 0u, p1, 0u, vb[k][2], vb[k][3]);
                }
                float inv;
                asm volatile("rcp.approx.ftz.f32 %0, %1;" : "=f"(inv) : "f"(cs[0]));
                const uint32_t b0 = pack_bf16(c0[0] * inv, c0[1] * inv), b1 = pack_bf16(c1[0] * inv, c1[1] * inv);
                DBG(20, 4);
#pragma unroll
                for (int i = 0; i < 8; i++) {
                    const int dr = (rank + i) & 7;
                    st_async_v2(remote(dsta + i * 1024, dr), b0, b1, remote(bar_o + 8 * (i * CH_OG / 8), dr));
                    if (i == 0) asm volatile("bar.arrive 7, 256;" ::: "memory");
                }
                DBG(5, 4);
                mbar_wait(bar_x + 8 * (par ^ 1), ((s + 1) >> 1) & 1);
                asm volatile("bar.sync 4, 256;" ::: "memory");
                if (CH_LSPOS == 0) local_scores(s);
            }
            pass32(par ^ 1);
            DBG(21, 0);
            DBG(1, 4);
            wgmma_wait<0>();
            DBG(2, 4);
            DBG(0, 0);
            store32(aO + (par ^ 1) * CH_TP + CO_T);
            if (wg == 0) fence_async_smem();
            DBG(22, 0);
            DBG(29, 4);
            if (CH_LSPOS == 1 && wg == 1) local_scores(s);
        }
        PT(10, 0);
        fence_async_smem();
        asm volatile("bar.sync 1, 256;" ::: "memory");
        if (warp < 5) asm volatile("bar.arrive 2, 288;" ::: "memory");
        if (wg == 0) {
            if (tid == 96) { mbar_wait(bar_l, 0); mbar_expect_tx(bar_l, 4096); store_ctx(NSEG - 3); asm volatile("cp.async.bulk.wait_group.read 0;" ::: "memory"); }
            __syncwarp();
            asm volatile("bar.sync 7, 256;" ::: "memory");
            local_pv(NSEG - 2, false);
            asm volatile("bar.arrive 6, 256;" ::: "memory");
            if (tid == 96) { store_ctx(NSEG - 2); asm volatile("cp.async.bulk.wait_group.read 0;" ::: "memory"); }
            __syncwarp();
            PT(11, 96);
            asm volatile("bar.sync 8, 256;" ::: "memory");
            PT(12, 96);
            local_pv(NSEG - 1, false);
            PT(13, 96);
            if (tid == 96) {
                store_ctx(NSEG - 1);
                asm volatile("cp.async.bulk.wait_group 0;" ::: "memory");
                PT(14, 96);
                signal_ctx(15, 16);
                PT(15, 96);
            }
            uint32_t* wp = g_xbuf + 16384 + (size_t)rank * 2048 + C * 256 + tid * 2;
            *reinterpret_cast<uint2*>(wp) = make_uint2(0u, 0u);
        } else {
            asm volatile("bar.sync 3, 256;" ::: "memory");
            asm volatile("bar.arrive 7, 256;" ::: "memory");
            local_scores(NSEG - 1);
        }
    } else {
        auto local_softmax = [&](int s) {
            float v[10];
            const float2 g = __ldcg(reinterpret_cast<const float2*>(g_gate + s * SEGL + t4 * 8 + 2 * qc));
            mbar_wait_cl(bar_l, s & 1);
            const uint32_t off = 2 * aL - sb + t4 * 1280;
            {
                const uint4 a0 = lds128(off + (s & 1) * 5120 + CO_LS), b0 = lds128(off + CO_LO), a1 = lds128(off + (s & 1) * 5120 + CO_LS + 512), b1 = lds128(off + CO_LO + 512);
                const float2 a2 = lds64f(aL + t4 * 1280 + (s & 1) * 5120 + CO_LS + 1024), b2 = lds64f(aL + t4 * 1280 + CO_LO + 1024);
                auto f = [](uint32_t a, uint32_t b) { return __uint_as_float(a) + __uint_as_float(b); };
                v[0] = f(a0.x, b0.x); v[1] = f(a0.y, b0.y); v[2] = f(a0.z, b0.z); v[3] = f(a0.w, b0.w);
                v[4] = f(a1.x, b1.x); v[5] = f(a1.y, b1.y); v[6] = f(a1.z, b1.z); v[7] = f(a1.w, b1.w);
                v[8] = a2.x + b2.x; v[9] = a2.y + b2.y;
            }
            const int lim = t4 * 8 + 2 * qc - qd;
#pragma unroll
            for (int n = 0; n < 4; n++) {
                if (8 * n > lim) v[2 * n] = -INFINITY;
                if (8 * n > lim + 1) v[2 * n + 1] = -INFINITY;
            }
            float m0 = fmaxf(fmaxf(fmaxf(v[0], v[2]), fmaxf(v[4], v[6])), v[8]), m1 = fmaxf(fmaxf(fmaxf(v[1], v[3]), fmaxf(v[5], v[7])), v[9]);
#pragma unroll
            for (int o = 4; o < 32; o *= 2) { m0 = fmaxf(m0, __shfl_xor_sync(0xffffffff, m0, o)); m1 = fmaxf(m1, __shfl_xor_sync(0xffffffff, m1, o)); }
            m0 *= CH_SC; m1 *= CH_SC;
#pragma unroll
            for (int n = 0; n < 5; n++) { v[2 * n] = ex2f(fmaf(v[2 * n], CH_SC, -m0)); v[2 * n + 1] = ex2f(fmaf(v[2 * n + 1], CH_SC, -m1)); }
            float s0 = ((v[0] + v[2]) + (v[4] + v[6])) + v[8], s1 = ((v[1] + v[3]) + (v[5] + v[7])) + v[9];
#pragma unroll
            for (int o = 4; o < 32; o *= 2) { s0 += __shfl_xor_sync(0xffffffff, s0, o); s1 += __shfl_xor_sync(0xffffffff, s1, o); }
            asm("rcp.approx.ftz.f32 %0, %0;" : "+f"(s0));
            asm("rcp.approx.ftz.f32 %0, %0;" : "+f"(s1));
            s0 *= 1.f - g.x; s1 *= 1.f - g.y;
            const uint32_t pa = 2 * aL - sb + CO_P + t4 * 768;
            stmatrix_x4_trans(pa, pack_bf16(v[0] * s0, v[1] * s1), pack_bf16(v[2] * s0, v[3] * s1), pack_bf16(v[4] * s0, v[5] * s1), pack_bf16(v[6] * s0, v[7] * s1));
            asm volatile("stmatrix.sync.aligned.m8n8.x1.trans.shared.b16 [%0], {%1};" :: "r"(pa + 512), "r"(pack_bf16(v[8] * s0, v[9] * s1)) : "memory");
            fence_async_smem();
            DBG(7, 8);
        };
        wait_ctr(CT_GATE, 64u);
#pragma unroll 1
        for (int s = 0; s < NSEG; s++) {
            const uint32_t par = s & 1;
            if (s > 0) local_softmax(s - 1);
            load_wa();
            if (s < NSEG - 1) mbar_wait(bar_x + 8 * (par ^ 1), ((s + 1) >> 1) & 1);
            asm volatile("bar.sync 2, 288;" ::: "memory");
            DBG(23, 8);
            mem_proj(s, false, true);
            asm volatile("bar.arrive 3, 256;" ::: "memory");
            if (s == NSEG - 1) break;
            DBG(24, 8);
            if (CH_V1 > 0) pass32(par ^ 1, 0, CH_V1);
            asm volatile("bar.sync 7, 256;" ::: "memory");
            pass32(par ^ 1, CH_V1, CH_V2);
            DBG(26, 8);
            asm volatile("bar.sync 6, 256;" ::: "memory");
            const uint2* xb = reinterpret_cast<const uint2*>(g_xbuf + (s & 3) * 16384 + (size_t)rank * 2048 + t4 * 64) + lane;
            uint2 p[8];
            auto poll_all = [&]() {
#pragma unroll
                for (int k = 0; k < 8; k++)
                    asm volatile("ld.relaxed.gpu.global.v2.u32 {%0, %1}, [%2];" : "=r"(p[k].x), "=r"(p[k].y) : "l"(xb + k * 128) : "memory");
                DBG(17, 8);
            };
            if (CH_V3 > CH_V2) { pace(CH_V3_DELAY); pass32(par ^ 1, CH_V2, CH_V3); }
            if (CH_VST == 0) {
                asm volatile("bar.sync 9, 256;" ::: "memory");
                wgmma_wait<0>();
                store32(aO + (par ^ 1) * CH_TP + CO_T);
                DBG(27, 8);
            }
            pace(CH_POLL_DELAY);
            auto lo = [](uint32_t u) { return __uint_as_float(~u << 16); };
            auto hi = [](uint32_t u) { return __uint_as_float(~u & 0xffff0000u); };
            poll_all();
            for (int it = 0; it < WAIT_LIMIT / 4; it++) {
                uint32_t bad = 0;
#pragma unroll
                for (int k = 0; k < 8; k++) bad |= (min(p[k].x, p[k].y) == 0u ? 1u : 0u) << k;
                if (__all_sync(0xffffffff, bad == 0u)) break;
                if (it == 0) DBG(12, 8);
                if (it == 1) DBG(14, 8);
                if (it == 2) DBG(15, 8);
#pragma unroll
                for (int k = 0; k < 8; k++)
                    if (bad & (1u << k))
                        asm volatile("ld.relaxed.gpu.global.v2.u32 {%0, %1}, [%2];" : "=r"(p[k].x), "=r"(p[k].y) : "l"(xb + k * 128) : "memory");
            }
            DBG(9, 8);
            const uint32_t m0 = pack_bf16(((lo(p[0].x) + lo(p[1].x)) + (lo(p[2].x) + lo(p[3].x))) + ((lo(p[4].x) + lo(p[5].x)) + (lo(p[6].x) + lo(p[7].x))),
                                          ((hi(p[0].x) + hi(p[1].x)) + (hi(p[2].x) + hi(p[3].x))) + ((hi(p[4].x) + hi(p[5].x)) + (hi(p[6].x) + hi(p[7].x))));
            const uint32_t m1 = pack_bf16(((lo(p[0].y) + lo(p[1].y)) + (lo(p[2].y) + lo(p[3].y))) + ((lo(p[4].y) + lo(p[5].y)) + (lo(p[6].y) + lo(p[7].y))),
                                          ((hi(p[0].y) + hi(p[1].y)) + (hi(p[2].y) + hi(p[3].y))) + ((hi(p[4].y) + hi(p[5].y)) + (hi(p[6].y) + hi(p[7].y))));
            const int row = t4 * 2 + (lane >> 4);
            const uint32_t dsta = sb + CO_MB + row * 128 + ((((lane & 15) >> 1) ^ row) << 4) + (lane & 1) * 8;
#pragma unroll
            for (int i = 0; i < 8; i++) {
                const int dr = (rank + (i & 1) * 4 + (i >> 1)) & 7;
                st_async_v2(remote(dsta + i * 1024, dr), m0, m1, remote(bar_mem + 8 * (i >> 1), dr));
            }
            DBG(10, 8);
            if (CH_VST == 1) {
                if (CH_V3 < 32) pass32(par ^ 1, CH_V3, 32);
                asm volatile("bar.sync 9, 256;" ::: "memory");
                wgmma_wait<0>();
                store32(aO + (par ^ 1) * CH_TP + CO_T);
                DBG(27, 8);
            }
        }
        asm volatile("bar.sync 6, 256;" ::: "memory");
        local_softmax(NSEG - 1);
        asm volatile("bar.arrive 8, 256;" ::: "memory");
    }
    __syncthreads();
    cluster_sync_all();
    TS_END(2);
}

struct Proj2Params {
    CUtensorMap mapA[2];
    CUtensorMap mapW[3];
    bf16* out[3];
};
#define P2T(i)
#define P2_NOMMA 0
#define P2_NOLOAD 0
constexpr int P2_STAGES = 6;
constexpr int P2_SMEM = 131072 + P2_STAGES * 16384 + 1024 + 1024;
constexpr int P2_ITEMS = 168 + 48;

__device__ __forceinline__ int p2_reps(int t) { return t >= 168 ? 1 : 2; }
__device__ __forceinline__ void p2_tile(int t, int w, int& z, int& mp, int& head) {
    if (t >= 168) { w += ((t - 168) & 1) * 2; t = 168 + ((t - 168) >> 1); }
    const int hq = t / 24, v = t % 24;
    mp = v & 7;
    if (v < 16) { head = hq * 4 + (v >> 3) * 2 + (w >> 1); z = 1 + (w & 1); }
    else { head = hq * 4 + w; z = 0; }
}
__device__ __forceinline__ void mbar_arrive_remote(uint32_t bar_cluster_addr) {
    asm volatile("mbarrier.arrive.release.cluster.shared::cluster.b64 _, [%0];" :: "r"(bar_cluster_addr) : "memory");
}
__device__ __forceinline__ void mbar_arrive_cl(uint32_t bar_cluster_addr) {
    asm volatile("mbarrier.arrive.shared::cluster.b64 _, [%0];" :: "r"(bar_cluster_addr) : "memory");
}
__device__ __forceinline__ void mbar_wait_acq_cluster(uint32_t bar, uint32_t parity) {
    asm volatile(
        "{\n"
        ".reg .pred p, q;\n"
        ".reg .u32 c;\n"
        "mov.u32 c, 0;\n"
        "WAIT_LOOP_C:\n"
        "mbarrier.try_wait.parity.acquire.cluster.shared::cta.b64 p, [%0], %1;\n"
        "@p bra WAIT_DONE_C;\n"
        "add.u32 c, c, 1;\n"
        "setp.lt.u32 q, c, 4000000;\n"
        "@q bra WAIT_LOOP_C;\n"
        "WAIT_DONE_C:\n"
        "}\n" :: "r"(bar), "r"(parity) : "memory");
}
__device__ __forceinline__ uint4 quad_transpose(uint32_t p0, uint32_t p1, uint32_t p2, uint32_t p3, int lane) {
    const bool o1 = lane & 1, o2 = lane & 2;
    uint32_t s0 = o1 ? p0 : p1, s1 = o1 ? p2 : p3;
    s0 = __shfl_xor_sync(0xffffffff, s0, 1); s1 = __shfl_xor_sync(0xffffffff, s1, 1);
    const uint32_t a_lo = o1 ? s0 : p0, a_hi = o1 ? p1 : s0, b_lo = o1 ? s1 : p2, b_hi = o1 ? p3 : s1;
    uint32_t t0 = o2 ? a_lo : b_lo, t1 = o2 ? a_hi : b_hi;
    t0 = __shfl_xor_sync(0xffffffff, t0, 2); t1 = __shfl_xor_sync(0xffffffff, t1, 2);
    return o2 ? make_uint4(t0, t1, b_lo, b_hi) : make_uint4(a_lo, a_hi, t0, t1);
}
#define P2_PACE 35
#define P2_PACE2 0
template <bool PERM, int PACE = 0>
__device__ __forceinline__ void store_frag_128(const float (&acc)[64], bf16* obase, int lane) {
#pragma unroll
    for (int rr = 0; rr < 2; rr++)
#pragma unroll
        for (int g = 0; g < 4; g++) {
            const float* a = &acc[g * 16 + rr * 2];
            const uint32_t p0 = pack_bf16(a[0], a[1]), p1 = pack_bf16(a[4], a[5]), p2 = pack_bf16(a[8], a[9]), p3 = pack_bf16(a[12], a[13]);
            *reinterpret_cast<uint4*>(obase + (size_t)(rr * 8) * HD + g * 32) = PERM ? make_uint4(p0, p1, p2, p3) : quad_transpose(p0, p1, p2, p3, lane);
            pace(PACE);
        }
}
__global__ void __cluster_dims__(2, 1, 1) __launch_bounds__(384, 1) proj2_kernel(const __grid_constant__ Proj2Params P) {
    extern __shared__ uint8_t smem_raw[];
    const uint32_t sbase = (smem_u32(smem_raw) + 1023) & ~1023u;
    const uint32_t sA = sbase, sB = sbase + 131072, sC = sB + P2_STAGES * 16384;
    const uint32_t bars = sC;
    const uint32_t a_full = bars, a_empty = bars + 64, b_full = bars + 128, b_empty = b_full + 8 * P2_STAGES;
    const uint32_t item_bar = b_empty + 8 * P2_STAGES, item_in = item_bar + 16, slot = item_in + 16;
    const uint32_t note_bar = slot + 16, note_free = note_bar + 64, note = note_free + 64;
    const int warp = threadIdx.x >> 5, lane = threadIdx.x & 31;
    const uint32_t rank = cluster_ctarank();
    TS_BEGIN(0);
    if (threadIdx.x == 0) {
        for (int i = 0; i < 8; i++) { mbar_init(a_full + 8 * i, 1); mbar_init(a_empty + 8 * i, 2); }
        for (int i = 0; i < P2_STAGES; i++) { mbar_init(b_full + 8 * i, 1); mbar_init(b_empty + 8 * i, 2); }
        mbar_init(item_bar, 1); mbar_init(item_bar + 8, 1); mbar_init(item_in, 2); mbar_init(item_in + 8, 2);
        for (int i = 0; i < 8; i++) { mbar_init(note_bar + 8 * i, 1); mbar_init(note_free + 8 * i, 1); }
        asm volatile("fence.mbarrier_init.release.cluster;" ::: "memory");
    }
    __syncthreads();
    cluster_sync_all();
    pdl_launch_dependents();
    if (warp == 9) {
        if (lane == 0) {
            for (int n = 0;; n++) {
                const int e = (n & 1) * 4 + ((n >> 1) & 3);
                mbar_wait(note_bar + 8 * e, (n >> 3) & 1);
                int m;
                asm volatile("ld.shared.s32 %0, [%1];" : "=r"(m) : "r"(note + e * 4) : "memory");
                mbar_arrive(note_free + 8 * e);
                if (m < 0) break;
                signal_ctr(m);
            }
        }
    } else if (warp == 10) {
        if (lane == 0) {
            auto publish = [&](int ic, int tq) {
                const int t = tq < P2_ITEMS ? tq : -1;
                asm volatile("st.shared.s32 [%0], %1;" :: "r"(slot + (ic & 3) * 4), "r"(t) : "memory");
                mbar_arrive(item_bar + 8 * (ic & 1));
                st_async_b32(mapa_u32(slot + (ic & 3) * 4, 1), (uint32_t)t, mapa_u32(item_bar + 8 * (ic & 1), 1));
            };
            const int npair = (int)(gridDim.x >> 1), pair = (int)(blockIdx.x >> 1);
            if (rank == 0) publish(0, pair);
            for (int ic = 0;; ic++) {
                if (rank == 1) mbar_expect_tx(item_bar + 8 * (ic & 1), 4);
                mbar_wait(item_bar + 8 * (ic & 1), (ic >> 1) & 1);
                int t;
                asm volatile("ld.shared.s32 %0, [%1];" : "=r"(t) : "r"(slot + (ic & 3) * 4) : "memory");
                if (t < 0) break;
                int z0, mp, h0;
                p2_tile(t, 0, z0, mp, h0);
                const int aidx = z0 >= 1 ? 1 : 0;
                const int m0 = (2 * mp + (int)rank) * 128;
                for (int k = 0; k < 8; k++) {
                    mbar_wait(a_empty + 8 * k, (ic & 1) ^ 1);
                    if (P2_NOLOAD) mbar_arrive(a_full + 8 * k); else {
                    mbar_expect_tx(a_full + 8 * k, 16384);
                    tma_load_2d(sA + k * 16384, &P.mapA[aidx], a_full + 8 * k, k * 64, m0); }
                }
                if (rank == 0) {
                    mbar_wait(item_in + 8 * (ic & 1), (ic >> 1) & 1);
                    publish(ic + 1, ic == 0 ? npair + pair : 2 * npair + (int)atomicAdd(&g_ctr[CT_PROJ], 1u));
                }
            }
        }
    } else if (warp == 8 || warp == 11) {
        if (lane == 0) {
            const int par2 = warp == 8 ? 0 : 1;
            int it = 0; uint32_t bph = 0;
            for (int ic = 0;; ic++) {
                mbar_wait(item_bar + 8 * (ic & 1), (ic >> 1) & 1);
                int t;
                asm volatile("ld.shared.s32 %0, [%1];" : "=r"(t) : "r"(slot + (ic & 3) * 4) : "memory");
                if (t < 0) break;
                const int nt = 2 * p2_reps(t);
                for (int w = 0; w < nt; w++) {
                    int z, mp, hd;
                    p2_tile(t, w, z, mp, hd);
                    for (int k = 0; k < 8; k++) {
                        const int s = it; const uint32_t phb = bph;
                        if (++it == P2_STAGES) { it = 0; bph ^= 1; }
                        if ((k & 1) != par2) continue;
                        mbar_wait(b_empty + 8 * s, phb ^ 1);
                        if (P2_NOLOAD) { mbar_arrive(b_full + 8 * s); continue; }
                        mbar_expect_tx(b_full + 8 * s, 16384);
                        tma_load_2d_mc(sB + s * 16384 + rank * 8192, &P.mapW[z], b_full + 8 * s, hd * 128 + (int)rank * 64, k * 64, (uint16_t)3);
                    }
                }
            }
        }
    } else {
        const int wg = warp >> 2;
        float acc[2][64];
        const uint32_t a_lo = desc_lo(sA, 16), b_lo0 = desc_lo(sB, 8192);
        const bool elected = (threadIdx.x & 127) == 0;
        int s = (wg * 8) % P2_STAGES;
        uint32_t ph = ((wg * 8) / P2_STAGES) & 1;
        int nnote = 0;
        if (wg == 1) asm volatile("bar.arrive 3, 256;" ::: "memory");
        for (int ic = 0;; ic++) {
            mbar_wait(item_bar + 8 * (ic & 1), (ic >> 1) & 1);
            int t;
            asm volatile("ld.shared.s32 %0, [%1];" : "=r"(t) : "r"(slot + (ic & 3) * 4) : "memory");
            P2T(7);
            if (wg == 0 && t < 0) {
                if (elected) {
                    const int e = nnote & 3;
                    mbar_wait(note_free + 8 * e, ((nnote >> 2) & 1) ^ 1);
                    asm volatile("st.shared.s32 [%0], %1;" :: "r"(note + e * 4), "r"(-1) : "memory");
                    mbar_arrive(note_bar + 8 * e);
                }
            }
            if (t < 0) break;
            const int reps = p2_reps(t);
#pragma unroll 1
            for (int rp = 0; rp < reps; rp++) {
            const bool first = rp == 0, last = rp == reps - 1;
            int z, mp, head;
            p2_tile(t, rp * 2 + wg, z, mp, head);
            asm volatile("bar.sync %0, 256;" :: "r"(3 + wg) : "memory");
            P2T(0);
            if (wg == 1 && last && elected) mbar_arrive_cl(mapa_u32(item_in + 8 * (ic & 1), 0));
            int sprev = 0;
#pragma unroll
            for (int k = 0; k < 8; k++) {
                if (k == 0) P2T(5);
                if (wg == 0 && first) mbar_wait(a_full + 8 * k, ic & 1);
                if (k == 0) P2T(6);
                mbar_wait(b_full + 8 * s, ph);
                if (k == 7) asm volatile("bar.arrive %0, 256;" :: "r"(4 - wg) : "memory");
                if (k == 0) P2T(1);
                if (k == 7) P2T(2);
                const uint32_t b_lo = b_lo0 + s * 1024;
                wgmma_fence();
#pragma unroll
                for (int kk = 0; kk < (P2_NOMMA ? 1 : 4); kk++) {
                    wgmma_ss_n128_lo<1>(acc[0], a_lo + k * 1024 + kk * 2, b_lo + kk * 128, (k | kk) != 0);
                    wgmma_ss_n128_lo<1>(acc[1], a_lo + k * 1024 + 512 + kk * 2, b_lo + kk * 128, (k | kk) != 0);
                }
                wgmma_commit();
                if (k > 0) {
                    wgmma_wait<1>();
                    if (elected) {
                        const uint32_t e = b_empty + 8 * sprev;
                        mbar_arrive_cl(mapa_u32(e, 0)); mbar_arrive_cl(mapa_u32(e, 1));
                        if (last) mbar_arrive(a_empty + 8 * (k - 1));
                    }
                }
                sprev = s;
                if (++s == P2_STAGES) { s = 0; ph ^= 1; }
            }
            wgmma_wait<0>();
            P2T(3);
            if (elected) {
                const uint32_t e = b_empty + 8 * sprev;
                mbar_arrive_cl(mapa_u32(e, 0)); mbar_arrive_cl(mapa_u32(e, 1));
                if (last) mbar_arrive(a_empty + 8 * 7);
            }
            s += 8 % P2_STAGES; ph ^= (8 / P2_STAGES) & 1;
            if (s >= P2_STAGES) { s -= P2_STAGES; ph ^= 1; }
            const int m0 = (2 * mp + (int)rank) * 128;
            bf16* obase = P.out[z] + ((size_t)head * SEQ + m0 + (warp & 3) * 16 + (lane >> 2)) * HD + (lane & 3) * 8;
            store_frag_128<true, P2_PACE>(acc[0], obase, lane); store_frag_128<true, P2_PACE>(acc[1], obase + (size_t)64 * HD, lane);
            P2T(4);
            {
                asm volatile("bar.sync %0, 128;" :: "r"(1 + wg) : "memory");
                if (elected) {
                    const int e = wg * 4 + (nnote & 3);
                    mbar_wait(note_free + 8 * e, ((nnote >> 2) & 1) ^ 1);
                    asm volatile("st.shared.s32 [%0], %1;" :: "r"(note + e * 4), "r"(CT_AP + (head >> 1)) : "memory");
                    mbar_arrive(note_bar + 8 * e);
                }
                nnote++;
            }
            }
        }
        TS_END(0);
    }
    __syncthreads();
    cluster_sync_all();
}

struct OutParams {
    CUtensorMap mapCtx[2];
    CUtensorMap mapWo[2];
    CUtensorMap mapOut;
};

#define OT(i)
#define OTP(i, th)
constexpr int O2_STAGES = 4;
constexpr int O2_SMEM = O2_STAGES * 49152 + 1024 + 256;
constexpr int O2_GRID = 132;
#define O2_NL 8
#define O2_FINE 8

__global__ void __cluster_dims__(2, 1, 1) __launch_bounds__(352, 1)
out2_kernel(const __grid_constant__ OutParams P) {
    extern __shared__ uint8_t smem_raw[];
    const uint32_t sbase = (smem_u32(smem_raw) + 1023) & ~1023u;
    const uint32_t bar_full = sbase + O2_STAGES * 49152, bar_empty = bar_full + 8 * O2_STAGES, bar_item = bar_empty + 8 * O2_STAGES;
    const uint32_t slot = bar_item + 64, stop = slot + 32;
    const int warp = threadIdx.x >> 5, lane = threadIdx.x & 31;
    const uint32_t rank = cluster_ctarank();
    const int cid = blockIdx.x >> 1;
    int pt, h0;
    if (cid < 32) { pt = cid < 16 ? cid : 31 - cid; h0 = cid >= 16; }
    else if (cid < 34) { pt = 12 + (cid & 1); h0 = 2; }
    else { pt = 14 + (cid & 1); h0 = 63 - ((cid - 34) >> 1); }
    const int ne = (pt >> 1) == 6 ? 3 : 2, nh = pt >= 14 ? 64 - O2_NL : 64;
    if (cid >= 34 + 2 * O2_NL) {
        if (threadIdx.x == 0 && atomicAdd(&g_ctr[CT_FIN], 1u) == gridDim.x - 1)
            for (int i = 0; i < CT_N / 4; i++) reinterpret_cast<uint4*>(g_ctr)[i] = make_uint4(0u, 0u, 0u, 0u);
        return;
    }
    const int mt = (pt >> 1) * 2 + (int)rank, m0 = mt * 128, n0 = (pt & 1) * 256;
    TS_BEGIN(4);
    OT(0);
    int tnext = 0;
    if (threadIdx.x == 256) {
        if (rank == 0) tnext = take_ticket(CT_OT + pt);
        for (int i = 0; i < O2_STAGES; i++) { mbar_init(bar_full + 8 * i, 1); mbar_init(bar_empty + 8 * i, 4); mbar_init(bar_item + 16 * i, 1); mbar_init(bar_item + 16 * i + 8, 1); }
        sts128(stop, 0u, 0u, 0u, 0u);
        asm volatile("fence.mbarrier_init.release.cluster;" ::: "memory");
    }
    __syncwarp();
    asm volatile("barrier.cluster.arrive.relaxed.aligned;" ::: "memory");
    if (threadIdx.x == 256) {
        asm volatile("prefetch.tensormap [%0];" :: "l"(&P.mapCtx[h0 >> 5]) : "memory");
        wait_ctr(h0 < 32 ? CT_CA + mt * 4 : CT_CB + mt, h0 < 32 ? 16u : 64u);
        OTP(8, 256);
        for (int i = 0; i < 2; i++) {
            mbar_expect_tx(bar_full + 8 * i, 49152);
            tma_load_2d(sbase + i * 49152, &P.mapCtx[h0 >> 5], bar_full + 8 * i, i * 64, (h0 & 31) * SEQ + m0);
        }
        OTP(11, 256);
    }
    if (threadIdx.x == 288) asm volatile("prefetch.tensormap [%0];" :: "l"(&P.mapWo[h0 >> 5]) : "memory");
    __syncwarp();
    asm volatile("barrier.cluster.wait.aligned;" ::: "memory");
    OTP(10, 288);
    if (warp >= 8) {
        if (lane == 0) {
            int s = 0, ready = h0 < 32 ? 1 : 16, q = h0 * 2, qe = q + 2; uint32_t ph = 0;
            for (int ic = 0;; ic++) {
                if (warp == 8 && rank == 0) {
                    const int t = tnext + ne;
                    asm volatile("st.shared.s32 [%0], %1;" :: "r"(slot + (ic & 7) * 4), "r"(t) : "memory");
                    mbar_arrive(bar_item + 8 * (ic & 7));
                    st_async_b32(mapa_u32(slot + (ic & 7) * 4, 1), (uint32_t)t, mapa_u32(bar_item + 8 * (ic & 7), 1));
                    if (t < nh + O2_FINE) tnext = take_ticket(CT_OT + pt);
                }
#pragma unroll 1
                for (; q < qe; q++) {
                    const int b = q >> 6, head = (q >> 1) & 31, dk = (q & 1) * 64;
                    mbar_wait(bar_empty + 8 * s, ph ^ 1);
                    const uint32_t sa = sbase + s * 49152;
                    if (warp == 8) {
                        const int f = b ? 4 : head >> 3;
                        if (!((ready >> f) & 1)) {
                            if (b && !(ready & 8)) { wait_ctr(CT_CA + mt * 4 + 3, 16u); ready |= 8; }
                            wait_ctr(b ? CT_CB + mt : CT_CA + mt * 4 + f, b ? 64u : 16u); ready |= 1 << f;
                        }
                        if (ic > 0) {
                            mbar_expect_tx(bar_full + 8 * s, 49152);
                            tma_load_2d(sa, &P.mapCtx[b], bar_full + 8 * s, dk, head * SEQ + m0);
                        }
                    } else {
                        const int j = (int)rank * 2 + (warp - 9);
                        tma_load_2d_mc(sa + 16384 + j * 8192, &P.mapWo[b], bar_full + 8 * s, n0 + j * 64, head * HD + dk, (uint16_t)3);
                    }
                    if (ic == 0 && s == 0) OTP(12, 288);
                    if (++s == O2_STAGES) { s = 0; ph ^= 1; }
                }
                if (warp == 8 && rank == 1) mbar_expect_tx(bar_item + 8 * (ic & 7), 4);
                mbar_wait(bar_item + 8 * (ic & 7), (ic >> 3) & 1);
                int t;
                asm volatile("ld.shared.s32 %0, [%1];" : "=r"(t) : "r"(slot + (ic & 7) * 4) : "memory");
                if (t >= nh + O2_FINE) break;
                if (t < nh - O2_FINE) { q = 2 * t; qe = q + 2; } else { q = nh - O2_FINE + t; qe = q + 1; }
            }
            if (warp == 8) {
                asm volatile("prefetch.tensormap [%0];" :: "l"(&P.mapOut) : "memory");
                if (!(ready & 8)) wait_ctr(CT_CA + mt * 4 + 3, 16u);
                mbar_wait(bar_empty + 8 * s, ph ^ 1);
                asm volatile("st.shared.s32 [%0], %1;" :: "r"(stop + s * 4), "r"(1) : "memory");
                mbar_arrive(bar_full + 8 * s);
                if (atomicAdd(&g_ctr[CT_FIN], 1u) == gridDim.x - 1)
                    for (int i = 0; i < CT_N / 4; i++) reinterpret_cast<uint4*>(g_ctr)[i] = make_uint4(0u, 0u, 0u, 0u);
                for (int i = 1; i < O2_STAGES; i++) {
                    if (++s == O2_STAGES) { s = 0; ph ^= 1; }
                    mbar_wait(bar_empty + 8 * s, ph ^ 1);
                }
            }
        }
    } else {
        const int wg = warp >> 2;
        const bool elected = (threadIdx.x & 127) == 0;
        float acc[128];
#pragma unroll
        for (int i = 0; i < 128; i++) acc[i] = 0.f;
        int s = 0, sprev = 0; uint32_t ph = 0;
#pragma unroll 1
        for (int i = 0;; i++) {
            mbar_wait(bar_full + 8 * s, ph);
            int st;
            asm volatile("ld.shared.s32 %0, [%1];" : "=r"(st) : "r"(stop + s * 4) : "memory");
            if (st) break;
            if (i == 0) OT(1);
            const uint32_t sa = sbase + s * 49152 + wg * 8192, sb = sbase + s * 49152 + 16384;
            wgmma_fence();
#pragma unroll
            for (int kk = 0; kk < 4; kk++)
                wgmma_ss_n256_tb(acc, make_desc(sa + kk * 32, 16, 1024), make_desc(sb + kk * 2048, 8192, 1024), 1);
            wgmma_commit();
            if (i > 0) {
                wgmma_wait<1>();
                if (elected) { const uint32_t e = bar_empty + 8 * sprev; mbar_arrive_cl(mapa_u32(e, 0)); mbar_arrive_cl(mapa_u32(e, 1)); }
            }
            sprev = s;
            if (++s == O2_STAGES) { s = 0; ph ^= 1; }
        }
        wgmma_wait<0>();
        if (elected) { const uint32_t e = bar_empty + 8 * sprev; mbar_arrive_cl(mapa_u32(e, 0)); mbar_arrive_cl(mapa_u32(e, 1)); }
        asm volatile("bar.sync %0, 128;" :: "r"(1 + wg) : "memory");
        OT(3);
        const int row = (lane & 7) + ((lane >> 3) & 1) * 8;
#pragma unroll
        for (int bx = 0; bx < 4; bx++) {
            const uint32_t stg = sbase + bx * 49152 + warp * 2048;
#pragma unroll
            for (int j = 0; j < 8; j += 2) {
                const float* a = &acc[bx * 32 + j * 4];
                stmatrix_x4(stg + row * 128 + (((j + (lane >> 4)) ^ (row & 7)) << 4), pack_bf16(a[0], a[1]), pack_bf16(a[2], a[3]), pack_bf16(a[4], a[5]), pack_bf16(a[6], a[7]));
            }
            asm volatile("fence.proxy.async.shared::cta;" ::: "memory");
            __syncwarp();
            if (lane == 0)
                asm volatile("cp.reduce.async.bulk.tensor.2d.global.shared::cta.add.tile.bulk_group [%0, {%2, %3}], [%1];"
                             :: "l"((uint64_t)&P.mapOut), "r"(stg), "r"(n0 + bx * 64), "r"(m0 + warp * 16) : "memory");
        }
        OT(4);
        if (lane == 0) {
            asm volatile("cp.async.bulk.commit_group;" ::: "memory");
            asm volatile("cp.async.bulk.wait_group.read 0;" ::: "memory");
        }
        TS_END(4);
    }
}

typedef CUresult (*PFN_encodeTiled)(CUtensorMap*, CUtensorMapDataType, cuuint32_t, void*, const cuuint64_t*,
                                    const cuuint64_t*, const cuuint32_t*, const cuuint32_t*, CUtensorMapInterleave,
                                    CUtensorMapSwizzle, CUtensorMapL2promotion, CUtensorMapFloatOOBfill);
static PFN_encodeTiled g_encode = nullptr;

static void make_map(CUtensorMap* m, const void* ptr, uint64_t rows, uint64_t cols, uint32_t box_rows, bool sw64 = false) {
    cuuint64_t dims[2] = {cols, rows};
    cuuint64_t strides[1] = {cols * 2};
    cuuint32_t box[2] = {sw64 ? 32u : 64u, box_rows};
    cuuint32_t es[2] = {1, 1};
    g_encode(m, CU_TENSOR_MAP_DATA_TYPE_BFLOAT16, 2, const_cast<void*>(ptr), dims, strides, box, es,
             CU_TENSOR_MAP_INTERLEAVE_NONE, sw64 ? CU_TENSOR_MAP_SWIZZLE_64B : CU_TENSOR_MAP_SWIZZLE_128B, CU_TENSOR_MAP_L2_PROMOTION_L2_256B,
             CU_TENSOR_MAP_FLOAT_OOB_FILL_NONE);
}

template <typename... KArgs, typename... Args>
static void launch_pdl(void (*kernel)(KArgs...), int grid, int block, size_t smem, cudaStream_t st, bool pdl, Args... args) {
    cudaLaunchConfig_t cfg = {};
    cfg.gridDim = dim3(grid); cfg.blockDim = dim3(block); cfg.dynamicSmemBytes = smem; cfg.stream = st;
    cudaLaunchAttribute at[1];
    at[0].id = cudaLaunchAttributeProgrammaticStreamSerialization;
    at[0].val.programmaticStreamSerializationAllowed = 1;
    cfg.attrs = at; cfg.numAttrs = pdl ? 1 : 0;
    cudaLaunchKernelEx(&cfg, kernel, KArgs(args)...);
}

extern "C" void kernel_launch(void* const* d_in, const int* in_sizes, int n_in, void* d_out, int out_size) {
    const bf16* x = (const bf16*)d_in[0];
    const bf16* ckv = (const bf16*)d_in[1];
    const bf16* wq = (const bf16*)d_in[2];
    const bf16* wuk = (const bf16*)d_in[3];
    const bf16* wuv = (const bf16*)d_in[4];
    const bf16* wo = (const bf16*)d_in[5];
    const bf16* mem0 = (const bf16*)d_in[7];
    const bf16* Wq = (const bf16*)d_in[8];
    const bf16* Wk = (const bf16*)d_in[9];
    const bf16* Wv = (const bf16*)d_in[10];
    const bf16* Wo = (const bf16*)d_in[11];
    const bf16* gate_w = (const bf16*)d_in[13];
    bf16* out = (bf16*)d_out;

    static Proj2Params P2;
    static ChainParams CP;
    static AttnParams AP;
    static OutParams OP;
    static bool init = false;
    static const void* last_in[14];
    static const void* last_out;
    bool same = init && last_out == d_out;
    for (int i = 0; i < 14 && same; i++) same = last_in[i] == d_in[i];
    if (!init) {
        cudaDriverEntryPointQueryResult qr;
        cudaGetDriverEntryPoint("cuTensorMapEncodeTiled", (void**)&g_encode, cudaEnableDefault, &qr);
        cudaFuncSetAttribute(proj2_kernel, cudaFuncAttributeMaxDynamicSharedMemorySize, P2_SMEM);
        cudaFuncSetAttribute(attn_kernel, cudaFuncAttributeMaxDynamicSharedMemorySize, FA_SMEM);
        cudaFuncSetAttribute(chain_kernel, cudaFuncAttributeMaxDynamicSharedMemorySize, CH_SMEM);
        cudaFuncSetAttribute(out2_kernel, cudaFuncAttributeMaxDynamicSharedMemorySize, O2_SMEM);
        init = true;
    }
    if (!same) {
        for (int i = 0; i < 14; i++) last_in[i] = d_in[i];
        last_out = d_out;
        void *pQA, *pKA, *pVA, *pCA, *pCB;
        cudaGetSymbolAddress(&pQA, g_QA); cudaGetSymbolAddress(&pKA, g_KA); cudaGetSymbolAddress(&pVA, g_VA);
        cudaGetSymbolAddress(&pCA, g_ctxA); cudaGetSymbolAddress(&pCB, g_ctxB);
        make_map(&P2.mapA[0], x, SEQ, DM, 128);
        make_map(&P2.mapA[1], ckv, SEQ, DM, 128);
        const void* ws[3] = {wq, wuk, wuv};
        void* cs[3] = {pQA, pKA, pVA};
        for (int i = 0; i < 3; i++) { make_map(&P2.mapW[i], ws[i], DM, NQ, 64); P2.out[i] = (bf16*)cs[i]; }
        make_map(&CP.mapW[0], Wq, DM, NQ, 64); make_map(&CP.mapW[1], Wk, DM, NQ, 64); make_map(&CP.mapW[2], Wv, DM, NQ, 64);
        make_map(&CP.mapX, x, SEQ, DM, 32);
        make_map(&CP.mapC, pCB, NH * SEQ, HD, 32);
        make_map(&AP.mapQ, pQA, NH * SEQ, HD, 128);
        make_map(&AP.mapK, pKA, NH * SEQ, HD, 128);
        make_map(&AP.mapV, pVA, NH * SEQ, HD, 128);
        make_map(&AP.mapO, pCA, NH * SEQ, HD, 64);
        make_map(&OP.mapCtx[0], pCA, NH * SEQ, HD, 128);
        make_map(&OP.mapCtx[1], pCB, NH * SEQ, HD, 128);
        make_map(&OP.mapWo[0], wo, NQ, DM, 64);
        make_map(&OP.mapWo[1], Wo, NQ, DM, 64);
        make_map(&OP.mapOut, out, SEQ, DM, 16);
        AP.out = out;
    }
    cudaStream_t s1 = cudaStreamPerThread;
    const bool pdl = true;
    launch_pdl(chain_kernel, 64, CH_BLOCK, CH_SMEM, s1, false, CP, mem0, Wo, x, gate_w);
    launch_pdl(proj2_kernel, 68, 384, P2_SMEM, s1, pdl, P2);
    launch_pdl(attn_kernel, FA_GRID, 384, FA_SMEM, s1, pdl, AP);
    launch_pdl(out2_kernel, O2_GRID, 352, O2_SMEM, s1, pdl, OP);
}
```

```cpp
#include <cuda_runtime.h>
#include <cuda_bf16.h>
#include <cuda.h>
#include <stdint.h>
#include <type_traits>

constexpr int SEQ = 2048;
constexpr int DM = 512;
constexpr int NH = 32;
constexpr int HD = 128;
constexpr int NQ = NH * HD;
constexpr int SEGL = 32;
constexpr int NMEM = 8;
constexpr int NSEG = SEQ / SEGL;

typedef __nv_bfloat16 bf16;

__device__ bf16 g_QA[SEQ * NQ];
__device__ bf16 g_KA[SEQ * NQ];
__device__ bf16 g_VA[SEQ * NQ];
__device__ bf16 g_ctxA[SEQ * NQ];
__device__ bf16 g_ctxB[SEQ * NQ];
constexpr int CT_PROJ = 0, CT_ATTN = 1, CT_FIN = 5;
constexpr int CT_AP = 64;
constexpr int CT_GATE = 96;
constexpr int CT_CA = 128;
constexpr int CT_CB = 192;
constexpr int CT_OT = 208;
constexpr int CT_N = 224;
__device__ __align__(16) unsigned int g_ctr[CT_N];
__device__ float g_gate[SEQ];
__device__ uint32_t g_xbuf[4 * 8 * 2048];

#define FA_GRID 68

#define TS_BEGIN(id)
#define TS_END(id)
#define WAIT_LIMIT 200000
__device__ __forceinline__ void pdl_launch_dependents() { asm volatile("griddepcontrol.launch_dependents;" ::: "memory"); }
__device__ __forceinline__ void wait_ctr(int idx, unsigned int n) {
    unsigned int v; int it = 0;
    do { asm volatile("ld.acquire.gpu.global.u32 %0, [%1];" : "=r"(v) : "l"(&g_ctr[idx]) : "memory"); } while (v < n && ++it < WAIT_LIMIT);
    asm volatile("fence.proxy.async.shared::cta;" ::: "memory");
}
__device__ __forceinline__ int take_ticket(int idx) {
    int v;
    asm volatile("atom.relaxed.gpu.global.inc.u32 %0, [%1], 0x7fffffff;" : "=r"(v) : "l"(&g_ctr[idx]) : "memory");
    return v;
}
__device__ __forceinline__ void signal_ctr(int idx) {
    asm volatile("fence.proxy.async;" ::: "memory");
    __threadfence();
    atomicAdd(&g_ctr[idx], 1u);
}
__device__ __forceinline__ void signal_ctr_generic(int idx) {
    asm volatile("red.release.gpu.global.add.u32 [%0], 1;" :: "l"(&g_ctr[idx]) : "memory");
}
__device__ __forceinline__ uint32_t smem_u32(const void* p) {
    return (uint32_t)__cvta_generic_to_shared(p);
}
__device__ __forceinline__ void mbar_init(uint32_t bar, uint32_t count) {
    asm volatile("mbarrier.init.shared::cta.b64 [%0], %1;" :: "r"(bar), "r"(count));
}
__device__ __forceinline__ void mbar_expect_tx(uint32_t bar, uint32_t bytes) {
    asm volatile("mbarrier.arrive.expect_tx.shared::cta.b64 _, [%0], %1;" :: "r"(bar), "r"(bytes) : "memory");
}
__device__ __forceinline__ void mbar_arrive(uint32_t bar) {
    asm volatile("mbarrier.arrive.shared::cta.b64 _, [%0];" :: "r"(bar) : "memory");
}
__device__ __forceinline__ void mbar_wait(uint32_t bar, uint32_t parity) {
    asm volatile(
        "{\n"
        ".reg .pred p, q;\n"
        ".reg .u32 c;\n"
        "mov.u32 c, 0;\n"
        "WAIT_LOOP:\n"
        "mbarrier.try_wait.parity.shared::cta.b64 p, [%0], %1;\n"
        "@p bra WAIT_DONE;\n"
        "add.u32 c, c, 1;\n"
        "setp.lt.u32 q, c, %2;\n"
        "@q bra WAIT_LOOP;\n"
        "WAIT_DONE:\n"
        "}\n" :: "r"(bar), "r"(parity), "n"(WAIT_LIMIT) : "memory");
}
__device__ __forceinline__ uint32_t mbar_test(uint32_t bar, uint32_t parity) {
    uint32_t done;
    asm volatile(
        "{\n.reg .pred p;\n"
        "mbarrier.test_wait.parity.shared::cta.b64 p, [%1], %2;\n"
        "selp.u32 %0, 1, 0, p;\n}\n" : "=r"(done) : "r"(bar), "r"(parity) : "memory");
    return done;
}
__device__ __forceinline__ uint32_t mbar_try(uint32_t bar, uint32_t parity) {
    uint32_t done;
    asm volatile(
        "{\n.reg .pred p;\n"
        "mbarrier.try_wait.parity.shared::cta.b64 p, [%1], %2;\n"
        "selp.u32 %0, 1, 0, p;\n}\n" : "=r"(done) : "r"(bar), "r"(parity) : "memory");
    return done;
}
__device__ __forceinline__ void tma_load_2d(uint32_t dst, const CUtensorMap* map, uint32_t bar, int c0, int c1) {
    asm volatile(
        "cp.async.bulk.tensor.2d.shared::cluster.global.mbarrier::complete_tx::bytes [%0], [%1, {%3, %4}], [%2];"
        :: "r"(dst), "l"((uint64_t)map), "r"(bar), "r"(c0), "r"(c1) : "memory");
}
__device__ __forceinline__ void wgmma_fence() { asm volatile("wgmma.fence.sync.aligned;" ::: "memory"); }
__device__ __forceinline__ void wgmma_commit() { asm volatile("wgmma.commit_group.sync.aligned;" ::: "memory"); }
template <int N> __device__ __forceinline__ void wgmma_wait() {
    asm volatile("wgmma.wait_group.sync.aligned %0;" :: "n"(N) : "memory");
}
__device__ __forceinline__ uint64_t make_desc(uint32_t addr, uint32_t lbo, uint32_t sbo) {
    uint64_t d = 0;
    d |= (uint64_t)((addr & 0x3FFFF) >> 4);
    d |= (uint64_t)((lbo >> 4) & 0x3FFF) << 16;
    d |= (uint64_t)((sbo >> 4) & 0x3FFF) << 32;
    d |= (uint64_t)1 << 62;
    return d;
}

#define ACC64(d) \
    "+f"(d[0]), "+f"(d[1]), "+f"(d[2]), "+f"(d[3]), "+f"(d[4]), "+f"(d[5]), "+f"(d[6]), "+f"(d[7]), \
    "+f"(d[8]), "+f"(d[9]), "+f"(d[10]), "+f"(d[11]), "+f"(d[12]), "+f"(d[13]), "+f"(d[14]), "+f"(d[15]), \
    "+f"(d[16]), "+f"(d[17]), "+f"(d[18]), "+f"(d[19]), "+f"(d[20]), "+f"(d[21]), "+f"(d[22]), "+f"(d[23]), \
    "+f"(d[24]), "+f"(d[25]), "+f"(d[26]), "+f"(d[27]), "+f"(d[28]), "+f"(d[29]), "+f"(d[30]), "+f"(d[31]), \
    "+f"(d[32]), "+f"(d[33]), "+f"(d[34]), "+f"(d[35]), "+f"(d[36]), "+f"(d[37]), "+f"(d[38]), "+f"(d[39]), \
    "+f"(d[40]), "+f"(d[41]), "+f"(d[42]), "+f"(d[43]), "+f"(d[44]), "+f"(d[45]), "+f"(d[46]), "+f"(d[47]), \
    "+f"(d[48]), "+f"(d[49]), "+f"(d[50]), "+f"(d[51]), "+f"(d[52]), "+f"(d[53]), "+f"(d[54]), "+f"(d[55]), \
    "+f"(d[56]), "+f"(d[57]), "+f"(d[58]), "+f"(d[59]), "+f"(d[60]), "+f"(d[61]), "+f"(d[62]), "+f"(d[63])
#define ACC64_STR \
    "{%0, %1, %2, %3, %4, %5, %6, %7, %8, %9, %10, %11, %12, %13, %14, %15, " \
    "%16, %17, %18, %19, %20, %21, %22, %23, %24, %25, %26, %27, %28, %29, %30, %31, " \
    "%32, %33, %34, %35, %36, %37, %38, %39, %40, %41, %42, %43, %44, %45, %46, %47, " \
    "%48, %49, %50, %51, %52, %53, %54, %55, %56, %57, %58, %59, %60, %61, %62, %63}"

template <int TB>
__device__ __forceinline__ void wgmma_ss_n128(float (&d)[64], uint64_t da, uint64_t db, int scale_d) {
    asm volatile(
        "{\n.reg .pred p;\nsetp.ne.b32 p, %66, 0;\n"
        "wgmma.mma_async.sync.aligned.m64n128k16.f32.bf16.bf16 " ACC64_STR ", %64, %65, p, 1, 1, 0, %67;\n}\n"
        : ACC64(d) : "l"(da), "l"(db), "r"(scale_d), "n"(TB));
}
__device__ __forceinline__ uint32_t desc_lo(uint32_t addr, uint32_t lbo) { return ((addr & 0x3FFFF) >> 4) | ((lbo >> 4) << 16); }
template <int TB>
__device__ __forceinline__ void wgmma_ss_n128_lo(float (&d)[64], uint32_t da_lo, uint32_t db_lo, int scale_d) {
    asm volatile(
        "{\n.reg .pred p;\n.reg .b64 da, db;\nsetp.ne.b32 p, %66, 0;\n"
        "mov.b64 da, {%64, 0x40000040};\nmov.b64 db, {%65, 0x40000040};\n"
        "wgmma.mma_async.sync.aligned.m64n128k16.f32.bf16.bf16 " ACC64_STR ", da, db, p, 1, 1, 0, %67;\n}\n"
        : ACC64(d) : "r"(da_lo), "r"(db_lo), "r"(scale_d), "n"(TB));
}
__device__ __forceinline__ void wgmma_rs_n128_tb(float (&d)[64], uint32_t a0, uint32_t a1, uint32_t a2, uint32_t a3,
                                                 uint64_t db, int scale_d) {
    asm volatile(
        "{\n.reg .pred p;\nsetp.ne.b32 p, %69, 0;\n"
        "wgmma.mma_async.sync.aligned.m64n128k16.f32.bf16.bf16 " ACC64_STR ", {%64, %65, %66, %67}, %68, p, 1, 1, 1;\n}\n"
        : ACC64(d) : "r"(a0), "r"(a1), "r"(a2), "r"(a3), "l"(db), "r"(scale_d));
}
__device__ __forceinline__ void wgmma_rs_n80(float (&d)[40], const uint32_t (&a)[4], uint32_t db_lo, int scale_d) {
    asm volatile(
        "{\n.reg .pred p;\n.reg .b64 db;\nsetp.ne.b32 p, %45, 0;\nmov.b64 db, {%44, 0x40000040};\n"
        "wgmma.mma_async.sync.aligned.m64n80k16.f32.bf16.bf16 "
        "{%0, %1, %2, %3, %4, %5, %6, %7, %8, %9, %10, %11, %12, %13, %14, %15, %16, %17, %18, %19, %20, %21, %22, %23, %24, %25, %26, %27, %28, %29, %30, %31, %32, %33, %34, %35, %36, %37, %38, %39}, "
        "{%40, %41, %42, %43}, db, p, 1, 1, 0;\n}\n"
        : "+f"(d[0]), "+f"(d[1]), "+f"(d[2]), "+f"(d[3]), "+f"(d[4]), "+f"(d[5]), "+f"(d[6]), "+f"(d[7]), "+f"(d[8]), "+f"(d[9]), "+f"(d[10]), "+f"(d[11]), "+f"(d[12]), "+f"(d[13]), "+f"(d[14]), "+f"(d[15]), "+f"(d[16]), "+f"(d[17]), "+f"(d[18]), "+f"(d[19]), "+f"(d[20]), "+f"(d[21]), "+f"(d[22]), "+f"(d[23]), "+f"(d[24]), "+f"(d[25]), "+f"(d[26]), "+f"(d[27]), "+f"(d[28]), "+f"(d[29]), "+f"(d[30]), "+f"(d[31]), "+f"(d[32]), "+f"(d[33]), "+f"(d[34]), "+f"(d[35]), "+f"(d[36]), "+f"(d[37]), "+f"(d[38]), "+f"(d[39])
        : "r"(a[0]), "r"(a[1]), "r"(a[2]), "r"(a[3]), "r"(db_lo), "r"(scale_d));
}
__device__ __forceinline__ void wgmma_ss_n256_tb(float (&d)[128], uint64_t da, uint64_t db, int scale_d) {
    asm volatile(
        "{\n.reg .pred p;\nsetp.ne.b32 p, %130, 0;\n"
        "wgmma.mma_async.sync.aligned.m64n256k16.f32.bf16.bf16 {%0, %1, %2, %3, %4, %5, %6, %7, %8, %9, %10, %11, %12, %13, %14, %15, %16, %17, %18, %19, %20, %21, %22, %23, %24, %25, %26, %27, %28, %29, %30, %31, %32, %33, %34, %35, %36, %37, %38, %39, %40, %41, %42, %43, %44, %45, %46, %47, %48, %49, %50, %51, %52, %53, %54, %55, %56, %57, %58, %59, %60, %61, %62, %63, %64, %65, %66, %67, %68, %69, %70, %71, %72, %73, %74, %75, %76, %77, %78, %79, %80, %81, %82, %83, %84, %85, %86, %87, %88, %89, %90, %91, %92, %93, %94, %95, %96, %97, %98, %99, %100, %101, %102, %103, %104, %105, %106, %107, %108, %109, %110, %111, %112, %113, %114, %115, %116, %117, %118, %119, %120, %121, %122, %123, %124, %125, %126, %127}, %128, %129, p, 1, 1, 0, 1;\n}\n"
        : "+f"(d[0]), "+f"(d[1]), "+f"(d[2]), "+f"(d[3]), "+f"(d[4]), "+f"(d[5]), "+f"(d[6]), "+f"(d[7]), "+f"(d[8]), "+f"(d[9]), "+f"(d[10]), "+f"(d[11]), "+f"(d[12]), "+f"(d[13]), "+f"(d[14]), "+f"(d[15]), "+f"(d[16]), "+f"(d[17]), "+f"(d[18]), "+f"(d[19]), "+f"(d[20]), "+f"(d[21]), "+f"(d[22]), "+f"(d[23]), "+f"(d[24]), "+f"(d[25]), "+f"(d[26]), "+f"(d[27]), "+f"(d[28]), "+f"(d[29]), "+f"(d[30]), "+f"(d[31]), "+f"(d[32]), "+f"(d[33]), "+f"(d[34]), "+f"(d[35]), "+f"(d[36]), "+f"(d[37]), "+f"(d[38]), "+f"(d[39]), "+f"(d[40]), "+f"(d[41]), "+f"(d[42]), "+f"(d[43]), "+f"(d[44]), "+f"(d[45]), "+f"(d[46]), "+f"(d[47]), "+f"(d[48]), "+f"(d[49]), "+f"(d[50]), "+f"(d[51]), "+f"(d[52]), "+f"(d[53]), "+f"(d[54]), "+f"(d[55]), "+f"(d[56]), "+f"(d[57]), "+f"(d[58]), "+f"(d[59]), "+f"(d[60]), "+f"(d[61]), "+f"(d[62]), "+f"(d[63]), "+f"(d[64]), "+f"(d[65]), "+f"(d[66]), "+f"(d[67]), "+f"(d[68]), "+f"(d[69]), "+f"(d[70]), "+f"(d[71]), "+f"(d[72]), "+f"(d[73]), "+f"(d[74]), "+f"(d[75]), "+f"(d[76]), "+f"(d[77]), "+f"(d[78]), "+f"(d[79]), "+f"(d[80]), "+f"(d[81]), "+f"(d[82]), "+f"(d[83]), "+f"(d[84]), "+f"(d[85]), "+f"(d[86]), "+f"(d[87]), "+f"(d[88]), "+f"(d[89]), "+f"(d[90]), "+f"(d[91]), "+f"(d[92]), "+f"(d[93]), "+f"(d[94]), "+f"(d[95]), "+f"(d[96]), "+f"(d[97]), "+f"(d[98]), "+f"(d[99]), "+f"(d[100]), "+f"(d[101]), "+f"(d[102]), "+f"(d[103]), "+f"(d[104]), "+f"(d[105]), "+f"(d[106]), "+f"(d[107]), "+f"(d[108]), "+f"(d[109]), "+f"(d[110]), "+f"(d[111]), "+f"(d[112]), "+f"(d[113]), "+f"(d[114]), "+f"(d[115]), "+f"(d[116]), "+f"(d[117]), "+f"(d[118]), "+f"(d[119]), "+f"(d[120]), "+f"(d[121]), "+f"(d[122]), "+f"(d[123]), "+f"(d[124]), "+f"(d[125]), "+f"(d[126]), "+f"(d[127])
        : "l"(da), "l"(db), "r"(scale_d));
}
__device__ __forceinline__ void stmatrix_x4(uint32_t addr, uint32_t r0, uint32_t r1, uint32_t r2, uint32_t r3) {
    asm volatile("stmatrix.sync.aligned.m8n8.x4.shared.b16 [%0], {%1, %2, %3, %4};" :: "r"(addr), "r"(r0), "r"(r1), "r"(r2), "r"(r3) : "memory");
}
__device__ __forceinline__ void tma_store_2d(const CUtensorMap* map, uint32_t src, int c0, int c1) {
    asm volatile("cp.async.bulk.tensor.2d.global.shared::cta.bulk_group [%0, {%2, %3}], [%1];"
                 :: "l"((uint64_t)map), "r"(src), "r"(c0), "r"(c1) : "memory");
}
__device__ __forceinline__ float ex2f(float x) { float y; asm("ex2.approx.ftz.f32 %0, %1;" : "=f"(y) : "f"(x)); return y; }
__device__ __forceinline__ uint32_t pack_bf16(float lo, float hi) {
    __nv_bfloat162 v = __floats2bfloat162_rn(lo, hi);
    return *reinterpret_cast<uint32_t*>(&v);
}
__device__ __forceinline__ void mma_16816(float (&c)[4], uint32_t a0, uint32_t a1, uint32_t a2, uint32_t a3,
                                          uint32_t b0, uint32_t b1) {
    asm volatile(
        "mma.sync.aligned.m16n8k16.row.col.f32.bf16.bf16.f32 {%0,%1,%2,%3}, {%4,%5,%6,%7}, {%8,%9}, {%0,%1,%2,%3};"
        : "+f"(c[0]), "+f"(c[1]), "+f"(c[2]), "+f"(c[3])
        : "r"(a0), "r"(a1), "r"(a2), "r"(a3), "r"(b0), "r"(b1));
}
__device__ __forceinline__ void ldmatrix_x4_trans(uint32_t& r0, uint32_t& r1, uint32_t& r2, uint32_t& r3, uint32_t addr) {
    asm volatile("ldmatrix.sync.aligned.m8n8.x4.trans.shared.b16 {%0,%1,%2,%3}, [%4];"
                 : "=r"(r0), "=r"(r1), "=r"(r2), "=r"(r3) : "r"(addr));
}

struct AttnParams {
    CUtensorMap mapQ, mapK, mapV;
    CUtensorMap mapO;
    bf16* out;
};
constexpr int FA_SMEM = 2 * 32768 + 2 * 65536 + 32768 + 1024 + 256;
constexpr int FA_ITEMS = 16 * NH;
__device__ __forceinline__ int fa_qt(int t) { return 15 - ((t & 127) >> 3); }
__device__ __forceinline__ int fa_head(int t) { return (t >> 7) * 8 + (t & 7); }
#define FA_TKA 2
#define FA_SPLIT 11

#define FA_P0 3
#define FA_HO 7
#define FA_LAG 2
#define FA_PK 3
#define FA_ST 4
#define FA_TG 16
#define FA_EARLY 0
#define FA_I0 0
static_assert(FA_GRID <= 104 && FA_HO >= FA_P0 && FA_P0 >= 1, "");
constexpr float FA_MARGIN = 16.f;
#define FAT(b, i)
__device__ __forceinline__ void mbar_arrive_if(uint32_t bar, bool c) {
    asm volatile("{\n.reg .pred p;\nsetp.ne.b32 p, %1, 0;\n@p mbarrier.arrive.shared::cta.b64 _, [%0];\n}" :: "r"(bar), "r"((int)c) : "memory");
}
__device__ __forceinline__ void sched_fence(int v, int id, const float* a, const float* b, const float* c) {
    asm volatile("{\n.reg .pred p;\nsetp.ne.s32 p, %0, %1;\n@p bra SF_SKIP;\nwgmma.wait_group.sync.aligned 0;\n"
                 "st.volatile.shared.f32 [%0], %2;\nst.volatile.shared.f32 [%0], %3;\nst.volatile.shared.f32 [%0], %4;\nst.volatile.shared.f32 [%0], %5;\n"
                 "st.volatile.shared.f32 [%0], %6;\nst.volatile.shared.f32 [%0], %7;\nst.volatile.shared.f32 [%0], %8;\nst.volatile.shared.f32 [%0], %9;\n"
                 "st.volatile.shared.f32 [%0], %10;\nst.volatile.shared.f32 [%0], %11;\nst.volatile.shared.f32 [%0], %12;\nst.volatile.shared.f32 [%0], %13;\n"
                 "exit;\nSF_SKIP:\n}" :: "r"(v), "r"(1000000 + id), "f"(a[0]), "f"(a[1]), "f"(a[2]), "f"(a[3]), "f"(b[0]), "f"(b[1]), "f"(b[2]), "f"(b[3]),
                 "f"(c[0]), "f"(c[1]), "f"(c[2]), "f"(c[3]) : "memory");
}
__device__ __forceinline__ float ex2v(float x) { float y; asm volatile("ex2.approx.ftz.f32 %0, %1;" : "=f"(y) : "f"(x)); return y; }
__device__ __forceinline__ void wgmma_rs_n128_tb_lo(float (&d)[64], const uint32_t* a, uint32_t db_lo, int scale_d) {
    asm volatile(
        "{\n.reg .pred p;\n.reg .b64 db;\nsetp.ne.b32 p, %69, 0;\nmov.b64 db, {%68, 0x40000040};\n"
        "wgmma.mma_async.sync.aligned.m64n128k16.f32.bf16.bf16 " ACC64_STR ", {%64, %65, %66, %67}, db, p, 1, 1, 1;\n}\n"
        : ACC64(d) : "r"(a[0]), "r"(a[1]), "r"(a[2]), "r"(a[3]), "r"(db_lo), "r"(scale_d));
}

__global__ void __launch_bounds__(384, 1) attn_kernel(const __grid_constant__ AttnParams P) {
    extern __shared__ uint8_t smem_raw[];
    constexpr uint32_t sbase = 1024;
    if (smem_u32(smem_raw) > sbase) __trap();
    constexpr uint32_t sQ = sbase;
    constexpr uint32_t sKV = sbase + 65536;
    constexpr uint32_t sO = sKV + 2 * 65536;
    constexpr uint32_t bars = sO + 32768;
    constexpr uint32_t bar_qf = bars, bar_qe = bars + 16, bar_kf = bars + 32, bar_vf = bars + 48, bar_ke = bars + 64, bar_ve = bars + 80,
                   bar_of = bars + 96, bar_oe = bars + 112, slot = bars + 128, oslot = bars + 136;
    const int warp = __shfl_sync(0xffffffff, threadIdx.x >> 5, 0);
    TS_BEGIN(1);
    if (threadIdx.x == 256) {
        asm volatile("prefetch.tensormap [%0];" :: "l"(&P.mapQ) : "memory");
        asm volatile("prefetch.tensormap [%0];" :: "l"(&P.mapK) : "memory");
        for (int i = 0; i < 2; i++) {
            mbar_init(bar_qf + 8 * i, 1); mbar_init(bar_qe + 8 * i, 8); mbar_init(bar_kf + 8 * i, 1); mbar_init(bar_vf + 8 * i, 1);
            mbar_init(bar_ke + 8 * i, 8); mbar_init(bar_ve + 8 * i, 8); mbar_init(bar_of + 8 * i, 4); mbar_init(bar_oe + 8 * i, 1);
        }
        asm volatile("fence.mbarrier_init.release.cluster;" ::: "memory");
    }
    __syncthreads();
    pdl_launch_dependents();
    if (warp >= 8) {
        asm volatile("setmaxnreg.dec.sync.aligned.u32 40;");
        if (threadIdx.x == 288 || threadIdx.x == 320) {
            const int wg = threadIdx.x == 288 ? 0 : 1;
            const uint32_t stg = sO + wg * 16384;
            for (int n = 0;; n++) {
                mbar_wait(bar_of + 8 * wg, n & 1);
                int t;
                asm volatile("ld.shared.s32 %0, [%1];" : "=r"(t) : "r"(oslot + wg * 4) : "memory");
                const int qt = fa_qt(t), h = fa_head(t & 1023);
                tma_store_2d(&P.mapO, stg, 0, h * SEQ + qt * 128 + wg * 64);
                tma_store_2d(&P.mapO, stg + 8192, 64, h * SEQ + qt * 128 + wg * 64);
                asm volatile("cp.async.bulk.commit_group;" ::: "memory");
                asm volatile("cp.async.bulk.wait_group.read 0;" ::: "memory");
                mbar_arrive(bar_oe + 8 * wg);
                asm volatile("cp.async.bulk.wait_group 0;" ::: "memory");
                signal_ctr(CT_CA + qt * 4 + (h >> 3));
                if (t >= 1024) break;
            }
        }
        if (threadIdx.x == 256) {
            int b = 0, hp_ready = 0, vrow = 0, t = blockIdx.x;
            auto load_v = [&](int i) {
                const uint32_t sv = sKV + (i & 1) * 65536 + 32768, bar = bar_vf + 8 * (i & 1);
                mbar_wait(bar_ve + 8 * (i & 1), ((i >> 1) & 1) ^ 1);
                mbar_expect_tx(bar, 32768);
                tma_load_2d(sv, &P.mapV, bar, 0, vrow);
                tma_load_2d(sv + 16384, &P.mapV, bar, 64, vrow);
            };
            for (int item = 0;; item++) {
                const bool valid = t < FA_ITEMS;
                const int qt = fa_qt(t), h = fa_head(t);
                if (valid && !((hp_ready >> (h >> 1)) & 1)) { wait_ctr(CT_AP + (h >> 1), 96u); hp_ready |= 1 << (h >> 1); }
                const uint32_t bq = bar_qf + 8 * (item & 1);
                mbar_wait(bar_qe + 8 * (item & 1), ((item >> 1) & 1) ^ 1);
                asm volatile("st.shared.s32 [%0], %1;" :: "r"(slot + (item & 1) * 4), "r"(valid ? t : -1) : "memory");
                if (!valid) { mbar_arrive(bq); break; }
                mbar_expect_tx(bq, 32768);
                tma_load_2d(sQ + (item & 1) * 32768, &P.mapQ, bq, 0, h * SEQ + qt * 128);
                tma_load_2d(sQ + (item & 1) * 32768 + 16384, &P.mapQ, bq, 64, h * SEQ + qt * 128);
#pragma unroll 1
                for (int j = 0; j <= qt; j++, b++) {
                    const uint32_t sk = sKV + (b & 1) * 65536, bar = bar_kf + 8 * (b & 1);
                    mbar_wait(bar_ke + 8 * (b & 1), ((b >> 1) & 1) ^ 1);
                    if (b == 2) wait_ctr(CT_GATE, 64u);
                    mbar_expect_tx(bar, 32768);
                    tma_load_2d(sk, &P.mapK, bar, 0, h * SEQ + j * 128);
                    tma_load_2d(sk + 16384, &P.mapK, bar, 64, h * SEQ + j * 128);
                    if (j == max(qt - FA_TKA, 0)) t = take_ticket(CT_ATTN);
                    if (b > 0) load_v(b - 1);
                    vrow = h * SEQ + j * 128;
                }
                t += gridDim.x;
            }
            load_v(b - 1);
        }
    } else {
        asm volatile("setmaxnreg.inc.sync.aligned.u32 232;");
        const int wg = warp >> 2;
        const int lane = threadIdx.x & 31;
        const float sc = 0.08838834764831845f * 1.4426950408889634f;
        const int r0 = wg * 64 + (warp & 3) * 16 + (lane >> 2);
        float o[64], s[64];
        uint32_t pa[32];
        float m0 = 0.f, m1 = 0.f, l0 = 0.f, l1 = 0.f, i0 = 0.f, i1 = 0.f, g0 = 0.f, g1 = 0.f;
        const uint32_t q_lo = desc_lo(sQ + wg * 8192, 16), k_lo = desc_lo(sKV, 16), v_lo = desc_lo(sKV + 32768, 16384);
        auto issue_qk = [&](int b, int item) {
            const uint32_t qd = q_lo + (item & 1) * 2048, kd = k_lo + (b & 1) * 4096;
            wgmma_fence();
#pragma unroll
            for (int kk = 0; kk < 8; kk++) wgmma_ss_n128_lo<0>(s, qd + (kk >> 2) * 1024 + (kk & 3) * 2, kd + (kk >> 2) * 1024 + (kk & 3) * 2, kk != 0);
            wgmma_commit();
        };
        auto issue_pv = [&](int b, bool acc, int n) {
            const uint32_t vd = v_lo + (b & 1) * 4096;
            mbar_wait(bar_vf + 8 * (b & 1), (b >> 1) & 1);
            wgmma_fence();
#pragma unroll
            for (int kk = 0; kk < 8; kk++) if (kk < n) wgmma_rs_n128_tb_lo(o, &pa[kk * 4], vd + kk * 128, kk ? 1 : (int)acc);
            wgmma_commit();
        };
        const int lim = r0 - (lane & 3) * 2;
        int item = -1, tnext = 0;
        uint32_t k_ready = 0, q_ready = 0;
        auto mask = [&](int i) { if ((i >> 2) * 8 + (i & 1) - ((i & 2) ? 8 : 0) > lim) s[i] = -INFINITY; };
        auto exps = [&](auto mode, int b, bool hand_over, float& u0, float& u1) {
            constexpr int MODE = decltype(mode)::value;
            float p[64], u[4] = {0.f, 0.f, 0.f, 0.f};
            const uint32_t vd = v_lo + ((b - 1) & 1) * 4096;
#pragma unroll
            for (int i = 0; i < 4; i++) p[i] = fmaf(s[i], sc, (i & 2) ? -m1 : -m0);
#pragma unroll
            for (int g = 0; g < 16 + FA_LAG; g++) {
                if (MODE && g >= FA_I0 && g - FA_I0 < 8 - FA_P0) {
                    const int kk = FA_P0 + g - FA_I0;
                    wgmma_fence();
                    wgmma_rs_n128_tb_lo(o, &pa[kk * 4], vd + kk * 128, 1);
                    wgmma_commit();
                    if (kk == FA_HO) asm volatile("{\n.reg .pred p;\nsetp.ne.b32 p, %1, 0;\n@p bar.arrive %0, 256;\n}" :: "r"(2 - wg), "r"((int)hand_over) : "memory");
                }
                if (MODE && g == FA_SPLIT) {
                    FAT(b, 2);
                    wgmma_wait<0>();
                    FAT(b - 1, 3);
                    mbar_arrive_if(bar_ve + 8 * ((b - 1) & 1), lane == 0);
                }
                if (MODE && g == FA_TG) {
                    k_ready = mbar_test(bar_kf + 8 * (~b & 1), ((b + 1) >> 1) & 1);
                    if (MODE == 2) {
                        q_ready = mbar_test(bar_qf + 8 * (~item & 1), ((item + 1) >> 1) & 1);
                        asm volatile("ld.shared.s32 %0, [%1];" : "=r"(tnext) : "r"(slot + (~item & 1) * 4) : "memory");
                    }
                }
#pragma unroll
                for (int j = 0; j < 4; j++) {
                    const int i = g * 4 + j;
                    if (g < 16) p[i] = ex2v(p[i]);
                    if (g < 15) {
                        if (MODE == 2) mask(i + 4);
                        p[i + 4] = fmaf(s[i + 4], sc, (i & 2) ? -m1 : -m0);
                    }
                    if (g >= FA_LAG) u[j] += p[i - FA_LAG * 4];
                }
#pragma unroll
                for (int gg = 0; gg < 16; gg++) {
                    const int at = MODE && gg + FA_LAG < FA_SPLIT + gg / FA_PK ? FA_SPLIT + gg / FA_PK : gg + FA_LAG;
                    if (at == g) { pa[gg * 2] = pack_bf16(p[gg * 4], p[gg * 4 + 1]); pa[gg * 2 + 1] = pack_bf16(p[gg * 4 + 2], p[gg * 4 + 3]); }
                }
                if (MODE && g < 16) sched_fence(b, g + MODE * 32, &p[g * 4], &p[(g < 15 ? g + 1 : g) * 4], u);
            }
            u0 = u[0] + u[1]; u1 = u[2] + u[3];
        };
        auto quad_max = [&](float& x0, float& x1) {
            x0 = fmaxf(x0, __shfl_xor_sync(0xffffffff, x0, 1)); x1 = fmaxf(x1, __shfl_xor_sync(0xffffffff, x1, 1));
            x0 = fmaxf(x0, __shfl_xor_sync(0xffffffff, x0, 2)); x1 = fmaxf(x1, __shfl_xor_sync(0xffffffff, x1, 2));
            x0 = fmaf(x0, sc, FA_MARGIN); x1 = fmaf(x1, sc, FA_MARGIN);
        };
        auto softmax_exact = [&](bool fresh, int b) {
            wgmma_wait<0>();
            float x[8];
#pragma unroll
            for (int i = 0; i < 8; i++) x[i] = fmaxf(s[i * 2], s[i * 2 + 1]);
#pragma unroll
            for (int i = 8; i < 32; i++) x[i & 7] = fmaxf(x[i & 7], fmaxf(s[i * 2], s[i * 2 + 1]));
            float x0 = fmaxf(fmaxf(x[0], x[2]), fmaxf(x[4], x[6])), x1 = fmaxf(fmaxf(x[1], x[3]), fmaxf(x[5], x[7]));
            quad_max(x0, x1);
            if (!fresh) {
                x0 = fmaxf(x0, m0); x1 = fmaxf(x1, m1);
                const float a0 = ex2f(m0 - x0), a1 = ex2f(m1 - x1);
                l0 *= a0; l1 *= a1;
#pragma unroll
                for (int i = 0; i < 16; i++) { o[i * 4 + 0] *= a0; o[i * 4 + 1] *= a0; o[i * 4 + 2] *= a1; o[i * 4 + 3] *= a1; }
            }
            m0 = x0; m1 = x1;
            float u0, u1;
            exps(std::integral_constant<int, 0>(), b, false, u0, u1);
            l0 += u0; l1 += u1;
        };
        auto finish_rows = [&]() {
            l0 += __shfl_xor_sync(0xffffffff, l0, 1); l1 += __shfl_xor_sync(0xffffffff, l1, 1);
            l0 += __shfl_xor_sync(0xffffffff, l0, 2); l1 += __shfl_xor_sync(0xffffffff, l1, 2);
            i0 = __fdividef(g0, l0); i1 = __fdividef(g1, l1);
        };
        auto clear_out = [&](int t) {
            if (t >= 384) {
                bf16* z = P.out + (size_t)(fa_qt(t) * 128 + wg * 64 + ((threadIdx.x & 127) >> 3)) * DM + (t & 7) * 64 + (lane & 7) * 8;
#pragma unroll
                for (int i = 0; i < 4; i++) *reinterpret_cast<uint4*>(z + i * 16 * DM) = make_uint4(0u, 0u, 0u, 0u);
            }
        };
        auto store_o = [&](int t, int n, int c0, int c1) {
            const uint32_t stg = sO + wg * 16384;
            if (c0 == 0) {
                mbar_wait(bar_oe + 8 * wg, (n & 1) ^ 1);
                asm volatile("st.shared.s32 [%0], %1;" :: "r"(oslot + wg * 4), "r"(t) : "memory");
            }
            const int row = (warp & 3) * 16 + (lane >> 2);
#pragma unroll
            for (int i = c0; i < c1; i++) {
                const int ch = i * 4 + (lane & 3);
                const uint32_t a = stg + (ch >> 3) * 8192 + row * 128 + (((ch & 7) ^ (row & 7)) << 4);
                const float* q = &o[i * 16];
                asm volatile("st.shared.v4.b32 [%0], {%1, %2, %3, %4};" :: "r"(a), "r"(pack_bf16(q[0] * i0, q[1] * i0)), "r"(pack_bf16(q[4] * i0, q[5] * i0)),
                             "r"(pack_bf16(q[8] * i0, q[9] * i0)), "r"(pack_bf16(q[12] * i0, q[13] * i0)) : "memory");
                asm volatile("st.shared.v4.b32 [%0], {%1, %2, %3, %4};" :: "r"(a + 1024), "r"(pack_bf16(q[2] * i1, q[3] * i1)), "r"(pack_bf16(q[6] * i1, q[7] * i1)),
                             "r"(pack_bf16(q[10] * i1, q[11] * i1)), "r"(pack_bf16(q[14] * i1, q[15] * i1)) : "memory");
            }
        };
        auto publish_o = [&]() {
            asm volatile("fence.proxy.async.shared::cta;" ::: "memory");
            __syncwarp();
            mbar_arrive_if(bar_of + 8 * wg, lane == 0);
        };
        int t = 0, left = 0, tdone = -1, b = 0, nout = 0;
        bool first = true, staged = false;
        if (wg == 1) asm volatile("bar.arrive 1, 256;" ::: "memory");
#pragma unroll 1
        for (;; b++) {
            const bool fresh = left == 0;
            const int tprev = t;
            FAT(b, 4);
            if (staged) { publish_o(); staged = false; }
            if (fresh) {
                item++;
                if (!q_ready) {
                    mbar_wait(bar_qf + 8 * (item & 1), (item >> 1) & 1);
                    asm volatile("ld.shared.s32 %0, [%1];" : "=r"(tnext) : "r"(slot + (item & 1) * 4) : "memory");
                }
                if (tnext < 0) break;
                t = tnext;
                left = fa_qt(t) + 1;
            }
            left--;
            if (tdone >= 0) store_o(tdone, nout, 0, FA_ST);
            FAT(b, 5);
            if (!k_ready) mbar_wait(bar_kf + 8 * (b & 1), (b >> 1) & 1);
            FAT(b, 6);
            asm volatile("bar.sync %0, 256;" :: "r"(1 + wg) : "memory");
            FAT(b, 0);
            issue_qk(b, item);
            bool early = false;
            if (!fresh && !first && left != 0) {
                issue_pv(b - 1, true, FA_P0);
                wgmma_wait<1>();
                FAT(b, 1);
                mbar_arrive_if(bar_ke + 8 * (b & 1), lane == 0);
            } else {
                early = (FA_EARLY && tdone >= 0) || b == 0;
                if (early) asm volatile("bar.arrive %0, 256;" :: "r"(2 - wg) : "memory");
                if (tdone >= 0) { wgmma_wait<1>(); store_o(tdone, nout++, FA_ST, 4); staged = true; }
                tdone = -1;
                if (fresh && b > 0) { finish_rows(); tdone = tprev; l0 = l1 = 0.f; }
                if (left == 0) { g0 = __ldcg(g_gate + fa_qt(t) * 128 + r0); g1 = __ldcg(g_gate + fa_qt(t) * 128 + r0 + 8); clear_out(t); }
                if (b > 0) issue_pv(b - 1, !first, FA_P0); else wgmma_commit();
                first = fresh;
                wgmma_wait<1>();
                FAT(b, 1);
                mbar_arrive_if(bar_ke + 8 * (b & 1), lane == 0);
                mbar_arrive_if(bar_qe + 8 * (item & 1), lane == 0 && left == 0);
                if (left == 0) { mask(0); mask(1); }
                if (fresh) { m0 = fmaxf(s[0], s[1]); m1 = fmaxf(s[2], s[3]); quad_max(m0, m1); }
            }
            if (b > 0) {
                float u0, u1;
                if (left == 0) exps(std::integral_constant<int, 2>(), b, !early, u0, u1);
                else exps(std::integral_constant<int, 1>(), b, !early, u0, u1);
                if (!__any_sync(0xffffffff, !(u0 + u1 < 1.f))) { l0 += u0; l1 += u1; continue; }
            }
            softmax_exact(fresh, b);
        }
        if (tdone >= 0) { store_o(tdone, nout++, 0, 4); publish_o(); }
        issue_pv(b - 1, !first, 8);
        finish_rows();
        wgmma_wait<0>();
        store_o(t + 1024, nout, 0, 4);
        publish_o();
        TS_END(1);
    }
}

__device__ __forceinline__ uint32_t cluster_ctarank() {
    uint32_t r; asm volatile("mov.u32 %0, %%cluster_ctarank;" : "=r"(r)); return r;
}
__device__ __forceinline__ uint32_t mapa_u32(uint32_t addr, uint32_t rank) {
    uint32_t r; asm volatile("mapa.shared::cluster.u32 %0, %1, %2;" : "=r"(r) : "r"(addr), "r"(rank)); return r;
}
__device__ __forceinline__ void cluster_sync_all() {
    asm volatile("barrier.cluster.arrive.release.aligned;\nbarrier.cluster.wait.acquire.aligned;" ::: "memory");
}
__device__ __forceinline__ void st_async_v4(uint32_t addr, uint32_t a, uint32_t b, uint32_t c, uint32_t d, uint32_t mbar) {
    asm volatile("st.async.weak.shared::cluster.mbarrier::complete_tx::bytes.v4.b32 [%0], {%1, %2, %3, %4}, [%5];"
                 :: "r"(addr), "r"(a), "r"(b), "r"(c), "r"(d), "r"(mbar) : "memory");
}
__device__ __forceinline__ void st_async_v2(uint32_t addr, uint32_t a, uint32_t b, uint32_t mbar) {
    asm volatile("st.async.weak.shared::cluster.mbarrier::complete_tx::bytes.v2.b32 [%0], {%1, %2}, [%3];"
                 :: "r"(addr), "r"(a), "r"(b), "r"(mbar) : "memory");
}
__device__ __forceinline__ void st_async_b32(uint32_t addr, uint32_t a, uint32_t mbar) {
    asm volatile("st.async.weak.shared::cluster.mbarrier::complete_tx::bytes.b32 [%0], %1, [%2];" :: "r"(addr), "r"(a), "r"(mbar) : "memory");
}
__device__ __forceinline__ void pace(int cycles) {
    if (cycles > 0) {
        uint32_t t0, t;
        asm volatile("mov.u32 %0, %%clock;" : "=r"(t0));
        do { asm volatile("mov.u32 %0, %%clock;" : "=r"(t)); } while (t - t0 < (uint32_t)cycles);
    }
}
__device__ __forceinline__ void mbar_wait_cl(uint32_t bar, uint32_t parity) {
    uint32_t done = 0;
    for (int it = 0; it < WAIT_LIMIT && !done; it++) {
        asm volatile(
            "{\n.reg .pred p;\n"
            "mbarrier.try_wait.parity.shared::cta.b64 p, [%1], %2;\n"
            "selp.u32 %0, 1, 0, p;\n}\n" : "=r"(done) : "r"(bar), "r"(parity) : "memory");
    }
}
__device__ __forceinline__ void ldmatrix_x4(uint32_t& r0, uint32_t& r1, uint32_t& r2, uint32_t& r3, uint32_t addr) {
    asm volatile("ldmatrix.sync.aligned.m8n8.x4.shared.b16 {%0,%1,%2,%3}, [%4];"
                 : "=r"(r0), "=r"(r1), "=r"(r2), "=r"(r3) : "r"(addr));
}
__device__ __forceinline__ void cp_async16(uint32_t dst, const void* src) {
    asm volatile("cp.async.cg.shared.global [%0], [%1], 16;" :: "r"(dst), "l"(src) : "memory");
}
__device__ __forceinline__ float bf16r(float x) { return __uint_as_float(pack_bf16(0.f, x) & 0xffff0000u); }

#define DBGP(i, w, ok)
#define DBG(i, w)
#define DBGD(i, w, dep)
#define DBG_EXTRA 0
__device__ __forceinline__ void tma_load_2d_mc(uint32_t dst, const CUtensorMap* map, uint32_t bar, int c0, int c1, uint16_t mask) {
    asm volatile(
        "cp.async.bulk.tensor.2d.shared::cluster.global.mbarrier::complete_tx::bytes.multicast::cluster [%0], [%1, {%3, %4}], [%2], %5;"
        :: "r"(dst), "l"((uint64_t)map), "r"(bar), "r"(c0), "r"(c1), "h"(mask) : "memory");
}
__device__ __forceinline__ void stmatrix_x4_trans(uint32_t addr, uint32_t r0, uint32_t r1, uint32_t r2, uint32_t r3) {
    asm volatile("stmatrix.sync.aligned.m8n8.x4.trans.shared.b16 [%0], {%1, %2, %3, %4};" :: "r"(addr), "r"(r0), "r"(r1), "r"(r2), "r"(r3) : "memory");
}
__device__ __forceinline__ void stmatrix_x2_trans(uint32_t addr, uint32_t r0, uint32_t r1) {
    asm volatile("stmatrix.sync.aligned.m8n8.x2.trans.shared.b16 [%0], {%1, %2};" :: "r"(addr), "r"(r0), "r"(r1) : "memory");
}
__device__ __forceinline__ uint4 lds128(uint32_t a) {
    uint4 v; asm volatile("ld.shared.v4.u32 {%0, %1, %2, %3}, [%4];" : "=r"(v.x), "=r"(v.y), "=r"(v.z), "=r"(v.w) : "r"(a) : "memory"); return v;
}
__device__ __forceinline__ void sts128(uint32_t a, uint32_t x, uint32_t y, uint32_t z, uint32_t w) {
    asm volatile("st.shared.v4.b32 [%0], {%1, %2, %3, %4};" :: "r"(a), "r"(x), "r"(y), "r"(z), "r"(w) : "memory");
}
__device__ __forceinline__ float2 lds64f(uint32_t a) {
    float2 v; asm volatile("ld.shared.v2.f32 {%0, %1}, [%2];" : "=f"(v.x), "=f"(v.y) : "r"(a) : "memory"); return v;
}
__device__ __forceinline__ void fence_async_smem() { asm volatile("fence.proxy.async.shared::cta;" ::: "memory"); }
#define ACC16(d) "+f"(d[0]), "+f"(d[1]), "+f"(d[2]), "+f"(d[3]), "+f"(d[4]), "+f"(d[5]), "+f"(d[6]), "+f"(d[7]), "+f"(d[8]), "+f"(d[9]), "+f"(d[10]), "+f"(d[11]), "+f"(d[12]), "+f"(d[13]), "+f"(d[14]), "+f"(d[15])
template <int ND>
__device__ __forceinline__ void wgmma_rs_n32(float (&d)[ND], const uint32_t (&a)[4], uint32_t db_lo, int scale_d) {
    asm volatile(
        "{\n.reg .pred p;\n.reg .b64 db;\nsetp.ne.b32 p, %21, 0;\nmov.b64 db, {%20, 0x40000040};\n"
        "wgmma.mma_async.sync.aligned.m64n32k16.f32.bf16.bf16 {%0,%1,%2,%3,%4,%5,%6,%7,%8,%9,%10,%11,%12,%13,%14,%15}, {%16,%17,%18,%19}, db, p, 1, 1, 0;\n}\n"
        : ACC16(d) : "r"(a[0]), "r"(a[1]), "r"(a[2]), "r"(a[3]), "r"(db_lo), "r"(scale_d));
}
template <int ND>
__device__ __forceinline__ void wgmma_ss_n32(float (&d)[ND], uint32_t da_lo, uint32_t db_lo, int scale_d) {
    asm volatile(
        "{\n.reg .pred p;\n.reg .b64 da, db;\nsetp.ne.b32 p, %18, 0;\nmov.b64 da, {%16, 0x40000040};\nmov.b64 db, {%17, 0x40000040};\n"
        "wgmma.mma_async.sync.aligned.m64n32k16.f32.bf16.bf16 {%0,%1,%2,%3,%4,%5,%6,%7,%8,%9,%10,%11,%12,%13,%14,%15}, da, db, p, 1, 1, 1, 0;\n}\n"
        : ACC16(d) : "r"(da_lo), "r"(db_lo), "r"(scale_d));
}
__device__ __forceinline__ void wgmma_ss_n8(float (&d)[4], uint32_t da_lo, uint32_t db_lo, int scale_d) {
    asm volatile(
        "{\n.reg .pred p;\n.reg .b64 da, db;\nsetp.ne.b32 p, %6, 0;\nmov.b64 da, {%4, 0x40000040};\nmov.b64 db, {%5, 0x00000010};\n"
        "wgmma.mma_async.sync.aligned.m64n8k16.f32.bf16.bf16 {%0,%1,%2,%3}, da, db, p, 1, 1, 1, 0;\n}\n"
        : "+f"(d[0]), "+f"(d[1]), "+f"(d[2]), "+f"(d[3]) : "r"(da_lo), "r"(db_lo), "r"(scale_d));
}

#define SCHED_FENCE()
__device__ __forceinline__ void wgmma_ss_n32_p(float (&d)[16], uint32_t da_lo, uint32_t db_lo, int scale_d) {
    asm volatile(
        "{\n.reg .pred p;\n.reg .b64 da, db;\nsetp.ne.b32 p, %18, 0;\nmov.b64 da, {%16, 0x40000040};\nmov.b64 db, {%17, 0x00000030};\n"
        "wgmma.mma_async.sync.aligned.m64n32k16.f32.bf16.bf16 {%0,%1,%2,%3,%4,%5,%6,%7,%8,%9,%10,%11,%12,%13,%14,%15}, da, db, p, 1, 1, 1, 0;\n}\n"
        : ACC16(d) : "r"(da_lo), "r"(db_lo), "r"(scale_d));
}

#define ACC20(d) ACC16(d), "+f"(d[16]), "+f"(d[17]), "+f"(d[18]), "+f"(d[19])
#define ACC20_STR "{%0,%1,%2,%3,%4,%5,%6,%7,%8,%9,%10,%11,%12,%13,%14,%15,%16,%17,%18,%19}"
__device__ __forceinline__ void wgmma_rs_n40(float (&d)[20], const uint32_t (&a)[4], uint32_t db_lo, int scale_d) {
    asm volatile(
        "{\n.reg .pred p;\n.reg .b64 db;\nsetp.ne.b32 p, %25, 0;\nmov.b64 db, {%24, 0x40000040};\n"
        "wgmma.mma_async.sync.aligned.m64n40k16.f32.bf16.bf16 " ACC20_STR ", {%20,%21,%22,%23}, db, p, 1, 1, 0;\n}\n"
        : ACC20(d) : "r"(a[0]), "r"(a[1]), "r"(a[2]), "r"(a[3]), "r"(db_lo), "r"(scale_d));
}
template <int TA, int SBO>
__device__ __forceinline__ void wgmma_ss_n40(float (&d)[20], uint32_t da_lo, uint32_t db_lo, int scale_d) {
    asm volatile(
        "{\n.reg .pred p;\n.reg .b64 da, db;\nsetp.ne.b32 p, %22, 0;\nmov.b64 da, {%20, %23};\nmov.b64 db, {%21, 0x40000040};\n"
        "wgmma.mma_async.sync.aligned.m64n40k16.f32.bf16.bf16 " ACC20_STR ", da, db, p, 1, 1, %24, 0;\n}\n"
        : ACC20(d) : "r"(da_lo), "r"(db_lo), "r"(scale_d), "n"(0x40000000 + SBO / 16), "n"(TA));
}

#define PT(i, th)
struct ChainParams {
    CUtensorMap mapW[3];
    CUtensorMap mapX;
    CUtensorMap mapC;
};
constexpr int CH_BLOCK = 384;
constexpr int CO_WO = 0;
constexpr int CH_XC = 5120, CH_XP = 8 * CH_XC;
constexpr int CO_XB = 65536;
constexpr int CO_OB = CO_XB + 2 * CH_XP;
constexpr int CO_P = CO_OB + 8192;
constexpr int CO_LS = CO_P + 3072;
constexpr int CO_SC = CO_LS + 8 * 1280;
constexpr int CH_TW = 6144 + 8192;
constexpr int CO_T = 21 * 8192;
constexpr int CO_WA = CO_T + 6144;
constexpr int CO_ST = CO_T + 3 * CH_TW + 6144;
constexpr int CO_OWN = CO_ST + 4096, CO_OWN2 = CO_SC + 1536;
constexpr int CO_BAR = CO_OWN + 4096;
constexpr int CH_SMEM = CO_BAR + 256 + DBG_EXTRA;
#define CH_NSM 4
static_assert(CO_OWN2 + 1024 <= CO_T && CH_NSM <= 4, "smem layout");
#define CH_POLL_DELAY 0
#define CH_VPOS 2
#define CH_OW 8
#define CH_OF 12
#define CH_Q1 0
#define CH_VA 9
#define CH_SPOS 0
#define CH_LSW 1
#define CH_QE 32
#define CH_KE 32
#define CH_QD 0
#define CH_GAP 45
#define CH_HA 15
#define CH_LD 4
#define CH_TWP 0
#define CH_CHAINS 4

constexpr float CH_SC = 0.08838834764831845f * 1.4426950408889634f;
__device__ __forceinline__ uint32_t pin(uint32_t v) { return __shfl_sync(0xffffffff, v, threadIdx.x & 31); }

__global__ void __cluster_dims__(8, 1, 1) __launch_bounds__(CH_BLOCK, 1)
chain_kernel(const __grid_constant__ ChainParams P, const bf16* __restrict__ mem0, const bf16* __restrict__ Wo, const bf16* __restrict__ x,
             const bf16* __restrict__ gate_w) {
    extern __shared__ uint8_t smem_raw[];
    const int tid = threadIdx.x, warp = __shfl_sync(0xffffffff, tid >> 5, 0), lane = tid & 31;
    const int rank = (int)cluster_ctarank();
    constexpr uint32_t sd = 1024;
    const uint32_t sb = ((uint32_t)rank << 24) + sd;
    if (smem_u32(smem_raw) != sb) __trap();
    const int C = blockIdx.x >> 3;
    const int h = C * 4 + (rank >> 1);
    const int qd = lane >> 2, qc = lane & 3;
    const int t4 = warp & 3, wg = warp >> 2;
    pdl_launch_dependents();
    TS_BEGIN(2);
    PT(0, 0);
    const uint32_t bar_mem = sb + CO_BAR, bar_o = bar_mem + 32, bar_sc = bar_o + 32, bar_x = bar_sc + 8, bar_l = bar_x + 16, bar_w = bar_l + 8;
    if (tid == 0) {
        for (int j = 0; j < 15; j++) mbar_init(bar_mem + 8 * j, 1);
        sts128(bar_mem + 128, 0xffff0000u, 0u, 0u, 0u);
        asm volatile("fence.mbarrier_init.release.cluster;" ::: "memory");
    }
    __syncthreads();
    auto chunk = [&](int i) { return (uint32_t)((rank - (i >> 1) - 4 * (i & 1)) & 7); };
    if ((tid & 127) == 0) {
        mbar_expect_tx(bar_w + 8 * wg, 65536);
        for (int i = 0; i < 8; i++)
            tma_load_2d(sb + (i ? (wg * 7 + i - 1) * 8192 : CO_WA + wg * CH_TW), &P.mapW[wg], bar_w + 8 * wg, h * HD + (rank & 1) * 64, chunk(i) * 64);
    }
    PT(1, 0);
    {
        for (int i = tid; i < 512; i += CH_BLOCK) asm volatile("prefetch.global.L2 [%0];" :: "l"(Wo + (size_t)(C * 512 + i) * DM + rank * 64));
        if (tid < 64) asm volatile("prefetch.global.L2 [%0];" :: "l"(x + (size_t)tid * DM + rank * 64));
    }
    if (tid < 256) {
        const int r = blockIdx.x * 32 + (tid >> 3);
        float sum = 0.f;
#pragma unroll
        for (int c = 0; c < 8; c++) {
            const int col = c * 64 + (tid & 7) * 8;
            const uint4 xv = __ldg(reinterpret_cast<const uint4*>(x + (size_t)r * DM + col));
            const uint4 gv = __ldg(reinterpret_cast<const uint4*>(gate_w + col));
            const bf16* xp = reinterpret_cast<const bf16*>(&xv);
            const bf16* gp = reinterpret_cast<const bf16*>(&gv);
#pragma unroll
            for (int e = 0; e < 8; e++) sum += bf16r(__bfloat162float(xp[e]) * __bfloat162float(gp[e]));
        }
        sum += __shfl_xor_sync(0xffffffff, sum, 1);
        sum += __shfl_xor_sync(0xffffffff, sum, 2);
        sum += __shfl_xor_sync(0xffffffff, sum, 4);
        if ((tid & 7) == 0) g_gate[r] = bf16r(1.f / (1.f + __expf(-bf16r(sum))));
        *reinterpret_cast<uint2*>(g_xbuf + (tid >> 7) * 16384 + (size_t)rank * 2048 + C * 256 + (tid & 127) * 2) = make_uint2(~0u, ~0u);
        asm volatile("bar.sync 1, 256;" ::: "memory");
        if (tid == 32) signal_ctr_generic(CT_GATE);
    }
    const uint32_t wfrag = (((lane >> 4) << 3) + (lane & 7)) * 128 + (((t4 * 2 + ((lane >> 3) & 1)) ^ (lane & 7)) << 4);
    const uint32_t aO = pin(sb + wg * CH_TW + wfrag);
    const uint32_t aL = pin(sb + lane * 16);
    uint32_t w[32][4];
    PT(2, 0);
    mbar_wait(bar_w + 8 * wg, 0);
    PT(3, 0); PT(4, 256);
#pragma unroll
    for (int e = CH_NSM; e < 32; e++)
        ldmatrix_x4_trans(w[e][0], w[e][1], w[e][2], w[e][3], e < 4 ? aO + CO_WA + e * 2048 : sb + wg * 7 * 8192 + wfrag + (e - 4) * 2048);
    fence_async_smem();
    __syncthreads();
    PT(5, 0);
    if (tid == 0) {
        fence_async_smem();
        for (int b = 0; b < 2; b++) {
            mbar_expect_tx(bar_x + 8 * b, 32768);
            for (int i = 0; i < 8; i++) tma_load_2d(sb + CO_XB + b * CH_XP + i * CH_XC, &P.mapX, bar_x + 8 * b, i * 64, b * SEGL);
        }
    }
#pragma unroll 2
    for (int i = tid; i < 512 * 4; i += CH_BLOCK) {
        const int r = i >> 2, cg = i & 3, ks = r >> 4, kp = r & 15;
        const int src = (rank - (ks >> 2)) & 7;
        const uint4* p = reinterpret_cast<const uint4*>(Wo + (size_t)(C * 512 + src * 64 + (ks & 3) * 16 + (kp >> 2) * 2 + (kp & 1) + (kp & 2) * 4) * DM + rank * 64 + cg * 16);
        const uint4 u0 = __ldg(p), u1 = __ldg(p + 1);
        const uint32_t a = sb + CO_WO + r * 128;
        sts128(a + (((cg * 2) ^ (r & 7)) << 4), __byte_perm(u0.x, u0.y, 0x5410), __byte_perm(u0.z, u0.w, 0x5410), __byte_perm(u1.x, u1.y, 0x5410), __byte_perm(u1.z, u1.w, 0x5410));
        sts128(a + (((cg * 2 + 1) ^ (r & 7)) << 4), __byte_perm(u0.x, u0.y, 0x7632), __byte_perm(u0.z, u0.w, 0x7632), __byte_perm(u1.x, u1.y, 0x7632), __byte_perm(u1.z, u1.w, 0x7632));
    }
#pragma unroll 1
    for (int i = tid; i < 512; i += CH_BLOCK) {
        const int n = i >> 6, c = i & 63;
        const uint4 u = __ldg(reinterpret_cast<const uint4*>(mem0 + n * DM + c * 8));
        sts128(sb + CO_XB + (c >> 3) * CH_XC + 4096 + n * 128 + (((c & 7) ^ n) << 4), u.x, u.y, u.z, u.w);
    }
    if (tid < 128) sts128(sb + CO_T + (2 + (tid >> 6)) * CH_TW + 5120 + (tid & 63) * 16, 0u, 0u, 0u, 0u);
    else if (tid < 160) sts128(sb + CO_P + ((tid >> 3) & 3) * 768 + 640 + (tid & 7) * 16, 0u, 0u, 0u, 0u);
    fence_async_smem();
    TS_END(6);
    PT(6, 0);
    auto pass = [&](auto& d, int b, int e0, int e1) {
        const uint32_t lo = desc_lo(sd + CO_XB + b * CH_XP, 16);
        wgmma_fence();
#pragma unroll
        for (int e = 0; e < 32; e++) if (e >= e0 && e < e1) {
            const uint32_t db = lo + chunk(e >> 2) * (CH_XC / 16) + (e & 3) * 2, da = desc_lo(sd + CO_WA + wg * CH_TW + e * 2048, 16);
            if constexpr (sizeof(d) == 64) { if (e < CH_NSM) wgmma_ss_n32(d, da, db, e != 0); else wgmma_rs_n32(d, w[e], db, e != 0); }
            else { if (e < CH_NSM) wgmma_ss_n40<1, 1024>(d, da, db, e != 0); else wgmma_rs_n40(d, w[e], db, e != 0); }
        }
        wgmma_commit();
    };
    auto store32 = [&](const float* d, uint32_t a) {
        stmatrix_x4_trans(a, pack_bf16(d[0], d[1]), pack_bf16(d[2], d[3]), pack_bf16(d[4], d[5]), pack_bf16(d[6], d[7]));
        stmatrix_x4_trans(a + 2048, pack_bf16(d[8], d[9]), pack_bf16(d[10], d[11]), pack_bf16(d[12], d[13]), pack_bf16(d[14], d[15]));
    };
    auto remote = [](uint32_t a, uint32_t r) { return mapa_u32(a, r); };
    auto scores = [&](float (&d)[20], auto sbo, uint32_t q) {
        wgmma_fence();
#pragma unroll
        for (int ks = 0; ks < 4; ks++) wgmma_ss_n40<0, decltype(sbo)::value>(d, desc_lo(sd + CO_T + q, 16) + ks * 2, desc_lo(sd + CO_T + CH_TW, 16) + ks * 2, ks != 0);
        wgmma_commit();
    };
    auto send_scores = [&](const float (&d)[20], uint32_t a, uint32_t bar, bool p0, bool p1, bool p2) {
        asm volatile("{\n.reg .pred p0, p1, p2;\nsetp.ne.b32 p0, %13, 0;\nsetp.ne.b32 p1, %14, 0;\nsetp.ne.b32 p2, %15, 0;\n"
                     "@p0 st.async.weak.shared::cluster.mbarrier::complete_tx::bytes.v4.f32 [%0], {%3, %4, %5, %6}, [%2];\n"
                     "@p1 st.async.weak.shared::cluster.mbarrier::complete_tx::bytes.v4.f32 [%0 + 512], {%7, %8, %9, %10}, [%2];\n"
                     "@p2 st.async.weak.shared::cluster.mbarrier::complete_tx::bytes.v2.f32 [%1], {%11, %12}, [%2];\n}"
                     :: "r"((aL + a) ^ (1u << 24)), "r"((aL + a + 1024 - lane * 8) ^ (1u << 24)), "r"(bar ^ (1u << 24)), "f"(d[0]), "f"(d[1]), "f"(d[4]), "f"(d[5]),
                        "f"(d[8]), "f"(d[9]), "f"(d[12]), "f"(d[13]), "f"(d[16]), "f"(d[17]), "r"((int)p0), "r"((int)p1), "r"((int)p2) : "memory");
    };
    auto own_scores = [&](const float (&d)[20], float (&v)[10]) {
#pragma unroll
        for (int j = 0; j < 5; j++) { v[2 * j] = d[4 * j]; v[2 * j + 1] = d[4 * j + 1]; }
    };
    auto add_scores = [&](uint32_t a, float (&v)[10], int dense) {
        const uint4 a0 = lds128(aL + a), a1 = lds128(aL + a + 512);
        const float2 a2 = lds64f(aL + a + 1024 - dense * lane * 8);
        v[0] += __uint_as_float(a0.x); v[1] += __uint_as_float(a0.y); v[2] += __uint_as_float(a0.z); v[3] += __uint_as_float(a0.w);
        v[4] += __uint_as_float(a1.x); v[5] += __uint_as_float(a1.y); v[6] += __uint_as_float(a1.z); v[7] += __uint_as_float(a1.w);
        v[8] += a2.x; v[9] += a2.y;
    };
    auto row_max = [&](const float (&v)[10]) {
        float mx = fmaxf(fmaxf(fmaxf(v[0], v[1]), fmaxf(v[2], v[3])), fmaxf(fmaxf(v[4], v[5]), fmaxf(v[6], v[7])));
        mx = fmaxf(mx, fmaxf(v[8], v[9]));
        mx = fmaxf(mx, __shfl_xor_sync(0xffffffff, mx, 1));
        return fmaxf(mx, __shfl_xor_sync(0xffffffff, mx, 2)) * CH_SC;
    };
    auto signal_ctx = [&](int m0, int m1) {
        asm volatile("fence.proxy.async;" ::: "memory");
        __threadfence();
        for (int m = m0; m < m1; m++) asm volatile("red.relaxed.gpu.global.add.u32 [%0], 1;" :: "l"(&g_ctr[CT_CB + m]) : "memory");
    };
    auto signal_step = [](int s) { return s == 33 || s == 49 || s == 57 || s == 61; };
    if (remote(bar_l, rank ^ 1) != (bar_l ^ (1u << 24))) __trap();
    mbar_wait(bar_x, 0);
    PT(7, 0);
    if (wg < 2) {
        float d[16];
        pass(d, 0, 0, 32);
        wgmma_wait<0>();
        store32(d, aO + CO_T);
    }
    if (tid == 128) mbar_expect_tx(bar_sc, 2048);
    __syncthreads();
    PT(8, 0);
    cluster_sync_all();
    TS_BEGIN(5);
    PT(9, 0);

    if (wg < 2) {
        const uint32_t aM = pin(sb + CO_XB + 4096 + (lane & 7) * 128 + (((lane >> 3) ^ (lane & 7)) << 4));
        auto mem_proj = [&](int s) {
            const uint32_t par = s & 1;
            float acc[CH_CHAINS][4];
#pragma unroll
            for (int i = 0; i < CH_CHAINS; i++) acc[i][0] = acc[i][1] = acc[i][2] = acc[i][3] = 0.f;
            const uint32_t am = aM + par * CH_XP;
            uint32_t b[CH_LD][4], ok[4] = {1, 1, 1, 1}, a0 = am, a1 = am ^ 64;
            auto load = [&](int i) {
                if (i == 12) DBG(13, 0);
                if (i && !(i & 3)) { a0 = ok[i >> 2] ? am : aL; a1 = a0 ^ 64; }
                uint32_t* r = b[i % CH_LD];
                ldmatrix_x4(r[0], r[1], r[2], r[3], ((i & 1) ? a1 : a0) + chunk(i >> 1) * CH_XC);
                if ((i & 3) == CH_TWP && i < 12) ok[(i >> 2) + 1] = mbar_try(bar_mem + 8 * ((i >> 2) + 1), par ^ 1);
            };
#pragma unroll
            for (int e = 0; e < CH_NSM; e++) ldmatrix_x4_trans(w[e][0], w[e][1], w[e][2], w[e][3], aO + CO_WA + e * 2048);
            mbar_wait(bar_mem, par ^ 1);
            DBG(11, 0);
            bool done = false;
#pragma unroll
            for (int i = 0; i < CH_LD; i++) load(i);
#pragma unroll
            for (int i = 0; i < 16; i++) {
                mma_16816(acc[(2 * i) % CH_CHAINS], w[2 * i][0], w[2 * i][1], w[2 * i][2], w[2 * i][3], b[i % CH_LD][0], b[i % CH_LD][1]);
                mma_16816(acc[(2 * i + 1) % CH_CHAINS], w[2 * i + 1][0], w[2 * i + 1][1], w[2 * i + 1][2], w[2 * i + 1][3], b[i % CH_LD][2], b[i % CH_LD][3]);
                if (i + CH_LD < 16) load(i + CH_LD);
                if (i == 12 - CH_LD) done = __all_sync(0xffffffff, ok[1] & ok[2] & ok[3]);
                if (i == CH_HA) asm volatile("{\n.reg .pred p;\nsetp.ne.b32 p, %0, 0;\n@p bar.arrive 5, 384;\n}" :: "r"((int)done) : "memory");
            }
#pragma unroll
            for (int i = 0; i < 4; i++) {
                if (CH_CHAINS == 4) { acc[0][i] += acc[2 % CH_CHAINS][i]; acc[1][i] += acc[3 % CH_CHAINS][i]; }
                if (CH_CHAINS == 3) acc[0][i] += acc[2 % CH_CHAINS][i];
            }
            const uint32_t r0 = pack_bf16(acc[0][0] + acc[1][0], acc[0][1] + acc[1][1]);
            const uint32_t r1 = pack_bf16(acc[0][2] + acc[1][2], acc[0][3] + acc[1][3]);
            DBGD(40 + warp, warp, r0 ^ r1);
            stmatrix_x2_trans(aO + CO_T + 4096, r0, r1);
            fence_async_smem();
            return done;
        };
#pragma unroll 1
        for (int s = 0; s < NSEG; s++) {
            const uint32_t par = s & 1;
#pragma unroll 1
            for (int it = 0; it < WAIT_LIMIT / 64; it++) if (mem_proj(s)) break;
            if (wg == 0) {
                asm volatile("bar.arrive 1, 256;" ::: "memory");
                if (s == NSEG - 1) break;
                if (tid == 96) {
#pragma unroll
                    for (int j = 0; j < 4; j++) { mbar_expect_tx(bar_mem + 8 * j, 2048); if (j < 2) mbar_expect_tx(bar_o + 8 * j, 4096); }
                }
                __syncwarp();
                uint32_t* wp = g_xbuf + (size_t)rank * 2048 + C * 256 + qc * 64 + t4 * 8 + qd;
                asm volatile("st.relaxed.gpu.global.u32 [%0], %1;" :: "l"(wp + ((s + 2) & 3) * 16384), "r"(~0u) : "memory");
                asm volatile("st.relaxed.gpu.global.u32 [%0], %1;" :: "l"(wp + ((s + 2) & 3) * 16384 + 32), "r"(~0u) : "memory");
                mbar_wait(bar_x + 8 * (par ^ 1), ((s + 1) >> 1) & 1);
                asm volatile("bar.sync 7, 384;" ::: "memory");
                float d[16];
                if (CH_Q1 > 0) pass(d, par ^ 1, 0, CH_Q1);
                float c[4];
                const uint32_t alo = desc_lo(sd + CO_WO, 16), blo = desc_lo(sd + CO_OB, 128);
                mbar_wait_cl(bar_o, par);
                DBG(16, 0);
                fence_async_smem();
                wgmma_fence();
#pragma unroll
                for (int i = 0; i < 32; i++) {
                    wgmma_ss_n8(c, alo + i * 128, blo + i * 16, i != 0);
                    if (i == CH_OW) mbar_wait_cl(bar_o + 8, par);
                    if (i == CH_OF) fence_async_smem();
                }
                wgmma_commit();
                wgmma_wait<0>();
                asm volatile("st.relaxed.gpu.global.u32 [%0], %1;" :: "l"(wp + (s & 3) * 16384), "r"(pack_bf16(c[0], c[2])) : "memory");
                asm volatile("st.relaxed.gpu.global.u32 [%0], %1;" :: "l"(wp + (s & 3) * 16384 + 32), "r"(pack_bf16(c[1], c[3])) : "memory");
                asm volatile("bar.arrive 6, 256;" ::: "memory");
                pace(CH_QD);
                asm volatile("bar.arrive 4, 384;" ::: "memory");
                DBG(8, 0);
                pass(d, par ^ 1, CH_Q1, CH_QE);
                DBG(21, 0);
                if (tid == 0 && s + 2 < NSEG) {
                    mbar_expect_tx(bar_x + 8 * par, 32768);
                    tma_load_2d_mc(sb + CO_XB + par * CH_XP + rank * CH_XC, &P.mapX, bar_x + 8 * par, rank * 64, (s + 2) * SEGL, (uint16_t)0xff);
                }
                __syncwarp();
                asm volatile("bar.sync 9, 256;" ::: "memory");
                wgmma_wait<0>();
                DBG(0, 0);
                store32(d, aO + CO_T);
                DBG(22, 0);
            } else {
                asm volatile("bar.sync 1, 256;" ::: "memory");
                float d[20];
                scores(d, std::integral_constant<int, 0>(), 4096);
                asm volatile("bar.arrive 8, 256;" ::: "memory");
                const uint32_t sca = pin((aL + CO_SC + min(t4, 2) * 512) ^ (1u << 24)), scb = pin(bar_sc ^ (1u << 24));
                wgmma_wait<0>();
                if (s == NSEG - 1) break;
                {
                    const bool w0 = t4 == 0, w1 = t4 == 1;
                    asm volatile("st.async.weak.shared::cluster.mbarrier::complete_tx::bytes.v4.f32 [%0], {%2, %3, %4, %5}, [%1];"
                                 :: "r"(sca), "r"(scb), "f"(w0 ? d[0] : w1 ? d[8] : d[16]), "f"(w0 ? d[1] : w1 ? d[9] : d[17]),
                                    "f"(w0 ? d[4] : d[12]), "f"(w0 ? d[5] : d[13]) : "memory");
                }
                DBG(3, 4);
                const uint32_t vaddr = pin(sb + CO_T + (2 + par) * CH_TW + (lane & 15) * 128 + (((t4 * 2 + (lane >> 4)) ^ (lane & 7)) << 4));
                const uint32_t dsta = pin(sb + CO_OB + t4 * 256 + (qc >> 1) * 128 + qd * 16 + (qc & 1) * 8);
                uint32_t vb[3][4];
                auto load_v = [&]() {
                    asm volatile("bar.sync 3, 256;" ::: "memory");
#pragma unroll
                    for (int k = 0; k < 3; k++) ldmatrix_x4_trans(vb[k][0], vb[k][1], vb[k][2], vb[k][3], vaddr + k * 2048);
                };
                mbar_wait_cl(bar_sc, par);
                DBG(4, 4);
                float v[10];
                own_scores(d, v);
                add_scores(CO_SC, v, 0);
                const float mx = row_max(v);
                if (CH_VPOS == 2) load_v();
#pragma unroll
                for (int j = 0; j < 10; j++) v[j] = ex2f(fmaf(v[j], CH_SC, -mx));
                uint32_t p[5];
#pragma unroll
                for (int j = 0; j < 5; j++) p[j] = pack_bf16(v[2 * j], v[2 * j + 1]);
                if (CH_VPOS == 3) load_v();
                DBG(19, 4);
                float c0[4] = {0.f, 0.f, 0.f, 0.f}, c1[4] = {0.f, 0.f, 0.f, 0.f}, cs[4] = {0.f, 0.f, 0.f, 0.f};
#pragma unroll
                for (int k = 0; k < 3; k++) {
                    const uint32_t p0 = p[2 * k], p1 = k < 2 ? p[2 * k + 1] : 0u;
                    mma_16816(cs, p0, 0u, p1, 0u, 0x3f803f80u, 0x3f803f80u);
                    mma_16816(c0, p0, 0u, p1, 0u, vb[k][0], vb[k][1]);
                    mma_16816(c1, p0, 0u, p1, 0u, vb[k][2], vb[k][3]);
                }
                float inv;
                asm volatile("rcp.approx.ftz.f32 %0, %1;" : "=f"(inv) : "f"(cs[0]));
                const uint32_t b0 = pack_bf16(c0[0] * inv, c0[1] * inv), b1 = pack_bf16(c1[0] * inv, c1[1] * inv);
                DBG(20, 4);
#pragma unroll
                for (int i = 0; i < 8; i++) {
                    const int dr = (rank + i) & 7;
                    st_async_v2(remote(dsta + i * 1024, dr), b0, b1, remote(bar_o + 8 * (i >> 2), dr));
                    if (i == 0) asm volatile("bar.arrive 7, 384;" ::: "memory");
                }
                DBG(5, 4);
                if (tid == 128) mbar_expect_tx(bar_sc, 2048);
                __syncwarp();
                mbar_wait(bar_x + 8 * (par ^ 1), ((s + 1) >> 1) & 1);
                asm volatile("bar.sync 4, 384;" ::: "memory");
                float dk[16];
                pass(dk, par ^ 1, 0, CH_KE);
                if (tid == 128 && signal_step(s)) signal_ctx((2 * s - 66) >> 2, s >> 2);
                __syncwarp();
                DBG(1, 4);
                wgmma_wait<0>();
                DBG(2, 4);
                store32(dk, aO + CO_T);
                DBG(29, 4);
            }
        }
        PT(10, 0);
    } else {
        auto store_ctx = [&](int s) {
            if (tid == 256) {
                tma_store_2d(&P.mapC, sb + CO_ST, (rank & 1) * 64, h * SEQ + s * SEGL);
                asm volatile("cp.async.bulk.commit_group;" ::: "memory");
            }
        };
        float gs;
        auto load_gate = [&](int s) { asm volatile("ld.global.cg.f32 %0, [%1];" : "=f"(gs) : "l"(g_gate + s * SEGL + t4 * 8 + qd) : "memory"); };
        auto softmax = [&](int s) {
            float v[10];
            {
                const uint4 a0 = lds128(aL + CO_OWN + t4 * 1024), a1 = lds128(aL + CO_OWN + t4 * 1024 + 512);
                const float2 a2 = lds64f(aL + CO_OWN2 + t4 * 256 - lane * 8);
                v[0] = __uint_as_float(a0.x); v[1] = __uint_as_float(a0.y); v[2] = __uint_as_float(a0.z); v[3] = __uint_as_float(a0.w);
                v[4] = __uint_as_float(a1.x); v[5] = __uint_as_float(a1.y); v[6] = __uint_as_float(a1.z); v[7] = __uint_as_float(a1.w);
                v[8] = a2.x; v[9] = a2.y;
            }
            mbar_wait_cl(bar_l, s & 1);
            add_scores(CO_LS + (s & 1) * 5120 + t4 * 1280, v, 1);
            const int lim = t4 * 8 + qd - 2 * qc;
#pragma unroll
            for (int j = 0; j < 8; j++) if ((j >> 1) * 8 + (j & 1) > lim) v[j] = -INFINITY;
            const float mx = row_max(v);
#pragma unroll
            for (int j = 0; j < 10; j++) v[j] = ex2f(fmaf(v[j], CH_SC, -mx));
            float sum = (((v[0] + v[1]) + (v[2] + v[3])) + ((v[4] + v[5]) + (v[6] + v[7]))) + (v[8] + v[9]);
            sum += __shfl_xor_sync(0xffffffff, sum, 1);
            sum += __shfl_xor_sync(0xffffffff, sum, 2);
            asm("rcp.approx.ftz.f32 %0, %0;" : "+f"(sum));
            sum *= 1.f - gs;
            const uint32_t pa = aL + CO_P + t4 * 768;
            stmatrix_x4(pa, pack_bf16(v[0] * sum, v[1] * sum), pack_bf16(v[2] * sum, v[3] * sum), pack_bf16(v[4] * sum, v[5] * sum), pack_bf16(v[6] * sum, v[7] * sum));
            asm volatile("stmatrix.sync.aligned.m8n8.x1.shared.b16 [%0], {%1};" :: "r"(pa + 512), "r"(pack_bf16(v[8] * sum, v[9] * sum)) : "memory");
        };
        auto pv = [&](float (&dc)[16], int s) {
            wgmma_fence();
#pragma unroll
            for (int ks = 0; ks < 3; ks++) wgmma_ss_n32_p(dc, desc_lo(sd + CO_T + (2 + (s & 1)) * CH_TW + ks * 2048, 16), desc_lo(sd + CO_P + ks * 256, 128), ks != 0);
            wgmma_commit();
        };
        const uint8_t* mkp = smem_raw + CO_BAR + 128;
        asm volatile("" : "+l"(mkp));
        wait_ctr(CT_GATE, 64u);
        load_gate(0);
#pragma unroll 1
        for (int s = 0; s < NSEG; s++) {
            const uint32_t par = s & 1;
            const bool last = s == NSEG - 1;
            softmax(s - 1);
            load_gate(s);
            DBG(7, 8);
#pragma unroll 1
            for (int it = 0; it < WAIT_LIMIT / 64; it++)
                if (mbar_try(bar_mem, par ^ 1) & mbar_try(bar_mem + 8, par ^ 1) & mbar_try(bar_mem + 16, par ^ 1) & mbar_try(bar_mem + 24, par ^ 1)) break;
            fence_async_smem();
            asm volatile("cp.async.bulk.wait_group.read 0;" ::: "memory");
            asm volatile("bar.sync 5, 384;" ::: "memory");
            DBG(23, 8);
            float d[20];
            pass(d, par, 0, CH_VA);
            asm volatile("bar.sync 8, 256;" ::: "memory");
            pass(d, par, CH_VA, 32);
            if (signal_step(s)) asm volatile("cp.async.bulk.wait_group 0;" ::: "memory");
            wgmma_wait<0>();
            stmatrix_x2_trans(aO + par * CH_TW + CO_T + 4096, pack_bf16(d[16], d[17]), pack_bf16(d[18], d[19]));
            store32(d, aO + par * CH_TW + CO_T);
            DBG(24, 8);
            if (!last) asm volatile("bar.arrive 3, 256;\nbar.sync 7, 384;" ::: "memory");
            {
                float dc[16];
                pv(dc, s + 1);
                wgmma_wait<0>();
                store32(dc, aO - 2 * CH_TW + CO_ST);
            }
            scores(d, std::integral_constant<int, 512>(), 0);
            asm volatile("{\n.reg .pred p;\nsetp.eq.s32 p, %1, 256;\n@p mbarrier.arrive.expect_tx.shared::cta.b64 _, [%0], 4096;\n}" :: "r"(bar_l), "r"(tid) : "memory");
            wgmma_wait<0>();
            sts128(aL + CO_OWN + t4 * 1024, __float_as_uint(d[0]), __float_as_uint(d[1]), __float_as_uint(d[4]), __float_as_uint(d[5]));
            sts128(aL + CO_OWN + t4 * 1024 + 512, __float_as_uint(d[8]), __float_as_uint(d[9]), __float_as_uint(d[12]), __float_as_uint(d[13]));
            asm volatile("st.shared.v2.f32 [%0], {%1, %2};" :: "r"(aL + CO_OWN2 + t4 * 256 - lane * 8), "f"(d[16]), "f"(d[17]) : "memory");
            if (CH_LSW && !last) mbar_wait_cl(bar_o + 8, par);
            send_scores(d, CO_LS + par * 5120 + t4 * 1280, bar_l, true, t4 >= 2, true);
            DBG(6, 8);
            fence_async_smem();
            asm volatile("bar.sync 2, 128;" ::: "memory");
            if (s > 0) store_ctx(s - 1);
            __syncwarp();
            if (last) break;
            asm volatile("bar.arrive 4, 384;\nbar.arrive 9, 256;\nbar.sync 6, 256;" ::: "memory");
            const uint2* xb = reinterpret_cast<const uint2*>(g_xbuf + (s & 3) * 16384 + (size_t)rank * 2048 + t4 * 64) + lane;
            uint2 p[8], q[8];
            pace(CH_POLL_DELAY);
#pragma unroll
            for (int k = 0; k < 8; k++)
                asm volatile("ld.relaxed.gpu.global.v2.u32 {%0, %1}, [%2];" : "=r"(p[k].x), "=r"(p[k].y) : "l"(xb + k * 128) : "memory");
            DBG(17, 8);
            {
                uint32_t z;
                asm volatile("mov.u32 %0, %%clock;" : "=r"(z) :: "memory");
#pragma unroll
                for (int i = 0; i < CH_GAP; i++) asm volatile("mul.lo.u32 %0, %0, %0;" : "+r"(z));
                asm volatile("and.b32 %0, %0, %1;" : "+r"(z) : "r"(s >> 10));
                xb += z;
            }
#pragma unroll
            for (int k = 0; k < 8; k++)
                asm volatile("ld.relaxed.gpu.global.v2.u32 {%0, %1}, [%2];" : "=r"(q[k].x), "=r"(q[k].y) : "l"(xb + k * 128) : "memory");
            uint32_t m0, m1, mk;
            asm volatile("ld.relaxed.gpu.u32 %0, [%1];" : "=r"(mk) : "l"(mkp) : "memory");
            auto sum = [&](const uint2 (&p)[8]) {
                auto lo = [&](uint32_t u) { return __uint_as_float(u * (0u - mk)); };
                auto hi = [&](uint32_t u) { return __uint_as_float(u & mk); };
                const float s0 = ((lo(p[0].x) + lo(p[1].x)) + (lo(p[2].x) + lo(p[3].x))) + ((lo(p[4].x) + lo(p[5].x)) + (lo(p[6].x) + lo(p[7].x)));
                const float s1 = ((lo(p[0].y) + lo(p[1].y)) + (lo(p[2].y) + lo(p[3].y))) + ((lo(p[4].y) + lo(p[5].y)) + (lo(p[6].y) + lo(p[7].y)));
                m0 = pack_bf16(s0, ((hi(p[0].x) + hi(p[1].x)) + (hi(p[2].x) + hi(p[3].x))) + ((hi(p[4].x) + hi(p[5].x)) + (hi(p[6].x) + hi(p[7].x))));
                m1 = pack_bf16(s1, ((hi(p[0].y) + hi(p[1].y)) + (hi(p[2].y) + hi(p[3].y))) + ((hi(p[4].y) + hi(p[5].y)) + (hi(p[6].y) + hi(p[7].y))));
                uint32_t ok;
                asm volatile("{\n.reg .pred p;\nsetp.num.f32 p, %1, %2;\nvote.sync.all.pred p, p, 0xffffffff;\nselp.u32 %0, 1, 0, p;\n}" : "=r"(ok) : "f"(s0), "f"(s1));
                return ok;
            };
            if (!sum(p)) {
                DBG(12, 8);
#pragma unroll 1
                for (int it = 0; it < WAIT_LIMIT / 4; it++) {
                    if (sum(q)) break;
                    uint32_t bad = 0;
#pragma unroll
                    for (int k = 0; k < 8; k++) bad |= (max(q[k].x, q[k].y) == ~0u ? 1u : 0u) << k;
                    if (__all_sync(0xffffffff, bad == 0u)) break;
                    if (it == 0) DBG(14, 8);
                    if (it == 1) DBG(15, 8);
#pragma unroll
                    for (int k = 0; k < 8; k++)
                        if (bad & (1u << k))
                            asm volatile("ld.relaxed.gpu.global.v2.u32 {%0, %1}, [%2];" : "=r"(q[k].x), "=r"(q[k].y) : "l"(xb + k * 128) : "memory");
                }
            }
            DBG(9, 8);
            const int row = t4 * 2 + (lane >> 4);
            const uint32_t dsta = sb + CO_XB + (par ^ 1) * CH_XP + rank * CH_XC + 4096 + row * 128 + ((((lane & 15) >> 1) ^ row) << 4) + (lane & 1) * 8;
#pragma unroll
            for (int i = 0; i < 8; i++) {
                const int dr = (rank + (i & 1) * 4 + (i >> 1)) & 7;
                st_async_v2(remote(dsta, dr), m0, m1, remote(bar_mem + 8 * (i >> 1), dr));
            }
            if (s == 1000000) {
#pragma unroll
                for (int k = 0; k < 8; k++) asm volatile("st.volatile.shared.v2.u32 [%0], {%1, %2};" :: "r"(s), "r"(q[k].x), "r"(q[k].y) : "memory");
            }
            DBG(10, 8);
        }
        PT(11, 256);
        softmax(NSEG - 1);
        fence_async_smem();
        asm volatile("cp.async.bulk.wait_group.read 0;" ::: "memory");
        asm volatile("bar.sync 2, 128;" ::: "memory");
        PT(12, 256);
        float dc[16];
        pv(dc, NSEG - 1);
        wgmma_wait<0>();
        store32(dc, aO - 2 * CH_TW + CO_ST);
        PT(13, 256);
        fence_async_smem();
        asm volatile("bar.sync 2, 128;" ::: "memory");
        store_ctx(NSEG - 1);
        if (tid == 256) {
            asm volatile("cp.async.bulk.wait_group 0;" ::: "memory");
            PT(14, 256);
            signal_ctx(15, 16);
            PT(15, 256);
        }
    }
    __syncthreads();
    cluster_sync_all();
    TS_END(2);
}

struct Proj2Params {
    CUtensorMap mapA[2];
    CUtensorMap mapW[3];
    bf16* out[3];
};
#define P2T(i)
#define P2_NOMMA 0
#define P2_NOLOAD 0
constexpr int P2_STAGES = 6;
constexpr int P2_SMEM = 131072 + P2_STAGES * 16384 + 1024 + 1024;
constexpr int P2_ITEMS = 168 + 48;

__device__ __forceinline__ int p2_reps(int t) { return t >= 168 ? 1 : 2; }
__device__ __forceinline__ void p2_tile(int t, int w, int& z, int& mp, int& head) {
    if (t >= 168) { w += ((t - 168) & 1) * 2; t = 168 + ((t - 168) >> 1); }
    const int hq = t / 24, v = t % 24;
    mp = v & 7;
    if (v < 16) { head = hq * 4 + (v >> 3) * 2 + (w >> 1); z = 1 + (w & 1); }
    else { head = hq * 4 + w; z = 0; }
}
__device__ __forceinline__ void mbar_arrive_remote(uint32_t bar_cluster_addr) {
    asm volatile("mbarrier.arrive.release.cluster.shared::cluster.b64 _, [%0];" :: "r"(bar_cluster_addr) : "memory");
}
__device__ __forceinline__ void mbar_arrive_cl(uint32_t bar_cluster_addr) {
    asm volatile("mbarrier.arrive.shared::cluster.b64 _, [%0];" :: "r"(bar_cluster_addr) : "memory");
}
__device__ __forceinline__ void mbar_wait_acq_cluster(uint32_t bar, uint32_t parity) {
    asm volatile(
        "{\n"
        ".reg .pred p, q;\n"
        ".reg .u32 c;\n"
        "mov.u32 c, 0;\n"
        "WAIT_LOOP_C:\n"
        "mbarrier.try_wait.parity.acquire.cluster.shared::cta.b64 p, [%0], %1;\n"
        "@p bra WAIT_DONE_C;\n"
        "add.u32 c, c, 1;\n"
        "setp.lt.u32 q, c, 4000000;\n"
        "@q bra WAIT_LOOP_C;\n"
        "WAIT_DONE_C:\n"
        "}\n" :: "r"(bar), "r"(parity) : "memory");
}
__device__ __forceinline__ uint4 quad_transpose(uint32_t p0, uint32_t p1, uint32_t p2, uint32_t p3, int lane) {
    const bool o1 = lane & 1, o2 = lane & 2;
    uint32_t s0 = o1 ? p0 : p1, s1 = o1 ? p2 : p3;
    s0 = __shfl_xor_sync(0xffffffff, s0, 1); s1 = __shfl_xor_sync(0xffffffff, s1, 1);
    const uint32_t a_lo = o1 ? s0 : p0, a_hi = o1 ? p1 : s0, b_lo = o1 ? s1 : p2, b_hi = o1 ? p3 : s1;
    uint32_t t0 = o2 ? a_lo : b_lo, t1 = o2 ? a_hi : b_hi;
    t0 = __shfl_xor_sync(0xffffffff, t0, 2); t1 = __shfl_xor_sync(0xffffffff, t1, 2);
    return o2 ? make_uint4(t0, t1, b_lo, b_hi) : make_uint4(a_lo, a_hi, t0, t1);
}
#define P2_PACE 35
#define P2_PACE2 0
template <bool PERM, int PACE = 0>
__device__ __forceinline__ void store_frag_128(const float (&acc)[64], bf16* obase, int lane) {
#pragma unroll
    for (int rr = 0; rr < 2; rr++)
#pragma unroll
        for (int g = 0; g < 4; g++) {
            const float* a = &acc[g * 16 + rr * 2];
            const uint32_t p0 = pack_bf16(a[0], a[1]), p1 = pack_bf16(a[4], a[5]), p2 = pack_bf16(a[8], a[9]), p3 = pack_bf16(a[12], a[13]);
            *reinterpret_cast<uint4*>(obase + (size_t)(rr * 8) * HD + g * 32) = PERM ? make_uint4(p0, p1, p2, p3) : quad_transpose(p0, p1, p2, p3, lane);
            pace(PACE);
        }
}
__global__ void __cluster_dims__(2, 1, 1) __launch_bounds__(384, 1) proj2_kernel(const __grid_constant__ Proj2Params P) {
    extern __shared__ uint8_t smem_raw[];
    const uint32_t sbase = (smem_u32(smem_raw) + 1023) & ~1023u;
    const uint32_t sA = sbase, sB = sbase + 131072, sC = sB + P2_STAGES * 16384;
    const uint32_t bars = sC;
    const uint32_t a_full = bars, a_empty = bars + 64, b_full = bars + 128, b_empty = b_full + 8 * P2_STAGES;
    const uint32_t item_bar = b_empty + 8 * P2_STAGES, item_in = item_bar + 16, slot = item_in + 16;
    const uint32_t note_bar = slot + 16, note_free = note_bar + 64, note = note_free + 64;
    const int warp = threadIdx.x >> 5, lane = threadIdx.x & 31;
    const uint32_t rank = cluster_ctarank();
    TS_BEGIN(0);
    if (threadIdx.x == 0) {
        for (int i = 0; i < 8; i++) { mbar_init(a_full + 8 * i, 1); mbar_init(a_empty + 8 * i, 2); }
        for (int i = 0; i < P2_STAGES; i++) { mbar_init(b_full + 8 * i, 1); mbar_init(b_empty + 8 * i, 2); }
        mbar_init(item_bar, 1); mbar_init(item_bar + 8, 1); mbar_init(item_in, 2); mbar_init(item_in + 8, 2);
        for (int i = 0; i < 8; i++) { mbar_init(note_bar + 8 * i, 1); mbar_init(note_free + 8 * i, 1); }
        asm volatile("fence.mbarrier_init.release.cluster;" ::: "memory");
    }
    __syncthreads();
    cluster_sync_all();
    pdl_launch_dependents();
    if (warp == 9) {
        if (lane == 0) {
            for (int n = 0;; n++) {
                const int e = (n & 1) * 4 + ((n >> 1) & 3);
                mbar_wait(note_bar + 8 * e, (n >> 3) & 1);
                int m;
                asm volatile("ld.shared.s32 %0, [%1];" : "=r"(m) : "r"(note + e * 4) : "memory");
                mbar_arrive(note_free + 8 * e);
                if (m < 0) break;
                signal_ctr(m);
            }
        }
    } else if (warp == 10) {
        if (lane == 0) {
            auto publish = [&](int ic, int tq) {
                const int t = tq < P2_ITEMS ? tq : -1;
                asm volatile("st.shared.s32 [%0], %1;" :: "r"(slot + (ic & 3) * 4), "r"(t) : "memory");
                mbar_arrive(item_bar + 8 * (ic & 1));
                st_async_b32(mapa_u32(slot + (ic & 3) * 4, 1), (uint32_t)t, mapa_u32(item_bar + 8 * (ic & 1), 1));
            };
            const int npair = (int)(gridDim.x >> 1), pair = (int)(blockIdx.x >> 1);
            if (rank == 0) publish(0, pair);
            for (int ic = 0;; ic++) {
                if (rank == 1) mbar_expect_tx(item_bar + 8 * (ic & 1), 4);
                mbar_wait(item_bar + 8 * (ic & 1), (ic >> 1) & 1);
                int t;
                asm volatile("ld.shared.s32 %0, [%1];" : "=r"(t) : "r"(slot + (ic & 3) * 4) : "memory");
                if (t < 0) break;
                int z0, mp, h0;
                p2_tile(t, 0, z0, mp, h0);
                const int aidx = z0 >= 1 ? 1 : 0;
                const int m0 = (2 * mp + (int)rank) * 128;
                for (int k = 0; k < 8; k++) {
                    mbar_wait(a_empty + 8 * k, (ic & 1) ^ 1);
                    if (P2_NOLOAD) mbar_arrive(a_full + 8 * k); else {
                    mbar_expect_tx(a_full + 8 * k, 16384);
                    tma_load_2d(sA + k * 16384, &P.mapA[aidx], a_full + 8 * k, k * 64, m0); }
                }
                if (rank == 0) {
                    mbar_wait(item_in + 8 * (ic & 1), (ic >> 1) & 1);
                    publish(ic + 1, ic == 0 ? npair + pair : 2 * npair + (int)atomicAdd(&g_ctr[CT_PROJ], 1u));
                }
            }
        }
    } else if (warp == 8 || warp == 11) {
        if (lane == 0) {
            const int par2 = warp == 8 ? 0 : 1;
            int it = 0; uint32_t bph = 0;
            for (int ic = 0;; ic++) {
                mbar_wait(item_bar + 8 * (ic & 1), (ic >> 1) & 1);
                int t;
                asm volatile("ld.shared.s32 %0, [%1];" : "=r"(t) : "r"(slot + (ic & 3) * 4) : "memory");
                if (t < 0) break;
                const int nt = 2 * p2_reps(t);
                for (int w = 0; w < nt; w++) {
                    int z, mp, hd;
                    p2_tile(t, w, z, mp, hd);
                    for (int k = 0; k < 8; k++) {
                        const int s = it; const uint32_t phb = bph;
                        if (++it == P2_STAGES) { it = 0; bph ^= 1; }
                        if ((k & 1) != par2) continue;
                        mbar_wait(b_empty + 8 * s, phb ^ 1);
                        if (P2_NOLOAD) { mbar_arrive(b_full + 8 * s); continue; }
                        mbar_expect_tx(b_full + 8 * s, 16384);
                        tma_load_2d_mc(sB + s * 16384 + rank * 8192, &P.mapW[z], b_full + 8 * s, hd * 128 + (int)rank * 64, k * 64, (uint16_t)3);
                    }
                }
            }
        }
    } else {
        const int wg = warp >> 2;
        float acc[2][64];
        const uint32_t a_lo = desc_lo(sA, 16), b_lo0 = desc_lo(sB, 8192);
        const bool elected = (threadIdx.x & 127) == 0;
        int s = (wg * 8) % P2_STAGES;
        uint32_t ph = ((wg * 8) / P2_STAGES) & 1;
        int nnote = 0;
        if (wg == 1) asm volatile("bar.arrive 3, 256;" ::: "memory");
        for (int ic = 0;; ic++) {
            mbar_wait(item_bar + 8 * (ic & 1), (ic >> 1) & 1);
            int t;
            asm volatile("ld.shared.s32 %0, [%1];" : "=r"(t) : "r"(slot + (ic & 3) * 4) : "memory");
            P2T(7);
            if (wg == 0 && t < 0) {
                if (elected) {
                    const int e = nnote & 3;
                    mbar_wait(note_free + 8 * e, ((nnote >> 2) & 1) ^ 1);
                    asm volatile("st.shared.s32 [%0], %1;" :: "r"(note + e * 4), "r"(-1) : "memory");
                    mbar_arrive(note_bar + 8 * e);
                }
            }
            if (t < 0) break;
            const int reps = p2_reps(t);
#pragma unroll 1
            for (int rp = 0; rp < reps; rp++) {
            const bool first = rp == 0, last = rp == reps - 1;
            int z, mp, head;
            p2_tile(t, rp * 2 + wg, z, mp, head);
            asm volatile("bar.sync %0, 256;" :: "r"(3 + wg) : "memory");
            P2T(0);
            if (wg == 1 && last && elected) mbar_arrive_cl(mapa_u32(item_in + 8 * (ic & 1), 0));
            int sprev = 0;
#pragma unroll
            for (int k = 0; k < 8; k++) {
                if (k == 0) P2T(5);
                if (wg == 0 && first) mbar_wait(a_full + 8 * k, ic & 1);
                if (k == 0) P2T(6);
                mbar_wait(b_full + 8 * s, ph);
                if (k == 7) asm volatile("bar.arrive %0, 256;" :: "r"(4 - wg) : "memory");
                if (k == 0) P2T(1);
                if (k == 7) P2T(2);
                const uint32_t b_lo = b_lo0 + s * 1024;
                wgmma_fence();
#pragma unroll
                for (int kk = 0; kk < (P2_NOMMA ? 1 : 4); kk++) {
                    wgmma_ss_n128_lo<1>(acc[0], a_lo + k * 1024 + kk * 2, b_lo + kk * 128, (k | kk) != 0);
                    wgmma_ss_n128_lo<1>(acc[1], a_lo + k * 1024 + 512 + kk * 2, b_lo + kk * 128, (k | kk) != 0);
                }
                wgmma_commit();
                if (k > 0) {
                    wgmma_wait<1>();
                    if (elected) {
                        const uint32_t e = b_empty + 8 * sprev;
                        mbar_arrive_cl(mapa_u32(e, 0)); mbar_arrive_cl(mapa_u32(e, 1));
                        if (last) mbar_arrive(a_empty + 8 * (k - 1));
                    }
                }
                sprev = s;
                if (++s == P2_STAGES) { s = 0; ph ^= 1; }
            }
            wgmma_wait<0>();
            P2T(3);
            if (elected) {
                const uint32_t e = b_empty + 8 * sprev;
                mbar_arrive_cl(mapa_u32(e, 0)); mbar_arrive_cl(mapa_u32(e, 1));
                if (last) mbar_arrive(a_empty + 8 * 7);
            }
            s += 8 % P2_STAGES; ph ^= (8 / P2_STAGES) & 1;
            if (s >= P2_STAGES) { s -= P2_STAGES; ph ^= 1; }
            const int m0 = (2 * mp + (int)rank) * 128;
            bf16* obase = P.out[z] + ((size_t)head * SEQ + m0 + (warp & 3) * 16 + (lane >> 2)) * HD + (lane & 3) * 8;
            store_frag_128<true, P2_PACE>(acc[0], obase, lane); store_frag_128<true, P2_PACE>(acc[1], obase + (size_t)64 * HD, lane);
            P2T(4);
            {
                asm volatile("bar.sync %0, 128;" :: "r"(1 + wg) : "memory");
                if (elected) {
                    const int e = wg * 4 + (nnote & 3);
                    mbar_wait(note_free + 8 * e, ((nnote >> 2) & 1) ^ 1);
                    asm volatile("st.shared.s32 [%0], %1;" :: "r"(note + e * 4), "r"(CT_AP + (head >> 1)) : "memory");
                    mbar_arrive(note_bar + 8 * e);
                }
                nnote++;
            }
            }
        }
        TS_END(0);
    }
    __syncthreads();
    cluster_sync_all();
}

struct OutParams {
    CUtensorMap mapCtx[2];
    CUtensorMap mapWo[2];
    CUtensorMap mapOut;
};

#define OT(i)
#define OTP(i, th)
constexpr int O2_STAGES = 4;
constexpr int O2_SMEM = O2_STAGES * 49152 + 1024 + 256;
constexpr int O2_GRID = 132;
#define O2_NL 8
#define O2_FINE 8

__global__ void __cluster_dims__(2, 1, 1) __launch_bounds__(352, 1)
out2_kernel(const __grid_constant__ OutParams P) {
    extern __shared__ uint8_t smem_raw[];
    const uint32_t sbase = (smem_u32(smem_raw) + 1023) & ~1023u;
    const uint32_t bar_full = sbase + O2_STAGES * 49152, bar_empty = bar_full + 8 * O2_STAGES, bar_item = bar_empty + 8 * O2_STAGES;
    const uint32_t slot = bar_item + 64, stop = slot + 32;
    const int warp = threadIdx.x >> 5, lane = threadIdx.x & 31;
    const uint32_t rank = cluster_ctarank();
    const int cid = blockIdx.x >> 1;
    int pt, h0;
    if (cid < 32) { pt = cid < 16 ? cid : 31 - cid; h0 = cid >= 16; }
    else if (cid < 34) { pt = 12 + (cid & 1); h0 = 2; }
    else { pt = 14 + (cid & 1); h0 = 63 - ((cid - 34) >> 1); }
    const int ne = (pt >> 1) == 6 ? 3 : 2, nh = pt >= 14 ? 64 - O2_NL : 64;
    if (cid >= 34 + 2 * O2_NL) {
        if (threadIdx.x == 0 && atomicAdd(&g_ctr[CT_FIN], 1u) == gridDim.x - 1)
            for (int i = 0; i < CT_N / 4; i++) reinterpret_cast<uint4*>(g_ctr)[i] = make_uint4(0u, 0u, 0u, 0u);
        return;
    }
    const int mt = (pt >> 1) * 2 + (int)rank, m0 = mt * 128, n0 = (pt & 1) * 256;
    TS_BEGIN(4);
    OT(0);
    int tnext = 0;
    if (threadIdx.x == 256) {
        if (rank == 0) tnext = take_ticket(CT_OT + pt);
        for (int i = 0; i < O2_STAGES; i++) { mbar_init(bar_full + 8 * i, 1); mbar_init(bar_empty + 8 * i, 4); mbar_init(bar_item + 16 * i, 1); mbar_init(bar_item + 16 * i + 8, 1); }
        sts128(stop, 0u, 0u, 0u, 0u);
        asm volatile("fence.mbarrier_init.release.cluster;" ::: "memory");
    }
    __syncwarp();
    asm volatile("barrier.cluster.arrive.relaxed.aligned;" ::: "memory");
    if (threadIdx.x == 256) {
        asm volatile("prefetch.tensormap [%0];" :: "l"(&P.mapCtx[h0 >> 5]) : "memory");
        wait_ctr(h0 < 32 ? CT_CA + mt * 4 : CT_CB + mt, h0 < 32 ? 16u : 64u);
        OTP(8, 256);
        for (int i = 0; i < 2; i++) {
            mbar_expect_tx(bar_full + 8 * i, 49152);
            tma_load_2d(sbase + i * 49152, &P.mapCtx[h0 >> 5], bar_full + 8 * i, i * 64, (h0 & 31) * SEQ + m0);
        }
        OTP(11, 256);
    }
    if (threadIdx.x == 288) asm volatile("prefetch.tensormap [%0];" :: "l"(&P.mapWo[h0 >> 5]) : "memory");
    __syncwarp();
    asm volatile("barrier.cluster.wait.aligned;" ::: "memory");
    OTP(10, 288);
    if (warp >= 8) {
        if (lane == 0) {
            int s = 0, ready = h0 < 32 ? 1 : 16, q = h0 * 2, qe = q + 2; uint32_t ph = 0;
            for (int ic = 0;; ic++) {
                if (warp == 8 && rank == 0) {
                    const int t = tnext + ne;
                    asm volatile("st.shared.s32 [%0], %1;" :: "r"(slot + (ic & 7) * 4), "r"(t) : "memory");
                    mbar_arrive(bar_item + 8 * (ic & 7));
                    st_async_b32(mapa_u32(slot + (ic & 7) * 4, 1), (uint32_t)t, mapa_u32(bar_item + 8 * (ic & 7), 1));
                    if (t < nh + O2_FINE) tnext = take_ticket(CT_OT + pt);
                }
#pragma unroll 1
                for (; q < qe; q++) {
                    const int b = q >> 6, head = (q >> 1) & 31, dk = (q & 1) * 64;
                    mbar_wait(bar_empty + 8 * s, ph ^ 1);
                    const uint32_t sa = sbase + s * 49152;
                    if (warp == 8) {
                        const int f = b ? 4 : head >> 3;
                        if (!((ready >> f) & 1)) {
                            if (b && !(ready & 8)) { wait_ctr(CT_CA + mt * 4 + 3, 16u); ready |= 8; }
                            wait_ctr(b ? CT_CB + mt : CT_CA + mt * 4 + f, b ? 64u : 16u); ready |= 1 << f;
                        }
                        if (ic > 0) {
                            mbar_expect_tx(bar_full + 8 * s, 49152);
                            tma_load_2d(sa, &P.mapCtx[b], bar_full + 8 * s, dk, head * SEQ + m0);
                        }
                    } else {
                        const int j = (int)rank * 2 + (warp - 9);
                        tma_load_2d_mc(sa + 16384 + j * 8192, &P.mapWo[b], bar_full + 8 * s, n0 + j * 64, head * HD + dk, (uint16_t)3);
                    }
                    if (ic == 0 && s == 0) OTP(12, 288);
                    if (++s == O2_STAGES) { s = 0; ph ^= 1; }
                }
                if (warp == 8 && rank == 1) mbar_expect_tx(bar_item + 8 * (ic & 7), 4);
                mbar_wait(bar_item + 8 * (ic & 7), (ic >> 3) & 1);
                int t;
                asm volatile("ld.shared.s32 %0, [%1];" : "=r"(t) : "r"(slot + (ic & 7) * 4) : "memory");
                if (t >= nh + O2_FINE) break;
                if (t < nh - O2_FINE) { q = 2 * t; qe = q + 2; } else { q = nh - O2_FINE + t; qe = q + 1; }
            }
            if (warp == 8) {
                asm volatile("prefetch.tensormap [%0];" :: "l"(&P.mapOut) : "memory");
                if (!(ready & 8)) wait_ctr(CT_CA + mt * 4 + 3, 16u);
                mbar_wait(bar_empty + 8 * s, ph ^ 1);
                asm volatile("st.shared.s32 [%0], %1;" :: "r"(stop + s * 4), "r"(1) : "memory");
                mbar_arrive(bar_full + 8 * s);
                if (atomicAdd(&g_ctr[CT_FIN], 1u) == gridDim.x - 1)
                    for (int i = 0; i < CT_N / 4; i++) reinterpret_cast<uint4*>(g_ctr)[i] = make_uint4(0u, 0u, 0u, 0u);
                for (int i = 1; i < O2_STAGES; i++) {
                    if (++s == O2_STAGES) { s = 0; ph ^= 1; }
                    mbar_wait(bar_empty + 8 * s, ph ^ 1);
                }
            }
        }
    } else {
        const int wg = warp >> 2;
        const bool elected = (threadIdx.x & 127) == 0;
        float acc[128];
#pragma unroll
        for (int i = 0; i < 128; i++) acc[i] = 0.f;
        int s = 0, sprev = 0; uint32_t ph = 0;
#pragma unroll 1
        for (int i = 0;; i++) {
            mbar_wait(bar_full + 8 * s, ph);
            int st;
            asm volatile("ld.shared.s32 %0, [%1];" : "=r"(st) : "r"(stop + s * 4) : "memory");
            if (st) break;
            if (i == 0) OT(1);
            const uint32_t sa = sbase + s * 49152 + wg * 8192, sb = sbase + s * 49152 + 16384;
            wgmma_fence();
#pragma unroll
            for (int kk = 0; kk < 4; kk++)
                wgmma_ss_n256_tb(acc, make_desc(sa + kk * 32, 16, 1024), make_desc(sb + kk * 2048, 8192, 1024), 1);
            wgmma_commit();
            if (i > 0) {
                wgmma_wait<1>();
                if (elected) { const uint32_t e = bar_empty + 8 * sprev; mbar_arrive_cl(mapa_u32(e, 0)); mbar_arrive_cl(mapa_u32(e, 1)); }
            }
            sprev = s;
            if (++s == O2_STAGES) { s = 0; ph ^= 1; }
        }
        wgmma_wait<0>();
        if (elected) { const uint32_t e = bar_empty + 8 * sprev; mbar_arrive_cl(mapa_u32(e, 0)); mbar_arrive_cl(mapa_u32(e, 1)); }
        asm volatile("bar.sync %0, 128;" :: "r"(1 + wg) : "memory");
        OT(3);
        const int row = (lane & 7) + ((lane >> 3) & 1) * 8;
#pragma unroll
        for (int bx = 0; bx < 4; bx++) {
            const uint32_t stg = sbase + bx * 49152 + warp * 2048;
#pragma unroll
            for (int j = 0; j < 8; j += 2) {
                const float* a = &acc[bx * 32 + j * 4];
                stmatrix_x4(stg + row * 128 + (((j + (lane >> 4)) ^ (row & 7)) << 4), pack_bf16(a[0], a[1]), pack_bf16(a[2], a[3]), pack_bf16(a[4], a[5]), pack_bf16(a[6], a[7]));
            }
            asm volatile("fence.proxy.async.shared::cta;" ::: "memory");
            __syncwarp();
            if (lane == 0)
                asm volatile("cp.reduce.async.bulk.tensor.2d.global.shared::cta.add.tile.bulk_group [%0, {%2, %3}], [%1];"
                             :: "l"((uint64_t)&P.mapOut), "r"(stg), "r"(n0 + bx * 64), "r"(m0 + warp * 16) : "memory");
        }
        OT(4);
        if (lane == 0) {
            asm volatile("cp.async.bulk.commit_group;" ::: "memory");
            asm volatile("cp.async.bulk.wait_group.read 0;" ::: "memory");
        }
        TS_END(4);
    }
}

typedef CUresult (*PFN_encodeTiled)(CUtensorMap*, CUtensorMapDataType, cuuint32_t, void*, const cuuint64_t*,
                                    const cuuint64_t*, const cuuint32_t*, const cuuint32_t*, CUtensorMapInterleave,
                                    CUtensorMapSwizzle, CUtensorMapL2promotion, CUtensorMapFloatOOBfill);
static PFN_encodeTiled g_encode = nullptr;

static void make_map(CUtensorMap* m, const void* ptr, uint64_t rows, uint64_t cols, uint32_t box_rows, bool sw64 = false) {
    cuuint64_t dims[2] = {cols, rows};
    cuuint64_t strides[1] = {cols * 2};
    cuuint32_t box[2] = {sw64 ? 32u : 64u, box_rows};
    cuuint32_t es[2] = {1, 1};
    g_encode(m, CU_TENSOR_MAP_DATA_TYPE_BFLOAT16, 2, const_cast<void*>(ptr), dims, strides, box, es,
             CU_TENSOR_MAP_INTERLEAVE_NONE, sw64 ? CU_TENSOR_MAP_SWIZZLE_64B : CU_TENSOR_MAP_SWIZZLE_128B, CU_TENSOR_MAP_L2_PROMOTION_L2_256B,
             CU_TENSOR_MAP_FLOAT_OOB_FILL_NONE);
}

template <typename... KArgs, typename... Args>
static void launch_pdl(void (*kernel)(KArgs...), int grid, int block, size_t smem, cudaStream_t st, bool pdl, Args... args) {
    cudaLaunchConfig_t cfg = {};
    cfg.gridDim = dim3(grid); cfg.blockDim = dim3(block); cfg.dynamicSmemBytes = smem; cfg.stream = st;
    cudaLaunchAttribute at[1];
    at[0].id = cudaLaunchAttributeProgrammaticStreamSerialization;
    at[0].val.programmaticStreamSerializationAllowed = 1;
    cfg.attrs = at; cfg.numAttrs = pdl ? 1 : 0;
    cudaLaunchKernelEx(&cfg, kernel, KArgs(args)...);
}

extern "C" void kernel_launch(void* const* d_in, const int* in_sizes, int n_in, void* d_out, int out_size) {
    const bf16* x = (const bf16*)d_in[0];
    const bf16* ckv = (const bf16*)d_in[1];
    const bf16* wq = (const bf16*)d_in[2];
    const bf16* wuk = (const bf16*)d_in[3];
    const bf16* wuv = (const bf16*)d_in[4];
    const bf16* wo = (const bf16*)d_in[5];
    const bf16* mem0 = (const bf16*)d_in[7];
    const bf16* Wq = (const bf16*)d_in[8];
    const bf16* Wk = (const bf16*)d_in[9];
    const bf16* Wv = (const bf16*)d_in[10];
    const bf16* Wo = (const bf16*)d_in[11];
    const bf16* gate_w = (const bf16*)d_in[13];
    bf16* out = (bf16*)d_out;

    static Proj2Params P2;
    static ChainParams CP;
    static AttnParams AP;
    static OutParams OP;
    static bool init = false;
    static const void* last_in[14];
    static const void* last_out;
    bool same = init && last_out == d_out;
    for (int i = 0; i < 14 && same; i++) same = last_in[i] == d_in[i];
    if (!init) {
        cudaDriverEntryPointQueryResult qr;
        cudaGetDriverEntryPoint("cuTensorMapEncodeTiled", (void**)&g_encode, cudaEnableDefault, &qr);
        cudaFuncSetAttribute(proj2_kernel, cudaFuncAttributeMaxDynamicSharedMemorySize, P2_SMEM);
        cudaFuncSetAttribute(attn_kernel, cudaFuncAttributeMaxDynamicSharedMemorySize, FA_SMEM);
        cudaFuncSetAttribute(chain_kernel, cudaFuncAttributeMaxDynamicSharedMemorySize, CH_SMEM);
        cudaFuncSetAttribute(out2_kernel, cudaFuncAttributeMaxDynamicSharedMemorySize, O2_SMEM);
        init = true;
    }
    if (!same) {
        for (int i = 0; i < 14; i++) last_in[i] = d_in[i];
        last_out = d_out;
        void *pQA, *pKA, *pVA, *pCA, *pCB;
        cudaGetSymbolAddress(&pQA, g_QA); cudaGetSymbolAddress(&pKA, g_KA); cudaGetSymbolAddress(&pVA, g_VA);
        cudaGetSymbolAddress(&pCA, g_ctxA); cudaGetSymbolAddress(&pCB, g_ctxB);
        make_map(&P2.mapA[0], x, SEQ, DM, 128);
        make_map(&P2.mapA[1], ckv, SEQ, DM, 128);
        const void* ws[3] = {wq, wuk, wuv};
        void* cs[3] = {pQA, pKA, pVA};
        for (int i = 0; i < 3; i++) { make_map(&P2.mapW[i], ws[i], DM, NQ, 64); P2.out[i] = (bf16*)cs[i]; }
        make_map(&CP.mapW[0], Wq, DM, NQ, 64); make_map(&CP.mapW[1], Wk, DM, NQ, 64); make_map(&CP.mapW[2], Wv, DM, NQ, 64);
        make_map(&CP.mapX, x, SEQ, DM, 32);
        make_map(&CP.mapC, pCB, NH * SEQ, HD, 32);
        make_map(&AP.mapQ, pQA, NH * SEQ, HD, 128);
        make_map(&AP.mapK, pKA, NH * SEQ, HD, 128);
        make_map(&AP.mapV, pVA, NH * SEQ, HD, 128);
        make_map(&AP.mapO, pCA, NH * SEQ, HD, 64);
        make_map(&OP.mapCtx[0], pCA, NH * SEQ, HD, 128);
        make_map(&OP.mapCtx[1], pCB, NH * SEQ, HD, 128);
        make_map(&OP.mapWo[0], wo, NQ, DM, 64);
        make_map(&OP.mapWo[1], Wo, NQ, DM, 64);
        make_map(&OP.mapOut, out, SEQ, DM, 16);
        AP.out = out;
    }
    cudaStream_t s1 = cudaStreamPerThread;
    const bool pdl = true;
    launch_pdl(chain_kernel, 64, CH_BLOCK, CH_SMEM, s1, false, CP, mem0, Wo, x, gate_w);
    launch_pdl(proj2_kernel, 68, 384, P2_SMEM, s1, pdl, P2);
    launch_pdl(attn_kernel, FA_GRID, 384, FA_SMEM, s1, pdl, AP);
    launch_pdl(out2_kernel, O2_GRID, 352, O2_SMEM, s1, pdl, OP);
}
```

```cpp
#include <cuda_runtime.h>
#include <cuda_bf16.h>
#include <cuda.h>
#include <stdint.h>
#include <type_traits>

constexpr int SEQ = 2048;
constexpr int DM = 512;
constexpr int NH = 32;
constexpr int HD = 128;
constexpr int NQ = NH * HD;
constexpr int SEGL = 32;
constexpr int NMEM = 8;
constexpr int NSEG = SEQ / SEGL;

typedef __nv_bfloat16 bf16;

__device__ bf16 g_QA[SEQ * NQ];
__device__ bf16 g_KA[SEQ * NQ];
__device__ bf16 g_VA[SEQ * NQ];
__device__ bf16 g_ctxA[SEQ * NQ];
__device__ bf16 g_ctxB[SEQ * NQ];
constexpr int CT_PROJ = 0, CT_ATTN = 1, CT_FIN = 5;
constexpr int CT_AP = 64;
constexpr int CT_GATE = 96;
constexpr int CT_CA = 128;
constexpr int CT_CB = 192;
constexpr int CT_OT = 208;
constexpr int CT_N = 224;
__device__ __align__(16) unsigned int g_ctr[CT_N];
__device__ float g_gate[SEQ];
__device__ uint32_t g_xbuf[4 * 8 * 2048];

#define FA_GRID 68

#define TS_BEGIN(id)
#define TS_END(id)
#define WAIT_LIMIT 200000
__device__ __forceinline__ void pdl_launch_dependents() { asm volatile("griddepcontrol.launch_dependents;" ::: "memory"); }
__device__ __forceinline__ void wait_ctr(int idx, unsigned int n) {
    unsigned int v; int it = 0;
    do { asm volatile("ld.acquire.gpu.global.u32 %0, [%1];" : "=r"(v) : "l"(&g_ctr[idx]) : "memory"); } while (v < n && ++it < WAIT_LIMIT);
    asm volatile("fence.proxy.async.shared::cta;" ::: "memory");
}
__device__ __forceinline__ int take_ticket(int idx) {
    int v;
    asm volatile("atom.relaxed.gpu.global.inc.u32 %0, [%1], 0x7fffffff;" : "=r"(v) : "l"(&g_ctr[idx]) : "memory");
    return v;
}
__device__ __forceinline__ void signal_ctr(int idx) {
    asm volatile("fence.proxy.async;" ::: "memory");
    __threadfence();
    atomicAdd(&g_ctr[idx], 1u);
}
__device__ __forceinline__ void signal_ctr_generic(int idx) {
    asm volatile("red.release.gpu.global.add.u32 [%0], 1;" :: "l"(&g_ctr[idx]) : "memory");
}
__device__ __forceinline__ uint32_t smem_u32(const void* p) {
    return (uint32_t)__cvta_generic_to_shared(p);
}
__device__ __forceinline__ void mbar_init(uint32_t bar, uint32_t count) {
    asm volatile("mbarrier.init.shared::cta.b64 [%0], %1;" :: "r"(bar), "r"(count));
}
__device__ __forceinline__ void mbar_expect_tx(uint32_t bar, uint32_t bytes) {
    asm volatile("mbarrier.arrive.expect_tx.shared::cta.b64 _, [%0], %1;" :: "r"(bar), "r"(bytes) : "memory");
}
__device__ __forceinline__ void mbar_arrive(uint32_t bar) {
    asm volatile("mbarrier.arrive.shared::cta.b64 _, [%0];" :: "r"(bar) : "memory");
}
__device__ __forceinline__ void mbar_wait(uint32_t bar, uint32_t parity) {
    asm volatile(
        "{\n"
        ".reg .pred p, q;\n"
        ".reg .u32 c;\n"
        "mov.u32 c, 0;\n"
        "WAIT_LOOP:\n"
        "mbarrier.try_wait.parity.shared::cta.b64 p, [%0], %1;\n"
        "@p bra WAIT_DONE;\n"
        "add.u32 c, c, 1;\n"
        "setp.lt.u32 q, c, %2;\n"
        "@q bra WAIT_LOOP;\n"
        "WAIT_DONE:\n"
        "}\n" :: "r"(bar), "r"(parity), "n"(WAIT_LIMIT) : "memory");
}
__device__ __forceinline__ uint32_t mbar_test(uint32_t bar, uint32_t parity) {
    uint32_t done;
    asm volatile(
        "{\n.reg .pred p;\n"
        "mbarrier.test_wait.parity.shared::cta.b64 p, [%1], %2;\n"
        "selp.u32 %0, 1, 0, p;\n}\n" : "=r"(done) : "r"(bar), "r"(parity) : "memory");
    return done;
}
__device__ __forceinline__ uint32_t mbar_try(uint32_t bar, uint32_t parity) {
    uint32_t done;
    asm volatile(
        "{\n.reg .pred p;\n"
        "mbarrier.try_wait.parity.shared::cta.b64 p, [%1], %2;\n"
        "selp.u32 %0, 1, 0, p;\n}\n" : "=r"(done) : "r"(bar), "r"(parity) : "memory");
    return done;
}
__device__ __forceinline__ void tma_load_2d(uint32_t dst, const CUtensorMap* map, uint32_t bar, int c0, int c1) {
    asm volatile(
        "cp.async.bulk.tensor.2d.shared::cluster.global.mbarrier::complete_tx::bytes [%0], [%1, {%3, %4}], [%2];"
        :: "r"(dst), "l"((uint64_t)map), "r"(bar), "r"(c0), "r"(c1) : "memory");
}
__device__ __forceinline__ void wgmma_fence() { asm volatile("wgmma.fence.sync.aligned;" ::: "memory"); }
__device__ __forceinline__ void wgmma_commit() { asm volatile("wgmma.commit_group.sync.aligned;" ::: "memory"); }
template <int N> __device__ __forceinline__ void wgmma_wait() {
    asm volatile("wgmma.wait_group.sync.aligned %0;" :: "n"(N) : "memory");
}
__device__ __forceinline__ uint64_t make_desc(uint32_t addr, uint32_t lbo, uint32_t sbo) {
    uint64_t d = 0;
    d |= (uint64_t)((addr & 0x3FFFF) >> 4);
    d |= (uint64_t)((lbo >> 4) & 0x3FFF) << 16;
    d |= (uint64_t)((sbo >> 4) & 0x3FFF) << 32;
    d |= (uint64_t)1 << 62;
    return d;
}

#define ACC64(d) \
    "+f"(d[0]), "+f"(d[1]), "+f"(d[2]), "+f"(d[3]), "+f"(d[4]), "+f"(d[5]), "+f"(d[6]), "+f"(d[7]), \
    "+f"(d[8]), "+f"(d[9]), "+f"(d[10]), "+f"(d[11]), "+f"(d[12]), "+f"(d[13]), "+f"(d[14]), "+f"(d[15]), \
    "+f"(d[16]), "+f"(d[17]), "+f"(d[18]), "+f"(d[19]), "+f"(d[20]), "+f"(d[21]), "+f"(d[22]), "+f"(d[23]), \
    "+f"(d[24]), "+f"(d[25]), "+f"(d[26]), "+f"(d[27]), "+f"(d[28]), "+f"(d[29]), "+f"(d[30]), "+f"(d[31]), \
    "+f"(d[32]), "+f"(d[33]), "+f"(d[34]), "+f"(d[35]), "+f"(d[36]), "+f"(d[37]), "+f"(d[38]), "+f"(d[39]), \
    "+f"(d[40]), "+f"(d[41]), "+f"(d[42]), "+f"(d[43]), "+f"(d[44]), "+f"(d[45]), "+f"(d[46]), "+f"(d[47]), \
    "+f"(d[48]), "+f"(d[49]), "+f"(d[50]), "+f"(d[51]), "+f"(d[52]), "+f"(d[53]), "+f"(d[54]), "+f"(d[55]), \
    "+f"(d[56]), "+f"(d[57]), "+f"(d[58]), "+f"(d[59]), "+f"(d[60]), "+f"(d[61]), "+f"(d[62]), "+f"(d[63])
#define ACC64_STR \
    "{%0, %1, %2, %3, %4, %5, %6, %7, %8, %9, %10, %11, %12, %13, %14, %15, " \
    "%16, %17, %18, %19, %20, %21, %22, %23, %24, %25, %26, %27, %28, %29, %30, %31, " \
    "%32, %33, %34, %35, %36, %37, %38, %39, %40, %41, %42, %43, %44, %45, %46, %47, " \
    "%48, %49, %50, %51, %52, %53, %54, %55, %56, %57, %58, %59, %60, %61, %62, %63}"

template <int TB>
__device__ __forceinline__ void wgmma_ss_n128(float (&d)[64], uint64_t da, uint64_t db, int scale_d) {
    asm volatile(
        "{\n.reg .pred p;\nsetp.ne.b32 p, %66, 0;\n"
        "wgmma.mma_async.sync.aligned.m64n128k16.f32.bf16.bf16 " ACC64_STR ", %64, %65, p, 1, 1, 0, %67;\n}\n"
        : ACC64(d) : "l"(da), "l"(db), "r"(scale_d), "n"(TB));
}
__device__ __forceinline__ uint32_t desc_lo(uint32_t addr, uint32_t lbo) { return ((addr & 0x3FFFF) >> 4) | ((lbo >> 4) << 16); }
template <int TB>
__device__ __forceinline__ void wgmma_ss_n128_lo(float (&d)[64], uint32_t da_lo, uint32_t db_lo, int scale_d) {
    asm volatile(
        "{\n.reg .pred p;\n.reg .b64 da, db;\nsetp.ne.b32 p, %66, 0;\n"
        "mov.b64 da, {%64, 0x40000040};\nmov.b64 db, {%65, 0x40000040};\n"
        "wgmma.mma_async.sync.aligned.m64n128k16.f32.bf16.bf16 " ACC64_STR ", da, db, p, 1, 1, 0, %67;\n}\n"
        : ACC64(d) : "r"(da_lo), "r"(db_lo), "r"(scale_d), "n"(TB));
}
__device__ __forceinline__ void wgmma_rs_n128_tb(float (&d)[64], uint32_t a0, uint32_t a1, uint32_t a2, uint32_t a3,
                                                 uint64_t db, int scale_d) {
    asm volatile(
        "{\n.reg .pred p;\nsetp.ne.b32 p, %69, 0;\n"
        "wgmma.mma_async.sync.aligned.m64n128k16.f32.bf16.bf16 " ACC64_STR ", {%64, %65, %66, %67}, %68, p, 1, 1, 1;\n}\n"
        : ACC64(d) : "r"(a0), "r"(a1), "r"(a2), "r"(a3), "l"(db), "r"(scale_d));
}
__device__ __forceinline__ void wgmma_rs_n80(float (&d)[40], const uint32_t (&a)[4], uint32_t db_lo, int scale_d) {
    asm volatile(
        "{\n.reg .pred p;\n.reg .b64 db;\nsetp.ne.b32 p, %45, 0;\nmov.b64 db, {%44, 0x40000040};\n"
        "wgmma.mma_async.sync.aligned.m64n80k16.f32.bf16.bf16 "
        "{%0, %1, %2, %3, %4, %5, %6, %7, %8, %9, %10, %11, %12, %13, %14, %15, %16, %17, %18, %19, %20, %21, %22, %23, %24, %25, %26, %27, %28, %29, %30, %31, %32, %33, %34, %35, %36, %37, %38, %39}, "
        "{%40, %41, %42, %43}, db, p, 1, 1, 0;\n}\n"
        : "+f"(d[0]), "+f"(d[1]), "+f"(d[2]), "+f"(d[3]), "+f"(d[4]), "+f"(d[5]), "+f"(d[6]), "+f"(d[7]), "+f"(d[8]), "+f"(d[9]), "+f"(d[10]), "+f"(d[11]), "+f"(d[12]), "+f"(d[13]), "+f"(d[14]), "+f"(d[15]), "+f"(d[16]), "+f"(d[17]), "+f"(d[18]), "+f"(d[19]), "+f"(d[20]), "+f"(d[21]), "+f"(d[22]), "+f"(d[23]), "+f"(d[24]), "+f"(d[25]), "+f"(d[26]), "+f"(d[27]), "+f"(d[28]), "+f"(d[29]), "+f"(d[30]), "+f"(d[31]), "+f"(d[32]), "+f"(d[33]), "+f"(d[34]), "+f"(d[35]), "+f"(d[36]), "+f"(d[37]), "+f"(d[38]), "+f"(d[39])
        : "r"(a[0]), "r"(a[1]), "r"(a[2]), "r"(a[3]), "r"(db_lo), "r"(scale_d));
}
__device__ __forceinline__ void wgmma_ss_n256_tb(float (&d)[128], uint64_t da, uint64_t db, int scale_d) {
    asm volatile(
        "{\n.reg .pred p;\nsetp.ne.b32 p, %130, 0;\n"
        "wgmma.mma_async.sync.aligned.m64n256k16.f32.bf16.bf16 {%0, %1, %2, %3, %4, %5, %6, %7, %8, %9, %10, %11, %12, %13, %14, %15, %16, %17, %18, %19, %20, %21, %22, %23, %24, %25, %26, %27, %28, %29, %30, %31, %32, %33, %34, %35, %36, %37, %38, %39, %40, %41, %42, %43, %44, %45, %46, %47, %48, %49, %50, %51, %52, %53, %54, %55, %56, %57, %58, %59, %60, %61, %62, %63, %64, %65, %66, %67, %68, %69, %70, %71, %72, %73, %74, %75, %76, %77, %78, %79, %80, %81, %82, %83, %84, %85, %86, %87, %88, %89, %90, %91, %92, %93, %94, %95, %96, %97, %98, %99, %100, %101, %102, %103, %104, %105, %106, %107, %108, %109, %110, %111, %112, %113, %114, %115, %116, %117, %118, %119, %120, %121, %122, %123, %124, %125, %126, %127}, %128, %129, p, 1, 1, 0, 1;\n}\n"
        : "+f"(d[0]), "+f"(d[1]), "+f"(d[2]), "+f"(d[3]), "+f"(d[4]), "+f"(d[5]), "+f"(d[6]), "+f"(d[7]), "+f"(d[8]), "+f"(d[9]), "+f"(d[10]), "+f"(d[11]), "+f"(d[12]), "+f"(d[13]), "+f"(d[14]), "+f"(d[15]), "+f"(d[16]), "+f"(d[17]), "+f"(d[18]), "+f"(d[19]), "+f"(d[20]), "+f"(d[21]), "+f"(d[22]), "+f"(d[23]), "+f"(d[24]), "+f"(d[25]), "+f"(d[26]), "+f"(d[27]), "+f"(d[28]), "+f"(d[29]), "+f"(d[30]), "+f"(d[31]), "+f"(d[32]), "+f"(d[33]), "+f"(d[34]), "+f"(d[35]), "+f"(d[36]), "+f"(d[37]), "+f"(d[38]), "+f"(d[39]), "+f"(d[40]), "+f"(d[41]), "+f"(d[42]), "+f"(d[43]), "+f"(d[44]), "+f"(d[45]), "+f"(d[46]), "+f"(d[47]), "+f"(d[48]), "+f"(d[49]), "+f"(d[50]), "+f"(d[51]), "+f"(d[52]), "+f"(d[53]), "+f"(d[54]), "+f"(d[55]), "+f"(d[56]), "+f"(d[57]), "+f"(d[58]), "+f"(d[59]), "+f"(d[60]), "+f"(d[61]), "+f"(d[62]), "+f"(d[63]), "+f"(d[64]), "+f"(d[65]), "+f"(d[66]), "+f"(d[67]), "+f"(d[68]), "+f"(d[69]), "+f"(d[70]), "+f"(d[71]), "+f"(d[72]), "+f"(d[73]), "+f"(d[74]), "+f"(d[75]), "+f"(d[76]), "+f"(d[77]), "+f"(d[78]), "+f"(d[79]), "+f"(d[80]), "+f"(d[81]), "+f"(d[82]), "+f"(d[83]), "+f"(d[84]), "+f"(d[85]), "+f"(d[86]), "+f"(d[87]), "+f"(d[88]), "+f"(d[89]), "+f"(d[90]), "+f"(d[91]), "+f"(d[92]), "+f"(d[93]), "+f"(d[94]), "+f"(d[95]), "+f"(d[96]), "+f"(d[97]), "+f"(d[98]), "+f"(d[99]), "+f"(d[100]), "+f"(d[101]), "+f"(d[102]), "+f"(d[103]), "+f"(d[104]), "+f"(d[105]), "+f"(d[106]), "+f"(d[107]), "+f"(d[108]), "+f"(d[109]), "+f"(d[110]), "+f"(d[111]), "+f"(d[112]), "+f"(d[113]), "+f"(d[114]), "+f"(d[115]), "+f"(d[116]), "+f"(d[117]), "+f"(d[118]), "+f"(d[119]), "+f"(d[120]), "+f"(d[121]), "+f"(d[122]), "+f"(d[123]), "+f"(d[124]), "+f"(d[125]), "+f"(d[126]), "+f"(d[127])
        : "l"(da), "l"(db), "r"(scale_d));
}
__device__ __forceinline__ void stmatrix_x4(uint32_t addr, uint32_t r0, uint32_t r1, uint32_t r2, uint32_t r3) {
    asm volatile("stmatrix.sync.aligned.m8n8.x4.shared.b16 [%0], {%1, %2, %3, %4};" :: "r"(addr), "r"(r0), "r"(r1), "r"(r2), "r"(r3) : "memory");
}
__device__ __forceinline__ void tma_store_2d(const CUtensorMap* map, uint32_t src, int c0, int c1) {
    asm volatile("cp.async.bulk.tensor.2d.global.shared::cta.bulk_group [%0, {%2, %3}], [%1];"
                 :: "l"((uint64_t)map), "r"(src), "r"(c0), "r"(c1) : "memory");
}
__device__ __forceinline__ float ex2f(float x) { float y; asm("ex2.approx.ftz.f32 %0, %1;" : "=f"(y) : "f"(x)); return y; }
__device__ __forceinline__ uint32_t pack_bf16(float lo, float hi) {
    __nv_bfloat162 v = __floats2bfloat162_rn(lo, hi);
    return *reinterpret_cast<uint32_t*>(&v);
}
__device__ __forceinline__ void mma_16816(float (&c)[4], uint32_t a0, uint32_t a1, uint32_t a2, uint32_t a3,
                                          uint32_t b0, uint32_t b1) {
    asm volatile(
        "mma.sync.aligned.m16n8k16.row.col.f32.bf16.bf16.f32 {%0,%1,%2,%3}, {%4,%5,%6,%7}, {%8,%9}, {%0,%1,%2,%3};"
        : "+f"(c[0]), "+f"(c[1]), "+f"(c[2]), "+f"(c[3])
        : "r"(a0), "r"(a1), "r"(a2), "r"(a3), "r"(b0), "r"(b1));
}
__device__ __forceinline__ void ldmatrix_x4_trans(uint32_t& r0, uint32_t& r1, uint32_t& r2, uint32_t& r3, uint32_t addr) {
    asm volatile("ldmatrix.sync.aligned.m8n8.x4.trans.shared.b16 {%0,%1,%2,%3}, [%4];"
                 : "=r"(r0), "=r"(r1), "=r"(r2), "=r"(r3) : "r"(addr));
}

struct AttnParams {
    CUtensorMap mapQ, mapK, mapV;
    CUtensorMap mapO;
    bf16* out;
};
constexpr int FA_SMEM = 2 * 32768 + 2 * 65536 + 32768 + 1024 + 256;
constexpr int FA_ITEMS = 16 * NH;
__device__ __forceinline__ int fa_qt(int t) { return 15 - ((t & 127) >> 3); }
__device__ __forceinline__ int fa_head(int t) { return (t >> 7) * 8 + (t & 7); }
#define FA_TKA 2
#define FA_SPLIT 11

#define FA_P0 3
#define FA_HO 7
#define FA_LAG 2
#define FA_PK 3
#define FA_ST 4
#define FA_TG 16
#define FA_EARLY 0
#define FA_I0 0
static_assert(FA_GRID <= 104 && FA_HO >= FA_P0 && FA_P0 >= 1, "");
constexpr float FA_MARGIN = 16.f;
#define FAT(b, i)
__device__ __forceinline__ void mbar_arrive_if(uint32_t bar, bool c) {
    asm volatile("{\n.reg .pred p;\nsetp.ne.b32 p, %1, 0;\n@p mbarrier.arrive.shared::cta.b64 _, [%0];\n}" :: "r"(bar), "r"((int)c) : "memory");
}
__device__ __forceinline__ void sched_fence(int v, int id, const float* a, const float* b, const float* c) {
    asm volatile("{\n.reg .pred p;\nsetp.ne.s32 p, %0, %1;\n@p bra SF_SKIP;\nwgmma.wait_group.sync.aligned 0;\n"
                 "st.volatile.shared.f32 [%0], %2;\nst.volatile.shared.f32 [%0], %3;\nst.volatile.shared.f32 [%0], %4;\nst.volatile.shared.f32 [%0], %5;\n"
                 "st.volatile.shared.f32 [%0], %6;\nst.volatile.shared.f32 [%0], %7;\nst.volatile.shared.f32 [%0], %8;\nst.volatile.shared.f32 [%0], %9;\n"
                 "st.volatile.shared.f32 [%0], %10;\nst.volatile.shared.f32 [%0], %11;\nst.volatile.shared.f32 [%0], %12;\nst.volatile.shared.f32 [%0], %13;\n"
                 "exit;\nSF_SKIP:\n}" :: "r"(v), "r"(1000000 + id), "f"(a[0]), "f"(a[1]), "f"(a[2]), "f"(a[3]), "f"(b[0]), "f"(b[1]), "f"(b[2]), "f"(b[3]),
                 "f"(c[0]), "f"(c[1]), "f"(c[2]), "f"(c[3]) : "memory");
}
__device__ __forceinline__ float ex2v(float x) { float y; asm volatile("ex2.approx.ftz.f32 %0, %1;" : "=f"(y) : "f"(x)); return y; }
__device__ __forceinline__ void wgmma_rs_n128_tb_lo(float (&d)[64], const uint32_t* a, uint32_t db_lo, int scale_d) {
    asm volatile(
        "{\n.reg .pred p;\n.reg .b64 db;\nsetp.ne.b32 p, %69, 0;\nmov.b64 db, {%68, 0x40000040};\n"
        "wgmma.mma_async.sync.aligned.m64n128k16.f32.bf16.bf16 " ACC64_STR ", {%64, %65, %66, %67}, db, p, 1, 1, 1;\n}\n"
        : ACC64(d) : "r"(a[0]), "r"(a[1]), "r"(a[2]), "r"(a[3]), "r"(db_lo), "r"(scale_d));
}

__global__ void __launch_bounds__(384, 1) attn_kernel(const __grid_constant__ AttnParams P) {
    extern __shared__ uint8_t smem_raw[];
    constexpr uint32_t sbase = 1024;
    if (smem_u32(smem_raw) > sbase) __trap();
    constexpr uint32_t sQ = sbase;
    constexpr uint32_t sKV = sbase + 65536;
    constexpr uint32_t sO = sKV + 2 * 65536;
    constexpr uint32_t bars = sO + 32768;
    constexpr uint32_t bar_qf = bars, bar_qe = bars + 16, bar_kf = bars + 32, bar_vf = bars + 48, bar_ke = bars + 64, bar_ve = bars + 80,
                   bar_of = bars + 96, bar_oe = bars + 112, slot = bars + 128, oslot = bars + 136;
    const int warp = __shfl_sync(0xffffffff, threadIdx.x >> 5, 0);
    TS_BEGIN(1);
    if (threadIdx.x == 256) {
        asm volatile("prefetch.tensormap [%0];" :: "l"(&P.mapQ) : "memory");
        asm volatile("prefetch.tensormap [%0];" :: "l"(&P.mapK) : "memory");
        for (int i = 0; i < 2; i++) {
            mbar_init(bar_qf + 8 * i, 1); mbar_init(bar_qe + 8 * i, 8); mbar_init(bar_kf + 8 * i, 1); mbar_init(bar_vf + 8 * i, 1);
            mbar_init(bar_ke + 8 * i, 8); mbar_init(bar_ve + 8 * i, 8); mbar_init(bar_of + 8 * i, 4); mbar_init(bar_oe + 8 * i, 1);
        }
        asm volatile("fence.mbarrier_init.release.cluster;" ::: "memory");
    }
    __syncthreads();
    pdl_launch_dependents();
    if (warp >= 8) {
        asm volatile("setmaxnreg.dec.sync.aligned.u32 40;");
        if (threadIdx.x == 288 || threadIdx.x == 320) {
            const int wg = threadIdx.x == 288 ? 0 : 1;
            const uint32_t stg = sO + wg * 16384;
            for (int n = 0;; n++) {
                mbar_wait(bar_of + 8 * wg, n & 1);
                int t;
                asm volatile("ld.shared.s32 %0, [%1];" : "=r"(t) : "r"(oslot + wg * 4) : "memory");
                const int qt = fa_qt(t), h = fa_head(t & 1023);
                tma_store_2d(&P.mapO, stg, 0, h * SEQ + qt * 128 + wg * 64);
                tma_store_2d(&P.mapO, stg + 8192, 64, h * SEQ + qt * 128 + wg * 64);
                asm volatile("cp.async.bulk.commit_group;" ::: "memory");
                asm volatile("cp.async.bulk.wait_group.read 0;" ::: "memory");
                mbar_arrive(bar_oe + 8 * wg);
                asm volatile("cp.async.bulk.wait_group 0;" ::: "memory");
                signal_ctr(CT_CA + qt * 4 + (h >> 3));
                if (t >= 1024) break;
            }
        }
        if (threadIdx.x == 256) {
            int b = 0, hp_ready = 0, vrow = 0, t = blockIdx.x;
            auto load_v = [&](int i) {
                const uint32_t sv = sKV + (i & 1) * 65536 + 32768, bar = bar_vf + 8 * (i & 1);
                mbar_wait(bar_ve + 8 * (i & 1), ((i >> 1) & 1) ^ 1);
                mbar_expect_tx(bar, 32768);
                tma_load_2d(sv, &P.mapV, bar, 0, vrow);
                tma_load_2d(sv + 16384, &P.mapV, bar, 64, vrow);
            };
            for (int item = 0;; item++) {
                const bool valid = t < FA_ITEMS;
                const int qt = fa_qt(t), h = fa_head(t);
                if (valid && !((hp_ready >> (h >> 1)) & 1)) { wait_ctr(CT_AP + (h >> 1), 96u); hp_ready |= 1 << (h >> 1); }
                const uint32_t bq = bar_qf + 8 * (item & 1);
                mbar_wait(bar_qe + 8 * (item & 1), ((item >> 1) & 1) ^ 1);
                asm volatile("st.shared.s32 [%0], %1;" :: "r"(slot + (item & 1) * 4), "r"(valid ? t : -1) : "memory");
                if (!valid) { mbar_arrive(bq); break; }
                mbar_expect_tx(bq, 32768);
                tma_load_2d(sQ + (item & 1) * 32768, &P.mapQ, bq, 0, h * SEQ + qt * 128);
                tma_load_2d(sQ + (item & 1) * 32768 + 16384, &P.mapQ, bq, 64, h * SEQ + qt * 128);
#pragma unroll 1
                for (int j = 0; j <= qt; j++, b++) {
                    const uint32_t sk = sKV + (b & 1) * 65536, bar = bar_kf + 8 * (b & 1);
                    mbar_wait(bar_ke + 8 * (b & 1), ((b >> 1) & 1) ^ 1);
                    if (b == 2) wait_ctr(CT_GATE, 64u);
                    mbar_expect_tx(bar, 32768);
                    tma_load_2d(sk, &P.mapK, bar, 0, h * SEQ + j * 128);
                    tma_load_2d(sk + 16384, &P.mapK, bar, 64, h * SEQ + j * 128);
                    if (j == max(qt - FA_TKA, 0)) t = take_ticket(CT_ATTN);
                    if (b > 0) load_v(b - 1);
                    vrow = h * SEQ + j * 128;
                }
                t += gridDim.x;
            }
            load_v(b - 1);
        }
    } else {
        asm volatile("setmaxnreg.inc.sync.aligned.u32 232;");
        const int wg = warp >> 2;
        const int lane = threadIdx.x & 31;
        const float sc = 0.08838834764831845f * 1.4426950408889634f;
        const int r0 = wg * 64 + (warp & 3) * 16 + (lane >> 2);
        float o[64], s[64];
        uint32_t pa[32];
        float m0 = 0.f, m1 = 0.f, l0 = 0.f, l1 = 0.f, i0 = 0.f, i1 = 0.f, g0 = 0.f, g1 = 0.f;
        const uint32_t q_lo = desc_lo(sQ + wg * 8192, 16), k_lo = desc_lo(sKV, 16), v_lo = desc_lo(sKV + 32768, 16384);
        auto issue_qk = [&](int b, int item) {
            const uint32_t qd = q_lo + (item & 1) * 2048, kd = k_lo + (b & 1) * 4096;
            wgmma_fence();
#pragma unroll
            for (int kk = 0; kk < 8; kk++) wgmma_ss_n128_lo<0>(s, qd + (kk >> 2) * 1024 + (kk & 3) * 2, kd + (kk >> 2) * 1024 + (kk & 3) * 2, kk != 0);
            wgmma_commit();
        };
        auto issue_pv = [&](int b, bool acc, int n) {
            const uint32_t vd = v_lo + (b & 1) * 4096;
            mbar_wait(bar_vf + 8 * (b & 1), (b >> 1) & 1);
            wgmma_fence();
#pragma unroll
            for (int kk = 0; kk < 8; kk++) if (kk < n) wgmma_rs_n128_tb_lo(o, &pa[kk * 4], vd + kk * 128, kk ? 1 : (int)acc);
            wgmma_commit();
        };
        const int lim = r0 - (lane & 3) * 2;
        int item = -1, tnext = 0;
        uint32_t k_ready = 0, q_ready = 0;
        auto mask = [&](int i) { if ((i >> 2) * 8 + (i & 1) - ((i & 2) ? 8 : 0) > lim) s[i] = -INFINITY; };
        auto exps = [&](auto mode, int b, bool hand_over, float& u0, float& u1) {
            constexpr int MODE = decltype(mode)::value;
            float p[64], u[4] = {0.f, 0.f, 0.f, 0.f};
            const uint32_t vd = v_lo + ((b - 1) & 1) * 4096;
#pragma unroll
            for (int i = 0; i < 4; i++) p[i] = fmaf(s[i], sc, (i & 2) ? -m1 : -m0);
#pragma unroll
            for (int g = 0; g < 16 + FA_LAG; g++) {
                if (MODE && g >= FA_I0 && g - FA_I0 < 8 - FA_P0) {
                    const int kk = FA_P0 + g - FA_I0;
                    wgmma_fence();
                    wgmma_rs_n128_tb_lo(o, &pa[kk * 4], vd + kk * 128, 1);
                    wgmma_commit();
                    if (kk == FA_HO) asm volatile("{\n.reg .pred p;\nsetp.ne.b32 p, %1, 0;\n@p bar.arrive %0, 256;\n}" :: "r"(2 - wg), "r"((int)hand_over) : "memory");
                }
                if (MODE && g == FA_SPLIT) {
                    FAT(b, 2);
                    wgmma_wait<0>();
                    FAT(b - 1, 3);
                    mbar_arrive_if(bar_ve + 8 * ((b - 1) & 1), lane == 0);
                }
                if (MODE && g == FA_TG) {
                    k_ready = mbar_test(bar_kf + 8 * (~b & 1), ((b + 1) >> 1) & 1);
                    if (MODE == 2) {
                        q_ready = mbar_test(bar_qf + 8 * (~item & 1), ((item + 1) >> 1) & 1);
                        asm volatile("ld.shared.s32 %0, [%1];" : "=r"(tnext) : "r"(slot + (~item & 1) * 4) : "memory");
                    }
                }
#pragma unroll
                for (int j = 0; j < 4; j++) {
                    const int i = g * 4 + j;
                    if (g < 16) p[i] = ex2v(p[i]);
                    if (g < 15) {
                        if (MODE == 2) mask(i + 4);
                        p[i + 4] = fmaf(s[i + 4], sc, (i & 2) ? -m1 : -m0);
                    }
                    if (g >= FA_LAG) u[j] += p[i - FA_LAG * 4];
                }
#pragma unroll
                for (int gg = 0; gg < 16; gg++) {
                    const int at = MODE && gg + FA_LAG < FA_SPLIT + gg / FA_PK ? FA_SPLIT + gg / FA_PK : gg + FA_LAG;
                    if (at == g) { pa[gg * 2] = pack_bf16(p[gg * 4], p[gg * 4 + 1]); pa[gg * 2 + 1] = pack_bf16(p[gg * 4 + 2], p[gg * 4 + 3]); }
                }
                if (MODE && g < 16) sched_fence(b, g + MODE * 32, &p[g * 4], &p[(g < 15 ? g + 1 : g) * 4], u);
            }
            u0 = u[0] + u[1]; u1 = u[2] + u[3];
        };
        auto quad_max = [&](float& x0, float& x1) {
            x0 = fmaxf(x0, __shfl_xor_sync(0xffffffff, x0, 1)); x1 = fmaxf(x1, __shfl_xor_sync(0xffffffff, x1, 1));
            x0 = fmaxf(x0, __shfl_xor_sync(0xffffffff, x0, 2)); x1 = fmaxf(x1, __shfl_xor_sync(0xffffffff, x1, 2));
            x0 = fmaf(x0, sc, FA_MARGIN); x1 = fmaf(x1, sc, FA_MARGIN);
        };
        auto softmax_exact = [&](bool fresh, int b) {
            wgmma_wait<0>();
            float x[8];
#pragma unroll
            for (int i = 0; i < 8; i++) x[i] = fmaxf(s[i * 2], s[i * 2 + 1]);
#pragma unroll
            for (int i = 8; i < 32; i++) x[i & 7] = fmaxf(x[i & 7], fmaxf(s[i * 2], s[i * 2 + 1]));
            float x0 = fmaxf(fmaxf(x[0], x[2]), fmaxf(x[4], x[6])), x1 = fmaxf(fmaxf(x[1], x[3]), fmaxf(x[5], x[7]));
            quad_max(x0, x1);
            if (!fresh) {
                x0 = fmaxf(x0, m0); x1 = fmaxf(x1, m1);
                const float a0 = ex2f(m0 - x0), a1 = ex2f(m1 - x1);
                l0 *= a0; l1 *= a1;
#pragma unroll
                for (int i = 0; i < 16; i++) { o[i * 4 + 0] *= a0; o[i * 4 + 1] *= a0; o[i * 4 + 2] *= a1; o[i * 4 + 3] *= a1; }
            }
            m0 = x0; m1 = x1;
            float u0, u1;
            exps(std::integral_constant<int, 0>(), b, false, u0, u1);
            l0 += u0; l1 += u1;
        };
        auto finish_rows = [&]() {
            l0 += __shfl_xor_sync(0xffffffff, l0, 1); l1 += __shfl_xor_sync(0xffffffff, l1, 1);
            l0 += __shfl_xor_sync(0xffffffff, l0, 2); l1 += __shfl_xor_sync(0xffffffff, l1, 2);
            i0 = __fdividef(g0, l0); i1 = __fdividef(g1, l1);
        };
        auto clear_out = [&](int t) {
            if (t >= 384) {
                bf16* z = P.out + (size_t)(fa_qt(t) * 128 + wg * 64 + ((threadIdx.x & 127) >> 3)) * DM + (t & 7) * 64 + (lane & 7) * 8;
#pragma unroll
                for (int i = 0; i < 4; i++) *reinterpret_cast<uint4*>(z + i * 16 * DM) = make_uint4(0u, 0u, 0u, 0u);
            }
        };
        auto store_o = [&](int t, int n, int c0, int c1) {
            const uint32_t stg = sO + wg * 16384;
            if (c0 == 0) {
                mbar_wait(bar_oe + 8 * wg, (n & 1) ^ 1);
                asm volatile("st.shared.s32 [%0], %1;" :: "r"(oslot + wg * 4), "r"(t) : "memory");
            }
            const int row = (warp & 3) * 16 + (lane >> 2);
#pragma unroll
            for (int i = c0; i < c1; i++) {
                const int ch = i * 4 + (lane & 3);
                const uint32_t a = stg + (ch >> 3) * 8192 + row * 128 + (((ch & 7) ^ (row & 7)) << 4);
                const float* q = &o[i * 16];
                asm volatile("st.shared.v4.b32 [%0], {%1, %2, %3, %4};" :: "r"(a), "r"(pack_bf16(q[0] * i0, q[1] * i0)), "r"(pack_bf16(q[4] * i0, q[5] * i0)),
                             "r"(pack_bf16(q[8] * i0, q[9] * i0)), "r"(pack_bf16(q[12] * i0, q[13] * i0)) : "memory");
                asm volatile("st.shared.v4.b32 [%0], {%1, %2, %3, %4};" :: "r"(a + 1024), "r"(pack_bf16(q[2] * i1, q[3] * i1)), "r"(pack_bf16(q[6] * i1, q[7] * i1)),
                             "r"(pack_bf16(q[10] * i1, q[11] * i1)), "r"(pack_bf16(q[14] * i1, q[15] * i1)) : "memory");
            }
        };
        auto publish_o = [&]() {
            asm volatile("fence.proxy.async.shared::cta;" ::: "memory");
            __syncwarp();
            mbar_arrive_if(bar_of + 8 * wg, lane == 0);
        };
        int t = 0, left = 0, tdone = -1, b = 0, nout = 0;
        bool first = true, staged = false;
        if (wg == 1) asm volatile("bar.arrive 1, 256;" ::: "memory");
#pragma unroll 1
        for (;; b++) {
            const bool fresh = left == 0;
            const int tprev = t;
            FAT(b, 4);
            if (staged) { publish_o(); staged = false; }
            if (fresh) {
                item++;
                if (!q_ready) {
                    mbar_wait(bar_qf + 8 * (item & 1), (item >> 1) & 1);
                    asm volatile("ld.shared.s32 %0, [%1];" : "=r"(tnext) : "r"(slot + (item & 1) * 4) : "memory");
                }
                if (tnext < 0) break;
                t = tnext;
                left = fa_qt(t) + 1;
            }
            left--;
            if (tdone >= 0) store_o(tdone, nout, 0, FA_ST);
            FAT(b, 5);
            if (!k_ready) mbar_wait(bar_kf + 8 * (b & 1), (b >> 1) & 1);
            FAT(b, 6);
            asm volatile("bar.sync %0, 256;" :: "r"(1 + wg) : "memory");
            FAT(b, 0);
            issue_qk(b, item);
            bool early = false;
            if (!fresh && !first && left != 0) {
                issue_pv(b - 1, true, FA_P0);
                wgmma_wait<1>();
                FAT(b, 1);
                mbar_arrive_if(bar_ke + 8 * (b & 1), lane == 0);
            } else {
                early = (FA_EARLY && tdone >= 0) || b == 0;
                if (early) asm volatile("bar.arrive %0, 256;" :: "r"(2 - wg) : "memory");
                if (tdone >= 0) { wgmma_wait<1>(); store_o(tdone, nout++, FA_ST, 4); staged = true; }
                tdone = -1;
                if (fresh && b > 0) { finish_rows(); tdone = tprev; l0 = l1 = 0.f; }
                if (left == 0) { g0 = __ldcg(g_gate + fa_qt(t) * 128 + r0); g1 = __ldcg(g_gate + fa_qt(t) * 128 + r0 + 8); clear_out(t); }
                if (b > 0) issue_pv(b - 1, !first, FA_P0); else wgmma_commit();
                first = fresh;
                wgmma_wait<1>();
                FAT(b, 1);
                mbar_arrive_if(bar_ke + 8 * (b & 1), lane == 0);
                mbar_arrive_if(bar_qe + 8 * (item & 1), lane == 0 && left == 0);
                if (left == 0) { mask(0); mask(1); }
                if (fresh) { m0 = fmaxf(s[0], s[1]); m1 = fmaxf(s[2], s[3]); quad_max(m0, m1); }
            }
            if (b > 0) {
                float u0, u1;
                if (left == 0) exps(std::integral_constant<int, 2>(), b, !early, u0, u1);
                else exps(std::integral_constant<int, 1>(), b, !early, u0, u1);
                if (!__any_sync(0xffffffff, !(u0 + u1 < 1.f))) { l0 += u0; l1 += u1; continue; }
            }
            softmax_exact(fresh, b);
        }
        if (tdone >= 0) { store_o(tdone, nout++, 0, 4); publish_o(); }
        issue_pv(b - 1, !first, 8);
        finish_rows();
        wgmma_wait<0>();
        store_o(t + 1024, nout, 0, 4);
        publish_o();
        TS_END(1);
    }
}

__device__ __forceinline__ uint32_t cluster_ctarank() {
    uint32_t r; asm volatile("mov.u32 %0, %%cluster_ctarank;" : "=r"(r)); return r;
}
__device__ __forceinline__ uint32_t mapa_u32(uint32_t addr, uint32_t rank) {
    uint32_t r; asm volatile("mapa.shared::cluster.u32 %0, %1, %2;" : "=r"(r) : "r"(addr), "r"(rank)); return r;
}
__device__ __forceinline__ void cluster_sync_all() {
    asm volatile("barrier.cluster.arrive.release.aligned;\nbarrier.cluster.wait.acquire.aligned;" ::: "memory");
}
__device__ __forceinline__ void st_async_v4(uint32_t addr, uint32_t a, uint32_t b, uint32_t c, uint32_t d, uint32_t mbar) {
    asm volatile("st.async.weak.shared::cluster.mbarrier::complete_tx::bytes.v4.b32 [%0], {%1, %2, %3, %4}, [%5];"
                 :: "r"(addr), "r"(a), "r"(b), "r"(c), "r"(d), "r"(mbar) : "memory");
}
__device__ __forceinline__ void st_async_v2(uint32_t addr, uint32_t a, uint32_t b, uint32_t mbar) {
    asm volatile("st.async.weak.shared::cluster.mbarrier::complete_tx::bytes.v2.b32 [%0], {%1, %2}, [%3];"
                 :: "r"(addr), "r"(a), "r"(b), "r"(mbar) : "memory");
}
__device__ __forceinline__ void st_async_b32(uint32_t addr, uint32_t a, uint32_t mbar) {
    asm volatile("st.async.weak.shared::cluster.mbarrier::complete_tx::bytes.b32 [%0], %1, [%2];" :: "r"(addr), "r"(a), "r"(mbar) : "memory");
}
__device__ __forceinline__ void pace(int cycles) {
    if (cycles > 0) {
        uint32_t t0, t;
        asm volatile("mov.u32 %0, %%clock;" : "=r"(t0));
        do { asm volatile("mov.u32 %0, %%clock;" : "=r"(t)); } while (t - t0 < (uint32_t)cycles);
    }
}
__device__ __forceinline__ void mbar_wait_cl(uint32_t bar, uint32_t parity) {
    uint32_t done = 0;
    for (int it = 0; it < WAIT_LIMIT && !done; it++) {
        asm volatile(
            "{\n.reg .pred p;\n"
            "mbarrier.try_wait.parity.shared::cta.b64 p, [%1], %2;\n"
            "selp.u32 %0, 1, 0, p;\n}\n" : "=r"(done) : "r"(bar), "r"(parity) : "memory");
    }
}
__device__ __forceinline__ void ldmatrix_x4(uint32_t& r0, uint32_t& r1, uint32_t& r2, uint32_t& r3, uint32_t addr) {
    asm volatile("ldmatrix.sync.aligned.m8n8.x4.shared.b16 {%0,%1,%2,%3}, [%4];"
                 : "=r"(r0), "=r"(r1), "=r"(r2), "=r"(r3) : "r"(addr));
}
__device__ __forceinline__ void cp_async16(uint32_t dst, const void* src) {
    asm volatile("cp.async.cg.shared.global [%0], [%1], 16;" :: "r"(dst), "l"(src) : "memory");
}
__device__ __forceinline__ float bf16r(float x) { return __uint_as_float(pack_bf16(0.f, x) & 0xffff0000u); }

#define DBGP(i, w, ok)
#define DBG(i, w)
#define DBGD(i, w, dep)
#define DBG_EXTRA 0
__device__ __forceinline__ void tma_load_2d_mc(uint32_t dst, const CUtensorMap* map, uint32_t bar, int c0, int c1, uint16_t mask) {
    asm volatile(
        "cp.async.bulk.tensor.2d.shared::cluster.global.mbarrier::complete_tx::bytes.multicast::cluster [%0], [%1, {%3, %4}], [%2], %5;"
        :: "r"(dst), "l"((uint64_t)map), "r"(bar), "r"(c0), "r"(c1), "h"(mask) : "memory");
}
__device__ __forceinline__ void stmatrix_x4_trans(uint32_t addr, uint32_t r0, uint32_t r1, uint32_t r2, uint32_t r3) {
    asm volatile("stmatrix.sync.aligned.m8n8.x4.trans.shared.b16 [%0], {%1, %2, %3, %4};" :: "r"(addr), "r"(r0), "r"(r1), "r"(r2), "r"(r3) : "memory");
}
__device__ __forceinline__ void stmatrix_x2_trans(uint32_t addr, uint32_t r0, uint32_t r1) {
    asm volatile("stmatrix.sync.aligned.m8n8.x2.trans.shared.b16 [%0], {%1, %2};" :: "r"(addr), "r"(r0), "r"(r1) : "memory");
}
__device__ __forceinline__ uint4 lds128(uint32_t a) {
    uint4 v; asm volatile("ld.shared.v4.u32 {%0, %1, %2, %3}, [%4];" : "=r"(v.x), "=r"(v.y), "=r"(v.z), "=r"(v.w) : "r"(a) : "memory"); return v;
}
__device__ __forceinline__ void sts128(uint32_t a, uint32_t x, uint32_t y, uint32_t z, uint32_t w) {
    asm volatile("st.shared.v4.b32 [%0], {%1, %2, %3, %4};" :: "r"(a), "r"(x), "r"(y), "r"(z), "r"(w) : "memory");
}
__device__ __forceinline__ float2 lds64f(uint32_t a) {
    float2 v; asm volatile("ld.shared.v2.f32 {%0, %1}, [%2];" : "=f"(v.x), "=f"(v.y) : "r"(a) : "memory"); return v;
}
__device__ __forceinline__ void fence_async_smem() { asm volatile("fence.proxy.async.shared::cta;" ::: "memory"); }
#define ACC16(d) "+f"(d[0]), "+f"(d[1]), "+f"(d[2]), "+f"(d[3]), "+f"(d[4]), "+f"(d[5]), "+f"(d[6]), "+f"(d[7]), "+f"(d[8]), "+f"(d[9]), "+f"(d[10]), "+f"(d[11]), "+f"(d[12]), "+f"(d[13]), "+f"(d[14]), "+f"(d[15])
template <int ND>
__device__ __forceinline__ void wgmma_rs_n32(float (&d)[ND], const uint32_t (&a)[4], uint32_t db_lo, int scale_d) {
    asm volatile(
        "{\n.reg .pred p;\n.reg .b64 db;\nsetp.ne.b32 p, %21, 0;\nmov.b64 db, {%20, 0x40000040};\n"
        "wgmma.mma_async.sync.aligned.m64n32k16.f32.bf16.bf16 {%0,%1,%2,%3,%4,%5,%6,%7,%8,%9,%10,%11,%12,%13,%14,%15}, {%16,%17,%18,%19}, db, p, 1, 1, 0;\n}\n"
        : ACC16(d) : "r"(a[0]), "r"(a[1]), "r"(a[2]), "r"(a[3]), "r"(db_lo), "r"(scale_d));
}
template <int ND>
__device__ __forceinline__ void wgmma_ss_n32(float (&d)[ND], uint32_t da_lo, uint32_t db_lo, int scale_d) {
    asm volatile(
        "{\n.reg .pred p;\n.reg .b64 da, db;\nsetp.ne.b32 p, %18, 0;\nmov.b64 da, {%16, 0x40000040};\nmov.b64 db, {%17, 0x40000040};\n"
        "wgmma.mma_async.sync.aligned.m64n32k16.f32.bf16.bf16 {%0,%1,%2,%3,%4,%5,%6,%7,%8,%9,%10,%11,%12,%13,%14,%15}, da, db, p, 1, 1, 1, 0;\n}\n"
        : ACC16(d) : "r"(da_lo), "r"(db_lo), "r"(scale_d));
}
__device__ __forceinline__ void wgmma_ss_n8(float (&d)[4], uint32_t da_lo, uint32_t db_lo, int scale_d) {
    asm volatile(
        "{\n.reg .pred p;\n.reg .b64 da, db;\nsetp.ne.b32 p, %6, 0;\nmov.b64 da, {%4, 0x40000040};\nmov.b64 db, {%5, 0x00000010};\n"
        "wgmma.mma_async.sync.aligned.m64n8k16.f32.bf16.bf16 {%0,%1,%2,%3}, da, db, p, 1, 1, 1, 0;\n}\n"
        : "+f"(d[0]), "+f"(d[1]), "+f"(d[2]), "+f"(d[3]) : "r"(da_lo), "r"(db_lo), "r"(scale_d));
}

#define SCHED_FENCE()
__device__ __forceinline__ void wgmma_ss_n32_p(float (&d)[16], uint32_t da_lo, uint32_t db_lo, int scale_d) {
    asm volatile(
        "{\n.reg .pred p;\n.reg .b64 da, db;\nsetp.ne.b32 p, %18, 0;\nmov.b64 da, {%16, 0x40000040};\nmov.b64 db, {%17, 0x00000030};\n"
        "wgmma.mma_async.sync.aligned.m64n32k16.f32.bf16.bf16 {%0,%1,%2,%3,%4,%5,%6,%7,%8,%9,%10,%11,%12,%13,%14,%15}, da, db, p, 1, 1, 1, 0;\n}\n"
        : ACC16(d) : "r"(da_lo), "r"(db_lo), "r"(scale_d));
}

#define ACC20(d) ACC16(d), "+f"(d[16]), "+f"(d[17]), "+f"(d[18]), "+f"(d[19])
#define ACC20_STR "{%0,%1,%2,%3,%4,%5,%6,%7,%8,%9,%10,%11,%12,%13,%14,%15,%16,%17,%18,%19}"
__device__ __forceinline__ void wgmma_rs_n40(float (&d)[20], const uint32_t (&a)[4], uint32_t db_lo, int scale_d) {
    asm volatile(
        "{\n.reg .pred p;\n.reg .b64 db;\nsetp.ne.b32 p, %25, 0;\nmov.b64 db, {%24, 0x40000040};\n"
        "wgmma.mma_async.sync.aligned.m64n40k16.f32.bf16.bf16 " ACC20_STR ", {%20,%21,%22,%23}, db, p, 1, 1, 0;\n}\n"
        : ACC20(d) : "r"(a[0]), "r"(a[1]), "r"(a[2]), "r"(a[3]), "r"(db_lo), "r"(scale_d));
}
template <int TA, int SBO>
__device__ __forceinline__ void wgmma_ss_n40(float (&d)[20], uint32_t da_lo, uint32_t db_lo, int scale_d) {
    asm volatile(
        "{\n.reg .pred p;\n.reg .b64 da, db;\nsetp.ne.b32 p, %22, 0;\nmov.b64 da, {%20, %23};\nmov.b64 db, {%21, 0x40000040};\n"
        "wgmma.mma_async.sync.aligned.m64n40k16.f32.bf16.bf16 " ACC20_STR ", da, db, p, 1, 1, %24, 0;\n}\n"
        : ACC20(d) : "r"(da_lo), "r"(db_lo), "r"(scale_d), "n"(0x40000000 + SBO / 16), "n"(TA));
}

#define PT(i, th)
struct ChainParams {
    CUtensorMap mapW[3];
    CUtensorMap mapX;
    CUtensorMap mapC;
};
constexpr int CH_BLOCK = 384;
constexpr int CO_WO = 0;
constexpr int CH_XC = 5120, CH_XP = 8 * CH_XC;
constexpr int CO_XB = 65536;
constexpr int CO_OB = CO_XB + 2 * CH_XP;
constexpr int CO_P = CO_OB + 8192;
constexpr int CO_LS = CO_P + 3072;
constexpr int CO_SC = CO_LS + 8 * 1280;
constexpr int CH_TW = 6144 + 8192;
constexpr int CO_T = 21 * 8192;
constexpr int CO_WA = CO_T + 6144;
constexpr int CO_ST = CO_T + 3 * CH_TW + 6144;
constexpr int CO_OWN = CO_ST + 4096, CO_OWN2 = CO_SC + 1536;
constexpr int CO_BAR = CO_OWN + 4096;
constexpr int CH_SMEM = CO_BAR + 256 + DBG_EXTRA;
#define CH_NSM 4
static_assert(CO_OWN2 + 1024 <= CO_T && CH_NSM <= 4, "smem layout");
#define CH_POLL_DELAY 200
#define CH_VPOS 2
#define CH_OW 8
#define CH_OF 12
#define CH_Q1 10
#define CH_VA 5
#define CH_SPOS 0
#define CH_LSW 1
#define CH_QE 32
#define CH_KE 32
#define CH_QD 0
#define CH_GAP 45
#define CH_QS 16
#define CH_KS 10
#define CH_VS 0
#define CH_A7 7
#define CH_HA 15
#define CH_LD 4
#define CH_TWP 0
#define CH_CHAINS 4

constexpr float CH_SC = 0.08838834764831845f * 1.4426950408889634f;
__device__ __forceinline__ uint32_t pin(uint32_t v) { return __shfl_sync(0xffffffff, v, threadIdx.x & 31); }

__global__ void __cluster_dims__(8, 1, 1) __launch_bounds__(CH_BLOCK, 1)
chain_kernel(const __grid_constant__ ChainParams P, const bf16* __restrict__ mem0, const bf16* __restrict__ Wo, const bf16* __restrict__ x,
             const bf16* __restrict__ gate_w) {
    extern __shared__ uint8_t smem_raw[];
    const int tid = threadIdx.x, warp = __shfl_sync(0xffffffff, tid >> 5, 0), lane = tid & 31;
    const int rank = (int)cluster_ctarank();
    constexpr uint32_t sd = 1024;
    const uint32_t sb = ((uint32_t)rank << 24) + sd;
    if (smem_u32(smem_raw) != sb) __trap();
    const int C = blockIdx.x >> 3;
    const int h = C * 4 + (rank >> 1);
    const int qd = lane >> 2, qc = lane & 3;
    const int t4 = warp & 3, wg = warp >> 2;
    pdl_launch_dependents();
    TS_BEGIN(2);
    PT(0, 0);
    const uint32_t bar_mem = sb + CO_BAR, bar_o = bar_mem + 32, bar_sc = bar_o + 32, bar_x = bar_sc + 8, bar_l = bar_x + 16, bar_w = bar_l + 8;
    if (tid == 0) {
        for (int j = 0; j < 15; j++) mbar_init(bar_mem + 8 * j, 1);
        sts128(bar_mem + 128, 0xffff0000u, 0u, 0u, 0u);
        asm volatile("fence.mbarrier_init.release.cluster;" ::: "memory");
    }
    __syncthreads();
    auto chunk = [&](int i) { return (uint32_t)((rank - (i >> 1) - 4 * (i & 1)) & 7); };
    if ((tid & 127) == 0) {
        mbar_expect_tx(bar_w + 8 * wg, 65536);
        for (int i = 0; i < 8; i++)
            tma_load_2d(sb + (i ? (wg * 7 + i - 1) * 8192 : CO_WA + wg * CH_TW), &P.mapW[wg], bar_w + 8 * wg, h * HD + (rank & 1) * 64, chunk(i) * 64);
    }
    PT(1, 0);
    {
        for (int i = tid; i < 512; i += CH_BLOCK) asm volatile("prefetch.global.L2 [%0];" :: "l"(Wo + (size_t)(C * 512 + i) * DM + rank * 64));
        if (tid < 64) asm volatile("prefetch.global.L2 [%0];" :: "l"(x + (size_t)tid * DM + rank * 64));
    }
    if (tid < 256) {
        const int r = blockIdx.x * 32 + (tid >> 3);
        float sum = 0.f;
#pragma unroll
        for (int c = 0; c < 8; c++) {
            const int col = c * 64 + (tid & 7) * 8;
            const uint4 xv = __ldg(reinterpret_cast<const uint4*>(x + (size_t)r * DM + col));
            const uint4 gv = __ldg(reinterpret_cast<const uint4*>(gate_w + col));
            const bf16* xp = reinterpret_cast<const bf16*>(&xv);
            const bf16* gp = reinterpret_cast<const bf16*>(&gv);
#pragma unroll
            for (int e = 0; e < 8; e++) sum += bf16r(__bfloat162float(xp[e]) * __bfloat162float(gp[e]));
        }
        sum += __shfl_xor_sync(0xffffffff, sum, 1);
        sum += __shfl_xor_sync(0xffffffff, sum, 2);
        sum += __shfl_xor_sync(0xffffffff, sum, 4);
        if ((tid & 7) == 0) g_gate[r] = bf16r(1.f / (1.f + __expf(-bf16r(sum))));
        *reinterpret_cast<uint2*>(g_xbuf + (tid >> 7) * 16384 + (size_t)rank * 2048 + C * 256 + (tid & 127) * 2) = make_uint2(~0u, ~0u);
        asm volatile("bar.sync 1, 256;" ::: "memory");
        if (tid == 32) signal_ctr_generic(CT_GATE);
    }
    const uint32_t wfrag = (((lane >> 4) << 3) + (lane & 7)) * 128 + (((t4 * 2 + ((lane >> 3) & 1)) ^ (lane & 7)) << 4);
    const uint32_t aO = pin(sb + wg * CH_TW + wfrag);
    const uint32_t aL = pin(sb + lane * 16);
    uint32_t w[32][4];
    PT(2, 0);
    mbar_wait(bar_w + 8 * wg, 0);
    PT(3, 0); PT(4, 256);
#pragma unroll
    for (int e = CH_NSM; e < 32; e++)
        ldmatrix_x4_trans(w[e][0], w[e][1], w[e][2], w[e][3], e < 4 ? aO + CO_WA + e * 2048 : sb + wg * 7 * 8192 + wfrag + (e - 4) * 2048);
    fence_async_smem();
    __syncthreads();
    PT(5, 0);
    if (tid == 0) {
        fence_async_smem();
        for (int b = 0; b < 2; b++) {
            mbar_expect_tx(bar_x + 8 * b, 32768);
            for (int i = 0; i < 8; i++) tma_load_2d(sb + CO_XB + b * CH_XP + i * CH_XC, &P.mapX, bar_x + 8 * b, i * 64, b * SEGL);
        }
    }
#pragma unroll 2
    for (int i = tid; i < 512 * 4; i += CH_BLOCK) {
        const int r = i >> 2, cg = i & 3, ks = r >> 4, kp = r & 15;
        const int src = (rank - (ks >> 2)) & 7;
        const uint4* p = reinterpret_cast<const uint4*>(Wo + (size_t)(C * 512 + src * 64 + (ks & 3) * 16 + (kp >> 2) * 2 + (kp & 1) + (kp & 2) * 4) * DM + rank * 64 + cg * 16);
        const uint4 u0 = __ldg(p), u1 = __ldg(p + 1);
        const uint32_t a = sb + CO_WO + r * 128;
        sts128(a + (((cg * 2) ^ (r & 7)) << 4), __byte_perm(u0.x, u0.y, 0x5410), __byte_perm(u0.z, u0.w, 0x5410), __byte_perm(u1.x, u1.y, 0x5410), __byte_perm(u1.z, u1.w, 0x5410));
        sts128(a + (((cg * 2 + 1) ^ (r & 7)) << 4), __byte_perm(u0.x, u0.y, 0x7632), __byte_perm(u0.z, u0.w, 0x7632), __byte_perm(u1.x, u1.y, 0x7632), __byte_perm(u1.z, u1.w, 0x7632));
    }
#pragma unroll 1
    for (int i = tid; i < 512; i += CH_BLOCK) {
        const int n = i >> 6, c = i & 63;
        const uint4 u = __ldg(reinterpret_cast<const uint4*>(mem0 + n * DM + c * 8));
        sts128(sb + CO_XB + (c >> 3) * CH_XC + 4096 + n * 128 + (((c & 7) ^ n) << 4), u.x, u.y, u.z, u.w);
    }
    if (tid < 128) sts128(sb + CO_T + (2 + (tid >> 6)) * CH_TW + 5120 + (tid & 63) * 16, 0u, 0u, 0u, 0u);
    else if (tid < 160) sts128(sb + CO_P + ((tid >> 3) & 3) * 768 + 640 + (tid & 7) * 16, 0u, 0u, 0u, 0u);
    fence_async_smem();
    TS_END(6);
    PT(6, 0);
    auto pass = [&](auto& d, int g, int b, int j0, int j1, int js) {
        const uint32_t lo = desc_lo(sd + CO_XB + b * CH_XP, 16);
        wgmma_fence();
#pragma unroll
        for (int j = 0; j < 32; j++) if (j >= j0 && j < j1) {
            const int e = j < js ? j + CH_NSM : j < js + CH_NSM ? j - js : j;
            const uint32_t db = lo + chunk(e >> 2) * (CH_XC / 16) + (e & 3) * 2, da = desc_lo(sd + CO_WA + g * CH_TW + e * 2048, 16);
            if constexpr (sizeof(d) == 64) { if (e < CH_NSM) wgmma_ss_n32(d, da, db, j != 0); else wgmma_rs_n32(d, w[e], db, j != 0); }
            else { if (e < CH_NSM) wgmma_ss_n40<1, 1024>(d, da, db, j != 0); else wgmma_rs_n40(d, w[e], db, j != 0); }
        }
        wgmma_commit();
    };
    auto uni = [](uint32_t v) { return __shfl_sync(0xffffffff, v, 0); };
    auto roff = [&](int j) { return (uint32_t)(((rank + j) & 7) - rank) << 24; };
    auto store32 = [&](const float* d, uint32_t a) {
        stmatrix_x4_trans(a, pack_bf16(d[0], d[1]), pack_bf16(d[2], d[3]), pack_bf16(d[4], d[5]), pack_bf16(d[6], d[7]));
        stmatrix_x4_trans(a + 2048, pack_bf16(d[8], d[9]), pack_bf16(d[10], d[11]), pack_bf16(d[12], d[13]), pack_bf16(d[14], d[15]));
    };
    auto scores = [&](float (&d)[20], auto sbo, uint32_t q) {
        wgmma_fence();
#pragma unroll
        for (int ks = 0; ks < 4; ks++) wgmma_ss_n40<0, decltype(sbo)::value>(d, desc_lo(sd + CO_T + q, 16) + ks * 2, desc_lo(sd + CO_T + CH_TW, 16) + ks * 2, ks != 0);
        wgmma_commit();
    };
    auto send_scores = [&](const float (&d)[20], uint32_t a, uint32_t bar, bool p0, bool p1, bool p2) {
        asm volatile("{\n.reg .pred p0, p1, p2;\nsetp.ne.b32 p0, %13, 0;\nsetp.ne.b32 p1, %14, 0;\nsetp.ne.b32 p2, %15, 0;\n"
                     "@p0 st.async.weak.shared::cluster.mbarrier::complete_tx::bytes.v4.f32 [%0], {%3, %4, %5, %6}, [%2];\n"
                     "@p1 st.async.weak.shared::cluster.mbarrier::complete_tx::bytes.v4.f32 [%0 + 512], {%7, %8, %9, %10}, [%2];\n"
                     "@p2 st.async.weak.shared::cluster.mbarrier::complete_tx::bytes.v2.f32 [%1], {%11, %12}, [%2];\n}"
                     :: "r"((aL + a) ^ (1u << 24)), "r"((aL + a + 1024 - lane * 8) ^ (1u << 24)), "r"(bar ^ (1u << 24)), "f"(d[0]), "f"(d[1]), "f"(d[4]), "f"(d[5]),
                        "f"(d[8]), "f"(d[9]), "f"(d[12]), "f"(d[13]), "f"(d[16]), "f"(d[17]), "r"((int)p0), "r"((int)p1), "r"((int)p2) : "memory");
    };
    auto own_scores = [&](const float (&d)[20], float (&v)[10]) {
#pragma unroll
        for (int j = 0; j < 5; j++) { v[2 * j] = d[4 * j]; v[2 * j + 1] = d[4 * j + 1]; }
    };
    auto add_scores = [&](uint32_t a, float (&v)[10], int dense) {
        const uint4 a0 = lds128(aL + a), a1 = lds128(aL + a + 512);
        const float2 a2 = lds64f(aL + a + 1024 - dense * lane * 8);
        v[0] += __uint_as_float(a0.x); v[1] += __uint_as_float(a0.y); v[2] += __uint_as_float(a0.z); v[3] += __uint_as_float(a0.w);
        v[4] += __uint_as_float(a1.x); v[5] += __uint_as_float(a1.y); v[6] += __uint_as_float(a1.z); v[7] += __uint_as_float(a1.w);
        v[8] += a2.x; v[9] += a2.y;
    };
    auto row_max = [&](const float (&v)[10]) {
        float mx = fmaxf(fmaxf(fmaxf(v[0], v[1]), fmaxf(v[2], v[3])), fmaxf(fmaxf(v[4], v[5]), fmaxf(v[6], v[7])));
        mx = fmaxf(mx, fmaxf(v[8], v[9]));
        mx = fmaxf(mx, __shfl_xor_sync(0xffffffff, mx, 1));
        return fmaxf(mx, __shfl_xor_sync(0xffffffff, mx, 2)) * CH_SC;
    };
    auto signal_ctx = [&](int m0, int m1) {
        asm volatile("fence.proxy.async;" ::: "memory");
        __threadfence();
        for (int m = m0; m < m1; m++) asm volatile("red.relaxed.gpu.global.add.u32 [%0], 1;" :: "l"(&g_ctr[CT_CB + m]) : "memory");
    };
    auto signal_step = [](int s) { return s == 33 || s == 49 || s == 57 || s == 61; };
    if (mapa_u32(bar_l, rank ^ 1) != (bar_l ^ (1u << 24)) || mapa_u32(bar_l, (rank + 3) & 7) != bar_l + roff(3)) __trap();
    mbar_wait(bar_x, 0);
    PT(7, 0);
    if (wg < 2) {
        float d[16];
        pass(d, wg, 0, 0, 32, 0);
        wgmma_wait<0>();
        store32(d, aO + CO_T);
    }
    if (tid == 128) mbar_expect_tx(bar_sc, 2048);
    __syncthreads();
    PT(8, 0);
    cluster_sync_all();
    TS_BEGIN(5);
    PT(9, 0);

    if (wg < 2) {
        const uint32_t aM = pin(sb + CO_XB + 4096 + (lane & 7) * 128 + (((lane >> 3) ^ (lane & 7)) << 4));
        uint32_t coff[8];
#pragma unroll
        for (int i = 0; i < 8; i++) coff[i] = uni(chunk(i) * CH_XC);
        auto mem_proj = [&](int s) {
            const uint32_t par = s & 1;
            float acc[CH_CHAINS][4];
#pragma unroll
            for (int i = 0; i < CH_CHAINS; i++) acc[i][0] = acc[i][1] = acc[i][2] = acc[i][3] = 0.f;
            const uint32_t am = aM + par * CH_XP;
            uint32_t b[CH_LD][4], ok[4] = {1, 1, 1, 1}, a0 = am, a1 = am ^ 64;
            auto load = [&](int i) {
                if (i == 12) DBG(13, 0);
                if (i && !(i & 3)) { a0 = ok[i >> 2] ? am : aL; a1 = a0 ^ 64; }
                uint32_t* r = b[i % CH_LD];
                ldmatrix_x4(r[0], r[1], r[2], r[3], ((i & 1) ? a1 : a0) + coff[i >> 1]);
                if ((i & 3) == CH_TWP && i < 12) ok[(i >> 2) + 1] = mbar_try(bar_mem + 8 * ((i >> 2) + 1), par ^ 1);
            };
#pragma unroll
            for (int e = 0; e < CH_NSM; e++) ldmatrix_x4_trans(w[e][0], w[e][1], w[e][2], w[e][3], aO + CO_WA + e * 2048);
            {
                uint32_t z = a0 & a1;
#pragma unroll
                for (int e = 0; e < CH_NSM; e++) z &= w[e][0];
                mbar_wait(bar_mem, (par ^ 1) + __shfl_sync(0xffffffff, z & (s >> 10), 0));
            }
            DBG(11, 0);
            bool done = false;
#pragma unroll
            for (int i = 0; i < CH_LD; i++) load(i);
#pragma unroll
            for (int i = 0; i < 16; i++) {
                mma_16816(acc[(2 * i) % CH_CHAINS], w[2 * i][0], w[2 * i][1], w[2 * i][2], w[2 * i][3], b[i % CH_LD][0], b[i % CH_LD][1]);
                mma_16816(acc[(2 * i + 1) % CH_CHAINS], w[2 * i + 1][0], w[2 * i + 1][1], w[2 * i + 1][2], w[2 * i + 1][3], b[i % CH_LD][2], b[i % CH_LD][3]);
                if (i + CH_LD < 16) load(i + CH_LD);
                if (i == 12 - CH_LD) done = __all_sync(0xffffffff, ok[1] & ok[2] & ok[3]);
                if (i == CH_HA) asm volatile("{\n.reg .pred p;\nsetp.ne.b32 p, %0, 0;\n@p bar.arrive 5, 384;\n}" :: "r"((int)done) : "memory");
            }
#pragma unroll
            for (int i = 0; i < 4; i++) {
                if (CH_CHAINS == 4) { acc[0][i] += acc[2 % CH_CHAINS][i]; acc[1][i] += acc[3 % CH_CHAINS][i]; }
                if (CH_CHAINS == 3) acc[0][i] += acc[2 % CH_CHAINS][i];
            }
            const uint32_t r0 = pack_bf16(acc[0][0] + acc[1][0], acc[0][1] + acc[1][1]);
            const uint32_t r1 = pack_bf16(acc[0][2] + acc[1][2], acc[0][3] + acc[1][3]);
            DBGD(40 + warp, warp, r0 ^ r1);
            stmatrix_x2_trans(aO + CO_T + 4096, r0, r1);
            fence_async_smem();
            return done;
        };
        if (wg == 0) {
#pragma unroll 1
            for (int s = 0; s < NSEG; s++) {
                const uint32_t par = s & 1;
#pragma unroll 1
                for (int it = 0; it < WAIT_LIMIT / 64; it++) if (mem_proj(s)) break;
                asm volatile("bar.arrive 1, 256;" ::: "memory");
                if (s == NSEG - 1) break;
                if (tid == 96) {
#pragma unroll
                    for (int j = 0; j < 4; j++) { mbar_expect_tx(bar_mem + 8 * j, 2048); if (j < 2) mbar_expect_tx(bar_o + 8 * j, 4096); }
                }
                __syncwarp();
                uint32_t* wp = g_xbuf + (size_t)rank * 2048 + C * 256 + qc * 64 + t4 * 8 + qd;
                asm volatile("st.relaxed.gpu.global.u32 [%0], %1;" :: "l"(wp + ((s + 2) & 3) * 16384), "r"(~0u) : "memory");
                asm volatile("st.relaxed.gpu.global.u32 [%0], %1;" :: "l"(wp + ((s + 2) & 3) * 16384 + 32), "r"(~0u) : "memory");
                mbar_wait(bar_x + 8 * (par ^ 1), ((s + 1) >> 1) & 1);
                asm volatile("bar.sync 7, 384;" ::: "memory");
                float d[16];
                if (CH_Q1 > 0) pass(d, 0, par ^ 1, 0, CH_Q1, CH_QS);
                float c[4];
                const uint32_t alo = desc_lo(sd + CO_WO, 16), blo = desc_lo(sd + CO_OB, 128);
                mbar_wait_cl(bar_o, par);
                DBG(16, 0);
                fence_async_smem();
                wgmma_fence();
#pragma unroll
                for (int i = 0; i < 32; i++) {
                    wgmma_ss_n8(c, alo + i * 128, blo + i * 16, i != 0);
                    if (i == CH_OW) mbar_wait_cl(bar_o + 8, par);
                    if (i == CH_OF) fence_async_smem();
                }
                wgmma_commit();
                wgmma_wait<0>();
                asm volatile("st.relaxed.gpu.global.u32 [%0], %1;" :: "l"(wp + (s & 3) * 16384), "r"(pack_bf16(c[0], c[2])) : "memory");
                asm volatile("st.relaxed.gpu.global.u32 [%0], %1;" :: "l"(wp + (s & 3) * 16384 + 32), "r"(pack_bf16(c[1], c[3])) : "memory");
                asm volatile("bar.arrive 6, 256;" ::: "memory");
                pace(CH_QD);
                asm volatile("bar.arrive 4, 384;" ::: "memory");
                DBG(8, 0);
                pass(d, 0, par ^ 1, CH_Q1, CH_QE, CH_QS);
                DBG(21, 0);
                if (tid == 0 && s + 2 < NSEG) {
                    mbar_expect_tx(bar_x + 8 * par, 32768);
                    tma_load_2d_mc(sb + CO_XB + par * CH_XP + rank * CH_XC, &P.mapX, bar_x + 8 * par, rank * 64, (s + 2) * SEGL, (uint16_t)0xff);
                }
                __syncwarp();
                asm volatile("bar.sync 9, 256;" ::: "memory");
                wgmma_wait<0>();
                DBG(0, 0);
                store32(d, aO + CO_T);
                DBG(22, 0);
            }
        } else {
            const uint32_t usc = uni(CO_SC + min(t4, 2) * 512 + roff((rank ^ 1) - rank)), uscb = uni(bar_sc ^ (1u << 24));
            const uint32_t vaddr = pin(sb + CO_T + 2 * CH_TW + (lane & 15) * 128 + (((t4 * 2 + (lane >> 4)) ^ (lane & 7)) << 4));
            const uint32_t dsta = pin(sb + CO_OB + t4 * 256 + (qc >> 1) * 128 + qd * 16 + (qc & 1) * 8);
            uint32_t uo[8], ub[8];
#pragma unroll
            for (int i = 0; i < 8; i++) { uo[i] = uni(roff(i) + i * 1024); ub[i] = uni(roff(i) + bar_o + 8 * (i >> 2)); }
#pragma unroll 1
            for (int s = 0; s < NSEG; s++) {
                const uint32_t par = s & 1;
#pragma unroll 1
                for (int it = 0; it < WAIT_LIMIT / 64; it++) if (mem_proj(s)) break;
                asm volatile("bar.sync 1, 256;" ::: "memory");
                float d[20];
                scores(d, std::integral_constant<int, 0>(), 4096);
                asm volatile("bar.arrive 8, 256;" ::: "memory");
                if (s == NSEG - 1) { wgmma_wait<0>(); break; }
                wgmma_wait<0>();
                {
                    const bool w0 = t4 == 0, w1 = t4 == 1;
                    asm volatile("st.async.weak.shared::cluster.mbarrier::complete_tx::bytes.v4.f32 [%0], {%2, %3, %4, %5}, [%1];"
                                 :: "r"((aL | (s >> 10)) + usc), "r"(uscb), "f"(w0 ? d[0] : w1 ? d[8] : d[16]), "f"(w0 ? d[1] : w1 ? d[9] : d[17]),
                                    "f"(w0 ? d[4] : d[12]), "f"(w0 ? d[5] : d[13]) : "memory");
                }
                DBG(3, 4);
                uint32_t vb[3][4];
                auto load_v = [&]() {
                    asm volatile("bar.sync 3, 256;" ::: "memory");
#pragma unroll
                    for (int k = 0; k < 3; k++) ldmatrix_x4_trans(vb[k][0], vb[k][1], vb[k][2], vb[k][3], vaddr + par * CH_TW + k * 2048);
                };
                mbar_wait_cl(bar_sc, par);
                DBG(4, 4);
                float v[10];
                own_scores(d, v);
                add_scores(CO_SC, v, 0);
                const float mx = row_max(v);
                if (CH_VPOS == 2) load_v();
#pragma unroll
                for (int j = 0; j < 10; j++) v[j] = ex2f(fmaf(v[j], CH_SC, -mx));
                uint32_t p[5];
#pragma unroll
                for (int j = 0; j < 5; j++) p[j] = pack_bf16(v[2 * j], v[2 * j + 1]);
                if (CH_VPOS == 3) load_v();
                DBG(19, 4);
                float c0[4] = {0.f, 0.f, 0.f, 0.f}, c1[4] = {0.f, 0.f, 0.f, 0.f}, cs[4] = {0.f, 0.f, 0.f, 0.f};
#pragma unroll
                for (int k = 0; k < 3; k++) {
                    const uint32_t p0 = p[2 * k], p1 = k < 2 ? p[2 * k + 1] : 0u;
                    mma_16816(cs, p0, 0u, p1, 0u, 0x3f803f80u, 0x3f803f80u);
                    mma_16816(c0, p0, 0u, p1, 0u, vb[k][0], vb[k][1]);
                    mma_16816(c1, p0, 0u, p1, 0u, vb[k][2], vb[k][3]);
                }
                float inv;
                asm volatile("rcp.approx.ftz.f32 %0, %1;" : "=f"(inv) : "f"(cs[0]));
                const uint32_t b0 = pack_bf16(c0[0] * inv, c0[1] * inv), b1 = pack_bf16(c1[0] * inv, c1[1] * inv);
                DBG(20, 4);
#pragma unroll
                for (int i = 0; i < 8; i++) {
                    st_async_v2((dsta | (s >> 10)) + uo[i], b0, b1, ub[i]);
                    if (i == CH_A7) asm volatile("bar.arrive 7, 384;" ::: "memory");
                }
                DBG(5, 4);
                if (tid == 128) mbar_expect_tx(bar_sc, 2048);
                __syncwarp();
                mbar_wait(bar_x + 8 * (par ^ 1), ((s + 1) >> 1) & 1);
                asm volatile("bar.sync 4, 384;" ::: "memory");
                float dk[16];
                pass(dk, 1, par ^ 1, 0, CH_KE, CH_KS);
                if (tid == 128 && signal_step(s)) signal_ctx((2 * s - 66) >> 2, s >> 2);
                __syncwarp();
                DBG(1, 4);
                wgmma_wait<0>();
                DBG(2, 4);
                store32(dk, aO + CO_T);
                DBG(29, 4);
            }
        }
        PT(10, 0);
    } else {
        auto store_ctx = [&](int s) {
            if (tid == 256) {
                tma_store_2d(&P.mapC, sb + CO_ST, (rank & 1) * 64, h * SEQ + s * SEGL);
                asm volatile("cp.async.bulk.commit_group;" ::: "memory");
            }
        };
        float gs;
        auto load_gate = [&](int s) { asm volatile("ld.global.cg.f32 %0, [%1];" : "=f"(gs) : "l"(g_gate + s * SEGL + t4 * 8 + qd) : "memory"); };
        auto softmax = [&](int s) {
            float v[10];
            {
                const uint4 a0 = lds128(aL + CO_OWN + t4 * 1024), a1 = lds128(aL + CO_OWN + t4 * 1024 + 512);
                const float2 a2 = lds64f(aL + CO_OWN2 + t4 * 256 - lane * 8);
                v[0] = __uint_as_float(a0.x); v[1] = __uint_as_float(a0.y); v[2] = __uint_as_float(a0.z); v[3] = __uint_as_float(a0.w);
                v[4] = __uint_as_float(a1.x); v[5] = __uint_as_float(a1.y); v[6] = __uint_as_float(a1.z); v[7] = __uint_as_float(a1.w);
                v[8] = a2.x; v[9] = a2.y;
            }
            mbar_wait_cl(bar_l, s & 1);
            add_scores(CO_LS + (s & 1) * 5120 + t4 * 1280, v, 1);
            const int lim = t4 * 8 + qd - 2 * qc;
#pragma unroll
            for (int j = 0; j < 8; j++) if ((j >> 1) * 8 + (j & 1) > lim) v[j] = -INFINITY;
            const float mx = row_max(v);
#pragma unroll
            for (int j = 0; j < 10; j++) v[j] = ex2f(fmaf(v[j], CH_SC, -mx));
            float sum = (((v[0] + v[1]) + (v[2] + v[3])) + ((v[4] + v[5]) + (v[6] + v[7]))) + (v[8] + v[9]);
            sum += __shfl_xor_sync(0xffffffff, sum, 1);
            sum += __shfl_xor_sync(0xffffffff, sum, 2);
            asm("rcp.approx.ftz.f32 %0, %0;" : "+f"(sum));
            sum *= 1.f - gs;
            const uint32_t pa = aL + CO_P + t4 * 768;
            stmatrix_x4(pa, pack_bf16(v[0] * sum, v[1] * sum), pack_bf16(v[2] * sum, v[3] * sum), pack_bf16(v[4] * sum, v[5] * sum), pack_bf16(v[6] * sum, v[7] * sum));
            asm volatile("stmatrix.sync.aligned.m8n8.x1.shared.b16 [%0], {%1};" :: "r"(pa + 512), "r"(pack_bf16(v[8] * sum, v[9] * sum)) : "memory");
        };
        auto pv = [&](float (&dc)[16], int s) {
            wgmma_fence();
#pragma unroll
            for (int ks = 0; ks < 3; ks++) wgmma_ss_n32_p(dc, desc_lo(sd + CO_T + (2 + (s & 1)) * CH_TW + ks * 2048, 16), desc_lo(sd + CO_P + ks * 256, 128), ks != 0);
            wgmma_commit();
        };
        uint32_t um[8], ub[8];
#pragma unroll
        for (int i = 0; i < 8; i++) { um[i] = uni(roff((i & 1) * 4 + (i >> 1))); ub[i] = uni(roff((i & 1) * 4 + (i >> 1)) + bar_mem + 8 * (i >> 1)); }
        const uint8_t* mkp = smem_raw + CO_BAR + 128;
        asm volatile("" : "+l"(mkp));
        wait_ctr(CT_GATE, 64u);
        load_gate(0);
#pragma unroll 1
        for (int s = 0; s < NSEG; s++) {
            const uint32_t par = s & 1;
            const bool last = s == NSEG - 1;
            softmax(s - 1);
            load_gate(s);
            DBG(7, 8);
#pragma unroll 1
            for (int it = 0; it < WAIT_LIMIT / 64; it++)
                if (mbar_try(bar_mem, par ^ 1) & mbar_try(bar_mem + 8, par ^ 1) & mbar_try(bar_mem + 16, par ^ 1) & mbar_try(bar_mem + 24, par ^ 1)) break;
            fence_async_smem();
            asm volatile("cp.async.bulk.wait_group.read 0;" ::: "memory");
            asm volatile("bar.sync 5, 384;" ::: "memory");
            DBG(23, 8);
            float d[20];
            pass(d, 2, par, 0, CH_VA, CH_VS);
            asm volatile("bar.sync 8, 256;" ::: "memory");
            pass(d, 2, par, CH_VA, 32, CH_VS);
            if (signal_step(s)) asm volatile("cp.async.bulk.wait_group 0;" ::: "memory");
            wgmma_wait<0>();
            stmatrix_x2_trans(aO + par * CH_TW + CO_T + 4096, pack_bf16(d[16], d[17]), pack_bf16(d[18], d[19]));
            store32(d, aO + par * CH_TW + CO_T);
            DBG(24, 8);
            if (!last) asm volatile("bar.arrive 3, 256;\nbar.sync 7, 384;" ::: "memory");
            {
                float dc[16];
                pv(dc, s + 1);
                wgmma_wait<0>();
                store32(dc, aO - 2 * CH_TW + CO_ST);
            }
            scores(d, std::integral_constant<int, 512>(), 0);
            asm volatile("{\n.reg .pred p;\nsetp.eq.s32 p, %1, 256;\n@p mbarrier.arrive.expect_tx.shared::cta.b64 _, [%0], 4096;\n}" :: "r"(bar_l), "r"(tid) : "memory");
            wgmma_wait<0>();
            sts128(aL + CO_OWN + t4 * 1024, __float_as_uint(d[0]), __float_as_uint(d[1]), __float_as_uint(d[4]), __float_as_uint(d[5]));
            sts128(aL + CO_OWN + t4 * 1024 + 512, __float_as_uint(d[8]), __float_as_uint(d[9]), __float_as_uint(d[12]), __float_as_uint(d[13]));
            asm volatile("st.shared.v2.f32 [%0], {%1, %2};" :: "r"(aL + CO_OWN2 + t4 * 256 - lane * 8), "f"(d[16]), "f"(d[17]) : "memory");
            if (CH_LSW && !last) mbar_wait_cl(bar_o + 8, par);
            send_scores(d, CO_LS + par * 5120 + t4 * 1280, bar_l, true, t4 >= 2, true);
            DBG(6, 8);
            fence_async_smem();
            asm volatile("bar.sync 2, 128;" ::: "memory");
            if (s > 0) store_ctx(s - 1);
            __syncwarp();
            if (last) break;
            asm volatile("bar.arrive 4, 384;\nbar.arrive 9, 256;\nbar.sync 6, 256;" ::: "memory");
            const uint2* xb = reinterpret_cast<const uint2*>(g_xbuf + (s & 3) * 16384 + (size_t)rank * 2048 + t4 * 64) + lane;
            uint2 p[8], q[8];
            pace(CH_POLL_DELAY);
#pragma unroll
            for (int k = 0; k < 8; k++)
                asm volatile("ld.relaxed.gpu.global.v2.u32 {%0, %1}, [%2];" : "=r"(p[k].x), "=r"(p[k].y) : "l"(xb + k * 128) : "memory");
            DBG(17, 8);
            {
                uint32_t z;
                asm volatile("mov.u32 %0, %%clock;" : "=r"(z) :: "memory");
#pragma unroll
                for (int i = 0; i < CH_GAP; i++) asm volatile("mul.lo.u32 %0, %0, %0;" : "+r"(z));
                asm volatile("and.b32 %0, %0, %1;" : "+r"(z) : "r"(s >> 10));
                xb += z;
            }
#pragma unroll
            for (int k = 0; k < 8; k++)
                asm volatile("ld.relaxed.gpu.global.v2.u32 {%0, %1}, [%2];" : "=r"(q[k].x), "=r"(q[k].y) : "l"(xb + k * 128) : "memory");
            uint32_t m0, m1, mk;
            asm volatile("ld.relaxed.gpu.u32 %0, [%1];" : "=r"(mk) : "l"(mkp) : "memory");
            auto sum = [&](const uint2 (&p)[8]) {
                auto lo = [&](uint32_t u) { return __uint_as_float(u * (0u - mk)); };
                auto hi = [&](uint32_t u) { return __uint_as_float(u & mk); };
                const float s0 = ((lo(p[0].x) + lo(p[1].x)) + (lo(p[2].x) + lo(p[3].x))) + ((lo(p[4].x) + lo(p[5].x)) + (lo(p[6].x) + lo(p[7].x)));
                const float s1 = ((lo(p[0].y) + lo(p[1].y)) + (lo(p[2].y) + lo(p[3].y))) + ((lo(p[4].y) + lo(p[5].y)) + (lo(p[6].y) + lo(p[7].y)));
                m0 = pack_bf16(s0, ((hi(p[0].x) + hi(p[1].x)) + (hi(p[2].x) + hi(p[3].x))) + ((hi(p[4].x) + hi(p[5].x)) + (hi(p[6].x) + hi(p[7].x))));
                m1 = pack_bf16(s1, ((hi(p[0].y) + hi(p[1].y)) + (hi(p[2].y) + hi(p[3].y))) + ((hi(p[4].y) + hi(p[5].y)) + (hi(p[6].y) + hi(p[7].y))));
                uint32_t ok;
                asm volatile("{\n.reg .pred p;\nsetp.num.f32 p, %1, %2;\nvote.sync.all.pred p, p, 0xffffffff;\nselp.u32 %0, 1, 0, p;\n}" : "=r"(ok) : "f"(s0), "f"(s1));
                return ok;
            };
            if (!sum(p)) {
                DBG(12, 8);
#pragma unroll 1
                for (int it = 0; it < WAIT_LIMIT / 4; it++) {
                    if (sum(q)) break;
                    uint32_t bad = 0;
#pragma unroll
                    for (int k = 0; k < 8; k++) bad |= (max(q[k].x, q[k].y) == ~0u ? 1u : 0u) << k;
                    if (__all_sync(0xffffffff, bad == 0u)) break;
                    if (it == 0) DBG(14, 8);
                    if (it == 1) DBG(15, 8);
#pragma unroll
                    for (int k = 0; k < 8; k++)
                        if (bad & (1u << k))
                            asm volatile("ld.relaxed.gpu.global.v2.u32 {%0, %1}, [%2];" : "=r"(q[k].x), "=r"(q[k].y) : "l"(xb + k * 128) : "memory");
                }
            }
            DBG(9, 8);
            const int row = t4 * 2 + (lane >> 4);
            const uint32_t dsta = sb + CO_XB + (par ^ 1) * CH_XP + rank * CH_XC + 4096 + row * 128 + ((((lane & 15) >> 1) ^ row) << 4) + (lane & 1) * 8;
#pragma unroll
            for (int i = 0; i < 8; i++) st_async_v2(dsta + um[i], m0, m1, ub[i]);
            if (s == 1000000) {
#pragma unroll
                for (int k = 0; k < 8; k++) asm volatile("st.volatile.shared.v2.u32 [%0], {%1, %2};" :: "r"(s), "r"(q[k].x), "r"(q[k].y) : "memory");
            }
            DBG(10, 8);
        }
        PT(11, 256);
        softmax(NSEG - 1);
        fence_async_smem();
        asm volatile("cp.async.bulk.wait_group.read 0;" ::: "memory");
        asm volatile("bar.sync 2, 128;" ::: "memory");
        PT(12, 256);
        float dc[16];
        pv(dc, NSEG - 1);
        wgmma_wait<0>();
        store32(dc, aO - 2 * CH_TW + CO_ST);
        PT(13, 256);
        fence_async_smem();
        asm volatile("bar.sync 2, 128;" ::: "memory");
        store_ctx(NSEG - 1);
        if (tid == 256) {
            asm volatile("cp.async.bulk.wait_group 0;" ::: "memory");
            PT(14, 256);
            signal_ctx(15, 16);
            PT(15, 256);
        }
    }
    __syncthreads();
    cluster_sync_all();
    TS_END(2);
}

struct Proj2Params {
    CUtensorMap mapA[2];
    CUtensorMap mapW[3];
    bf16* out[3];
};
#define P2T(i)
#define P2_NOMMA 0
#define P2_NOLOAD 0
constexpr int P2_STAGES = 6;
constexpr int P2_SMEM = 131072 + P2_STAGES * 16384 + 1024 + 1024;
constexpr int P2_ITEMS = 168 + 48;

__device__ __forceinline__ int p2_reps(int t) { return t >= 168 ? 1 : 2; }
__device__ __forceinline__ void p2_tile(int t, int w, int& z, int& mp, int& head) {
    if (t >= 168) { w += ((t - 168) & 1) * 2; t = 168 + ((t - 168) >> 1); }
    const int hq = t / 24, v = t % 24;
    mp = v & 7;
    if (v < 16) { head = hq * 4 + (v >> 3) * 2 + (w >> 1); z = 1 + (w & 1); }
    else { head = hq * 4 + w; z = 0; }
}
__device__ __forceinline__ void mbar_arrive_remote(uint32_t bar_cluster_addr) {
    asm volatile("mbarrier.arrive.release.cluster.shared::cluster.b64 _, [%0];" :: "r"(bar_cluster_addr) : "memory");
}
__device__ __forceinline__ void mbar_arrive_cl(uint32_t bar_cluster_addr) {
    asm volatile("mbarrier.arrive.shared::cluster.b64 _, [%0];" :: "r"(bar_cluster_addr) : "memory");
}
__device__ __forceinline__ void mbar_wait_acq_cluster(uint32_t bar, uint32_t parity) {
    asm volatile(
        "{\n"
        ".reg .pred p, q;\n"
        ".reg .u32 c;\n"
        "mov.u32 c, 0;\n"
        "WAIT_LOOP_C:\n"
        "mbarrier.try_wait.parity.acquire.cluster.shared::cta.b64 p, [%0], %1;\n"
        "@p bra WAIT_DONE_C;\n"
        "add.u32 c, c, 1;\n"
        "setp.lt.u32 q, c, 4000000;\n"
        "@q bra WAIT_LOOP_C;\n"
        "WAIT_DONE_C:\n"
        "}\n" :: "r"(bar), "r"(parity) : "memory");
}
__device__ __forceinline__ uint4 quad_transpose(uint32_t p0, uint32_t p1, uint32_t p2, uint32_t p3, int lane) {
    const bool o1 = lane & 1, o2 = lane & 2;
    uint32_t s0 = o1 ? p0 : p1, s1 = o1 ? p2 : p3;
    s0 = __shfl_xor_sync(0xffffffff, s0, 1); s1 = __shfl_xor_sync(0xffffffff, s1, 1);
    const uint32_t a_lo = o1 ? s0 : p0, a_hi = o1 ? p1 : s0, b_lo = o1 ? s1 : p2, b_hi = o1 ? p3 : s1;
    uint32_t t0 = o2 ? a_lo : b_lo, t1 = o2 ? a_hi : b_hi;
    t0 = __shfl_xor_sync(0xffffffff, t0, 2); t1 = __shfl_xor_sync(0xffffffff, t1, 2);
    return o2 ? make_uint4(t0, t1, b_lo, b_hi) : make_uint4(a_lo, a_hi, t0, t1);
}
#define P2_PACE 35
#define P2_PACE2 0
template <bool PERM, int PACE = 0>
__device__ __forceinline__ void store_frag_128(const float (&acc)[64], bf16* obase, int lane) {
#pragma unroll
    for (int rr = 0; rr < 2; rr++)
#pragma unroll
        for (int g = 0; g < 4; g++) {
            const float* a = &acc[g * 16 + rr * 2];
            const uint32_t p0 = pack_bf16(a[0], a[1]), p1 = pack_bf16(a[4], a[5]), p2 = pack_bf16(a[8], a[9]), p3 = pack_bf16(a[12], a[13]);
            *reinterpret_cast<uint4*>(obase + (size_t)(rr * 8) * HD + g * 32) = PERM ? make_uint4(p0, p1, p2, p3) : quad_transpose(p0, p1, p2, p3, lane);
            pace(PACE);
        }
}
__global__ void __cluster_dims__(2, 1, 1) __launch_bounds__(384, 1) proj2_kernel(const __grid_constant__ Proj2Params P) {
    extern __shared__ uint8_t smem_raw[];
    const uint32_t sbase = (smem_u32(smem_raw) + 1023) & ~1023u;
    const uint32_t sA = sbase, sB = sbase + 131072, sC = sB + P2_STAGES * 16384;
    const uint32_t bars = sC;
    const uint32_t a_full = bars, a_empty = bars + 64, b_full = bars + 128, b_empty = b_full + 8 * P2_STAGES;
    const uint32_t item_bar = b_empty + 8 * P2_STAGES, item_in = item_bar + 16, slot = item_in + 16;
    const uint32_t note_bar = slot + 16, note_free = note_bar + 64, note = note_free + 64;
    const int warp = threadIdx.x >> 5, lane = threadIdx.x & 31;
    const uint32_t rank = cluster_ctarank();
    TS_BEGIN(0);
    if (threadIdx.x == 0) {
        for (int i = 0; i < 8; i++) { mbar_init(a_full + 8 * i, 1); mbar_init(a_empty + 8 * i, 2); }
        for (int i = 0; i < P2_STAGES; i++) { mbar_init(b_full + 8 * i, 1); mbar_init(b_empty + 8 * i, 2); }
        mbar_init(item_bar, 1); mbar_init(item_bar + 8, 1); mbar_init(item_in, 2); mbar_init(item_in + 8, 2);
        for (int i = 0; i < 8; i++) { mbar_init(note_bar + 8 * i, 1); mbar_init(note_free + 8 * i, 1); }
        asm volatile("fence.mbarrier_init.release.cluster;" ::: "memory");
    }
    __syncthreads();
    cluster_sync_all();
    pdl_launch_dependents();
    if (warp == 9) {
        if (lane == 0) {
            for (int n = 0;; n++) {
                const int e = (n & 1) * 4 + ((n >> 1) & 3);
                mbar_wait(note_bar + 8 * e, (n >> 3) & 1);
                int m;
                asm volatile("ld.shared.s32 %0, [%1];" : "=r"(m) : "r"(note + e * 4) : "memory");
                mbar_arrive(note_free + 8 * e);
                if (m < 0) break;
                signal_ctr(m);
            }
        }
    } else if (warp == 10) {
        if (lane == 0) {
            auto publish = [&](int ic, int tq) {
                const int t = tq < P2_ITEMS ? tq : -1;
                asm volatile("st.shared.s32 [%0], %1;" :: "r"(slot + (ic & 3) * 4), "r"(t) : "memory");
                mbar_arrive(item_bar + 8 * (ic & 1));
                st_async_b32(mapa_u32(slot + (ic & 3) * 4, 1), (uint32_t)t, mapa_u32(item_bar + 8 * (ic & 1), 1));
            };
            const int npair = (int)(gridDim.x >> 1), pair = (int)(blockIdx.x >> 1);
            if (rank == 0) publish(0, pair);
            for (int ic = 0;; ic++) {
                if (rank == 1) mbar_expect_tx(item_bar + 8 * (ic & 1), 4);
                mbar_wait(item_bar + 8 * (ic & 1), (ic >> 1) & 1);
                int t;
                asm volatile("ld.shared.s32 %0, [%1];" : "=r"(t) : "r"(slot + (ic & 3) * 4) : "memory");
                if (t < 0) break;
                int z0, mp, h0;
                p2_tile(t, 0, z0, mp, h0);
                const int aidx = z0 >= 1 ? 1 : 0;
                const int m0 = (2 * mp + (int)rank) * 128;
                for (int k = 0; k < 8; k++) {
                    mbar_wait(a_empty + 8 * k, (ic & 1) ^ 1);
                    if (P2_NOLOAD) mbar_arrive(a_full + 8 * k); else {
                    mbar_expect_tx(a_full + 8 * k, 16384);
                    tma_load_2d(sA + k * 16384, &P.mapA[aidx], a_full + 8 * k, k * 64, m0); }
                }
                if (rank == 0) {
                    mbar_wait(item_in + 8 * (ic & 1), (ic >> 1) & 1);
                    publish(ic + 1, ic == 0 ? npair + pair : 2 * npair + (int)atomicAdd(&g_ctr[CT_PROJ], 1u));
                }
            }
        }
    } else if (warp == 8 || warp == 11) {
        if (lane == 0) {
            const int par2 = warp == 8 ? 0 : 1;
            int it = 0; uint32_t bph = 0;
            for (int ic = 0;; ic++) {
                mbar_wait(item_bar + 8 * (ic & 1), (ic >> 1) & 1);
                int t;
                asm volatile("ld.shared.s32 %0, [%1];" : "=r"(t) : "r"(slot + (ic & 3) * 4) : "memory");
                if (t < 0) break;
                const int nt = 2 * p2_reps(t);
                for (int w = 0; w < nt; w++) {
                    int z, mp, hd;
                    p2_tile(t, w, z, mp, hd);
                    for (int k = 0; k < 8; k++) {
                        const int s = it; const uint32_t phb = bph;
                        if (++it == P2_STAGES) { it = 0; bph ^= 1; }
                        if ((k & 1) != par2) continue;
                        mbar_wait(b_empty + 8 * s, phb ^ 1);
                        if (P2_NOLOAD) { mbar_arrive(b_full + 8 * s); continue; }
                        mbar_expect_tx(b_full + 8 * s, 16384);
                        tma_load_2d_mc(sB + s * 16384 + rank * 8192, &P.mapW[z], b_full + 8 * s, hd * 128 + (int)rank * 64, k * 64, (uint16_t)3);
                    }
                }
            }
        }
    } else {
        const int wg = warp >> 2;
        float acc[2][64];
        const uint32_t a_lo = desc_lo(sA, 16), b_lo0 = desc_lo(sB, 8192);
        const bool elected = (threadIdx.x & 127) == 0;
        int s = (wg * 8) % P2_STAGES;
        uint32_t ph = ((wg * 8) / P2_STAGES) & 1;
        int nnote = 0;
        if (wg == 1) asm volatile("bar.arrive 3, 256;" ::: "memory");
        for (int ic = 0;; ic++) {
            mbar_wait(item_bar + 8 * (ic & 1), (ic >> 1) & 1);
            int t;
            asm volatile("ld.shared.s32 %0, [%1];" : "=r"(t) : "r"(slot + (ic & 3) * 4) : "memory");
            P2T(7);
            if (wg == 0 && t < 0) {
                if (elected) {
                    const int e = nnote & 3;
                    mbar_wait(note_free + 8 * e, ((nnote >> 2) & 1) ^ 1);
                    asm volatile("st.shared.s32 [%0], %1;" :: "r"(note + e * 4), "r"(-1) : "memory");
                    mbar_arrive(note_bar + 8 * e);
                }
            }
            if (t < 0) break;
            const int reps = p2_reps(t);
#pragma unroll 1
            for (int rp = 0; rp < reps; rp++) {
            const bool first = rp == 0, last = rp == reps - 1;
            int z, mp, head;
            p2_tile(t, rp * 2 + wg, z, mp, head);
            asm volatile("bar.sync %0, 256;" :: "r"(3 + wg) : "memory");
            P2T(0);
            if (wg == 1 && last && elected) mbar_arrive_cl(mapa_u32(item_in + 8 * (ic & 1), 0));
            int sprev = 0;
#pragma unroll
            for (int k = 0; k < 8; k++) {
                if (k == 0) P2T(5);
                if (wg == 0 && first) mbar_wait(a_full + 8 * k, ic & 1);
                if (k == 0) P2T(6);
                mbar_wait(b_full + 8 * s, ph);
                if (k == 7) asm volatile("bar.arrive %0, 256;" :: "r"(4 - wg) : "memory");
                if (k == 0) P2T(1);
                if (k == 7) P2T(2);
                const uint32_t b_lo = b_lo0 + s * 1024;
                wgmma_fence();
#pragma unroll
                for (int kk = 0; kk < (P2_NOMMA ? 1 : 4); kk++) {
                    wgmma_ss_n128_lo<1>(acc[0], a_lo + k * 1024 + kk * 2, b_lo + kk * 128, (k | kk) != 0);
                    wgmma_ss_n128_lo<1>(acc[1], a_lo + k * 1024 + 512 + kk * 2, b_lo + kk * 128, (k | kk) != 0);
                }
                wgmma_commit();
                if (k > 0) {
                    wgmma_wait<1>();
                    if (elected) {
                        const uint32_t e = b_empty + 8 * sprev;
                        mbar_arrive_cl(mapa_u32(e, 0)); mbar_arrive_cl(mapa_u32(e, 1));
                        if (last) mbar_arrive(a_empty + 8 * (k - 1));
                    }
                }
                sprev = s;
                if (++s == P2_STAGES) { s = 0; ph ^= 1; }
            }
            wgmma_wait<0>();
            P2T(3);
            if (elected) {
                const uint32_t e = b_empty + 8 * sprev;
                mbar_arrive_cl(mapa_u32(e, 0)); mbar_arrive_cl(mapa_u32(e, 1));
                if (last) mbar_arrive(a_empty + 8 * 7);
            }
            s += 8 % P2_STAGES; ph ^= (8 / P2_STAGES) & 1;
            if (s >= P2_STAGES) { s -= P2_STAGES; ph ^= 1; }
            const int m0 = (2 * mp + (int)rank) * 128;
            bf16* obase = P.out[z] + ((size_t)head * SEQ + m0 + (warp & 3) * 16 + (lane >> 2)) * HD + (lane & 3) * 8;
            store_frag_128<true, P2_PACE>(acc[0], obase, lane); store_frag_128<true, P2_PACE>(acc[1], obase + (size_t)64 * HD, lane);
            P2T(4);
            {
                asm volatile("bar.sync %0, 128;" :: "r"(1 + wg) : "memory");
                if (elected) {
                    const int e = wg * 4 + (nnote & 3);
                    mbar_wait(note_free + 8 * e, ((nnote >> 2) & 1) ^ 1);
                    asm volatile("st.shared.s32 [%0], %1;" :: "r"(note + e * 4), "r"(CT_AP + (head >> 1)) : "memory");
                    mbar_arrive(note_bar + 8 * e);
                }
                nnote++;
            }
            }
        }
        TS_END(0);
    }
    __syncthreads();
    cluster_sync_all();
}

struct OutParams {
    CUtensorMap mapCtx[2];
    CUtensorMap mapWo[2];
    CUtensorMap mapOut;
};

#define OT(i)
#define OTP(i, th)
constexpr int O2_STAGES = 4;
constexpr int O2_SMEM = O2_STAGES * 49152 + 1024 + 256;
constexpr int O2_GRID = 132;
#define O2_NL 8
#define O2_FINE 8

__global__ void __cluster_dims__(2, 1, 1) __launch_bounds__(352, 1)
out2_kernel(const __grid_constant__ OutParams P) {
    extern __shared__ uint8_t smem_raw[];
    const uint32_t sbase = (smem_u32(smem_raw) + 1023) & ~1023u;
    const uint32_t bar_full = sbase + O2_STAGES * 49152, bar_empty = bar_full + 8 * O2_STAGES, bar_item = bar_empty + 8 * O2_STAGES;
    const uint32_t slot = bar_item + 64, stop = slot + 32;
    const int warp = threadIdx.x >> 5, lane = threadIdx.x & 31;
    const uint32_t rank = cluster_ctarank();
    const int cid = blockIdx.x >> 1;
    int pt, h0;
    if (cid < 32) { pt = cid < 16 ? cid : 31 - cid; h0 = cid >= 16; }
    else if (cid < 34) { pt = 12 + (cid & 1); h0 = 2; }
    else { pt = 14 + (cid & 1); h0 = 63 - ((cid - 34) >> 1); }
    const int ne = (pt >> 1) == 6 ? 3 : 2, nh = pt >= 14 ? 64 - O2_NL : 64;
    if (cid >= 34 + 2 * O2_NL) {
        if (threadIdx.x == 0 && atomicAdd(&g_ctr[CT_FIN], 1u) == gridDim.x - 1)
            for (int i = 0; i < CT_N / 4; i++) reinterpret_cast<uint4*>(g_ctr)[i] = make_uint4(0u, 0u, 0u, 0u);
        return;
    }
    const int mt = (pt >> 1) * 2 + (int)rank, m0 = mt * 128, n0 = (pt & 1) * 256;
    TS_BEGIN(4);
    OT(0);
    int tnext = 0;
    if (threadIdx.x == 256) {
        if (rank == 0) tnext = take_ticket(CT_OT + pt);
        for (int i = 0; i < O2_STAGES; i++) { mbar_init(bar_full + 8 * i, 1); mbar_init(bar_empty + 8 * i, 4); mbar_init(bar_item + 16 * i, 1); mbar_init(bar_item + 16 * i + 8, 1); }
        sts128(stop, 0u, 0u, 0u, 0u);
        asm volatile("fence.mbarrier_init.release.cluster;" ::: "memory");
    }
    __syncwarp();
    asm volatile("barrier.cluster.arrive.relaxed.aligned;" ::: "memory");
    if (threadIdx.x == 256) {
        asm volatile("prefetch.tensormap [%0];" :: "l"(&P.mapCtx[h0 >> 5]) : "memory");
        wait_ctr(h0 < 32 ? CT_CA + mt * 4 : CT_CB + mt, h0 < 32 ? 16u : 64u);
        OTP(8, 256);
        for (int i = 0; i < 2; i++) {
            mbar_expect_tx(bar_full + 8 * i, 49152);
            tma_load_2d(sbase + i * 49152, &P.mapCtx[h0 >> 5], bar_full + 8 * i, i * 64, (h0 & 31) * SEQ + m0);
        }
        OTP(11, 256);
    }
    if (threadIdx.x == 288) asm volatile("prefetch.tensormap [%0];" :: "l"(&P.mapWo[h0 >> 5]) : "memory");
    __syncwarp();
    asm volatile("barrier.cluster.wait.aligned;" ::: "memory");
    OTP(10, 288);
    if (warp >= 8) {
        if (lane == 0) {
            int s = 0, ready = h0 < 32 ? 1 : 16, q = h0 * 2, qe = q + 2; uint32_t ph = 0;
            for (int ic = 0;; ic++) {
                if (warp == 8 && rank == 0) {
                    const int t = tnext + ne;
                    asm volatile("st.shared.s32 [%0], %1;" :: "r"(slot + (ic & 7) * 4), "r"(t) : "memory");
                    mbar_arrive(bar_item + 8 * (ic & 7));
                    st_async_b32(mapa_u32(slot + (ic & 7) * 4, 1), (uint32_t)t, mapa_u32(bar_item + 8 * (ic & 7), 1));
                    if (t < nh + O2_FINE) tnext = take_ticket(CT_OT + pt);
                }
#pragma unroll 1
                for (; q < qe; q++) {
                    const int b = q >> 6, head = (q >> 1) & 31, dk = (q & 1) * 64;
                    mbar_wait(bar_empty + 8 * s, ph ^ 1);
                    const uint32_t sa = sbase + s * 49152;
                    if (warp == 8) {
                        const int f = b ? 4 : head >> 3;
                        if (!((ready >> f) & 1)) {
                            if (b && !(ready & 8)) { wait_ctr(CT_CA + mt * 4 + 3, 16u); ready |= 8; }
                            wait_ctr(b ? CT_CB + mt : CT_CA + mt * 4 + f, b ? 64u : 16u); ready |= 1 << f;
                        }
                        if (ic > 0) {
                            mbar_expect_tx(bar_full + 8 * s, 49152);
                            tma_load_2d(sa, &P.mapCtx[b], bar_full + 8 * s, dk, head * SEQ + m0);
                        }
                    } else {
                        const int j = (int)rank * 2 + (warp - 9);
                        tma_load_2d_mc(sa + 16384 + j * 8192, &P.mapWo[b], bar_full + 8 * s, n0 + j * 64, head * HD + dk, (uint16_t)3);
                    }
                    if (ic == 0 && s == 0) OTP(12, 288);
                    if (++s == O2_STAGES) { s = 0; ph ^= 1; }
                }
                if (warp == 8 && rank == 1) mbar_expect_tx(bar_item + 8 * (ic & 7), 4);
                mbar_wait(bar_item + 8 * (ic & 7), (ic >> 3) & 1);
                int t;
                asm volatile("ld.shared.s32 %0, [%1];" : "=r"(t) : "r"(slot + (ic & 7) * 4) : "memory");
                if (t >= nh + O2_FINE) break;
                if (t < nh - O2_FINE) { q = 2 * t; qe = q + 2; } else { q = nh - O2_FINE + t; qe = q + 1; }
            }
            if (warp == 8) {
                asm volatile("prefetch.tensormap [%0];" :: "l"(&P.mapOut) : "memory");
                if (!(ready & 8)) wait_ctr(CT_CA + mt * 4 + 3, 16u);
                mbar_wait(bar_empty + 8 * s, ph ^ 1);
                asm volatile("st.shared.s32 [%0], %1;" :: "r"(stop + s * 4), "r"(1) : "memory");
                mbar_arrive(bar_full + 8 * s);
                if (atomicAdd(&g_ctr[CT_FIN], 1u) == gridDim.x - 1)
                    for (int i = 0; i < CT_N / 4; i++) reinterpret_cast<uint4*>(g_ctr)[i] = make_uint4(0u, 0u, 0u, 0u);
                for (int i = 1; i < O2_STAGES; i++) {
                    if (++s == O2_STAGES) { s = 0; ph ^= 1; }
                    mbar_wait(bar_empty + 8 * s, ph ^ 1);
                }
            }
        }
    } else {
        const int wg = warp >> 2;
        const bool elected = (threadIdx.x & 127) == 0;
        float acc[128];
#pragma unroll
        for (int i = 0; i < 128; i++) acc[i] = 0.f;
        int s = 0, sprev = 0; uint32_t ph = 0;
#pragma unroll 1
        for (int i = 0;; i++) {
            mbar_wait(bar_full + 8 * s, ph);
            int st;
            asm volatile("ld.shared.s32 %0, [%1];" : "=r"(st) : "r"(stop + s * 4) : "memory");
            if (st) break;
            if (i == 0) OT(1);
            const uint32_t sa = sbase + s * 49152 + wg * 8192, sb = sbase + s * 49152 + 16384;
            wgmma_fence();
#pragma unroll
            for (int kk = 0; kk < 4; kk++)
                wgmma_ss_n256_tb(acc, make_desc(sa + kk * 32, 16, 1024), make_desc(sb + kk * 2048, 8192, 1024), 1);
            wgmma_commit();
            if (i > 0) {
                wgmma_wait<1>();
                if (elected) { const uint32_t e = bar_empty + 8 * sprev; mbar_arrive_cl(mapa_u32(e, 0)); mbar_arrive_cl(mapa_u32(e, 1)); }
            }
            sprev = s;
            if (++s == O2_STAGES) { s = 0; ph ^= 1; }
        }
        wgmma_wait<0>();
        if (elected) { const uint32_t e = bar_empty + 8 * sprev; mbar_arrive_cl(mapa_u32(e, 0)); mbar_arrive_cl(mapa_u32(e, 1)); }
        asm volatile("bar.sync %0, 128;" :: "r"(1 + wg) : "memory");
        OT(3);
        const int row = (lane & 7) + ((lane >> 3) & 1) * 8;
#pragma unroll
        for (int bx = 0; bx < 4; bx++) {
            const uint32_t stg = sbase + bx * 49152 + warp * 2048;
#pragma unroll
            for (int j = 0; j < 8; j += 2) {
                const float* a = &acc[bx * 32 + j * 4];
                stmatrix_x4(stg + row * 128 + (((j + (lane >> 4)) ^ (row & 7)) << 4), pack_bf16(a[0], a[1]), pack_bf16(a[2], a[3]), pack_bf16(a[4], a[5]), pack_bf16(a[6], a[7]));
            }
            asm volatile("fence.proxy.async.shared::cta;" ::: "memory");
            __syncwarp();
            if (lane == 0)
                asm volatile("cp.reduce.async.bulk.tensor.2d.global.shared::cta.add.tile.bulk_group [%0, {%2, %3}], [%1];"
                             :: "l"((uint64_t)&P.mapOut), "r"(stg), "r"(n0 + bx * 64), "r"(m0 + warp * 16) : "memory");
        }
        OT(4);
        if (lane == 0) {
            asm volatile("cp.async.bulk.commit_group;" ::: "memory");
            asm volatile("cp.async.bulk.wait_group.read 0;" ::: "memory");
        }
        TS_END(4);
    }
}

typedef CUresult (*PFN_encodeTiled)(CUtensorMap*, CUtensorMapDataType, cuuint32_t, void*, const cuuint64_t*,
                                    const cuuint64_t*, const cuuint32_t*, const cuuint32_t*, CUtensorMapInterleave,
                                    CUtensorMapSwizzle, CUtensorMapL2promotion, CUtensorMapFloatOOBfill);
static PFN_encodeTiled g_encode = nullptr;

static void make_map(CUtensorMap* m, const void* ptr, uint64_t rows, uint64_t cols, uint32_t box_rows, bool sw64 = false) {
    cuuint64_t dims[2] = {cols, rows};
    cuuint64_t strides[1] = {cols * 2};
    cuuint32_t box[2] = {sw64 ? 32u : 64u, box_rows};
    cuuint32_t es[2] = {1, 1};
    g_encode(m, CU_TENSOR_MAP_DATA_TYPE_BFLOAT16, 2, const_cast<void*>(ptr), dims, strides, box, es,
             CU_TENSOR_MAP_INTERLEAVE_NONE, sw64 ? CU_TENSOR_MAP_SWIZZLE_64B : CU_TENSOR_MAP_SWIZZLE_128B, CU_TENSOR_MAP_L2_PROMOTION_L2_256B,
             CU_TENSOR_MAP_FLOAT_OOB_FILL_NONE);
}

template <typename... KArgs, typename... Args>
static void launch_pdl(void (*kernel)(KArgs...), int grid, int block, size_t smem, cudaStream_t st, bool pdl, Args... args) {
    cudaLaunchConfig_t cfg = {};
    cfg.gridDim = dim3(grid); cfg.blockDim = dim3(block); cfg.dynamicSmemBytes = smem; cfg.stream = st;
    cudaLaunchAttribute at[1];
    at[0].id = cudaLaunchAttributeProgrammaticStreamSerialization;
    at[0].val.programmaticStreamSerializationAllowed = 1;
    cfg.attrs = at; cfg.numAttrs = pdl ? 1 : 0;
    cudaLaunchKernelEx(&cfg, kernel, KArgs(args)...);
}

extern "C" void kernel_launch(void* const* d_in, const int* in_sizes, int n_in, void* d_out, int out_size) {
    const bf16* x = (const bf16*)d_in[0];
    const bf16* ckv = (const bf16*)d_in[1];
    const bf16* wq = (const bf16*)d_in[2];
    const bf16* wuk = (const bf16*)d_in[3];
    const bf16* wuv = (const bf16*)d_in[4];
    const bf16* wo = (const bf16*)d_in[5];
    const bf16* mem0 = (const bf16*)d_in[7];
    const bf16* Wq = (const bf16*)d_in[8];
    const bf16* Wk = (const bf16*)d_in[9];
    const bf16* Wv = (const bf16*)d_in[10];
    const bf16* Wo = (const bf16*)d_in[11];
    const bf16* gate_w = (const bf16*)d_in[13];
    bf16* out = (bf16*)d_out;

    static Proj2Params P2;
    static ChainParams CP;
    static AttnParams AP;
    static OutParams OP;
    static bool init = false;
    static const void* last_in[14];
    static const void* last_out;
    bool same = init && last_out == d_out;
    for (int i = 0; i < 14 && same; i++) same = last_in[i] == d_in[i];
    if (!init) {
        cudaDriverEntryPointQueryResult qr;
        cudaGetDriverEntryPoint("cuTensorMapEncodeTiled", (void**)&g_encode, cudaEnableDefault, &qr);
        cudaFuncSetAttribute(proj2_kernel, cudaFuncAttributeMaxDynamicSharedMemorySize, P2_SMEM);
        cudaFuncSetAttribute(attn_kernel, cudaFuncAttributeMaxDynamicSharedMemorySize, FA_SMEM);
        cudaFuncSetAttribute(chain_kernel, cudaFuncAttributeMaxDynamicSharedMemorySize, CH_SMEM);
        cudaFuncSetAttribute(out2_kernel, cudaFuncAttributeMaxDynamicSharedMemorySize, O2_SMEM);
        init = true;
    }
    if (!same) {
        for (int i = 0; i < 14; i++) last_in[i] = d_in[i];
        last_out = d_out;
        void *pQA, *pKA, *pVA, *pCA, *pCB;
        cudaGetSymbolAddress(&pQA, g_QA); cudaGetSymbolAddress(&pKA, g_KA); cudaGetSymbolAddress(&pVA, g_VA);
        cudaGetSymbolAddress(&pCA, g_ctxA); cudaGetSymbolAddress(&pCB, g_ctxB);
        make_map(&P2.mapA[0], x, SEQ, DM, 128);
        make_map(&P2.mapA[1], ckv, SEQ, DM, 128);
        const void* ws[3] = {wq, wuk, wuv};
        void* cs[3] = {pQA, pKA, pVA};
        for (int i = 0; i < 3; i++) { make_map(&P2.mapW[i], ws[i], DM, NQ, 64); P2.out[i] = (bf16*)cs[i]; }
        make_map(&CP.mapW[0], Wq, DM, NQ, 64); make_map(&CP.mapW[1], Wk, DM, NQ, 64); make_map(&CP.mapW[2], Wv, DM, NQ, 64);
        make_map(&CP.mapX, x, SEQ, DM, 32);
        make_map(&CP.mapC, pCB, NH * SEQ, HD, 32);
        make_map(&AP.mapQ, pQA, NH * SEQ, HD, 128);
        make_map(&AP.mapK, pKA, NH * SEQ, HD, 128);
        make_map(&AP.mapV, pVA, NH * SEQ, HD, 128);
        make_map(&AP.mapO, pCA, NH * SEQ, HD, 64);
        make_map(&OP.mapCtx[0], pCA, NH * SEQ, HD, 128);
        make_map(&OP.mapCtx[1], pCB, NH * SEQ, HD, 128);
        make_map(&OP.mapWo[0], wo, NQ, DM, 64);
        make_map(&OP.mapWo[1], Wo, NQ, DM, 64);
        make_map(&OP.mapOut, out, SEQ, DM, 16);
        AP.out = out;
    }
    cudaStream_t s1 = cudaStreamPerThread;
    const bool pdl = true;
    launch_pdl(chain_kernel, 64, CH_BLOCK, CH_SMEM, s1, false, CP, mem0, Wo, x, gate_w);
    launch_pdl(proj2_kernel, 68, 384, P2_SMEM, s1, pdl, P2);
    launch_pdl(attn_kernel, FA_GRID, 384, FA_SMEM, s1, pdl, AP);
    launch_pdl(out2_kernel, O2_GRID, 352, O2_SMEM, s1, pdl, OP);
}
```

```cpp
#include <cuda_runtime.h>
#include <cuda_bf16.h>
#include <cuda.h>
#include <stdint.h>
#include <type_traits>

constexpr int SEQ = 2048;
constexpr int DM = 512;
constexpr int NH = 32;
constexpr int HD = 128;
constexpr int NQ = NH * HD;
constexpr int SEGL = 32;
constexpr int NMEM = 8;
constexpr int NSEG = SEQ / SEGL;

typedef __nv_bfloat16 bf16;

__device__ bf16 g_QA[SEQ * NQ];
__device__ bf16 g_KA[SEQ * NQ];
__device__ bf16 g_VA[SEQ * NQ];
__device__ bf16 g_ctxA[SEQ * NQ];
__device__ bf16 g_ctxB[SEQ * NQ];
constexpr int CT_PROJ = 0, CT_ATTN = 1, CT_FIN = 5;
constexpr int CT_AP = 64;
constexpr int CT_GATE = 96;
constexpr int CT_CA = 128;
constexpr int CT_CB = 192;
constexpr int CT_OT = 208;
constexpr int CT_N = 224;
__device__ __align__(16) unsigned int g_ctr[CT_N];
__device__ float g_gate[SEQ];
__device__ uint32_t g_xbuf[4 * 8 * 2048];

#define FA_GRID 68

#define TS_BEGIN(id)
#define TS_END(id)
#define WAIT_LIMIT 200000
__device__ __forceinline__ void pdl_launch_dependents() { asm volatile("griddepcontrol.launch_dependents;" ::: "memory"); }
__device__ __forceinline__ void wait_ctr(int idx, unsigned int n) {
    unsigned int v; int it = 0;
    do { asm volatile("ld.acquire.gpu.global.u32 %0, [%1];" : "=r"(v) : "l"(&g_ctr[idx]) : "memory"); } while (v < n && ++it < WAIT_LIMIT);
    asm volatile("fence.proxy.async.shared::cta;" ::: "memory");
}
__device__ __forceinline__ int take_ticket(int idx) {
    int v;
    asm volatile("atom.relaxed.gpu.global.inc.u32 %0, [%1], 0x7fffffff;" : "=r"(v) : "l"(&g_ctr[idx]) : "memory");
    return v;
}
__device__ __forceinline__ void signal_ctr(int idx) {
    asm volatile("fence.proxy.async;" ::: "memory");
    __threadfence();
    atomicAdd(&g_ctr[idx], 1u);
}
__device__ __forceinline__ void signal_ctr_generic(int idx) {
    asm volatile("red.release.gpu.global.add.u32 [%0], 1;" :: "l"(&g_ctr[idx]) : "memory");
}
__device__ __forceinline__ uint32_t smem_u32(const void* p) {
    return (uint32_t)__cvta_generic_to_shared(p);
}
__device__ __forceinline__ void mbar_init(uint32_t bar, uint32_t count) {
    asm volatile("mbarrier.init.shared::cta.b64 [%0], %1;" :: "r"(bar), "r"(count));
}
__device__ __forceinline__ void mbar_expect_tx(uint32_t bar, uint32_t bytes) {
    asm volatile("mbarrier.arrive.expect_tx.shared::cta.b64 _, [%0], %1;" :: "r"(bar), "r"(bytes) : "memory");
}
__device__ __forceinline__ void mbar_arrive(uint32_t bar) {
    asm volatile("mbarrier.arrive.shared::cta.b64 _, [%0];" :: "r"(bar) : "memory");
}
__device__ __forceinline__ void mbar_wait(uint32_t bar, uint32_t parity) {
    asm volatile(
        "{\n"
        ".reg .pred p, q;\n"
        ".reg .u32 c;\n"
        "mov.u32 c, 0;\n"
        "WAIT_LOOP:\n"
        "mbarrier.try_wait.parity.shared::cta.b64 p, [%0], %1;\n"
        "@p bra WAIT_DONE;\n"
        "add.u32 c, c, 1;\n"
        "setp.lt.u32 q, c, %2;\n"
        "@q bra WAIT_LOOP;\n"
        "WAIT_DONE:\n"
        "}\n" :: "r"(bar), "r"(parity), "n"(WAIT_LIMIT) : "memory");
}
__device__ __forceinline__ uint32_t mbar_test(uint32_t bar, uint32_t parity) {
    uint32_t done;
    asm volatile(
        "{\n.reg .pred p;\n"
        "mbarrier.test_wait.parity.shared::cta.b64 p, [%1], %2;\n"
        "selp.u32 %0, 1, 0, p;\n}\n" : "=r"(done) : "r"(bar), "r"(parity) : "memory");
    return done;
}
__device__ __forceinline__ uint32_t mbar_try(uint32_t bar, uint32_t parity) {
    uint32_t done;
    asm volatile(
        "{\n.reg .pred p;\n"
        "mbarrier.try_wait.parity.shared::cta.b64 p, [%1], %2;\n"
        "selp.u32 %0, 1, 0, p;\n}\n" : "=r"(done) : "r"(bar), "r"(parity) : "memory");
    return done;
}
__device__ __forceinline__ void tma_load_2d(uint32_t dst, const CUtensorMap* map, uint32_t bar, int c0, int c1) {
    asm volatile(
        "cp.async.bulk.tensor.2d.shared::cluster.global.mbarrier::complete_tx::bytes [%0], [%1, {%3, %4}], [%2];"
        :: "r"(dst), "l"((uint64_t)map), "r"(bar), "r"(c0), "r"(c1) : "memory");
}
__device__ __forceinline__ void wgmma_fence() { asm volatile("wgmma.fence.sync.aligned;" ::: "memory"); }
__device__ __forceinline__ void wgmma_commit() { asm volatile("wgmma.commit_group.sync.aligned;" ::: "memory"); }
template <int N> __device__ __forceinline__ void wgmma_wait() {
    asm volatile("wgmma.wait_group.sync.aligned %0;" :: "n"(N) : "memory");
}
__device__ __forceinline__ uint64_t make_desc(uint32_t addr, uint32_t lbo, uint32_t sbo) {
    uint64_t d = 0;
    d |= (uint64_t)((addr & 0x3FFFF) >> 4);
    d |= (uint64_t)((lbo >> 4) & 0x3FFF) << 16;
    d |= (uint64_t)((sbo >> 4) & 0x3FFF) << 32;
    d |= (uint64_t)1 << 62;
    return d;
}

#define ACC64(d) \
    "+f"(d[0]), "+f"(d[1]), "+f"(d[2]), "+f"(d[3]), "+f"(d[4]), "+f"(d[5]), "+f"(d[6]), "+f"(d[7]), \
    "+f"(d[8]), "+f"(d[9]), "+f"(d[10]), "+f"(d[11]), "+f"(d[12]), "+f"(d[13]), "+f"(d[14]), "+f"(d[15]), \
    "+f"(d[16]), "+f"(d[17]), "+f"(d[18]), "+f"(d[19]), "+f"(d[20]), "+f"(d[21]), "+f"(d[22]), "+f"(d[23]), \
    "+f"(d[24]), "+f"(d[25]), "+f"(d[26]), "+f"(d[27]), "+f"(d[28]), "+f"(d[29]), "+f"(d[30]), "+f"(d[31]), \
    "+f"(d[32]), "+f"(d[33]), "+f"(d[34]), "+f"(d[35]), "+f"(d[36]), "+f"(d[37]), "+f"(d[38]), "+f"(d[39]), \
    "+f"(d[40]), "+f"(d[41]), "+f"(d[42]), "+f"(d[43]), "+f"(d[44]), "+f"(d[45]), "+f"(d[46]), "+f"(d[47]), \
    "+f"(d[48]), "+f"(d[49]), "+f"(d[50]), "+f"(d[51]), "+f"(d[52]), "+f"(d[53]), "+f"(d[54]), "+f"(d[55]), \
    "+f"(d[56]), "+f"(d[57]), "+f"(d[58]), "+f"(d[59]), "+f"(d[60]), "+f"(d[61]), "+f"(d[62]), "+f"(d[63])
#define ACC64_STR \
    "{%0, %1, %2, %3, %4, %5, %6, %7, %8, %9, %10, %11, %12, %13, %14, %15, " \
    "%16, %17, %18, %19, %20, %21, %22, %23, %24, %25, %26, %27, %28, %29, %30, %31, " \
    "%32, %33, %34, %35, %36, %37, %38, %39, %40, %41, %42, %43, %44, %45, %46, %47, " \
    "%48, %49, %50, %51, %52, %53, %54, %55, %56, %57, %58, %59, %60, %61, %62, %63}"

template <int TB>
__device__ __forceinline__ void wgmma_ss_n128(float (&d)[64], uint64_t da, uint64_t db, int scale_d) {
    asm volatile(
        "{\n.reg .pred p;\nsetp.ne.b32 p, %66, 0;\n"
        "wgmma.mma_async.sync.aligned.m64n128k16.f32.bf16.bf16 " ACC64_STR ", %64, %65, p, 1, 1, 0, %67;\n}\n"
        : ACC64(d) : "l"(da), "l"(db), "r"(scale_d), "n"(TB));
}
__device__ __forceinline__ uint32_t desc_lo(uint32_t addr, uint32_t lbo) { return ((addr & 0x3FFFF) >> 4) | ((lbo >> 4) << 16); }
template <int TB>
__device__ __forceinline__ void wgmma_ss_n128_lo(float (&d)[64], uint32_t da_lo, uint32_t db_lo, int scale_d) {
    asm volatile(
        "{\n.reg .pred p;\n.reg .b64 da, db;\nsetp.ne.b32 p, %66, 0;\n"
        "mov.b64 da, {%64, 0x40000040};\nmov.b64 db, {%65, 0x40000040};\n"
        "wgmma.mma_async.sync.aligned.m64n128k16.f32.bf16.bf16 " ACC64_STR ", da, db, p, 1, 1, 0, %67;\n}\n"
        : ACC64(d) : "r"(da_lo), "r"(db_lo), "r"(scale_d), "n"(TB));
}
__device__ __forceinline__ void wgmma_rs_n128_tb(float (&d)[64], uint32_t a0, uint32_t a1, uint32_t a2, uint32_t a3,
                                                 uint64_t db, int scale_d) {
    asm volatile(
        "{\n.reg .pred p;\nsetp.ne.b32 p, %69, 0;\n"
        "wgmma.mma_async.sync.aligned.m64n128k16.f32.bf16.bf16 " ACC64_STR ", {%64, %65, %66, %67}, %68, p, 1, 1, 1;\n}\n"
        : ACC64(d) : "r"(a0), "r"(a1), "r"(a2), "r"(a3), "l"(db), "r"(scale_d));
}
__device__ __forceinline__ void wgmma_rs_n80(float (&d)[40], const uint32_t (&a)[4], uint32_t db_lo, int scale_d) {
    asm volatile(
        "{\n.reg .pred p;\n.reg .b64 db;\nsetp.ne.b32 p, %45, 0;\nmov.b64 db, {%44, 0x40000040};\n"
        "wgmma.mma_async.sync.aligned.m64n80k16.f32.bf16.bf16 "
        "{%0, %1, %2, %3, %4, %5, %6, %7, %8, %9, %10, %11, %12, %13, %14, %15, %16, %17, %18, %19, %20, %21, %22, %23, %24, %25, %26, %27, %28, %29, %30, %31, %32, %33, %34, %35, %36, %37, %38, %39}, "
        "{%40, %41, %42, %43}, db, p, 1, 1, 0;\n}\n"
        : "+f"(d[0]), "+f"(d[1]), "+f"(d[2]), "+f"(d[3]), "+f"(d[4]), "+f"(d[5]), "+f"(d[6]), "+f"(d[7]), "+f"(d[8]), "+f"(d[9]), "+f"(d[10]), "+f"(d[11]), "+f"(d[12]), "+f"(d[13]), "+f"(d[14]), "+f"(d[15]), "+f"(d[16]), "+f"(d[17]), "+f"(d[18]), "+f"(d[19]), "+f"(d[20]), "+f"(d[21]), "+f"(d[22]), "+f"(d[23]), "+f"(d[24]), "+f"(d[25]), "+f"(d[26]), "+f"(d[27]), "+f"(d[28]), "+f"(d[29]), "+f"(d[30]), "+f"(d[31]), "+f"(d[32]), "+f"(d[33]), "+f"(d[34]), "+f"(d[35]), "+f"(d[36]), "+f"(d[37]), "+f"(d[38]), "+f"(d[39])
        : "r"(a[0]), "r"(a[1]), "r"(a[2]), "r"(a[3]), "r"(db_lo), "r"(scale_d));
}
__device__ __forceinline__ void wgmma_ss_n256_tb(float (&d)[128], uint64_t da, uint64_t db, int scale_d) {
    asm volatile(
        "{\n.reg .pred p;\nsetp.ne.b32 p, %130, 0;\n"
        "wgmma.mma_async.sync.aligned.m64n256k16.f32.bf16.bf16 {%0, %1, %2, %3, %4, %5, %6, %7, %8, %9, %10, %11, %12, %13, %14, %15, %16, %17, %18, %19, %20, %21, %22, %23, %24, %25, %26, %27, %28, %29, %30, %31, %32, %33, %34, %35, %36, %37, %38, %39, %40, %41, %42, %43, %44, %45, %46, %47, %48, %49, %50, %51, %52, %53, %54, %55, %56, %57, %58, %59, %60, %61, %62, %63, %64, %65, %66, %67, %68, %69, %70, %71, %72, %73, %74, %75, %76, %77, %78, %79, %80, %81, %82, %83, %84, %85, %86, %87, %88, %89, %90, %91, %92, %93, %94, %95, %96, %97, %98, %99, %100, %101, %102, %103, %104, %105, %106, %107, %108, %109, %110, %111, %112, %113, %114, %115, %116, %117, %118, %119, %120, %121, %122, %123, %124, %125, %126, %127}, %128, %129, p, 1, 1, 0, 1;\n}\n"
        : "+f"(d[0]), "+f"(d[1]), "+f"(d[2]), "+f"(d[3]), "+f"(d[4]), "+f"(d[5]), "+f"(d[6]), "+f"(d[7]), "+f"(d[8]), "+f"(d[9]), "+f"(d[10]), "+f"(d[11]), "+f"(d[12]), "+f"(d[13]), "+f"(d[14]), "+f"(d[15]), "+f"(d[16]), "+f"(d[17]), "+f"(d[18]), "+f"(d[19]), "+f"(d[20]), "+f"(d[21]), "+f"(d[22]), "+f"(d[23]), "+f"(d[24]), "+f"(d[25]), "+f"(d[26]), "+f"(d[27]), "+f"(d[28]), "+f"(d[29]), "+f"(d[30]), "+f"(d[31]), "+f"(d[32]), "+f"(d[33]), "+f"(d[34]), "+f"(d[35]), "+f"(d[36]), "+f"(d[37]), "+f"(d[38]), "+f"(d[39]), "+f"(d[40]), "+f"(d[41]), "+f"(d[42]), "+f"(d[43]), "+f"(d[44]), "+f"(d[45]), "+f"(d[46]), "+f"(d[47]), "+f"(d[48]), "+f"(d[49]), "+f"(d[50]), "+f"(d[51]), "+f"(d[52]), "+f"(d[53]), "+f"(d[54]), "+f"(d[55]), "+f"(d[56]), "+f"(d[57]), "+f"(d[58]), "+f"(d[59]), "+f"(d[60]), "+f"(d[61]), "+f"(d[62]), "+f"(d[63]), "+f"(d[64]), "+f"(d[65]), "+f"(d[66]), "+f"(d[67]), "+f"(d[68]), "+f"(d[69]), "+f"(d[70]), "+f"(d[71]), "+f"(d[72]), "+f"(d[73]), "+f"(d[74]), "+f"(d[75]), "+f"(d[76]), "+f"(d[77]), "+f"(d[78]), "+f"(d[79]), "+f"(d[80]), "+f"(d[81]), "+f"(d[82]), "+f"(d[83]), "+f"(d[84]), "+f"(d[85]), "+f"(d[86]), "+f"(d[87]), "+f"(d[88]), "+f"(d[89]), "+f"(d[90]), "+f"(d[91]), "+f"(d[92]), "+f"(d[93]), "+f"(d[94]), "+f"(d[95]), "+f"(d[96]), "+f"(d[97]), "+f"(d[98]), "+f"(d[99]), "+f"(d[100]), "+f"(d[101]), "+f"(d[102]), "+f"(d[103]), "+f"(d[104]), "+f"(d[105]), "+f"(d[106]), "+f"(d[107]), "+f"(d[108]), "+f"(d[109]), "+f"(d[110]), "+f"(d[111]), "+f"(d[112]), "+f"(d[113]), "+f"(d[114]), "+f"(d[115]), "+f"(d[116]), "+f"(d[117]), "+f"(d[118]), "+f"(d[119]), "+f"(d[120]), "+f"(d[121]), "+f"(d[122]), "+f"(d[123]), "+f"(d[124]), "+f"(d[125]), "+f"(d[126]), "+f"(d[127])
        : "l"(da), "l"(db), "r"(scale_d));
}
__device__ __forceinline__ void stmatrix_x4(uint32_t addr, uint32_t r0, uint32_t r1, uint32_t r2, uint32_t r3) {
    asm volatile("stmatrix.sync.aligned.m8n8.x4.shared.b16 [%0], {%1, %2, %3, %4};" :: "r"(addr), "r"(r0), "r"(r1), "r"(r2), "r"(r3) : "memory");
}
__device__ __forceinline__ void tma_store_2d(const CUtensorMap* map, uint32_t src, int c0, int c1) {
    asm volatile("cp.async.bulk.tensor.2d.global.shared::cta.bulk_group [%0, {%2, %3}], [%1];"
                 :: "l"((uint64_t)map), "r"(src), "r"(c0), "r"(c1) : "memory");
}
__device__ __forceinline__ float ex2f(float x) { float y; asm("ex2.approx.ftz.f32 %0, %1;" : "=f"(y) : "f"(x)); return y; }
__device__ __forceinline__ uint32_t pack_bf16(float lo, float hi) {
    __nv_bfloat162 v = __floats2bfloat162_rn(lo, hi);
    return *reinterpret_cast<uint32_t*>(&v);
}
__device__ __forceinline__ void mma_16816(float (&c)[4], uint32_t a0, uint32_t a1, uint32_t a2, uint32_t a3,
                                          uint32_t b0, uint32_t b1) {
    asm volatile(
        "mma.sync.aligned.m16n8k16.row.col.f32.bf16.bf16.f32 {%0,%1,%2,%3}, {%4,%5,%6,%7}, {%8,%9}, {%0,%1,%2,%3};"
        : "+f"(c[0]), "+f"(c[1]), "+f"(c[2]), "+f"(c[3])
        : "r"(a0), "r"(a1), "r"(a2), "r"(a3), "r"(b0), "r"(b1));
}
__device__ __forceinline__ void ldmatrix_x4_trans(uint32_t& r0, uint32_t& r1, uint32_t& r2, uint32_t& r3, uint32_t addr) {
    asm volatile("ldmatrix.sync.aligned.m8n8.x4.trans.shared.b16 {%0,%1,%2,%3}, [%4];"
                 : "=r"(r0), "=r"(r1), "=r"(r2), "=r"(r3) : "r"(addr));
}

struct AttnParams {
    CUtensorMap mapQ, mapK, mapV;
    CUtensorMap mapO;
    bf16* out;
};
constexpr int FA_SMEM = 2 * 32768 + 2 * 65536 + 32768 + 1024 + 256;
constexpr int FA_ITEMS = 16 * NH;
__device__ __forceinline__ int fa_qt(int t) { return 15 - ((t & 127) >> 3); }
__device__ __forceinline__ int fa_head(int t) { return (t >> 7) * 8 + (t & 7); }
#define FA_TKA 2
#define FA_SPLIT 11

#define FA_P0 3
#define FA_HO 7
#define FA_LAG 2
#define FA_PK 3
#define FA_ST 4
#define FA_TG 16
#define FA_EARLY 0
#define FA_I0 0
static_assert(FA_GRID <= 104 && FA_HO >= FA_P0 && FA_P0 >= 1, "");
constexpr float FA_MARGIN = 16.f;
#define FAT(b, i)
__device__ __forceinline__ void mbar_arrive_if(uint32_t bar, bool c) {
    asm volatile("{\n.reg .pred p;\nsetp.ne.b32 p, %1, 0;\n@p mbarrier.arrive.shared::cta.b64 _, [%0];\n}" :: "r"(bar), "r"((int)c) : "memory");
}
__device__ __forceinline__ void sched_fence(int v, int id, const float* a, const float* b, const float* c) {
    asm volatile("{\n.reg .pred p;\nsetp.ne.s32 p, %0, %1;\n@p bra SF_SKIP;\nwgmma.wait_group.sync.aligned 0;\n"
                 "st.volatile.shared.f32 [%0], %2;\nst.volatile.shared.f32 [%0], %3;\nst.volatile.shared.f32 [%0], %4;\nst.volatile.shared.f32 [%0], %5;\n"
                 "st.volatile.shared.f32 [%0], %6;\nst.volatile.shared.f32 [%0], %7;\nst.volatile.shared.f32 [%0], %8;\nst.volatile.shared.f32 [%0], %9;\n"
                 "st.volatile.shared.f32 [%0], %10;\nst.volatile.shared.f32 [%0], %11;\nst.volatile.shared.f32 [%0], %12;\nst.volatile.shared.f32 [%0], %13;\n"
                 "exit;\nSF_SKIP:\n}" :: "r"(v), "r"(1000000 + id), "f"(a[0]), "f"(a[1]), "f"(a[2]), "f"(a[3]), "f"(b[0]), "f"(b[1]), "f"(b[2]), "f"(b[3]),
                 "f"(c[0]), "f"(c[1]), "f"(c[2]), "f"(c[3]) : "memory");
}
__device__ __forceinline__ float ex2v(float x) { float y; asm volatile("ex2.approx.ftz.f32 %0, %1;" : "=f"(y) : "f"(x)); return y; }
__device__ __forceinline__ void wgmma_rs_n128_tb_lo(float (&d)[64], const uint32_t* a, uint32_t db_lo, int scale_d) {
    asm volatile(
        "{\n.reg .pred p;\n.reg .b64 db;\nsetp.ne.b32 p, %69, 0;\nmov.b64 db, {%68, 0x40000040};\n"
        "wgmma.mma_async.sync.aligned.m64n128k16.f32.bf16.bf16 " ACC64_STR ", {%64, %65, %66, %67}, db, p, 1, 1, 1;\n}\n"
        : ACC64(d) : "r"(a[0]), "r"(a[1]), "r"(a[2]), "r"(a[3]), "r"(db_lo), "r"(scale_d));
}

__global__ void __launch_bounds__(384, 1) attn_kernel(const __grid_constant__ AttnParams P) {
    extern __shared__ uint8_t smem_raw[];
    constexpr uint32_t sbase = 1024;
    if (smem_u32(smem_raw) > sbase) __trap();
    constexpr uint32_t sQ = sbase;
    constexpr uint32_t sKV = sbase + 65536;
    constexpr uint32_t sO = sKV + 2 * 65536;
    constexpr uint32_t bars = sO + 32768;
    constexpr uint32_t bar_qf = bars, bar_qe = bars + 16, bar_kf = bars + 32, bar_vf = bars + 48, bar_ke = bars + 64, bar_ve = bars + 80,
                   bar_of = bars + 96, bar_oe = bars + 112, slot = bars + 128, oslot = bars + 136;
    const int warp = __shfl_sync(0xffffffff, threadIdx.x >> 5, 0);
    TS_BEGIN(1);
    if (threadIdx.x == 256) {
        asm volatile("prefetch.tensormap [%0];" :: "l"(&P.mapQ) : "memory");
        asm volatile("prefetch.tensormap [%0];" :: "l"(&P.mapK) : "memory");
        for (int i = 0; i < 2; i++) {
            mbar_init(bar_qf + 8 * i, 1); mbar_init(bar_qe + 8 * i, 8); mbar_init(bar_kf + 8 * i, 1); mbar_init(bar_vf + 8 * i, 1);
            mbar_init(bar_ke + 8 * i, 8); mbar_init(bar_ve + 8 * i, 8); mbar_init(bar_of + 8 * i, 4); mbar_init(bar_oe + 8 * i, 1);
        }
        asm volatile("fence.mbarrier_init.release.cluster;" ::: "memory");
    }
    __syncthreads();
    pdl_launch_dependents();
    if (warp >= 8) {
        asm volatile("setmaxnreg.dec.sync.aligned.u32 40;");
        if (threadIdx.x == 288 || threadIdx.x == 320) {
            const int wg = threadIdx.x == 288 ? 0 : 1;
            const uint32_t stg = sO + wg * 16384;
            for (int n = 0;; n++) {
                mbar_wait(bar_of + 8 * wg, n & 1);
                int t;
                asm volatile("ld.shared.s32 %0, [%1];" : "=r"(t) : "r"(oslot + wg * 4) : "memory");
                const int qt = fa_qt(t), h = fa_head(t & 1023);
                tma_store_2d(&P.mapO, stg, 0, h * SEQ + qt * 128 + wg * 64);
                tma_store_2d(&P.mapO, stg + 8192, 64, h * SEQ + qt * 128 + wg * 64);
                asm volatile("cp.async.bulk.commit_group;" ::: "memory");
                asm volatile("cp.async.bulk.wait_group.read 0;" ::: "memory");
                mbar_arrive(bar_oe + 8 * wg);
                asm volatile("cp.async.bulk.wait_group 0;" ::: "memory");
                signal_ctr(CT_CA + qt * 4 + (h >> 3));
                if (t >= 1024) break;
            }
        }
        if (threadIdx.x == 256) {
            int b = 0, hp_ready = 0, vrow = 0, t = blockIdx.x;
            auto load_v = [&](int i) {
                const uint32_t sv = sKV + (i & 1) * 65536 + 32768, bar = bar_vf + 8 * (i & 1);
                mbar_wait(bar_ve + 8 * (i & 1), ((i >> 1) & 1) ^ 1);
                mbar_expect_tx(bar, 32768);
                tma_load_2d(sv, &P.mapV, bar, 0, vrow);
                tma_load_2d(sv + 16384, &P.mapV, bar, 64, vrow);
            };
            for (int item = 0;; item++) {
                const bool valid = t < FA_ITEMS;
                const int qt = fa_qt(t), h = fa_head(t);
                if (valid && !((hp_ready >> (h >> 1)) & 1)) { wait_ctr(CT_AP + (h >> 1), 96u); hp_ready |= 1 << (h >> 1); }
                const uint32_t bq = bar_qf + 8 * (item & 1);
                mbar_wait(bar_qe + 8 * (item & 1), ((item >> 1) & 1) ^ 1);
                asm volatile("st.shared.s32 [%0], %1;" :: "r"(slot + (item & 1) * 4), "r"(valid ? t : -1) : "memory");
                if (!valid) { mbar_arrive(bq); break; }
                mbar_expect_tx(bq, 32768);
                tma_load_2d(sQ + (item & 1) * 32768, &P.mapQ, bq, 0, h * SEQ + qt * 128);
                tma_load_2d(sQ + (item & 1) * 32768 + 16384, &P.mapQ, bq, 64, h * SEQ + qt * 128);
#pragma unroll 1
                for (int j = 0; j <= qt; j++, b++) {
                    const uint32_t sk = sKV + (b & 1) * 65536, bar = bar_kf + 8 * (b & 1);
                    mbar_wait(bar_ke + 8 * (b & 1), ((b >> 1) & 1) ^ 1);
                    if (b == 2) wait_ctr(CT_GATE, 64u);
                    mbar_expect_tx(bar, 32768);
                    tma_load_2d(sk, &P.mapK, bar, 0, h * SEQ + j * 128);
                    tma_load_2d(sk + 16384, &P.mapK, bar, 64, h * SEQ + j * 128);
                    if (j == max(qt - FA_TKA, 0)) t = take_ticket(CT_ATTN);
                    if (b > 0) load_v(b - 1);
                    vrow = h * SEQ + j * 128;
                }
                t += gridDim.x;
            }
            load_v(b - 1);
        }
    } else {
        asm volatile("setmaxnreg.inc.sync.aligned.u32 232;");
        const int wg = warp >> 2;
        const int lane = threadIdx.x & 31;
        const float sc = 0.08838834764831845f * 1.4426950408889634f;
        const int r0 = wg * 64 + (warp & 3) * 16 + (lane >> 2);
        float o[64], s[64];
        uint32_t pa[32];
        float m0 = 0.f, m1 = 0.f, l0 = 0.f, l1 = 0.f, i0 = 0.f, i1 = 0.f, g0 = 0.f, g1 = 0.f;
        const uint32_t q_lo = desc_lo(sQ + wg * 8192, 16), k_lo = desc_lo(sKV, 16), v_lo = desc_lo(sKV + 32768, 16384);
        auto issue_qk = [&](int b, int item) {
            const uint32_t qd = q_lo + (item & 1) * 2048, kd = k_lo + (b & 1) * 4096;
            wgmma_fence();
#pragma unroll
            for (int kk = 0; kk < 8; kk++) wgmma_ss_n128_lo<0>(s, qd + (kk >> 2) * 1024 + (kk & 3) * 2, kd + (kk >> 2) * 1024 + (kk & 3) * 2, kk != 0);
            wgmma_commit();
        };
        auto issue_pv = [&](int b, bool acc, int n) {
            const uint32_t vd = v_lo + (b & 1) * 4096;
            mbar_wait(bar_vf + 8 * (b & 1), (b >> 1) & 1);
            wgmma_fence();
#pragma unroll
            for (int kk = 0; kk < 8; kk++) if (kk < n) wgmma_rs_n128_tb_lo(o, &pa[kk * 4], vd + kk * 128, kk ? 1 : (int)acc);
            wgmma_commit();
        };
        const int lim = r0 - (lane & 3) * 2;
        int item = -1, tnext = 0;
        uint32_t k_ready = 0, q_ready = 0;
        auto mask = [&](int i) { if ((i >> 2) * 8 + (i & 1) - ((i & 2) ? 8 : 0) > lim) s[i] = -INFINITY; };
        auto exps = [&](auto mode, int b, bool hand_over, float& u0, float& u1) {
            constexpr int MODE = decltype(mode)::value;
            float p[64], u[4] = {0.f, 0.f, 0.f, 0.f};
            const uint32_t vd = v_lo + ((b - 1) & 1) * 4096;
#pragma unroll
            for (int i = 0; i < 4; i++) p[i] = fmaf(s[i], sc, (i & 2) ? -m1 : -m0);
#pragma unroll
            for (int g = 0; g < 16 + FA_LAG; g++) {
                if (MODE && g >= FA_I0 && g - FA_I0 < 8 - FA_P0) {
                    const int kk = FA_P0 + g - FA_I0;
                    wgmma_fence();
                    wgmma_rs_n128_tb_lo(o, &pa[kk * 4], vd + kk * 128, 1);
                    wgmma_commit();
                    if (kk == FA_HO) asm volatile("{\n.reg .pred p;\nsetp.ne.b32 p, %1, 0;\n@p bar.arrive %0, 256;\n}" :: "r"(2 - wg), "r"((int)hand_over) : "memory");
                }
                if (MODE && g == FA_SPLIT) {
                    FAT(b, 2);
                    wgmma_wait<0>();
                    FAT(b - 1, 3);
                    mbar_arrive_if(bar_ve + 8 * ((b - 1) & 1), lane == 0);
                }
                if (MODE && g == FA_TG) {
                    k_ready = mbar_test(bar_kf + 8 * (~b & 1), ((b + 1) >> 1) & 1);
                    if (MODE == 2) {
                        q_ready = mbar_test(bar_qf + 8 * (~item & 1), ((item + 1) >> 1) & 1);
                        asm volatile("ld.shared.s32 %0, [%1];" : "=r"(tnext) : "r"(slot + (~item & 1) * 4) : "memory");
                    }
                }
#pragma unroll
                for (int j = 0; j < 4; j++) {
                    const int i = g * 4 + j;
                    if (g < 16) p[i] = ex2v(p[i]);
                    if (g < 15) {
                        if (MODE == 2) mask(i + 4);
                        p[i + 4] = fmaf(s[i + 4], sc, (i & 2) ? -m1 : -m0);
                    }
                    if (g >= FA_LAG) u[j] += p[i - FA_LAG * 4];
                }
#pragma unroll
                for (int gg = 0; gg < 16; gg++) {
                    const int at = MODE && gg + FA_LAG < FA_SPLIT + gg / FA_PK ? FA_SPLIT + gg / FA_PK : gg + FA_LAG;
                    if (at == g) { pa[gg * 2] = pack_bf16(p[gg * 4], p[gg * 4 + 1]); pa[gg * 2 + 1] = pack_bf16(p[gg * 4 + 2], p[gg * 4 + 3]); }
                }
                if (MODE && g < 16) sched_fence(b, g + MODE * 32, &p[g * 4], &p[(g < 15 ? g + 1 : g) * 4], u);
            }
            u0 = u[0] + u[1]; u1 = u[2] + u[3];
        };
        auto quad_max = [&](float& x0, float& x1) {
            x0 = fmaxf(x0, __shfl_xor_sync(0xffffffff, x0, 1)); x1 = fmaxf(x1, __shfl_xor_sync(0xffffffff, x1, 1));
            x0 = fmaxf(x0, __shfl_xor_sync(0xffffffff, x0, 2)); x1 = fmaxf(x1, __shfl_xor_sync(0xffffffff, x1, 2));
            x0 = fmaf(x0, sc, FA_MARGIN); x1 = fmaf(x1, sc, FA_MARGIN);
        };
        auto softmax_exact = [&](bool fresh, int b) {
            wgmma_wait<0>();
            float x[8];
#pragma unroll
            for (int i = 0; i < 8; i++) x[i] = fmaxf(s[i * 2], s[i * 2 + 1]);
#pragma unroll
            for (int i = 8; i < 32; i++) x[i & 7] = fmaxf(x[i & 7], fmaxf(s[i * 2], s[i * 2 + 1]));
            float x0 = fmaxf(fmaxf(x[0], x[2]), fmaxf(x[4], x[6])), x1 = fmaxf(fmaxf(x[1], x[3]), fmaxf(x[5], x[7]));
            quad_max(x0, x1);
            if (!fresh) {
                x0 = fmaxf(x0, m0); x1 = fmaxf(x1, m1);
                const float a0 = ex2f(m0 - x0), a1 = ex2f(m1 - x1);
                l0 *= a0; l1 *= a1;
#pragma unroll
                for (int i = 0; i < 16; i++) { o[i * 4 + 0] *= a0; o[i * 4 + 1] *= a0; o[i * 4 + 2] *= a1; o[i * 4 + 3] *= a1; }
            }
            m0 = x0; m1 = x1;
            float u0, u1;
            exps(std::integral_constant<int, 0>(), b, false, u0, u1);
            l0 += u0; l1 += u1;
        };
        auto finish_rows = [&]() {
            l0 += __shfl_xor_sync(0xffffffff, l0, 1); l1 += __shfl_xor_sync(0xffffffff, l1, 1);
            l0 += __shfl_xor_sync(0xffffffff, l0, 2); l1 += __shfl_xor_sync(0xffffffff, l1, 2);
            i0 = __fdividef(g0, l0); i1 = __fdividef(g1, l1);
        };
        auto clear_out = [&](int t) {
            if (t >= 384) {
                bf16* z = P.out + (size_t)(fa_qt(t) * 128 + wg * 64 + ((threadIdx.x & 127) >> 3)) * DM + (t & 7) * 64 + (lane & 7) * 8;
#pragma unroll
                for (int i = 0; i < 4; i++) *reinterpret_cast<uint4*>(z + i * 16 * DM) = make_uint4(0u, 0u, 0u, 0u);
            }
        };
        auto store_o = [&](int t, int n, int c0, int c1) {
            const uint32_t stg = sO + wg * 16384;
            if (c0 == 0) {
                mbar_wait(bar_oe + 8 * wg, (n & 1) ^ 1);
                asm volatile("st.shared.s32 [%0], %1;" :: "r"(oslot + wg * 4), "r"(t) : "memory");
            }
            const int row = (warp & 3) * 16 + (lane >> 2);
#pragma unroll
            for (int i = c0; i < c1; i++) {
                const int ch = i * 4 + (lane & 3);
                const uint32_t a = stg + (ch >> 3) * 8192 + row * 128 + (((ch & 7) ^ (row & 7)) << 4);
                const float* q = &o[i * 16];
                asm volatile("st.shared.v4.b32 [%0], {%1, %2, %3, %4};" :: "r"(a), "r"(pack_bf16(q[0] * i0, q[1] * i0)), "r"(pack_bf16(q[4] * i0, q[5] * i0)),
                             "r"(pack_bf16(q[8] * i0, q[9] * i0)), "r"(pack_bf16(q[12] * i0, q[13] * i0)) : "memory");
                asm volatile("st.shared.v4.b32 [%0], {%1, %2, %3, %4};" :: "r"(a + 1024), "r"(pack_bf16(q[2] * i1, q[3] * i1)), "r"(pack_bf16(q[6] * i1, q[7] * i1)),
                             "r"(pack_bf16(q[10] * i1, q[11] * i1)), "r"(pack_bf16(q[14] * i1, q[15] * i1)) : "memory");
            }
        };
        auto publish_o = [&]() {
            asm volatile("fence.proxy.async.shared::cta;" ::: "memory");
            __syncwarp();
            mbar_arrive_if(bar_of + 8 * wg, lane == 0);
        };
        int t = 0, left = 0, tdone = -1, b = 0, nout = 0;
        bool first = true, staged = false;
        if (wg == 1) asm volatile("bar.arrive 1, 256;" ::: "memory");
#pragma unroll 1
        for (;; b++) {
            const bool fresh = left == 0;
            const int tprev = t;
            FAT(b, 4);
            if (staged) { publish_o(); staged = false; }
            if (fresh) {
                item++;
                if (!q_ready) {
                    mbar_wait(bar_qf + 8 * (item & 1), (item >> 1) & 1);
                    asm volatile("ld.shared.s32 %0, [%1];" : "=r"(tnext) : "r"(slot + (item & 1) * 4) : "memory");
                }
                if (tnext < 0) break;
                t = tnext;
                left = fa_qt(t) + 1;
            }
            left--;
            if (tdone >= 0) store_o(tdone, nout, 0, FA_ST);
            FAT(b, 5);
            if (!k_ready) mbar_wait(bar_kf + 8 * (b & 1), (b >> 1) & 1);
            FAT(b, 6);
            asm volatile("bar.sync %0, 256;" :: "r"(1 + wg) : "memory");
            FAT(b, 0);
            issue_qk(b, item);
            bool early = false;
            if (!fresh && !first && left != 0) {
                issue_pv(b - 1, true, FA_P0);
                wgmma_wait<1>();
                FAT(b, 1);
                mbar_arrive_if(bar_ke + 8 * (b & 1), lane == 0);
            } else {
                early = (FA_EARLY && tdone >= 0) || b == 0;
                if (early) asm volatile("bar.arrive %0, 256;" :: "r"(2 - wg) : "memory");
                if (tdone >= 0) { wgmma_wait<1>(); store_o(tdone, nout++, FA_ST, 4); staged = true; }
                tdone = -1;
                if (fresh && b > 0) { finish_rows(); tdone = tprev; l0 = l1 = 0.f; }
                if (left == 0) { g0 = __ldcg(g_gate + fa_qt(t) * 128 + r0); g1 = __ldcg(g_gate + fa_qt(t) * 128 + r0 + 8); clear_out(t); }
                if (b > 0) issue_pv(b - 1, !first, FA_P0); else wgmma_commit();
                first = fresh;
                wgmma_wait<1>();
                FAT(b, 1);
                mbar_arrive_if(bar_ke + 8 * (b & 1), lane == 0);
                mbar_arrive_if(bar_qe + 8 * (item & 1), lane == 0 && left == 0);
                if (left == 0) { mask(0); mask(1); }
                if (fresh) { m0 = fmaxf(s[0], s[1]); m1 = fmaxf(s[2], s[3]); quad_max(m0, m1); }
            }
            if (b > 0) {
                float u0, u1;
                if (left == 0) exps(std::integral_constant<int, 2>(), b, !early, u0, u1);
                else exps(std::integral_constant<int, 1>(), b, !early, u0, u1);
                if (!__any_sync(0xffffffff, !(u0 + u1 < 1.f))) { l0 += u0; l1 += u1; continue; }
            }
            softmax_exact(fresh, b);
        }
        if (tdone >= 0) { store_o(tdone, nout++, 0, 4); publish_o(); }
        issue_pv(b - 1, !first, 8);
        finish_rows();
        wgmma_wait<0>();
        store_o(t + 1024, nout, 0, 4);
        publish_o();
        TS_END(1);
    }
}

__device__ __forceinline__ uint32_t cluster_ctarank() {
    uint32_t r; asm volatile("mov.u32 %0, %%cluster_ctarank;" : "=r"(r)); return r;
}
__device__ __forceinline__ uint32_t mapa_u32(uint32_t addr, uint32_t rank) {
    uint32_t r; asm volatile("mapa.shared::cluster.u32 %0, %1, %2;" : "=r"(r) : "r"(addr), "r"(rank)); return r;
}
__device__ __forceinline__ void cluster_sync_all() {
    asm volatile("barrier.cluster.arrive.release.aligned;\nbarrier.cluster.wait.acquire.aligned;" ::: "memory");
}
__device__ __forceinline__ void st_async_v4(uint32_t addr, uint32_t a, uint32_t b, uint32_t c, uint32_t d, uint32_t mbar) {
    asm volatile("st.async.weak.shared::cluster.mbarrier::complete_tx::bytes.v4.b32 [%0], {%1, %2, %3, %4}, [%5];"
                 :: "r"(addr), "r"(a), "r"(b), "r"(c), "r"(d), "r"(mbar) : "memory");
}
__device__ __forceinline__ void st_async_v2(uint32_t addr, uint32_t a, uint32_t b, uint32_t mbar) {
    asm volatile("st.async.weak.shared::cluster.mbarrier::complete_tx::bytes.v2.b32 [%0], {%1, %2}, [%3];"
                 :: "r"(addr), "r"(a), "r"(b), "r"(mbar) : "memory");
}
__device__ __forceinline__ void st_async_b32(uint32_t addr, uint32_t a, uint32_t mbar) {
    asm volatile("st.async.weak.shared::cluster.mbarrier::complete_tx::bytes.b32 [%0], %1, [%2];" :: "r"(addr), "r"(a), "r"(mbar) : "memory");
}
__device__ __forceinline__ void pace(int cycles) {
    if (cycles > 0) {
        uint32_t t0, t;
        asm volatile("mov.u32 %0, %%clock;" : "=r"(t0));
        do { asm volatile("mov.u32 %0, %%clock;" : "=r"(t)); } while (t - t0 < (uint32_t)cycles);
    }
}
__device__ __forceinline__ void mbar_wait_cl(uint32_t bar, uint32_t parity) {
    uint32_t done = 0;
    for (int it = 0; it < WAIT_LIMIT && !done; it++) {
        asm volatile(
            "{\n.reg .pred p;\n"
            "mbarrier.try_wait.parity.shared::cta.b64 p, [%1], %2;\n"
            "selp.u32 %0, 1, 0, p;\n}\n" : "=r"(done) : "r"(bar), "r"(parity) : "memory");
    }
}
__device__ __forceinline__ void ldmatrix_x4(uint32_t& r0, uint32_t& r1, uint32_t& r2, uint32_t& r3, uint32_t addr) {
    asm volatile("ldmatrix.sync.aligned.m8n8.x4.shared.b16 {%0,%1,%2,%3}, [%4];"
                 : "=r"(r0), "=r"(r1), "=r"(r2), "=r"(r3) : "r"(addr));
}
__device__ __forceinline__ void cp_async16(uint32_t dst, const void* src) {
    asm volatile("cp.async.cg.shared.global [%0], [%1], 16;" :: "r"(dst), "l"(src) : "memory");
}
__device__ __forceinline__ float bf16r(float x) { return __uint_as_float(pack_bf16(0.f, x) & 0xffff0000u); }

#define DBGP(i, w, ok)
#define DBG(i, w)
#define DBGD(i, w, dep)
#define DBG_EXTRA 0
__device__ __forceinline__ void tma_load_2d_mc(uint32_t dst, const CUtensorMap* map, uint32_t bar, int c0, int c1, uint16_t mask) {
    asm volatile(
        "cp.async.bulk.tensor.2d.shared::cluster.global.mbarrier::complete_tx::bytes.multicast::cluster [%0], [%1, {%3, %4}], [%2], %5;"
        :: "r"(dst), "l"((uint64_t)map), "r"(bar), "r"(c0), "r"(c1), "h"(mask) : "memory");
}
__device__ __forceinline__ void stmatrix_x4_trans(uint32_t addr, uint32_t r0, uint32_t r1, uint32_t r2, uint32_t r3) {
    asm volatile("stmatrix.sync.aligned.m8n8.x4.trans.shared.b16 [%0], {%1, %2, %3, %4};" :: "r"(addr), "r"(r0), "r"(r1), "r"(r2), "r"(r3) : "memory");
}
__device__ __forceinline__ void stmatrix_x2_trans(uint32_t addr, uint32_t r0, uint32_t r1) {
    asm volatile("stmatrix.sync.aligned.m8n8.x2.trans.shared.b16 [%0], {%1, %2};" :: "r"(addr), "r"(r0), "r"(r1) : "memory");
}
__device__ __forceinline__ uint4 lds128(uint32_t a) {
    uint4 v; asm volatile("ld.shared.v4.u32 {%0, %1, %2, %3}, [%4];" : "=r"(v.x), "=r"(v.y), "=r"(v.z), "=r"(v.w) : "r"(a) : "memory"); return v;
}
__device__ __forceinline__ void sts128(uint32_t a, uint32_t x, uint32_t y, uint32_t z, uint32_t w) {
    asm volatile("st.shared.v4.b32 [%0], {%1, %2, %3, %4};" :: "r"(a), "r"(x), "r"(y), "r"(z), "r"(w) : "memory");
}
__device__ __forceinline__ float2 lds64f(uint32_t a) {
    float2 v; asm volatile("ld.shared.v2.f32 {%0, %1}, [%2];" : "=f"(v.x), "=f"(v.y) : "r"(a) : "memory"); return v;
}
__device__ __forceinline__ void fence_async_smem() { asm volatile("fence.proxy.async.shared::cta;" ::: "memory"); }
#define ACC16(d) "+f"(d[0]), "+f"(d[1]), "+f"(d[2]), "+f"(d[3]), "+f"(d[4]), "+f"(d[5]), "+f"(d[6]), "+f"(d[7]), "+f"(d[8]), "+f"(d[9]), "+f"(d[10]), "+f"(d[11]), "+f"(d[12]), "+f"(d[13]), "+f"(d[14]), "+f"(d[15])
template <int ND>
__device__ __forceinline__ void wgmma_rs_n32(float (&d)[ND], const uint32_t (&a)[4], uint32_t db_lo, int scale_d) {
    asm volatile(
        "{\n.reg .pred p;\n.reg .b64 db;\nsetp.ne.b32 p, %21, 0;\nmov.b64 db, {%20, 0x40000040};\n"
        "wgmma.mma_async.sync.aligned.m64n32k16.f32.bf16.bf16 {%0,%1,%2,%3,%4,%5,%6,%7,%8,%9,%10,%11,%12,%13,%14,%15}, {%16,%17,%18,%19}, db, p, 1, 1, 0;\n}\n"
        : ACC16(d) : "r"(a[0]), "r"(a[1]), "r"(a[2]), "r"(a[3]), "r"(db_lo), "r"(scale_d));
}
template <int ND>
__device__ __forceinline__ void wgmma_ss_n32(float (&d)[ND], uint32_t da_lo, uint32_t db_lo, int scale_d) {
    asm volatile(
        "{\n.reg .pred p;\n.reg .b64 da, db;\nsetp.ne.b32 p, %18, 0;\nmov.b64 da, {%16, 0x40000040};\nmov.b64 db, {%17, 0x40000040};\n"
        "wgmma.mma_async.sync.aligned.m64n32k16.f32.bf16.bf16 {%0,%1,%2,%3,%4,%5,%6,%7,%8,%9,%10,%11,%12,%13,%14,%15}, da, db, p, 1, 1, 1, 0;\n}\n"
        : ACC16(d) : "r"(da_lo), "r"(db_lo), "r"(scale_d));
}
__device__ __forceinline__ void wgmma_ss_n8(float (&d)[4], uint32_t da_lo, uint32_t db_lo, int scale_d) {
    asm volatile(
        "{\n.reg .pred p;\n.reg .b64 da, db;\nsetp.ne.b32 p, %6, 0;\nmov.b64 da, {%4, 0x40000040};\nmov.b64 db, {%5, 0x00000010};\n"
        "wgmma.mma_async.sync.aligned.m64n8k16.f32.bf16.bf16 {%0,%1,%2,%3}, da, db, p, 1, 1, 1, 0;\n}\n"
        : "+f"(d[0]), "+f"(d[1]), "+f"(d[2]), "+f"(d[3]) : "r"(da_lo), "r"(db_lo), "r"(scale_d));
}

#define SCHED_FENCE()
__device__ __forceinline__ void wgmma_ss_n32_p(float (&d)[16], uint32_t da_lo, uint32_t db_lo, int scale_d) {
    asm volatile(
        "{\n.reg .pred p;\n.reg .b64 da, db;\nsetp.ne.b32 p, %18, 0;\nmov.b64 da, {%16, 0x40000040};\nmov.b64 db, {%17, 0x00000030};\n"
        "wgmma.mma_async.sync.aligned.m64n32k16.f32.bf16.bf16 {%0,%1,%2,%3,%4,%5,%6,%7,%8,%9,%10,%11,%12,%13,%14,%15}, da, db, p, 1, 1, 1, 0;\n}\n"
        : ACC16(d) : "r"(da_lo), "r"(db_lo), "r"(scale_d));
}

#define ACC20(d) ACC16(d), "+f"(d[16]), "+f"(d[17]), "+f"(d[18]), "+f"(d[19])
#define ACC20_STR "{%0,%1,%2,%3,%4,%5,%6,%7,%8,%9,%10,%11,%12,%13,%14,%15,%16,%17,%18,%19}"
__device__ __forceinline__ void wgmma_rs_n40(float (&d)[20], const uint32_t (&a)[4], uint32_t db_lo, int scale_d) {
    asm volatile(
        "{\n.reg .pred p;\n.reg .b64 db;\nsetp.ne.b32 p, %25, 0;\nmov.b64 db, {%24, 0x40000040};\n"
        "wgmma.mma_async.sync.aligned.m64n40k16.f32.bf16.bf16 " ACC20_STR ", {%20,%21,%22,%23}, db, p, 1, 1, 0;\n}\n"
        : ACC20(d) : "r"(a[0]), "r"(a[1]), "r"(a[2]), "r"(a[3]), "r"(db_lo), "r"(scale_d));
}
template <int TA, int SBO>
__device__ __forceinline__ void wgmma_ss_n40(float (&d)[20], uint32_t da_lo, uint32_t db_lo, int scale_d) {
    asm volatile(
        "{\n.reg .pred p;\n.reg .b64 da, db;\nsetp.ne.b32 p, %22, 0;\nmov.b64 da, {%20, %23};\nmov.b64 db, {%21, 0x40000040};\n"
        "wgmma.mma_async.sync.aligned.m64n40k16.f32.bf16.bf16 " ACC20_STR ", da, db, p, 1, 1, %24, 0;\n}\n"
        : ACC20(d) : "r"(da_lo), "r"(db_lo), "r"(scale_d), "n"(0x40000000 + SBO / 16), "n"(TA));
}

#define PT(i, th)
struct ChainParams {
    CUtensorMap mapW[3];
    CUtensorMap mapX;
    CUtensorMap mapC;
};
constexpr int CH_BLOCK = 384;
constexpr int CO_WO = 0;
constexpr int CH_XC = 5120, CH_XP = 8 * CH_XC;
constexpr int CO_XB = 65536;
constexpr int CO_OB = CO_XB + 2 * CH_XP;
constexpr int CO_P = CO_OB + 8192;
constexpr int CO_LS = CO_P + 3072;
constexpr int CO_SC = CO_LS + 8 * 1280;
constexpr int CH_TW = 6144 + 8192;
constexpr int CO_T = 21 * 8192;
constexpr int CO_WA = CO_T + 6144;
constexpr int CO_ST = CO_T + 3 * CH_TW + 6144;
constexpr int CO_OWN = CO_ST + 4096, CO_OWN2 = CO_SC + 1536;
constexpr int CO_BAR = CO_OWN + 4096;
constexpr int CH_SMEM = CO_BAR + 256 + DBG_EXTRA;
#define CH_NSM 4
static_assert(CO_OWN2 + 1024 <= CO_T && CH_NSM <= 4, "smem layout");
#define CH_POLL_DELAY 200
#define CH_VPOS 2
#define CH_OW 12
#define CH_OF 12
#define CH_Q0 0
#define CH_QI 12
#define CH_QX 0
#define CH_Q1 (CH_Q0 + CH_QI + CH_QX)
#define CH_VA 5
#define CH_SPOS 0
#define CH_LSW 1
#define CH_QE 32
#define CH_KE 32
#define CH_QD 0
#define CH_GAP 0
#define CH_QS (CH_Q1 + 6)
#define CH_KS 10
#define CH_VS 0
#define CH_A7 7
#define CH_RF 0
#define CH_LSS 2
#define CH_OS 1
#define CH_MS 1
#define CH_HA 15
#define CH_LD 4
#define CH_TWP 0
#define CH_CHAINS 4

constexpr float CH_SC = 0.08838834764831845f * 1.4426950408889634f;
__device__ __forceinline__ uint32_t pin(uint32_t v) { return __shfl_sync(0xffffffff, v, threadIdx.x & 31); }

__global__ void __cluster_dims__(8, 1, 1) __launch_bounds__(CH_BLOCK, 1)
chain_kernel(const __grid_constant__ ChainParams P, const bf16* __restrict__ mem0, const bf16* __restrict__ Wo, const bf16* __restrict__ x,
             const bf16* __restrict__ gate_w) {
    extern __shared__ uint8_t smem_raw[];
    const int tid = threadIdx.x, warp = __shfl_sync(0xffffffff, tid >> 5, 0), lane = tid & 31;
    const int rank = (int)cluster_ctarank();
    constexpr uint32_t sd = 1024;
    const uint32_t sb = ((uint32_t)rank << 24) + sd;
    if (smem_u32(smem_raw) != sb) __trap();
    const int C = blockIdx.x >> 3;
    const int h = C * 4 + (rank >> 1);
    const int qd = lane >> 2, qc = lane & 3;
    const int t4 = warp & 3, wg = warp >> 2;
    pdl_launch_dependents();
    TS_BEGIN(2);
    PT(0, 0);
    const uint32_t bar_mem = sb + CO_BAR, bar_o = bar_mem + 32, bar_sc = bar_o + 32, bar_x = bar_sc + 8, bar_l = bar_x + 16, bar_w = bar_l + 8;
    if (tid == 0) {
        for (int j = 0; j < 15; j++) mbar_init(bar_mem + 8 * j, 1);
        sts128(bar_mem + 128, 0xffff0000u, 0u, 0u, 0u);
        asm volatile("fence.mbarrier_init.release.cluster;" ::: "memory");
    }
    __syncthreads();
    auto chunk = [&](int i) { return (uint32_t)((rank - (i >> 1) - 4 * (i & 1)) & 7); };
    if ((tid & 127) == 0) {
        mbar_expect_tx(bar_w + 8 * wg, 65536);
        for (int i = 0; i < 8; i++)
            tma_load_2d(sb + (i ? (wg * 7 + i - 1) * 8192 : CO_WA + wg * CH_TW), &P.mapW[wg], bar_w + 8 * wg, h * HD + (rank & 1) * 64, chunk(i) * 64);
    }
    PT(1, 0);
    {
        for (int i = tid; i < 512; i += CH_BLOCK) asm volatile("prefetch.global.L2 [%0];" :: "l"(Wo + (size_t)(C * 512 + i) * DM + rank * 64));
        if (tid < 64) asm volatile("prefetch.global.L2 [%0];" :: "l"(x + (size_t)tid * DM + rank * 64));
    }
    if (tid < 256) {
        const int r = blockIdx.x * 32 + (tid >> 3);
        float sum = 0.f;
#pragma unroll
        for (int c = 0; c < 8; c++) {
            const int col = c * 64 + (tid & 7) * 8;
            const uint4 xv = __ldg(reinterpret_cast<const uint4*>(x + (size_t)r * DM + col));
            const uint4 gv = __ldg(reinterpret_cast<const uint4*>(gate_w + col));
            const bf16* xp = reinterpret_cast<const bf16*>(&xv);
            const bf16* gp = reinterpret_cast<const bf16*>(&gv);
#pragma unroll
            for (int e = 0; e < 8; e++) sum += bf16r(__bfloat162float(xp[e]) * __bfloat162float(gp[e]));
        }
        sum += __shfl_xor_sync(0xffffffff, sum, 1);
        sum += __shfl_xor_sync(0xffffffff, sum, 2);
        sum += __shfl_xor_sync(0xffffffff, sum, 4);
        if ((tid & 7) == 0) g_gate[r] = bf16r(1.f / (1.f + __expf(-bf16r(sum))));
        *reinterpret_cast<uint2*>(g_xbuf + (tid >> 7) * 16384 + (size_t)rank * 2048 + C * 256 + (tid & 127) * 2) = make_uint2(~0u, ~0u);
        asm volatile("bar.sync 1, 256;" ::: "memory");
        if (tid == 32) signal_ctr_generic(CT_GATE);
    }
    const uint32_t wfrag = (((lane >> 4) << 3) + (lane & 7)) * 128 + (((t4 * 2 + ((lane >> 3) & 1)) ^ (lane & 7)) << 4);
    const uint32_t aO = pin(sb + wg * CH_TW + wfrag);
    const uint32_t aL = pin(sb + lane * 16);
    uint32_t w[32][4];
    PT(2, 0);
    mbar_wait(bar_w + 8 * wg, 0);
    PT(3, 0); PT(4, 256);
#pragma unroll
    for (int e = CH_NSM; e < 32; e++)
        ldmatrix_x4_trans(w[e][0], w[e][1], w[e][2], w[e][3], e < 4 ? aO + CO_WA + e * 2048 : sb + wg * 7 * 8192 + wfrag + (e - 4) * 2048);
    fence_async_smem();
    __syncthreads();
    PT(5, 0);
    if (tid == 0) {
        fence_async_smem();
        for (int b = 0; b < 2; b++) {
            mbar_expect_tx(bar_x + 8 * b, 32768);
            for (int i = 0; i < 8; i++) tma_load_2d(sb + CO_XB + b * CH_XP + i * CH_XC, &P.mapX, bar_x + 8 * b, i * 64, b * SEGL);
        }
    }
#pragma unroll 2
    for (int i = tid; i < 512 * 4; i += CH_BLOCK) {
        const int r = i >> 2, cg = i & 3, ks = r >> 4, kp = r & 15;
        const int src = (rank - (ks >> 2)) & 7;
        const uint4* p = reinterpret_cast<const uint4*>(Wo + (size_t)(C * 512 + src * 64 + (ks & 3) * 16 + (kp >> 2) * 2 + (kp & 1) + (kp & 2) * 4) * DM + rank * 64 + cg * 16);
        const uint4 u0 = __ldg(p), u1 = __ldg(p + 1);
        const uint32_t a = sb + CO_WO + r * 128;
        sts128(a + (((cg * 2) ^ (r & 7)) << 4), __byte_perm(u0.x, u0.y, 0x5410), __byte_perm(u0.z, u0.w, 0x5410), __byte_perm(u1.x, u1.y, 0x5410), __byte_perm(u1.z, u1.w, 0x5410));
        sts128(a + (((cg * 2 + 1) ^ (r & 7)) << 4), __byte_perm(u0.x, u0.y, 0x7632), __byte_perm(u0.z, u0.w, 0x7632), __byte_perm(u1.x, u1.y, 0x7632), __byte_perm(u1.z, u1.w, 0x7632));
    }
#pragma unroll 1
    for (int i = tid; i < 512; i += CH_BLOCK) {
        const int n = i >> 6, c = i & 63;
        const uint4 u = __ldg(reinterpret_cast<const uint4*>(mem0 + n * DM + c * 8));
        sts128(sb + CO_XB + (c >> 3) * CH_XC + 4096 + n * 128 + (((c & 7) ^ n) << 4), u.x, u.y, u.z, u.w);
    }
    if (tid < 128) sts128(sb + CO_T + (2 + (tid >> 6)) * CH_TW + 5120 + (tid & 63) * 16, 0u, 0u, 0u, 0u);
    else if (tid < 160) sts128(sb + CO_P + ((tid >> 3) & 3) * 768 + 640 + (tid & 7) * 16, 0u, 0u, 0u, 0u);
    fence_async_smem();
    TS_END(6);
    PT(6, 0);
    auto pass = [&](auto& d, int g, int b, int j0, int j1, int js, bool group = true) {
        const uint32_t lo = desc_lo(sd + CO_XB + b * CH_XP, 16);
        if (group) wgmma_fence();
#pragma unroll
        for (int j = 0; j < 32; j++) if (j >= j0 && j < j1) {
            const int e = j < js ? j + CH_NSM : j < js + CH_NSM ? j - js : j;
            const uint32_t db = lo + chunk(e >> 2) * (CH_XC / 16) + (e & 3) * 2, da = desc_lo(sd + CO_WA + g * CH_TW + e * 2048, 16);
            if constexpr (sizeof(d) == 64) { if (e < CH_NSM) wgmma_ss_n32(d, da, db, j != 0); else wgmma_rs_n32(d, w[e], db, j != 0); }
            else { if (e < CH_NSM) wgmma_ss_n40<1, 1024>(d, da, db, j != 0); else wgmma_rs_n40(d, w[e], db, j != 0); }
        }
        if (group) wgmma_commit();
    };
    auto uni = [](uint32_t v) { return __shfl_sync(0xffffffff, v, 0); };
    auto roff = [&](int j) { return (uint32_t)(((rank + j) & 7) - rank) << 24; };
    auto store32 = [&](const float* d, uint32_t a) {
        stmatrix_x4_trans(a, pack_bf16(d[0], d[1]), pack_bf16(d[2], d[3]), pack_bf16(d[4], d[5]), pack_bf16(d[6], d[7]));
        stmatrix_x4_trans(a + 2048, pack_bf16(d[8], d[9]), pack_bf16(d[10], d[11]), pack_bf16(d[12], d[13]), pack_bf16(d[14], d[15]));
    };
    auto scores = [&](float (&d)[20], auto sbo, uint32_t q) {
        wgmma_fence();
#pragma unroll
        for (int ks = 0; ks < 4; ks++) wgmma_ss_n40<0, decltype(sbo)::value>(d, desc_lo(sd + CO_T + q, 16) + ks * 2, desc_lo(sd + CO_T + CH_TW, 16) + ks * 2, ks != 0);
        wgmma_commit();
    };
    auto own_scores = [&](const float (&d)[20], float (&v)[10]) {
#pragma unroll
        for (int j = 0; j < 5; j++) { v[2 * j] = d[4 * j]; v[2 * j + 1] = d[4 * j + 1]; }
    };
    auto add_scores = [&](uint32_t a, uint32_t b, float (&v)[10]) {
        const uint4 a0 = lds128(a), a1 = lds128(a + 512);
        const float2 a2 = lds64f(b);
        v[0] += __uint_as_float(a0.x); v[1] += __uint_as_float(a0.y); v[2] += __uint_as_float(a0.z); v[3] += __uint_as_float(a0.w);
        v[4] += __uint_as_float(a1.x); v[5] += __uint_as_float(a1.y); v[6] += __uint_as_float(a1.z); v[7] += __uint_as_float(a1.w);
        v[8] += a2.x; v[9] += a2.y;
    };
    auto row_max = [&](const float (&v)[10]) {
        float mx = fmaxf(fmaxf(fmaxf(v[0], v[1]), fmaxf(v[2], v[3])), fmaxf(fmaxf(v[4], v[5]), fmaxf(v[6], v[7])));
        mx = fmaxf(mx, fmaxf(v[8], v[9]));
        mx = fmaxf(mx, __shfl_xor_sync(0xffffffff, mx, 1));
        return fmaxf(mx, __shfl_xor_sync(0xffffffff, mx, 2)) * CH_SC;
    };
    auto signal_ctx = [&](int m0, int m1) {
        for (int m = m0; m < m1; m++) asm volatile("red.relaxed.gpu.global.add.u32 [%0], 1;" :: "l"(&g_ctr[CT_CB + m]) : "memory");
    };
    auto signal_step = [](int s) { return s == 33 || s == 49 || s == 57 || s == 61; };
    if (mapa_u32(bar_l, rank ^ 1) != (bar_l ^ (1u << 24)) || mapa_u32(bar_l, (rank + 3) & 7) != bar_l + roff(3)) __trap();
    mbar_wait(bar_x, 0);
    PT(7, 0);
    if (wg < 2) {
        float d[16];
        pass(d, wg, 0, 0, 32, 0);
        wgmma_wait<0>();
        store32(d, aO + CO_T);
    }
    if (tid == 128) mbar_expect_tx(bar_sc, 1280);
    __syncthreads();
    PT(8, 0);
    cluster_sync_all();
    TS_BEGIN(5);
    PT(9, 0);

    if (wg < 2) {
        const uint32_t aM = pin(sb + CO_XB + 4096 + (lane & 7) * 128 + (((lane >> 3) ^ (lane & 7)) << 4));
        uint32_t coff[8];
#pragma unroll
        for (int i = 0; i < 8; i++) coff[i] = uni(chunk(i) * CH_XC);
        auto mem_proj = [&](int s, int it) {
            const uint32_t par = s & 1;
            float acc[CH_CHAINS][4];
#pragma unroll
            for (int i = 0; i < CH_CHAINS; i++) acc[i][0] = acc[i][1] = acc[i][2] = acc[i][3] = 0.f;
            const uint32_t am = aM + par * CH_XP;
            uint32_t b[CH_LD][4], ok[4] = {1, 1, 1, 1}, a0 = am, a1 = am ^ 64;
            auto load = [&](int i) {
                if (i == 12) DBG(13, 0);
                if (i == 2 || (i && !(i & 3))) { a0 = ok[i >> 2] ? am : aL; a1 = a0 ^ 64; }
                uint32_t* r = b[i % CH_LD];
                ldmatrix_x4(r[0], r[1], r[2], r[3], ((i & 1) ? a1 : a0) + coff[i >> 1]);
                if (i == 1) ok[0] = mbar_try(bar_mem, par ^ 1);
                if (i == 2 || i == 4 || i == 8) ok[(i >> 2) + 1] = mbar_try(bar_mem + 8 * ((i >> 2) + 1), par ^ 1);
            };
            auto mma = [&](int i) {
                mma_16816(acc[(2 * i) % CH_CHAINS], w[2 * i][0], w[2 * i][1], w[2 * i][2], w[2 * i][3], b[i % CH_LD][0], b[i % CH_LD][1]);
                mma_16816(acc[(2 * i + 1) % CH_CHAINS], w[2 * i + 1][0], w[2 * i + 1][1], w[2 * i + 1][2], w[2 * i + 1][3], b[i % CH_LD][2], b[i % CH_LD][3]);
            };
#pragma unroll
            for (int e = 0; e < CH_NSM; e++) ldmatrix_x4_trans(w[e][0], w[e][1], w[e][2], w[e][3], aO + CO_WA + e * 2048);
            asm volatile("{\n.reg .pred p;\nsetp.eq.s32 p, %0, 0;\n@p bar.sync 10, 384;\n}" :: "r"(it) : "memory");
            DBG(11, 0);
            bool done = false;
            load(0); load(1); mma(0); mma(1);
            load(2); load(3); mma(2);
#pragma unroll
            for (int i = 4; i < 3 + CH_LD; i++) load(i);
#pragma unroll
            for (int i = 3; i < 16; i++) {
                mma(i);
                if (i + CH_LD < 16) load(i + CH_LD);
                if (i == 12 - CH_LD) done = __all_sync(0xffffffff, ok[0] & ok[1] & ok[2] & ok[3]);
                if (i == CH_HA) asm volatile("{\n.reg .pred p;\nsetp.ne.b32 p, %0, 0;\n@p bar.arrive 5, 384;\n}" :: "r"((int)done) : "memory");
            }
#pragma unroll
            for (int i = 0; i < 4; i++)
#pragma unroll
                for (int c = 1; c < CH_CHAINS; c++) acc[0][i] += acc[c][i];
            const uint32_t r0 = pack_bf16(acc[0][0], acc[0][1]);
            const uint32_t r1 = pack_bf16(acc[0][2], acc[0][3]);
            DBGD(40 + warp, warp, r0 ^ r1);
            stmatrix_x2_trans(aO + CO_T + 4096, r0, r1);
            fence_async_smem();
            return done;
        };
        if (wg == 0) {
#pragma unroll 1
            for (int s = 0; s < NSEG; s++) {
                const uint32_t par = s & 1;
#pragma unroll 1
                for (int it = 0; it < WAIT_LIMIT / 64; it++) if (mem_proj(s, it)) break;
                asm volatile("bar.arrive 1, 256;" ::: "memory");
                if (s == NSEG - 1) break;
                if (tid == 96) {
#pragma unroll
                    for (int j = 0; j < 4; j++) { mbar_expect_tx(bar_mem + 8 * j, j ? 2048 : 1024); if (j < 3) mbar_expect_tx(bar_o + 8 * j, 1024 << j); }
                }
                __syncwarp();
                uint32_t* wp = g_xbuf + (size_t)rank * 2048 + C * 256 + qc * 64 + t4 * 8 + qd;
                asm volatile("st.relaxed.gpu.global.u32 [%0], %1;" :: "l"(wp + ((s + 2) & 3) * 16384), "r"(~0u) : "memory");
                asm volatile("st.relaxed.gpu.global.u32 [%0], %1;" :: "l"(wp + ((s + 2) & 3) * 16384 + 32), "r"(~0u) : "memory");
                mbar_wait(bar_x + 8 * (par ^ 1), ((s + 1) >> 1) & 1);
                asm volatile("bar.sync 7, 384;" ::: "memory");
                float d[16];
                float c[4];
                const uint32_t alo = desc_lo(sd + CO_WO, 16), blo = desc_lo(sd + CO_OB, 128);
                wgmma_fence();
                pass(d, 0, par ^ 1, 0, CH_Q0, CH_QS, false);
                asm volatile("bar.sync 11, 256;" ::: "memory");
#pragma unroll
                for (int i = 0; i < 32; i++) {
                    if (i == 4) { pass(d, 0, par ^ 1, CH_Q0 + min(4, CH_QI), CH_Q0 + min(4, CH_QI) + CH_QX, CH_QS, false); mbar_wait_cl(bar_o, par); }
                    if (i == 8) mbar_wait_cl(bar_o + 8, par);
                    if (i == CH_OW) mbar_wait_cl(bar_o + 16, par);
                    wgmma_ss_n8(c, alo + i * 128, blo + i * 16, i != 0);
                    if (i < CH_QI) pass(d, 0, par ^ 1, CH_Q0 + i + (i < 4 ? 0 : CH_QX), CH_Q0 + i + (i < 4 ? 0 : CH_QX) + 1, CH_QS, false);
                }
                wgmma_commit();
                wgmma_wait<0>();
                asm volatile("st.relaxed.gpu.global.u32 [%0], %1;" :: "l"(wp + (s & 3) * 16384), "r"(pack_bf16(c[0], c[2])) : "memory");
                asm volatile("st.relaxed.gpu.global.u32 [%0], %1;" :: "l"(wp + (s & 3) * 16384 + 32), "r"(pack_bf16(c[1], c[3])) : "memory");
                asm volatile("bar.arrive 6, 384;" ::: "memory");
                pace(CH_QD);
                asm volatile("bar.arrive 4, 384;" ::: "memory");
                DBG(8, 0);
                pass(d, 0, par ^ 1, CH_Q1, CH_QE, CH_QS);
                DBG(21, 0);
                if (tid == 0 && s + 2 < NSEG) {
                    mbar_expect_tx(bar_x + 8 * par, 32768);
                    tma_load_2d_mc(sb + CO_XB + par * CH_XP + rank * CH_XC, &P.mapX, bar_x + 8 * par, rank * 64, (s + 2) * SEGL, (uint16_t)0xff);
                }
                __syncwarp();
                asm volatile("bar.sync 9, 256;" ::: "memory");
                wgmma_wait<0>();
                DBG(0, 0);
                store32(d, aO + CO_T);
                DBG(22, 0);
            }
        } else {
            const uint32_t usc = uni(CO_SC + min(t4, 2) * 512 + roff((rank ^ 1) - rank)), uscb = uni(bar_sc ^ (1u << 24));
            const uint32_t vaddr = pin(sb + CO_T + 2 * CH_TW + (lane & 15) * 128 + (((t4 * 2 + (lane >> 4)) ^ (lane & 7)) << 4));
            const uint32_t dsta = pin(sb + CO_OB + t4 * 256 + (qc >> 1) * 128 + qd * 16 + (qc & 1) * 8);
            auto local_pv = [&](int s, int st) {
                float dc[16];
                wgmma_fence();
#pragma unroll
                for (int ks = 0; ks < 3; ks++) wgmma_ss_n32_p(dc, desc_lo(sd + CO_T + (2 + (s & 1)) * CH_TW + ks * 2048, 16), desc_lo(sd + CO_P + ks * 256, 128), ks != 0);
                wgmma_commit();
                wgmma_wait<0>();
                store32(dc, aO - CH_TW + st);
            };
            auto store_ctx = [&](int s, int st) {
                if (tid == 128 && s >= 0) {
                    tma_store_2d(&P.mapC, sb + st, (rank & 1) * 64, h * SEQ + s * SEGL);
                    asm volatile("cp.async.bulk.commit_group;" ::: "memory");
                }
                __syncwarp();
            };
            uint32_t uo[8], ub[8];
#pragma unroll
            for (int i = 0; i < 8; i++) { uo[i] = uni(roff(i) + i * 1024); ub[i] = uni(roff(i) + bar_o + (i < 2 ? 0 : i < 4 ? 8 : 16)); }
#pragma unroll 1
            for (int s = 0; s < NSEG; s++) {
                const uint32_t par = s & 1;
#pragma unroll 1
                for (int it = 0; it < WAIT_LIMIT / 64; it++) if (mem_proj(s, it)) break;
                asm volatile("bar.sync 1, 256;" ::: "memory");
                float d[20];
                scores(d, std::integral_constant<int, 0>(), 4096);
                if (s == NSEG - 1) { wgmma_wait<0>(); break; }
                asm volatile("bar.arrive 8, 256;" ::: "memory");
                wgmma_wait<0>();
                {
                    const bool w0 = t4 == 0;
                    asm volatile("{\n.reg .pred p, q;\nsetp.lt.s32 p, %8, 2;\nsetp.eq.s32 q, %8, 2;\n"
                                 "@p st.async.weak.shared::cluster.mbarrier::complete_tx::bytes.v4.f32 [%0], {%2, %3, %4, %5}, [%1];\n"
                                 "@q st.async.weak.shared::cluster.mbarrier::complete_tx::bytes.v2.f32 [%0], {%6, %7}, [%1];\n}"
                                 :: "r"((aL | (s >> 10)) + usc), "r"(uscb), "f"(w0 ? d[0] : d[8]), "f"(w0 ? d[1] : d[9]),
                                    "f"(w0 ? d[4] : d[12]), "f"(w0 ? d[5] : d[13]), "f"(d[16]), "f"(d[17]), "r"(t4) : "memory");
                }
                DBG(3, 4);
                store_ctx(s - 2, CO_ST);
                uint32_t vb[3][4];
                auto load_v = [&]() {
                    asm volatile("bar.sync 3, 256;" ::: "memory");
#pragma unroll
                    for (int k = 0; k < 3; k++) ldmatrix_x4_trans(vb[k][0], vb[k][1], vb[k][2], vb[k][3], vaddr + par * CH_TW + k * 2048);
                };
                mbar_wait_cl(bar_sc, par);
                DBG(4, 4);
                float v[10];
                own_scores(d, v);
                add_scores(aL + CO_SC, aL + CO_SC + 1024, v);
                const float mx = row_max(v);
                if (CH_VPOS == 2) load_v();
#pragma unroll
                for (int j = 0; j < 10; j++) v[j] = ex2f(fmaf(v[j], CH_SC, -mx));
                uint32_t p[5];
#pragma unroll
                for (int j = 0; j < 5; j++) p[j] = pack_bf16(v[2 * j], v[2 * j + 1]);
                if (CH_VPOS == 3) load_v();
                DBG(19, 4);
                float c0[4] = {0.f, 0.f, 0.f, 0.f}, c1[4] = {0.f, 0.f, 0.f, 0.f}, cs[4] = {0.f, 0.f, 0.f, 0.f};
#pragma unroll
                for (int k = 0; k < 3; k++) {
                    const uint32_t p0 = p[2 * k], p1 = k < 2 ? p[2 * k + 1] : 0u;
                    mma_16816(cs, p0, 0u, p1, 0u, 0x3f803f80u, 0x3f803f80u);
                    mma_16816(c0, p0, 0u, p1, 0u, vb[k][0], vb[k][1]);
                    mma_16816(c1, p0, 0u, p1, 0u, vb[k][2], vb[k][3]);
                }
                float inv;
                asm volatile("rcp.approx.ftz.f32 %0, %1;" : "=f"(inv) : "f"(cs[0]));
                const uint32_t b0 = pack_bf16(c0[0] * inv, c0[1] * inv), b1 = pack_bf16(c1[0] * inv, c1[1] * inv);
                DBG(20, 4);
#pragma unroll
                for (int i = 1; i < 8; i++) {
                    st_async_v2((dsta | (s >> 10)) + uo[i], b0, b1, ub[i]);
                    if (i == CH_OS) asm volatile("st.shared.v2.b32 [%0], {%1, %2};" :: "r"(dsta), "r"(b0), "r"(b1) : "memory");
                }
                DBG(5, 4);
                asm volatile("cp.async.bulk.wait_group.read 0;" ::: "memory");
                asm volatile("bar.sync 7, 384;" ::: "memory");
                fence_async_smem();
                asm volatile("bar.arrive 11, 256;" ::: "memory");
                local_pv(s + 1, CO_ST);
                asm volatile("bar.arrive 6, 384;" ::: "memory");
                if (tid == 128) mbar_expect_tx(bar_sc, 1280);
                __syncwarp();
                mbar_wait(bar_x + 8 * (par ^ 1), ((s + 1) >> 1) & 1);
                asm volatile("bar.sync 4, 384;" ::: "memory");
                float dk[16];
                pass(dk, 1, par ^ 1, 0, CH_KE, CH_KS);
                if (tid == 128 && signal_step(s)) {
                    asm volatile("cp.async.bulk.wait_group 0;" ::: "memory");
                    signal_ctx((2 * s - 66) >> 2, s >> 2);
                }
                __syncwarp();
                DBG(1, 4);
                wgmma_wait<0>();
                DBG(2, 4);
                store32(dk, aO + CO_T);
                DBG(29, 4);
            }
            asm volatile("bar.sync 8, 256;" ::: "memory");
            store_ctx(NSEG - 3, CO_ST);
#pragma unroll 1
            for (int i = 0; i < 2; i++) {
                local_pv(i, CO_OB + i * 4096);
                fence_async_smem();
                if (i == 0) asm volatile("bar.arrive 9, 256;" ::: "memory");
                asm volatile("bar.sync 2, 128;" ::: "memory");
                store_ctx(NSEG - 2 + i, CO_OB + i * 4096);
                if (i == 0) asm volatile("bar.sync 3, 256;" ::: "memory");
            }
            if (tid == 128) {
                asm volatile("cp.async.bulk.wait_group 0;" ::: "memory");
                PT(14, 128);
                signal_ctx(15, 16);
                PT(15, 128);
            }
        }
        PT(10, 0);
    } else {
        float gs;
        auto load_gate = [&](int s) { asm volatile("ld.global.cg.f32 %0, [%1];" : "=f"(gs) : "l"(g_gate + s * SEGL + t4 * 8 + qd) : "memory"); };
        auto softmax = [&](int s) {
            float v[10];
            {
                const uint4 a0 = lds128(aL + CO_OWN + t4 * 1024), a1 = lds128(aL + CO_OWN + t4 * 1024 + 512);
                const float2 a2 = lds64f(aL + CO_OWN2 + t4 * 256 - lane * 8);
                v[0] = __uint_as_float(a0.x); v[1] = __uint_as_float(a0.y); v[2] = __uint_as_float(a0.z); v[3] = __uint_as_float(a0.w);
                v[4] = __uint_as_float(a1.x); v[5] = __uint_as_float(a1.y); v[6] = __uint_as_float(a1.z); v[7] = __uint_as_float(a1.w);
                v[8] = a2.x; v[9] = a2.y;
            }
            mbar_wait_cl(bar_l, s & 1);
            add_scores(aL + t4 * 1024 + CO_LS + (s & 1) * 5120, aL + t4 * 256 - lane * 8 + CO_LS + (s & 1) * 5120 + 4096, v);
            const int lim = t4 * 8 + qd - 2 * qc;
#pragma unroll
            for (int j = 0; j < 8; j++) if ((j >> 1) * 8 + (j & 1) > lim) v[j] = -INFINITY;
            const float mx = row_max(v);
#pragma unroll
            for (int j = 0; j < 10; j++) v[j] = ex2f(fmaf(v[j], CH_SC, -mx));
            float sum = (((v[0] + v[1]) + (v[2] + v[3])) + ((v[4] + v[5]) + (v[6] + v[7]))) + (v[8] + v[9]);
            sum += __shfl_xor_sync(0xffffffff, sum, 1);
            sum += __shfl_xor_sync(0xffffffff, sum, 2);
            asm("rcp.approx.ftz.f32 %0, %0;" : "+f"(sum));
            sum *= 1.f - gs;
            const uint32_t pa = aL + CO_P + t4 * 768;
            stmatrix_x4(pa, pack_bf16(v[0] * sum, v[1] * sum), pack_bf16(v[2] * sum, v[3] * sum), pack_bf16(v[4] * sum, v[5] * sum), pack_bf16(v[6] * sum, v[7] * sum));
            asm volatile("stmatrix.sync.aligned.m8n8.x1.shared.b16 [%0], {%1};" :: "r"(pa + 512), "r"(pack_bf16(v[8] * sum, v[9] * sum)) : "memory");
        };
        uint32_t um[8], ub[8];
#pragma unroll
        for (int i = 0; i < 8; i++) { um[i] = uni(roff((i & 1) * 4 + (i >> 1))); ub[i] = uni(roff((i & 1) * 4 + (i >> 1)) + bar_mem + 8 * (i >> 1)); }
        const uint8_t* mkp = smem_raw + CO_BAR + 128;
        asm volatile("" : "+l"(mkp));
        asm volatile("bar.arrive 10, 384;" ::: "memory");
        wait_ctr(CT_GATE, 64u);
        load_gate(0);
#pragma unroll 1
        for (int s = 0; s < NSEG; s++) {
            const uint32_t par = s & 1;
            const bool last = s == NSEG - 1;
            softmax(s - 1);
            load_gate(s);
            DBG(7, 8);
#pragma unroll 1
            for (int it = 0; it < (CH_RF ? WAIT_LIMIT / 64 : 0); it++)
                if (mbar_try(bar_mem, par ^ 1) & mbar_try(bar_mem + 8, par ^ 1) & mbar_try(bar_mem + 16, par ^ 1) & mbar_try(bar_mem + 24, par ^ 1)) break;
            fence_async_smem();
            asm volatile("bar.sync 5, 384;" ::: "memory");
            DBG(23, 8);
            float d[20];
            pass(d, 2, par, 0, CH_VA, CH_VS);
            asm volatile("bar.sync 8, 256;" ::: "memory");
            pass(d, 2, par, CH_VA, 32, CH_VS);
            wgmma_wait<0>();
            stmatrix_x2_trans(aO + par * CH_TW + CO_T + 4096, pack_bf16(d[16], d[17]), pack_bf16(d[18], d[19]));
            store32(d, aO + par * CH_TW + CO_T);
            DBG(24, 8);
            if (!last) asm volatile("bar.arrive 3, 256;\nbar.sync 7, 384;" ::: "memory");
            scores(d, std::integral_constant<int, 512>(), 0);
            asm volatile("{\n.reg .pred p;\nsetp.eq.s32 p, %1, 256;\n@p mbarrier.arrive.expect_tx.shared::cta.b64 _, [%0], 5120;\n}" :: "r"(bar_l), "r"(tid) : "memory");
            wgmma_wait<0>();
            auto send_scores = [&]() {
                const uint32_t a = aL + t4 * 1024, a2 = aL + t4 * 256 - lane * 8, r = roff((rank ^ 1) - rank) + CO_LS + par * 5120;
                asm volatile("st.async.weak.shared::cluster.mbarrier::complete_tx::bytes.v4.f32 [%0], {%3, %4, %5, %6}, [%2];\n"
                             "st.async.weak.shared::cluster.mbarrier::complete_tx::bytes.v4.f32 [%0 + 512], {%7, %8, %9, %10}, [%2];\n"
                             "st.async.weak.shared::cluster.mbarrier::complete_tx::bytes.v2.f32 [%1], {%11, %12}, [%2];"
                             :: "r"(a + r), "r"(a2 + r + 4096), "r"(bar_l ^ (1u << 24)), "f"(d[0]), "f"(d[1]), "f"(d[4]), "f"(d[5]),
                                "f"(d[8]), "f"(d[9]), "f"(d[12]), "f"(d[13]), "f"(d[16]), "f"(d[17]) : "memory");
                sts128(a + CO_OWN, __float_as_uint(d[0]), __float_as_uint(d[1]), __float_as_uint(d[4]), __float_as_uint(d[5]));
                sts128(a + CO_OWN + 512, __float_as_uint(d[8]), __float_as_uint(d[9]), __float_as_uint(d[12]), __float_as_uint(d[13]));
                asm volatile("st.shared.v2.f32 [%0], {%1, %2};" :: "r"(a2 + CO_OWN2), "f"(d[16]), "f"(d[17]) : "memory");
            };
            if (CH_LSS == 0) send_scores();
            if (last) { if (CH_LSS) send_scores(); break; }
            asm volatile("bar.arrive 4, 384;\nbar.arrive 9, 256;\nbar.sync 6, 384;" ::: "memory");
            if (CH_LSS == 1) send_scores();
            const uint2* xb = reinterpret_cast<const uint2*>(g_xbuf + (s & 3) * 16384 + (size_t)rank * 2048 + t4 * 64) + lane;
            uint2 p[8], q[8];
            pace(CH_POLL_DELAY);
#pragma unroll
            for (int k = 0; k < 8; k++)
                asm volatile("ld.relaxed.gpu.global.v2.u32 {%0, %1}, [%2];" : "=r"(p[k].x), "=r"(p[k].y) : "l"(xb + k * 128) : "memory");
            DBG(17, 8);
            if (CH_LSS == 2) send_scores();
            {
                uint32_t z;
                asm volatile("mov.u32 %0, %%clock;" : "=r"(z) :: "memory");
#pragma unroll
                for (int i = 0; i < CH_GAP; i++) asm volatile("mul.lo.u32 %0, %0, %0;" : "+r"(z));
                asm volatile("and.b32 %0, %0, %1;" : "+r"(z) : "r"(s >> 10));
                xb += z;
            }
#pragma unroll
            for (int k = 0; k < 8; k++)
                asm volatile("ld.relaxed.gpu.global.v2.u32 {%0, %1}, [%2];" : "=r"(q[k].x), "=r"(q[k].y) : "l"(xb + k * 128) : "memory");
            uint32_t m0, m1, mk;
            asm volatile("ld.relaxed.gpu.u32 %0, [%1];" : "=r"(mk) : "l"(mkp) : "memory");
            auto sum = [&](const uint2 (&p)[8]) {
                auto lo = [&](uint32_t u) { return __uint_as_float(u * (0u - mk)); };
                auto hi = [&](uint32_t u) { return __uint_as_float(u & mk); };
                const float s0 = ((lo(p[0].x) + lo(p[1].x)) + (lo(p[2].x) + lo(p[3].x))) + ((lo(p[4].x) + lo(p[5].x)) + (lo(p[6].x) + lo(p[7].x)));
                const float s1 = ((lo(p[0].y) + lo(p[1].y)) + (lo(p[2].y) + lo(p[3].y))) + ((lo(p[4].y) + lo(p[5].y)) + (lo(p[6].y) + lo(p[7].y)));
                m0 = pack_bf16(s0, ((hi(p[0].x) + hi(p[1].x)) + (hi(p[2].x) + hi(p[3].x))) + ((hi(p[4].x) + hi(p[5].x)) + (hi(p[6].x) + hi(p[7].x))));
                m1 = pack_bf16(s1, ((hi(p[0].y) + hi(p[1].y)) + (hi(p[2].y) + hi(p[3].y))) + ((hi(p[4].y) + hi(p[5].y)) + (hi(p[6].y) + hi(p[7].y))));
                uint32_t ok;
                asm volatile("{\n.reg .pred p;\nsetp.num.f32 p, %1, %2;\nvote.sync.all.pred p, p, 0xffffffff;\nselp.u32 %0, 1, 0, p;\n}" : "=r"(ok) : "f"(s0), "f"(s1));
                return ok;
            };
            if (!sum(p)) {
                DBG(12, 8);
#pragma unroll 1
                for (int it = 0; it < WAIT_LIMIT / 4; it++) {
                    if (sum(q)) break;
                    uint32_t bad = 0;
#pragma unroll
                    for (int k = 0; k < 8; k++) bad |= (max(q[k].x, q[k].y) == ~0u ? 1u : 0u) << k;
                    if (__all_sync(0xffffffff, bad == 0u)) break;
                    if (it == 0) DBG(14, 8);
                    if (it == 1) DBG(15, 8);
#pragma unroll
                    for (int k = 0; k < 8; k++)
                        if (bad & (1u << k))
                            asm volatile("ld.relaxed.gpu.global.v2.u32 {%0, %1}, [%2];" : "=r"(q[k].x), "=r"(q[k].y) : "l"(xb + k * 128) : "memory");
                }
            }
            DBG(9, 8);
            const int row = t4 * 2 + (lane >> 4);
            const uint32_t dsta = sb + CO_XB + (par ^ 1) * CH_XP + rank * CH_XC + 4096 + row * 128 + ((((lane & 15) >> 1) ^ row) << 4) + (lane & 1) * 8;
#pragma unroll
            for (int i = 1; i < 8; i++) {
                st_async_v2(dsta + um[i], m0, m1, ub[i]);
                if (i == CH_MS) asm volatile("st.shared.v2.b32 [%0], {%1, %2};\nbar.arrive 10, 384;" :: "r"(dsta), "r"(m0), "r"(m1) : "memory");
            }
            if (s == 1000000) {
#pragma unroll
                for (int k = 0; k < 8; k++) asm volatile("st.volatile.shared.v2.u32 [%0], {%1, %2};" :: "r"(s), "r"(q[k].x), "r"(q[k].y) : "memory");
            }
            DBG(10, 8);
        }
        PT(11, 256);
        asm volatile("bar.sync 9, 256;" ::: "memory");
        softmax(NSEG - 1);
        fence_async_smem();
        asm volatile("bar.arrive 3, 256;" ::: "memory");
    }
    __syncthreads();
    cluster_sync_all();
    TS_END(2);
}

struct Proj2Params {
    CUtensorMap mapA[2];
    CUtensorMap mapW[3];
    bf16* out[3];
};
#define P2T(i)
#define P2_NOMMA 0
#define P2_NOLOAD 0
constexpr int P2_STAGES = 6;
constexpr int P2_SMEM = 131072 + P2_STAGES * 16384 + 1024 + 1024;
constexpr int P2_ITEMS = 168 + 48;

__device__ __forceinline__ int p2_reps(int t) { return t >= 168 ? 1 : 2; }
__device__ __forceinline__ void p2_tile(int t, int w, int& z, int& mp, int& head) {
    if (t >= 168) { w += ((t - 168) & 1) * 2; t = 168 + ((t - 168) >> 1); }
    const int hq = t / 24, v = t % 24;
    mp = v & 7;
    if (v < 16) { head = hq * 4 + (v >> 3) * 2 + (w >> 1); z = 1 + (w & 1); }
    else { head = hq * 4 + w; z = 0; }
}
__device__ __forceinline__ void mbar_arrive_remote(uint32_t bar_cluster_addr) {
    asm volatile("mbarrier.arrive.release.cluster.shared::cluster.b64 _, [%0];" :: "r"(bar_cluster_addr) : "memory");
}
__device__ __forceinline__ void mbar_arrive_cl(uint32_t bar_cluster_addr) {
    asm volatile("mbarrier.arrive.shared::cluster.b64 _, [%0];" :: "r"(bar_cluster_addr) : "memory");
}
__device__ __forceinline__ void mbar_wait_acq_cluster(uint32_t bar, uint32_t parity) {
    asm volatile(
        "{\n"
        ".reg .pred p, q;\n"
        ".reg .u32 c;\n"
        "mov.u32 c, 0;\n"
        "WAIT_LOOP_C:\n"
        "mbarrier.try_wait.parity.acquire.cluster.shared::cta.b64 p, [%0], %1;\n"
        "@p bra WAIT_DONE_C;\n"
        "add.u32 c, c, 1;\n"
        "setp.lt.u32 q, c, 4000000;\n"
        "@q bra WAIT_LOOP_C;\n"
        "WAIT_DONE_C:\n"
        "}\n" :: "r"(bar), "r"(parity) : "memory");
}
__device__ __forceinline__ uint4 quad_transpose(uint32_t p0, uint32_t p1, uint32_t p2, uint32_t p3, int lane) {
    const bool o1 = lane & 1, o2 = lane & 2;
    uint32_t s0 = o1 ? p0 : p1, s1 = o1 ? p2 : p3;
    s0 = __shfl_xor_sync(0xffffffff, s0, 1); s1 = __shfl_xor_sync(0xffffffff, s1, 1);
    const uint32_t a_lo = o1 ? s0 : p0, a_hi = o1 ? p1 : s0, b_lo = o1 ? s1 : p2, b_hi = o1 ? p3 : s1;
    uint32_t t0 = o2 ? a_lo : b_lo, t1 = o2 ? a_hi : b_hi;
    t0 = __shfl_xor_sync(0xffffffff, t0, 2); t1 = __shfl_xor_sync(0xffffffff, t1, 2);
    return o2 ? make_uint4(t0, t1, b_lo, b_hi) : make_uint4(a_lo, a_hi, t0, t1);
}
#define P2_PACE 35
#define P2_PACE2 0
template <bool PERM, int PACE = 0>
__device__ __forceinline__ void store_frag_128(const float (&acc)[64], bf16* obase, int lane) {
#pragma unroll
    for (int rr = 0; rr < 2; rr++)
#pragma unroll
        for (int g = 0; g < 4; g++) {
            const float* a = &acc[g * 16 + rr * 2];
            const uint32_t p0 = pack_bf16(a[0], a[1]), p1 = pack_bf16(a[4], a[5]), p2 = pack_bf16(a[8], a[9]), p3 = pack_bf16(a[12], a[13]);
            *reinterpret_cast<uint4*>(obase + (size_t)(rr * 8) * HD + g * 32) = PERM ? make_uint4(p0, p1, p2, p3) : quad_transpose(p0, p1, p2, p3, lane);
            pace(PACE);
        }
}
__global__ void __cluster_dims__(2, 1, 1) __launch_bounds__(384, 1) proj2_kernel(const __grid_constant__ Proj2Params P) {
    extern __shared__ uint8_t smem_raw[];
    const uint32_t sbase = (smem_u32(smem_raw) + 1023) & ~1023u;
    const uint32_t sA = sbase, sB = sbase + 131072, sC = sB + P2_STAGES * 16384;
    const uint32_t bars = sC;
    const uint32_t a_full = bars, a_empty = bars + 64, b_full = bars + 128, b_empty = b_full + 8 * P2_STAGES;
    const uint32_t item_bar = b_empty + 8 * P2_STAGES, item_in = item_bar + 16, slot = item_in + 16;
    const uint32_t note_bar = slot + 16, note_free = note_bar + 64, note = note_free + 64;
    const int warp = threadIdx.x >> 5, lane = threadIdx.x & 31;
    const uint32_t rank = cluster_ctarank();
    TS_BEGIN(0);
    if (threadIdx.x == 0) {
        for (int i = 0; i < 8; i++) { mbar_init(a_full + 8 * i, 1); mbar_init(a_empty + 8 * i, 2); }
        for (int i = 0; i < P2_STAGES; i++) { mbar_init(b_full + 8 * i, 1); mbar_init(b_empty + 8 * i, 2); }
        mbar_init(item_bar, 1); mbar_init(item_bar + 8, 1); mbar_init(item_in, 2); mbar_init(item_in + 8, 2);
        for (int i = 0; i < 8; i++) { mbar_init(note_bar + 8 * i, 1); mbar_init(note_free + 8 * i, 1); }
        asm volatile("fence.mbarrier_init.release.cluster;" ::: "memory");
    }
    __syncthreads();
    cluster_sync_all();
    pdl_launch_dependents();
    if (warp == 9) {
        if (lane == 0) {
            for (int n = 0;; n++) {
                const int e = (n & 1) * 4 + ((n >> 1) & 3);
                mbar_wait(note_bar + 8 * e, (n >> 3) & 1);
                int m;
                asm volatile("ld.shared.s32 %0, [%1];" : "=r"(m) : "r"(note + e * 4) : "memory");
                mbar_arrive(note_free + 8 * e);
                if (m < 0) break;
                signal_ctr(m);
            }
        }
    } else if (warp == 10) {
        if (lane == 0) {
            auto publish = [&](int ic, int tq) {
                const int t = tq < P2_ITEMS ? tq : -1;
                asm volatile("st.shared.s32 [%0], %1;" :: "r"(slot + (ic & 3) * 4), "r"(t) : "memory");
                mbar_arrive(item_bar + 8 * (ic & 1));
                st_async_b32(mapa_u32(slot + (ic & 3) * 4, 1), (uint32_t)t, mapa_u32(item_bar + 8 * (ic & 1), 1));
            };
            const int npair = (int)(gridDim.x >> 1), pair = (int)(blockIdx.x >> 1);
            if (rank == 0) publish(0, pair);
            for (int ic = 0;; ic++) {
                if (rank == 1) mbar_expect_tx(item_bar + 8 * (ic & 1), 4);
                mbar_wait(item_bar + 8 * (ic & 1), (ic >> 1) & 1);
                int t;
                asm volatile("ld.shared.s32 %0, [%1];" : "=r"(t) : "r"(slot + (ic & 3) * 4) : "memory");
                if (t < 0) break;
                int z0, mp, h0;
                p2_tile(t, 0, z0, mp, h0);
                const int aidx = z0 >= 1 ? 1 : 0;
                const int m0 = (2 * mp + (int)rank) * 128;
                for (int k = 0; k < 8; k++) {
                    mbar_wait(a_empty + 8 * k, (ic & 1) ^ 1);
                    if (P2_NOLOAD) mbar_arrive(a_full + 8 * k); else {
                    mbar_expect_tx(a_full + 8 * k, 16384);
                    tma_load_2d(sA + k * 16384, &P.mapA[aidx], a_full + 8 * k, k * 64, m0); }
                }
                if (rank == 0) {
                    mbar_wait(item_in + 8 * (ic & 1), (ic >> 1) & 1);
                    publish(ic + 1, ic == 0 ? npair + pair : 2 * npair + (int)atomicAdd(&g_ctr[CT_PROJ], 1u));
                }
            }
        }
    } else if (warp == 8 || warp == 11) {
        if (lane == 0) {
            const int par2 = warp == 8 ? 0 : 1;
            int it = 0; uint32_t bph = 0;
            for (int ic = 0;; ic++) {
                mbar_wait(item_bar + 8 * (ic & 1), (ic >> 1) & 1);
                int t;
                asm volatile("ld.shared.s32 %0, [%1];" : "=r"(t) : "r"(slot + (ic & 3) * 4) : "memory");
                if (t < 0) break;
                const int nt = 2 * p2_reps(t);
                for (int w = 0; w < nt; w++) {
                    int z, mp, hd;
                    p2_tile(t, w, z, mp, hd);
                    for (int k = 0; k < 8; k++) {
                        const int s = it; const uint32_t phb = bph;
                        if (++it == P2_STAGES) { it = 0; bph ^= 1; }
                        if ((k & 1) != par2) continue;
                        mbar_wait(b_empty + 8 * s, phb ^ 1);
                        if (P2_NOLOAD) { mbar_arrive(b_full + 8 * s); continue; }
                        mbar_expect_tx(b_full + 8 * s, 16384);
                        tma_load_2d_mc(sB + s * 16384 + rank * 8192, &P.mapW[z], b_full + 8 * s, hd * 128 + (int)rank * 64, k * 64, (uint16_t)3);
                    }
                }
            }
        }
    } else {
        const int wg = warp >> 2;
        float acc[2][64];
        const uint32_t a_lo = desc_lo(sA, 16), b_lo0 = desc_lo(sB, 8192);
        const bool elected = (threadIdx.x & 127) == 0;
        int s = (wg * 8) % P2_STAGES;
        uint32_t ph = ((wg * 8) / P2_STAGES) & 1;
        int nnote = 0;
        if (wg == 1) asm volatile("bar.arrive 3, 256;" ::: "memory");
        for (int ic = 0;; ic++) {
            mbar_wait(item_bar + 8 * (ic & 1), (ic >> 1) & 1);
            int t;
            asm volatile("ld.shared.s32 %0, [%1];" : "=r"(t) : "r"(slot + (ic & 3) * 4) : "memory");
            P2T(7);
            if (wg == 0 && t < 0) {
                if (elected) {
                    const int e = nnote & 3;
                    mbar_wait(note_free + 8 * e, ((nnote >> 2) & 1) ^ 1);
                    asm volatile("st.shared.s32 [%0], %1;" :: "r"(note + e * 4), "r"(-1) : "memory");
                    mbar_arrive(note_bar + 8 * e);
                }
            }
            if (t < 0) break;
            const int reps = p2_reps(t);
#pragma unroll 1
            for (int rp = 0; rp < reps; rp++) {
            const bool first = rp == 0, last = rp == reps - 1;
            int z, mp, head;
            p2_tile(t, rp * 2 + wg, z, mp, head);
            asm volatile("bar.sync %0, 256;" :: "r"(3 + wg) : "memory");
            P2T(0);
            if (wg == 1 && last && elected) mbar_arrive_cl(mapa_u32(item_in + 8 * (ic & 1), 0));
            int sprev = 0;
#pragma unroll
            for (int k = 0; k < 8; k++) {
                if (k == 0) P2T(5);
                if (wg == 0 && first) mbar_wait(a_full + 8 * k, ic & 1);
                if (k == 0) P2T(6);
                mbar_wait(b_full + 8 * s, ph);
                if (k == 7) asm volatile("bar.arrive %0, 256;" :: "r"(4 - wg) : "memory");
                if (k == 0) P2T(1);
                if (k == 7) P2T(2);
                const uint32_t b_lo = b_lo0 + s * 1024;
                wgmma_fence();
#pragma unroll
                for (int kk = 0; kk < (P2_NOMMA ? 1 : 4); kk++) {
                    wgmma_ss_n128_lo<1>(acc[0], a_lo + k * 1024 + kk * 2, b_lo + kk * 128, (k | kk) != 0);
                    wgmma_ss_n128_lo<1>(acc[1], a_lo + k * 1024 + 512 + kk * 2, b_lo + kk * 128, (k | kk) != 0);
                }
                wgmma_commit();
                if (k > 0) {
                    wgmma_wait<1>();
                    if (elected) {
                        const uint32_t e = b_empty + 8 * sprev;
                        mbar_arrive_cl(mapa_u32(e, 0)); mbar_arrive_cl(mapa_u32(e, 1));
                        if (last) mbar_arrive(a_empty + 8 * (k - 1));
                    }
                }
                sprev = s;
                if (++s == P2_STAGES) { s = 0; ph ^= 1; }
            }
            wgmma_wait<0>();
            P2T(3);
            if (elected) {
                const uint32_t e = b_empty + 8 * sprev;
                mbar_arrive_cl(mapa_u32(e, 0)); mbar_arrive_cl(mapa_u32(e, 1));
                if (last) mbar_arrive(a_empty + 8 * 7);
            }
            s += 8 % P2_STAGES; ph ^= (8 / P2_STAGES) & 1;
            if (s >= P2_STAGES) { s -= P2_STAGES; ph ^= 1; }
            const int m0 = (2 * mp + (int)rank) * 128;
            bf16* obase = P.out[z] + ((size_t)head * SEQ + m0 + (warp & 3) * 16 + (lane >> 2)) * HD + (lane & 3) * 8;
            store_frag_128<true, P2_PACE>(acc[0], obase, lane); store_frag_128<true, P2_PACE>(acc[1], obase + (size_t)64 * HD, lane);
            P2T(4);
            {
                asm volatile("bar.sync %0, 128;" :: "r"(1 + wg) : "memory");
                if (elected) {
                    const int e = wg * 4 + (nnote & 3);
                    mbar_wait(note_free + 8 * e, ((nnote >> 2) & 1) ^ 1);
                    asm volatile("st.shared.s32 [%0], %1;" :: "r"(note + e * 4), "r"(CT_AP + (head >> 1)) : "memory");
                    mbar_arrive(note_bar + 8 * e);
                }
                nnote++;
            }
            }
        }
        TS_END(0);
    }
    __syncthreads();
    cluster_sync_all();
}

struct OutParams {
    CUtensorMap mapCtx[2];
    CUtensorMap mapWo[2];
    CUtensorMap mapOut;
};

#define OT(i)
#define OTP(i, th)
constexpr int O2_STAGES = 4;
constexpr int O2_SMEM = O2_STAGES * 49152 + 1024 + 256;
constexpr int O2_GRID = 132;
#define O2_NL 16
#define O2_FINE 8

__global__ void __cluster_dims__(2, 1, 1) __launch_bounds__(352, 1)
out2_kernel(const __grid_constant__ OutParams P) {
    extern __shared__ uint8_t smem_raw[];
    const uint32_t sbase = (smem_u32(smem_raw) + 1023) & ~1023u;
    const uint32_t bar_full = sbase + O2_STAGES * 49152, bar_empty = bar_full + 8 * O2_STAGES, bar_item = bar_empty + 8 * O2_STAGES;
    const uint32_t slot = bar_item + 64, stop = slot + 32;
    const int warp = threadIdx.x >> 5, lane = threadIdx.x & 31;
    const uint32_t rank = cluster_ctarank();
    const int cid = blockIdx.x >> 1;
    int pt, h0;
    if (cid < 32) { pt = cid < 16 ? cid : 31 - cid; h0 = cid >= 16; }
    else if (cid < 34) { pt = 12 + (cid & 1); h0 = 2; }
    else { pt = 14 + (cid & 1); h0 = 63 - ((cid - 34) >> 1); }
    const int ne = (pt >> 1) == 6 ? 3 : 2, nh = pt >= 14 ? 64 - O2_NL : 64;
    if (cid >= 34 + 2 * O2_NL) {
        if (threadIdx.x == 0 && atomicAdd(&g_ctr[CT_FIN], 1u) == gridDim.x - 1)
            for (int i = 0; i < CT_N / 4; i++) reinterpret_cast<uint4*>(g_ctr)[i] = make_uint4(0u, 0u, 0u, 0u);
        return;
    }
    const int mt = (pt >> 1) * 2 + (int)rank, m0 = mt * 128, n0 = (pt & 1) * 256;
    TS_BEGIN(4);
    OT(0);
    int tnext = 0;
    if (threadIdx.x == 256) {
        if (rank == 0) tnext = take_ticket(CT_OT + pt);
        for (int i = 0; i < O2_STAGES; i++) { mbar_init(bar_full + 8 * i, 1); mbar_init(bar_empty + 8 * i, 4); mbar_init(bar_item + 16 * i, 1); mbar_init(bar_item + 16 * i + 8, 1); }
        sts128(stop, 0u, 0u, 0u, 0u);
        asm volatile("fence.mbarrier_init.release.cluster;" ::: "memory");
    }
    __syncwarp();
    asm volatile("barrier.cluster.arrive.relaxed.aligned;" ::: "memory");
    if (threadIdx.x == 256) {
        asm volatile("prefetch.tensormap [%0];" :: "l"(&P.mapCtx[h0 >> 5]) : "memory");
        wait_ctr(h0 < 32 ? CT_CA + mt * 4 : CT_CB + mt, h0 < 32 ? 16u : 64u);
        OTP(8, 256);
        for (int i = 0; i < 2; i++) {
            mbar_expect_tx(bar_full + 8 * i, 49152);
            tma_load_2d(sbase + i * 49152, &P.mapCtx[h0 >> 5], bar_full + 8 * i, i * 64, (h0 & 31) * SEQ + m0);
        }
        OTP(11, 256);
    }
    if (threadIdx.x == 288) asm volatile("prefetch.tensormap [%0];" :: "l"(&P.mapWo[h0 >> 5]) : "memory");
    __syncwarp();
    asm volatile("barrier.cluster.wait.aligned;" ::: "memory");
    OTP(10, 288);
    if (warp >= 8) {
        if (lane == 0) {
            int s = 0, ready = h0 < 32 ? 1 : 16, q = h0 * 2, qe = q + 2; uint32_t ph = 0;
            for (int ic = 0;; ic++) {
                if (warp == 8 && rank == 0) {
                    const int t = tnext + ne;
                    asm volatile("st.shared.s32 [%0], %1;" :: "r"(slot + (ic & 7) * 4), "r"(t) : "memory");
                    mbar_arrive(bar_item + 8 * (ic & 7));
                    st_async_b32(mapa_u32(slot + (ic & 7) * 4, 1), (uint32_t)t, mapa_u32(bar_item + 8 * (ic & 7), 1));
                    if (t < nh + O2_FINE) tnext = take_ticket(CT_OT + pt);
                }
#pragma unroll 1
                for (; q < qe; q++) {
                    const int b = q >> 6, head = (q >> 1) & 31, dk = (q & 1) * 64;
                    mbar_wait(bar_empty + 8 * s, ph ^ 1);
                    const uint32_t sa = sbase + s * 49152;
                    if (warp == 8) {
                        const int f = b ? 4 : head >> 3;
                        if (!((ready >> f) & 1)) {
                            if (b && !(ready & 8)) { wait_ctr(CT_CA + mt * 4 + 3, 16u); ready |= 8; }
                            wait_ctr(b ? CT_CB + mt : CT_CA + mt * 4 + f, b ? 64u : 16u); ready |= 1 << f;
                        }
                        if (ic > 0) {
                            mbar_expect_tx(bar_full + 8 * s, 49152);
                            tma_load_2d(sa, &P.mapCtx[b], bar_full + 8 * s, dk, head * SEQ + m0);
                        }
                    } else {
                        const int j = (int)rank * 2 + (warp - 9);
                        tma_load_2d_mc(sa + 16384 + j * 8192, &P.mapWo[b], bar_full + 8 * s, n0 + j * 64, head * HD + dk, (uint16_t)3);
                    }
                    if (ic == 0 && s == 0) OTP(12, 288);
                    if (++s == O2_STAGES) { s = 0; ph ^= 1; }
                }
                if (warp == 8 && rank == 1) mbar_expect_tx(bar_item + 8 * (ic & 7), 4);
                mbar_wait(bar_item + 8 * (ic & 7), (ic >> 3) & 1);
                int t;
                asm volatile("ld.shared.s32 %0, [%1];" : "=r"(t) : "r"(slot + (ic & 7) * 4) : "memory");
                if (t >= nh + O2_FINE) break;
                if (t < nh - O2_FINE) { q = 2 * t; qe = q + 2; } else { q = nh - O2_FINE + t; qe = q + 1; }
            }
            if (warp == 8) {
                asm volatile("prefetch.tensormap [%0];" :: "l"(&P.mapOut) : "memory");
                if (!(ready & 8)) wait_ctr(CT_CA + mt * 4 + 3, 16u);
                mbar_wait(bar_empty + 8 * s, ph ^ 1);
                asm volatile("st.shared.s32 [%0], %1;" :: "r"(stop + s * 4), "r"(1) : "memory");
                mbar_arrive(bar_full + 8 * s);
                if (atomicAdd(&g_ctr[CT_FIN], 1u) == gridDim.x - 1)
                    for (int i = 0; i < CT_N / 4; i++) reinterpret_cast<uint4*>(g_ctr)[i] = make_uint4(0u, 0u, 0u, 0u);
                for (int i = 1; i < O2_STAGES; i++) {
                    if (++s == O2_STAGES) { s = 0; ph ^= 1; }
                    mbar_wait(bar_empty + 8 * s, ph ^ 1);
                }
            }
        }
    } else {
        const int wg = warp >> 2;
        const bool elected = (threadIdx.x & 127) == 0;
        float acc[128];
#pragma unroll
        for (int i = 0; i < 128; i++) acc[i] = 0.f;
        int s = 0, sprev = 0; uint32_t ph = 0;
#pragma unroll 1
        for (int i = 0;; i++) {
            mbar_wait(bar_full + 8 * s, ph);
            int st;
            asm volatile("ld.shared.s32 %0, [%1];" : "=r"(st) : "r"(stop + s * 4) : "memory");
            if (st) break;
            if (i == 0) OT(1);
            const uint32_t sa = sbase + s * 49152 + wg * 8192, sb = sbase + s * 49152 + 16384;
            wgmma_fence();
#pragma unroll
            for (int kk = 0; kk < 4; kk++)
                wgmma_ss_n256_tb(acc, make_desc(sa + kk * 32, 16, 1024), make_desc(sb + kk * 2048, 8192, 1024), 1);
            wgmma_commit();
            if (i > 0) {
                wgmma_wait<1>();
                if (elected) { const uint32_t e = bar_empty + 8 * sprev; mbar_arrive_cl(mapa_u32(e, 0)); mbar_arrive_cl(mapa_u32(e, 1)); }
            }
            sprev = s;
            if (++s == O2_STAGES) { s = 0; ph ^= 1; }
        }
        wgmma_wait<0>();
        if (elected) { const uint32_t e = bar_empty + 8 * sprev; mbar_arrive_cl(mapa_u32(e, 0)); mbar_arrive_cl(mapa_u32(e, 1)); }
        asm volatile("bar.sync %0, 128;" :: "r"(1 + wg) : "memory");
        OT(3);
        const int row = (lane & 7) + ((lane >> 3) & 1) * 8;
#pragma unroll
        for (int bx = 0; bx < 4; bx++) {
            const uint32_t stg = sbase + bx * 49152 + warp * 2048;
#pragma unroll
            for (int j = 0; j < 8; j += 2) {
                const float* a = &acc[bx * 32 + j * 4];
                stmatrix_x4(stg + row * 128 + (((j + (lane >> 4)) ^ (row & 7)) << 4), pack_bf16(a[0], a[1]), pack_bf16(a[2], a[3]), pack_bf16(a[4], a[5]), pack_bf16(a[6], a[7]));
            }
            asm volatile("fence.proxy.async.shared::cta;" ::: "memory");
            __syncwarp();
            if (lane == 0)
                asm volatile("cp.reduce.async.bulk.tensor.2d.global.shared::cta.add.tile.bulk_group [%0, {%2, %3}], [%1];"
                             :: "l"((uint64_t)&P.mapOut), "r"(stg), "r"(n0 + bx * 64), "r"(m0 + warp * 16) : "memory");
        }
        OT(4);
        if (lane == 0) {
            asm volatile("cp.async.bulk.commit_group;" ::: "memory");
            asm volatile("cp.async.bulk.wait_group.read 0;" ::: "memory");
        }
        TS_END(4);
    }
}

typedef CUresult (*PFN_encodeTiled)(CUtensorMap*, CUtensorMapDataType, cuuint32_t, void*, const cuuint64_t*,
                                    const cuuint64_t*, const cuuint32_t*, const cuuint32_t*, CUtensorMapInterleave,
                                    CUtensorMapSwizzle, CUtensorMapL2promotion, CUtensorMapFloatOOBfill);
static PFN_encodeTiled g_encode = nullptr;

static void make_map(CUtensorMap* m, const void* ptr, uint64_t rows, uint64_t cols, uint32_t box_rows, bool sw64 = false) {
    cuuint64_t dims[2] = {cols, rows};
    cuuint64_t strides[1] = {cols * 2};
    cuuint32_t box[2] = {sw64 ? 32u : 64u, box_rows};
    cuuint32_t es[2] = {1, 1};
    g_encode(m, CU_TENSOR_MAP_DATA_TYPE_BFLOAT16, 2, const_cast<void*>(ptr), dims, strides, box, es,
             CU_TENSOR_MAP_INTERLEAVE_NONE, sw64 ? CU_TENSOR_MAP_SWIZZLE_64B : CU_TENSOR_MAP_SWIZZLE_128B, CU_TENSOR_MAP_L2_PROMOTION_L2_256B,
             CU_TENSOR_MAP_FLOAT_OOB_FILL_NONE);
}

template <typename... KArgs, typename... Args>
static void launch_pdl(void (*kernel)(KArgs...), int grid, int block, size_t smem, cudaStream_t st, bool pdl, Args... args) {
    cudaLaunchConfig_t cfg = {};
    cfg.gridDim = dim3(grid); cfg.blockDim = dim3(block); cfg.dynamicSmemBytes = smem; cfg.stream = st;
    cudaLaunchAttribute at[1];
    at[0].id = cudaLaunchAttributeProgrammaticStreamSerialization;
    at[0].val.programmaticStreamSerializationAllowed = 1;
    cfg.attrs = at; cfg.numAttrs = pdl ? 1 : 0;
    cudaLaunchKernelEx(&cfg, kernel, KArgs(args)...);
}

extern "C" void kernel_launch(void* const* d_in, const int* in_sizes, int n_in, void* d_out, int out_size) {
    const bf16* x = (const bf16*)d_in[0];
    const bf16* ckv = (const bf16*)d_in[1];
    const bf16* wq = (const bf16*)d_in[2];
    const bf16* wuk = (const bf16*)d_in[3];
    const bf16* wuv = (const bf16*)d_in[4];
    const bf16* wo = (const bf16*)d_in[5];
    const bf16* mem0 = (const bf16*)d_in[7];
    const bf16* Wq = (const bf16*)d_in[8];
    const bf16* Wk = (const bf16*)d_in[9];
    const bf16* Wv = (const bf16*)d_in[10];
    const bf16* Wo = (const bf16*)d_in[11];
    const bf16* gate_w = (const bf16*)d_in[13];
    bf16* out = (bf16*)d_out;

    static Proj2Params P2;
    static ChainParams CP;
    static AttnParams AP;
    static OutParams OP;
    static bool init = false;
    static const void* last_in[14];
    static const void* last_out;
    bool same = init && last_out == d_out;
    for (int i = 0; i < 14 && same; i++) same = last_in[i] == d_in[i];
    if (!init) {
        cudaDriverEntryPointQueryResult qr;
        cudaGetDriverEntryPoint("cuTensorMapEncodeTiled", (void**)&g_encode, cudaEnableDefault, &qr);
        cudaFuncSetAttribute(proj2_kernel, cudaFuncAttributeMaxDynamicSharedMemorySize, P2_SMEM);
        cudaFuncSetAttribute(attn_kernel, cudaFuncAttributeMaxDynamicSharedMemorySize, FA_SMEM);
        cudaFuncSetAttribute(chain_kernel, cudaFuncAttributeMaxDynamicSharedMemorySize, CH_SMEM);
        cudaFuncSetAttribute(out2_kernel, cudaFuncAttributeMaxDynamicSharedMemorySize, O2_SMEM);
        init = true;
    }
    if (!same) {
        for (int i = 0; i < 14; i++) last_in[i] = d_in[i];
        last_out = d_out;
        void *pQA, *pKA, *pVA, *pCA, *pCB;
        cudaGetSymbolAddress(&pQA, g_QA); cudaGetSymbolAddress(&pKA, g_KA); cudaGetSymbolAddress(&pVA, g_VA);
        cudaGetSymbolAddress(&pCA, g_ctxA); cudaGetSymbolAddress(&pCB, g_ctxB);
        make_map(&P2.mapA[0], x, SEQ, DM, 128);
        make_map(&P2.mapA[1], ckv, SEQ, DM, 128);
        const void* ws[3] = {wq, wuk, wuv};
        void* cs[3] = {pQA, pKA, pVA};
        for (int i = 0; i < 3; i++) { make_map(&P2.mapW[i], ws[i], DM, NQ, 64); P2.out[i] = (bf16*)cs[i]; }
        make_map(&CP.mapW[0], Wq, DM, NQ, 64); make_map(&CP.mapW[1], Wk, DM, NQ, 64); make_map(&CP.mapW[2], Wv, DM, NQ, 64);
        make_map(&CP.mapX, x, SEQ, DM, 32);
        make_map(&CP.mapC, pCB, NH * SEQ, HD, 32);
        make_map(&AP.mapQ, pQA, NH * SEQ, HD, 128);
        make_map(&AP.mapK, pKA, NH * SEQ, HD, 128);
        make_map(&AP.mapV, pVA, NH * SEQ, HD, 128);
        make_map(&AP.mapO, pCA, NH * SEQ, HD, 64);
        make_map(&OP.mapCtx[0], pCA, NH * SEQ, HD, 128);
        make_map(&OP.mapCtx[1], pCB, NH * SEQ, HD, 128);
        make_map(&OP.mapWo[0], wo, NQ, DM, 64);
        make_map(&OP.mapWo[1], Wo, NQ, DM, 64);
        make_map(&OP.mapOut, out, SEQ, DM, 16);
        AP.out = out;
    }
    cudaStream_t s1 = cudaStreamPerThread;
    const bool pdl = true;
    launch_pdl(chain_kernel, 64, CH_BLOCK, CH_SMEM, s1, false, CP, mem0, Wo, x, gate_w);
    launch_pdl(proj2_kernel, 68, 384, P2_SMEM, s1, pdl, P2);
    launch_pdl(attn_kernel, FA_GRID, 384, FA_SMEM, s1, pdl, AP);
    launch_pdl(out2_kernel, O2_GRID, 352, O2_SMEM, s1, pdl, OP);
}
```

```cpp
#include <cuda_runtime.h>
#include <cuda_bf16.h>
#include <cuda.h>
#include <stdint.h>
#include <type_traits>

constexpr int SEQ = 2048;
constexpr int DM = 512;
constexpr int NH = 32;
constexpr int HD = 128;
constexpr int NQ = NH * HD;
constexpr int SEGL = 32;
constexpr int NMEM = 8;
constexpr int NSEG = SEQ / SEGL;

typedef __nv_bfloat16 bf16;

__device__ bf16 g_QA[SEQ * NQ];
__device__ bf16 g_KA[SEQ * NQ];
__device__ bf16 g_VA[SEQ * NQ];
__device__ bf16 g_ctxA[SEQ * NQ];
__device__ bf16 g_ctxB[SEQ * NQ];
constexpr int CT_PROJ = 0, CT_ATTN = 1, CT_FIN = 5;
constexpr int CT_AP = 64;
constexpr int CT_GATE = 96;
constexpr int CT_CA = 128;
constexpr int CT_CB = 192;
constexpr int CT_OT = 208;
constexpr int CT_N = 224;
__device__ __align__(16) unsigned int g_ctr[CT_N];
__device__ float g_gate[SEQ];
__device__ uint32_t g_xbuf[4 * 8 * 2048];

#define FA_GRID 68

#define TS_BEGIN(id)
#define TS_END(id)
#define TS_BEGIN2(id, th)
#define TS_END2(id, th)
#define WAIT_LIMIT 200000
__device__ __forceinline__ void pdl_launch_dependents() { asm volatile("griddepcontrol.launch_dependents;" ::: "memory"); }
__device__ __forceinline__ void wait_ctr(int idx, unsigned int n) {
    unsigned int v; int it = 0;
    do { asm volatile("ld.acquire.gpu.global.u32 %0, [%1];" : "=r"(v) : "l"(&g_ctr[idx]) : "memory"); } while (v < n && ++it < WAIT_LIMIT);
    asm volatile("fence.proxy.async.shared::cta;" ::: "memory");
}
__device__ __forceinline__ int take_ticket(int idx) {
    int v;
    asm volatile("atom.relaxed.gpu.global.inc.u32 %0, [%1], 0x7fffffff;" : "=r"(v) : "l"(&g_ctr[idx]) : "memory");
    return v;
}
__device__ __forceinline__ void signal_ctr(int idx) {
    asm volatile("fence.proxy.async;" ::: "memory");
    __threadfence();
    atomicAdd(&g_ctr[idx], 1u);
}
__device__ __forceinline__ void signal_ctr_generic(int idx) {
    asm volatile("red.release.gpu.global.add.u32 [%0], 1;" :: "l"(&g_ctr[idx]) : "memory");
}
__device__ __forceinline__ uint32_t smem_u32(const void* p) {
    return (uint32_t)__cvta_generic_to_shared(p);
}
__device__ __forceinline__ void mbar_init(uint32_t bar, uint32_t count) {
    asm volatile("mbarrier.init.shared::cta.b64 [%0], %1;" :: "r"(bar), "r"(count));
}
__device__ __forceinline__ void mbar_expect_tx(uint32_t bar, uint32_t bytes) {
    asm volatile("mbarrier.arrive.expect_tx.shared::cta.b64 _, [%0], %1;" :: "r"(bar), "r"(bytes) : "memory");
}
__device__ __forceinline__ void mbar_arrive(uint32_t bar) {
    asm volatile("mbarrier.arrive.shared::cta.b64 _, [%0];" :: "r"(bar) : "memory");
}
__device__ __forceinline__ void mbar_wait(uint32_t bar, uint32_t parity) {
    asm volatile(
        "{\n"
        ".reg .pred p, q;\n"
        ".reg .u32 c;\n"
        "mov.u32 c, 0;\n"
        "WAIT_LOOP:\n"
        "mbarrier.try_wait.parity.shared::cta.b64 p, [%0], %1;\n"
        "@p bra WAIT_DONE;\n"
        "add.u32 c, c, 1;\n"
        "setp.lt.u32 q, c, %2;\n"
        "@q bra WAIT_LOOP;\n"
        "WAIT_DONE:\n"
        "}\n" :: "r"(bar), "r"(parity), "n"(WAIT_LIMIT) : "memory");
}
__device__ __forceinline__ uint32_t mbar_test(uint32_t bar, uint32_t parity) {
    uint32_t done;
    asm volatile(
        "{\n.reg .pred p;\n"
        "mbarrier.test_wait.parity.shared::cta.b64 p, [%1], %2;\n"
        "selp.u32 %0, 1, 0, p;\n}\n" : "=r"(done) : "r"(bar), "r"(parity) : "memory");
    return done;
}
__device__ __forceinline__ uint32_t mbar_try(uint32_t bar, uint32_t parity) {
    uint32_t done;
    asm volatile(
        "{\n.reg .pred p;\n"
        "mbarrier.try_wait.parity.shared::cta.b64 p, [%1], %2;\n"
        "selp.u32 %0, 1, 0, p;\n}\n" : "=r"(done) : "r"(bar), "r"(parity) : "memory");
    return done;
}
__device__ __forceinline__ void tma_load_2d(uint32_t dst, const CUtensorMap* map, uint32_t bar, int c0, int c1) {
    asm volatile(
        "cp.async.bulk.tensor.2d.shared::cluster.global.mbarrier::complete_tx::bytes [%0], [%1, {%3, %4}], [%2];"
        :: "r"(dst), "l"((uint64_t)map), "r"(bar), "r"(c0), "r"(c1) : "memory");
}
__device__ __forceinline__ void wgmma_fence() { asm volatile("wgmma.fence.sync.aligned;" ::: "memory"); }
__device__ __forceinline__ void wgmma_commit() { asm volatile("wgmma.commit_group.sync.aligned;" ::: "memory"); }
template <int N> __device__ __forceinline__ void wgmma_wait() {
    asm volatile("wgmma.wait_group.sync.aligned %0;" :: "n"(N) : "memory");
}
__device__ __forceinline__ uint64_t make_desc(uint32_t addr, uint32_t lbo, uint32_t sbo) {
    uint64_t d = 0;
    d |= (uint64_t)((addr & 0x3FFFF) >> 4);
    d |= (uint64_t)((lbo >> 4) & 0x3FFF) << 16;
    d |= (uint64_t)((sbo >> 4) & 0x3FFF) << 32;
    d |= (uint64_t)1 << 62;
    return d;
}

#define ACC64(d) \
    "+f"(d[0]), "+f"(d[1]), "+f"(d[2]), "+f"(d[3]), "+f"(d[4]), "+f"(d[5]), "+f"(d[6]), "+f"(d[7]), \
    "+f"(d[8]), "+f"(d[9]), "+f"(d[10]), "+f"(d[11]), "+f"(d[12]), "+f"(d[13]), "+f"(d[14]), "+f"(d[15]), \
    "+f"(d[16]), "+f"(d[17]), "+f"(d[18]), "+f"(d[19]), "+f"(d[20]), "+f"(d[21]), "+f"(d[22]), "+f"(d[23]), \
    "+f"(d[24]), "+f"(d[25]), "+f"(d[26]), "+f"(d[27]), "+f"(d[28]), "+f"(d[29]), "+f"(d[30]), "+f"(d[31]), \
    "+f"(d[32]), "+f"(d[33]), "+f"(d[34]), "+f"(d[35]), "+f"(d[36]), "+f"(d[37]), "+f"(d[38]), "+f"(d[39]), \
    "+f"(d[40]), "+f"(d[41]), "+f"(d[42]), "+f"(d[43]), "+f"(d[44]), "+f"(d[45]), "+f"(d[46]), "+f"(d[47]), \
    "+f"(d[48]), "+f"(d[49]), "+f"(d[50]), "+f"(d[51]), "+f"(d[52]), "+f"(d[53]), "+f"(d[54]), "+f"(d[55]), \
    "+f"(d[56]), "+f"(d[57]), "+f"(d[58]), "+f"(d[59]), "+f"(d[60]), "+f"(d[61]), "+f"(d[62]), "+f"(d[63])
#define ACC64_STR \
    "{%0, %1, %2, %3, %4, %5, %6, %7, %8, %9, %10, %11, %12, %13, %14, %15, " \
    "%16, %17, %18, %19, %20, %21, %22, %23, %24, %25, %26, %27, %28, %29, %30, %31, " \
    "%32, %33, %34, %35, %36, %37, %38, %39, %40, %41, %42, %43, %44, %45, %46, %47, " \
    "%48, %49, %50, %51, %52, %53, %54, %55, %56, %57, %58, %59, %60, %61, %62, %63}"

template <int TB>
__device__ __forceinline__ void wgmma_ss_n128(float (&d)[64], uint64_t da, uint64_t db, int scale_d) {
    asm volatile(
        "{\n.reg .pred p;\nsetp.ne.b32 p, %66, 0;\n"
        "wgmma.mma_async.sync.aligned.m64n128k16.f32.bf16.bf16 " ACC64_STR ", %64, %65, p, 1, 1, 0, %67;\n}\n"
        : ACC64(d) : "l"(da), "l"(db), "r"(scale_d), "n"(TB));
}
__device__ __forceinline__ uint32_t desc_lo(uint32_t addr, uint32_t lbo) { return ((addr & 0x3FFFF) >> 4) | ((lbo >> 4) << 16); }
template <int TB>
__device__ __forceinline__ void wgmma_ss_n128_lo(float (&d)[64], uint32_t da_lo, uint32_t db_lo, int scale_d) {
    asm volatile(
        "{\n.reg .pred p;\n.reg .b64 da, db;\nsetp.ne.b32 p, %66, 0;\n"
        "mov.b64 da, {%64, 0x40000040};\nmov.b64 db, {%65, 0x40000040};\n"
        "wgmma.mma_async.sync.aligned.m64n128k16.f32.bf16.bf16 " ACC64_STR ", da, db, p, 1, 1, 0, %67;\n}\n"
        : ACC64(d) : "r"(da_lo), "r"(db_lo), "r"(scale_d), "n"(TB));
}
__device__ __forceinline__ void wgmma_rs_n128_tb(float (&d)[64], uint32_t a0, uint32_t a1, uint32_t a2, uint32_t a3,
                                                 uint64_t db, int scale_d) {
    asm volatile(
        "{\n.reg .pred p;\nsetp.ne.b32 p, %69, 0;\n"
        "wgmma.mma_async.sync.aligned.m64n128k16.f32.bf16.bf16 " ACC64_STR ", {%64, %65, %66, %67}, %68, p, 1, 1, 1;\n}\n"
        : ACC64(d) : "r"(a0), "r"(a1), "r"(a2), "r"(a3), "l"(db), "r"(scale_d));
}
__device__ __forceinline__ void wgmma_rs_n80(float (&d)[40], const uint32_t (&a)[4], uint32_t db_lo, int scale_d) {
    asm volatile(
        "{\n.reg .pred p;\n.reg .b64 db;\nsetp.ne.b32 p, %45, 0;\nmov.b64 db, {%44, 0x40000040};\n"
        "wgmma.mma_async.sync.aligned.m64n80k16.f32.bf16.bf16 "
        "{%0, %1, %2, %3, %4, %5, %6, %7, %8, %9, %10, %11, %12, %13, %14, %15, %16, %17, %18, %19, %20, %21, %22, %23, %24, %25, %26, %27, %28, %29, %30, %31, %32, %33, %34, %35, %36, %37, %38, %39}, "
        "{%40, %41, %42, %43}, db, p, 1, 1, 0;\n}\n"
        : "+f"(d[0]), "+f"(d[1]), "+f"(d[2]), "+f"(d[3]), "+f"(d[4]), "+f"(d[5]), "+f"(d[6]), "+f"(d[7]), "+f"(d[8]), "+f"(d[9]), "+f"(d[10]), "+f"(d[11]), "+f"(d[12]), "+f"(d[13]), "+f"(d[14]), "+f"(d[15]), "+f"(d[16]), "+f"(d[17]), "+f"(d[18]), "+f"(d[19]), "+f"(d[20]), "+f"(d[21]), "+f"(d[22]), "+f"(d[23]), "+f"(d[24]), "+f"(d[25]), "+f"(d[26]), "+f"(d[27]), "+f"(d[28]), "+f"(d[29]), "+f"(d[30]), "+f"(d[31]), "+f"(d[32]), "+f"(d[33]), "+f"(d[34]), "+f"(d[35]), "+f"(d[36]), "+f"(d[37]), "+f"(d[38]), "+f"(d[39])
        : "r"(a[0]), "r"(a[1]), "r"(a[2]), "r"(a[3]), "r"(db_lo), "r"(scale_d));
}
__device__ __forceinline__ void wgmma_ss_n256_tb(float (&d)[128], uint64_t da, uint64_t db, int scale_d) {
    asm volatile(
        "{\n.reg .pred p;\nsetp.ne.b32 p, %130, 0;\n"
        "wgmma.mma_async.sync.aligned.m64n256k16.f32.bf16.bf16 {%0, %1, %2, %3, %4, %5, %6, %7, %8, %9, %10, %11, %12, %13, %14, %15, %16, %17, %18, %19, %20, %21, %22, %23, %24, %25, %26, %27, %28, %29, %30, %31, %32, %33, %34, %35, %36, %37, %38, %39, %40, %41, %42, %43, %44, %45, %46, %47, %48, %49, %50, %51, %52, %53, %54, %55, %56, %57, %58, %59, %60, %61, %62, %63, %64, %65, %66, %67, %68, %69, %70, %71, %72, %73, %74, %75, %76, %77, %78, %79, %80, %81, %82, %83, %84, %85, %86, %87, %88, %89, %90, %91, %92, %93, %94, %95, %96, %97, %98, %99, %100, %101, %102, %103, %104, %105, %106, %107, %108, %109, %110, %111, %112, %113, %114, %115, %116, %117, %118, %119, %120, %121, %122, %123, %124, %125, %126, %127}, %128, %129, p, 1, 1, 0, 1;\n}\n"
        : "+f"(d[0]), "+f"(d[1]), "+f"(d[2]), "+f"(d[3]), "+f"(d[4]), "+f"(d[5]), "+f"(d[6]), "+f"(d[7]), "+f"(d[8]), "+f"(d[9]), "+f"(d[10]), "+f"(d[11]), "+f"(d[12]), "+f"(d[13]), "+f"(d[14]), "+f"(d[15]), "+f"(d[16]), "+f"(d[17]), "+f"(d[18]), "+f"(d[19]), "+f"(d[20]), "+f"(d[21]), "+f"(d[22]), "+f"(d[23]), "+f"(d[24]), "+f"(d[25]), "+f"(d[26]), "+f"(d[27]), "+f"(d[28]), "+f"(d[29]), "+f"(d[30]), "+f"(d[31]), "+f"(d[32]), "+f"(d[33]), "+f"(d[34]), "+f"(d[35]), "+f"(d[36]), "+f"(d[37]), "+f"(d[38]), "+f"(d[39]), "+f"(d[40]), "+f"(d[41]), "+f"(d[42]), "+f"(d[43]), "+f"(d[44]), "+f"(d[45]), "+f"(d[46]), "+f"(d[47]), "+f"(d[48]), "+f"(d[49]), "+f"(d[50]), "+f"(d[51]), "+f"(d[52]), "+f"(d[53]), "+f"(d[54]), "+f"(d[55]), "+f"(d[56]), "+f"(d[57]), "+f"(d[58]), "+f"(d[59]), "+f"(d[60]), "+f"(d[61]), "+f"(d[62]), "+f"(d[63]), "+f"(d[64]), "+f"(d[65]), "+f"(d[66]), "+f"(d[67]), "+f"(d[68]), "+f"(d[69]), "+f"(d[70]), "+f"(d[71]), "+f"(d[72]), "+f"(d[73]), "+f"(d[74]), "+f"(d[75]), "+f"(d[76]), "+f"(d[77]), "+f"(d[78]), "+f"(d[79]), "+f"(d[80]), "+f"(d[81]), "+f"(d[82]), "+f"(d[83]), "+f"(d[84]), "+f"(d[85]), "+f"(d[86]), "+f"(d[87]), "+f"(d[88]), "+f"(d[89]), "+f"(d[90]), "+f"(d[91]), "+f"(d[92]), "+f"(d[93]), "+f"(d[94]), "+f"(d[95]), "+f"(d[96]), "+f"(d[97]), "+f"(d[98]), "+f"(d[99]), "+f"(d[100]), "+f"(d[101]), "+f"(d[102]), "+f"(d[103]), "+f"(d[104]), "+f"(d[105]), "+f"(d[106]), "+f"(d[107]), "+f"(d[108]), "+f"(d[109]), "+f"(d[110]), "+f"(d[111]), "+f"(d[112]), "+f"(d[113]), "+f"(d[114]), "+f"(d[115]), "+f"(d[116]), "+f"(d[117]), "+f"(d[118]), "+f"(d[119]), "+f"(d[120]), "+f"(d[121]), "+f"(d[122]), "+f"(d[123]), "+f"(d[124]), "+f"(d[125]), "+f"(d[126]), "+f"(d[127])
        : "l"(da), "l"(db), "r"(scale_d));
}
__device__ __forceinline__ void stmatrix_x4(uint32_t addr, uint32_t r0, uint32_t r1, uint32_t r2, uint32_t r3) {
    asm volatile("stmatrix.sync.aligned.m8n8.x4.shared.b16 [%0], {%1, %2, %3, %4};" :: "r"(addr), "r"(r0), "r"(r1), "r"(r2), "r"(r3) : "memory");
}
__device__ __forceinline__ void tma_store_2d(const CUtensorMap* map, uint32_t src, int c0, int c1) {
    asm volatile("cp.async.bulk.tensor.2d.global.shared::cta.bulk_group [%0, {%2, %3}], [%1];"
                 :: "l"((uint64_t)map), "r"(src), "r"(c0), "r"(c1) : "memory");
}
__device__ __forceinline__ float ex2f(float x) { float y; asm("ex2.approx.ftz.f32 %0, %1;" : "=f"(y) : "f"(x)); return y; }
__device__ __forceinline__ uint32_t pack_bf16(float lo, float hi) {
    __nv_bfloat162 v = __floats2bfloat162_rn(lo, hi);
    return *reinterpret_cast<uint32_t*>(&v);
}
__device__ __forceinline__ void mma_16816(float (&c)[4], uint32_t a0, uint32_t a1, uint32_t a2, uint32_t a3,
                                          uint32_t b0, uint32_t b1) {
    asm volatile(
        "mma.sync.aligned.m16n8k16.row.col.f32.bf16.bf16.f32 {%0,%1,%2,%3}, {%4,%5,%6,%7}, {%8,%9}, {%0,%1,%2,%3};"
        : "+f"(c[0]), "+f"(c[1]), "+f"(c[2]), "+f"(c[3])
        : "r"(a0), "r"(a1), "r"(a2), "r"(a3), "r"(b0), "r"(b1));
}
__device__ __forceinline__ void ldmatrix_x4_trans(uint32_t& r0, uint32_t& r1, uint32_t& r2, uint32_t& r3, uint32_t addr) {
    asm volatile("ldmatrix.sync.aligned.m8n8.x4.trans.shared.b16 {%0,%1,%2,%3}, [%4];"
                 : "=r"(r0), "=r"(r1), "=r"(r2), "=r"(r3) : "r"(addr));
}

struct AttnParams {
    CUtensorMap mapQ, mapK, mapV;
    CUtensorMap mapO;
    bf16* out;
};
constexpr int FA_ITEMS = 16 * NH;
__device__ __forceinline__ int fa_qt(int t) { return 15 - ((t & 127) >> 3); }
__device__ __forceinline__ int fa_head(int t) { return (t >> 7) * 8 + (t & 7); }
#define FA_TKA 2
#define FA_SPLIT 11

#define FA_P0 4
#define FA_HO 7
#define FA_LAG 2
#define FA_PK 3
#define FA_ST 4
#define FA_TG 16
#define FA_EARLY 0
#define FA_I0 0
static_assert(FA_GRID <= 104 && FA_HO >= FA_P0 && FA_P0 >= 1, "");
constexpr float FA_MARGIN = 16.f;
#define FAT(b, i)
__device__ __forceinline__ void mbar_arrive_if(uint32_t bar, bool c) {
    asm volatile("{\n.reg .pred p;\nsetp.ne.b32 p, %1, 0;\n@p mbarrier.arrive.shared::cta.b64 _, [%0];\n}" :: "r"(bar), "r"((int)c) : "memory");
}
__device__ __forceinline__ void sched_fence(int v, int id, const float* a, const float* b, const float* c) {
    asm volatile("{\n.reg .pred p;\nsetp.ne.s32 p, %0, %1;\n@p bra SF_SKIP;\nwgmma.wait_group.sync.aligned 0;\n"
                 "st.volatile.shared.f32 [%0], %2;\nst.volatile.shared.f32 [%0], %3;\nst.volatile.shared.f32 [%0], %4;\nst.volatile.shared.f32 [%0], %5;\n"
                 "st.volatile.shared.f32 [%0], %6;\nst.volatile.shared.f32 [%0], %7;\nst.volatile.shared.f32 [%0], %8;\nst.volatile.shared.f32 [%0], %9;\n"
                 "st.volatile.shared.f32 [%0], %10;\nst.volatile.shared.f32 [%0], %11;\nst.volatile.shared.f32 [%0], %12;\nst.volatile.shared.f32 [%0], %13;\n"
                 "exit;\nSF_SKIP:\n}" :: "r"(v), "r"(1000000 + id), "f"(a[0]), "f"(a[1]), "f"(a[2]), "f"(a[3]), "f"(b[0]), "f"(b[1]), "f"(b[2]), "f"(b[3]),
                 "f"(c[0]), "f"(c[1]), "f"(c[2]), "f"(c[3]) : "memory");
}
__device__ __forceinline__ float ex2v(float x) { float y; asm volatile("ex2.approx.ftz.f32 %0, %1;" : "=f"(y) : "f"(x)); return y; }
__device__ __forceinline__ void wgmma_rs_n128_tb_lo(float (&d)[64], const uint32_t* a, uint32_t db_lo, int scale_d) {
    asm volatile(
        "{\n.reg .pred p;\n.reg .b64 db;\nsetp.ne.b32 p, %69, 0;\nmov.b64 db, {%68, 0x40000040};\n"
        "wgmma.mma_async.sync.aligned.m64n128k16.f32.bf16.bf16 " ACC64_STR ", {%64, %65, %66, %67}, db, p, 1, 1, 1;\n}\n"
        : ACC64(d) : "r"(a[0]), "r"(a[1]), "r"(a[2]), "r"(a[3]), "r"(db_lo), "r"(scale_d));
}

constexpr int M_GRID = 68;
constexpr uint32_t SD = 1024;
constexpr uint32_t MO_BAR = 229376;
constexpr int M_SMEM = MO_BAR + 1024;
constexpr uint32_t FO_Q = 0, FO_KV = 65536, FO_O = FO_KV + 2 * 65536, FO_BAR = MO_BAR + 512;
constexpr uint32_t FB_QF = FO_BAR, FB_QE = FO_BAR + 16, FB_KF = FO_BAR + 32, FB_VF = FO_BAR + 48, FB_KE = FO_BAR + 64, FB_VE = FO_BAR + 80,
                   FB_OF = FO_BAR + 96, FB_OE = FO_BAR + 112, FB_SLOT = FO_BAR + 128, FB_OSLOT = FO_BAR + 136;
__device__ __forceinline__ void attn_init(uint32_t sb) {
    for (int i = 0; i < 2; i++) {
        mbar_init(sb + FB_QF + 8 * i, 1); mbar_init(sb + FB_QE + 8 * i, 8); mbar_init(sb + FB_KF + 8 * i, 1); mbar_init(sb + FB_VF + 8 * i, 1);
        mbar_init(sb + FB_KE + 8 * i, 8); mbar_init(sb + FB_VE + 8 * i, 8); mbar_init(sb + FB_OF + 8 * i, 4); mbar_init(sb + FB_OE + 8 * i, 1);
    }
}
__device__ __forceinline__ void attn_helper(const AttnParams& P, uint32_t sb, int wg) {
    const uint32_t stg = sb + FO_O + wg * 16384;
    for (int n = 0;; n++) {
        mbar_wait(sb + FB_OF + 8 * wg, n & 1);
        int t;
        asm volatile("ld.shared.s32 %0, [%1];" : "=r"(t) : "r"(sb + FB_OSLOT + wg * 4) : "memory");
        const int qt = fa_qt(t), h = fa_head(t & 1023);
        tma_store_2d(&P.mapO, stg, 0, h * SEQ + qt * 128 + wg * 64);
        tma_store_2d(&P.mapO, stg + 8192, 64, h * SEQ + qt * 128 + wg * 64);
        asm volatile("cp.async.bulk.commit_group;" ::: "memory");
        asm volatile("cp.async.bulk.wait_group.read 0;" ::: "memory");
        mbar_arrive(sb + FB_OE + 8 * wg);
        asm volatile("cp.async.bulk.wait_group 0;" ::: "memory");
        signal_ctr(CT_CA + qt * 4 + (h >> 3));
        if (t >= 1024) break;
    }
}
__device__ __forceinline__ void attn_producer(const AttnParams& P, uint32_t sb, uint32_t free_bar, uint32_t free_par) {
    const uint32_t sQ = sb + FO_Q, sKV = sb + FO_KV;
    int b = 0, hp_ready = 0, vrow = 0, t = blockIdx.x, item = 0;
    auto load_v = [&](int i) {
        const uint32_t sv = sKV + (i & 1) * 65536 + 32768, bar = sb + FB_VF + 8 * (i & 1);
        mbar_wait(sb + FB_VE + 8 * (i & 1), ((i >> 1) & 1) ^ 1);
        mbar_expect_tx(bar, 32768);
        tma_load_2d(sv, &P.mapV, bar, 0, vrow);
        tma_load_2d(sv + 16384, &P.mapV, bar, 64, vrow);
    };
    for (;; item++) {
        const bool valid = t < FA_ITEMS;
        const int qt = fa_qt(t), h = fa_head(t);
        if (valid && !((hp_ready >> (h >> 1)) & 1)) { wait_ctr(CT_AP + (h >> 1), 96u); hp_ready |= 1 << (h >> 1); }
        const uint32_t bq = sb + FB_QF + 8 * (item & 1);
        mbar_wait(item ? sb + FB_QE + 8 * (item & 1) : free_bar + 8, item ? ((item >> 1) & 1) ^ 1 : free_par);
        asm volatile("st.shared.s32 [%0], %1;" :: "r"(sb + FB_SLOT + (item & 1) * 4), "r"(valid ? t : -1) : "memory");
        if (!valid) { mbar_arrive(bq); break; }
        mbar_expect_tx(bq, 32768);
        tma_load_2d(sQ + (item & 1) * 32768, &P.mapQ, bq, 0, h * SEQ + qt * 128);
        tma_load_2d(sQ + (item & 1) * 32768 + 16384, &P.mapQ, bq, 64, h * SEQ + qt * 128);
#pragma unroll 1
        for (int j = 0; j <= qt; j++, b++) {
            const uint32_t sk = sKV + (b & 1) * 65536, bar = sb + FB_KF + 8 * (b & 1);
            mbar_wait(b >= 2 ? sb + FB_KE + 8 * (b & 1) : free_bar + 24 + 32 * b, b >= 2 ? ((b >> 1) & 1) ^ 1 : free_par);
            if (b == 1) { TS_END2(0, 256); TS_BEGIN2(1, 256); }
            if (b == 2) wait_ctr(CT_GATE, 64u);
            mbar_expect_tx(bar, 32768);
            tma_load_2d(sk, &P.mapK, bar, 0, h * SEQ + j * 128);
            tma_load_2d(sk + 16384, &P.mapK, bar, 64, h * SEQ + j * 128);
            if (j == max(qt - FA_TKA, 0)) t = take_ticket(CT_ATTN);
            if (b > 0) load_v(b - 1);
            vrow = h * SEQ + j * 128;
        }
        t += M_GRID;
    }
    load_v(b - 1);
    mbar_wait(sb + FB_KE + 8 * (~b & 1), ((b - 1) >> 1) & 1);
}
template <uint32_t sb, typename F>
__device__ __forceinline__ void attn_consumer(const AttnParams& P, int warp, F done) {
    constexpr uint32_t sQ = SD + FO_Q, sKV = SD + FO_KV;
    constexpr uint32_t sO = sb + FO_O;
    constexpr uint32_t bar_qf = sb + FB_QF, bar_qe = sb + FB_QE, bar_kf = sb + FB_KF, bar_vf = sb + FB_VF, bar_ke = sb + FB_KE, bar_ve = sb + FB_VE,
                   bar_of = sb + FB_OF, bar_oe = sb + FB_OE, slot = sb + FB_SLOT, oslot = sb + FB_OSLOT;
    {
        const int wg = warp >> 2;
        const int lane = threadIdx.x & 31;
        const float sc = 0.08838834764831845f * 1.4426950408889634f;
        const int r0 = wg * 64 + (warp & 3) * 16 + (lane >> 2);
        float o[64], s[64];
        uint32_t pa[32];
        float m0 = 0.f, m1 = 0.f, l0 = 0.f, l1 = 0.f, i0 = 0.f, i1 = 0.f, g0 = 0.f, g1 = 0.f;
        const uint32_t q_lo = desc_lo(sQ + wg * 8192, 16), k_lo = desc_lo(sKV, 16), v_lo = desc_lo(sKV + 32768, 16384);
        auto issue_qk = [&](int b, int item) {
            const uint32_t qd = q_lo + (item & 1) * 2048, kd = k_lo + (b & 1) * 4096;
            wgmma_fence();
#pragma unroll
            for (int kk = 0; kk < 8; kk++) wgmma_ss_n128_lo<0>(s, qd + (kk >> 2) * 1024 + (kk & 3) * 2, kd + (kk >> 2) * 1024 + (kk & 3) * 2, kk != 0);
            wgmma_commit();
        };
        auto issue_pv = [&](int b, bool acc, int n) {
            const uint32_t vd = v_lo + (b & 1) * 4096;
            mbar_wait(bar_vf + 8 * (b & 1), (b >> 1) & 1);
            wgmma_fence();
#pragma unroll
            for (int kk = 0; kk < 8; kk++) if (kk < n) wgmma_rs_n128_tb_lo(o, &pa[kk * 4], vd + kk * 128, kk ? 1 : (int)acc);
            wgmma_commit();
        };
        const int lim = r0 - (lane & 3) * 2;
        int item = -1, tnext = 0;
        uint32_t k_ready = 0, q_ready = 0;
        auto mask = [&](int i) { if ((i >> 2) * 8 + (i & 1) - ((i & 2) ? 8 : 0) > lim) s[i] = -INFINITY; };
        auto exps = [&](auto mode, int b, bool hand_over, float& u0, float& u1) {
            constexpr int MODE = decltype(mode)::value;
            float p[64], u[4] = {0.f, 0.f, 0.f, 0.f};
            const uint32_t vd = v_lo + ((b - 1) & 1) * 4096;
#pragma unroll
            for (int i = 0; i < 4; i++) p[i] = fmaf(s[i], sc, (i & 2) ? -m1 : -m0);
#pragma unroll
            for (int g = 0; g < 16 + FA_LAG; g++) {
                if (MODE && g >= FA_I0 && g - FA_I0 < 8 - FA_P0) {
                    const int kk = FA_P0 + g - FA_I0;
                    wgmma_fence();
                    wgmma_rs_n128_tb_lo(o, &pa[kk * 4], vd + kk * 128, 1);
                    wgmma_commit();
                    if (kk == FA_HO) asm volatile("{\n.reg .pred p;\nsetp.ne.b32 p, %1, 0;\n@p bar.arrive %0, 256;\n}" :: "r"(4 - wg), "r"((int)hand_over) : "memory");
                }
                if (MODE && g == FA_SPLIT) {
                    FAT(b, 2);
                    wgmma_wait<0>();
                    FAT(b - 1, 3);
                    mbar_arrive_if(bar_ve + 8 * ((b - 1) & 1), lane == 0);
                }
                if (MODE && g == FA_TG) {
                    k_ready = mbar_test(bar_kf + 8 * (~b & 1), ((b + 1) >> 1) & 1);
                    if (MODE == 2) {
                        q_ready = mbar_test(bar_qf + 8 * (~item & 1), ((item + 1) >> 1) & 1);
                        asm volatile("ld.shared.s32 %0, [%1];" : "=r"(tnext) : "r"(slot + (~item & 1) * 4) : "memory");
                    }
                }
#pragma unroll
                for (int j = 0; j < 4; j++) {
                    const int i = g * 4 + j;
                    if (g < 16) p[i] = ex2v(p[i]);
                    if (g < 15) {
                        if (MODE == 2) mask(i + 4);
                        p[i + 4] = fmaf(s[i + 4], sc, (i & 2) ? -m1 : -m0);
                    }
                    if (g >= FA_LAG) u[j] += p[i - FA_LAG * 4];
                }
#pragma unroll
                for (int gg = 0; gg < 16; gg++) {
                    const int at = MODE && gg + FA_LAG < FA_SPLIT + gg / FA_PK ? FA_SPLIT + gg / FA_PK : gg + FA_LAG;
                    if (at == g) { pa[gg * 2] = pack_bf16(p[gg * 4], p[gg * 4 + 1]); pa[gg * 2 + 1] = pack_bf16(p[gg * 4 + 2], p[gg * 4 + 3]); }
                }
                if (MODE && g < 16) sched_fence(b, g + MODE * 32, &p[g * 4], &p[(g < 15 ? g + 1 : g) * 4], u);
            }
            u0 = u[0] + u[1]; u1 = u[2] + u[3];
        };
        auto quad_max = [&](float& x0, float& x1) {
            x0 = fmaxf(x0, __shfl_xor_sync(0xffffffff, x0, 1)); x1 = fmaxf(x1, __shfl_xor_sync(0xffffffff, x1, 1));
            x0 = fmaxf(x0, __shfl_xor_sync(0xffffffff, x0, 2)); x1 = fmaxf(x1, __shfl_xor_sync(0xffffffff, x1, 2));
            x0 = fmaf(x0, sc, FA_MARGIN); x1 = fmaf(x1, sc, FA_MARGIN);
        };
        auto softmax_exact = [&](bool fresh, int b) {
            wgmma_wait<0>();
            float x[8];
#pragma unroll
            for (int i = 0; i < 8; i++) x[i] = fmaxf(s[i * 2], s[i * 2 + 1]);
#pragma unroll
            for (int i = 8; i < 32; i++) x[i & 7] = fmaxf(x[i & 7], fmaxf(s[i * 2], s[i * 2 + 1]));
            float x0 = fmaxf(fmaxf(x[0], x[2]), fmaxf(x[4], x[6])), x1 = fmaxf(fmaxf(x[1], x[3]), fmaxf(x[5], x[7]));
            quad_max(x0, x1);
            if (!fresh) {
                x0 = fmaxf(x0, m0); x1 = fmaxf(x1, m1);
                const float a0 = ex2f(m0 - x0), a1 = ex2f(m1 - x1);
                l0 *= a0; l1 *= a1;
#pragma unroll
                for (int i = 0; i < 16; i++) { o[i * 4 + 0] *= a0; o[i * 4 + 1] *= a0; o[i * 4 + 2] *= a1; o[i * 4 + 3] *= a1; }
            }
            m0 = x0; m1 = x1;
            float u0, u1;
            exps(std::integral_constant<int, 0>(), b, false, u0, u1);
            l0 += u0; l1 += u1;
        };
        auto finish_rows = [&]() {
            l0 += __shfl_xor_sync(0xffffffff, l0, 1); l1 += __shfl_xor_sync(0xffffffff, l1, 1);
            l0 += __shfl_xor_sync(0xffffffff, l0, 2); l1 += __shfl_xor_sync(0xffffffff, l1, 2);
            i0 = __fdividef(g0, l0); i1 = __fdividef(g1, l1);
        };
        auto clear_out = [&](int t) {
            if (t >= 384) {
                bf16* z = P.out + (size_t)(fa_qt(t) * 128 + wg * 64 + ((threadIdx.x & 127) >> 3)) * DM + (t & 7) * 64 + (lane & 7) * 8;
#pragma unroll
                for (int i = 0; i < 4; i++) *reinterpret_cast<uint4*>(z + i * 16 * DM) = make_uint4(0u, 0u, 0u, 0u);
            }
        };
        auto store_o = [&](int t, int n, int c0, int c1) {
            const uint32_t stg = sO + wg * 16384;
            if (c0 == 0) {
                mbar_wait(bar_oe + 8 * wg, (n & 1) ^ 1);
                asm volatile("st.shared.s32 [%0], %1;" :: "r"(oslot + wg * 4), "r"(t) : "memory");
            }
            const int row = (warp & 3) * 16 + (lane >> 2);
#pragma unroll
            for (int i = c0; i < c1; i++) {
                const int ch = i * 4 + (lane & 3);
                const uint32_t a = stg + (ch >> 3) * 8192 + row * 128 + (((ch & 7) ^ (row & 7)) << 4);
                const float* q = &o[i * 16];
                asm volatile("st.shared.v4.b32 [%0], {%1, %2, %3, %4};" :: "r"(a), "r"(pack_bf16(q[0] * i0, q[1] * i0)), "r"(pack_bf16(q[4] * i0, q[5] * i0)),
                             "r"(pack_bf16(q[8] * i0, q[9] * i0)), "r"(pack_bf16(q[12] * i0, q[13] * i0)) : "memory");
                asm volatile("st.shared.v4.b32 [%0], {%1, %2, %3, %4};" :: "r"(a + 1024), "r"(pack_bf16(q[2] * i1, q[3] * i1)), "r"(pack_bf16(q[6] * i1, q[7] * i1)),
                             "r"(pack_bf16(q[10] * i1, q[11] * i1)), "r"(pack_bf16(q[14] * i1, q[15] * i1)) : "memory");
            }
        };
        auto publish_o = [&]() {
            asm volatile("fence.proxy.async.shared::cta;" ::: "memory");
            __syncwarp();
            mbar_arrive_if(bar_of + 8 * wg, lane == 0);
        };
        int t = 0, left = 0, tdone = -1, b = 0, nout = 0;
        bool first = true, staged = false;
#pragma unroll 1
        for (;; b++) {
            const bool fresh = left == 0;
            const int tprev = t;
            FAT(b, 4);
            if (staged) { publish_o(); staged = false; }
            if (fresh) {
                item++;
                if (!q_ready) {
                    mbar_wait(bar_qf + 8 * (item & 1), (item >> 1) & 1);
                    asm volatile("ld.shared.s32 %0, [%1];" : "=r"(tnext) : "r"(slot + (item & 1) * 4) : "memory");
                }
                if (tnext < 0) break;
                t = tnext;
                left = fa_qt(t) + 1;
            }
            left--;
            if (tdone >= 0) store_o(tdone, nout, 0, FA_ST);
            FAT(b, 5);
            if (!k_ready) mbar_wait(bar_kf + 8 * (b & 1), (b >> 1) & 1);
            FAT(b, 6);
            asm volatile("bar.sync %0, 256;" :: "r"(3 + wg) : "memory");
            FAT(b, 0);
            issue_qk(b, item);
            bool early = false;
            if (!fresh && !first && left != 0) {
                issue_pv(b - 1, true, FA_P0);
                wgmma_wait<1>();
                FAT(b, 1);
                mbar_arrive_if(bar_ke + 8 * (b & 1), lane == 0);
            } else {
                early = (FA_EARLY && tdone >= 0) || b == 0;
                if (early) asm volatile("bar.arrive %0, 256;" :: "r"(4 - wg) : "memory");
                if (tdone >= 0) { wgmma_wait<1>(); store_o(tdone, nout++, FA_ST, 4); staged = true; }
                tdone = -1;
                if (fresh && b > 0) { finish_rows(); tdone = tprev; l0 = l1 = 0.f; }
                if (left == 0) { g0 = __ldcg(g_gate + fa_qt(t) * 128 + r0); g1 = __ldcg(g_gate + fa_qt(t) * 128 + r0 + 8); clear_out(t); }
                if (b > 0) issue_pv(b - 1, !first, FA_P0); else { wgmma_fence(); wgmma_commit(); }
                first = fresh;
                wgmma_wait<1>();
                FAT(b, 1);
                mbar_arrive_if(bar_ke + 8 * (b & 1), lane == 0);
                mbar_arrive_if(bar_qe + 8 * (item & 1), lane == 0 && left == 0);
                if (left == 0) { mask(0); mask(1); }
                if (fresh) { m0 = fmaxf(s[0], s[1]); m1 = fmaxf(s[2], s[3]); quad_max(m0, m1); }
            }
            if (b > 0) {
                float u0, u1;
                if (left == 0) exps(std::integral_constant<int, 2>(), b, !early, u0, u1);
                else exps(std::integral_constant<int, 1>(), b, !early, u0, u1);
                if (!__any_sync(0xffffffff, !(u0 + u1 < 1.f))) { l0 += u0; l1 += u1; continue; }
            }
            softmax_exact(fresh, b);
        }
        if (tdone >= 0) { store_o(tdone, nout++, 0, 4); publish_o(); }
        issue_pv(b - 1, !first, 8);
        finish_rows();
        wgmma_wait<0>();
        done();
        store_o(t + 1024, nout, 0, 4);
        publish_o();
    }
}

__device__ __forceinline__ uint32_t cluster_ctarank() {
    uint32_t r; asm volatile("mov.u32 %0, %%cluster_ctarank;" : "=r"(r)); return r;
}
__device__ __forceinline__ uint32_t mapa_u32(uint32_t addr, uint32_t rank) {
    uint32_t r; asm volatile("mapa.shared::cluster.u32 %0, %1, %2;" : "=r"(r) : "r"(addr), "r"(rank)); return r;
}
__device__ __forceinline__ void cluster_sync_all() {
    asm volatile("barrier.cluster.arrive.release.aligned;\nbarrier.cluster.wait.acquire.aligned;" ::: "memory");
}
__device__ __forceinline__ void st_async_v4(uint32_t addr, uint32_t a, uint32_t b, uint32_t c, uint32_t d, uint32_t mbar) {
    asm volatile("st.async.weak.shared::cluster.mbarrier::complete_tx::bytes.v4.b32 [%0], {%1, %2, %3, %4}, [%5];"
                 :: "r"(addr), "r"(a), "r"(b), "r"(c), "r"(d), "r"(mbar) : "memory");
}
__device__ __forceinline__ void st_async_v2(uint32_t addr, uint32_t a, uint32_t b, uint32_t mbar) {
    asm volatile("st.async.weak.shared::cluster.mbarrier::complete_tx::bytes.v2.b32 [%0], {%1, %2}, [%3];"
                 :: "r"(addr), "r"(a), "r"(b), "r"(mbar) : "memory");
}
__device__ __forceinline__ void st_async_b32(uint32_t addr, uint32_t a, uint32_t mbar) {
    asm volatile("st.async.weak.shared::cluster.mbarrier::complete_tx::bytes.b32 [%0], %1, [%2];" :: "r"(addr), "r"(a), "r"(mbar) : "memory");
}
__device__ __forceinline__ void pace(int cycles) {
    if (cycles > 0) {
        uint32_t t0, t;
        asm volatile("mov.u32 %0, %%clock;" : "=r"(t0));
        do { asm volatile("mov.u32 %0, %%clock;" : "=r"(t)); } while (t - t0 < (uint32_t)cycles);
    }
}
__device__ __forceinline__ void mbar_wait_cl(uint32_t bar, uint32_t parity) {
    uint32_t done = 0;
    for (int it = 0; it < WAIT_LIMIT && !done; it++) {
        asm volatile(
            "{\n.reg .pred p;\n"
            "mbarrier.try_wait.parity.shared::cta.b64 p, [%1], %2;\n"
            "selp.u32 %0, 1, 0, p;\n}\n" : "=r"(done) : "r"(bar), "r"(parity) : "memory");
    }
}
__device__ __forceinline__ void ldmatrix_x4(uint32_t& r0, uint32_t& r1, uint32_t& r2, uint32_t& r3, uint32_t addr) {
    asm volatile("ldmatrix.sync.aligned.m8n8.x4.shared.b16 {%0,%1,%2,%3}, [%4];"
                 : "=r"(r0), "=r"(r1), "=r"(r2), "=r"(r3) : "r"(addr));
}
__device__ __forceinline__ void cp_async16(uint32_t dst, const void* src) {
    asm volatile("cp.async.cg.shared.global [%0], [%1], 16;" :: "r"(dst), "l"(src) : "memory");
}
__device__ __forceinline__ float bf16r(float x) { return __uint_as_float(pack_bf16(0.f, x) & 0xffff0000u); }

#define DBGP(i, w, ok)
#define DBG(i, w)
#define DBGD(i, w, dep)
#define DBG_EXTRA 0
__device__ __forceinline__ void tma_load_2d_mc(uint32_t dst, const CUtensorMap* map, uint32_t bar, int c0, int c1, uint16_t mask) {
    asm volatile(
        "cp.async.bulk.tensor.2d.shared::cluster.global.mbarrier::complete_tx::bytes.multicast::cluster [%0], [%1, {%3, %4}], [%2], %5;"
        :: "r"(dst), "l"((uint64_t)map), "r"(bar), "r"(c0), "r"(c1), "h"(mask) : "memory");
}
__device__ __forceinline__ void stmatrix_x4_trans(uint32_t addr, uint32_t r0, uint32_t r1, uint32_t r2, uint32_t r3) {
    asm volatile("stmatrix.sync.aligned.m8n8.x4.trans.shared.b16 [%0], {%1, %2, %3, %4};" :: "r"(addr), "r"(r0), "r"(r1), "r"(r2), "r"(r3) : "memory");
}
__device__ __forceinline__ void stmatrix_x2_trans(uint32_t addr, uint32_t r0, uint32_t r1) {
    asm volatile("stmatrix.sync.aligned.m8n8.x2.trans.shared.b16 [%0], {%1, %2};" :: "r"(addr), "r"(r0), "r"(r1) : "memory");
}
__device__ __forceinline__ uint4 lds128(uint32_t a) {
    uint4 v; asm volatile("ld.shared.v4.u32 {%0, %1, %2, %3}, [%4];" : "=r"(v.x), "=r"(v.y), "=r"(v.z), "=r"(v.w) : "r"(a) : "memory"); return v;
}
__device__ __forceinline__ void sts128(uint32_t a, uint32_t x, uint32_t y, uint32_t z, uint32_t w) {
    asm volatile("st.shared.v4.b32 [%0], {%1, %2, %3, %4};" :: "r"(a), "r"(x), "r"(y), "r"(z), "r"(w) : "memory");
}
__device__ __forceinline__ float2 lds64f(uint32_t a) {
    float2 v; asm volatile("ld.shared.v2.f32 {%0, %1}, [%2];" : "=f"(v.x), "=f"(v.y) : "r"(a) : "memory"); return v;
}
__device__ __forceinline__ void fence_async_smem() { asm volatile("fence.proxy.async.shared::cta;" ::: "memory"); }
#define ACC16(d) "+f"(d[0]), "+f"(d[1]), "+f"(d[2]), "+f"(d[3]), "+f"(d[4]), "+f"(d[5]), "+f"(d[6]), "+f"(d[7]), "+f"(d[8]), "+f"(d[9]), "+f"(d[10]), "+f"(d[11]), "+f"(d[12]), "+f"(d[13]), "+f"(d[14]), "+f"(d[15])
template <int ND>
__device__ __forceinline__ void wgmma_rs_n32(float (&d)[ND], const uint32_t (&a)[4], uint32_t db_lo, int scale_d) {
    asm volatile(
        "{\n.reg .pred p;\n.reg .b64 db;\nsetp.ne.b32 p, %21, 0;\nmov.b64 db, {%20, 0x40000040};\n"
        "wgmma.mma_async.sync.aligned.m64n32k16.f32.bf16.bf16 {%0,%1,%2,%3,%4,%5,%6,%7,%8,%9,%10,%11,%12,%13,%14,%15}, {%16,%17,%18,%19}, db, p, 1, 1, 0;\n}\n"
        : ACC16(d) : "r"(a[0]), "r"(a[1]), "r"(a[2]), "r"(a[3]), "r"(db_lo), "r"(scale_d));
}
template <int ND>
__device__ __forceinline__ void wgmma_ss_n32(float (&d)[ND], uint32_t da_lo, uint32_t db_lo, int scale_d) {
    asm volatile(
        "{\n.reg .pred p;\n.reg .b64 da, db;\nsetp.ne.b32 p, %18, 0;\nmov.b64 da, {%16, 0x40000040};\nmov.b64 db, {%17, 0x40000040};\n"
        "wgmma.mma_async.sync.aligned.m64n32k16.f32.bf16.bf16 {%0,%1,%2,%3,%4,%5,%6,%7,%8,%9,%10,%11,%12,%13,%14,%15}, da, db, p, 1, 1, 1, 0;\n}\n"
        : ACC16(d) : "r"(da_lo), "r"(db_lo), "r"(scale_d));
}
__device__ __forceinline__ void wgmma_ss_n8(float (&d)[4], uint32_t da_lo, uint32_t db_lo, int scale_d) {
    asm volatile(
        "{\n.reg .pred p;\n.reg .b64 da, db;\nsetp.ne.b32 p, %6, 0;\nmov.b64 da, {%4, 0x40000040};\nmov.b64 db, {%5, 0x00000010};\n"
        "wgmma.mma_async.sync.aligned.m64n8k16.f32.bf16.bf16 {%0,%1,%2,%3}, da, db, p, 1, 1, 1, 0;\n}\n"
        : "+f"(d[0]), "+f"(d[1]), "+f"(d[2]), "+f"(d[3]) : "r"(da_lo), "r"(db_lo), "r"(scale_d));
}

#define SCHED_FENCE()
__device__ __forceinline__ void wgmma_ss_n32_p(float (&d)[16], uint32_t da_lo, uint32_t db_lo, int scale_d) {
    asm volatile(
        "{\n.reg .pred p;\n.reg .b64 da, db;\nsetp.ne.b32 p, %18, 0;\nmov.b64 da, {%16, 0x40000040};\nmov.b64 db, {%17, 0x00000030};\n"
        "wgmma.mma_async.sync.aligned.m64n32k16.f32.bf16.bf16 {%0,%1,%2,%3,%4,%5,%6,%7,%8,%9,%10,%11,%12,%13,%14,%15}, da, db, p, 1, 1, 1, 0;\n}\n"
        : ACC16(d) : "r"(da_lo), "r"(db_lo), "r"(scale_d));
}

#define ACC20(d) ACC16(d), "+f"(d[16]), "+f"(d[17]), "+f"(d[18]), "+f"(d[19])
#define ACC20_STR "{%0,%1,%2,%3,%4,%5,%6,%7,%8,%9,%10,%11,%12,%13,%14,%15,%16,%17,%18,%19}"
__device__ __forceinline__ void wgmma_rs_n40(float (&d)[20], const uint32_t (&a)[4], uint32_t db_lo, int scale_d) {
    asm volatile(
        "{\n.reg .pred p;\n.reg .b64 db;\nsetp.ne.b32 p, %25, 0;\nmov.b64 db, {%24, 0x40000040};\n"
        "wgmma.mma_async.sync.aligned.m64n40k16.f32.bf16.bf16 " ACC20_STR ", {%20,%21,%22,%23}, db, p, 1, 1, 0;\n}\n"
        : ACC20(d) : "r"(a[0]), "r"(a[1]), "r"(a[2]), "r"(a[3]), "r"(db_lo), "r"(scale_d));
}
template <int TA, int SBO>
__device__ __forceinline__ void wgmma_ss_n40(float (&d)[20], uint32_t da_lo, uint32_t db_lo, int scale_d) {
    asm volatile(
        "{\n.reg .pred p;\n.reg .b64 da, db;\nsetp.ne.b32 p, %22, 0;\nmov.b64 da, {%20, %23};\nmov.b64 db, {%21, 0x40000040};\n"
        "wgmma.mma_async.sync.aligned.m64n40k16.f32.bf16.bf16 " ACC20_STR ", da, db, p, 1, 1, %24, 0;\n}\n"
        : ACC20(d) : "r"(da_lo), "r"(db_lo), "r"(scale_d), "n"(0x40000000 + SBO / 16), "n"(TA));
}

#define PT(i, th)
struct ChainParams {
    CUtensorMap mapW[3];
    CUtensorMap mapX;
    CUtensorMap mapC;
};
constexpr int CH_BLOCK = 384;
constexpr int CO_WO = 0;
constexpr int CH_XC = 5120, CH_XP = 8 * CH_XC;
constexpr int CO_XB = 65536;
constexpr int CO_OB = CO_XB + 2 * CH_XP;
constexpr int CO_P = CO_OB + 8192;
constexpr int CO_LS = CO_P + 3072;
constexpr int CO_SC = CO_LS + 8 * 1280;
constexpr int CH_TW = 6144 + 8192;
constexpr int CO_T = 21 * 8192;
constexpr int CO_WA = CO_T + 6144;
constexpr int CO_ST = CO_T + 3 * CH_TW + 6144;
constexpr int CO_OWN = CO_ST + 4096, CO_OWN2 = CO_SC + 1536;
constexpr int CO_BAR = CO_OWN + 4096;
constexpr int CH_SMEM = CO_BAR + 256 + DBG_EXTRA;
#define CH_NSM 4
static_assert(CO_OWN2 + 1024 <= CO_T && CH_NSM <= 4, "smem layout");
#define CH_POLL_DELAY 200
#define CH_VPOS 2
#define CH_OW 12
#define CH_OF 12
#define CH_Q0 0
#define CH_QI 12
#define CH_QX 0
#define CH_Q1 (CH_Q0 + CH_QI + CH_QX)
#define CH_VA 5
#define CH_SPOS 0
#define CH_LSW 1
#define CH_QE 32
#define CH_KE 32
#define CH_QD 0
#define CH_GAP 0
#define CH_QS (CH_Q1 + 6)
#define CH_KS 10
#define CH_VS 0
#define CH_A7 7
#define CH_RF 0
#define CH_LSS 2
#define CH_OS 1
#define CH_MS 1
#define CH_HA 15
#define CH_LD 4
#define CH_TWP 0
#define CH_CHAINS 4

constexpr float CH_SC = 0.08838834764831845f * 1.4426950408889634f;
__device__ __forceinline__ uint32_t pin(uint32_t v) { return __shfl_sync(0xffffffff, v, threadIdx.x & 31); }

__global__ void __cluster_dims__(8, 1, 1) __launch_bounds__(CH_BLOCK, 1)
chain_kernel(const __grid_constant__ ChainParams P, const bf16* __restrict__ mem0, const bf16* __restrict__ Wo, const bf16* __restrict__ x,
             const bf16* __restrict__ gate_w) {
    extern __shared__ uint8_t smem_raw[];
    const int tid = threadIdx.x, warp = __shfl_sync(0xffffffff, tid >> 5, 0), lane = tid & 31;
    const int rank = (int)cluster_ctarank();
    constexpr uint32_t sd = 1024;
    const uint32_t sb = ((uint32_t)rank << 24) + sd;
    if (smem_u32(smem_raw) != sb) __trap();
    const int C = blockIdx.x >> 3;
    const int h = C * 4 + (rank >> 1);
    const int qd = lane >> 2, qc = lane & 3;
    const int t4 = warp & 3, wg = warp >> 2;
    pdl_launch_dependents();
    TS_BEGIN(2);
    PT(0, 0);
    const uint32_t bar_mem = sb + CO_BAR, bar_o = bar_mem + 32, bar_sc = bar_o + 32, bar_x = bar_sc + 8, bar_l = bar_x + 16, bar_w = bar_l + 8;
    if (tid == 0) {
        for (int j = 0; j < 15; j++) mbar_init(bar_mem + 8 * j, 1);
        sts128(bar_mem + 128, 0xffff0000u, 0u, 0u, 0u);
        asm volatile("fence.mbarrier_init.release.cluster;" ::: "memory");
    }
    __syncthreads();
    auto chunk = [&](int i) { return (uint32_t)((rank - (i >> 1) - 4 * (i & 1)) & 7); };
    if ((tid & 127) == 0) {
        mbar_expect_tx(bar_w + 8 * wg, 65536);
        for (int i = 0; i < 8; i++)
            tma_load_2d(sb + (i ? (wg * 7 + i - 1) * 8192 : CO_WA + wg * CH_TW), &P.mapW[wg], bar_w + 8 * wg, h * HD + (rank & 1) * 64, chunk(i) * 64);
    }
    PT(1, 0);
    {
        for (int i = tid; i < 512; i += CH_BLOCK) asm volatile("prefetch.global.L2 [%0];" :: "l"(Wo + (size_t)(C * 512 + i) * DM + rank * 64));
        if (tid < 64) asm volatile("prefetch.global.L2 [%0];" :: "l"(x + (size_t)tid * DM + rank * 64));
    }
    if (tid < 256) {
        const int r = blockIdx.x * 32 + (tid >> 3);
        float sum = 0.f;
#pragma unroll
        for (int c = 0; c < 8; c++) {
            const int col = c * 64 + (tid & 7) * 8;
            const uint4 xv = __ldg(reinterpret_cast<const uint4*>(x + (size_t)r * DM + col));
            const uint4 gv = __ldg(reinterpret_cast<const uint4*>(gate_w + col));
            const bf16* xp = reinterpret_cast<const bf16*>(&xv);
            const bf16* gp = reinterpret_cast<const bf16*>(&gv);
#pragma unroll
            for (int e = 0; e < 8; e++) sum += bf16r(__bfloat162float(xp[e]) * __bfloat162float(gp[e]));
        }
        sum += __shfl_xor_sync(0xffffffff, sum, 1);
        sum += __shfl_xor_sync(0xffffffff, sum, 2);
        sum += __shfl_xor_sync(0xffffffff, sum, 4);
        if ((tid & 7) == 0) g_gate[r] = bf16r(1.f / (1.f + __expf(-bf16r(sum))));
        *reinterpret_cast<uint2*>(g_xbuf + (tid >> 7) * 16384 + (size_t)rank * 2048 + C * 256 + (tid & 127) * 2) = make_uint2(~0u, ~0u);
        asm volatile("bar.sync 1, 256;" ::: "memory");
        if (tid == 32) signal_ctr_generic(CT_GATE);
    }
    const uint32_t wfrag = (((lane >> 4) << 3) + (lane & 7)) * 128 + (((t4 * 2 + ((lane >> 3) & 1)) ^ (lane & 7)) << 4);
    const uint32_t aO = pin(sb + wg * CH_TW + wfrag);
    const uint32_t aL = pin(sb + lane * 16);
    uint32_t w[32][4];
    PT(2, 0);
    mbar_wait(bar_w + 8 * wg, 0);
    PT(3, 0); PT(4, 256);
#pragma unroll
    for (int e = CH_NSM; e < 32; e++)
        ldmatrix_x4_trans(w[e][0], w[e][1], w[e][2], w[e][3], e < 4 ? aO + CO_WA + e * 2048 : sb + wg * 7 * 8192 + wfrag + (e - 4) * 2048);
    fence_async_smem();
    __syncthreads();
    PT(5, 0);
    if (tid == 0) {
        fence_async_smem();
        for (int b = 0; b < 2; b++) {
            mbar_expect_tx(bar_x + 8 * b, 32768);
            for (int i = 0; i < 8; i++) tma_load_2d(sb + CO_XB + b * CH_XP + i * CH_XC, &P.mapX, bar_x + 8 * b, i * 64, b * SEGL);
        }
    }
#pragma unroll 2
    for (int i = tid; i < 512 * 4; i += CH_BLOCK) {
        const int r = i >> 2, cg = i & 3, ks = r >> 4, kp = r & 15;
        const int src = (rank - (ks >> 2)) & 7;
        const uint4* p = reinterpret_cast<const uint4*>(Wo + (size_t)(C * 512 + src * 64 + (ks & 3) * 16 + (kp >> 2) * 2 + (kp & 1) + (kp & 2) * 4) * DM + rank * 64 + cg * 16);
        const uint4 u0 = __ldg(p), u1 = __ldg(p + 1);
        const uint32_t a = sb + CO_WO + r * 128;
        sts128(a + (((cg * 2) ^ (r & 7)) << 4), __byte_perm(u0.x, u0.y, 0x5410), __byte_perm(u0.z, u0.w, 0x5410), __byte_perm(u1.x, u1.y, 0x5410), __byte_perm(u1.z, u1.w, 0x5410));
        sts128(a + (((cg * 2 + 1) ^ (r & 7)) << 4), __byte_perm(u0.x, u0.y, 0x7632), __byte_perm(u0.z, u0.w, 0x7632), __byte_perm(u1.x, u1.y, 0x7632), __byte_perm(u1.z, u1.w, 0x7632));
    }
#pragma unroll 1
    for (int i = tid; i < 512; i += CH_BLOCK) {
        const int n = i >> 6, c = i & 63;
        const uint4 u = __ldg(reinterpret_cast<const uint4*>(mem0 + n * DM + c * 8));
        sts128(sb + CO_XB + (c >> 3) * CH_XC + 4096 + n * 128 + (((c & 7) ^ n) << 4), u.x, u.y, u.z, u.w);
    }
    if (tid < 128) sts128(sb + CO_T + (2 + (tid >> 6)) * CH_TW + 5120 + (tid & 63) * 16, 0u, 0u, 0u, 0u);
    else if (tid < 160) sts128(sb + CO_P + ((tid >> 3) & 3) * 768 + 640 + (tid & 7) * 16, 0u, 0u, 0u, 0u);
    fence_async_smem();
    TS_END(6);
    PT(6, 0);
    auto pass = [&](auto& d, int g, int b, int j0, int j1, int js, bool group = true) {
        const uint32_t lo = desc_lo(sd + CO_XB + b * CH_XP, 16);
        if (group) wgmma_fence();
#pragma unroll
        for (int j = 0; j < 32; j++) if (j >= j0 && j < j1) {
            const int e = j < js ? j + CH_NSM : j < js + CH_NSM ? j - js : j;
            const uint32_t db = lo + chunk(e >> 2) * (CH_XC / 16) + (e & 3) * 2, da = desc_lo(sd + CO_WA + g * CH_TW + e * 2048, 16);
            if constexpr (sizeof(d) == 64) { if (e < CH_NSM) wgmma_ss_n32(d, da, db, j != 0); else wgmma_rs_n32(d, w[e], db, j != 0); }
            else { if (e < CH_NSM) wgmma_ss_n40<1, 1024>(d, da, db, j != 0); else wgmma_rs_n40(d, w[e], db, j != 0); }
        }
        if (group) wgmma_commit();
    };
    auto uni = [](uint32_t v) { return __shfl_sync(0xffffffff, v, 0); };
    auto roff = [&](int j) { return (uint32_t)(((rank + j) & 7) - rank) << 24; };
    auto store32 = [&](const float* d, uint32_t a) {
        stmatrix_x4_trans(a, pack_bf16(d[0], d[1]), pack_bf16(d[2], d[3]), pack_bf16(d[4], d[5]), pack_bf16(d[6], d[7]));
        stmatrix_x4_trans(a + 2048, pack_bf16(d[8], d[9]), pack_bf16(d[10], d[11]), pack_bf16(d[12], d[13]), pack_bf16(d[14], d[15]));
    };
    auto scores = [&](float (&d)[20], auto sbo, uint32_t q) {
        wgmma_fence();
#pragma unroll
        for (int ks = 0; ks < 4; ks++) wgmma_ss_n40<0, decltype(sbo)::value>(d, desc_lo(sd + CO_T + q, 16) + ks * 2, desc_lo(sd + CO_T + CH_TW, 16) + ks * 2, ks != 0);
        wgmma_commit();
    };
    auto own_scores = [&](const float (&d)[20], float (&v)[10]) {
#pragma unroll
        for (int j = 0; j < 5; j++) { v[2 * j] = d[4 * j]; v[2 * j + 1] = d[4 * j + 1]; }
    };
    auto add_scores = [&](uint32_t a, uint32_t b, float (&v)[10]) {
        const uint4 a0 = lds128(a), a1 = lds128(a + 512);
        const float2 a2 = lds64f(b);
        v[0] += __uint_as_float(a0.x); v[1] += __uint_as_float(a0.y); v[2] += __uint_as_float(a0.z); v[3] += __uint_as_float(a0.w);
        v[4] += __uint_as_float(a1.x); v[5] += __uint_as_float(a1.y); v[6] += __uint_as_float(a1.z); v[7] += __uint_as_float(a1.w);
        v[8] += a2.x; v[9] += a2.y;
    };
    auto row_max = [&](const float (&v)[10]) {
        float mx = fmaxf(fmaxf(fmaxf(v[0], v[1]), fmaxf(v[2], v[3])), fmaxf(fmaxf(v[4], v[5]), fmaxf(v[6], v[7])));
        mx = fmaxf(mx, fmaxf(v[8], v[9]));
        mx = fmaxf(mx, __shfl_xor_sync(0xffffffff, mx, 1));
        return fmaxf(mx, __shfl_xor_sync(0xffffffff, mx, 2)) * CH_SC;
    };
    auto signal_ctx = [&](int m0, int m1) {
        for (int m = m0; m < m1; m++) asm volatile("red.relaxed.gpu.global.add.u32 [%0], 1;" :: "l"(&g_ctr[CT_CB + m]) : "memory");
    };
    auto signal_step = [](int s) { return s == 33 || s == 49 || s == 57 || s == 61; };
    if (mapa_u32(bar_l, rank ^ 1) != (bar_l ^ (1u << 24)) || mapa_u32(bar_l, (rank + 3) & 7) != bar_l + roff(3)) __trap();
    mbar_wait(bar_x, 0);
    PT(7, 0);
    if (wg < 2) {
        float d[16];
        pass(d, wg, 0, 0, 32, 0);
        wgmma_wait<0>();
        store32(d, aO + CO_T);
    }
    if (tid == 128) mbar_expect_tx(bar_sc, 1280);
    __syncthreads();
    PT(8, 0);
    cluster_sync_all();
    TS_BEGIN(5);
    PT(9, 0);

    if (wg < 2) {
        const uint32_t aM = pin(sb + CO_XB + 4096 + (lane & 7) * 128 + (((lane >> 3) ^ (lane & 7)) << 4));
        uint32_t coff[8];
#pragma unroll
        for (int i = 0; i < 8; i++) coff[i] = uni(chunk(i) * CH_XC);
        auto mem_proj = [&](int s, int it) {
            const uint32_t par = s & 1;
            float acc[CH_CHAINS][4];
#pragma unroll
            for (int i = 0; i < CH_CHAINS; i++) acc[i][0] = acc[i][1] = acc[i][2] = acc[i][3] = 0.f;
            const uint32_t am = aM + par * CH_XP;
            uint32_t b[CH_LD][4], ok[4] = {1, 1, 1, 1}, a0 = am, a1 = am ^ 64;
            auto load = [&](int i) {
                if (i == 12) DBG(13, 0);
                if (i == 2 || (i && !(i & 3))) { a0 = ok[i >> 2] ? am : aL; a1 = a0 ^ 64; }
                uint32_t* r = b[i % CH_LD];
                ldmatrix_x4(r[0], r[1], r[2], r[3], ((i & 1) ? a1 : a0) + coff[i >> 1]);
                if (i == 1) ok[0] = mbar_try(bar_mem, par ^ 1);
                if (i == 2 || i == 4 || i == 8) ok[(i >> 2) + 1] = mbar_try(bar_mem + 8 * ((i >> 2) + 1), par ^ 1);
            };
            auto mma = [&](int i) {
                mma_16816(acc[(2 * i) % CH_CHAINS], w[2 * i][0], w[2 * i][1], w[2 * i][2], w[2 * i][3], b[i % CH_LD][0], b[i % CH_LD][1]);
                mma_16816(acc[(2 * i + 1) % CH_CHAINS], w[2 * i + 1][0], w[2 * i + 1][1], w[2 * i + 1][2], w[2 * i + 1][3], b[i % CH_LD][2], b[i % CH_LD][3]);
            };
#pragma unroll
            for (int e = 0; e < CH_NSM; e++) ldmatrix_x4_trans(w[e][0], w[e][1], w[e][2], w[e][3], aO + CO_WA + e * 2048);
            asm volatile("{\n.reg .pred p;\nsetp.eq.s32 p, %0, 0;\n@p bar.sync 10, 384;\n}" :: "r"(it) : "memory");
            DBG(11, 0);
            bool done = false;
            load(0); load(1); mma(0); mma(1);
            load(2); load(3); mma(2);
#pragma unroll
            for (int i = 4; i < 3 + CH_LD; i++) load(i);
#pragma unroll
            for (int i = 3; i < 16; i++) {
                mma(i);
                if (i + CH_LD < 16) load(i + CH_LD);
                if (i == 12 - CH_LD) done = __all_sync(0xffffffff, ok[0] & ok[1] & ok[2] & ok[3]);
                if (i == CH_HA) asm volatile("{\n.reg .pred p;\nsetp.ne.b32 p, %0, 0;\n@p bar.arrive 5, 384;\n}" :: "r"((int)done) : "memory");
            }
#pragma unroll
            for (int i = 0; i < 4; i++)
#pragma unroll
                for (int c = 1; c < CH_CHAINS; c++) acc[0][i] += acc[c][i];
            const uint32_t r0 = pack_bf16(acc[0][0], acc[0][1]);
            const uint32_t r1 = pack_bf16(acc[0][2], acc[0][3]);
            DBGD(40 + warp, warp, r0 ^ r1);
            stmatrix_x2_trans(aO + CO_T + 4096, r0, r1);
            fence_async_smem();
            return done;
        };
        if (wg == 0) {
#pragma unroll 1
            for (int s = 0; s < NSEG; s++) {
                const uint32_t par = s & 1;
#pragma unroll 1
                for (int it = 0; it < WAIT_LIMIT / 64; it++) if (mem_proj(s, it)) break;
                asm volatile("bar.arrive 1, 256;" ::: "memory");
                if (s == NSEG - 1) break;
                if (tid == 96) {
#pragma unroll
                    for (int j = 0; j < 4; j++) { mbar_expect_tx(bar_mem + 8 * j, j ? 2048 : 1024); if (j < 3) mbar_expect_tx(bar_o + 8 * j, 1024 << j); }
                }
                __syncwarp();
                uint32_t* wp = g_xbuf + (size_t)rank * 2048 + C * 256 + qc * 64 + t4 * 8 + qd;
                asm volatile("st.relaxed.gpu.global.u32 [%0], %1;" :: "l"(wp + ((s + 2) & 3) * 16384), "r"(~0u) : "memory");
                asm volatile("st.relaxed.gpu.global.u32 [%0], %1;" :: "l"(wp + ((s + 2) & 3) * 16384 + 32), "r"(~0u) : "memory");
                mbar_wait(bar_x + 8 * (par ^ 1), ((s + 1) >> 1) & 1);
                asm volatile("bar.sync 7, 384;" ::: "memory");
                float d[16];
                float c[4];
                const uint32_t alo = desc_lo(sd + CO_WO, 16), blo = desc_lo(sd + CO_OB, 128);
                wgmma_fence();
                pass(d, 0, par ^ 1, 0, CH_Q0, CH_QS, false);
                asm volatile("bar.sync 11, 256;" ::: "memory");
#pragma unroll
                for (int i = 0; i < 32; i++) {
                    if (i == 4) { pass(d, 0, par ^ 1, CH_Q0 + min(4, CH_QI), CH_Q0 + min(4, CH_QI) + CH_QX, CH_QS, false); mbar_wait_cl(bar_o, par); }
                    if (i == 8) mbar_wait_cl(bar_o + 8, par);
                    if (i == CH_OW) mbar_wait_cl(bar_o + 16, par);
                    wgmma_ss_n8(c, alo + i * 128, blo + i * 16, i != 0);
                    if (i < CH_QI) pass(d, 0, par ^ 1, CH_Q0 + i + (i < 4 ? 0 : CH_QX), CH_Q0 + i + (i < 4 ? 0 : CH_QX) + 1, CH_QS, false);
                }
                wgmma_commit();
                wgmma_wait<0>();
                asm volatile("st.relaxed.gpu.global.u32 [%0], %1;" :: "l"(wp + (s & 3) * 16384), "r"(pack_bf16(c[0], c[2])) : "memory");
                asm volatile("st.relaxed.gpu.global.u32 [%0], %1;" :: "l"(wp + (s & 3) * 16384 + 32), "r"(pack_bf16(c[1], c[3])) : "memory");
                asm volatile("bar.arrive 6, 384;" ::: "memory");
                pace(CH_QD);
                asm volatile("bar.arrive 4, 384;" ::: "memory");
                DBG(8, 0);
                pass(d, 0, par ^ 1, CH_Q1, CH_QE, CH_QS);
                DBG(21, 0);
                if (tid == 0 && s + 2 < NSEG) {
                    mbar_expect_tx(bar_x + 8 * par, 32768);
                    tma_load_2d_mc(sb + CO_XB + par * CH_XP + rank * CH_XC, &P.mapX, bar_x + 8 * par, rank * 64, (s + 2) * SEGL, (uint16_t)0xff);
                }
                __syncwarp();
                asm volatile("bar.sync 9, 256;" ::: "memory");
                wgmma_wait<0>();
                DBG(0, 0);
                store32(d, aO + CO_T);
                DBG(22, 0);
            }
        } else {
            const uint32_t usc = uni(CO_SC + min(t4, 2) * 512 + roff((rank ^ 1) - rank)), uscb = uni(bar_sc ^ (1u << 24));
            const uint32_t vaddr = pin(sb + CO_T + 2 * CH_TW + (lane & 15) * 128 + (((t4 * 2 + (lane >> 4)) ^ (lane & 7)) << 4));
            const uint32_t dsta = pin(sb + CO_OB + t4 * 256 + (qc >> 1) * 128 + qd * 16 + (qc & 1) * 8);
            auto local_pv = [&](int s, int st) {
                float dc[16];
                wgmma_fence();
#pragma unroll
                for (int ks = 0; ks < 3; ks++) wgmma_ss_n32_p(dc, desc_lo(sd + CO_T + (2 + (s & 1)) * CH_TW + ks * 2048, 16), desc_lo(sd + CO_P + ks * 256, 128), ks != 0);
                wgmma_commit();
                wgmma_wait<0>();
                store32(dc, aO - CH_TW + st);
            };
            auto store_ctx = [&](int s, int st) {
                if (tid == 128 && s >= 0) {
                    tma_store_2d(&P.mapC, sb + st, (rank & 1) * 64, h * SEQ + s * SEGL);
                    asm volatile("cp.async.bulk.commit_group;" ::: "memory");
                }
                __syncwarp();
            };
            uint32_t uo[8], ub[8];
#pragma unroll
            for (int i = 0; i < 8; i++) { uo[i] = uni(roff(i) + i * 1024); ub[i] = uni(roff(i) + bar_o + (i < 2 ? 0 : i < 4 ? 8 : 16)); }
#pragma unroll 1
            for (int s = 0; s < NSEG; s++) {
                const uint32_t par = s & 1;
#pragma unroll 1
                for (int it = 0; it < WAIT_LIMIT / 64; it++) if (mem_proj(s, it)) break;
                asm volatile("bar.sync 1, 256;" ::: "memory");
                float d[20];
                scores(d, std::integral_constant<int, 0>(), 4096);
                if (s == NSEG - 1) { wgmma_wait<0>(); break; }
                asm volatile("bar.arrive 8, 256;" ::: "memory");
                wgmma_wait<0>();
                {
                    const bool w0 = t4 == 0;
                    asm volatile("{\n.reg .pred p, q;\nsetp.lt.s32 p, %8, 2;\nsetp.eq.s32 q, %8, 2;\n"
                                 "@p st.async.weak.shared::cluster.mbarrier::complete_tx::bytes.v4.f32 [%0], {%2, %3, %4, %5}, [%1];\n"
                                 "@q st.async.weak.shared::cluster.mbarrier::complete_tx::bytes.v2.f32 [%0], {%6, %7}, [%1];\n}"
                                 :: "r"((aL | (s >> 10)) + usc), "r"(uscb), "f"(w0 ? d[0] : d[8]), "f"(w0 ? d[1] : d[9]),
                                    "f"(w0 ? d[4] : d[12]), "f"(w0 ? d[5] : d[13]), "f"(d[16]), "f"(d[17]), "r"(t4) : "memory");
                }
                DBG(3, 4);
                store_ctx(s - 2, CO_ST);
                uint32_t vb[3][4];
                auto load_v = [&]() {
                    asm volatile("bar.sync 3, 256;" ::: "memory");
#pragma unroll
                    for (int k = 0; k < 3; k++) ldmatrix_x4_trans(vb[k][0], vb[k][1], vb[k][2], vb[k][3], vaddr + par * CH_TW + k * 2048);
                };
                mbar_wait_cl(bar_sc, par);
                DBG(4, 4);
                float v[10];
                own_scores(d, v);
                add_scores(aL + CO_SC, aL + CO_SC + 1024, v);
                const float mx = row_max(v);
                if (CH_VPOS == 2) load_v();
#pragma unroll
                for (int j = 0; j < 10; j++) v[j] = ex2f(fmaf(v[j], CH_SC, -mx));
                uint32_t p[5];
#pragma unroll
                for (int j = 0; j < 5; j++) p[j] = pack_bf16(v[2 * j], v[2 * j + 1]);
                if (CH_VPOS == 3) load_v();
                DBG(19, 4);
                float c0[4] = {0.f, 0.f, 0.f, 0.f}, c1[4] = {0.f, 0.f, 0.f, 0.f}, cs[4] = {0.f, 0.f, 0.f, 0.f};
#pragma unroll
                for (int k = 0; k < 3; k++) {
                    const uint32_t p0 = p[2 * k], p1 = k < 2 ? p[2 * k + 1] : 0u;
                    mma_16816(cs, p0, 0u, p1, 0u, 0x3f803f80u, 0x3f803f80u);
                    mma_16816(c0, p0, 0u, p1, 0u, vb[k][0], vb[k][1]);
                    mma_16816(c1, p0, 0u, p1, 0u, vb[k][2], vb[k][3]);
                }
                float inv;
                asm volatile("rcp.approx.ftz.f32 %0, %1;" : "=f"(inv) : "f"(cs[0]));
                const uint32_t b0 = pack_bf16(c0[0] * inv, c0[1] * inv), b1 = pack_bf16(c1[0] * inv, c1[1] * inv);
                DBG(20, 4);
#pragma unroll
                for (int i = 1; i < 8; i++) {
                    st_async_v2((dsta | (s >> 10)) + uo[i], b0, b1, ub[i]);
                    if (i == CH_OS) asm volatile("st.shared.v2.b32 [%0], {%1, %2};" :: "r"(dsta), "r"(b0), "r"(b1) : "memory");
                }
                DBG(5, 4);
                asm volatile("cp.async.bulk.wait_group.read 0;" ::: "memory");
                asm volatile("bar.sync 7, 384;" ::: "memory");
                fence_async_smem();
                asm volatile("bar.arrive 11, 256;" ::: "memory");
                local_pv(s + 1, CO_ST);
                asm volatile("bar.arrive 6, 384;" ::: "memory");
                if (tid == 128) mbar_expect_tx(bar_sc, 1280);
                __syncwarp();
                mbar_wait(bar_x + 8 * (par ^ 1), ((s + 1) >> 1) & 1);
                asm volatile("bar.sync 4, 384;" ::: "memory");
                float dk[16];
                pass(dk, 1, par ^ 1, 0, CH_KE, CH_KS);
                if (tid == 128 && signal_step(s)) {
                    asm volatile("cp.async.bulk.wait_group 0;" ::: "memory");
                    signal_ctx((2 * s - 66) >> 2, s >> 2);
                }
                __syncwarp();
                DBG(1, 4);
                wgmma_wait<0>();
                DBG(2, 4);
                store32(dk, aO + CO_T);
                DBG(29, 4);
            }
            asm volatile("bar.sync 8, 256;" ::: "memory");
            store_ctx(NSEG - 3, CO_ST);
#pragma unroll 1
            for (int i = 0; i < 2; i++) {
                local_pv(i, CO_OB + i * 4096);
                fence_async_smem();
                if (i == 0) asm volatile("bar.arrive 9, 256;" ::: "memory");
                asm volatile("bar.sync 2, 128;" ::: "memory");
                store_ctx(NSEG - 2 + i, CO_OB + i * 4096);
                if (i == 0) asm volatile("bar.sync 3, 256;" ::: "memory");
            }
            if (tid == 128) {
                asm volatile("cp.async.bulk.wait_group 0;" ::: "memory");
                PT(14, 128);
                signal_ctx(15, 16);
                PT(15, 128);
            }
        }
        PT(10, 0);
    } else {
        float gs;
        auto load_gate = [&](int s) { asm volatile("ld.global.cg.f32 %0, [%1];" : "=f"(gs) : "l"(g_gate + s * SEGL + t4 * 8 + qd) : "memory"); };
        auto softmax = [&](int s) {
            float v[10];
            {
                const uint4 a0 = lds128(aL + CO_OWN + t4 * 1024), a1 = lds128(aL + CO_OWN + t4 * 1024 + 512);
                const float2 a2 = lds64f(aL + CO_OWN2 + t4 * 256 - lane * 8);
                v[0] = __uint_as_float(a0.x); v[1] = __uint_as_float(a0.y); v[2] = __uint_as_float(a0.z); v[3] = __uint_as_float(a0.w);
                v[4] = __uint_as_float(a1.x); v[5] = __uint_as_float(a1.y); v[6] = __uint_as_float(a1.z); v[7] = __uint_as_float(a1.w);
                v[8] = a2.x; v[9] = a2.y;
            }
            mbar_wait_cl(bar_l, s & 1);
            add_scores(aL + t4 * 1024 + CO_LS + (s & 1) * 5120, aL + t4 * 256 - lane * 8 + CO_LS + (s & 1) * 5120 + 4096, v);
            const int lim = t4 * 8 + qd - 2 * qc;
#pragma unroll
            for (int j = 0; j < 8; j++) if ((j >> 1) * 8 + (j & 1) > lim) v[j] = -INFINITY;
            const float mx = row_max(v);
#pragma unroll
            for (int j = 0; j < 10; j++) v[j] = ex2f(fmaf(v[j], CH_SC, -mx));
            float sum = (((v[0] + v[1]) + (v[2] + v[3])) + ((v[4] + v[5]) + (v[6] + v[7]))) + (v[8] + v[9]);
            sum += __shfl_xor_sync(0xffffffff, sum, 1);
            sum += __shfl_xor_sync(0xffffffff, sum, 2);
            asm("rcp.approx.ftz.f32 %0, %0;" : "+f"(sum));
            sum *= 1.f - gs;
            const uint32_t pa = aL + CO_P + t4 * 768;
            stmatrix_x4(pa, pack_bf16(v[0] * sum, v[1] * sum), pack_bf16(v[2] * sum, v[3] * sum), pack_bf16(v[4] * sum, v[5] * sum), pack_bf16(v[6] * sum, v[7] * sum));
            asm volatile("stmatrix.sync.aligned.m8n8.x1.shared.b16 [%0], {%1};" :: "r"(pa + 512), "r"(pack_bf16(v[8] * sum, v[9] * sum)) : "memory");
        };
        uint32_t um[8], ub[8];
#pragma unroll
        for (int i = 0; i < 8; i++) { um[i] = uni(roff((i & 1) * 4 + (i >> 1))); ub[i] = uni(roff((i & 1) * 4 + (i >> 1)) + bar_mem + 8 * (i >> 1)); }
        const uint8_t* mkp = smem_raw + CO_BAR + 128;
        asm volatile("" : "+l"(mkp));
        asm volatile("bar.arrive 10, 384;" ::: "memory");
        wait_ctr(CT_GATE, 64u);
        load_gate(0);
#pragma unroll 1
        for (int s = 0; s < NSEG; s++) {
            const uint32_t par = s & 1;
            const bool last = s == NSEG - 1;
            softmax(s - 1);
            load_gate(s);
            DBG(7, 8);
#pragma unroll 1
            for (int it = 0; it < (CH_RF ? WAIT_LIMIT / 64 : 0); it++)
                if (mbar_try(bar_mem, par ^ 1) & mbar_try(bar_mem + 8, par ^ 1) & mbar_try(bar_mem + 16, par ^ 1) & mbar_try(bar_mem + 24, par ^ 1)) break;
            fence_async_smem();
            asm volatile("bar.sync 5, 384;" ::: "memory");
            DBG(23, 8);
            float d[20];
            pass(d, 2, par, 0, CH_VA, CH_VS);
            asm volatile("bar.sync 8, 256;" ::: "memory");
            pass(d, 2, par, CH_VA, 32, CH_VS);
            wgmma_wait<0>();
            stmatrix_x2_trans(aO + par * CH_TW + CO_T + 4096, pack_bf16(d[16], d[17]), pack_bf16(d[18], d[19]));
            store32(d, aO + par * CH_TW + CO_T);
            DBG(24, 8);
            if (!last) asm volatile("bar.arrive 3, 256;\nbar.sync 7, 384;" ::: "memory");
            scores(d, std::integral_constant<int, 512>(), 0);
            asm volatile("{\n.reg .pred p;\nsetp.eq.s32 p, %1, 256;\n@p mbarrier.arrive.expect_tx.shared::cta.b64 _, [%0], 5120;\n}" :: "r"(bar_l), "r"(tid) : "memory");
            wgmma_wait<0>();
            auto send_scores = [&]() {
                const uint32_t a = aL + t4 * 1024, a2 = aL + t4 * 256 - lane * 8, r = roff((rank ^ 1) - rank) + CO_LS + par * 5120;
                asm volatile("st.async.weak.shared::cluster.mbarrier::complete_tx::bytes.v4.f32 [%0], {%3, %4, %5, %6}, [%2];\n"
                             "st.async.weak.shared::cluster.mbarrier::complete_tx::bytes.v4.f32 [%0 + 512], {%7, %8, %9, %10}, [%2];\n"
                             "st.async.weak.shared::cluster.mbarrier::complete_tx::bytes.v2.f32 [%1], {%11, %12}, [%2];"
                             :: "r"(a + r), "r"(a2 + r + 4096), "r"(bar_l ^ (1u << 24)), "f"(d[0]), "f"(d[1]), "f"(d[4]), "f"(d[5]),
                                "f"(d[8]), "f"(d[9]), "f"(d[12]), "f"(d[13]), "f"(d[16]), "f"(d[17]) : "memory");
                sts128(a + CO_OWN, __float_as_uint(d[0]), __float_as_uint(d[1]), __float_as_uint(d[4]), __float_as_uint(d[5]));
                sts128(a + CO_OWN + 512, __float_as_uint(d[8]), __float_as_uint(d[9]), __float_as_uint(d[12]), __float_as_uint(d[13]));
                asm volatile("st.shared.v2.f32 [%0], {%1, %2};" :: "r"(a2 + CO_OWN2), "f"(d[16]), "f"(d[17]) : "memory");
            };
            if (CH_LSS == 0) send_scores();
            if (last) { if (CH_LSS) send_scores(); break; }
            asm volatile("bar.arrive 4, 384;\nbar.arrive 9, 256;\nbar.sync 6, 384;" ::: "memory");
            if (CH_LSS == 1) send_scores();
            const uint2* xb = reinterpret_cast<const uint2*>(g_xbuf + (s & 3) * 16384 + (size_t)rank * 2048 + t4 * 64) + lane;
            uint2 p[8], q[8];
            pace(CH_POLL_DELAY);
#pragma unroll
            for (int k = 0; k < 8; k++)
                asm volatile("ld.relaxed.gpu.global.v2.u32 {%0, %1}, [%2];" : "=r"(p[k].x), "=r"(p[k].y) : "l"(xb + k * 128) : "memory");
            DBG(17, 8);
            if (CH_LSS == 2) send_scores();
            {
                uint32_t z;
                asm volatile("mov.u32 %0, %%clock;" : "=r"(z) :: "memory");
#pragma unroll
                for (int i = 0; i < CH_GAP; i++) asm volatile("mul.lo.u32 %0, %0, %0;" : "+r"(z));
                asm volatile("and.b32 %0, %0, %1;" : "+r"(z) : "r"(s >> 10));
                xb += z;
            }
#pragma unroll
            for (int k = 0; k < 8; k++)
                asm volatile("ld.relaxed.gpu.global.v2.u32 {%0, %1}, [%2];" : "=r"(q[k].x), "=r"(q[k].y) : "l"(xb + k * 128) : "memory");
            uint32_t m0, m1, mk;
            asm volatile("ld.relaxed.gpu.u32 %0, [%1];" : "=r"(mk) : "l"(mkp) : "memory");
            auto sum = [&](const uint2 (&p)[8]) {
                auto lo = [&](uint32_t u) { return __uint_as_float(u * (0u - mk)); };
                auto hi = [&](uint32_t u) { return __uint_as_float(u & mk); };
                const float s0 = ((lo(p[0].x) + lo(p[1].x)) + (lo(p[2].x) + lo(p[3].x))) + ((lo(p[4].x) + lo(p[5].x)) + (lo(p[6].x) + lo(p[7].x)));
                const float s1 = ((lo(p[0].y) + lo(p[1].y)) + (lo(p[2].y) + lo(p[3].y))) + ((lo(p[4].y) + lo(p[5].y)) + (lo(p[6].y) + lo(p[7].y)));
                m0 = pack_bf16(s0, ((hi(p[0].x) + hi(p[1].x)) + (hi(p[2].x) + hi(p[3].x))) + ((hi(p[4].x) + hi(p[5].x)) + (hi(p[6].x) + hi(p[7].x))));
                m1 = pack_bf16(s1, ((hi(p[0].y) + hi(p[1].y)) + (hi(p[2].y) + hi(p[3].y))) + ((hi(p[4].y) + hi(p[5].y)) + (hi(p[6].y) + hi(p[7].y))));
                uint32_t ok;
                asm volatile("{\n.reg .pred p;\nsetp.num.f32 p, %1, %2;\nvote.sync.all.pred p, p, 0xffffffff;\nselp.u32 %0, 1, 0, p;\n}" : "=r"(ok) : "f"(s0), "f"(s1));
                return ok;
            };
            if (!sum(p)) {
                DBG(12, 8);
#pragma unroll 1
                for (int it = 0; it < WAIT_LIMIT / 4; it++) {
                    if (sum(q)) break;
                    uint32_t bad = 0;
#pragma unroll
                    for (int k = 0; k < 8; k++) bad |= (max(q[k].x, q[k].y) == ~0u ? 1u : 0u) << k;
                    if (__all_sync(0xffffffff, bad == 0u)) break;
                    if (it == 0) DBG(14, 8);
                    if (it == 1) DBG(15, 8);
#pragma unroll
                    for (int k = 0; k < 8; k++)
                        if (bad & (1u << k))
                            asm volatile("ld.relaxed.gpu.global.v2.u32 {%0, %1}, [%2];" : "=r"(q[k].x), "=r"(q[k].y) : "l"(xb + k * 128) : "memory");
                }
            }
            DBG(9, 8);
            const int row = t4 * 2 + (lane >> 4);
            const uint32_t dsta = sb + CO_XB + (par ^ 1) * CH_XP + rank * CH_XC + 4096 + row * 128 + ((((lane & 15) >> 1) ^ row) << 4) + (lane & 1) * 8;
#pragma unroll
            for (int i = 1; i < 8; i++) {
                st_async_v2(dsta + um[i], m0, m1, ub[i]);
                if (i == CH_MS) asm volatile("st.shared.v2.b32 [%0], {%1, %2};\nbar.arrive 10, 384;" :: "r"(dsta), "r"(m0), "r"(m1) : "memory");
            }
            if (s == 1000000) {
#pragma unroll
                for (int k = 0; k < 8; k++) asm volatile("st.volatile.shared.v2.u32 [%0], {%1, %2};" :: "r"(s), "r"(q[k].x), "r"(q[k].y) : "memory");
            }
            DBG(10, 8);
        }
        PT(11, 256);
        asm volatile("bar.sync 9, 256;" ::: "memory");
        softmax(NSEG - 1);
        fence_async_smem();
        asm volatile("bar.arrive 3, 256;" ::: "memory");
    }
    __syncthreads();
    cluster_sync_all();
    TS_END(2);
}

struct Proj2Params {
    CUtensorMap mapA[2];
    CUtensorMap mapW[3];
    bf16* out[3];
};
#define P2T(i)
#define P2_NOMMA 0
#define P2_NOLOAD 0
#define P2_ROT 4
#define P2_NP 1
#define P2_NI 4
constexpr int P2_STAGES = 6;
constexpr int P2_ITEMS = 168 + 48;

__device__ __forceinline__ int p2_reps(int t) { return t >= 168 ? 1 : 2; }
__device__ __forceinline__ void p2_tile(int t, int w, int& z, int& mp, int& head) {
    if (t >= 168) { w += ((t - 168) & 1) * 2; t = 168 + ((t - 168) >> 1); }
    const int hq = (t / 24 + P2_ROT) & 7, v = t % 24;
    mp = v & 7;
    if (v < 16) { head = hq * 4 + (v >> 3) * 2 + (w >> 1); z = 1 + (w & 1); }
    else { head = hq * 4 + w; z = 0; }
}
__device__ __forceinline__ void mbar_arrive_remote(uint32_t bar_cluster_addr) {
    asm volatile("mbarrier.arrive.release.cluster.shared::cluster.b64 _, [%0];" :: "r"(bar_cluster_addr) : "memory");
}
__device__ __forceinline__ void mbar_arrive_cl(uint32_t bar_cluster_addr) {
    asm volatile("mbarrier.arrive.shared::cluster.b64 _, [%0];" :: "r"(bar_cluster_addr) : "memory");
}
__device__ __forceinline__ void mbar_wait_acq_cluster(uint32_t bar, uint32_t parity) {
    asm volatile(
        "{\n"
        ".reg .pred p, q;\n"
        ".reg .u32 c;\n"
        "mov.u32 c, 0;\n"
        "WAIT_LOOP_C:\n"
        "mbarrier.try_wait.parity.acquire.cluster.shared::cta.b64 p, [%0], %1;\n"
        "@p bra WAIT_DONE_C;\n"
        "add.u32 c, c, 1;\n"
        "setp.lt.u32 q, c, 4000000;\n"
        "@q bra WAIT_LOOP_C;\n"
        "WAIT_DONE_C:\n"
        "}\n" :: "r"(bar), "r"(parity) : "memory");
}
__device__ __forceinline__ uint4 quad_transpose(uint32_t p0, uint32_t p1, uint32_t p2, uint32_t p3, int lane) {
    const bool o1 = lane & 1, o2 = lane & 2;
    uint32_t s0 = o1 ? p0 : p1, s1 = o1 ? p2 : p3;
    s0 = __shfl_xor_sync(0xffffffff, s0, 1); s1 = __shfl_xor_sync(0xffffffff, s1, 1);
    const uint32_t a_lo = o1 ? s0 : p0, a_hi = o1 ? p1 : s0, b_lo = o1 ? s1 : p2, b_hi = o1 ? p3 : s1;
    uint32_t t0 = o2 ? a_lo : b_lo, t1 = o2 ? a_hi : b_hi;
    t0 = __shfl_xor_sync(0xffffffff, t0, 2); t1 = __shfl_xor_sync(0xffffffff, t1, 2);
    return o2 ? make_uint4(t0, t1, b_lo, b_hi) : make_uint4(a_lo, a_hi, t0, t1);
}
#define P2_PACE 35
#define P2_PACE2 0
template <bool PERM, int PACE = 0>
__device__ __forceinline__ void store_frag_128(const float (&acc)[64], bf16* obase, int lane) {
#pragma unroll
    for (int rr = 0; rr < 2; rr++)
#pragma unroll
        for (int g = 0; g < 4; g++) {
            const float* a = &acc[g * 16 + rr * 2];
            const uint32_t p0 = pack_bf16(a[0], a[1]), p1 = pack_bf16(a[4], a[5]), p2 = pack_bf16(a[8], a[9]), p3 = pack_bf16(a[12], a[13]);
            *reinterpret_cast<uint4*>(obase + (size_t)(rr * 8) * HD + g * 32) = PERM ? make_uint4(p0, p1, p2, p3) : quad_transpose(p0, p1, p2, p3, lane);
            pace(PACE);
        }
}
struct OutParams {
    CUtensorMap mapCtx[2];
    CUtensorMap mapWo[2];
    CUtensorMap mapOut;
};

#define OT(i)
#define OTP(i, th)
constexpr int O2_STAGES = 4;
#define O2_NL 16
constexpr int O2_GRID = 4 * O2_NL;
#define O2_FINE 8

constexpr uint32_t OB_FULL = 0, OB_EMPTY = 32, OB_ITEM = 64, OB_SLOT = 128, OB_STOP = 160;
__device__ __forceinline__ void out_init(uint32_t bars) {
    for (int i = 0; i < O2_STAGES; i++) {
        mbar_init(bars + OB_FULL + 8 * i, 1); mbar_init(bars + OB_EMPTY + 8 * i, 4); mbar_init(bars + OB_ITEM + 16 * i, 1); mbar_init(bars + OB_ITEM + 16 * i + 8, 1);
    }
    sts128(bars + OB_STOP, 0u, 0u, 0u, 0u);
}
__device__ __forceinline__ void out_map(int cid, int& pt, int& h0) {
    if (cid < 32) { pt = cid < 16 ? cid : 31 - cid; h0 = cid >= 16; }
    else if (cid < 34) { pt = 12 + (cid & 1); h0 = 2; }
    else { pt = 14 + (cid & 1); h0 = 63 - ((cid - 34) >> 1); }
}
__device__ __forceinline__ void out_finished() {
    if (atomicAdd(&g_ctr[CT_FIN], 1u) == M_GRID + O2_GRID - 1)
        for (int i = 0; i < CT_N / 4; i++) reinterpret_cast<uint4*>(g_ctr)[i] = make_uint4(0u, 0u, 0u, 0u);
}
__device__ __forceinline__ void out_producer(const OutParams& P, uint32_t sbase, uint32_t bars, uint32_t rank, int pt, int h0, bool lead, bool LATE, int tnext) {
    const uint32_t bar_full = bars + OB_FULL, bar_empty = bars + OB_EMPTY, bar_item = bars + OB_ITEM, slot = bars + OB_SLOT, stop = bars + OB_STOP;
    const int ne = (pt >> 1) == 6 ? 3 : 2, nh = pt >= 14 ? 64 - O2_NL : 64;
    const int mt = (pt >> 1) * 2 + (int)rank, m0 = mt * 128, n0 = (pt & 1) * 256;
    int s = 0, ready = LATE ? 16 : 0, q = h0 * 2, qe = q + 2; uint32_t ph = LATE;
    for (int ic = 0;; ic++) {
        if (lead && rank == 0) {
            const int t = tnext + ne;
            asm volatile("st.shared.s32 [%0], %1;" :: "r"(slot + (ic & 7) * 4), "r"(t) : "memory");
            mbar_arrive(bar_item + 8 * (ic & 7));
            st_async_b32(mapa_u32(slot + (ic & 7) * 4, 1), (uint32_t)t, mapa_u32(bar_item + 8 * (ic & 7), 1));
            if (t < nh + O2_FINE) tnext = take_ticket(CT_OT + pt);
        }
#pragma unroll 1
        for (; q < qe; q++) {
            const int b = q >> 6, head = (q >> 1) & 31, dk = (q & 1) * 64;
            mbar_wait(bar_empty + 8 * s, ph);
            const uint32_t sa = sbase + s * 49152;
            if (lead) {
                const int f = b ? 4 : head >> 3;
                if (!((ready >> f) & 1)) {
                    if (b && !(ready & 8)) { wait_ctr(CT_CA + mt * 4 + 3, 16u); ready |= 8; }
                    wait_ctr(b ? CT_CB + mt : CT_CA + mt * 4 + f, b ? 64u : 16u); ready |= 1 << f;
                }
                if (!LATE || ic > 0) {
                    mbar_expect_tx(bar_full + 8 * s, 49152);
                    tma_load_2d(sa, &P.mapCtx[b], bar_full + 8 * s, dk, head * SEQ + m0);
                }
            } else {
                for (int j = (int)rank * 2; j < (int)rank * 2 + 2; j++)
                    tma_load_2d_mc(sa + 16384 + j * 8192, &P.mapWo[b], bar_full + 8 * s, n0 + j * 64, head * HD + dk, (uint16_t)3);
            }
            if (++s == O2_STAGES) { s = 0; ph ^= 1; }
        }
        if (lead && rank == 1) mbar_expect_tx(bar_item + 8 * (ic & 7), 4);
        mbar_wait(bar_item + 8 * (ic & 7), (ic >> 3) & 1);
        int t;
        asm volatile("ld.shared.s32 %0, [%1];" : "=r"(t) : "r"(slot + (ic & 7) * 4) : "memory");
        if (t >= nh + O2_FINE) break;
        if (t < nh - O2_FINE) { q = 2 * t; qe = q + 2; } else { q = nh - O2_FINE + t; qe = q + 1; }
    }
    if (lead) {
        asm volatile("prefetch.tensormap [%0];" :: "l"(&P.mapOut) : "memory");
        if (!(ready & 8)) wait_ctr(CT_CA + mt * 4 + 3, 16u);
        mbar_wait(bar_empty + 8 * s, ph);
        asm volatile("st.shared.s32 [%0], %1;" :: "r"(stop + s * 4), "r"(1) : "memory");
        mbar_arrive(bar_full + 8 * s);
        out_finished();
        for (int i = 1; i < O2_STAGES; i++) {
            if (++s == O2_STAGES) { s = 0; ph ^= 1; }
            mbar_wait(bar_empty + 8 * s, ph);
        }
    }
}
__device__ __forceinline__ void out_consumer(const OutParams& P, uint32_t sbase, uint32_t bars, uint32_t rank, int pt, int warp) {
    const uint32_t bar_full = bars + OB_FULL, bar_empty = bars + OB_EMPTY, stop = bars + OB_STOP;
    const int m0 = ((pt >> 1) * 2 + (int)rank) * 128, n0 = (pt & 1) * 256;
    const int wg = warp >> 2, lane = threadIdx.x & 31;
    const bool elected = (threadIdx.x & 127) == 0;
    float acc[128];
#pragma unroll
    for (int i = 0; i < 128; i++) acc[i] = 0.f;
    int s = 0, sprev = 0; uint32_t ph = 0;
#pragma unroll 1
    for (int i = 0;; i++) {
        mbar_wait(bar_full + 8 * s, ph);
        int st;
        asm volatile("ld.shared.s32 %0, [%1];" : "=r"(st) : "r"(stop + s * 4) : "memory");
        if (st) break;
        if (i == 0) OT(1);
        const uint32_t sa = sbase + s * 49152 + wg * 8192, sb = sbase + s * 49152 + 16384;
        wgmma_fence();
#pragma unroll
        for (int kk = 0; kk < 4; kk++)
            wgmma_ss_n256_tb(acc, make_desc(sa + kk * 32, 16, 1024), make_desc(sb + kk * 2048, 8192, 1024), 1);
        wgmma_commit();
        if (i > 0) {
            wgmma_wait<1>();
            if (elected) { const uint32_t e = bar_empty + 8 * sprev; mbar_arrive_cl(mapa_u32(e, 0)); mbar_arrive_cl(mapa_u32(e, 1)); }
        }
        sprev = s;
        if (++s == O2_STAGES) { s = 0; ph ^= 1; }
    }
    wgmma_wait<0>();
    if (elected) { const uint32_t e = bar_empty + 8 * sprev; mbar_arrive_cl(mapa_u32(e, 0)); mbar_arrive_cl(mapa_u32(e, 1)); }
    asm volatile("bar.sync %0, 128;" :: "r"(1 + wg) : "memory");
    OT(3);
    const int row = (lane & 7) + ((lane >> 3) & 1) * 8;
#pragma unroll
    for (int bx = 0; bx < 4; bx++) {
        const uint32_t stg = sbase + bx * 49152 + warp * 2048;
#pragma unroll
        for (int j = 0; j < 8; j += 2) {
            const float* a = &acc[bx * 32 + j * 4];
            stmatrix_x4(stg + row * 128 + (((j + (lane >> 4)) ^ (row & 7)) << 4), pack_bf16(a[0], a[1]), pack_bf16(a[2], a[3]), pack_bf16(a[4], a[5]), pack_bf16(a[6], a[7]));
        }
        asm volatile("fence.proxy.async.shared::cta;" ::: "memory");
        __syncwarp();
        if (lane == 0)
            asm volatile("cp.reduce.async.bulk.tensor.2d.global.shared::cta.add.tile.bulk_group [%0, {%2, %3}], [%1];"
                         :: "l"((uint64_t)&P.mapOut), "r"(stg), "r"(n0 + bx * 64), "r"(m0 + warp * 16) : "memory");
    }
    OT(4);
    if (lane == 0) {
        asm volatile("cp.async.bulk.commit_group;" ::: "memory");
        asm volatile("cp.async.bulk.wait_group.read 0;" ::: "memory");
    }
}

constexpr int O2_SMEM = O2_STAGES * 49152 + 1024 + 256;
__global__ void __cluster_dims__(2, 1, 1) __launch_bounds__(320, 1)
out2_kernel(const __grid_constant__ OutParams P) {
    extern __shared__ uint8_t smem_raw[];
    const uint32_t sbase = (smem_u32(smem_raw) + 1023) & ~1023u;
    const uint32_t bars = sbase + O2_STAGES * 49152;
    const int warp = threadIdx.x >> 5, lane = threadIdx.x & 31;
    const uint32_t rank = cluster_ctarank();
    int pt, h0;
    out_map(M_GRID / 2 + (blockIdx.x >> 1), pt, h0);
    const int mt = (pt >> 1) * 2 + (int)rank;
    TS_BEGIN(4);
    OT(0);
    int tnext = 0;
    if (threadIdx.x == 256) {
        if (rank == 0) tnext = take_ticket(CT_OT + pt);
        out_init(bars);
        asm volatile("fence.mbarrier_init.release.cluster;" ::: "memory");
    }
    __syncwarp();
    asm volatile("barrier.cluster.arrive.relaxed.aligned;" ::: "memory");
    if (threadIdx.x == 256) {
        asm volatile("prefetch.tensormap [%0];" :: "l"(&P.mapCtx[1]) : "memory");
        wait_ctr(CT_CB + mt, 64u);
        for (int i = 0; i < 2; i++) {
            mbar_expect_tx(bars + OB_FULL + 8 * i, 49152);
            tma_load_2d(sbase + i * 49152, &P.mapCtx[1], bars + OB_FULL + 8 * i, i * 64, (h0 & 31) * SEQ + mt * 128);
        }
    }
    if (threadIdx.x == 288) asm volatile("prefetch.tensormap [%0];" :: "l"(&P.mapWo[1]) : "memory");
    __syncwarp();
    asm volatile("barrier.cluster.wait.aligned;" ::: "memory");
    if (warp >= 8) {
        if (lane == 0) out_producer(P, sbase, bars, rank, pt, h0, warp == 8, true, tnext);
    } else {
        out_consumer(P, sbase, bars, rank, pt, warp);
        TS_END(4);
    }
}

struct MainParams { Proj2Params p; AttnParams a; OutParams o; };
__device__ __forceinline__ int p2_apos(int k) { return k < 2 ? k : k < 6 ? k + 2 : k - 4; }
__global__ void __cluster_dims__(2, 1, 1) __launch_bounds__(384, 1) main_kernel(const __grid_constant__ MainParams MP) {
    const Proj2Params& P = MP.p;
    extern __shared__ uint8_t smem_raw[];
    const uint32_t rank = cluster_ctarank();
    const uint32_t sbase = (rank << 24) + SD;
    if (smem_u32(smem_raw) != sbase) __trap();
    const uint32_t sA = sbase, sB = sbase + 131072;
    const uint32_t bars = sbase + MO_BAR, obars = bars + 768;
    const uint32_t a_full = bars, a_empty = bars + 64, b_full = bars + 128, b_empty = b_full + 8 * P2_STAGES;
    const uint32_t item_bar = b_empty + 8 * P2_STAGES, item_in = item_bar + 16, slot = item_in + 16;
    const uint32_t note_bar = slot + 16, note_free = note_bar + 64, note = note_free + 64;
    const int warp = __shfl_sync(0xffffffff, threadIdx.x >> 5, 0), lane = threadIdx.x & 31;
    int pt, h0;
    out_map(blockIdx.x >> 1, pt, h0);
    TS_BEGIN(0);
    if (threadIdx.x == 0) {
        for (int i = 0; i < 8; i++) { mbar_init(a_full + 8 * i, 1); mbar_init(a_empty + 8 * i, 2); }
        for (int i = 0; i < P2_STAGES; i++) { mbar_init(b_full + 8 * i, 1); mbar_init(b_empty + 8 * i, 2); }
        mbar_init(item_bar, 1); mbar_init(item_bar + 8, 1); mbar_init(item_in, 2); mbar_init(item_in + 8, 2);
        for (int i = 0; i < 8; i++) { mbar_init(note_bar + 8 * i, 1); mbar_init(note_free + 8 * i, 1); }
        asm volatile("fence.mbarrier_init.release.cluster;" ::: "memory");
    }
    if (threadIdx.x == 32) {
        attn_init(sbase);
        asm volatile("fence.mbarrier_init.release.cluster;" ::: "memory");
    }
    if (threadIdx.x == 256) {
        out_init(obars);
        asm volatile("fence.mbarrier_init.release.cluster;" ::: "memory");
    }
    __syncthreads();
    asm volatile("barrier.cluster.arrive.relaxed.aligned;" ::: "memory");
    pdl_launch_dependents();
    if (warp >= 8) {
    asm volatile("setmaxnreg.dec.sync.aligned.u32 40;");
    asm volatile("barrier.cluster.wait.aligned;" ::: "memory");
    if (warp == 9) {
        if (lane == 0) {
            for (int n = 0;; n++) {
                const int e = (n & 1) * 4 + ((n >> 1) & 3);
                mbar_wait(note_bar + 8 * e, (n >> 3) & 1);
                int m;
                asm volatile("ld.shared.s32 %0, [%1];" : "=r"(m) : "r"(note + e * 4) : "memory");
                mbar_arrive(note_free + 8 * e);
                if (m < 0) break;
                signal_ctr(m);
            }
            attn_helper(MP.a, sbase, 0);
        }
    } else if (warp == 10) {
        if (lane == 0) {
            auto publish = [&](int ic, int tq) {
                const int t = tq < P2_ITEMS ? tq : -1;
                asm volatile("st.shared.s32 [%0], %1;" :: "r"(slot + (ic & 3) * 4), "r"(t) : "memory");
                mbar_arrive(item_bar + 8 * (ic & 1));
                st_async_b32(mapa_u32(slot + (ic & 3) * 4, 1), (uint32_t)t, mapa_u32(item_bar + 8 * (ic & 1), 1));
            };
            const int npair = M_GRID / 2, pair = (int)(blockIdx.x >> 1);
            if (rank == 0) publish(0, pair);
            for (int ic = 0;; ic++) {
                if (rank == 1) mbar_expect_tx(item_bar + 8 * (ic & 1), 4);
                mbar_wait(item_bar + 8 * (ic & 1), (ic >> 1) & 1);
                int t;
                asm volatile("ld.shared.s32 %0, [%1];" : "=r"(t) : "r"(slot + (ic & 3) * 4) : "memory");
                if (t < 0) break;
                int z0, mp, h0;
                p2_tile(t, 0, z0, mp, h0);
                const int aidx = z0 >= 1 ? 1 : 0;
                const int m0 = (2 * mp + (int)rank) * 128;
                for (int k = 0; k < 8; k++) {
                    mbar_wait(a_empty + 8 * k, (ic & 1) ^ 1);
                    if (P2_NOLOAD) mbar_arrive(a_full + 8 * k); else {
                    mbar_expect_tx(a_full + 8 * k, 16384);
                    tma_load_2d(sA + p2_apos(k) * 16384, &P.mapA[aidx], a_full + 8 * k, k * 64, m0); }
                }
                if (rank == 0) {
                    mbar_wait(item_in + 8 * (ic & 1), (ic >> 1) & 1);
                    publish(ic + 1, ic == 0 ? npair + pair : pair < P2_NP && ic + 1 >= P2_NI ? P2_ITEMS : 2 * npair + (int)atomicAdd(&g_ctr[CT_PROJ], 1u));
                }
            }
            attn_helper(MP.a, sbase, 1);
        }
    } else {
        if (lane == 0) {
            const int par2 = warp == 8 ? 0 : 1;
            int it = 0, ic = 0; uint32_t bph = 0;
            for (;; ic++) {
                mbar_wait(item_bar + 8 * (ic & 1), (ic >> 1) & 1);
                int t;
                asm volatile("ld.shared.s32 %0, [%1];" : "=r"(t) : "r"(slot + (ic & 3) * 4) : "memory");
                if (t < 0) break;
                const int nt = 2 * p2_reps(t);
                for (int w = 0; w < nt; w++) {
                    int z, mp, hd;
                    p2_tile(t, w, z, mp, hd);
                    for (int k = 0; k < 8; k++) {
                        const int s = it; const uint32_t phb = bph;
                        if (++it == P2_STAGES) { it = 0; bph ^= 1; }
                        if ((k & 1) != par2) continue;
                        mbar_wait(b_empty + 8 * s, phb ^ 1);
                        if (P2_NOLOAD) { mbar_arrive(b_full + 8 * s); continue; }
                        mbar_expect_tx(b_full + 8 * s, 16384);
                        tma_load_2d_mc(sB + s * 16384 + rank * 8192, &P.mapW[z], b_full + 8 * s, hd * 128 + (int)rank * 64, k * 64, (uint16_t)3);
                    }
                }
            }
            int tnext = 0;
            if (warp == 8) {
                attn_producer(MP.a, sbase, a_empty, ~ic & 1);
                TS_END2(1, 256); TS_BEGIN2(3, 256);
                if (rank == 0) tnext = take_ticket(CT_OT + pt);
                for (int i = 0; i < 4; i++) {
                    const uint32_t e = mapa_u32(obars + OB_EMPTY + 8 * (i & 1), i >> 1);
                    mbar_arrive_cl(e); mbar_arrive_cl(e);
                }
            }
            out_producer(MP.o, sbase, obars, rank, pt, h0, warp == 8, false, tnext);
            TS_END2(3, 256);
        }
    }
    } else {
        asm volatile("setmaxnreg.inc.sync.aligned.u32 232;");
        asm volatile("barrier.cluster.wait.aligned;" ::: "memory");
        const int wg = warp >> 2;
        float acc[2][64];
        const uint32_t a_lo = desc_lo(SD, 16), b_lo0 = desc_lo(SD + 131072, 8192);
        const bool elected = (threadIdx.x & 127) == 0;
        int s = (wg * 8) % P2_STAGES;
        uint32_t ph = ((wg * 8) / P2_STAGES) & 1;
        int nnote = 0;
        if (wg == 1) asm volatile("bar.arrive 3, 256;" ::: "memory");
        for (int ic = 0;; ic++) {
            mbar_wait(item_bar + 8 * (ic & 1), (ic >> 1) & 1);
            int t;
            asm volatile("ld.shared.s32 %0, [%1];" : "=r"(t) : "r"(slot + (ic & 3) * 4) : "memory");
            t = __shfl_sync(0xffffffff, t, 0);
            P2T(7);
            if (wg == 0 && t < 0) {
                if (elected) {
                    const int e = nnote & 3;
                    mbar_wait(note_free + 8 * e, ((nnote >> 2) & 1) ^ 1);
                    asm volatile("st.shared.s32 [%0], %1;" :: "r"(note + e * 4), "r"(-1) : "memory");
                    mbar_arrive(note_bar + 8 * e);
                }
            }
            if (t < 0) break;
            const int reps = p2_reps(t);
#pragma unroll 1
            for (int rp = 0; rp < reps; rp++) {
            const bool first = rp == 0, last = rp == reps - 1;
            int z, mp, head;
            p2_tile(t, rp * 2 + wg, z, mp, head);
            asm volatile("bar.sync %0, 256;" :: "r"(3 + wg) : "memory");
            P2T(0);
            if (wg == 1 && last && elected) mbar_arrive_cl(mapa_u32(item_in + 8 * (ic & 1), 0));
            int sprev = 0;
#pragma unroll
            for (int k = 0; k < 8; k++) {
                if (k == 0) P2T(5);
                if (wg == 0 && first) mbar_wait(a_full + 8 * k, ic & 1);
                if (k == 0) P2T(6);
                mbar_wait(b_full + 8 * s, ph);
                if (k == 7) asm volatile("bar.arrive %0, 256;" :: "r"(4 - wg) : "memory");
                if (k == 0) P2T(1);
                if (k == 7) P2T(2);
                const uint32_t b_lo = b_lo0 + s * 1024;
                wgmma_fence();
#pragma unroll
                for (int kk = 0; kk < (P2_NOMMA ? 1 : 4); kk++) {
                    wgmma_ss_n128_lo<1>(acc[0], a_lo + p2_apos(k) * 1024 + kk * 2, b_lo + kk * 128, (k | kk) != 0);
                    wgmma_ss_n128_lo<1>(acc[1], a_lo + p2_apos(k) * 1024 + 512 + kk * 2, b_lo + kk * 128, (k | kk) != 0);
                }
                wgmma_commit();
                if (k > 0) {
                    wgmma_wait<1>();
                    if (elected) {
                        const uint32_t e = b_empty + 8 * sprev;
                        mbar_arrive_cl(mapa_u32(e, 0)); mbar_arrive_cl(mapa_u32(e, 1));
                        if (last) mbar_arrive(a_empty + 8 * (k - 1));
                    }
                }
                sprev = s;
                if (++s == P2_STAGES) { s = 0; ph ^= 1; }
            }
            wgmma_wait<0>();
            P2T(3);
            if (elected) {
                const uint32_t e = b_empty + 8 * sprev;
                mbar_arrive_cl(mapa_u32(e, 0)); mbar_arrive_cl(mapa_u32(e, 1));
                if (last) mbar_arrive(a_empty + 8 * 7);
            }
            s += 8 % P2_STAGES; ph ^= (8 / P2_STAGES) & 1;
            if (s >= P2_STAGES) { s -= P2_STAGES; ph ^= 1; }
            const int m0 = (2 * mp + (int)rank) * 128;
            bf16* obase = P.out[z] + ((size_t)head * SEQ + m0 + (warp & 3) * 16 + (lane >> 2)) * HD + (lane & 3) * 8;
            store_frag_128<true, P2_PACE>(acc[0], obase, lane); store_frag_128<true, P2_PACE>(acc[1], obase + (size_t)64 * HD, lane);
            P2T(4);
            {
                asm volatile("bar.sync %0, 128;" :: "r"(1 + wg) : "memory");
                if (elected) {
                    const int e = wg * 4 + (nnote & 3);
                    mbar_wait(note_free + 8 * e, ((nnote >> 2) & 1) ^ 1);
                    asm volatile("st.shared.s32 [%0], %1;" :: "r"(note + e * 4), "r"(CT_AP + (head >> 1)) : "memory");
                    mbar_arrive(note_bar + 8 * e);
                }
                nnote++;
            }
            }
        }
        auto done = [&]() {
            if ((threadIdx.x & 127) == 0) for (int i = 0; i < 4; i++) mbar_arrive_cl(SD + MO_BAR + 768 + OB_EMPTY + 16 + 8 * (i & 1) + ((i >> 1) << 24));
        };
        asm volatile("bar.sync %0, 128;" :: "r"(1 + wg) : "memory");
        if (rank == 0) attn_consumer<SD>(MP.a, warp, done); else attn_consumer<SD + (1u << 24)>(MP.a, warp, done);
        OT(0);
        {
            const uint32_t rank2 = cluster_ctarank(), sb2 = (rank2 << 24) + SD;
            int cid;
            asm volatile("mov.u32 %0, %%clusterid.x;" : "=r"(cid));
            out_map(cid, pt, h0);
            out_consumer(MP.o, sb2, sb2 + MO_BAR + 768, rank2, pt, warp);
        }
    }
}

typedef CUresult (*PFN_encodeTiled)(CUtensorMap*, CUtensorMapDataType, cuuint32_t, void*, const cuuint64_t*,
                                    const cuuint64_t*, const cuuint32_t*, const cuuint32_t*, CUtensorMapInterleave,
                                    CUtensorMapSwizzle, CUtensorMapL2promotion, CUtensorMapFloatOOBfill);
static PFN_encodeTiled g_encode = nullptr;

static void make_map(CUtensorMap* m, const void* ptr, uint64_t rows, uint64_t cols, uint32_t box_rows, bool sw64 = false) {
    cuuint64_t dims[2] = {cols, rows};
    cuuint64_t strides[1] = {cols * 2};
    cuuint32_t box[2] = {sw64 ? 32u : 64u, box_rows};
    cuuint32_t es[2] = {1, 1};
    g_encode(m, CU_TENSOR_MAP_DATA_TYPE_BFLOAT16, 2, const_cast<void*>(ptr), dims, strides, box, es,
             CU_TENSOR_MAP_INTERLEAVE_NONE, sw64 ? CU_TENSOR_MAP_SWIZZLE_64B : CU_TENSOR_MAP_SWIZZLE_128B, CU_TENSOR_MAP_L2_PROMOTION_L2_256B,
             CU_TENSOR_MAP_FLOAT_OOB_FILL_NONE);
}

template <typename... KArgs, typename... Args>
static void launch_pdl(void (*kernel)(KArgs...), int grid, int block, size_t smem, cudaStream_t st, bool pdl, Args... args) {
    cudaLaunchConfig_t cfg = {};
    cfg.gridDim = dim3(grid); cfg.blockDim = dim3(block); cfg.dynamicSmemBytes = smem; cfg.stream = st;
    cudaLaunchAttribute at[1];
    at[0].id = cudaLaunchAttributeProgrammaticStreamSerialization;
    at[0].val.programmaticStreamSerializationAllowed = 1;
    cfg.attrs = at; cfg.numAttrs = pdl ? 1 : 0;
    cudaLaunchKernelEx(&cfg, kernel, KArgs(args)...);
}

extern "C" void kernel_launch(void* const* d_in, const int* in_sizes, int n_in, void* d_out, int out_size) {
    const bf16* x = (const bf16*)d_in[0];
    const bf16* ckv = (const bf16*)d_in[1];
    const bf16* wq = (const bf16*)d_in[2];
    const bf16* wuk = (const bf16*)d_in[3];
    const bf16* wuv = (const bf16*)d_in[4];
    const bf16* wo = (const bf16*)d_in[5];
    const bf16* mem0 = (const bf16*)d_in[7];
    const bf16* Wq = (const bf16*)d_in[8];
    const bf16* Wk = (const bf16*)d_in[9];
    const bf16* Wv = (const bf16*)d_in[10];
    const bf16* Wo = (const bf16*)d_in[11];
    const bf16* gate_w = (const bf16*)d_in[13];
    bf16* out = (bf16*)d_out;

    static MainParams MP;
    static ChainParams CP;
    Proj2Params& P2 = MP.p;
    AttnParams& AP = MP.a;
    OutParams& OP = MP.o;
    static bool init = false;
    static const void* last_in[14];
    static const void* last_out;
    bool same = init && last_out == d_out;
    for (int i = 0; i < 14 && same; i++) same = last_in[i] == d_in[i];
    if (!init) {
        cudaDriverEntryPointQueryResult qr;
        cudaGetDriverEntryPoint("cuTensorMapEncodeTiled", (void**)&g_encode, cudaEnableDefault, &qr);
        cudaFuncSetAttribute(main_kernel, cudaFuncAttributeMaxDynamicSharedMemorySize, M_SMEM);
        cudaFuncSetAttribute(out2_kernel, cudaFuncAttributeMaxDynamicSharedMemorySize, O2_SMEM);
        cudaFuncSetAttribute(chain_kernel, cudaFuncAttributeMaxDynamicSharedMemorySize, CH_SMEM);
        init = true;
    }
    if (!same) {
        for (int i = 0; i < 14; i++) last_in[i] = d_in[i];
        last_out = d_out;
        void *pQA, *pKA, *pVA, *pCA, *pCB;
        cudaGetSymbolAddress(&pQA, g_QA); cudaGetSymbolAddress(&pKA, g_KA); cudaGetSymbolAddress(&pVA, g_VA);
        cudaGetSymbolAddress(&pCA, g_ctxA); cudaGetSymbolAddress(&pCB, g_ctxB);
        make_map(&P2.mapA[0], x, SEQ, DM, 128);
        make_map(&P2.mapA[1], ckv, SEQ, DM, 128);
        const void* ws[3] = {wq, wuk, wuv};
        void* cs[3] = {pQA, pKA, pVA};
        for (int i = 0; i < 3; i++) { make_map(&P2.mapW[i], ws[i], DM, NQ, 64); P2.out[i] = (bf16*)cs[i]; }
        make_map(&CP.mapW[0], Wq, DM, NQ, 64); make_map(&CP.mapW[1], Wk, DM, NQ, 64); make_map(&CP.mapW[2], Wv, DM, NQ, 64);
        make_map(&CP.mapX, x, SEQ, DM, 32);
        make_map(&CP.mapC, pCB, NH * SEQ, HD, 32);
        make_map(&AP.mapQ, pQA, NH * SEQ, HD, 128);
        make_map(&AP.mapK, pKA, NH * SEQ, HD, 128);
        make_map(&AP.mapV, pVA, NH * SEQ, HD, 128);
        make_map(&AP.mapO, pCA, NH * SEQ, HD, 64);
        make_map(&OP.mapCtx[0], pCA, NH * SEQ, HD, 128);
        make_map(&OP.mapCtx[1], pCB, NH * SEQ, HD, 128);
        make_map(&OP.mapWo[0], wo, NQ, DM, 64);
        make_map(&OP.mapWo[1], Wo, NQ, DM, 64);
        make_map(&OP.mapOut, out, SEQ, DM, 16);
        AP.out = out;
    }
    cudaStream_t s1 = cudaStreamPerThread;
    const bool pdl = true;
    launch_pdl(chain_kernel, 64, CH_BLOCK, CH_SMEM, s1, false, CP, mem0, Wo, x, gate_w);
    launch_pdl(main_kernel, M_GRID, 384, M_SMEM, s1, pdl, MP);
    launch_pdl(out2_kernel, O2_GRID, 320, O2_SMEM, s1, pdl, OP);
}
```

```cpp
#include <cuda_runtime.h>
#include <cuda_bf16.h>
#include <cuda.h>
#include <stdint.h>
#include <type_traits>

constexpr int SEQ = 2048;
constexpr int DM = 512;
constexpr int NH = 32;
constexpr int HD = 128;
constexpr int NQ = NH * HD;
constexpr int SEGL = 32;
constexpr int NMEM = 8;
constexpr int NSEG = SEQ / SEGL;

typedef __nv_bfloat16 bf16;

__device__ bf16 g_QA[SEQ * NQ];
__device__ bf16 g_KA[SEQ * NQ];
__device__ bf16 g_VA[SEQ * NQ];
__device__ bf16 g_ctxA[SEQ * NQ];
__device__ bf16 g_ctxB[SEQ * NQ];
constexpr int CT_PROJ = 0, CT_ATTN = 1, CT_FIN = 5;
constexpr int CT_AP = 64;
constexpr int CT_GATE = 96;
constexpr int CT_CA = 128;
constexpr int CT_CB = 192;
constexpr int CT_OT = 208;
constexpr int CT_N = 224;
__device__ __align__(16) unsigned int g_ctr[CT_N];
__device__ float g_gate[SEQ];
#define XB8(v) v, v, v, v, v, v, v, v
__device__ uint32_t g_xbuf[4 * 8 * 2048] = {XB8(XB8(XB8(XB8(XB8(~0u)))))};

#define FA_GRID 68

#define TS_BEGIN(id)
#define TS_END(id)
#define TS_BEGIN2(id, th)
#define TS_END2(id, th)
#define WAIT_LIMIT 200000
__device__ __forceinline__ void pdl_launch_dependents() { asm volatile("griddepcontrol.launch_dependents;" ::: "memory"); }
__device__ __forceinline__ void wait_ctr(int idx, unsigned int n) {
    unsigned int v; int it = 0;
    do { asm volatile("ld.acquire.gpu.global.u32 %0, [%1];" : "=r"(v) : "l"(&g_ctr[idx]) : "memory"); } while (v < n && ++it < WAIT_LIMIT);
    asm volatile("fence.proxy.async.shared::cta;" ::: "memory");
}
__device__ __forceinline__ int take_ticket(int idx) {
    int v;
    asm volatile("atom.relaxed.gpu.global.inc.u32 %0, [%1], 0x7fffffff;" : "=r"(v) : "l"(&g_ctr[idx]) : "memory");
    return v;
}
__device__ __forceinline__ void signal_ctr(int idx) {
    asm volatile("fence.proxy.async;" ::: "memory");
    __threadfence();
    atomicAdd(&g_ctr[idx], 1u);
}
__device__ __forceinline__ void signal_ctr_generic(int idx) {
    asm volatile("red.release.gpu.global.add.u32 [%0], 1;" :: "l"(&g_ctr[idx]) : "memory");
}
__device__ __forceinline__ uint32_t smem_u32(const void* p) {
    return (uint32_t)__cvta_generic_to_shared(p);
}
__device__ __forceinline__ void mbar_init(uint32_t bar, uint32_t count) {
    asm volatile("mbarrier.init.shared::cta.b64 [%0], %1;" :: "r"(bar), "r"(count));
}
__device__ __forceinline__ void mbar_expect_tx(uint32_t bar, uint32_t bytes) {
    asm volatile("mbarrier.arrive.expect_tx.shared::cta.b64 _, [%0], %1;" :: "r"(bar), "r"(bytes) : "memory");
}
__device__ __forceinline__ void mbar_arrive(uint32_t bar) {
    asm volatile("mbarrier.arrive.shared::cta.b64 _, [%0];" :: "r"(bar) : "memory");
}
__device__ __forceinline__ void mbar_wait(uint32_t bar, uint32_t parity) {
    asm volatile(
        "{\n"
        ".reg .pred p, q;\n"
        ".reg .u32 c;\n"
        "mov.u32 c, 0;\n"
        "WAIT_LOOP:\n"
        "mbarrier.try_wait.parity.shared::cta.b64 p, [%0], %1;\n"
        "@p bra WAIT_DONE;\n"
        "add.u32 c, c, 1;\n"
        "setp.lt.u32 q, c, %2;\n"
        "@q bra WAIT_LOOP;\n"
        "WAIT_DONE:\n"
        "}\n" :: "r"(bar), "r"(parity), "n"(WAIT_LIMIT) : "memory");
}
__device__ __forceinline__ uint32_t mbar_test(uint32_t bar, uint32_t parity) {
    uint32_t done;
    asm volatile(
        "{\n.reg .pred p;\n"
        "mbarrier.test_wait.parity.shared::cta.b64 p, [%1], %2;\n"
        "selp.u32 %0, 1, 0, p;\n}\n" : "=r"(done) : "r"(bar), "r"(parity) : "memory");
    return done;
}
__device__ __forceinline__ uint32_t mbar_try(uint32_t bar, uint32_t parity) {
    uint32_t done;
    asm volatile(
        "{\n.reg .pred p;\n"
        "mbarrier.try_wait.parity.shared::cta.b64 p, [%1], %2;\n"
        "selp.u32 %0, 1, 0, p;\n}\n" : "=r"(done) : "r"(bar), "r"(parity) : "memory");
    return done;
}
__device__ __forceinline__ void tma_load_2d(uint32_t dst, const CUtensorMap* map, uint32_t bar, int c0, int c1) {
    asm volatile(
        "cp.async.bulk.tensor.2d.shared::cluster.global.mbarrier::complete_tx::bytes [%0], [%1, {%3, %4}], [%2];"
        :: "r"(dst), "l"((uint64_t)map), "r"(bar), "r"(c0), "r"(c1) : "memory");
}
__device__ __forceinline__ void wgmma_fence() { asm volatile("wgmma.fence.sync.aligned;" ::: "memory"); }
__device__ __forceinline__ void wgmma_commit() { asm volatile("wgmma.commit_group.sync.aligned;" ::: "memory"); }
template <int N> __device__ __forceinline__ void wgmma_wait() {
    asm volatile("wgmma.wait_group.sync.aligned %0;" :: "n"(N) : "memory");
}
__device__ __forceinline__ uint64_t make_desc(uint32_t addr, uint32_t lbo, uint32_t sbo) {
    uint64_t d = 0;
    d |= (uint64_t)((addr & 0x3FFFF) >> 4);
    d |= (uint64_t)((lbo >> 4) & 0x3FFF) << 16;
    d |= (uint64_t)((sbo >> 4) & 0x3FFF) << 32;
    d |= (uint64_t)1 << 62;
    return d;
}

#define ACC64(d) \
    "+f"(d[0]), "+f"(d[1]), "+f"(d[2]), "+f"(d[3]), "+f"(d[4]), "+f"(d[5]), "+f"(d[6]), "+f"(d[7]), \
    "+f"(d[8]), "+f"(d[9]), "+f"(d[10]), "+f"(d[11]), "+f"(d[12]), "+f"(d[13]), "+f"(d[14]), "+f"(d[15]), \
    "+f"(d[16]), "+f"(d[17]), "+f"(d[18]), "+f"(d[19]), "+f"(d[20]), "+f"(d[21]), "+f"(d[22]), "+f"(d[23]), \
    "+f"(d[24]), "+f"(d[25]), "+f"(d[26]), "+f"(d[27]), "+f"(d[28]), "+f"(d[29]), "+f"(d[30]), "+f"(d[31]), \
    "+f"(d[32]), "+f"(d[33]), "+f"(d[34]), "+f"(d[35]), "+f"(d[36]), "+f"(d[37]), "+f"(d[38]), "+f"(d[39]), \
    "+f"(d[40]), "+f"(d[41]), "+f"(d[42]), "+f"(d[43]), "+f"(d[44]), "+f"(d[45]), "+f"(d[46]), "+f"(d[47]), \
    "+f"(d[48]), "+f"(d[49]), "+f"(d[50]), "+f"(d[51]), "+f"(d[52]), "+f"(d[53]), "+f"(d[54]), "+f"(d[55]), \
    "+f"(d[56]), "+f"(d[57]), "+f"(d[58]), "+f"(d[59]), "+f"(d[60]), "+f"(d[61]), "+f"(d[62]), "+f"(d[63])
#define ACC64_STR \
    "{%0, %1, %2, %3, %4, %5, %6, %7, %8, %9, %10, %11, %12, %13, %14, %15, " \
    "%16, %17, %18, %19, %20, %21, %22, %23, %24, %25, %26, %27, %28, %29, %30, %31, " \
    "%32, %33, %34, %35, %36, %37, %38, %39, %40, %41, %42, %43, %44, %45, %46, %47, " \
    "%48, %49, %50, %51, %52, %53, %54, %55, %56, %57, %58, %59, %60, %61, %62, %63}"

template <int TB>
__device__ __forceinline__ void wgmma_ss_n128(float (&d)[64], uint64_t da, uint64_t db, int scale_d) {
    asm volatile(
        "{\n.reg .pred p;\nsetp.ne.b32 p, %66, 0;\n"
        "wgmma.mma_async.sync.aligned.m64n128k16.f32.bf16.bf16 " ACC64_STR ", %64, %65, p, 1, 1, 0, %67;\n}\n"
        : ACC64(d) : "l"(da), "l"(db), "r"(scale_d), "n"(TB));
}
__device__ __forceinline__ uint32_t desc_lo(uint32_t addr, uint32_t lbo) { return ((addr & 0x3FFFF) >> 4) | ((lbo >> 4) << 16); }
template <int TB>
__device__ __forceinline__ void wgmma_ss_n128_lo(float (&d)[64], uint32_t da_lo, uint32_t db_lo, int scale_d) {
    asm volatile(
        "{\n.reg .pred p;\n.reg .b64 da, db;\nsetp.ne.b32 p, %66, 0;\n"
        "mov.b64 da, {%64, 0x40000040};\nmov.b64 db, {%65, 0x40000040};\n"
        "wgmma.mma_async.sync.aligned.m64n128k16.f32.bf16.bf16 " ACC64_STR ", da, db, p, 1, 1, 0, %67;\n}\n"
        : ACC64(d) : "r"(da_lo), "r"(db_lo), "r"(scale_d), "n"(TB));
}
__device__ __forceinline__ void wgmma_rs_n128_tb(float (&d)[64], uint32_t a0, uint32_t a1, uint32_t a2, uint32_t a3,
                                                 uint64_t db, int scale_d) {
    asm volatile(
        "{\n.reg .pred p;\nsetp.ne.b32 p, %69, 0;\n"
        "wgmma.mma_async.sync.aligned.m64n128k16.f32.bf16.bf16 " ACC64_STR ", {%64, %65, %66, %67}, %68, p, 1, 1, 1;\n}\n"
        : ACC64(d) : "r"(a0), "r"(a1), "r"(a2), "r"(a3), "l"(db), "r"(scale_d));
}
__device__ __forceinline__ void wgmma_rs_n80(float (&d)[40], const uint32_t (&a)[4], uint32_t db_lo, int scale_d) {
    asm volatile(
        "{\n.reg .pred p;\n.reg .b64 db;\nsetp.ne.b32 p, %45, 0;\nmov.b64 db, {%44, 0x40000040};\n"
        "wgmma.mma_async.sync.aligned.m64n80k16.f32.bf16.bf16 "
        "{%0, %1, %2, %3, %4, %5, %6, %7, %8, %9, %10, %11, %12, %13, %14, %15, %16, %17, %18, %19, %20, %21, %22, %23, %24, %25, %26, %27, %28, %29, %30, %31, %32, %33, %34, %35, %36, %37, %38, %39}, "
        "{%40, %41, %42, %43}, db, p, 1, 1, 0;\n}\n"
        : "+f"(d[0]), "+f"(d[1]), "+f"(d[2]), "+f"(d[3]), "+f"(d[4]), "+f"(d[5]), "+f"(d[6]), "+f"(d[7]), "+f"(d[8]), "+f"(d[9]), "+f"(d[10]), "+f"(d[11]), "+f"(d[12]), "+f"(d[13]), "+f"(d[14]), "+f"(d[15]), "+f"(d[16]), "+f"(d[17]), "+f"(d[18]), "+f"(d[19]), "+f"(d[20]), "+f"(d[21]), "+f"(d[22]), "+f"(d[23]), "+f"(d[24]), "+f"(d[25]), "+f"(d[26]), "+f"(d[27]), "+f"(d[28]), "+f"(d[29]), "+f"(d[30]), "+f"(d[31]), "+f"(d[32]), "+f"(d[33]), "+f"(d[34]), "+f"(d[35]), "+f"(d[36]), "+f"(d[37]), "+f"(d[38]), "+f"(d[39])
        : "r"(a[0]), "r"(a[1]), "r"(a[2]), "r"(a[3]), "r"(db_lo), "r"(scale_d));
}
__device__ __forceinline__ void wgmma_ss_n256_tb(float (&d)[128], uint64_t da, uint64_t db, int scale_d) {
    asm volatile(
        "{\n.reg .pred p;\nsetp.ne.b32 p, %130, 0;\n"
        "wgmma.mma_async.sync.aligned.m64n256k16.f32.bf16.bf16 {%0, %1, %2, %3, %4, %5, %6, %7, %8, %9, %10, %11, %12, %13, %14, %15, %16, %17, %18, %19, %20, %21, %22, %23, %24, %25, %26, %27, %28, %29, %30, %31, %32, %33, %34, %35, %36, %37, %38, %39, %40, %41, %42, %43, %44, %45, %46, %47, %48, %49, %50, %51, %52, %53, %54, %55, %56, %57, %58, %59, %60, %61, %62, %63, %64, %65, %66, %67, %68, %69, %70, %71, %72, %73, %74, %75, %76, %77, %78, %79, %80, %81, %82, %83, %84, %85, %86, %87, %88, %89, %90, %91, %92, %93, %94, %95, %96, %97, %98, %99, %100, %101, %102, %103, %104, %105, %106, %107, %108, %109, %110, %111, %112, %113, %114, %115, %116, %117, %118, %119, %120, %121, %122, %123, %124, %125, %126, %127}, %128, %129, p, 1, 1, 0, 1;\n}\n"
        : "+f"(d[0]), "+f"(d[1]), "+f"(d[2]), "+f"(d[3]), "+f"(d[4]), "+f"(d[5]), "+f"(d[6]), "+f"(d[7]), "+f"(d[8]), "+f"(d[9]), "+f"(d[10]), "+f"(d[11]), "+f"(d[12]), "+f"(d[13]), "+f"(d[14]), "+f"(d[15]), "+f"(d[16]), "+f"(d[17]), "+f"(d[18]), "+f"(d[19]), "+f"(d[20]), "+f"(d[21]), "+f"(d[22]), "+f"(d[23]), "+f"(d[24]), "+f"(d[25]), "+f"(d[26]), "+f"(d[27]), "+f"(d[28]), "+f"(d[29]), "+f"(d[30]), "+f"(d[31]), "+f"(d[32]), "+f"(d[33]), "+f"(d[34]), "+f"(d[35]), "+f"(d[36]), "+f"(d[37]), "+f"(d[38]), "+f"(d[39]), "+f"(d[40]), "+f"(d[41]), "+f"(d[42]), "+f"(d[43]), "+f"(d[44]), "+f"(d[45]), "+f"(d[46]), "+f"(d[47]), "+f"(d[48]), "+f"(d[49]), "+f"(d[50]), "+f"(d[51]), "+f"(d[52]), "+f"(d[53]), "+f"(d[54]), "+f"(d[55]), "+f"(d[56]), "+f"(d[57]), "+f"(d[58]), "+f"(d[59]), "+f"(d[60]), "+f"(d[61]), "+f"(d[62]), "+f"(d[63]), "+f"(d[64]), "+f"(d[65]), "+f"(d[66]), "+f"(d[67]), "+f"(d[68]), "+f"(d[69]), "+f"(d[70]), "+f"(d[71]), "+f"(d[72]), "+f"(d[73]), "+f"(d[74]), "+f"(d[75]), "+f"(d[76]), "+f"(d[77]), "+f"(d[78]), "+f"(d[79]), "+f"(d[80]), "+f"(d[81]), "+f"(d[82]), "+f"(d[83]), "+f"(d[84]), "+f"(d[85]), "+f"(d[86]), "+f"(d[87]), "+f"(d[88]), "+f"(d[89]), "+f"(d[90]), "+f"(d[91]), "+f"(d[92]), "+f"(d[93]), "+f"(d[94]), "+f"(d[95]), "+f"(d[96]), "+f"(d[97]), "+f"(d[98]), "+f"(d[99]), "+f"(d[100]), "+f"(d[101]), "+f"(d[102]), "+f"(d[103]), "+f"(d[104]), "+f"(d[105]), "+f"(d[106]), "+f"(d[107]), "+f"(d[108]), "+f"(d[109]), "+f"(d[110]), "+f"(d[111]), "+f"(d[112]), "+f"(d[113]), "+f"(d[114]), "+f"(d[115]), "+f"(d[116]), "+f"(d[117]), "+f"(d[118]), "+f"(d[119]), "+f"(d[120]), "+f"(d[121]), "+f"(d[122]), "+f"(d[123]), "+f"(d[124]), "+f"(d[125]), "+f"(d[126]), "+f"(d[127])
        : "l"(da), "l"(db), "r"(scale_d));
}
__device__ __forceinline__ void stmatrix_x4(uint32_t addr, uint32_t r0, uint32_t r1, uint32_t r2, uint32_t r3) {
    asm volatile("stmatrix.sync.aligned.m8n8.x4.shared.b16 [%0], {%1, %2, %3, %4};" :: "r"(addr), "r"(r0), "r"(r1), "r"(r2), "r"(r3) : "memory");
}
__device__ __forceinline__ void tma_store_2d(const CUtensorMap* map, uint32_t src, int c0, int c1) {
    asm volatile("cp.async.bulk.tensor.2d.global.shared::cta.bulk_group [%0, {%2, %3}], [%1];"
                 :: "l"((uint64_t)map), "r"(src), "r"(c0), "r"(c1) : "memory");
}
__device__ __forceinline__ float ex2f(float x) { float y; asm("ex2.approx.ftz.f32 %0, %1;" : "=f"(y) : "f"(x)); return y; }
__device__ __forceinline__ uint32_t pack_bf16(float lo, float hi) {
    __nv_bfloat162 v = __floats2bfloat162_rn(lo, hi);
    return *reinterpret_cast<uint32_t*>(&v);
}
__device__ __forceinline__ void mma_16816(float (&c)[4], uint32_t a0, uint32_t a1, uint32_t a2, uint32_t a3,
                                          uint32_t b0, uint32_t b1) {
    asm volatile(
        "mma.sync.aligned.m16n8k16.row.col.f32.bf16.bf16.f32 {%0,%1,%2,%3}, {%4,%5,%6,%7}, {%8,%9}, {%0,%1,%2,%3};"
        : "+f"(c[0]), "+f"(c[1]), "+f"(c[2]), "+f"(c[3])
        : "r"(a0), "r"(a1), "r"(a2), "r"(a3), "r"(b0), "r"(b1));
}
__device__ __forceinline__ void ldmatrix_x4_trans(uint32_t& r0, uint32_t& r1, uint32_t& r2, uint32_t& r3, uint32_t addr) {
    asm volatile("ldmatrix.sync.aligned.m8n8.x4.trans.shared.b16 {%0,%1,%2,%3}, [%4];"
                 : "=r"(r0), "=r"(r1), "=r"(r2), "=r"(r3) : "r"(addr));
}

struct AttnParams {
    CUtensorMap mapQ, mapK, mapV;
    CUtensorMap mapO;
    bf16* out;
};
constexpr int FA_ITEMS = 16 * NH;
__device__ __forceinline__ int fa_qt(int t) { return 15 - ((t & 127) >> 3); }
__device__ __forceinline__ int fa_head(int t) { return (t >> 7) * 8 + (t & 7); }
#define FA_TKA 2
#define FA_SPLIT 11

#define FA_P0 4
#define FA_HO 7
#define FA_LAG 2
#define FA_PK 3
#define FA_ST 4
#define FA_TG 16
#define FA_EARLY 0
#define FA_I0 0
static_assert(FA_GRID <= 104 && FA_HO >= FA_P0 && FA_P0 >= 1, "");
constexpr float FA_MARGIN = 16.f;
#define FAT(b, i)
__device__ __forceinline__ void mbar_arrive_if(uint32_t bar, bool c) {
    asm volatile("{\n.reg .pred p;\nsetp.ne.b32 p, %1, 0;\n@p mbarrier.arrive.shared::cta.b64 _, [%0];\n}" :: "r"(bar), "r"((int)c) : "memory");
}
__device__ __forceinline__ void sched_fence(int v, int id, const float* a, const float* b, const float* c) {
    asm volatile("{\n.reg .pred p;\nsetp.ne.s32 p, %0, %1;\n@p bra SF_SKIP;\nwgmma.wait_group.sync.aligned 0;\n"
                 "st.volatile.shared.f32 [%0], %2;\nst.volatile.shared.f32 [%0], %3;\nst.volatile.shared.f32 [%0], %4;\nst.volatile.shared.f32 [%0], %5;\n"
                 "st.volatile.shared.f32 [%0], %6;\nst.volatile.shared.f32 [%0], %7;\nst.volatile.shared.f32 [%0], %8;\nst.volatile.shared.f32 [%0], %9;\n"
                 "st.volatile.shared.f32 [%0], %10;\nst.volatile.shared.f32 [%0], %11;\nst.volatile.shared.f32 [%0], %12;\nst.volatile.shared.f32 [%0], %13;\n"
                 "exit;\nSF_SKIP:\n}" :: "r"(v), "r"(1000000 + id), "f"(a[0]), "f"(a[1]), "f"(a[2]), "f"(a[3]), "f"(b[0]), "f"(b[1]), "f"(b[2]), "f"(b[3]),
                 "f"(c[0]), "f"(c[1]), "f"(c[2]), "f"(c[3]) : "memory");
}
__device__ __forceinline__ float ex2v(float x) { float y; asm volatile("ex2.approx.ftz.f32 %0, %1;" : "=f"(y) : "f"(x)); return y; }
__device__ __forceinline__ void wgmma_rs_n128_tb_lo(float (&d)[64], const uint32_t* a, uint32_t db_lo, int scale_d) {
    asm volatile(
        "{\n.reg .pred p;\n.reg .b64 db;\nsetp.ne.b32 p, %69, 0;\nmov.b64 db, {%68, 0x40000040};\n"
        "wgmma.mma_async.sync.aligned.m64n128k16.f32.bf16.bf16 " ACC64_STR ", {%64, %65, %66, %67}, db, p, 1, 1, 1;\n}\n"
        : ACC64(d) : "r"(a[0]), "r"(a[1]), "r"(a[2]), "r"(a[3]), "r"(db_lo), "r"(scale_d));
}

constexpr int M_GRID = 68;
constexpr uint32_t SD = 1024;
constexpr uint32_t MO_BAR = 229376;
constexpr int M_SMEM = MO_BAR + 1024;
constexpr uint32_t FO_Q = 0, FO_KV = 65536, FO_O = FO_KV + 2 * 65536, FO_BAR = MO_BAR + 512;
constexpr uint32_t FB_QF = FO_BAR, FB_QE = FO_BAR + 16, FB_KF = FO_BAR + 32, FB_VF = FO_BAR + 48, FB_KE = FO_BAR + 64, FB_VE = FO_BAR + 80,
                   FB_OF = FO_BAR + 96, FB_OE = FO_BAR + 112, FB_SLOT = FO_BAR + 128, FB_OSLOT = FO_BAR + 136;
__device__ __forceinline__ void attn_init(uint32_t sb) {
    for (int i = 0; i < 2; i++) {
        mbar_init(sb + FB_QF + 8 * i, 1); mbar_init(sb + FB_QE + 8 * i, 8); mbar_init(sb + FB_KF + 8 * i, 1); mbar_init(sb + FB_VF + 8 * i, 1);
        mbar_init(sb + FB_KE + 8 * i, 8); mbar_init(sb + FB_VE + 8 * i, 8); mbar_init(sb + FB_OF + 8 * i, 4); mbar_init(sb + FB_OE + 8 * i, 1);
    }
}
__device__ __forceinline__ void attn_helper(const AttnParams& P, uint32_t sb, int wg) {
    const uint32_t stg = sb + FO_O + wg * 16384;
    for (int n = 0;; n++) {
        mbar_wait(sb + FB_OF + 8 * wg, n & 1);
        int t;
        asm volatile("ld.shared.s32 %0, [%1];" : "=r"(t) : "r"(sb + FB_OSLOT + wg * 4) : "memory");
        const int qt = fa_qt(t), h = fa_head(t & 1023);
        tma_store_2d(&P.mapO, stg, 0, h * SEQ + qt * 128 + wg * 64);
        tma_store_2d(&P.mapO, stg + 8192, 64, h * SEQ + qt * 128 + wg * 64);
        asm volatile("cp.async.bulk.commit_group;" ::: "memory");
        asm volatile("cp.async.bulk.wait_group.read 0;" ::: "memory");
        mbar_arrive(sb + FB_OE + 8 * wg);
        asm volatile("cp.async.bulk.wait_group 0;" ::: "memory");
        signal_ctr(CT_CA + qt * 4 + (h >> 3));
        if (t >= 1024) break;
    }
}
__device__ __forceinline__ void attn_producer(const AttnParams& P, uint32_t sb, uint32_t free_bar, uint32_t free_par) {
    const uint32_t sQ = sb + FO_Q, sKV = sb + FO_KV;
    int b = 0, hp_ready = 0, vrow = 0, t = blockIdx.x, item = 0;
    auto load_v = [&](int i) {
        const uint32_t sv = sKV + (i & 1) * 65536 + 32768, bar = sb + FB_VF + 8 * (i & 1);
        mbar_wait(sb + FB_VE + 8 * (i & 1), ((i >> 1) & 1) ^ 1);
        mbar_expect_tx(bar, 32768);
        tma_load_2d(sv, &P.mapV, bar, 0, vrow);
        tma_load_2d(sv + 16384, &P.mapV, bar, 64, vrow);
    };
    for (;; item++) {
        const bool valid = t < FA_ITEMS;
        const int qt = fa_qt(t), h = fa_head(t);
        if (valid && !((hp_ready >> (h >> 1)) & 1)) { wait_ctr(CT_AP + (h >> 1), 96u); hp_ready |= 1 << (h >> 1); }
        const uint32_t bq = sb + FB_QF + 8 * (item & 1);
        mbar_wait(item ? sb + FB_QE + 8 * (item & 1) : free_bar + 8, item ? ((item >> 1) & 1) ^ 1 : free_par);
        asm volatile("st.shared.s32 [%0], %1;" :: "r"(sb + FB_SLOT + (item & 1) * 4), "r"(valid ? t : -1) : "memory");
        if (!valid) { mbar_arrive(bq); break; }
        mbar_expect_tx(bq, 32768);
        tma_load_2d(sQ + (item & 1) * 32768, &P.mapQ, bq, 0, h * SEQ + qt * 128);
        tma_load_2d(sQ + (item & 1) * 32768 + 16384, &P.mapQ, bq, 64, h * SEQ + qt * 128);
#pragma unroll 1
        for (int j = 0; j <= qt; j++, b++) {
            const uint32_t sk = sKV + (b & 1) * 65536, bar = sb + FB_KF + 8 * (b & 1);
            mbar_wait(b >= 2 ? sb + FB_KE + 8 * (b & 1) : free_bar + 24 + 32 * b, b >= 2 ? ((b >> 1) & 1) ^ 1 : free_par);
            if (b == 1) { TS_END2(0, 256); TS_BEGIN2(1, 256); }
            if (b == 2) wait_ctr(CT_GATE, 256u);
            mbar_expect_tx(bar, 32768);
            tma_load_2d(sk, &P.mapK, bar, 0, h * SEQ + j * 128);
            tma_load_2d(sk + 16384, &P.mapK, bar, 64, h * SEQ + j * 128);
            if (j == max(qt - FA_TKA, 0)) t = take_ticket(CT_ATTN);
            if (b > 0) load_v(b - 1);
            vrow = h * SEQ + j * 128;
        }
        t += M_GRID;
    }
    load_v(b - 1);
    mbar_wait(sb + FB_KE + 8 * (~b & 1), ((b - 1) >> 1) & 1);
}
template <uint32_t sb, typename F>
__device__ __forceinline__ void attn_consumer(const AttnParams& P, int warp, F done) {
    constexpr uint32_t sQ = SD + FO_Q, sKV = SD + FO_KV;
    constexpr uint32_t sO = sb + FO_O;
    constexpr uint32_t bar_qf = sb + FB_QF, bar_qe = sb + FB_QE, bar_kf = sb + FB_KF, bar_vf = sb + FB_VF, bar_ke = sb + FB_KE, bar_ve = sb + FB_VE,
                   bar_of = sb + FB_OF, bar_oe = sb + FB_OE, slot = sb + FB_SLOT, oslot = sb + FB_OSLOT;
    {
        const int wg = warp >> 2;
        const int lane = threadIdx.x & 31;
        const float sc = 0.08838834764831845f * 1.4426950408889634f;
        const int r0 = wg * 64 + (warp & 3) * 16 + (lane >> 2);
        float o[64], s[64];
        uint32_t pa[32];
        float m0 = 0.f, m1 = 0.f, l0 = 0.f, l1 = 0.f, i0 = 0.f, i1 = 0.f, g0 = 0.f, g1 = 0.f;
        const uint32_t q_lo = desc_lo(sQ + wg * 8192, 16), k_lo = desc_lo(sKV, 16), v_lo = desc_lo(sKV + 32768, 16384);
        auto issue_qk = [&](int b, int item) {
            const uint32_t qd = q_lo + (item & 1) * 2048, kd = k_lo + (b & 1) * 4096;
            wgmma_fence();
#pragma unroll
            for (int kk = 0; kk < 8; kk++) wgmma_ss_n128_lo<0>(s, qd + (kk >> 2) * 1024 + (kk & 3) * 2, kd + (kk >> 2) * 1024 + (kk & 3) * 2, kk != 0);
            wgmma_commit();
        };
        auto issue_pv = [&](int b, bool acc, int n) {
            const uint32_t vd = v_lo + (b & 1) * 4096;
            mbar_wait(bar_vf + 8 * (b & 1), (b >> 1) & 1);
            wgmma_fence();
#pragma unroll
            for (int kk = 0; kk < 8; kk++) if (kk < n) wgmma_rs_n128_tb_lo(o, &pa[kk * 4], vd + kk * 128, kk ? 1 : (int)acc);
            wgmma_commit();
        };
        const int lim = r0 - (lane & 3) * 2;
        int item = -1, tnext = 0;
        uint32_t k_ready = 0, q_ready = 0;
        auto mask = [&](int i) { if ((i >> 2) * 8 + (i & 1) - ((i & 2) ? 8 : 0) > lim) s[i] = -INFINITY; };
        auto exps = [&](auto mode, int b, bool hand_over, float& u0, float& u1) {
            constexpr int MODE = decltype(mode)::value;
            float p[64], u[4] = {0.f, 0.f, 0.f, 0.f};
            const uint32_t vd = v_lo + ((b - 1) & 1) * 4096;
#pragma unroll
            for (int i = 0; i < 4; i++) p[i] = fmaf(s[i], sc, (i & 2) ? -m1 : -m0);
#pragma unroll
            for (int g = 0; g < 16 + FA_LAG; g++) {
                if (MODE && g >= FA_I0 && g - FA_I0 < 8 - FA_P0) {
                    const int kk = FA_P0 + g - FA_I0;
                    wgmma_fence();
                    wgmma_rs_n128_tb_lo(o, &pa[kk * 4], vd + kk * 128, 1);
                    wgmma_commit();
                    if (kk == FA_HO) asm volatile("{\n.reg .pred p;\nsetp.ne.b32 p, %1, 0;\n@p bar.arrive %0, 256;\n}" :: "r"(4 - wg), "r"((int)hand_over) : "memory");
                }
                if (MODE && g == FA_SPLIT) {
                    FAT(b, 2);
                    wgmma_wait<0>();
                    FAT(b - 1, 3);
                    mbar_arrive_if(bar_ve + 8 * ((b - 1) & 1), lane == 0);
                }
                if (MODE && g == FA_TG) {
                    k_ready = mbar_test(bar_kf + 8 * (~b & 1), ((b + 1) >> 1) & 1);
                    if (MODE == 2) {
                        q_ready = mbar_test(bar_qf + 8 * (~item & 1), ((item + 1) >> 1) & 1);
                        asm volatile("ld.shared.s32 %0, [%1];" : "=r"(tnext) : "r"(slot + (~item & 1) * 4) : "memory");
                    }
                }
#pragma unroll
                for (int j = 0; j < 4; j++) {
                    const int i = g * 4 + j;
                    if (g < 16) p[i] = ex2v(p[i]);
                    if (g < 15) {
                        if (MODE == 2) mask(i + 4);
                        p[i + 4] = fmaf(s[i + 4], sc, (i & 2) ? -m1 : -m0);
                    }
                    if (g >= FA_LAG) u[j] += p[i - FA_LAG * 4];
                }
#pragma unroll
                for (int gg = 0; gg < 16; gg++) {
                    const int at = MODE && gg + FA_LAG < FA_SPLIT + gg / FA_PK ? FA_SPLIT + gg / FA_PK : gg + FA_LAG;
                    if (at == g) { pa[gg * 2] = pack_bf16(p[gg * 4], p[gg * 4 + 1]); pa[gg * 2 + 1] = pack_bf16(p[gg * 4 + 2], p[gg * 4 + 3]); }
                }
                if (MODE && g < 16) sched_fence(b, g + MODE * 32, &p[g * 4], &p[(g < 15 ? g + 1 : g) * 4], u);
            }
            u0 = u[0] + u[1]; u1 = u[2] + u[3];
        };
        auto quad_max = [&](float& x0, float& x1) {
            x0 = fmaxf(x0, __shfl_xor_sync(0xffffffff, x0, 1)); x1 = fmaxf(x1, __shfl_xor_sync(0xffffffff, x1, 1));
            x0 = fmaxf(x0, __shfl_xor_sync(0xffffffff, x0, 2)); x1 = fmaxf(x1, __shfl_xor_sync(0xffffffff, x1, 2));
            x0 = fmaf(x0, sc, FA_MARGIN); x1 = fmaf(x1, sc, FA_MARGIN);
        };
        auto softmax_exact = [&](bool fresh, int b) {
            wgmma_wait<0>();
            float x[8];
#pragma unroll
            for (int i = 0; i < 8; i++) x[i] = fmaxf(s[i * 2], s[i * 2 + 1]);
#pragma unroll
            for (int i = 8; i < 32; i++) x[i & 7] = fmaxf(x[i & 7], fmaxf(s[i * 2], s[i * 2 + 1]));
            float x0 = fmaxf(fmaxf(x[0], x[2]), fmaxf(x[4], x[6])), x1 = fmaxf(fmaxf(x[1], x[3]), fmaxf(x[5], x[7]));
            quad_max(x0, x1);
            if (!fresh) {
                x0 = fmaxf(x0, m0); x1 = fmaxf(x1, m1);
                const float a0 = ex2f(m0 - x0), a1 = ex2f(m1 - x1);
                l0 *= a0; l1 *= a1;
#pragma unroll
                for (int i = 0; i < 16; i++) { o[i * 4 + 0] *= a0; o[i * 4 + 1] *= a0; o[i * 4 + 2] *= a1; o[i * 4 + 3] *= a1; }
            }
            m0 = x0; m1 = x1;
            float u0, u1;
            exps(std::integral_constant<int, 0>(), b, false, u0, u1);
            l0 += u0; l1 += u1;
        };
        auto finish_rows = [&]() {
            l0 += __shfl_xor_sync(0xffffffff, l0, 1); l1 += __shfl_xor_sync(0xffffffff, l1, 1);
            l0 += __shfl_xor_sync(0xffffffff, l0, 2); l1 += __shfl_xor_sync(0xffffffff, l1, 2);
            i0 = __fdividef(g0, l0); i1 = __fdividef(g1, l1);
        };
        auto clear_out = [&](int t) {
            if (t >= 384) {
                bf16* z = P.out + (size_t)(fa_qt(t) * 128 + wg * 64 + ((threadIdx.x & 127) >> 3)) * DM + (t & 7) * 64 + (lane & 7) * 8;
#pragma unroll
                for (int i = 0; i < 4; i++) *reinterpret_cast<uint4*>(z + i * 16 * DM) = make_uint4(0u, 0u, 0u, 0u);
            }
        };
        auto store_o = [&](int t, int n, int c0, int c1) {
            const uint32_t stg = sO + wg * 16384;
            if (c0 == 0) {
                mbar_wait(bar_oe + 8 * wg, (n & 1) ^ 1);
                asm volatile("st.shared.s32 [%0], %1;" :: "r"(oslot + wg * 4), "r"(t) : "memory");
            }
            const int row = (warp & 3) * 16 + (lane >> 2);
#pragma unroll
            for (int i = c0; i < c1; i++) {
                const int ch = i * 4 + (lane & 3);
                const uint32_t a = stg + (ch >> 3) * 8192 + row * 128 + (((ch & 7) ^ (row & 7)) << 4);
                const float* q = &o[i * 16];
                asm volatile("st.shared.v4.b32 [%0], {%1, %2, %3, %4};" :: "r"(a), "r"(pack_bf16(q[0] * i0, q[1] * i0)), "r"(pack_bf16(q[4] * i0, q[5] * i0)),
                             "r"(pack_bf16(q[8] * i0, q[9] * i0)), "r"(pack_bf16(q[12] * i0, q[13] * i0)) : "memory");
                asm volatile("st.shared.v4.b32 [%0], {%1, %2, %3, %4};" :: "r"(a + 1024), "r"(pack_bf16(q[2] * i1, q[3] * i1)), "r"(pack_bf16(q[6] * i1, q[7] * i1)),
                             "r"(pack_bf16(q[10] * i1, q[11] * i1)), "r"(pack_bf16(q[14] * i1, q[15] * i1)) : "memory");
            }
        };
        auto publish_o = [&]() {
            asm volatile("fence.proxy.async.shared::cta;" ::: "memory");
            __syncwarp();
            mbar_arrive_if(bar_of + 8 * wg, lane == 0);
        };
        int t = 0, left = 0, tdone = -1, b = 0, nout = 0;
        bool first = true, staged = false;
#pragma unroll 1
        for (;; b++) {
            const bool fresh = left == 0;
            const int tprev = t;
            FAT(b, 4);
            if (staged) { publish_o(); staged = false; }
            if (fresh) {
                item++;
                if (!q_ready) {
                    mbar_wait(bar_qf + 8 * (item & 1), (item >> 1) & 1);
                    asm volatile("ld.shared.s32 %0, [%1];" : "=r"(tnext) : "r"(slot + (item & 1) * 4) : "memory");
                }
                if (tnext < 0) break;
                t = tnext;
                left = fa_qt(t) + 1;
            }
            left--;
            if (tdone >= 0) store_o(tdone, nout, 0, FA_ST);
            FAT(b, 5);
            if (!k_ready) mbar_wait(bar_kf + 8 * (b & 1), (b >> 1) & 1);
            FAT(b, 6);
            asm volatile("bar.sync %0, 256;" :: "r"(3 + wg) : "memory");
            FAT(b, 0);
            issue_qk(b, item);
            bool early = false;
            if (!fresh && !first && left != 0) {
                issue_pv(b - 1, true, FA_P0);
                wgmma_wait<1>();
                FAT(b, 1);
                mbar_arrive_if(bar_ke + 8 * (b & 1), lane == 0);
            } else {
                early = (FA_EARLY && tdone >= 0) || b == 0;
                if (early) asm volatile("bar.arrive %0, 256;" :: "r"(4 - wg) : "memory");
                if (tdone >= 0) { wgmma_wait<1>(); store_o(tdone, nout++, FA_ST, 4); staged = true; }
                tdone = -1;
                if (fresh && b > 0) { finish_rows(); tdone = tprev; l0 = l1 = 0.f; }
                if (left == 0) { g0 = __ldcg(g_gate + fa_qt(t) * 128 + r0); g1 = __ldcg(g_gate + fa_qt(t) * 128 + r0 + 8); clear_out(t); }
                if (b > 0) issue_pv(b - 1, !first, FA_P0); else { wgmma_fence(); wgmma_commit(); }
                first = fresh;
                wgmma_wait<1>();
                FAT(b, 1);
                mbar_arrive_if(bar_ke + 8 * (b & 1), lane == 0);
                mbar_arrive_if(bar_qe + 8 * (item & 1), lane == 0 && left == 0);
                if (left == 0) { mask(0); mask(1); }
                if (fresh) { m0 = fmaxf(s[0], s[1]); m1 = fmaxf(s[2], s[3]); quad_max(m0, m1); }
            }
            if (b > 0) {
                float u0, u1;
                if (left == 0) exps(std::integral_constant<int, 2>(), b, !early, u0, u1);
                else exps(std::integral_constant<int, 1>(), b, !early, u0, u1);
                if (!__any_sync(0xffffffff, !(u0 + u1 < 1.f))) { l0 += u0; l1 += u1; continue; }
            }
            softmax_exact(fresh, b);
        }
        if (tdone >= 0) { store_o(tdone, nout++, 0, 4); publish_o(); }
        issue_pv(b - 1, !first, 8);
        finish_rows();
        wgmma_wait<0>();
        done();
        store_o(t + 1024, nout, 0, 4);
        publish_o();
    }
}

__device__ __forceinline__ uint32_t cluster_ctarank() {
    uint32_t r; asm volatile("mov.u32 %0, %%cluster_ctarank;" : "=r"(r)); return r;
}
__device__ __forceinline__ uint32_t mapa_u32(uint32_t addr, uint32_t rank) {
    uint32_t r; asm volatile("mapa.shared::cluster.u32 %0, %1, %2;" : "=r"(r) : "r"(addr), "r"(rank)); return r;
}
__device__ __forceinline__ void cluster_sync_all() {
    asm volatile("barrier.cluster.arrive.release.aligned;\nbarrier.cluster.wait.acquire.aligned;" ::: "memory");
}
__device__ __forceinline__ void st_async_v4(uint32_t addr, uint32_t a, uint32_t b, uint32_t c, uint32_t d, uint32_t mbar) {
    asm volatile("st.async.weak.shared::cluster.mbarrier::complete_tx::bytes.v4.b32 [%0], {%1, %2, %3, %4}, [%5];"
                 :: "r"(addr), "r"(a), "r"(b), "r"(c), "r"(d), "r"(mbar) : "memory");
}
__device__ __forceinline__ void st_async_v2(uint32_t addr, uint32_t a, uint32_t b, uint32_t mbar) {
    asm volatile("st.async.weak.shared::cluster.mbarrier::complete_tx::bytes.v2.b32 [%0], {%1, %2}, [%3];"
                 :: "r"(addr), "r"(a), "r"(b), "r"(mbar) : "memory");
}
__device__ __forceinline__ void st_async_b32(uint32_t addr, uint32_t a, uint32_t mbar) {
    asm volatile("st.async.weak.shared::cluster.mbarrier::complete_tx::bytes.b32 [%0], %1, [%2];" :: "r"(addr), "r"(a), "r"(mbar) : "memory");
}
__device__ __forceinline__ void pace(int cycles) {
    if (cycles > 0) {
        uint32_t t0, t;
        asm volatile("mov.u32 %0, %%clock;" : "=r"(t0));
        do { asm volatile("mov.u32 %0, %%clock;" : "=r"(t)); } while (t - t0 < (uint32_t)cycles);
    }
}
__device__ __forceinline__ void mbar_wait_cl(uint32_t bar, uint32_t parity) {
    uint32_t done = 0;
    for (int it = 0; it < WAIT_LIMIT && !done; it++) {
        asm volatile(
            "{\n.reg .pred p;\n"
            "mbarrier.try_wait.parity.shared::cta.b64 p, [%1], %2;\n"
            "selp.u32 %0, 1, 0, p;\n}\n" : "=r"(done) : "r"(bar), "r"(parity) : "memory");
    }
}
__device__ __forceinline__ void ldmatrix_x4(uint32_t& r0, uint32_t& r1, uint32_t& r2, uint32_t& r3, uint32_t addr) {
    asm volatile("ldmatrix.sync.aligned.m8n8.x4.shared.b16 {%0,%1,%2,%3}, [%4];"
                 : "=r"(r0), "=r"(r1), "=r"(r2), "=r"(r3) : "r"(addr));
}
__device__ __forceinline__ void cp_async16(uint32_t dst, const void* src) {
    asm volatile("cp.async.cg.shared.global [%0], [%1], 16;" :: "r"(dst), "l"(src) : "memory");
}
__device__ __forceinline__ float bf16r(float x) { return __uint_as_float(pack_bf16(0.f, x) & 0xffff0000u); }

#define DBGP(i, w, ok)
#define DBG(i, w)
#define DBGD(i, w, dep)
#define DBG_EXTRA 0
__device__ __forceinline__ void tma_load_2d_mc(uint32_t dst, const CUtensorMap* map, uint32_t bar, int c0, int c1, uint16_t mask) {
    asm volatile(
        "cp.async.bulk.tensor.2d.shared::cluster.global.mbarrier::complete_tx::bytes.multicast::cluster [%0], [%1, {%3, %4}], [%2], %5;"
        :: "r"(dst), "l"((uint64_t)map), "r"(bar), "r"(c0), "r"(c1), "h"(mask) : "memory");
}
__device__ __forceinline__ void stmatrix_x4_trans(uint32_t addr, uint32_t r0, uint32_t r1, uint32_t r2, uint32_t r3) {
    asm volatile("stmatrix.sync.aligned.m8n8.x4.trans.shared.b16 [%0], {%1, %2, %3, %4};" :: "r"(addr), "r"(r0), "r"(r1), "r"(r2), "r"(r3) : "memory");
}
__device__ __forceinline__ void stmatrix_x2_trans(uint32_t addr, uint32_t r0, uint32_t r1) {
    asm volatile("stmatrix.sync.aligned.m8n8.x2.trans.shared.b16 [%0], {%1, %2};" :: "r"(addr), "r"(r0), "r"(r1) : "memory");
}
__device__ __forceinline__ uint4 lds128(uint32_t a) {
    uint4 v; asm volatile("ld.shared.v4.u32 {%0, %1, %2, %3}, [%4];" : "=r"(v.x), "=r"(v.y), "=r"(v.z), "=r"(v.w) : "r"(a) : "memory"); return v;
}
__device__ __forceinline__ void sts128(uint32_t a, uint32_t x, uint32_t y, uint32_t z, uint32_t w) {
    asm volatile("st.shared.v4.b32 [%0], {%1, %2, %3, %4};" :: "r"(a), "r"(x), "r"(y), "r"(z), "r"(w) : "memory");
}
__device__ __forceinline__ float2 lds64f(uint32_t a) {
    float2 v; asm volatile("ld.shared.v2.f32 {%0, %1}, [%2];" : "=f"(v.x), "=f"(v.y) : "r"(a) : "memory"); return v;
}
__device__ __forceinline__ void fence_async_smem() { asm volatile("fence.proxy.async.shared::cta;" ::: "memory"); }
#define ACC16(d) "+f"(d[0]), "+f"(d[1]), "+f"(d[2]), "+f"(d[3]), "+f"(d[4]), "+f"(d[5]), "+f"(d[6]), "+f"(d[7]), "+f"(d[8]), "+f"(d[9]), "+f"(d[10]), "+f"(d[11]), "+f"(d[12]), "+f"(d[13]), "+f"(d[14]), "+f"(d[15])
template <int ND>
__device__ __forceinline__ void wgmma_rs_n32(float (&d)[ND], const uint32_t (&a)[4], uint32_t db_lo, int scale_d) {
    asm volatile(
        "{\n.reg .pred p;\n.reg .b64 db;\nsetp.ne.b32 p, %21, 0;\nmov.b64 db, {%20, 0x40000040};\n"
        "wgmma.mma_async.sync.aligned.m64n32k16.f32.bf16.bf16 {%0,%1,%2,%3,%4,%5,%6,%7,%8,%9,%10,%11,%12,%13,%14,%15}, {%16,%17,%18,%19}, db, p, 1, 1, 0;\n}\n"
        : ACC16(d) : "r"(a[0]), "r"(a[1]), "r"(a[2]), "r"(a[3]), "r"(db_lo), "r"(scale_d));
}
template <int ND>
__device__ __forceinline__ void wgmma_ss_n32(float (&d)[ND], uint32_t da_lo, uint32_t db_lo, int scale_d) {
    asm volatile(
        "{\n.reg .pred p;\n.reg .b64 da, db;\nsetp.ne.b32 p, %18, 0;\nmov.b64 da, {%16, 0x40000040};\nmov.b64 db, {%17, 0x40000040};\n"
        "wgmma.mma_async.sync.aligned.m64n32k16.f32.bf16.bf16 {%0,%1,%2,%3,%4,%5,%6,%7,%8,%9,%10,%11,%12,%13,%14,%15}, da, db, p, 1, 1, 1, 0;\n}\n"
        : ACC16(d) : "r"(da_lo), "r"(db_lo), "r"(scale_d));
}
__device__ __forceinline__ void wgmma_ss_n8(float (&d)[4], uint32_t da_lo, uint32_t db_lo, int scale_d) {
    asm volatile(
        "{\n.reg .pred p;\n.reg .b64 da, db;\nsetp.ne.b32 p, %6, 0;\nmov.b64 da, {%4, 0x40000040};\nmov.b64 db, {%5, 0x00000010};\n"
        "wgmma.mma_async.sync.aligned.m64n8k16.f32.bf16.bf16 {%0,%1,%2,%3}, da, db, p, 1, 1, 1, 0;\n}\n"
        : "+f"(d[0]), "+f"(d[1]), "+f"(d[2]), "+f"(d[3]) : "r"(da_lo), "r"(db_lo), "r"(scale_d));
}

#define SCHED_FENCE()
__device__ __forceinline__ void wgmma_ss_n32_p(float (&d)[16], uint32_t da_lo, uint32_t db_lo, int scale_d) {
    asm volatile(
        "{\n.reg .pred p;\n.reg .b64 da, db;\nsetp.ne.b32 p, %18, 0;\nmov.b64 da, {%16, 0x40000040};\nmov.b64 db, {%17, 0x00000030};\n"
        "wgmma.mma_async.sync.aligned.m64n32k16.f32.bf16.bf16 {%0,%1,%2,%3,%4,%5,%6,%7,%8,%9,%10,%11,%12,%13,%14,%15}, da, db, p, 1, 1, 1, 0;\n}\n"
        : ACC16(d) : "r"(da_lo), "r"(db_lo), "r"(scale_d));
}

#define ACC20(d) ACC16(d), "+f"(d[16]), "+f"(d[17]), "+f"(d[18]), "+f"(d[19])
#define ACC20_STR "{%0,%1,%2,%3,%4,%5,%6,%7,%8,%9,%10,%11,%12,%13,%14,%15,%16,%17,%18,%19}"
__device__ __forceinline__ void wgmma_rs_n40(float (&d)[20], const uint32_t (&a)[4], uint32_t db_lo, int scale_d) {
    asm volatile(
        "{\n.reg .pred p;\n.reg .b64 db;\nsetp.ne.b32 p, %25, 0;\nmov.b64 db, {%24, 0x40000040};\n"
        "wgmma.mma_async.sync.aligned.m64n40k16.f32.bf16.bf16 " ACC20_STR ", {%20,%21,%22,%23}, db, p, 1, 1, 0;\n}\n"
        : ACC20(d) : "r"(a[0]), "r"(a[1]), "r"(a[2]), "r"(a[3]), "r"(db_lo), "r"(scale_d));
}
template <int TA, int SBO>
__device__ __forceinline__ void wgmma_ss_n40(float (&d)[20], uint32_t da_lo, uint32_t db_lo, int scale_d) {
    asm volatile(
        "{\n.reg .pred p;\n.reg .b64 da, db;\nsetp.ne.b32 p, %22, 0;\nmov.b64 da, {%20, %23};\nmov.b64 db, {%21, 0x40000040};\n"
        "wgmma.mma_async.sync.aligned.m64n40k16.f32.bf16.bf16 " ACC20_STR ", da, db, p, 1, 1, %24, 0;\n}\n"
        : ACC20(d) : "r"(da_lo), "r"(db_lo), "r"(scale_d), "n"(0x40000000 + SBO / 16), "n"(TA));
}

#define PT(i, th)
struct ChainParams {
    CUtensorMap mapW[3];
    CUtensorMap mapX;
    CUtensorMap mapC;
    CUtensorMap mapWo;
    CUtensorMap mapM;
};
constexpr int CH_BLOCK = 384;
constexpr int CO_WO = 0;
constexpr int CH_XC = 5120, CH_XP = 8 * CH_XC;
constexpr int CO_XB = 65536;
constexpr int CO_OB = CO_XB + 2 * CH_XP;
constexpr int CO_P = CO_OB + 8192;
constexpr int CO_LS = CO_P + 3072;
constexpr int CO_SC = CO_LS + 8 * 1280;
constexpr int CH_TW = 6144 + 8192;
constexpr int CO_T = 21 * 8192;
constexpr int CO_WA = CO_T + 6144;
constexpr int CO_ST = CO_T + 3 * CH_TW + 6144;
constexpr int CO_OWN = CO_ST + 4096, CO_OWN2 = CO_SC + 1536;
constexpr int CO_BAR = CO_OWN + 4096;
constexpr int CH_SMEM = CO_BAR + 256 + DBG_EXTRA;
#define CH_NSM 4
static_assert(CO_OWN2 + 1024 <= CO_T && CH_NSM <= 4, "smem layout");
#define CH_POLL_DELAY 200
#define CH_VPOS 2
#define CH_OW 12
#define CH_OF 12
#define CH_Q0 0
#define CH_QI 12
#define CH_QX 0
#define CH_Q1 (CH_Q0 + CH_QI + CH_QX)
#define CH_VA 5
#define CH_SPOS 0
#define CH_LSW 1
#define CH_QE 32
#define CH_KE 32
#define CH_QD 0
#define CH_GAP 0
#define CH_QS (CH_Q1 + 6)
#define CH_KS 10
#define CH_VS 0
#define CH_A7 7
#define CH_RF 0
#define CH_LSS 2
#define CH_OS 1
#define CH_MS 1
#define CH_HA 15
#define CH_LD 4
#define CH_TWP 0
#define CH_DRY 1
#define CH_D1 3000
#define CH_D2 10000
#define CH_CHAINS 4

constexpr float CH_SC = 0.08838834764831845f * 1.4426950408889634f;
__device__ __forceinline__ uint32_t pin(uint32_t v) { return __shfl_sync(0xffffffff, v, threadIdx.x & 31); }

__global__ void __cluster_dims__(8, 1, 1) __launch_bounds__(CH_BLOCK, 1)
chain_kernel(const __grid_constant__ ChainParams P) {
    extern __shared__ uint8_t smem_raw[];
    const int tid = threadIdx.x, warp = __shfl_sync(0xffffffff, tid >> 5, 0), lane = tid & 31;
    const int rank = (int)cluster_ctarank();
    constexpr uint32_t sd = 1024;
    const uint32_t sb = ((uint32_t)rank << 24) + sd;
    if (smem_u32(smem_raw) != sb) __trap();
    const int C = blockIdx.x >> 3;
    const int h = C * 4 + (rank >> 1);
    const int qd = lane >> 2, qc = lane & 3;
    const int t4 = warp & 3, wg = warp >> 2;
    pdl_launch_dependents();
    uint32_t t_start;
    asm volatile("mov.u32 %0, %%clock;" : "=r"(t_start));
    t_start = __shfl_sync(0xffffffff, t_start, 0);
    TS_BEGIN(2);
    PT(0, 0);
    const uint32_t bar_mem = sb + CO_BAR, bar_o = bar_mem + 32, bar_sc = bar_o + 32, bar_x = bar_sc + 8, bar_l = bar_x + 16, bar_w = bar_l + 8;
    const uint32_t bar_wo = bar_o + 24;
    auto chunk = [&](int i) { return (uint32_t)((rank - (i >> 1) - 4 * (i & 1)) & 7); };
    const int wcol = h * HD + (rank & 1) * 64;
    auto wdst = [&](int g, int i) { return i == 0 ? CO_WA + g * CH_TW : g && i == 7 ? CO_ST : (g ? CO_XB + CH_XP : 0) + (i - 1) * 8192; };
    if ((tid & 127) == 0) {
        const uint32_t bar = wg == 2 ? bar_x : bar_w + 8 * wg;
        mbar_init(bar, 1);
        asm volatile("fence.mbarrier_init.release.cluster;" ::: "memory");
        mbar_expect_tx(bar, wg == 2 ? CH_XP : 65536);
#pragma unroll 1
        for (int i = 0; i < 8; i++) {
            if (wg == 2) {
                tma_load_2d(sb + CO_XB + i * CH_XC, &P.mapX, bar, i * 64, 0);
                tma_load_2d(sb + CO_XB + i * CH_XC + 4096, &P.mapM, bar, i * 64, 0);
            } else tma_load_2d(sb + wdst(wg, i), &P.mapW[wg], bar, wcol, chunk(i) * 64);
        }
    }
    if (warp == 9 && lane < 15 && lane != 9 && (lane >> 1) != 6) {
        mbar_init(bar_mem + 8 * lane, 1);
        sts128(bar_mem + 128, 0xffff0000u, 0u, 0u, 0u);
        asm volatile("fence.mbarrier_init.release.cluster;" ::: "memory");
    }
    __syncthreads();
    PT(1, 0);
    if (wg == 2) {
        const int t = tid - 256;
        asm volatile("bar.arrive 10, 384;" ::: "memory");
        sts128(sb + CO_T + (2 + (t >> 6)) * CH_TW + 5120 + (t & 63) * 16, 0u, 0u, 0u, 0u);
        if (t < 32) sts128(sb + CO_P + (t >> 3) * 768 + 640 + (t & 7) * 16, 0u, 0u, 0u, 0u);
    }
    const uint32_t wfrag = (((lane >> 4) << 3) + (lane & 7)) * 128 + (((t4 * 2 + ((lane >> 3) & 1)) ^ (lane & 7)) << 4);
    const uint32_t aO = pin(sb + wg * CH_TW + wfrag);
    const uint32_t aL = pin(sb + lane * 16);
    uint32_t w[32][4];
    auto load_w = [&](int g) {
#pragma unroll
        for (int e = CH_NSM; e < 32; e++) ldmatrix_x4_trans(w[e][0], w[e][1], w[e][2], w[e][3], aO + (wdst(g, e >> 2) - g * CH_TW + (e & 3) * 2048));
        fence_async_smem();
    };
    auto pass = [&](auto& d, int g, int b, int j0, int j1, int js, bool group = true) {
        const uint32_t lo = desc_lo(sd + CO_XB + b * CH_XP, 16);
        if (group) wgmma_fence();
#pragma unroll
        for (int j = 0; j < 32; j++) if (j >= j0 && j < j1) {
            const int e = j < js ? j + CH_NSM : j < js + CH_NSM ? j - js : j;
            const uint32_t db = lo + chunk(e >> 2) * (CH_XC / 16) + (e & 3) * 2, da = desc_lo(sd + CO_WA + g * CH_TW + e * 2048, 16);
            if constexpr (sizeof(d) == 64) { if (e < CH_NSM) wgmma_ss_n32(d, da, db, j != 0); else wgmma_rs_n32(d, w[e], db, j != 0); }
            else { if (e < CH_NSM) wgmma_ss_n40<1, 1024>(d, da, db, j != 0); else wgmma_rs_n40(d, w[e], db, j != 0); }
        }
        if (group) wgmma_commit();
    };
    auto uni = [](uint32_t v) { return __shfl_sync(0xffffffff, v, 0); };
    auto roff = [&](int j) { return (uint32_t)(((rank + j) & 7) - rank) << 24; };
    auto store32 = [&](const float* d, uint32_t a) {
        stmatrix_x4_trans(a, pack_bf16(d[0], d[1]), pack_bf16(d[2], d[3]), pack_bf16(d[4], d[5]), pack_bf16(d[6], d[7]));
        stmatrix_x4_trans(a + 2048, pack_bf16(d[8], d[9]), pack_bf16(d[10], d[11]), pack_bf16(d[12], d[13]), pack_bf16(d[14], d[15]));
    };
    auto scores = [&](float (&d)[20], auto sbo, uint32_t q) {
        wgmma_fence();
#pragma unroll
        for (int ks = 0; ks < 4; ks++) wgmma_ss_n40<0, decltype(sbo)::value>(d, desc_lo(sd + CO_T + q, 16) + ks * 2, desc_lo(sd + CO_T + CH_TW, 16) + ks * 2, ks != 0);
        wgmma_commit();
    };
    auto own_scores = [&](const float (&d)[20], float (&v)[10]) {
#pragma unroll
        for (int j = 0; j < 5; j++) { v[2 * j] = d[4 * j]; v[2 * j + 1] = d[4 * j + 1]; }
    };
    auto add_scores = [&](uint32_t a, uint32_t b, float (&v)[10]) {
        const uint4 a0 = lds128(a), a1 = lds128(a + 512);
        const float2 a2 = lds64f(b);
        v[0] += __uint_as_float(a0.x); v[1] += __uint_as_float(a0.y); v[2] += __uint_as_float(a0.z); v[3] += __uint_as_float(a0.w);
        v[4] += __uint_as_float(a1.x); v[5] += __uint_as_float(a1.y); v[6] += __uint_as_float(a1.z); v[7] += __uint_as_float(a1.w);
        v[8] += a2.x; v[9] += a2.y;
    };
    auto row_max = [&](const float (&v)[10]) {
        float mx = fmaxf(fmaxf(fmaxf(v[0], v[1]), fmaxf(v[2], v[3])), fmaxf(fmaxf(v[4], v[5]), fmaxf(v[6], v[7])));
        mx = fmaxf(mx, fmaxf(v[8], v[9]));
        mx = fmaxf(mx, __shfl_xor_sync(0xffffffff, mx, 1));
        return fmaxf(mx, __shfl_xor_sync(0xffffffff, mx, 2)) * CH_SC;
    };
    auto signal_ctx = [&](int m0, int m1) {
        for (int m = m0; m < m1; m++) asm volatile("red.relaxed.gpu.global.add.u32 [%0], 1;" :: "l"(&g_ctr[CT_CB + m]) : "memory");
    };
    auto signal_step = [](int s) { return s == 33 || s == 49 || s == 57 || s == 61; };
    if (mapa_u32(bar_l, rank ^ 1) != (bar_l ^ (1u << 24)) || mapa_u32(bar_l, (rank + 3) & 7) != bar_l + roff(3)) __trap();
    asm volatile("bar.sync %0, 128;" :: "r"(12 + wg) : "memory");
    if (wg < 2) {
#pragma unroll 1
        for (int rep = CH_DRY ? 0 : 1; rep < 2; rep++) {
            if (rep) mbar_wait(bar_w + 8 * wg, 0);
            PT(3, 0);
            load_w(wg);
            if (rep) {
                asm volatile("bar.arrive %0, 160;" :: "r"(wg ? 2 : 15) : "memory");
                asm volatile("barrier.cluster.arrive.relaxed.aligned;" ::: "memory");
                mbar_wait(bar_x, 0);
            }
            asm volatile("bar.sync %0, 128;" :: "r"(12 + wg) : "memory");
            PT(7, 0);
            float d[16];
            pass(d, wg, 0, 0, 32, 0);
            wgmma_wait<0>();
            store32(d, aO + CO_T);
        }
    }
    PT(8, 0);
    TS_BEGIN(5);
    PT(9, 0);

    if (wg < 2) {
        const uint32_t aM = pin(sb + CO_XB + 4096 + (lane & 7) * 128 + (((lane >> 3) ^ (lane & 7)) << 4));
        uint32_t coff[8];
#pragma unroll
        for (int i = 0; i < 8; i++) coff[i] = uni(chunk(i) * CH_XC);
        auto mem_proj = [&](int s, int it) {
            const uint32_t par = s & 1;
            float acc[CH_CHAINS][4];
#pragma unroll
            for (int i = 0; i < CH_CHAINS; i++) acc[i][0] = acc[i][1] = acc[i][2] = acc[i][3] = 0.f;
            const uint32_t am = aM + par * CH_XP;
            uint32_t b[CH_LD][4], ok[4] = {1, 1, 1, 1}, a0 = am, a1 = am ^ 64;
            auto load = [&](int i) {
                if (i == 12) DBG(13, 0);
                if (i == 2 || (i && !(i & 3))) { a0 = ok[i >> 2] ? am : aL; a1 = a0 ^ 64; }
                uint32_t* r = b[i % CH_LD];
                ldmatrix_x4(r[0], r[1], r[2], r[3], ((i & 1) ? a1 : a0) + coff[i >> 1]);
                if (i == 1) ok[0] = mbar_try(bar_mem, par ^ 1);
                if (i == 2 || i == 4 || i == 8) ok[(i >> 2) + 1] = mbar_try(bar_mem + 8 * ((i >> 2) + 1), par ^ 1);
            };
            auto mma = [&](int i) {
                mma_16816(acc[(2 * i) % CH_CHAINS], w[2 * i][0], w[2 * i][1], w[2 * i][2], w[2 * i][3], b[i % CH_LD][0], b[i % CH_LD][1]);
                mma_16816(acc[(2 * i + 1) % CH_CHAINS], w[2 * i + 1][0], w[2 * i + 1][1], w[2 * i + 1][2], w[2 * i + 1][3], b[i % CH_LD][2], b[i % CH_LD][3]);
            };
#pragma unroll
            for (int e = 0; e < CH_NSM; e++) ldmatrix_x4_trans(w[e][0], w[e][1], w[e][2], w[e][3], aO + CO_WA + e * 2048);
            asm volatile("{\n.reg .pred p;\nsetp.eq.s32 p, %0, 0;\n@p bar.sync 10, 384;\n}" :: "r"(it) : "memory");
            DBG(11, 0);
            bool done = false;
            load(0); load(1); mma(0); mma(1);
            load(2); load(3); mma(2);
#pragma unroll
            for (int i = 4; i < 3 + CH_LD; i++) load(i);
#pragma unroll
            for (int i = 3; i < 16; i++) {
                mma(i);
                if (i + CH_LD < 16) load(i + CH_LD);
                if (i == 12 - CH_LD) done = __all_sync(0xffffffff, ok[0] & ok[1] & ok[2] & ok[3]);
                if (i == CH_HA) asm volatile("{\n.reg .pred p;\nsetp.ne.b32 p, %0, 0;\n@p bar.arrive 5, 384;\n}" :: "r"((int)done) : "memory");
            }
#pragma unroll
            for (int i = 0; i < 4; i++)
#pragma unroll
                for (int c = 1; c < CH_CHAINS; c++) acc[0][i] += acc[c][i];
            const uint32_t r0 = pack_bf16(acc[0][0], acc[0][1]);
            const uint32_t r1 = pack_bf16(acc[0][2], acc[0][3]);
            DBGD(40 + warp, warp, r0 ^ r1);
            stmatrix_x2_trans(aO + CO_T + 4096, r0, r1);
            fence_async_smem();
            return done;
        };
        if (wg == 0) {
#pragma unroll 1
            for (int s = 0; s < NSEG; s++) {
                const uint32_t par = s & 1;
#pragma unroll 1
                for (int it = 0; it < WAIT_LIMIT / 64; it++) if (mem_proj(s, it)) break;
                asm volatile("bar.arrive 1, 256;" ::: "memory");
                if (s == NSEG - 1) break;
                if (tid == 96) {
#pragma unroll
                    for (int j = 0; j < 4; j++) { mbar_expect_tx(bar_mem + 8 * j, j ? 2048 : 1024); if (j < 3) mbar_expect_tx(bar_o + 8 * j, 1024 << j); }
                }
                __syncwarp();
                uint32_t* wp = g_xbuf + (size_t)rank * 2048 + C * 256 + qc * 64 + t4 * 8 + qd;
                asm volatile("st.relaxed.gpu.global.u32 [%0], %1;" :: "l"(wp + ((s + 2) & 3) * 16384), "r"(~0u) : "memory");
                asm volatile("st.relaxed.gpu.global.u32 [%0], %1;" :: "l"(wp + ((s + 2) & 3) * 16384 + 32), "r"(~0u) : "memory");
                if (s == 0) {
                    asm volatile("barrier.cluster.wait.aligned;" ::: "memory");
                    mbar_wait(bar_wo, 0);
                    const int sr = (qd >> 2) * 2 + (qd & 1) + (qd & 2) * 4;
#pragma unroll 2
                    for (int ks = t4; ks < 32; ks += 4) {
                        const uint32_t a = sb + CO_WO + ks * 2048;
                        uint4 u[2][2];
#pragma unroll
                        for (int i = 0; i < 4; i++) { const int r = sr + (i >> 1) * 4; u[i >> 1][i & 1] = lds128(a + r * 128 + (((qc * 2 + (i & 1)) ^ (r & 7)) << 4)); }
                        __syncwarp();
#pragma unroll
                        for (int i = 0; i < 4; i++) {
                            const uint4 u0 = u[i >> 1][0], u1 = u[i >> 1][1];
                            const uint32_t sel = (i & 1) ? 0x7632 : 0x5410;
                            sts128(a + (qd + (i >> 1) * 8) * 128 + (((qc * 2 + (i & 1)) ^ qd) << 4),
                                   __byte_perm(u0.x, u0.y, sel), __byte_perm(u0.z, u0.w, sel), __byte_perm(u1.x, u1.y, sel), __byte_perm(u1.z, u1.w, sel));
                        }
                    }
                    fence_async_smem();
                }
                mbar_wait(bar_x + 8 * (par ^ 1), ((s + 1) >> 1) & 1);
                asm volatile("bar.sync 7, 384;" ::: "memory");
                float d[16];
                float c[4];
                const uint32_t alo = desc_lo(sd + CO_WO, 16), blo = desc_lo(sd + CO_OB, 128);
                wgmma_fence();
                pass(d, 0, par ^ 1, 0, CH_Q0, CH_QS, false);
                asm volatile("bar.sync 11, 256;" ::: "memory");
#pragma unroll
                for (int i = 0; i < 32; i++) {
                    if (i == 4) { pass(d, 0, par ^ 1, CH_Q0 + min(4, CH_QI), CH_Q0 + min(4, CH_QI) + CH_QX, CH_QS, false); mbar_wait_cl(bar_o, par); }
                    if (i == 8) mbar_wait_cl(bar_o + 8, par);
                    if (i == CH_OW) mbar_wait_cl(bar_o + 16, par);
                    wgmma_ss_n8(c, alo + i * 128, blo + i * 16, i != 0);
                    if (i < CH_QI) pass(d, 0, par ^ 1, CH_Q0 + i + (i < 4 ? 0 : CH_QX), CH_Q0 + i + (i < 4 ? 0 : CH_QX) + 1, CH_QS, false);
                }
                wgmma_commit();
                wgmma_wait<0>();
                asm volatile("st.relaxed.gpu.global.u32 [%0], %1;" :: "l"(wp + (s & 3) * 16384), "r"(pack_bf16(c[0], c[2])) : "memory");
                asm volatile("st.relaxed.gpu.global.u32 [%0], %1;" :: "l"(wp + (s & 3) * 16384 + 32), "r"(pack_bf16(c[1], c[3])) : "memory");
                asm volatile("bar.arrive 6, 384;" ::: "memory");
                pace(CH_QD);
                asm volatile("bar.arrive 4, 384;" ::: "memory");
                DBG(8, 0);
                pass(d, 0, par ^ 1, CH_Q1, CH_QE, CH_QS);
                DBG(21, 0);
                if (tid == 0 && s + 2 < NSEG) {
                    mbar_expect_tx(bar_x + 8 * par, 32768);
                    tma_load_2d_mc(sb + CO_XB + par * CH_XP + rank * CH_XC, &P.mapX, bar_x + 8 * par, rank * 64, (s + 2) * SEGL, (uint16_t)0xff);
                }
                __syncwarp();
                asm volatile("bar.sync 9, 256;" ::: "memory");
                wgmma_wait<0>();
                DBG(0, 0);
                store32(d, aO + CO_T);
                DBG(22, 0);
            }
            *reinterpret_cast<uint2*>(g_xbuf + 16384 + blockIdx.x * 256 + tid * 2) = make_uint2(~0u, ~0u);
        } else {
            const uint32_t usc = uni(CO_SC + min(t4, 2) * 512 + roff((rank ^ 1) - rank)), uscb = uni(bar_sc ^ (1u << 24));
            const uint32_t vaddr = pin(sb + CO_T + 2 * CH_TW + (lane & 15) * 128 + (((t4 * 2 + (lane >> 4)) ^ (lane & 7)) << 4));
            const uint32_t dsta = pin(sb + CO_OB + t4 * 256 + (qc >> 1) * 128 + qd * 16 + (qc & 1) * 8);
            auto local_pv = [&](int s, int st) {
                float dc[16];
                wgmma_fence();
#pragma unroll
                for (int ks = 0; ks < 3; ks++) wgmma_ss_n32_p(dc, desc_lo(sd + CO_T + (2 + (s & 1)) * CH_TW + ks * 2048, 16), desc_lo(sd + CO_P + ks * 256, 128), ks != 0);
                wgmma_commit();
                wgmma_wait<0>();
                store32(dc, aO - CH_TW + st);
            };
            auto store_ctx = [&](int s, int st) {
                if (tid == 128 && s >= 0) {
                    tma_store_2d(&P.mapC, sb + st, (rank & 1) * 64, h * SEQ + s * SEGL);
                    asm volatile("cp.async.bulk.commit_group;" ::: "memory");
                }
                __syncwarp();
            };
            uint32_t uo[8], ub[8];
#pragma unroll
            for (int i = 0; i < 8; i++) { uo[i] = uni(roff(i) + i * 1024); ub[i] = uni(roff(i) + bar_o + (i < 2 ? 0 : i < 4 ? 8 : 16)); }
#pragma unroll 1
            for (int s = 0; s < NSEG; s++) {
                const uint32_t par = s & 1;
#pragma unroll 1
                for (int it = 0; it < WAIT_LIMIT / 64; it++) if (mem_proj(s, it)) break;
                asm volatile("bar.sync 1, 256;" ::: "memory");
                float d[20];
                scores(d, std::integral_constant<int, 0>(), 4096);
                if (s == NSEG - 1) { wgmma_wait<0>(); break; }
                asm volatile("bar.arrive 8, 256;" ::: "memory");
                if (s == 0) asm volatile("barrier.cluster.wait.aligned;" ::: "memory");
                wgmma_wait<0>();
                {
                    const bool w0 = t4 == 0;
                    asm volatile("{\n.reg .pred p, q;\nsetp.lt.s32 p, %8, 2;\nsetp.eq.s32 q, %8, 2;\n"
                                 "@p st.async.weak.shared::cluster.mbarrier::complete_tx::bytes.v4.f32 [%0], {%2, %3, %4, %5}, [%1];\n"
                                 "@q st.async.weak.shared::cluster.mbarrier::complete_tx::bytes.v2.f32 [%0], {%6, %7}, [%1];\n}"
                                 :: "r"((aL | (s >> 10)) + usc), "r"(uscb), "f"(w0 ? d[0] : d[8]), "f"(w0 ? d[1] : d[9]),
                                    "f"(w0 ? d[4] : d[12]), "f"(w0 ? d[5] : d[13]), "f"(d[16]), "f"(d[17]), "r"(t4) : "memory");
                }
                DBG(3, 4);
                store_ctx(s - 2, CO_ST);
                uint32_t vb[3][4];
                auto load_v = [&]() {
                    asm volatile("bar.sync 3, 256;" ::: "memory");
#pragma unroll
                    for (int k = 0; k < 3; k++) ldmatrix_x4_trans(vb[k][0], vb[k][1], vb[k][2], vb[k][3], vaddr + par * CH_TW + k * 2048);
                };
                mbar_wait_cl(bar_sc, par);
                DBG(4, 4);
                float v[10];
                own_scores(d, v);
                add_scores(aL + CO_SC, aL + CO_SC + 1024, v);
                const float mx = row_max(v);
                if (CH_VPOS == 2) load_v();
#pragma unroll
                for (int j = 0; j < 10; j++) v[j] = ex2f(fmaf(v[j], CH_SC, -mx));
                uint32_t p[5];
#pragma unroll
                for (int j = 0; j < 5; j++) p[j] = pack_bf16(v[2 * j], v[2 * j + 1]);
                if (CH_VPOS == 3) load_v();
                DBG(19, 4);
                float c0[4] = {0.f, 0.f, 0.f, 0.f}, c1[4] = {0.f, 0.f, 0.f, 0.f}, cs[4] = {0.f, 0.f, 0.f, 0.f};
#pragma unroll
                for (int k = 0; k < 3; k++) {
                    const uint32_t p0 = p[2 * k], p1 = k < 2 ? p[2 * k + 1] : 0u;
                    mma_16816(cs, p0, 0u, p1, 0u, 0x3f803f80u, 0x3f803f80u);
                    mma_16816(c0, p0, 0u, p1, 0u, vb[k][0], vb[k][1]);
                    mma_16816(c1, p0, 0u, p1, 0u, vb[k][2], vb[k][3]);
                }
                float inv;
                asm volatile("rcp.approx.ftz.f32 %0, %1;" : "=f"(inv) : "f"(cs[0]));
                const uint32_t b0 = pack_bf16(c0[0] * inv, c0[1] * inv), b1 = pack_bf16(c1[0] * inv, c1[1] * inv);
                DBG(20, 4);
#pragma unroll
                for (int i = 1; i < 8; i++) {
                    st_async_v2((dsta | (s >> 10)) + uo[i], b0, b1, ub[i]);
                    if (i == CH_OS) asm volatile("st.shared.v2.b32 [%0], {%1, %2};" :: "r"(dsta), "r"(b0), "r"(b1) : "memory");
                }
                DBG(5, 4);
                asm volatile("cp.async.bulk.wait_group.read 0;" ::: "memory");
                asm volatile("bar.sync 7, 384;" ::: "memory");
                fence_async_smem();
                asm volatile("bar.arrive 11, 256;" ::: "memory");
                local_pv(s + 1, CO_ST);
                asm volatile("bar.arrive 6, 384;" ::: "memory");
                if (tid == 128) mbar_expect_tx(bar_sc, 1280);
                __syncwarp();
                mbar_wait(bar_x + 8 * (par ^ 1), ((s + 1) >> 1) & 1);
                asm volatile("bar.sync 4, 384;" ::: "memory");
                float dk[16];
                pass(dk, 1, par ^ 1, 0, CH_KE, CH_KS);
                if (tid == 128 && signal_step(s)) {
                    asm volatile("cp.async.bulk.wait_group 0;" ::: "memory");
                    signal_ctx((2 * s - 66) >> 2, s >> 2);
                }
                __syncwarp();
                DBG(1, 4);
                wgmma_wait<0>();
                DBG(2, 4);
                store32(dk, aO + CO_T);
                DBG(29, 4);
            }
            asm volatile("bar.sync 8, 256;" ::: "memory");
            store_ctx(NSEG - 3, CO_ST);
#pragma unroll 1
            for (int i = 0; i < 2; i++) {
                local_pv(i, CO_OB + i * 4096);
                fence_async_smem();
                if (i == 0) asm volatile("bar.arrive 9, 256;" ::: "memory");
                asm volatile("bar.sync 2, 128;" ::: "memory");
                store_ctx(NSEG - 2 + i, CO_OB + i * 4096);
                if (i == 0) asm volatile("bar.sync 3, 256;" ::: "memory");
            }
            if (tid == 128) {
                asm volatile("cp.async.bulk.wait_group 0;" ::: "memory");
                PT(14, 128);
                signal_ctx(15, 16);
                PT(15, 128);
            }
        }
        PT(10, 0);
    } else {
        float gs;
        auto load_gate = [&](int s) { asm volatile("ld.global.cg.f32 %0, [%1];" : "=f"(gs) : "l"(g_gate + s * SEGL + t4 * 8 + qd) : "memory"); };
        auto softmax = [&](int s) {
            float v[10];
            {
                const uint4 a0 = lds128(aL + CO_OWN + t4 * 1024), a1 = lds128(aL + CO_OWN + t4 * 1024 + 512);
                const float2 a2 = lds64f(aL + CO_OWN2 + t4 * 256 - lane * 8);
                v[0] = __uint_as_float(a0.x); v[1] = __uint_as_float(a0.y); v[2] = __uint_as_float(a0.z); v[3] = __uint_as_float(a0.w);
                v[4] = __uint_as_float(a1.x); v[5] = __uint_as_float(a1.y); v[6] = __uint_as_float(a1.z); v[7] = __uint_as_float(a1.w);
                v[8] = a2.x; v[9] = a2.y;
            }
            mbar_wait_cl(bar_l, s & 1);
            add_scores(aL + t4 * 1024 + CO_LS + (s & 1) * 5120, aL + t4 * 256 - lane * 8 + CO_LS + (s & 1) * 5120 + 4096, v);
            const int lim = t4 * 8 + qd - 2 * qc;
#pragma unroll
            for (int j = 0; j < 8; j++) if ((j >> 1) * 8 + (j & 1) > lim) v[j] = -INFINITY;
            const float mx = row_max(v);
#pragma unroll
            for (int j = 0; j < 10; j++) v[j] = ex2f(fmaf(v[j], CH_SC, -mx));
            float sum = (((v[0] + v[1]) + (v[2] + v[3])) + ((v[4] + v[5]) + (v[6] + v[7]))) + (v[8] + v[9]);
            sum += __shfl_xor_sync(0xffffffff, sum, 1);
            sum += __shfl_xor_sync(0xffffffff, sum, 2);
            asm("rcp.approx.ftz.f32 %0, %0;" : "+f"(sum));
            sum *= 1.f - gs;
            const uint32_t pa = aL + CO_P + t4 * 768;
            stmatrix_x4(pa, pack_bf16(v[0] * sum, v[1] * sum), pack_bf16(v[2] * sum, v[3] * sum), pack_bf16(v[4] * sum, v[5] * sum), pack_bf16(v[6] * sum, v[7] * sum));
            asm volatile("stmatrix.sync.aligned.m8n8.x1.shared.b16 [%0], {%1};" :: "r"(pa + 512), "r"(pack_bf16(v[8] * sum, v[9] * sum)) : "memory");
        };
        uint32_t um[8], ub[8];
#pragma unroll
        for (int i = 0; i < 8; i++) { um[i] = uni(roff((i & 1) * 4 + (i >> 1))); ub[i] = uni(roff((i & 1) * 4 + (i >> 1)) + bar_mem + 8 * (i >> 1)); }
        const uint8_t* mkp = smem_raw + CO_BAR + 128;
        asm volatile("" : "+l"(mkp));
        gs = 0.f;
#pragma unroll 1
        for (int s = 0; s < NSEG; s++) {
            const uint32_t par = s & 1;
            const bool last = s == NSEG - 1;
            if (s == 1) { wait_ctr(CT_GATE, 256u); load_gate(0); }
            softmax(s - 1);
            load_gate(s);
            if (s == 0) {
                PT(2, 256);
                int lane;
                asm volatile("mov.u32 %0, %%laneid;" : "=r"(lane));
                if (t4 >= 2) {
                    const CUtensorMap* map = t4 == 2 ? &P.mapWo : &P.mapW[2];
                    const uint32_t bar = t4 == 2 ? bar_wo : bar_w + 16;
                    const int c0 = t4 == 2 ? rank * 64 : wcol;
                    auto row = [&](int i) { return t4 == 2 ? C * 512 + ((rank - i) & 7) * 64 : (int)chunk(i) * 64; };
                    uint32_t now;
                    do { asm volatile("mov.u32 %0, %%clock;" : "=r"(now)); } while (now - t_start < (uint32_t)(t4 == 2 ? CH_D2 : CH_D1));
                    if (lane == 0) {
#pragma unroll 1
                        for (int i = 0; i < 8; i++) asm volatile("cp.async.bulk.prefetch.tensor.2d.L2.global [%0, {%1, %2}];" :: "l"(map), "r"(c0), "r"(row(i)) : "memory");
                        mbar_expect_tx(bar, 65536);
                    }
                    __syncwarp();
                    asm volatile("bar.sync %0, 160;" :: "r"(t4 == 2 ? 15 : 2) : "memory");
                    if (lane == 0) {
#pragma unroll 1
                        for (int i = 0; i < 8; i++) tma_load_2d(sb + (t4 == 2 ? CO_WO + i * 8192 : wdst(2, i)), map, bar, c0, row(i));
                    }
                } else if (t4 == 0 && lane == 0) {
                    asm volatile("cp.async.bulk.prefetch.tensor.2d.L2.global [%0, {%1, %2}];" :: "l"(&P.mapX), "r"(rank * 64), "r"(SEGL) : "memory");
                    asm volatile("prefetch.tensormap [%0];" :: "l"(&P.mapC) : "memory");
                    mbar_expect_tx(bar_sc, 1280);
                    mbar_expect_tx(bar_x + 8, 32768);
                }
                __syncwarp();
                mbar_wait(bar_w + 16, 0);
                PT(4, 256);
                load_w(2);
                asm volatile("bar.sync 14, 128;" ::: "memory");
                asm volatile("barrier.cluster.arrive.relaxed.aligned;" ::: "memory");
                if (t4 == 0 && lane == 0) {
#pragma unroll 1
                    for (int i = 0; i < 8; i++) tma_load_2d(sb + CO_XB + CH_XP + i * CH_XC, &P.mapX, bar_x + 8, i * 64, SEGL);
                }
                __syncwarp();
                PT(6, 256);
            }
            DBG(7, 8);
#pragma unroll 1
            for (int it = 0; it < (CH_RF ? WAIT_LIMIT / 64 : 0); it++)
                if (mbar_try(bar_mem, par ^ 1) & mbar_try(bar_mem + 8, par ^ 1) & mbar_try(bar_mem + 16, par ^ 1) & mbar_try(bar_mem + 24, par ^ 1)) break;
            fence_async_smem();
            asm volatile("bar.sync 5, 384;" ::: "memory");
            DBG(23, 8);
            float d[20];
            pass(d, 2, par, 0, CH_VA, CH_VS);
            asm volatile("bar.sync 8, 256;" ::: "memory");
            pass(d, 2, par, CH_VA, 32, CH_VS);
            wgmma_wait<0>();
            stmatrix_x2_trans(aO + par * CH_TW + CO_T + 4096, pack_bf16(d[16], d[17]), pack_bf16(d[18], d[19]));
            store32(d, aO + par * CH_TW + CO_T);
            DBG(24, 8);
            if (!last) asm volatile("bar.arrive 3, 256;\nbar.sync 7, 384;" ::: "memory");
            scores(d, std::integral_constant<int, 512>(), 0);
            asm volatile("{\n.reg .pred p;\nsetp.eq.s32 p, %1, 256;\n@p mbarrier.arrive.expect_tx.shared::cta.b64 _, [%0], 5120;\n}" :: "r"(bar_l), "r"(tid) : "memory");
            wgmma_wait<0>();
            auto send_scores = [&]() {
                const uint32_t a = aL + t4 * 1024, a2 = aL + t4 * 256 - lane * 8, r = roff((rank ^ 1) - rank) + CO_LS + par * 5120;
                asm volatile("st.async.weak.shared::cluster.mbarrier::complete_tx::bytes.v4.f32 [%0], {%3, %4, %5, %6}, [%2];\n"
                             "st.async.weak.shared::cluster.mbarrier::complete_tx::bytes.v4.f32 [%0 + 512], {%7, %8, %9, %10}, [%2];\n"
                             "st.async.weak.shared::cluster.mbarrier::complete_tx::bytes.v2.f32 [%1], {%11, %12}, [%2];"
                             :: "r"(a + r), "r"(a2 + r + 4096), "r"(bar_l ^ (1u << 24)), "f"(d[0]), "f"(d[1]), "f"(d[4]), "f"(d[5]),
                                "f"(d[8]), "f"(d[9]), "f"(d[12]), "f"(d[13]), "f"(d[16]), "f"(d[17]) : "memory");
                sts128(a + CO_OWN, __float_as_uint(d[0]), __float_as_uint(d[1]), __float_as_uint(d[4]), __float_as_uint(d[5]));
                sts128(a + CO_OWN + 512, __float_as_uint(d[8]), __float_as_uint(d[9]), __float_as_uint(d[12]), __float_as_uint(d[13]));
                asm volatile("st.shared.v2.f32 [%0], {%1, %2};" :: "r"(a2 + CO_OWN2), "f"(d[16]), "f"(d[17]) : "memory");
            };
            if (s == 0) asm volatile("barrier.cluster.wait.aligned;" ::: "memory");
            if (CH_LSS == 0) send_scores();
            if (last) { if (CH_LSS) send_scores(); break; }
            asm volatile("bar.arrive 4, 384;\nbar.arrive 9, 256;\nbar.sync 6, 384;" ::: "memory");
            if (CH_LSS == 1) send_scores();
            const uint2* xb = reinterpret_cast<const uint2*>(g_xbuf + (s & 3) * 16384 + (size_t)rank * 2048 + t4 * 64) + lane;
            uint2 p[8], q[8];
            pace(CH_POLL_DELAY);
#pragma unroll
            for (int k = 0; k < 8; k++)
                asm volatile("ld.relaxed.gpu.global.v2.u32 {%0, %1}, [%2];" : "=r"(p[k].x), "=r"(p[k].y) : "l"(xb + k * 128) : "memory");
            DBG(17, 8);
            if (CH_LSS == 2) send_scores();
            {
                uint32_t z;
                asm volatile("mov.u32 %0, %%clock;" : "=r"(z) :: "memory");
#pragma unroll
                for (int i = 0; i < CH_GAP; i++) asm volatile("mul.lo.u32 %0, %0, %0;" : "+r"(z));
                asm volatile("and.b32 %0, %0, %1;" : "+r"(z) : "r"(s >> 10));
                xb += z;
            }
#pragma unroll
            for (int k = 0; k < 8; k++)
                asm volatile("ld.relaxed.gpu.global.v2.u32 {%0, %1}, [%2];" : "=r"(q[k].x), "=r"(q[k].y) : "l"(xb + k * 128) : "memory");
            const int row = t4 * 2 + (lane >> 4);
            const uint32_t dsta = pin(sb + CO_XB + (par ^ 1) * CH_XP + rank * CH_XC + 4096 + row * 128 + ((((lane & 15) >> 1) ^ row) << 4) + (lane & 1) * 8);
            const uint32_t dst1 = pin(dsta + um[1]), bar1 = pin(ub[1] | (s >> 10));
            uint32_t m0, m1, mk;
            asm volatile("ld.relaxed.gpu.u32 %0, [%1];" : "=r"(mk) : "l"(mkp) : "memory");
            auto sum = [&](const uint2 (&p)[8]) {
                auto lo = [&](uint32_t u) { return __uint_as_float(u * (0u - mk)); };
                auto hi = [&](uint32_t u) { return __uint_as_float(u & mk); };
                const float s0 = ((lo(p[0].x) + lo(p[1].x)) + (lo(p[2].x) + lo(p[3].x))) + ((lo(p[4].x) + lo(p[5].x)) + (lo(p[6].x) + lo(p[7].x)));
                const float s1 = ((lo(p[0].y) + lo(p[1].y)) + (lo(p[2].y) + lo(p[3].y))) + ((lo(p[4].y) + lo(p[5].y)) + (lo(p[6].y) + lo(p[7].y)));
                m0 = pack_bf16(s0, ((hi(p[0].x) + hi(p[1].x)) + (hi(p[2].x) + hi(p[3].x))) + ((hi(p[4].x) + hi(p[5].x)) + (hi(p[6].x) + hi(p[7].x))));
                m1 = pack_bf16(s1, ((hi(p[0].y) + hi(p[1].y)) + (hi(p[2].y) + hi(p[3].y))) + ((hi(p[4].y) + hi(p[5].y)) + (hi(p[6].y) + hi(p[7].y))));
                uint32_t ok;
                asm volatile("{\n.reg .pred p;\nsetp.num.f32 p, %1, %2;\nvote.sync.all.pred p, p, 0xffffffff;\nselp.u32 %0, 1, 0, p;\n}" : "=r"(ok) : "f"(s0), "f"(s1));
                return ok;
            };
            if (!sum(p)) {
                DBG(12, 8);
#pragma unroll 1
                for (int it = 0; it < WAIT_LIMIT / 4; it++) {
                    if (sum(q)) break;
                    uint32_t bad = 0;
#pragma unroll
                    for (int k = 0; k < 8; k++) bad |= (max(q[k].x, q[k].y) == ~0u ? 1u : 0u) << k;
                    if (__all_sync(0xffffffff, bad == 0u)) break;
                    if (it == 0) DBG(14, 8);
                    if (it == 1) DBG(15, 8);
#pragma unroll
                    for (int k = 0; k < 8; k++)
                        if (bad & (1u << k))
                            asm volatile("ld.relaxed.gpu.global.v2.u32 {%0, %1}, [%2];" : "=r"(q[k].x), "=r"(q[k].y) : "l"(xb + k * 128) : "memory");
                }
            }
            DBG(9, 8);
#pragma unroll
            for (int i = 1; i < 8; i++) {
                st_async_v2(i == 1 ? dst1 : dsta + um[i], m0, m1, i == 1 ? bar1 : ub[i]);
                if (i == CH_MS) asm volatile("st.shared.v2.b32 [%0], {%1, %2};\nbar.arrive 10, 384;" :: "r"(dsta), "r"(m0), "r"(m1) : "memory");
            }
            if (s == 1000000) {
#pragma unroll
                for (int k = 0; k < 8; k++) asm volatile("st.volatile.shared.v2.u32 [%0], {%1, %2};" :: "r"(s), "r"(q[k].x), "r"(q[k].y) : "memory");
            }
            DBG(10, 8);
        }
        PT(11, 256);
        asm volatile("bar.sync 9, 256;" ::: "memory");
        softmax(NSEG - 1);
        fence_async_smem();
        asm volatile("bar.arrive 3, 256;" ::: "memory");
    }
    __syncthreads();
    cluster_sync_all();
    TS_END(2);
}

struct Proj2Params {
    CUtensorMap mapA[2];
    CUtensorMap mapW[3];
    bf16* out[3];
};
#define P2T(i)
#define P2_NOMMA 0
#define P2_NOLOAD 0
#define P2_ROT 4
#define P2_NP 1
#define P2_NI 4
constexpr int P2_STAGES = 6;
constexpr int P2_ITEMS = 168 + 48;

__device__ __forceinline__ int p2_reps(int t) { return t >= 168 ? 1 : 2; }
__device__ __forceinline__ void p2_tile(int t, int w, int& z, int& mp, int& head) {
    if (t >= 168) { w += ((t - 168) & 1) * 2; t = 168 + ((t - 168) >> 1); }
    const int hq = (t / 24 + P2_ROT) & 7, v = t % 24;
    mp = v & 7;
    if (v < 16) { head = hq * 4 + (v >> 3) * 2 + (w >> 1); z = 1 + (w & 1); }
    else { head = hq * 4 + w; z = 0; }
}
__device__ __forceinline__ void mbar_arrive_remote(uint32_t bar_cluster_addr) {
    asm volatile("mbarrier.arrive.release.cluster.shared::cluster.b64 _, [%0];" :: "r"(bar_cluster_addr) : "memory");
}
__device__ __forceinline__ void mbar_arrive_cl(uint32_t bar_cluster_addr) {
    asm volatile("mbarrier.arrive.shared::cluster.b64 _, [%0];" :: "r"(bar_cluster_addr) : "memory");
}
__device__ __forceinline__ void mbar_wait_acq_cluster(uint32_t bar, uint32_t parity) {
    asm volatile(
        "{\n"
        ".reg .pred p, q;\n"
        ".reg .u32 c;\n"
        "mov.u32 c, 0;\n"
        "WAIT_LOOP_C:\n"
        "mbarrier.try_wait.parity.acquire.cluster.shared::cta.b64 p, [%0], %1;\n"
        "@p bra WAIT_DONE_C;\n"
        "add.u32 c, c, 1;\n"
        "setp.lt.u32 q, c, 4000000;\n"
        "@q bra WAIT_LOOP_C;\n"
        "WAIT_DONE_C:\n"
        "}\n" :: "r"(bar), "r"(parity) : "memory");
}
__device__ __forceinline__ uint4 quad_transpose(uint32_t p0, uint32_t p1, uint32_t p2, uint32_t p3, int lane) {
    const bool o1 = lane & 1, o2 = lane & 2;
    uint32_t s0 = o1 ? p0 : p1, s1 = o1 ? p2 : p3;
    s0 = __shfl_xor_sync(0xffffffff, s0, 1); s1 = __shfl_xor_sync(0xffffffff, s1, 1);
    const uint32_t a_lo = o1 ? s0 : p0, a_hi = o1 ? p1 : s0, b_lo = o1 ? s1 : p2, b_hi = o1 ? p3 : s1;
    uint32_t t0 = o2 ? a_lo : b_lo, t1 = o2 ? a_hi : b_hi;
    t0 = __shfl_xor_sync(0xffffffff, t0, 2); t1 = __shfl_xor_sync(0xffffffff, t1, 2);
    return o2 ? make_uint4(t0, t1, b_lo, b_hi) : make_uint4(a_lo, a_hi, t0, t1);
}
#define P2_PACE 35
#define P2_PACE2 0
template <bool PERM, int PACE = 0>
__device__ __forceinline__ void store_frag_128(const float (&acc)[64], bf16* obase, int lane) {
#pragma unroll
    for (int rr = 0; rr < 2; rr++)
#pragma unroll
        for (int g = 0; g < 4; g++) {
            const float* a = &acc[g * 16 + rr * 2];
            const uint32_t p0 = pack_bf16(a[0], a[1]), p1 = pack_bf16(a[4], a[5]), p2 = pack_bf16(a[8], a[9]), p3 = pack_bf16(a[12], a[13]);
            *reinterpret_cast<uint4*>(obase + (size_t)(rr * 8) * HD + g * 32) = PERM ? make_uint4(p0, p1, p2, p3) : quad_transpose(p0, p1, p2, p3, lane);
            pace(PACE);
        }
}
struct OutParams {
    CUtensorMap mapCtx[2];
    CUtensorMap mapWo[2];
    CUtensorMap mapOut;
};

#define OT(i)
#define OTP(i, th)
constexpr int O2_STAGES = 4;
#define O2_NL 16
constexpr int O2_GRID = 4 * O2_NL;
#define O2_FINE 8

constexpr uint32_t OB_FULL = 0, OB_EMPTY = 32, OB_ITEM = 64, OB_SLOT = 128, OB_STOP = 160;
__device__ __forceinline__ void out_init(uint32_t bars) {
    for (int i = 0; i < O2_STAGES; i++) {
        mbar_init(bars + OB_FULL + 8 * i, 1); mbar_init(bars + OB_EMPTY + 8 * i, 4); mbar_init(bars + OB_ITEM + 16 * i, 1); mbar_init(bars + OB_ITEM + 16 * i + 8, 1);
    }
    sts128(bars + OB_STOP, 0u, 0u, 0u, 0u);
}
__device__ __forceinline__ void out_map(int cid, int& pt, int& h0) {
    if (cid < 32) { pt = cid < 16 ? cid : 31 - cid; h0 = cid >= 16; }
    else if (cid < 34) { pt = 12 + (cid & 1); h0 = 2; }
    else { pt = 14 + (cid & 1); h0 = 63 - ((cid - 34) >> 1); }
}
__device__ __forceinline__ void out_finished() {
    if (atomicAdd(&g_ctr[CT_FIN], 1u) == M_GRID + O2_GRID - 1)
        for (int i = 0; i < CT_N / 4; i++) reinterpret_cast<uint4*>(g_ctr)[i] = make_uint4(0u, 0u, 0u, 0u);
}
__device__ __forceinline__ void out_producer(const OutParams& P, uint32_t sbase, uint32_t bars, uint32_t rank, int pt, int h0, bool lead, bool LATE, int tnext) {
    const uint32_t bar_full = bars + OB_FULL, bar_empty = bars + OB_EMPTY, bar_item = bars + OB_ITEM, slot = bars + OB_SLOT, stop = bars + OB_STOP;
    const int ne = (pt >> 1) == 6 ? 3 : 2, nh = pt >= 14 ? 64 - O2_NL : 64;
    const int mt = (pt >> 1) * 2 + (int)rank, m0 = mt * 128, n0 = (pt & 1) * 256;
    int s = 0, ready = LATE ? 16 : 0, q = h0 * 2, qe = q + 2; uint32_t ph = LATE;
    for (int ic = 0;; ic++) {
        if (lead && rank == 0) {
            const int t = tnext + ne;
            asm volatile("st.shared.s32 [%0], %1;" :: "r"(slot + (ic & 7) * 4), "r"(t) : "memory");
            mbar_arrive(bar_item + 8 * (ic & 7));
            st_async_b32(mapa_u32(slot + (ic & 7) * 4, 1), (uint32_t)t, mapa_u32(bar_item + 8 * (ic & 7), 1));
            if (t < nh + O2_FINE) tnext = take_ticket(CT_OT + pt);
        }
#pragma unroll 1
        for (; q < qe; q++) {
            const int b = q >> 6, head = (q >> 1) & 31, dk = (q & 1) * 64;
            mbar_wait(bar_empty + 8 * s, ph);
            const uint32_t sa = sbase + s * 49152;
            if (lead) {
                const int f = b ? 4 : head >> 3;
                if (!((ready >> f) & 1)) {
                    if (b && !(ready & 8)) { wait_ctr(CT_CA + mt * 4 + 3, 16u); ready |= 8; }
                    wait_ctr(b ? CT_CB + mt : CT_CA + mt * 4 + f, b ? 64u : 16u); ready |= 1 << f;
                }
                if (!LATE || ic > 0) {
                    mbar_expect_tx(bar_full + 8 * s, 49152);
                    tma_load_2d(sa, &P.mapCtx[b], bar_full + 8 * s, dk, head * SEQ + m0);
                }
            } else {
                for (int j = (int)rank * 2; j < (int)rank * 2 + 2; j++)
                    tma_load_2d_mc(sa + 16384 + j * 8192, &P.mapWo[b], bar_full + 8 * s, n0 + j * 64, head * HD + dk, (uint16_t)3);
            }
            if (++s == O2_STAGES) { s = 0; ph ^= 1; }
        }
        if (lead && rank == 1) mbar_expect_tx(bar_item + 8 * (ic & 7), 4);
        mbar_wait(bar_item + 8 * (ic & 7), (ic >> 3) & 1);
        int t;
        asm volatile("ld.shared.s32 %0, [%1];" : "=r"(t) : "r"(slot + (ic & 7) * 4) : "memory");
        if (t >= nh + O2_FINE) break;
        if (t < nh - O2_FINE) { q = 2 * t; qe = q + 2; } else { q = nh - O2_FINE + t; qe = q + 1; }
    }
    if (lead) {
        asm volatile("prefetch.tensormap [%0];" :: "l"(&P.mapOut) : "memory");
        if (!(ready & 8)) wait_ctr(CT_CA + mt * 4 + 3, 16u);
        mbar_wait(bar_empty + 8 * s, ph);
        asm volatile("st.shared.s32 [%0], %1;" :: "r"(stop + s * 4), "r"(1) : "memory");
        mbar_arrive(bar_full + 8 * s);
        out_finished();
        for (int i = 1; i < O2_STAGES; i++) {
            if (++s == O2_STAGES) { s = 0; ph ^= 1; }
            mbar_wait(bar_empty + 8 * s, ph);
        }
    }
}
__device__ __forceinline__ void out_consumer(const OutParams& P, uint32_t sbase, uint32_t bars, uint32_t rank, int pt, int warp) {
    const uint32_t bar_full = bars + OB_FULL, bar_empty = bars + OB_EMPTY, stop = bars + OB_STOP;
    const int m0 = ((pt >> 1) * 2 + (int)rank) * 128, n0 = (pt & 1) * 256;
    const int wg = warp >> 2, lane = threadIdx.x & 31;
    const bool elected = (threadIdx.x & 127) == 0;
    float acc[128];
#pragma unroll
    for (int i = 0; i < 128; i++) acc[i] = 0.f;
    int s = 0, sprev = 0; uint32_t ph = 0;
#pragma unroll 1
    for (int i = 0;; i++) {
        mbar_wait(bar_full + 8 * s, ph);
        int st;
        asm volatile("ld.shared.s32 %0, [%1];" : "=r"(st) : "r"(stop + s * 4) : "memory");
        if (st) break;
        if (i == 0) OT(1);
        const uint32_t sa = sbase + s * 49152 + wg * 8192, sb = sbase + s * 49152 + 16384;
        wgmma_fence();
#pragma unroll
        for (int kk = 0; kk < 4; kk++)
            wgmma_ss_n256_tb(acc, make_desc(sa + kk * 32, 16, 1024), make_desc(sb + kk * 2048, 8192, 1024), 1);
        wgmma_commit();
        if (i > 0) {
            wgmma_wait<1>();
            if (elected) { const uint32_t e = bar_empty + 8 * sprev; mbar_arrive_cl(mapa_u32(e, 0)); mbar_arrive_cl(mapa_u32(e, 1)); }
        }
        sprev = s;
        if (++s == O2_STAGES) { s = 0; ph ^= 1; }
    }
    wgmma_wait<0>();
    if (elected) { const uint32_t e = bar_empty + 8 * sprev; mbar_arrive_cl(mapa_u32(e, 0)); mbar_arrive_cl(mapa_u32(e, 1)); }
    asm volatile("bar.sync %0, 128;" :: "r"(1 + wg) : "memory");
    OT(3);
    const int row = (lane & 7) + ((lane >> 3) & 1) * 8;
#pragma unroll
    for (int bx = 0; bx < 4; bx++) {
        const uint32_t stg = sbase + bx * 49152 + warp * 2048;
#pragma unroll
        for (int j = 0; j < 8; j += 2) {
            const float* a = &acc[bx * 32 + j * 4];
            stmatrix_x4(stg + row * 128 + (((j + (lane >> 4)) ^ (row & 7)) << 4), pack_bf16(a[0], a[1]), pack_bf16(a[2], a[3]), pack_bf16(a[4], a[5]), pack_bf16(a[6], a[7]));
        }
        asm volatile("fence.proxy.async.shared::cta;" ::: "memory");
        __syncwarp();
        if (lane == 0)
            asm volatile("cp.reduce.async.bulk.tensor.2d.global.shared::cta.add.tile.bulk_group [%0, {%2, %3}], [%1];"
                         :: "l"((uint64_t)&P.mapOut), "r"(stg), "r"(n0 + bx * 64), "r"(m0 + warp * 16) : "memory");
    }
    OT(4);
    if (lane == 0) {
        asm volatile("cp.async.bulk.commit_group;" ::: "memory");
        asm volatile("cp.async.bulk.wait_group.read 0;" ::: "memory");
    }
}

constexpr int O2_SMEM = O2_STAGES * 49152 + 1024 + 256;
__global__ void __cluster_dims__(2, 1, 1) __launch_bounds__(320, 1)
out2_kernel(const __grid_constant__ OutParams P) {
    extern __shared__ uint8_t smem_raw[];
    const uint32_t sbase = (smem_u32(smem_raw) + 1023) & ~1023u;
    const uint32_t bars = sbase + O2_STAGES * 49152;
    const int warp = threadIdx.x >> 5, lane = threadIdx.x & 31;
    const uint32_t rank = cluster_ctarank();
    int pt, h0;
    out_map(M_GRID / 2 + (blockIdx.x >> 1), pt, h0);
    const int mt = (pt >> 1) * 2 + (int)rank;
    TS_BEGIN(4);
    OT(0);
    int tnext = 0;
    if (threadIdx.x == 256) {
        if (rank == 0) tnext = take_ticket(CT_OT + pt);
        out_init(bars);
        asm volatile("fence.mbarrier_init.release.cluster;" ::: "memory");
    }
    __syncwarp();
    asm volatile("barrier.cluster.arrive.relaxed.aligned;" ::: "memory");
    if (threadIdx.x == 256) {
        asm volatile("prefetch.tensormap [%0];" :: "l"(&P.mapCtx[1]) : "memory");
        wait_ctr(CT_CB + mt, 64u);
        for (int i = 0; i < 2; i++) {
            mbar_expect_tx(bars + OB_FULL + 8 * i, 49152);
            tma_load_2d(sbase + i * 49152, &P.mapCtx[1], bars + OB_FULL + 8 * i, i * 64, (h0 & 31) * SEQ + mt * 128);
        }
    }
    if (threadIdx.x == 288) asm volatile("prefetch.tensormap [%0];" :: "l"(&P.mapWo[1]) : "memory");
    __syncwarp();
    asm volatile("barrier.cluster.wait.aligned;" ::: "memory");
    if (warp >= 8) {
        if (lane == 0) out_producer(P, sbase, bars, rank, pt, h0, warp == 8, true, tnext);
    } else {
        out_consumer(P, sbase, bars, rank, pt, warp);
        TS_END(4);
    }
}

struct MainParams { Proj2Params p; AttnParams a; OutParams o; const bf16 *x, *gate_w; };
__device__ __forceinline__ int p2_apos(int k) { return k < 2 ? k : k < 6 ? k + 2 : k - 4; }
__global__ void __cluster_dims__(2, 1, 1) __launch_bounds__(384, 1) main_kernel(const __grid_constant__ MainParams MP) {
    const Proj2Params& P = MP.p;
    extern __shared__ uint8_t smem_raw[];
    const uint32_t rank = cluster_ctarank();
    const uint32_t sbase = (rank << 24) + SD;
    if (smem_u32(smem_raw) != sbase) __trap();
    const uint32_t sA = sbase, sB = sbase + 131072;
    const uint32_t bars = sbase + MO_BAR, obars = bars + 768;
    const uint32_t a_full = bars, a_empty = bars + 64, b_full = bars + 128, b_empty = b_full + 8 * P2_STAGES;
    const uint32_t item_bar = b_empty + 8 * P2_STAGES, item_in = item_bar + 16, slot = item_in + 16;
    const uint32_t note_bar = slot + 16, note_free = note_bar + 64, note = note_free + 64;
    const int warp = __shfl_sync(0xffffffff, threadIdx.x >> 5, 0), lane = threadIdx.x & 31;
    int pt, h0;
    out_map(blockIdx.x >> 1, pt, h0);
    TS_BEGIN(0);
    if (threadIdx.x == 0) {
        for (int i = 0; i < 8; i++) { mbar_init(a_full + 8 * i, 1); mbar_init(a_empty + 8 * i, 2); }
        for (int i = 0; i < P2_STAGES; i++) { mbar_init(b_full + 8 * i, 1); mbar_init(b_empty + 8 * i, 2); }
        mbar_init(item_bar, 1); mbar_init(item_bar + 8, 1); mbar_init(item_in, 2); mbar_init(item_in + 8, 2);
        for (int i = 0; i < 8; i++) { mbar_init(note_bar + 8 * i, 1); mbar_init(note_free + 8 * i, 1); }
        asm volatile("fence.mbarrier_init.release.cluster;" ::: "memory");
    }
    if (threadIdx.x == 32) {
        attn_init(sbase);
        asm volatile("fence.mbarrier_init.release.cluster;" ::: "memory");
    }
    if (threadIdx.x == 256) {
        out_init(obars);
        asm volatile("fence.mbarrier_init.release.cluster;" ::: "memory");
    }
    __syncthreads();
    asm volatile("barrier.cluster.arrive.relaxed.aligned;" ::: "memory");
    pdl_launch_dependents();
    if (warp >= 8) {
    asm volatile("setmaxnreg.dec.sync.aligned.u32 40;");
    asm volatile("barrier.cluster.wait.aligned;" ::: "memory");
    if (warp == 9) {
        if (lane == 0) {
            for (int n = 0;; n++) {
                const int e = (n & 1) * 4 + ((n >> 1) & 3);
                mbar_wait(note_bar + 8 * e, (n >> 3) & 1);
                int m;
                asm volatile("ld.shared.s32 %0, [%1];" : "=r"(m) : "r"(note + e * 4) : "memory");
                mbar_arrive(note_free + 8 * e);
                if (m < 0) break;
                signal_ctr(m);
            }
            attn_helper(MP.a, sbase, 0);
        }
    } else if (warp == 10) {
        if (lane == 0) {
            auto publish = [&](int ic, int tq) {
                const int t = tq < P2_ITEMS ? tq : -1;
                asm volatile("st.shared.s32 [%0], %1;" :: "r"(slot + (ic & 3) * 4), "r"(t) : "memory");
                mbar_arrive(item_bar + 8 * (ic & 1));
                st_async_b32(mapa_u32(slot + (ic & 3) * 4, 1), (uint32_t)t, mapa_u32(item_bar + 8 * (ic & 1), 1));
            };
            const int npair = M_GRID / 2, pair = (int)(blockIdx.x >> 1);
            if (rank == 0) publish(0, pair);
            for (int ic = 0;; ic++) {
                if (rank == 1) mbar_expect_tx(item_bar + 8 * (ic & 1), 4);
                mbar_wait(item_bar + 8 * (ic & 1), (ic >> 1) & 1);
                int t;
                asm volatile("ld.shared.s32 %0, [%1];" : "=r"(t) : "r"(slot + (ic & 3) * 4) : "memory");
                if (t < 0) break;
                int z0, mp, h0;
                p2_tile(t, 0, z0, mp, h0);
                const int aidx = z0 >= 1 ? 1 : 0;
                const int m0 = (2 * mp + (int)rank) * 128;
                for (int k = 0; k < 8; k++) {
                    mbar_wait(a_empty + 8 * k, (ic & 1) ^ 1);
                    if (P2_NOLOAD) mbar_arrive(a_full + 8 * k); else {
                    mbar_expect_tx(a_full + 8 * k, 16384);
                    tma_load_2d(sA + p2_apos(k) * 16384, &P.mapA[aidx], a_full + 8 * k, k * 64, m0); }
                }
                if (rank == 0) {
                    mbar_wait(item_in + 8 * (ic & 1), (ic >> 1) & 1);
                    publish(ic + 1, ic == 0 ? npair + pair : pair < P2_NP && ic + 1 >= P2_NI ? P2_ITEMS : 2 * npair + (int)atomicAdd(&g_ctr[CT_PROJ], 1u));
                }
            }
            attn_helper(MP.a, sbase, 1);
        }
    } else {
        if (lane == 0) {
            const int par2 = warp == 8 ? 0 : 1;
            int it = 0, ic = 0; uint32_t bph = 0;
            for (;; ic++) {
                mbar_wait(item_bar + 8 * (ic & 1), (ic >> 1) & 1);
                int t;
                asm volatile("ld.shared.s32 %0, [%1];" : "=r"(t) : "r"(slot + (ic & 3) * 4) : "memory");
                if (t < 0) break;
                const int nt = 2 * p2_reps(t);
                for (int w = 0; w < nt; w++) {
                    int z, mp, hd;
                    p2_tile(t, w, z, mp, hd);
                    for (int k = 0; k < 8; k++) {
                        const int s = it; const uint32_t phb = bph;
                        if (++it == P2_STAGES) { it = 0; bph ^= 1; }
                        if ((k & 1) != par2) continue;
                        mbar_wait(b_empty + 8 * s, phb ^ 1);
                        if (P2_NOLOAD) { mbar_arrive(b_full + 8 * s); continue; }
                        mbar_expect_tx(b_full + 8 * s, 16384);
                        tma_load_2d_mc(sB + s * 16384 + rank * 8192, &P.mapW[z], b_full + 8 * s, hd * 128 + (int)rank * 64, k * 64, (uint16_t)3);
                    }
                }
            }
            int tnext = 0;
            if (warp == 8) {
                attn_producer(MP.a, sbase, a_empty, ~ic & 1);
                TS_END2(1, 256); TS_BEGIN2(3, 256);
                if (rank == 0) tnext = take_ticket(CT_OT + pt);
                for (int i = 0; i < 4; i++) {
                    const uint32_t e = mapa_u32(obars + OB_EMPTY + 8 * (i & 1), i >> 1);
                    mbar_arrive_cl(e); mbar_arrive_cl(e);
                }
            }
            out_producer(MP.o, sbase, obars, rank, pt, h0, warp == 8, false, tnext);
            TS_END2(3, 256);
        }
    }
    } else {
        asm volatile("setmaxnreg.inc.sync.aligned.u32 232;");
        asm volatile("barrier.cluster.wait.aligned;" ::: "memory");
        const int wg = warp >> 2;
        float acc[2][64];
        const uint32_t a_lo = desc_lo(SD, 16), b_lo0 = desc_lo(SD + 131072, 8192);
        const bool elected = (threadIdx.x & 127) == 0;
        int s = (wg * 8) % P2_STAGES;
        uint32_t ph = ((wg * 8) / P2_STAGES) & 1;
        int nnote = 0;
        if (wg == 1) {
            asm volatile("bar.arrive 3, 256;" ::: "memory");
            if (blockIdx.x < 64) {
                const int r = blockIdx.x * 32 + (warp & 3) * 8 + (lane >> 2);
                float c[4] = {0.f, 0.f, 0.f, 0.f};
                uint4 xv[16], gv[16];
#pragma unroll
                for (int i = 0; i < 16; i++) {
                    xv[i] = __ldg(reinterpret_cast<const uint4*>(MP.x + (size_t)r * DM + i * 32 + (lane & 3) * 8));
                    gv[i] = __ldg(reinterpret_cast<const uint4*>(MP.gate_w + i * 32 + (lane & 3) * 8));
                }
                auto mul = [](uint32_t a, uint32_t b) { uint32_t p; asm("mul.rn.bf16x2 %0, %1, %2;" : "=r"(p) : "r"(a), "r"(b)); return p; };
#pragma unroll
                for (int i = 0; i < 16; i++)
                    mma_16816(c, mul(xv[i].x, gv[i].x), mul(xv[i].y, gv[i].y), mul(xv[i].z, gv[i].z), mul(xv[i].w, gv[i].w), 0x3f803f80u, 0x3f803f80u);
                if ((lane & 3) == 0) g_gate[r] = bf16r(__fdividef(1.f, 1.f + __expf(-bf16r(c[0] + c[2]))));
                __syncwarp();
                if (lane == 0) signal_ctr_generic(CT_GATE);
                __syncwarp();
            }
        }
        for (int ic = 0;; ic++) {
            mbar_wait(item_bar + 8 * (ic & 1), (ic >> 1) & 1);
            int t;
            asm volatile("ld.shared.s32 %0, [%1];" : "=r"(t) : "r"(slot + (ic & 3) * 4) : "memory");
            t = __shfl_sync(0xffffffff, t, 0);
            P2T(7);
            if (wg == 0 && t < 0) {
                if (elected) {
                    const int e = nnote & 3;
                    mbar_wait(note_free + 8 * e, ((nnote >> 2) & 1) ^ 1);
                    asm volatile("st.shared.s32 [%0], %1;" :: "r"(note + e * 4), "r"(-1) : "memory");
                    mbar_arrive(note_bar + 8 * e);
                }
            }
            if (t < 0) break;
            const int reps = p2_reps(t);
#pragma unroll 1
            for (int rp = 0; rp < reps; rp++) {
            const bool first = rp == 0, last = rp == reps - 1;
            int z, mp, head;
            p2_tile(t, rp * 2 + wg, z, mp, head);
            asm volatile("bar.sync %0, 256;" :: "r"(3 + wg) : "memory");
            P2T(0);
            if (wg == 1 && last && elected) mbar_arrive_cl(mapa_u32(item_in + 8 * (ic & 1), 0));
            int sprev = 0;
#pragma unroll
            for (int k = 0; k < 8; k++) {
                if (k == 0) P2T(5);
                if (wg == 0 && first) mbar_wait(a_full + 8 * k, ic & 1);
                if (k == 0) P2T(6);
                mbar_wait(b_full + 8 * s, ph);
                if (k == 7) asm volatile("bar.arrive %0, 256;" :: "r"(4 - wg) : "memory");
                if (k == 0) P2T(1);
                if (k == 7) P2T(2);
                const uint32_t b_lo = b_lo0 + s * 1024;
                wgmma_fence();
#pragma unroll
                for (int kk = 0; kk < (P2_NOMMA ? 1 : 4); kk++) {
                    wgmma_ss_n128_lo<1>(acc[0], a_lo + p2_apos(k) * 1024 + kk * 2, b_lo + kk * 128, (k | kk) != 0);
                    wgmma_ss_n128_lo<1>(acc[1], a_lo + p2_apos(k) * 1024 + 512 + kk * 2, b_lo + kk * 128, (k | kk) != 0);
                }
                wgmma_commit();
                if (k > 0) {
                    wgmma_wait<1>();
                    if (elected) {
                        const uint32_t e = b_empty + 8 * sprev;
                        mbar_arrive_cl(mapa_u32(e, 0)); mbar_arrive_cl(mapa_u32(e, 1));
                        if (last) mbar_arrive(a_empty + 8 * (k - 1));
                    }
                }
                sprev = s;
                if (++s == P2_STAGES) { s = 0; ph ^= 1; }
            }
            wgmma_wait<0>();
            P2T(3);
            if (elected) {
                const uint32_t e = b_empty + 8 * sprev;
                mbar_arrive_cl(mapa_u32(e, 0)); mbar_arrive_cl(mapa_u32(e, 1));
                if (last) mbar_arrive(a_empty + 8 * 7);
            }
            s += 8 % P2_STAGES; ph ^= (8 / P2_STAGES) & 1;
            if (s >= P2_STAGES) { s -= P2_STAGES; ph ^= 1; }
            const int m0 = (2 * mp + (int)rank) * 128;
            bf16* obase = P.out[z] + ((size_t)head * SEQ + m0 + (warp & 3) * 16 + (lane >> 2)) * HD + (lane & 3) * 8;
            store_frag_128<true, P2_PACE>(acc[0], obase, lane); store_frag_128<true, P2_PACE>(acc[1], obase + (size_t)64 * HD, lane);
            P2T(4);
            {
                asm volatile("bar.sync %0, 128;" :: "r"(1 + wg) : "memory");
                if (elected) {
                    const int e = wg * 4 + (nnote & 3);
                    mbar_wait(note_free + 8 * e, ((nnote >> 2) & 1) ^ 1);
                    asm volatile("st.shared.s32 [%0], %1;" :: "r"(note + e * 4), "r"(CT_AP + (head >> 1)) : "memory");
                    mbar_arrive(note_bar + 8 * e);
                }
                nnote++;
            }
            }
        }
        auto done = [&]() {
            if ((threadIdx.x & 127) == 0) for (int i = 0; i < 4; i++) mbar_arrive_cl(SD + MO_BAR + 768 + OB_EMPTY + 16 + 8 * (i & 1) + ((i >> 1) << 24));
        };
        asm volatile("bar.sync %0, 128;" :: "r"(1 + wg) : "memory");
        if (rank == 0) attn_consumer<SD>(MP.a, warp, done); else attn_consumer<SD + (1u << 24)>(MP.a, warp, done);
        OT(0);
        {
            const uint32_t rank2 = cluster_ctarank(), sb2 = (rank2 << 24) + SD;
            int cid;
            asm volatile("mov.u32 %0, %%clusterid.x;" : "=r"(cid));
            out_map(cid, pt, h0);
            out_consumer(MP.o, sb2, sb2 + MO_BAR + 768, rank2, pt, warp);
        }
    }
}

typedef CUresult (*PFN_encodeTiled)(CUtensorMap*, CUtensorMapDataType, cuuint32_t, void*, const cuuint64_t*,
                                    const cuuint64_t*, const cuuint32_t*, const cuuint32_t*, CUtensorMapInterleave,
                                    CUtensorMapSwizzle, CUtensorMapL2promotion, CUtensorMapFloatOOBfill);
static PFN_encodeTiled g_encode = nullptr;

static void make_map(CUtensorMap* m, const void* ptr, uint64_t rows, uint64_t cols, uint32_t box_rows, bool sw64 = false) {
    cuuint64_t dims[2] = {cols, rows};
    cuuint64_t strides[1] = {cols * 2};
    cuuint32_t box[2] = {sw64 ? 32u : 64u, box_rows};
    cuuint32_t es[2] = {1, 1};
    g_encode(m, CU_TENSOR_MAP_DATA_TYPE_BFLOAT16, 2, const_cast<void*>(ptr), dims, strides, box, es,
             CU_TENSOR_MAP_INTERLEAVE_NONE, sw64 ? CU_TENSOR_MAP_SWIZZLE_64B : CU_TENSOR_MAP_SWIZZLE_128B, CU_TENSOR_MAP_L2_PROMOTION_L2_256B,
             CU_TENSOR_MAP_FLOAT_OOB_FILL_NONE);
}

template <typename... KArgs, typename... Args>
static void launch_pdl(void (*kernel)(KArgs...), int grid, int block, size_t smem, cudaStream_t st, bool pdl, Args... args) {
    cudaLaunchConfig_t cfg = {};
    cfg.gridDim = dim3(grid); cfg.blockDim = dim3(block); cfg.dynamicSmemBytes = smem; cfg.stream = st;
    cudaLaunchAttribute at[1];
    at[0].id = cudaLaunchAttributeProgrammaticStreamSerialization;
    at[0].val.programmaticStreamSerializationAllowed = 1;
    cfg.attrs = at; cfg.numAttrs = pdl ? 1 : 0;
    cudaLaunchKernelEx(&cfg, kernel, KArgs(args)...);
}

extern "C" void kernel_launch(void* const* d_in, const int* in_sizes, int n_in, void* d_out, int out_size) {
    const bf16* x = (const bf16*)d_in[0];
    const bf16* ckv = (const bf16*)d_in[1];
    const bf16* wq = (const bf16*)d_in[2];
    const bf16* wuk = (const bf16*)d_in[3];
    const bf16* wuv = (const bf16*)d_in[4];
    const bf16* wo = (const bf16*)d_in[5];
    const bf16* mem0 = (const bf16*)d_in[7];
    const bf16* Wq = (const bf16*)d_in[8];
    const bf16* Wk = (const bf16*)d_in[9];
    const bf16* Wv = (const bf16*)d_in[10];
    const bf16* Wo = (const bf16*)d_in[11];
    const bf16* gate_w = (const bf16*)d_in[13];
    bf16* out = (bf16*)d_out;

    static MainParams MP;
    static ChainParams CP;
    Proj2Params& P2 = MP.p;
    AttnParams& AP = MP.a;
    OutParams& OP = MP.o;
    static bool init = false;
    static const void* last_in[14];
    static const void* last_out;
    bool same = init && last_out == d_out;
    for (int i = 0; i < 14 && same; i++) same = last_in[i] == d_in[i];
    if (!init) {
        cudaDriverEntryPointQueryResult qr;
        cudaGetDriverEntryPoint("cuTensorMapEncodeTiled", (void**)&g_encode, cudaEnableDefault, &qr);
        cudaFuncSetAttribute(main_kernel, cudaFuncAttributeMaxDynamicSharedMemorySize, M_SMEM);
        cudaFuncSetAttribute(out2_kernel, cudaFuncAttributeMaxDynamicSharedMemorySize, O2_SMEM);
        cudaFuncSetAttribute(chain_kernel, cudaFuncAttributeMaxDynamicSharedMemorySize, CH_SMEM);
        init = true;
    }
    if (!same) {
        for (int i = 0; i < 14; i++) last_in[i] = d_in[i];
        last_out = d_out;
        void *pQA, *pKA, *pVA, *pCA, *pCB;
        cudaGetSymbolAddress(&pQA, g_QA); cudaGetSymbolAddress(&pKA, g_KA); cudaGetSymbolAddress(&pVA, g_VA);
        cudaGetSymbolAddress(&pCA, g_ctxA); cudaGetSymbolAddress(&pCB, g_ctxB);
        make_map(&P2.mapA[0], x, SEQ, DM, 128);
        make_map(&P2.mapA[1], ckv, SEQ, DM, 128);
        const void* ws[3] = {wq, wuk, wuv};
        void* cs[3] = {pQA, pKA, pVA};
        for (int i = 0; i < 3; i++) { make_map(&P2.mapW[i], ws[i], DM, NQ, 64); P2.out[i] = (bf16*)cs[i]; }
        make_map(&CP.mapW[0], Wq, DM, NQ, 64); make_map(&CP.mapW[1], Wk, DM, NQ, 64); make_map(&CP.mapW[2], Wv, DM, NQ, 64);
        make_map(&CP.mapX, x, SEQ, DM, 32);
        make_map(&CP.mapWo, Wo, NQ, DM, 64);
        make_map(&CP.mapM, mem0, NMEM, DM, 8);
        MP.x = x; MP.gate_w = gate_w;
        make_map(&CP.mapC, pCB, NH * SEQ, HD, 32);
        make_map(&AP.mapQ, pQA, NH * SEQ, HD, 128);
        make_map(&AP.mapK, pKA, NH * SEQ, HD, 128);
        make_map(&AP.mapV, pVA, NH * SEQ, HD, 128);
        make_map(&AP.mapO, pCA, NH * SEQ, HD, 64);
        make_map(&OP.mapCtx[0], pCA, NH * SEQ, HD, 128);
        make_map(&OP.mapCtx[1], pCB, NH * SEQ, HD, 128);
        make_map(&OP.mapWo[0], wo, NQ, DM, 64);
        make_map(&OP.mapWo[1], Wo, NQ, DM, 64);
        make_map(&OP.mapOut, out, SEQ, DM, 16);
        AP.out = out;
    }
    cudaStream_t s1 = cudaStreamPerThread;
    const bool pdl = true;
    launch_pdl(chain_kernel, 64, CH_BLOCK, CH_SMEM, s1, false, CP);
    launch_pdl(main_kernel, M_GRID, 384, M_SMEM, s1, pdl, MP);
    launch_pdl(out2_kernel, O2_GRID, 320, O2_SMEM, s1, pdl, OP);
}
```

```cpp
#include <cuda_runtime.h>
#include <cuda_bf16.h>
#include <cuda.h>
#include <stdint.h>
#include <type_traits>

constexpr int SEQ = 2048;
constexpr int DM = 512;
constexpr int NH = 32;
constexpr int HD = 128;
constexpr int NQ = NH * HD;
constexpr int SEGL = 32;
constexpr int NMEM = 8;
constexpr int NSEG = SEQ / SEGL;

typedef __nv_bfloat16 bf16;

__device__ bf16 g_QA[SEQ * NQ];
__device__ bf16 g_KA[SEQ * NQ];
__device__ bf16 g_VA[SEQ * NQ];
__device__ bf16 g_ctxA[SEQ * NQ];
__device__ bf16 g_ctxB[SEQ * NQ];
constexpr int CT_PROJ = 0, CT_ATTN = 1, CT_FIN = 5;
constexpr int CT_AP = 64;
constexpr int CT_GATE = 96;
constexpr int CT_CA = 128;
constexpr int CT_CB = 192;
constexpr int CT_OT = 208;
constexpr int CT_N = 224;
__device__ __align__(16) unsigned int g_ctr[CT_N];
__device__ float g_gate[SEQ];
#define XB8(v) v, v, v, v, v, v, v, v
__device__ uint32_t g_xbuf[4 * 8 * 2048] = {XB8(XB8(XB8(XB8(XB8(~0u)))))};

#define FA_GRID 68

#define TS_BEGIN(id)
#define TS_END(id)
#define TS_BEGIN2(id, th)
#define TS_END2(id, th)
#define WAIT_LIMIT 200000
__device__ __forceinline__ void pdl_launch_dependents() { asm volatile("griddepcontrol.launch_dependents;" ::: "memory"); }
__device__ __forceinline__ void wait_ctr(int idx, unsigned int n) {
    unsigned int v; int it = 0;
    do { asm volatile("ld.acquire.gpu.global.u32 %0, [%1];" : "=r"(v) : "l"(&g_ctr[idx]) : "memory"); } while (v < n && ++it < WAIT_LIMIT);
    asm volatile("fence.proxy.async.shared::cta;" ::: "memory");
}
__device__ __forceinline__ int take_ticket(int idx) {
    int v;
    asm volatile("atom.relaxed.gpu.global.inc.u32 %0, [%1], 0x7fffffff;" : "=r"(v) : "l"(&g_ctr[idx]) : "memory");
    return v;
}
__device__ __forceinline__ void signal_ctr(int idx) {
    asm volatile("fence.proxy.async;" ::: "memory");
    __threadfence();
    atomicAdd(&g_ctr[idx], 1u);
}
__device__ __forceinline__ void signal_ctr_generic(int idx) {
    asm volatile("red.release.gpu.global.add.u32 [%0], 1;" :: "l"(&g_ctr[idx]) : "memory");
}
__device__ __forceinline__ uint32_t smem_u32(const void* p) {
    return (uint32_t)__cvta_generic_to_shared(p);
}
__device__ __forceinline__ void mbar_init(uint32_t bar, uint32_t count) {
    asm volatile("mbarrier.init.shared::cta.b64 [%0], %1;" :: "r"(bar), "r"(count));
}
__device__ __forceinline__ void mbar_expect_tx(uint32_t bar, uint32_t bytes) {
    asm volatile("mbarrier.arrive.expect_tx.shared::cta.b64 _, [%0], %1;" :: "r"(bar), "r"(bytes) : "memory");
}
__device__ __forceinline__ void mbar_arrive(uint32_t bar) {
    asm volatile("mbarrier.arrive.shared::cta.b64 _, [%0];" :: "r"(bar) : "memory");
}
__device__ __forceinline__ void mbar_wait(uint32_t bar, uint32_t parity) {
    asm volatile(
        "{\n"
        ".reg .pred p, q;\n"
        ".reg .u32 c;\n"
        "mov.u32 c, 0;\n"
        "WAIT_LOOP:\n"
        "mbarrier.try_wait.parity.shared::cta.b64 p, [%0], %1;\n"
        "@p bra WAIT_DONE;\n"
        "add.u32 c, c, 1;\n"
        "setp.lt.u32 q, c, %2;\n"
        "@q bra WAIT_LOOP;\n"
        "WAIT_DONE:\n"
        "}\n" :: "r"(bar), "r"(parity), "n"(WAIT_LIMIT) : "memory");
}
__device__ __forceinline__ uint32_t mbar_test(uint32_t bar, uint32_t parity) {
    uint32_t done;
    asm volatile(
        "{\n.reg .pred p;\n"
        "mbarrier.test_wait.parity.shared::cta.b64 p, [%1], %2;\n"
        "selp.u32 %0, 1, 0, p;\n}\n" : "=r"(done) : "r"(bar), "r"(parity) : "memory");
    return done;
}
__device__ __forceinline__ uint32_t mbar_try(uint32_t bar, uint32_t parity) {
    uint32_t done;
    asm volatile(
        "{\n.reg .pred p;\n"
        "mbarrier.try_wait.parity.shared::cta.b64 p, [%1], %2;\n"
        "selp.u32 %0, 1, 0, p;\n}\n" : "=r"(done) : "r"(bar), "r"(parity) : "memory");
    return done;
}
__device__ __forceinline__ void tma_load_2d(uint32_t dst, const CUtensorMap* map, uint32_t bar, int c0, int c1) {
    asm volatile(
        "cp.async.bulk.tensor.2d.shared::cluster.global.mbarrier::complete_tx::bytes [%0], [%1, {%3, %4}], [%2];"
        :: "r"(dst), "l"((uint64_t)map), "r"(bar), "r"(c0), "r"(c1) : "memory");
}
__device__ __forceinline__ void wgmma_fence() { asm volatile("wgmma.fence.sync.aligned;" ::: "memory"); }
__device__ __forceinline__ void wgmma_commit() { asm volatile("wgmma.commit_group.sync.aligned;" ::: "memory"); }
template <int N> __device__ __forceinline__ void wgmma_wait() {
    asm volatile("wgmma.wait_group.sync.aligned %0;" :: "n"(N) : "memory");
}
__device__ __forceinline__ uint64_t make_desc(uint32_t addr, uint32_t lbo, uint32_t sbo) {
    uint64_t d = 0;
    d |= (uint64_t)((addr & 0x3FFFF) >> 4);
    d |= (uint64_t)((lbo >> 4) & 0x3FFF) << 16;
    d |= (uint64_t)((sbo >> 4) & 0x3FFF) << 32;
    d |= (uint64_t)1 << 62;
    return d;
}

#define ACC64(d) \
    "+f"(d[0]), "+f"(d[1]), "+f"(d[2]), "+f"(d[3]), "+f"(d[4]), "+f"(d[5]), "+f"(d[6]), "+f"(d[7]), \
    "+f"(d[8]), "+f"(d[9]), "+f"(d[10]), "+f"(d[11]), "+f"(d[12]), "+f"(d[13]), "+f"(d[14]), "+f"(d[15]), \
    "+f"(d[16]), "+f"(d[17]), "+f"(d[18]), "+f"(d[19]), "+f"(d[20]), "+f"(d[21]), "+f"(d[22]), "+f"(d[23]), \
    "+f"(d[24]), "+f"(d[25]), "+f"(d[26]), "+f"(d[27]), "+f"(d[28]), "+f"(d[29]), "+f"(d[30]), "+f"(d[31]), \
    "+f"(d[32]), "+f"(d[33]), "+f"(d[34]), "+f"(d[35]), "+f"(d[36]), "+f"(d[37]), "+f"(d[38]), "+f"(d[39]), \
    "+f"(d[40]), "+f"(d[41]), "+f"(d[42]), "+f"(d[43]), "+f"(d[44]), "+f"(d[45]), "+f"(d[46]), "+f"(d[47]), \
    "+f"(d[48]), "+f"(d[49]), "+f"(d[50]), "+f"(d[51]), "+f"(d[52]), "+f"(d[53]), "+f"(d[54]), "+f"(d[55]), \
    "+f"(d[56]), "+f"(d[57]), "+f"(d[58]), "+f"(d[59]), "+f"(d[60]), "+f"(d[61]), "+f"(d[62]), "+f"(d[63])
#define ACC64_STR \
    "{%0, %1, %2, %3, %4, %5, %6, %7, %8, %9, %10, %11, %12, %13, %14, %15, " \
    "%16, %17, %18, %19, %20, %21, %22, %23, %24, %25, %26, %27, %28, %29, %30, %31, " \
    "%32, %33, %34, %35, %36, %37, %38, %39, %40, %41, %42, %43, %44, %45, %46, %47, " \
    "%48, %49, %50, %51, %52, %53, %54, %55, %56, %57, %58, %59, %60, %61, %62, %63}"

template <int TB>
__device__ __forceinline__ void wgmma_ss_n128(float (&d)[64], uint64_t da, uint64_t db, int scale_d) {
    asm volatile(
        "{\n.reg .pred p;\nsetp.ne.b32 p, %66, 0;\n"
        "wgmma.mma_async.sync.aligned.m64n128k16.f32.bf16.bf16 " ACC64_STR ", %64, %65, p, 1, 1, 0, %67;\n}\n"
        : ACC64(d) : "l"(da), "l"(db), "r"(scale_d), "n"(TB));
}
__device__ __forceinline__ uint32_t desc_lo(uint32_t addr, uint32_t lbo) { return ((addr & 0x3FFFF) >> 4) | ((lbo >> 4) << 16); }
template <int TB>
__device__ __forceinline__ void wgmma_ss_n128_lo(float (&d)[64], uint32_t da_lo, uint32_t db_lo, int scale_d) {
    asm volatile(
        "{\n.reg .pred p;\n.reg .b64 da, db;\nsetp.ne.b32 p, %66, 0;\n"
        "mov.b64 da, {%64, 0x40000040};\nmov.b64 db, {%65, 0x40000040};\n"
        "wgmma.mma_async.sync.aligned.m64n128k16.f32.bf16.bf16 " ACC64_STR ", da, db, p, 1, 1, 0, %67;\n}\n"
        : ACC64(d) : "r"(da_lo), "r"(db_lo), "r"(scale_d), "n"(TB));
}
__device__ __forceinline__ void wgmma_rs_n128_tb(float (&d)[64], uint32_t a0, uint32_t a1, uint32_t a2, uint32_t a3,
                                                 uint64_t db, int scale_d) {
    asm volatile(
        "{\n.reg .pred p;\nsetp.ne.b32 p, %69, 0;\n"
        "wgmma.mma_async.sync.aligned.m64n128k16.f32.bf16.bf16 " ACC64_STR ", {%64, %65, %66, %67}, %68, p, 1, 1, 1;\n}\n"
        : ACC64(d) : "r"(a0), "r"(a1), "r"(a2), "r"(a3), "l"(db), "r"(scale_d));
}
__device__ __forceinline__ void wgmma_rs_n80(float (&d)[40], const uint32_t (&a)[4], uint32_t db_lo, int scale_d) {
    asm volatile(
        "{\n.reg .pred p;\n.reg .b64 db;\nsetp.ne.b32 p, %45, 0;\nmov.b64 db, {%44, 0x40000040};\n"
        "wgmma.mma_async.sync.aligned.m64n80k16.f32.bf16.bf16 "
        "{%0, %1, %2, %3, %4, %5, %6, %7, %8, %9, %10, %11, %12, %13, %14, %15, %16, %17, %18, %19, %20, %21, %22, %23, %24, %25, %26, %27, %28, %29, %30, %31, %32, %33, %34, %35, %36, %37, %38, %39}, "
        "{%40, %41, %42, %43}, db, p, 1, 1, 0;\n}\n"
        : "+f"(d[0]), "+f"(d[1]), "+f"(d[2]), "+f"(d[3]), "+f"(d[4]), "+f"(d[5]), "+f"(d[6]), "+f"(d[7]), "+f"(d[8]), "+f"(d[9]), "+f"(d[10]), "+f"(d[11]), "+f"(d[12]), "+f"(d[13]), "+f"(d[14]), "+f"(d[15]), "+f"(d[16]), "+f"(d[17]), "+f"(d[18]), "+f"(d[19]), "+f"(d[20]), "+f"(d[21]), "+f"(d[22]), "+f"(d[23]), "+f"(d[24]), "+f"(d[25]), "+f"(d[26]), "+f"(d[27]), "+f"(d[28]), "+f"(d[29]), "+f"(d[30]), "+f"(d[31]), "+f"(d[32]), "+f"(d[33]), "+f"(d[34]), "+f"(d[35]), "+f"(d[36]), "+f"(d[37]), "+f"(d[38]), "+f"(d[39])
        : "r"(a[0]), "r"(a[1]), "r"(a[2]), "r"(a[3]), "r"(db_lo), "r"(scale_d));
}
__device__ __forceinline__ void wgmma_ss_n256_tb(float (&d)[128], uint64_t da, uint64_t db, int scale_d) {
    asm volatile(
        "{\n.reg .pred p;\nsetp.ne.b32 p, %130, 0;\n"
        "wgmma.mma_async.sync.aligned.m64n256k16.f32.bf16.bf16 {%0, %1, %2, %3, %4, %5, %6, %7, %8, %9, %10, %11, %12, %13, %14, %15, %16, %17, %18, %19, %20, %21, %22, %23, %24, %25, %26, %27, %28, %29, %30, %31, %32, %33, %34, %35, %36, %37, %38, %39, %40, %41, %42, %43, %44, %45, %46, %47, %48, %49, %50, %51, %52, %53, %54, %55, %56, %57, %58, %59, %60, %61, %62, %63, %64, %65, %66, %67, %68, %69, %70, %71, %72, %73, %74, %75, %76, %77, %78, %79, %80, %81, %82, %83, %84, %85, %86, %87, %88, %89, %90, %91, %92, %93, %94, %95, %96, %97, %98, %99, %100, %101, %102, %103, %104, %105, %106, %107, %108, %109, %110, %111, %112, %113, %114, %115, %116, %117, %118, %119, %120, %121, %122, %123, %124, %125, %126, %127}, %128, %129, p, 1, 1, 0, 1;\n}\n"
        : "+f"(d[0]), "+f"(d[1]), "+f"(d[2]), "+f"(d[3]), "+f"(d[4]), "+f"(d[5]), "+f"(d[6]), "+f"(d[7]), "+f"(d[8]), "+f"(d[9]), "+f"(d[10]), "+f"(d[11]), "+f"(d[12]), "+f"(d[13]), "+f"(d[14]), "+f"(d[15]), "+f"(d[16]), "+f"(d[17]), "+f"(d[18]), "+f"(d[19]), "+f"(d[20]), "+f"(d[21]), "+f"(d[22]), "+f"(d[23]), "+f"(d[24]), "+f"(d[25]), "+f"(d[26]), "+f"(d[27]), "+f"(d[28]), "+f"(d[29]), "+f"(d[30]), "+f"(d[31]), "+f"(d[32]), "+f"(d[33]), "+f"(d[34]), "+f"(d[35]), "+f"(d[36]), "+f"(d[37]), "+f"(d[38]), "+f"(d[39]), "+f"(d[40]), "+f"(d[41]), "+f"(d[42]), "+f"(d[43]), "+f"(d[44]), "+f"(d[45]), "+f"(d[46]), "+f"(d[47]), "+f"(d[48]), "+f"(d[49]), "+f"(d[50]), "+f"(d[51]), "+f"(d[52]), "+f"(d[53]), "+f"(d[54]), "+f"(d[55]), "+f"(d[56]), "+f"(d[57]), "+f"(d[58]), "+f"(d[59]), "+f"(d[60]), "+f"(d[61]), "+f"(d[62]), "+f"(d[63]), "+f"(d[64]), "+f"(d[65]), "+f"(d[66]), "+f"(d[67]), "+f"(d[68]), "+f"(d[69]), "+f"(d[70]), "+f"(d[71]), "+f"(d[72]), "+f"(d[73]), "+f"(d[74]), "+f"(d[75]), "+f"(d[76]), "+f"(d[77]), "+f"(d[78]), "+f"(d[79]), "+f"(d[80]), "+f"(d[81]), "+f"(d[82]), "+f"(d[83]), "+f"(d[84]), "+f"(d[85]), "+f"(d[86]), "+f"(d[87]), "+f"(d[88]), "+f"(d[89]), "+f"(d[90]), "+f"(d[91]), "+f"(d[92]), "+f"(d[93]), "+f"(d[94]), "+f"(d[95]), "+f"(d[96]), "+f"(d[97]), "+f"(d[98]), "+f"(d[99]), "+f"(d[100]), "+f"(d[101]), "+f"(d[102]), "+f"(d[103]), "+f"(d[104]), "+f"(d[105]), "+f"(d[106]), "+f"(d[107]), "+f"(d[108]), "+f"(d[109]), "+f"(d[110]), "+f"(d[111]), "+f"(d[112]), "+f"(d[113]), "+f"(d[114]), "+f"(d[115]), "+f"(d[116]), "+f"(d[117]), "+f"(d[118]), "+f"(d[119]), "+f"(d[120]), "+f"(d[121]), "+f"(d[122]), "+f"(d[123]), "+f"(d[124]), "+f"(d[125]), "+f"(d[126]), "+f"(d[127])
        : "l"(da), "l"(db), "r"(scale_d));
}
__device__ __forceinline__ void stmatrix_x4(uint32_t addr, uint32_t r0, uint32_t r1, uint32_t r2, uint32_t r3) {
    asm volatile("stmatrix.sync.aligned.m8n8.x4.shared.b16 [%0], {%1, %2, %3, %4};" :: "r"(addr), "r"(r0), "r"(r1), "r"(r2), "r"(r3) : "memory");
}
__device__ __forceinline__ void tma_store_2d(const CUtensorMap* map, uint32_t src, int c0, int c1) {
    asm volatile("cp.async.bulk.tensor.2d.global.shared::cta.bulk_group [%0, {%2, %3}], [%1];"
                 :: "l"((uint64_t)map), "r"(src), "r"(c0), "r"(c1) : "memory");
}
__device__ __forceinline__ float ex2f(float x) { float y; asm("ex2.approx.ftz.f32 %0, %1;" : "=f"(y) : "f"(x)); return y; }
__device__ __forceinline__ uint32_t pack_bf16(float lo, float hi) {
    __nv_bfloat162 v = __floats2bfloat162_rn(lo, hi);
    return *reinterpret_cast<uint32_t*>(&v);
}
__device__ __forceinline__ void mma_16816(float (&c)[4], uint32_t a0, uint32_t a1, uint32_t a2, uint32_t a3,
                                          uint32_t b0, uint32_t b1) {
    asm volatile(
        "mma.sync.aligned.m16n8k16.row.col.f32.bf16.bf16.f32 {%0,%1,%2,%3}, {%4,%5,%6,%7}, {%8,%9}, {%0,%1,%2,%3};"
        : "+f"(c[0]), "+f"(c[1]), "+f"(c[2]), "+f"(c[3])
        : "r"(a0), "r"(a1), "r"(a2), "r"(a3), "r"(b0), "r"(b1));
}
__device__ __forceinline__ void ldmatrix_x4_trans(uint32_t& r0, uint32_t& r1, uint32_t& r2, uint32_t& r3, uint32_t addr) {
    asm volatile("ldmatrix.sync.aligned.m8n8.x4.trans.shared.b16 {%0,%1,%2,%3}, [%4];"
                 : "=r"(r0), "=r"(r1), "=r"(r2), "=r"(r3) : "r"(addr));
}

struct AttnParams {
    CUtensorMap mapQ, mapK, mapV;
    CUtensorMap mapO;
    bf16* out;
};
constexpr int FA_ITEMS = 16 * NH;
__device__ __forceinline__ int fa_qt(int t) { return 15 - ((t & 127) >> 3); }
__device__ __forceinline__ int fa_head(int t) { return (t >> 7) * 8 + (t & 7); }
#define FA_TKA 2
#define FA_SPLIT 11

#define FA_P0 4
#define FA_HO 7
#define FA_LAG 2
#define FA_PK 3
#define FA_ST 4
#define FA_TG 16
#define FA_EARLY 0
#define FA_I0 0
static_assert(FA_GRID <= 104 && FA_HO >= FA_P0 && FA_P0 >= 1, "");
constexpr float FA_MARGIN = 16.f;
#define FAT(b, i)
__device__ __forceinline__ void mbar_arrive_if(uint32_t bar, bool c) {
    asm volatile("{\n.reg .pred p;\nsetp.ne.b32 p, %1, 0;\n@p mbarrier.arrive.shared::cta.b64 _, [%0];\n}" :: "r"(bar), "r"((int)c) : "memory");
}
__device__ __forceinline__ void sched_fence(int v, int id, const float* a, const float* b, const float* c) {
    asm volatile("{\n.reg .pred p;\nsetp.ne.s32 p, %0, %1;\n@p bra SF_SKIP;\nwgmma.wait_group.sync.aligned 0;\n"
                 "st.volatile.shared.f32 [%0], %2;\nst.volatile.shared.f32 [%0], %3;\nst.volatile.shared.f32 [%0], %4;\nst.volatile.shared.f32 [%0], %5;\n"
                 "st.volatile.shared.f32 [%0], %6;\nst.volatile.shared.f32 [%0], %7;\nst.volatile.shared.f32 [%0], %8;\nst.volatile.shared.f32 [%0], %9;\n"
                 "st.volatile.shared.f32 [%0], %10;\nst.volatile.shared.f32 [%0], %11;\nst.volatile.shared.f32 [%0], %12;\nst.volatile.shared.f32 [%0], %13;\n"
                 "exit;\nSF_SKIP:\n}" :: "r"(v), "r"(1000000 + id), "f"(a[0]), "f"(a[1]), "f"(a[2]), "f"(a[3]), "f"(b[0]), "f"(b[1]), "f"(b[2]), "f"(b[3]),
                 "f"(c[0]), "f"(c[1]), "f"(c[2]), "f"(c[3]) : "memory");
}
__device__ __forceinline__ float ex2v(float x) { float y; asm volatile("ex2.approx.ftz.f32 %0, %1;" : "=f"(y) : "f"(x)); return y; }
__device__ __forceinline__ void wgmma_rs_n128_tb_lo(float (&d)[64], const uint32_t* a, uint32_t db_lo, int scale_d) {
    asm volatile(
        "{\n.reg .pred p;\n.reg .b64 db;\nsetp.ne.b32 p, %69, 0;\nmov.b64 db, {%68, 0x40000040};\n"
        "wgmma.mma_async.sync.aligned.m64n128k16.f32.bf16.bf16 " ACC64_STR ", {%64, %65, %66, %67}, db, p, 1, 1, 1;\n}\n"
        : ACC64(d) : "r"(a[0]), "r"(a[1]), "r"(a[2]), "r"(a[3]), "r"(db_lo), "r"(scale_d));
}

constexpr int M_GRID = 68;
constexpr uint32_t SD = 1024;
constexpr uint32_t MO_BAR = 229376;
constexpr int M_SMEM = MO_BAR + 1024;
constexpr uint32_t FO_Q = 0, FO_KV = 65536, FO_O = FO_KV + 2 * 65536, FO_BAR = MO_BAR + 512;
constexpr uint32_t FB_QF = FO_BAR, FB_QE = FO_BAR + 16, FB_KF = FO_BAR + 32, FB_VF = FO_BAR + 48, FB_KE = FO_BAR + 64, FB_VE = FO_BAR + 80,
                   FB_OF = FO_BAR + 96, FB_OE = FO_BAR + 112, FB_SLOT = FO_BAR + 128, FB_OSLOT = FO_BAR + 136;
__device__ __forceinline__ void attn_init(uint32_t sb) {
    for (int i = 0; i < 2; i++) {
        mbar_init(sb + FB_QF + 8 * i, 1); mbar_init(sb + FB_QE + 8 * i, 8); mbar_init(sb + FB_KF + 8 * i, 1); mbar_init(sb + FB_VF + 8 * i, 1);
        mbar_init(sb + FB_KE + 8 * i, 8); mbar_init(sb + FB_VE + 8 * i, 8); mbar_init(sb + FB_OF + 8 * i, 4); mbar_init(sb + FB_OE + 8 * i, 1);
    }
}
__device__ __forceinline__ void attn_helper(const AttnParams& P, uint32_t sb, int wg) {
    const uint32_t stg = sb + FO_O + wg * 16384;
    for (int n = 0;; n++) {
        mbar_wait(sb + FB_OF + 8 * wg, n & 1);
        int t;
        asm volatile("ld.shared.s32 %0, [%1];" : "=r"(t) : "r"(sb + FB_OSLOT + wg * 4) : "memory");
        const int qt = fa_qt(t), h = fa_head(t & 1023);
        tma_store_2d(&P.mapO, stg, 0, h * SEQ + qt * 128 + wg * 64);
        tma_store_2d(&P.mapO, stg + 8192, 64, h * SEQ + qt * 128 + wg * 64);
        asm volatile("cp.async.bulk.commit_group;" ::: "memory");
        asm volatile("cp.async.bulk.wait_group.read 0;" ::: "memory");
        mbar_arrive(sb + FB_OE + 8 * wg);
        asm volatile("cp.async.bulk.wait_group 0;" ::: "memory");
        signal_ctr(CT_CA + qt * 4 + (h >> 3));
        if (t >= 1024) break;
    }
}
__device__ __forceinline__ void attn_producer(const AttnParams& P, uint32_t sb, uint32_t free_bar, uint32_t free_par) {
    const uint32_t sQ = sb + FO_Q, sKV = sb + FO_KV;
    int b = 0, hp_ready = 0, vrow = 0, t = blockIdx.x, item = 0;
    auto load_v = [&](int i) {
        const uint32_t sv = sKV + (i & 1) * 65536 + 32768, bar = sb + FB_VF + 8 * (i & 1);
        mbar_wait(sb + FB_VE + 8 * (i & 1), ((i >> 1) & 1) ^ 1);
        mbar_expect_tx(bar, 32768);
        tma_load_2d(sv, &P.mapV, bar, 0, vrow);
        tma_load_2d(sv + 16384, &P.mapV, bar, 64, vrow);
    };
    for (;; item++) {
        const bool valid = t < FA_ITEMS;
        const int qt = fa_qt(t), h = fa_head(t);
        if (valid && !((hp_ready >> (h >> 1)) & 1)) { wait_ctr(CT_AP + (h >> 1), 96u); hp_ready |= 1 << (h >> 1); }
        const uint32_t bq = sb + FB_QF + 8 * (item & 1);
        mbar_wait(item ? sb + FB_QE + 8 * (item & 1) : free_bar + 8, item ? ((item >> 1) & 1) ^ 1 : free_par);
        asm volatile("st.shared.s32 [%0], %1;" :: "r"(sb + FB_SLOT + (item & 1) * 4), "r"(valid ? t : -1) : "memory");
        if (!valid) { mbar_arrive(bq); break; }
        mbar_expect_tx(bq, 32768);
        tma_load_2d(sQ + (item & 1) * 32768, &P.mapQ, bq, 0, h * SEQ + qt * 128);
        tma_load_2d(sQ + (item & 1) * 32768 + 16384, &P.mapQ, bq, 64, h * SEQ + qt * 128);
#pragma unroll 1
        for (int j = 0; j <= qt; j++, b++) {
            const uint32_t sk = sKV + (b & 1) * 65536, bar = sb + FB_KF + 8 * (b & 1);
            mbar_wait(b >= 2 ? sb + FB_KE + 8 * (b & 1) : free_bar + 24 + 32 * b, b >= 2 ? ((b >> 1) & 1) ^ 1 : free_par);
            if (b == 1) { TS_END2(0, 256); TS_BEGIN2(1, 256); }
            if (b == 2) wait_ctr(CT_GATE, 256u);
            mbar_expect_tx(bar, 32768);
            tma_load_2d(sk, &P.mapK, bar, 0, h * SEQ + j * 128);
            tma_load_2d(sk + 16384, &P.mapK, bar, 64, h * SEQ + j * 128);
            if (j == max(qt - FA_TKA, 0)) t = take_ticket(CT_ATTN);
            if (b > 0) load_v(b - 1);
            vrow = h * SEQ + j * 128;
        }
        t += M_GRID;
    }
    load_v(b - 1);
    mbar_wait(sb + FB_KE + 8 * (~b & 1), ((b - 1) >> 1) & 1);
}
template <uint32_t sb, typename F>
__device__ __forceinline__ void attn_consumer(const AttnParams& P, int warp, F done) {
    constexpr uint32_t sQ = SD + FO_Q, sKV = SD + FO_KV;
    constexpr uint32_t sO = sb + FO_O;
    constexpr uint32_t bar_qf = sb + FB_QF, bar_qe = sb + FB_QE, bar_kf = sb + FB_KF, bar_vf = sb + FB_VF, bar_ke = sb + FB_KE, bar_ve = sb + FB_VE,
                   bar_of = sb + FB_OF, bar_oe = sb + FB_OE, slot = sb + FB_SLOT, oslot = sb + FB_OSLOT;
    {
        const int wg = warp >> 2;
        const int lane = threadIdx.x & 31;
        const float sc = 0.08838834764831845f * 1.4426950408889634f;
        const int r0 = wg * 64 + (warp & 3) * 16 + (lane >> 2);
        float o[64], s[64];
        uint32_t pa[32];
        float m0 = 0.f, m1 = 0.f, l0 = 0.f, l1 = 0.f, i0 = 0.f, i1 = 0.f, g0 = 0.f, g1 = 0.f;
        const uint32_t q_lo = desc_lo(sQ + wg * 8192, 16), k_lo = desc_lo(sKV, 16), v_lo = desc_lo(sKV + 32768, 16384);
        auto issue_qk = [&](int b, int item) {
            const uint32_t qd = q_lo + (item & 1) * 2048, kd = k_lo + (b & 1) * 4096;
            wgmma_fence();
#pragma unroll
            for (int kk = 0; kk < 8; kk++) wgmma_ss_n128_lo<0>(s, qd + (kk >> 2) * 1024 + (kk & 3) * 2, kd + (kk >> 2) * 1024 + (kk & 3) * 2, kk != 0);
            wgmma_commit();
        };
        auto issue_pv = [&](int b, bool acc, int n) {
            const uint32_t vd = v_lo + (b & 1) * 4096;
            mbar_wait(bar_vf + 8 * (b & 1), (b >> 1) & 1);
            wgmma_fence();
#pragma unroll
            for (int kk = 0; kk < 8; kk++) if (kk < n) wgmma_rs_n128_tb_lo(o, &pa[kk * 4], vd + kk * 128, kk ? 1 : (int)acc);
            wgmma_commit();
        };
        const int lim = r0 - (lane & 3) * 2;
        int item = -1, tnext = 0;
        uint32_t k_ready = 0, q_ready = 0;
        auto mask = [&](int i) { if ((i >> 2) * 8 + (i & 1) - ((i & 2) ? 8 : 0) > lim) s[i] = -INFINITY; };
        auto exps = [&](auto mode, int b, bool hand_over, float& u0, float& u1) {
            constexpr int MODE = decltype(mode)::value;
            float p[64], u[4] = {0.f, 0.f, 0.f, 0.f};
            const uint32_t vd = v_lo + ((b - 1) & 1) * 4096;
#pragma unroll
            for (int i = 0; i < 4; i++) p[i] = fmaf(s[i], sc, (i & 2) ? -m1 : -m0);
#pragma unroll
            for (int g = 0; g < 16 + FA_LAG; g++) {
                if (MODE && g >= FA_I0 && g - FA_I0 < 8 - FA_P0) {
                    const int kk = FA_P0 + g - FA_I0;
                    wgmma_fence();
                    wgmma_rs_n128_tb_lo(o, &pa[kk * 4], vd + kk * 128, 1);
                    wgmma_commit();
                    if (kk == FA_HO) asm volatile("{\n.reg .pred p;\nsetp.ne.b32 p, %1, 0;\n@p bar.arrive %0, 256;\n}" :: "r"(4 - wg), "r"((int)hand_over) : "memory");
                }
                if (MODE && g == FA_SPLIT) {
                    FAT(b, 2);
                    wgmma_wait<0>();
                    FAT(b - 1, 3);
                    mbar_arrive_if(bar_ve + 8 * ((b - 1) & 1), lane == 0);
                }
                if (MODE && g == FA_TG) {
                    k_ready = mbar_test(bar_kf + 8 * (~b & 1), ((b + 1) >> 1) & 1);
                    if (MODE == 2) {
                        q_ready = mbar_test(bar_qf + 8 * (~item & 1), ((item + 1) >> 1) & 1);
                        asm volatile("ld.shared.s32 %0, [%1];" : "=r"(tnext) : "r"(slot + (~item & 1) * 4) : "memory");
                    }
                }
#pragma unroll
                for (int j = 0; j < 4; j++) {
                    const int i = g * 4 + j;
                    if (g < 16) p[i] = ex2v(p[i]);
                    if (g < 15) {
                        if (MODE == 2) mask(i + 4);
                        p[i + 4] = fmaf(s[i + 4], sc, (i & 2) ? -m1 : -m0);
                    }
                    if (g >= FA_LAG) u[j] += p[i - FA_LAG * 4];
                }
#pragma unroll
                for (int gg = 0; gg < 16; gg++) {
                    const int at = MODE && gg + FA_LAG < FA_SPLIT + gg / FA_PK ? FA_SPLIT + gg / FA_PK : gg + FA_LAG;
                    if (at == g) { pa[gg * 2] = pack_bf16(p[gg * 4], p[gg * 4 + 1]); pa[gg * 2 + 1] = pack_bf16(p[gg * 4 + 2], p[gg * 4 + 3]); }
                }
                if (MODE && g < 16) sched_fence(b, g + MODE * 32, &p[g * 4], &p[(g < 15 ? g + 1 : g) * 4], u);
            }
            u0 = u[0] + u[1]; u1 = u[2] + u[3];
        };
        auto quad_max = [&](float& x0, float& x1) {
            x0 = fmaxf(x0, __shfl_xor_sync(0xffffffff, x0, 1)); x1 = fmaxf(x1, __shfl_xor_sync(0xffffffff, x1, 1));
            x0 = fmaxf(x0, __shfl_xor_sync(0xffffffff, x0, 2)); x1 = fmaxf(x1, __shfl_xor_sync(0xffffffff, x1, 2));
            x0 = fmaf(x0, sc, FA_MARGIN); x1 = fmaf(x1, sc, FA_MARGIN);
        };
        auto softmax_exact = [&](bool fresh, int b) {
            wgmma_wait<0>();
            float x[8];
#pragma unroll
            for (int i = 0; i < 8; i++) x[i] = fmaxf(s[i * 2], s[i * 2 + 1]);
#pragma unroll
            for (int i = 8; i < 32; i++) x[i & 7] = fmaxf(x[i & 7], fmaxf(s[i * 2], s[i * 2 + 1]));
            float x0 = fmaxf(fmaxf(x[0], x[2]), fmaxf(x[4], x[6])), x1 = fmaxf(fmaxf(x[1], x[3]), fmaxf(x[5], x[7]));
            quad_max(x0, x1);
            if (!fresh) {
                x0 = fmaxf(x0, m0); x1 = fmaxf(x1, m1);
                const float a0 = ex2f(m0 - x0), a1 = ex2f(m1 - x1);
                l0 *= a0; l1 *= a1;
#pragma unroll
                for (int i = 0; i < 16; i++) { o[i * 4 + 0] *= a0; o[i * 4 + 1] *= a0; o[i * 4 + 2] *= a1; o[i * 4 + 3] *= a1; }
            }
            m0 = x0; m1 = x1;
            float u0, u1;
            exps(std::integral_constant<int, 0>(), b, false, u0, u1);
            l0 += u0; l1 += u1;
        };
        auto finish_rows = [&]() {
            l0 += __shfl_xor_sync(0xffffffff, l0, 1); l1 += __shfl_xor_sync(0xffffffff, l1, 1);
            l0 += __shfl_xor_sync(0xffffffff, l0, 2); l1 += __shfl_xor_sync(0xffffffff, l1, 2);
            i0 = __fdividef(g0, l0); i1 = __fdividef(g1, l1);
        };
        auto clear_out = [&](int t) {
            if (t >= 384) {
                bf16* z = P.out + (size_t)(fa_qt(t) * 128 + wg * 64 + ((threadIdx.x & 127) >> 3)) * DM + (t & 7) * 64 + (lane & 7) * 8;
#pragma unroll
                for (int i = 0; i < 4; i++) *reinterpret_cast<uint4*>(z + i * 16 * DM) = make_uint4(0u, 0u, 0u, 0u);
            }
        };
        auto store_o = [&](int t, int n, int c0, int c1) {
            const uint32_t stg = sO + wg * 16384;
            if (c0 == 0) {
                mbar_wait(bar_oe + 8 * wg, (n & 1) ^ 1);
                asm volatile("st.shared.s32 [%0], %1;" :: "r"(oslot + wg * 4), "r"(t) : "memory");
            }
            const int row = (warp & 3) * 16 + (lane >> 2);
#pragma unroll
            for (int i = c0; i < c1; i++) {
                const int ch = i * 4 + (lane & 3);
                const uint32_t a = stg + (ch >> 3) * 8192 + row * 128 + (((ch & 7) ^ (row & 7)) << 4);
                const float* q = &o[i * 16];
                asm volatile("st.shared.v4.b32 [%0], {%1, %2, %3, %4};" :: "r"(a), "r"(pack_bf16(q[0] * i0, q[1] * i0)), "r"(pack_bf16(q[4] * i0, q[5] * i0)),
                             "r"(pack_bf16(q[8] * i0, q[9] * i0)), "r"(pack_bf16(q[12] * i0, q[13] * i0)) : "memory");
                asm volatile("st.shared.v4.b32 [%0], {%1, %2, %3, %4};" :: "r"(a + 1024), "r"(pack_bf16(q[2] * i1, q[3] * i1)), "r"(pack_bf16(q[6] * i1, q[7] * i1)),
                             "r"(pack_bf16(q[10] * i1, q[11] * i1)), "r"(pack_bf16(q[14] * i1, q[15] * i1)) : "memory");
            }
        };
        auto publish_o = [&]() {
            asm volatile("fence.proxy.async.shared::cta;" ::: "memory");
            __syncwarp();
            mbar_arrive_if(bar_of + 8 * wg, lane == 0);
        };
        int t = 0, left = 0, tdone = -1, b = 0, nout = 0;
        bool first = true, staged = false;
#pragma unroll 1
        for (;; b++) {
            const bool fresh = left == 0;
            const int tprev = t;
            FAT(b, 4);
            if (staged) { publish_o(); staged = false; }
            if (fresh) {
                item++;
                if (!q_ready) {
                    mbar_wait(bar_qf + 8 * (item & 1), (item >> 1) & 1);
                    asm volatile("ld.shared.s32 %0, [%1];" : "=r"(tnext) : "r"(slot + (item & 1) * 4) : "memory");
                }
                if (tnext < 0) break;
                t = tnext;
                left = fa_qt(t) + 1;
            }
            left--;
            if (tdone >= 0) store_o(tdone, nout, 0, FA_ST);
            FAT(b, 5);
            if (!k_ready) mbar_wait(bar_kf + 8 * (b & 1), (b >> 1) & 1);
            FAT(b, 6);
            asm volatile("bar.sync %0, 256;" :: "r"(3 + wg) : "memory");
            FAT(b, 0);
            issue_qk(b, item);
            bool early = false;
            if (!fresh && !first && left != 0) {
                issue_pv(b - 1, true, FA_P0);
                wgmma_wait<1>();
                FAT(b, 1);
                mbar_arrive_if(bar_ke + 8 * (b & 1), lane == 0);
            } else {
                early = (FA_EARLY && tdone >= 0) || b == 0;
                if (early) asm volatile("bar.arrive %0, 256;" :: "r"(4 - wg) : "memory");
                if (tdone >= 0) { wgmma_wait<1>(); store_o(tdone, nout++, FA_ST, 4); staged = true; }
                tdone = -1;
                if (fresh && b > 0) { finish_rows(); tdone = tprev; l0 = l1 = 0.f; }
                if (left == 0) { g0 = __ldcg(g_gate + fa_qt(t) * 128 + r0); g1 = __ldcg(g_gate + fa_qt(t) * 128 + r0 + 8); clear_out(t); }
                if (b > 0) issue_pv(b - 1, !first, FA_P0); else { wgmma_fence(); wgmma_commit(); }
                first = fresh;
                wgmma_wait<1>();
                FAT(b, 1);
                mbar_arrive_if(bar_ke + 8 * (b & 1), lane == 0);
                mbar_arrive_if(bar_qe + 8 * (item & 1), lane == 0 && left == 0);
                if (left == 0) { mask(0); mask(1); }
                if (fresh) { m0 = fmaxf(s[0], s[1]); m1 = fmaxf(s[2], s[3]); quad_max(m0, m1); }
            }
            if (b > 0) {
                float u0, u1;
                if (left == 0) exps(std::integral_constant<int, 2>(), b, !early, u0, u1);
                else exps(std::integral_constant<int, 1>(), b, !early, u0, u1);
                if (!__any_sync(0xffffffff, !(u0 + u1 < 1.f))) { l0 += u0; l1 += u1; continue; }
            }
            softmax_exact(fresh, b);
        }
        if (tdone >= 0) { store_o(tdone, nout++, 0, 4); publish_o(); }
        issue_pv(b - 1, !first, 8);
        finish_rows();
        wgmma_wait<0>();
        done();
        store_o(t + 1024, nout, 0, 4);
        publish_o();
    }
}

__device__ __forceinline__ uint32_t cluster_ctarank() {
    uint32_t r; asm volatile("mov.u32 %0, %%cluster_ctarank;" : "=r"(r)); return r;
}
__device__ __forceinline__ uint32_t mapa_u32(uint32_t addr, uint32_t rank) {
    uint32_t r; asm volatile("mapa.shared::cluster.u32 %0, %1, %2;" : "=r"(r) : "r"(addr), "r"(rank)); return r;
}
__device__ __forceinline__ void cluster_sync_all() {
    asm volatile("barrier.cluster.arrive.release.aligned;\nbarrier.cluster.wait.acquire.aligned;" ::: "memory");
}
__device__ __forceinline__ void st_async_v4(uint32_t addr, uint32_t a, uint32_t b, uint32_t c, uint32_t d, uint32_t mbar) {
    asm volatile("st.async.weak.shared::cluster.mbarrier::complete_tx::bytes.v4.b32 [%0], {%1, %2, %3, %4}, [%5];"
                 :: "r"(addr), "r"(a), "r"(b), "r"(c), "r"(d), "r"(mbar) : "memory");
}
__device__ __forceinline__ void st_async_v2(uint32_t addr, uint32_t a, uint32_t b, uint32_t mbar) {
    asm volatile("st.async.weak.shared::cluster.mbarrier::complete_tx::bytes.v2.b32 [%0], {%1, %2}, [%3];"
                 :: "r"(addr), "r"(a), "r"(b), "r"(mbar) : "memory");
}
__device__ __forceinline__ void st_async_b32(uint32_t addr, uint32_t a, uint32_t mbar) {
    asm volatile("st.async.weak.shared::cluster.mbarrier::complete_tx::bytes.b32 [%0], %1, [%2];" :: "r"(addr), "r"(a), "r"(mbar) : "memory");
}
__device__ __forceinline__ void pace(int cycles) {
    if (cycles > 0) {
        uint32_t t0, t;
        asm volatile("mov.u32 %0, %%clock;" : "=r"(t0));
        do { asm volatile("mov.u32 %0, %%clock;" : "=r"(t)); } while (t - t0 < (uint32_t)cycles);
    }
}
__device__ __forceinline__ void mbar_wait_cl(uint32_t bar, uint32_t parity) {
    uint32_t done = 0;
    for (int it = 0; it < WAIT_LIMIT && !done; it++) {
        asm volatile(
            "{\n.reg .pred p;\n"
            "mbarrier.try_wait.parity.shared::cta.b64 p, [%1], %2;\n"
            "selp.u32 %0, 1, 0, p;\n}\n" : "=r"(done) : "r"(bar), "r"(parity) : "memory");
    }
}
__device__ __forceinline__ void ldmatrix_x4(uint32_t& r0, uint32_t& r1, uint32_t& r2, uint32_t& r3, uint32_t addr) {
    asm volatile("ldmatrix.sync.aligned.m8n8.x4.shared.b16 {%0,%1,%2,%3}, [%4];"
                 : "=r"(r0), "=r"(r1), "=r"(r2), "=r"(r3) : "r"(addr));
}
__device__ __forceinline__ void cp_async16(uint32_t dst, const void* src) {
    asm volatile("cp.async.cg.shared.global [%0], [%1], 16;" :: "r"(dst), "l"(src) : "memory");
}
__device__ __forceinline__ float bf16r(float x) { return __uint_as_float(pack_bf16(0.f, x) & 0xffff0000u); }

#define DBGP(i, w, ok)
#define DBG(i, w)
#define DBGD(i, w, dep)
#define DBG_EXTRA 0
__device__ __forceinline__ void tma_load_2d_mc(uint32_t dst, const CUtensorMap* map, uint32_t bar, int c0, int c1, uint16_t mask) {
    asm volatile(
        "cp.async.bulk.tensor.2d.shared::cluster.global.mbarrier::complete_tx::bytes.multicast::cluster [%0], [%1, {%3, %4}], [%2], %5;"
        :: "r"(dst), "l"((uint64_t)map), "r"(bar), "r"(c0), "r"(c1), "h"(mask) : "memory");
}
__device__ __forceinline__ void stmatrix_x4_trans(uint32_t addr, uint32_t r0, uint32_t r1, uint32_t r2, uint32_t r3) {
    asm volatile("stmatrix.sync.aligned.m8n8.x4.trans.shared.b16 [%0], {%1, %2, %3, %4};" :: "r"(addr), "r"(r0), "r"(r1), "r"(r2), "r"(r3) : "memory");
}
__device__ __forceinline__ void stmatrix_x2_trans(uint32_t addr, uint32_t r0, uint32_t r1) {
    asm volatile("stmatrix.sync.aligned.m8n8.x2.trans.shared.b16 [%0], {%1, %2};" :: "r"(addr), "r"(r0), "r"(r1) : "memory");
}
__device__ __forceinline__ uint4 lds128(uint32_t a) {
    uint4 v; asm volatile("ld.shared.v4.u32 {%0, %1, %2, %3}, [%4];" : "=r"(v.x), "=r"(v.y), "=r"(v.z), "=r"(v.w) : "r"(a) : "memory"); return v;
}
__device__ __forceinline__ void sts128(uint32_t a, uint32_t x, uint32_t y, uint32_t z, uint32_t w) {
    asm volatile("st.shared.v4.b32 [%0], {%1, %2, %3, %4};" :: "r"(a), "r"(x), "r"(y), "r"(z), "r"(w) : "memory");
}
__device__ __forceinline__ float2 lds64f(uint32_t a) {
    float2 v; asm volatile("ld.shared.v2.f32 {%0, %1}, [%2];" : "=f"(v.x), "=f"(v.y) : "r"(a) : "memory"); return v;
}
__device__ __forceinline__ void fence_async_smem() { asm volatile("fence.proxy.async.shared::cta;" ::: "memory"); }
#define ACC16(d) "+f"(d[0]), "+f"(d[1]), "+f"(d[2]), "+f"(d[3]), "+f"(d[4]), "+f"(d[5]), "+f"(d[6]), "+f"(d[7]), "+f"(d[8]), "+f"(d[9]), "+f"(d[10]), "+f"(d[11]), "+f"(d[12]), "+f"(d[13]), "+f"(d[14]), "+f"(d[15])
template <int ND>
__device__ __forceinline__ void wgmma_rs_n32(float (&d)[ND], const uint32_t (&a)[4], uint32_t db_lo, int scale_d) {
    asm volatile(
        "{\n.reg .pred p;\n.reg .b64 db;\nsetp.ne.b32 p, %21, 0;\nmov.b64 db, {%20, 0x40000040};\n"
        "wgmma.mma_async.sync.aligned.m64n32k16.f32.bf16.bf16 {%0,%1,%2,%3,%4,%5,%6,%7,%8,%9,%10,%11,%12,%13,%14,%15}, {%16,%17,%18,%19}, db, p, 1, 1, 0;\n}\n"
        : ACC16(d) : "r"(a[0]), "r"(a[1]), "r"(a[2]), "r"(a[3]), "r"(db_lo), "r"(scale_d));
}
template <int ND>
__device__ __forceinline__ void wgmma_ss_n32(float (&d)[ND], uint32_t da_lo, uint32_t db_lo, int scale_d) {
    asm volatile(
        "{\n.reg .pred p;\n.reg .b64 da, db;\nsetp.ne.b32 p, %18, 0;\nmov.b64 da, {%16, 0x40000040};\nmov.b64 db, {%17, 0x40000040};\n"
        "wgmma.mma_async.sync.aligned.m64n32k16.f32.bf16.bf16 {%0,%1,%2,%3,%4,%5,%6,%7,%8,%9,%10,%11,%12,%13,%14,%15}, da, db, p, 1, 1, 1, 0;\n}\n"
        : ACC16(d) : "r"(da_lo), "r"(db_lo), "r"(scale_d));
}
__device__ __forceinline__ void wgmma_ss_n8(float (&d)[4], uint32_t da_lo, uint32_t db_lo, int scale_d) {
    asm volatile(
        "{\n.reg .pred p;\n.reg .b64 da, db;\nsetp.ne.b32 p, %6, 0;\nmov.b64 da, {%4, 0x40000040};\nmov.b64 db, {%5, 0x00000010};\n"
        "wgmma.mma_async.sync.aligned.m64n8k16.f32.bf16.bf16 {%0,%1,%2,%3}, da, db, p, 1, 1, 1, 0;\n}\n"
        : "+f"(d[0]), "+f"(d[1]), "+f"(d[2]), "+f"(d[3]) : "r"(da_lo), "r"(db_lo), "r"(scale_d));
}

#define SCHED_FENCE()
__device__ __forceinline__ void wgmma_ss_n32_p(float (&d)[16], uint32_t da_lo, uint32_t db_lo, int scale_d) {
    asm volatile(
        "{\n.reg .pred p;\n.reg .b64 da, db;\nsetp.ne.b32 p, %18, 0;\nmov.b64 da, {%16, 0x40000040};\nmov.b64 db, {%17, 0x00000030};\n"
        "wgmma.mma_async.sync.aligned.m64n32k16.f32.bf16.bf16 {%0,%1,%2,%3,%4,%5,%6,%7,%8,%9,%10,%11,%12,%13,%14,%15}, da, db, p, 1, 1, 1, 0;\n}\n"
        : ACC16(d) : "r"(da_lo), "r"(db_lo), "r"(scale_d));
}

#define ACC20(d) ACC16(d), "+f"(d[16]), "+f"(d[17]), "+f"(d[18]), "+f"(d[19])
#define ACC20_STR "{%0,%1,%2,%3,%4,%5,%6,%7,%8,%9,%10,%11,%12,%13,%14,%15,%16,%17,%18,%19}"
__device__ __forceinline__ void wgmma_rs_n40(float (&d)[20], const uint32_t (&a)[4], uint32_t db_lo, int scale_d) {
    asm volatile(
        "{\n.reg .pred p;\n.reg .b64 db;\nsetp.ne.b32 p, %25, 0;\nmov.b64 db, {%24, 0x40000040};\n"
        "wgmma.mma_async.sync.aligned.m64n40k16.f32.bf16.bf16 " ACC20_STR ", {%20,%21,%22,%23}, db, p, 1, 1, 0;\n}\n"
        : ACC20(d) : "r"(a[0]), "r"(a[1]), "r"(a[2]), "r"(a[3]), "r"(db_lo), "r"(scale_d));
}
template <int TA, int SBO>
__device__ __forceinline__ void wgmma_ss_n40(float (&d)[20], uint32_t da_lo, uint32_t db_lo, int scale_d) {
    asm volatile(
        "{\n.reg .pred p;\n.reg .b64 da, db;\nsetp.ne.b32 p, %22, 0;\nmov.b64 da, {%20, %23};\nmov.b64 db, {%21, 0x40000040};\n"
        "wgmma.mma_async.sync.aligned.m64n40k16.f32.bf16.bf16 " ACC20_STR ", da, db, p, 1, 1, %24, 0;\n}\n"
        : ACC20(d) : "r"(da_lo), "r"(db_lo), "r"(scale_d), "n"(0x40000000 + SBO / 16), "n"(TA));
}

#define PT(i, th)
struct ChainParams {
    CUtensorMap mapW[3];
    CUtensorMap mapX;
    CUtensorMap mapC;
    CUtensorMap mapWo;
    CUtensorMap mapM;
};
constexpr int CH_BLOCK = 384;
constexpr int CO_WO = 0;
constexpr int CH_XC = 5120, CH_XP = 8 * CH_XC;
constexpr int CO_XB = 65536;
constexpr int CO_OB = CO_XB + 2 * CH_XP;
constexpr int CO_P = CO_OB + 8192;
constexpr int CO_LS = CO_P + 3072;
constexpr int CO_SC = CO_LS + 8 * 1280;
constexpr int CH_TW = 6144 + 8192;
constexpr int CO_T = 21 * 8192;
constexpr int CO_WA = CO_T + 6144;
constexpr int CO_ST = CO_T + 3 * CH_TW + 6144;
constexpr int CO_OWN = CO_ST + 4096, CO_OWN2 = CO_SC + 1536;
constexpr int CO_BAR = CO_OWN + 4096;
constexpr int CH_SMEM = CO_BAR + 256 + DBG_EXTRA;
#define CH_NSM 4
static_assert(CO_OWN2 + 1024 <= CO_T && CH_NSM <= 4, "smem layout");
#define CH_POLL_DELAY 260
#define CH_VPOS 2
#define CH_OW 12
#define CH_OF 12
#define CH_Q0 0
#define CH_QI 12
#define CH_QX 0
#define CH_Q1 (CH_Q0 + CH_QI + CH_QX)
#define CH_VA 5
#define CH_SPOS 0
#define CH_LSW 1
#define CH_QE 32
#define CH_KE 32
#define CH_QD 0
#define CH_GAP 0
#define CH_QS (CH_Q1 + 6)
#define CH_KS 10
#define CH_VS 0
#define CH_A7 7
#define CH_RF 0
#define CH_LSS 2
#define CH_OS 1
#define CH_MS 1
#define CH_HA 15
#define CH_LD 4
#define CH_TWP 0
#define CH_SUMC 1
#define CH_DRY 1
#define CH_D1 3000
#define CH_D2 10000
#define CH_CHAINS 4

constexpr float CH_SC = 0.08838834764831845f * 1.4426950408889634f;
__device__ __forceinline__ uint32_t pin(uint32_t v) { return __shfl_sync(0xffffffff, v, threadIdx.x & 31); }

__global__ void __cluster_dims__(8, 1, 1) __launch_bounds__(CH_BLOCK, 1)
chain_kernel(const __grid_constant__ ChainParams P) {
    extern __shared__ uint8_t smem_raw[];
    const int tid = threadIdx.x, warp = __shfl_sync(0xffffffff, tid >> 5, 0), lane = tid & 31;
    const int rank = (int)cluster_ctarank();
    constexpr uint32_t sd = 1024;
    const uint32_t sb = ((uint32_t)rank << 24) + sd;
    if (smem_u32(smem_raw) != sb) __trap();
    const int C = blockIdx.x >> 3;
    const int h = C * 4 + (rank >> 1);
    const int qd = lane >> 2, qc = lane & 3;
    const int t4 = warp & 3, wg = warp >> 2;
    pdl_launch_dependents();
    uint32_t t_start;
    asm volatile("mov.u32 %0, %%clock;" : "=r"(t_start));
    t_start = __shfl_sync(0xffffffff, t_start, 0);
    TS_BEGIN(2);
    PT(0, 0);
    const uint32_t bar_mem = sb + CO_BAR, bar_o = bar_mem + 32, bar_sc = bar_o + 32, bar_x = bar_sc + 8, bar_l = bar_x + 16, bar_w = bar_l + 8;
    const uint32_t bar_wo = bar_o + 24;
    auto chunk = [&](int i) { return (uint32_t)((rank - (i >> 1) - 4 * (i & 1)) & 7); };
    const int wcol = h * HD + (rank & 1) * 64;
    auto wdst = [&](int g, int i) { return i == 0 ? CO_WA + g * CH_TW : g && i == 7 ? CO_ST : (g ? CO_XB + CH_XP : 0) + (i - 1) * 8192; };
    if ((tid & 127) == 0) {
        const uint32_t bar = wg == 2 ? bar_x : bar_w + 8 * wg;
        mbar_init(bar, 1);
        asm volatile("fence.mbarrier_init.release.cluster;" ::: "memory");
        mbar_expect_tx(bar, wg == 2 ? CH_XP : 65536);
#pragma unroll 1
        for (int i = 0; i < 8; i++) {
            if (wg == 2) {
                tma_load_2d(sb + CO_XB + i * CH_XC, &P.mapX, bar, i * 64, 0);
                tma_load_2d(sb + CO_XB + i * CH_XC + 4096, &P.mapM, bar, i * 64, 0);
            } else tma_load_2d(sb + wdst(wg, i), &P.mapW[wg], bar, wcol, chunk(i) * 64);
        }
    }
    if (warp == 9 && lane < 15 && lane != 9 && (lane >> 1) != 6) {
        mbar_init(bar_mem + 8 * lane, 1);
        asm volatile("fence.mbarrier_init.release.cluster;" ::: "memory");
    }
    __syncthreads();
    PT(1, 0);
    if (wg == 2) {
        const int t = tid - 256;
        asm volatile("bar.arrive 10, 384;" ::: "memory");
        sts128(sb + CO_T + (2 + (t >> 6)) * CH_TW + 5120 + (t & 63) * 16, 0u, 0u, 0u, 0u);
        if (t < 32) sts128(sb + CO_P + (t >> 3) * 768 + 640 + (t & 7) * 16, 0u, 0u, 0u, 0u);
    }
    const uint32_t wfrag = (((lane >> 4) << 3) + (lane & 7)) * 128 + (((t4 * 2 + ((lane >> 3) & 1)) ^ (lane & 7)) << 4);
    const uint32_t aO = pin(sb + wg * CH_TW + wfrag);
    const uint32_t aL = pin(sb + lane * 16);
    uint32_t w[32][4];
    auto load_w = [&](int g) {
#pragma unroll
        for (int e = CH_NSM; e < 32; e++) ldmatrix_x4_trans(w[e][0], w[e][1], w[e][2], w[e][3], aO + (wdst(g, e >> 2) - g * CH_TW + (e & 3) * 2048));
        fence_async_smem();
    };
    auto pass = [&](auto& d, int g, int b, int j0, int j1, int js, bool group = true) {
        const uint32_t lo = desc_lo(sd + CO_XB + b * CH_XP, 16);
        if (group) wgmma_fence();
#pragma unroll
        for (int j = 0; j < 32; j++) if (j >= j0 && j < j1) {
            const int e = j < js ? j + CH_NSM : j < js + CH_NSM ? j - js : j;
            const uint32_t db = lo + chunk(e >> 2) * (CH_XC / 16) + (e & 3) * 2, da = desc_lo(sd + CO_WA + g * CH_TW + e * 2048, 16);
            if constexpr (sizeof(d) == 64) { if (e < CH_NSM) wgmma_ss_n32(d, da, db, j != 0); else wgmma_rs_n32(d, w[e], db, j != 0); }
            else { if (e < CH_NSM) wgmma_ss_n40<1, 1024>(d, da, db, j != 0); else wgmma_rs_n40(d, w[e], db, j != 0); }
        }
        if (group) wgmma_commit();
    };
    auto uni = [](uint32_t v) { return __shfl_sync(0xffffffff, v, 0); };
    auto roff = [&](int j) { return (uint32_t)(((rank + j) & 7) - rank) << 24; };
    auto store32 = [&](const float* d, uint32_t a) {
        stmatrix_x4_trans(a, pack_bf16(d[0], d[1]), pack_bf16(d[2], d[3]), pack_bf16(d[4], d[5]), pack_bf16(d[6], d[7]));
        stmatrix_x4_trans(a + 2048, pack_bf16(d[8], d[9]), pack_bf16(d[10], d[11]), pack_bf16(d[12], d[13]), pack_bf16(d[14], d[15]));
    };
    auto scores = [&](float (&d)[20], auto sbo, uint32_t q) {
        wgmma_fence();
#pragma unroll
        for (int ks = 0; ks < 4; ks++) wgmma_ss_n40<0, decltype(sbo)::value>(d, desc_lo(sd + CO_T + q, 16) + ks * 2, desc_lo(sd + CO_T + CH_TW, 16) + ks * 2, ks != 0);
        wgmma_commit();
    };
    auto own_scores = [&](const float (&d)[20], float (&v)[10]) {
#pragma unroll
        for (int j = 0; j < 5; j++) { v[2 * j] = d[4 * j]; v[2 * j + 1] = d[4 * j + 1]; }
    };
    auto add_scores = [&](uint32_t a, uint32_t b, float (&v)[10]) {
        const uint4 a0 = lds128(a), a1 = lds128(a + 512);
        const float2 a2 = lds64f(b);
        v[0] += __uint_as_float(a0.x); v[1] += __uint_as_float(a0.y); v[2] += __uint_as_float(a0.z); v[3] += __uint_as_float(a0.w);
        v[4] += __uint_as_float(a1.x); v[5] += __uint_as_float(a1.y); v[6] += __uint_as_float(a1.z); v[7] += __uint_as_float(a1.w);
        v[8] += a2.x; v[9] += a2.y;
    };
    auto row_max = [&](const float (&v)[10]) {
        float mx = fmaxf(fmaxf(fmaxf(v[0], v[1]), fmaxf(v[2], v[3])), fmaxf(fmaxf(v[4], v[5]), fmaxf(v[6], v[7])));
        mx = fmaxf(mx, fmaxf(v[8], v[9]));
        mx = fmaxf(mx, __shfl_xor_sync(0xffffffff, mx, 1));
        return fmaxf(mx, __shfl_xor_sync(0xffffffff, mx, 2)) * CH_SC;
    };
    auto signal_ctx = [&](int m0, int m1) {
        for (int m = m0; m < m1; m++) asm volatile("red.relaxed.gpu.global.add.u32 [%0], 1;" :: "l"(&g_ctr[CT_CB + m]) : "memory");
    };
    auto signal_step = [](int s) { return s == 33 || s == 49 || s == 57 || s == 61; };
    if (mapa_u32(bar_l, rank ^ 1) != (bar_l ^ (1u << 24)) || mapa_u32(bar_l, (rank + 3) & 7) != bar_l + roff(3)) __trap();
    asm volatile("bar.sync %0, 128;" :: "r"(12 + wg) : "memory");
    if (wg < 2) {
#pragma unroll 1
        for (int rep = CH_DRY ? 0 : 1; rep < 2; rep++) {
            if (rep) mbar_wait(bar_w + 8 * wg, 0);
            PT(3, 0);
            load_w(wg);
            if (rep) {
                asm volatile("bar.arrive %0, 160;" :: "r"(wg ? 2 : 15) : "memory");
                asm volatile("barrier.cluster.arrive.relaxed.aligned;" ::: "memory");
                mbar_wait(bar_x, 0);
            }
            asm volatile("bar.sync %0, 128;" :: "r"(12 + wg) : "memory");
            PT(7, 0);
            float d[16];
            pass(d, wg, 0, 0, 32, 0);
            wgmma_wait<0>();
            store32(d, aO + CO_T);
        }
    }
    PT(8, 0);
    TS_BEGIN(5);
    PT(9, 0);

    if (wg < 2) {
        const uint32_t aM = pin(sb + CO_XB + 4096 + (lane & 7) * 128 + (((lane >> 3) ^ (lane & 7)) << 4));
        uint32_t coff[8];
#pragma unroll
        for (int i = 0; i < 8; i++) coff[i] = uni(chunk(i) * CH_XC);
        auto mem_proj = [&](int s, int it) {
            const uint32_t par = s & 1;
            float acc[CH_CHAINS][4];
#pragma unroll
            for (int i = 0; i < CH_CHAINS; i++) acc[i][0] = acc[i][1] = acc[i][2] = acc[i][3] = 0.f;
            const uint32_t am = aM + par * CH_XP;
            uint32_t b[CH_LD][4], ok[4] = {1, 1, 1, 1}, a0 = am, a1 = am ^ 64;
            auto load = [&](int i) {
                if (i == 12) DBG(13, 0);
                if (i == 2 || (i && !(i & 3))) { a0 = ok[i >> 2] ? am : aL; a1 = a0 ^ 64; }
                uint32_t* r = b[i % CH_LD];
                ldmatrix_x4(r[0], r[1], r[2], r[3], ((i & 1) ? a1 : a0) + coff[i >> 1]);
                if (i == 1) ok[0] = mbar_try(bar_mem, par ^ 1);
                if (i == 2 || i == 4 || i == 8) ok[(i >> 2) + 1] = mbar_try(bar_mem + 8 * ((i >> 2) + 1), par ^ 1);
            };
            auto mma = [&](int i) {
                mma_16816(acc[(2 * i) % CH_CHAINS], w[2 * i][0], w[2 * i][1], w[2 * i][2], w[2 * i][3], b[i % CH_LD][0], b[i % CH_LD][1]);
                mma_16816(acc[(2 * i + 1) % CH_CHAINS], w[2 * i + 1][0], w[2 * i + 1][1], w[2 * i + 1][2], w[2 * i + 1][3], b[i % CH_LD][2], b[i % CH_LD][3]);
            };
#pragma unroll
            for (int e = 0; e < CH_NSM; e++) ldmatrix_x4_trans(w[e][0], w[e][1], w[e][2], w[e][3], aO + CO_WA + e * 2048);
            asm volatile("{\n.reg .pred p;\nsetp.eq.s32 p, %0, 0;\n@p bar.sync 10, 384;\n}" :: "r"(it) : "memory");
            DBG(11, 0);
            bool done = false;
            load(0); load(1); mma(0); mma(1);
            load(2); load(3); mma(2);
#pragma unroll
            for (int i = 4; i < 3 + CH_LD; i++) load(i);
#pragma unroll
            for (int i = 3; i < 16; i++) {
                mma(i);
                if (i + CH_LD < 16) load(i + CH_LD);
                if (i == 12 - CH_LD) done = __all_sync(0xffffffff, ok[0] & ok[1] & ok[2] & ok[3]);
                if (i == CH_HA) asm volatile("{\n.reg .pred p;\nsetp.ne.b32 p, %0, 0;\n@p bar.arrive 5, 384;\n}" :: "r"((int)done) : "memory");
            }
#pragma unroll
            for (int i = 0; i < 4; i++)
#pragma unroll
                for (int c = 1; c < CH_CHAINS; c++) acc[0][i] += acc[c][i];
            const uint32_t r0 = pack_bf16(acc[0][0], acc[0][1]);
            const uint32_t r1 = pack_bf16(acc[0][2], acc[0][3]);
            DBGD(40 + warp, warp, r0 ^ r1);
            stmatrix_x2_trans(aO + CO_T + 4096, r0, r1);
            fence_async_smem();
            return done;
        };
        if (wg == 0) {
#pragma unroll 1
            for (int s = 0; s < NSEG; s++) {
                const uint32_t par = s & 1;
#pragma unroll 1
                for (int it = 0; it < WAIT_LIMIT / 64; it++) if (mem_proj(s, it)) break;
                asm volatile("bar.arrive 1, 256;" ::: "memory");
                if (s == NSEG - 1) break;
                if (tid == 96) {
#pragma unroll
                    for (int j = 0; j < 4; j++) { mbar_expect_tx(bar_mem + 8 * j, j ? 2048 : 1024); if (j < 3) mbar_expect_tx(bar_o + 8 * j, 1024 << j); }
                }
                __syncwarp();
                uint32_t* wp = g_xbuf + (size_t)rank * 2048 + C * 256 + qc * 64 + t4 * 8 + qd;
                asm volatile("st.relaxed.gpu.global.u32 [%0], %1;" :: "l"(wp + ((s + 2) & 3) * 16384), "r"(~0u) : "memory");
                asm volatile("st.relaxed.gpu.global.u32 [%0], %1;" :: "l"(wp + ((s + 2) & 3) * 16384 + 32), "r"(~0u) : "memory");
                if (s == 0) {
                    asm volatile("barrier.cluster.wait.aligned;" ::: "memory");
                    mbar_wait(bar_wo, 0);
                    const int sr = (qd >> 2) * 2 + (qd & 1) + (qd & 2) * 4;
#pragma unroll 2
                    for (int ks = t4; ks < 32; ks += 4) {
                        const uint32_t a = sb + CO_WO + ks * 2048;
                        uint4 u[2][2];
#pragma unroll
                        for (int i = 0; i < 4; i++) { const int r = sr + (i >> 1) * 4; u[i >> 1][i & 1] = lds128(a + r * 128 + (((qc * 2 + (i & 1)) ^ (r & 7)) << 4)); }
                        __syncwarp();
#pragma unroll
                        for (int i = 0; i < 4; i++) {
                            const uint4 u0 = u[i >> 1][0], u1 = u[i >> 1][1];
                            const uint32_t sel = (i & 1) ? 0x7632 : 0x5410;
                            sts128(a + (qd + (i >> 1) * 8) * 128 + (((qc * 2 + (i & 1)) ^ qd) << 4),
                                   __byte_perm(u0.x, u0.y, sel), __byte_perm(u0.z, u0.w, sel), __byte_perm(u1.x, u1.y, sel), __byte_perm(u1.z, u1.w, sel));
                        }
                    }
                    fence_async_smem();
                }
                mbar_wait(bar_x + 8 * (par ^ 1), ((s + 1) >> 1) & 1);
                asm volatile("bar.sync 7, 384;" ::: "memory");
                float d[16];
                float c[4];
                const uint32_t alo = desc_lo(sd + CO_WO, 16), blo = desc_lo(sd + CO_OB, 128);
                wgmma_fence();
                pass(d, 0, par ^ 1, 0, CH_Q0, CH_QS, false);
                asm volatile("bar.sync 11, 256;" ::: "memory");
#pragma unroll
                for (int i = 0; i < 32; i++) {
                    if (i == 4) { pass(d, 0, par ^ 1, CH_Q0 + min(4, CH_QI), CH_Q0 + min(4, CH_QI) + CH_QX, CH_QS, false); mbar_wait_cl(bar_o, par); }
                    if (i == 8) mbar_wait_cl(bar_o + 8, par);
                    if (i == CH_OW) mbar_wait_cl(bar_o + 16, par);
                    wgmma_ss_n8(c, alo + i * 128, blo + i * 16, i != 0);
                    if (i < CH_QI) pass(d, 0, par ^ 1, CH_Q0 + i + (i < 4 ? 0 : CH_QX), CH_Q0 + i + (i < 4 ? 0 : CH_QX) + 1, CH_QS, false);
                }
                wgmma_commit();
                wgmma_wait<0>();
                asm volatile("st.relaxed.gpu.global.u32 [%0], %1;" :: "l"(wp + (s & 3) * 16384), "r"(pack_bf16(c[0], c[2])) : "memory");
                asm volatile("st.relaxed.gpu.global.u32 [%0], %1;" :: "l"(wp + (s & 3) * 16384 + 32), "r"(pack_bf16(c[1], c[3])) : "memory");
                asm volatile("bar.arrive 6, 384;" ::: "memory");
                pace(CH_QD);
                asm volatile("bar.arrive 4, 384;" ::: "memory");
                DBG(8, 0);
                pass(d, 0, par ^ 1, CH_Q1, CH_QE, CH_QS);
                DBG(21, 0);
                if (tid == 0 && s + 2 < NSEG) {
                    mbar_expect_tx(bar_x + 8 * par, 32768);
                    tma_load_2d_mc(sb + CO_XB + par * CH_XP + rank * CH_XC, &P.mapX, bar_x + 8 * par, rank * 64, (s + 2) * SEGL, (uint16_t)0xff);
                }
                __syncwarp();
                asm volatile("bar.sync 9, 256;" ::: "memory");
                wgmma_wait<0>();
                DBG(0, 0);
                store32(d, aO + CO_T);
                DBG(22, 0);
            }
            *reinterpret_cast<uint2*>(g_xbuf + 16384 + blockIdx.x * 256 + tid * 2) = make_uint2(~0u, ~0u);
        } else {
            const uint32_t usc = uni(CO_SC + min(t4, 2) * 512 + roff((rank ^ 1) - rank)), uscb = uni(bar_sc ^ (1u << 24));
            const uint32_t vaddr = pin(sb + CO_T + 2 * CH_TW + (lane & 15) * 128 + (((t4 * 2 + (lane >> 4)) ^ (lane & 7)) << 4));
            const uint32_t dsta = pin(sb + CO_OB + t4 * 256 + (qc >> 1) * 128 + qd * 16 + (qc & 1) * 8);
            auto local_pv = [&](int s, int st) {
                float dc[16];
                wgmma_fence();
#pragma unroll
                for (int ks = 0; ks < 3; ks++) wgmma_ss_n32_p(dc, desc_lo(sd + CO_T + (2 + (s & 1)) * CH_TW + ks * 2048, 16), desc_lo(sd + CO_P + ks * 256, 128), ks != 0);
                wgmma_commit();
                wgmma_wait<0>();
                store32(dc, aO - CH_TW + st);
            };
            auto store_ctx = [&](int s, int st) {
                if (tid == 128 && s >= 0) {
                    tma_store_2d(&P.mapC, sb + st, (rank & 1) * 64, h * SEQ + s * SEGL);
                    asm volatile("cp.async.bulk.commit_group;" ::: "memory");
                }
                __syncwarp();
            };
            uint32_t uo[8], ub[8];
#pragma unroll
            for (int i = 0; i < 8; i++) { uo[i] = uni(roff(i) + i * 1024); ub[i] = uni(roff(i) + bar_o + (i < 2 ? 0 : i < 4 ? 8 : 16)); }
#pragma unroll 1
            for (int s = 0; s < NSEG; s++) {
                const uint32_t par = s & 1;
#pragma unroll 1
                for (int it = 0; it < WAIT_LIMIT / 64; it++) if (mem_proj(s, it)) break;
                asm volatile("bar.sync 1, 256;" ::: "memory");
                float d[20];
                scores(d, std::integral_constant<int, 0>(), 4096);
                if (s == NSEG - 1) { wgmma_wait<0>(); break; }
                asm volatile("bar.arrive 8, 256;" ::: "memory");
                if (s == 0) asm volatile("barrier.cluster.wait.aligned;" ::: "memory");
                wgmma_wait<0>();
                {
                    const bool w0 = t4 == 0;
                    asm volatile("{\n.reg .pred p, q;\nsetp.lt.s32 p, %8, 2;\nsetp.eq.s32 q, %8, 2;\n"
                                 "@p st.async.weak.shared::cluster.mbarrier::complete_tx::bytes.v4.f32 [%0], {%2, %3, %4, %5}, [%1];\n"
                                 "@q st.async.weak.shared::cluster.mbarrier::complete_tx::bytes.v2.f32 [%0], {%6, %7}, [%1];\n}"
                                 :: "r"((aL | (s >> 10)) + usc), "r"(uscb), "f"(w0 ? d[0] : d[8]), "f"(w0 ? d[1] : d[9]),
                                    "f"(w0 ? d[4] : d[12]), "f"(w0 ? d[5] : d[13]), "f"(d[16]), "f"(d[17]), "r"(t4) : "memory");
                }
                DBG(3, 4);
                store_ctx(s - 2, CO_ST);
                uint32_t vb[3][4];
                auto load_v = [&]() {
                    asm volatile("bar.sync 3, 256;" ::: "memory");
#pragma unroll
                    for (int k = 0; k < 3; k++) ldmatrix_x4_trans(vb[k][0], vb[k][1], vb[k][2], vb[k][3], vaddr + par * CH_TW + k * 2048);
                };
                mbar_wait_cl(bar_sc, par);
                DBG(4, 4);
                float v[10];
                own_scores(d, v);
                add_scores(aL + CO_SC, aL + CO_SC + 1024, v);
                const float mx = row_max(v);
                if (CH_VPOS == 2) load_v();
#pragma unroll
                for (int j = 0; j < 10; j++) v[j] = ex2f(fmaf(v[j], CH_SC, -mx));
                uint32_t p[5];
#pragma unroll
                for (int j = 0; j < 5; j++) p[j] = pack_bf16(v[2 * j], v[2 * j + 1]);
                if (CH_VPOS == 3) load_v();
                DBG(19, 4);
                float c0[4] = {0.f, 0.f, 0.f, 0.f}, c1[4] = {0.f, 0.f, 0.f, 0.f}, cs[4] = {0.f, 0.f, 0.f, 0.f};
#pragma unroll
                for (int k = 0; k < 3; k++) {
                    const uint32_t p0 = p[2 * k], p1 = k < 2 ? p[2 * k + 1] : 0u;
                    mma_16816(cs, p0, 0u, p1, 0u, 0x3f803f80u, 0x3f803f80u);
                    mma_16816(c0, p0, 0u, p1, 0u, vb[k][0], vb[k][1]);
                    mma_16816(c1, p0, 0u, p1, 0u, vb[k][2], vb[k][3]);
                }
                float inv;
                asm volatile("rcp.approx.ftz.f32 %0, %1;" : "=f"(inv) : "f"(cs[0]));
                const uint32_t b0 = pack_bf16(c0[0] * inv, c0[1] * inv), b1 = pack_bf16(c1[0] * inv, c1[1] * inv);
                DBG(20, 4);
#pragma unroll
                for (int i = 1; i < 8; i++) {
                    st_async_v2((dsta | (s >> 10)) + uo[i], b0, b1, ub[i]);
                    if (i == CH_OS) asm volatile("st.shared.v2.b32 [%0], {%1, %2};" :: "r"(dsta), "r"(b0), "r"(b1) : "memory");
                }
                DBG(5, 4);
                asm volatile("cp.async.bulk.wait_group.read 0;" ::: "memory");
                asm volatile("bar.sync 7, 384;" ::: "memory");
                fence_async_smem();
                asm volatile("bar.arrive 11, 256;" ::: "memory");
                local_pv(s + 1, CO_ST);
                asm volatile("bar.arrive 6, 384;" ::: "memory");
                if (tid == 128) mbar_expect_tx(bar_sc, 1280);
                __syncwarp();
                mbar_wait(bar_x + 8 * (par ^ 1), ((s + 1) >> 1) & 1);
                asm volatile("bar.sync 4, 384;" ::: "memory");
                float dk[16];
                pass(dk, 1, par ^ 1, 0, CH_KE, CH_KS);
                if (tid == 128 && signal_step(s)) {
                    asm volatile("cp.async.bulk.wait_group 0;" ::: "memory");
                    signal_ctx((2 * s - 66) >> 2, s >> 2);
                }
                __syncwarp();
                DBG(1, 4);
                wgmma_wait<0>();
                DBG(2, 4);
                store32(dk, aO + CO_T);
                DBG(29, 4);
            }
            asm volatile("bar.sync 8, 256;" ::: "memory");
            store_ctx(NSEG - 3, CO_ST);
#pragma unroll 1
            for (int i = 0; i < 2; i++) {
                local_pv(i, CO_OB + i * 4096);
                fence_async_smem();
                if (i == 0) asm volatile("bar.arrive 9, 256;" ::: "memory");
                asm volatile("bar.sync 2, 128;" ::: "memory");
                store_ctx(NSEG - 2 + i, CO_OB + i * 4096);
                if (i == 0) asm volatile("bar.sync 3, 256;" ::: "memory");
            }
            if (tid == 128) {
                asm volatile("cp.async.bulk.wait_group 0;" ::: "memory");
                PT(14, 128);
                signal_ctx(15, 16);
                PT(15, 128);
            }
        }
        PT(10, 0);
    } else {
        float gs;
        auto load_gate = [&](int s) { asm volatile("ld.global.cg.f32 %0, [%1];" : "=f"(gs) : "l"(g_gate + s * SEGL + t4 * 8 + qd) : "memory"); };
        auto softmax = [&](int s) {
            float v[10];
            {
                const uint4 a0 = lds128(aL + CO_OWN + t4 * 1024), a1 = lds128(aL + CO_OWN + t4 * 1024 + 512);
                const float2 a2 = lds64f(aL + CO_OWN2 + t4 * 256 - lane * 8);
                v[0] = __uint_as_float(a0.x); v[1] = __uint_as_float(a0.y); v[2] = __uint_as_float(a0.z); v[3] = __uint_as_float(a0.w);
                v[4] = __uint_as_float(a1.x); v[5] = __uint_as_float(a1.y); v[6] = __uint_as_float(a1.z); v[7] = __uint_as_float(a1.w);
                v[8] = a2.x; v[9] = a2.y;
            }
            mbar_wait_cl(bar_l, s & 1);
            add_scores(aL + t4 * 1024 + CO_LS + (s & 1) * 5120, aL + t4 * 256 - lane * 8 + CO_LS + (s & 1) * 5120 + 4096, v);
            const int lim = t4 * 8 + qd - 2 * qc;
#pragma unroll
            for (int j = 0; j < 8; j++) if ((j >> 1) * 8 + (j & 1) > lim) v[j] = -INFINITY;
            const float mx = row_max(v);
#pragma unroll
            for (int j = 0; j < 10; j++) v[j] = ex2f(fmaf(v[j], CH_SC, -mx));
            float sum = (((v[0] + v[1]) + (v[2] + v[3])) + ((v[4] + v[5]) + (v[6] + v[7]))) + (v[8] + v[9]);
            sum += __shfl_xor_sync(0xffffffff, sum, 1);
            sum += __shfl_xor_sync(0xffffffff, sum, 2);
            asm("rcp.approx.ftz.f32 %0, %0;" : "+f"(sum));
            sum *= 1.f - gs;
            const uint32_t pa = aL + CO_P + t4 * 768;
            stmatrix_x4(pa, pack_bf16(v[0] * sum, v[1] * sum), pack_bf16(v[2] * sum, v[3] * sum), pack_bf16(v[4] * sum, v[5] * sum), pack_bf16(v[6] * sum, v[7] * sum));
            asm volatile("stmatrix.sync.aligned.m8n8.x1.shared.b16 [%0], {%1};" :: "r"(pa + 512), "r"(pack_bf16(v[8] * sum, v[9] * sum)) : "memory");
        };
        uint32_t um[8], ub[8];
#pragma unroll
        for (int i = 0; i < 8; i++) { um[i] = uni(roff((i & 1) * 4 + (i >> 1))); ub[i] = uni(roff((i & 1) * 4 + (i >> 1)) + bar_mem + 8 * (i >> 1)); }
        gs = 0.f;
#pragma unroll 1
        for (int s = 0; s < NSEG; s++) {
            const uint32_t par = s & 1;
            const bool last = s == NSEG - 1;
            if (s == 1) { wait_ctr(CT_GATE, 256u); load_gate(0); }
            softmax(s - 1);
            load_gate(s);
            if (s == 0) {
                PT(2, 256);
                int lane;
                asm volatile("mov.u32 %0, %%laneid;" : "=r"(lane));
                if (t4 >= 2) {
                    const CUtensorMap* map = t4 == 2 ? &P.mapWo : &P.mapW[2];
                    const uint32_t bar = t4 == 2 ? bar_wo : bar_w + 16;
                    const int c0 = t4 == 2 ? rank * 64 : wcol;
                    auto row = [&](int i) { return t4 == 2 ? C * 512 + ((rank - i) & 7) * 64 : (int)chunk(i) * 64; };
                    uint32_t now;
                    do { asm volatile("mov.u32 %0, %%clock;" : "=r"(now)); } while (now - t_start < (uint32_t)(t4 == 2 ? CH_D2 : CH_D1));
                    if (lane == 0) {
#pragma unroll 1
                        for (int i = 0; i < 8; i++) asm volatile("cp.async.bulk.prefetch.tensor.2d.L2.global [%0, {%1, %2}];" :: "l"(map), "r"(c0), "r"(row(i)) : "memory");
                        mbar_expect_tx(bar, 65536);
                    }
                    __syncwarp();
                    asm volatile("bar.sync %0, 160;" :: "r"(t4 == 2 ? 15 : 2) : "memory");
                    if (lane == 0) {
#pragma unroll 1
                        for (int i = 0; i < 8; i++) tma_load_2d(sb + (t4 == 2 ? CO_WO + i * 8192 : wdst(2, i)), map, bar, c0, row(i));
                    }
                } else if (t4 == 0 && lane == 0) {
                    asm volatile("cp.async.bulk.prefetch.tensor.2d.L2.global [%0, {%1, %2}];" :: "l"(&P.mapX), "r"(rank * 64), "r"(SEGL) : "memory");
                    asm volatile("prefetch.tensormap [%0];" :: "l"(&P.mapC) : "memory");
                    mbar_expect_tx(bar_sc, 1280);
                    mbar_expect_tx(bar_x + 8, 32768);
                }
                __syncwarp();
                mbar_wait(bar_w + 16, 0);
                PT(4, 256);
                load_w(2);
                asm volatile("bar.sync 14, 128;" ::: "memory");
                asm volatile("barrier.cluster.arrive.relaxed.aligned;" ::: "memory");
                if (t4 == 0 && lane == 0) {
#pragma unroll 1
                    for (int i = 0; i < 8; i++) tma_load_2d(sb + CO_XB + CH_XP + i * CH_XC, &P.mapX, bar_x + 8, i * 64, SEGL);
                }
                __syncwarp();
                PT(6, 256);
            }
            DBG(7, 8);
#pragma unroll 1
            for (int it = 0; it < (CH_RF ? WAIT_LIMIT / 64 : 0); it++)
                if (mbar_try(bar_mem, par ^ 1) & mbar_try(bar_mem + 8, par ^ 1) & mbar_try(bar_mem + 16, par ^ 1) & mbar_try(bar_mem + 24, par ^ 1)) break;
            fence_async_smem();
            asm volatile("bar.sync 5, 384;" ::: "memory");
            DBG(23, 8);
            float d[20];
            pass(d, 2, par, 0, CH_VA, CH_VS);
            asm volatile("bar.sync 8, 256;" ::: "memory");
            pass(d, 2, par, CH_VA, 32, CH_VS);
            wgmma_wait<0>();
            stmatrix_x2_trans(aO + par * CH_TW + CO_T + 4096, pack_bf16(d[16], d[17]), pack_bf16(d[18], d[19]));
            store32(d, aO + par * CH_TW + CO_T);
            DBG(24, 8);
            if (!last) asm volatile("bar.arrive 3, 256;\nbar.sync 7, 384;" ::: "memory");
            scores(d, std::integral_constant<int, 512>(), 0);
            asm volatile("{\n.reg .pred p;\nsetp.eq.s32 p, %1, 256;\n@p mbarrier.arrive.expect_tx.shared::cta.b64 _, [%0], 5120;\n}" :: "r"(bar_l), "r"(tid) : "memory");
            wgmma_wait<0>();
            auto send_scores = [&]() {
                const uint32_t a = aL + t4 * 1024, a2 = aL + t4 * 256 - lane * 8, r = roff((rank ^ 1) - rank) + CO_LS + par * 5120;
                asm volatile("st.async.weak.shared::cluster.mbarrier::complete_tx::bytes.v4.f32 [%0], {%3, %4, %5, %6}, [%2];\n"
                             "st.async.weak.shared::cluster.mbarrier::complete_tx::bytes.v4.f32 [%0 + 512], {%7, %8, %9, %10}, [%2];\n"
                             "st.async.weak.shared::cluster.mbarrier::complete_tx::bytes.v2.f32 [%1], {%11, %12}, [%2];"
                             :: "r"(a + r), "r"(a2 + r + 4096), "r"(bar_l ^ (1u << 24)), "f"(d[0]), "f"(d[1]), "f"(d[4]), "f"(d[5]),
                                "f"(d[8]), "f"(d[9]), "f"(d[12]), "f"(d[13]), "f"(d[16]), "f"(d[17]) : "memory");
                sts128(a + CO_OWN, __float_as_uint(d[0]), __float_as_uint(d[1]), __float_as_uint(d[4]), __float_as_uint(d[5]));
                sts128(a + CO_OWN + 512, __float_as_uint(d[8]), __float_as_uint(d[9]), __float_as_uint(d[12]), __float_as_uint(d[13]));
                asm volatile("st.shared.v2.f32 [%0], {%1, %2};" :: "r"(a2 + CO_OWN2), "f"(d[16]), "f"(d[17]) : "memory");
            };
            if (s == 0) asm volatile("barrier.cluster.wait.aligned;" ::: "memory");
            if (CH_LSS == 0) send_scores();
            if (last) { if (CH_LSS) send_scores(); break; }
            asm volatile("bar.arrive 4, 384;\nbar.arrive 9, 256;" ::: "memory");
            uint32_t t0, t1;
            asm volatile("bar.sync 6, 384;\nmov.u32 %0, %%clock;" : "=r"(t0) :: "memory");
            const int row = t4 * 2 + (lane >> 4);
            const uint32_t dsta = pin(sb + CO_XB + (par ^ 1) * CH_XP + rank * CH_XC + 4096 + row * 128 + ((((lane & 15) >> 1) ^ row) << 4) + (lane & 1) * 8);
            const uint32_t dst1 = pin(dsta + um[1]), bar1 = pin(ub[1] | (s >> 10));
            uint32_t sel = pin(((qd >> 1) == qc ? 0x3f80u << (qd & 1) * 16 : 0u) | (s >> 10));
            const uint2* xb = reinterpret_cast<const uint2*>(g_xbuf + (s & 3) * 16384 + (size_t)rank * 2048 + t4 * 64) + pin(lane | (s >> 10));
            if (CH_LSS == 1) send_scores();
            uint2 p[8], q[8];
            do { asm volatile("mov.u32 %0, %%clock;" : "=r"(t1) :: "memory"); } while (t1 - t0 < CH_POLL_DELAY);
#pragma unroll
            for (int k = 0; k < 8; k++)
                asm volatile("ld.relaxed.gpu.global.v2.u32 {%0, %1}, [%2];" : "=r"(p[k].x), "=r"(p[k].y) : "l"(xb + k * 128) : "memory");
            DBG(17, 8);
            if (CH_LSS == 2) send_scores();
            {
                uint32_t z;
                asm volatile("mov.u32 %0, %%clock;" : "=r"(z) :: "memory");
#pragma unroll
                for (int i = 0; i < CH_GAP; i++) asm volatile("mul.lo.u32 %0, %0, %0;" : "+r"(z));
                asm volatile("and.b32 %0, %0, %1;" : "+r"(z) : "r"(s >> 10));
                xb += z;
            }
#pragma unroll
            for (int k = 0; k < 8; k++)
                asm volatile("ld.relaxed.gpu.global.v2.u32 {%0, %1}, [%2];" : "=r"(q[k].x), "=r"(q[k].y) : "l"(xb + k * 128) : "memory");
            uint32_t m0, m1;
            {
                uint32_t z;
                asm volatile("mov.u32 %0, %%clock;" : "=r"(z) :: "memory");
                sel |= z & (s >> 10);
            }
            auto sum = [&](const uint2 (&p)[8]) {
                float c[CH_SUMC][4];
#pragma unroll
                for (int k = 0; k < 4; k++) {
                    if (k < CH_SUMC) c[k][0] = c[k][1] = c[k][2] = c[k][3] = 0.f;
                    mma_16816(c[k % CH_SUMC], p[2 * k].x, p[2 * k].y, p[2 * k + 1].x, p[2 * k + 1].y, sel, sel);
                }
#pragma unroll
                for (int k = 1; k < CH_SUMC; k++) { c[0][0] += c[k][0]; c[0][1] += c[k][1]; c[0][2] += c[k][2]; c[0][3] += c[k][3]; }
                m0 = pack_bf16(c[0][0], c[0][1]);
                m1 = pack_bf16(c[0][2], c[0][3]);
                uint32_t ok;
                asm volatile("{\n.reg .pred p;\nsetp.num.f32 p, %1, %2;\nvote.sync.all.pred p, p, 0xffffffff;\nselp.u32 %0, 1, 0, p;\n}" : "=r"(ok) : "f"(c[0][0]), "f"(c[0][2]));
                return ok;
            };
            if (!sum(p)) {
                DBG(12, 8);
#pragma unroll 1
                for (int it = 0; it < WAIT_LIMIT / 4; it++) {
                    if (sum(q)) break;
                    uint32_t bad = 0;
#pragma unroll
                    for (int k = 0; k < 8; k++) bad |= (max(q[k].x, q[k].y) == ~0u ? 1u : 0u) << k;
                    if (__all_sync(0xffffffff, bad == 0u)) break;
                    if (it == 0) DBG(14, 8);
                    if (it == 1) DBG(15, 8);
#pragma unroll
                    for (int k = 0; k < 8; k++)
                        if (bad & (1u << k))
                            asm volatile("ld.relaxed.gpu.global.v2.u32 {%0, %1}, [%2];" : "=r"(q[k].x), "=r"(q[k].y) : "l"(xb + k * 128) : "memory");
                }
            }
            DBG(9, 8);
#pragma unroll
            for (int i = 1; i < 8; i++) {
                st_async_v2(i == 1 ? dst1 : dsta + um[i], m0, m1, i == 1 ? bar1 : ub[i]);
                if (i == CH_MS) asm volatile("st.shared.v2.b32 [%0], {%1, %2};\nbar.arrive 10, 384;" :: "r"(dsta), "r"(m0), "r"(m1) : "memory");
            }
            if (s == 1000000) {
#pragma unroll
                for (int k = 0; k < 8; k++) asm volatile("st.volatile.shared.v2.u32 [%0], {%1, %2};" :: "r"(s), "r"(q[k].x), "r"(q[k].y) : "memory");
            }
            DBG(10, 8);
        }
        PT(11, 256);
        asm volatile("bar.sync 9, 256;" ::: "memory");
        softmax(NSEG - 1);
        fence_async_smem();
        asm volatile("bar.arrive 3, 256;" ::: "memory");
    }
    __syncthreads();
    cluster_sync_all();
    TS_END(2);
}

struct Proj2Params {
    CUtensorMap mapA[2];
    CUtensorMap mapW[3];
    bf16* out[3];
};
#define P2T(i)
#define P2_NOMMA 0
#define P2_NOLOAD 0
#define P2_ROT 4
#define P2_NP 1
#define P2_NI 4
constexpr int P2_STAGES = 6;
constexpr int P2_ITEMS = 168 + 48;

__device__ __forceinline__ int p2_reps(int t) { return t >= 168 ? 1 : 2; }
__device__ __forceinline__ void p2_tile(int t, int w, int& z, int& mp, int& head) {
    if (t >= 168) { w += ((t - 168) & 1) * 2; t = 168 + ((t - 168) >> 1); }
    const int hq = (t / 24 + P2_ROT) & 7, v = t % 24;
    mp = v & 7;
    if (v < 16) { head = hq * 4 + (v >> 3) * 2 + (w >> 1); z = 1 + (w & 1); }
    else { head = hq * 4 + w; z = 0; }
}
__device__ __forceinline__ void mbar_arrive_remote(uint32_t bar_cluster_addr) {
    asm volatile("mbarrier.arrive.release.cluster.shared::cluster.b64 _, [%0];" :: "r"(bar_cluster_addr) : "memory");
}
__device__ __forceinline__ void mbar_arrive_cl(uint32_t bar_cluster_addr) {
    asm volatile("mbarrier.arrive.shared::cluster.b64 _, [%0];" :: "r"(bar_cluster_addr) : "memory");
}
__device__ __forceinline__ void mbar_wait_acq_cluster(uint32_t bar, uint32_t parity) {
    asm volatile(
        "{\n"
        ".reg .pred p, q;\n"
        ".reg .u32 c;\n"
        "mov.u32 c, 0;\n"
        "WAIT_LOOP_C:\n"
        "mbarrier.try_wait.parity.acquire.cluster.shared::cta.b64 p, [%0], %1;\n"
        "@p bra WAIT_DONE_C;\n"
        "add.u32 c, c, 1;\n"
        "setp.lt.u32 q, c, 4000000;\n"
        "@q bra WAIT_LOOP_C;\n"
        "WAIT_DONE_C:\n"
        "}\n" :: "r"(bar), "r"(parity) : "memory");
}
__device__ __forceinline__ uint4 quad_transpose(uint32_t p0, uint32_t p1, uint32_t p2, uint32_t p3, int lane) {
    const bool o1 = lane & 1, o2 = lane & 2;
    uint32_t s0 = o1 ? p0 : p1, s1 = o1 ? p2 : p3;
    s0 = __shfl_xor_sync(0xffffffff, s0, 1); s1 = __shfl_xor_sync(0xffffffff, s1, 1);
    const uint32_t a_lo = o1 ? s0 : p0, a_hi = o1 ? p1 : s0, b_lo = o1 ? s1 : p2, b_hi = o1 ? p3 : s1;
    uint32_t t0 = o2 ? a_lo : b_lo, t1 = o2 ? a_hi : b_hi;
    t0 = __shfl_xor_sync(0xffffffff, t0, 2); t1 = __shfl_xor_sync(0xffffffff, t1, 2);
    return o2 ? make_uint4(t0, t1, b_lo, b_hi) : make_uint4(a_lo, a_hi, t0, t1);
}
#define P2_PACE 35
#define P2_PACE2 0
template <bool PERM, int PACE = 0>
__device__ __forceinline__ void store_frag_128(const float (&acc)[64], bf16* obase, int lane) {
#pragma unroll
    for (int rr = 0; rr < 2; rr++)
#pragma unroll
        for (int g = 0; g < 4; g++) {
            const float* a = &acc[g * 16 + rr * 2];
            const uint32_t p0 = pack_bf16(a[0], a[1]), p1 = pack_bf16(a[4], a[5]), p2 = pack_bf16(a[8], a[9]), p3 = pack_bf16(a[12], a[13]);
            *reinterpret_cast<uint4*>(obase + (size_t)(rr * 8) * HD + g * 32) = PERM ? make_uint4(p0, p1, p2, p3) : quad_transpose(p0, p1, p2, p3, lane);
            pace(PACE);
        }
}
struct OutParams {
    CUtensorMap mapCtx[2];
    CUtensorMap mapWo[2];
    CUtensorMap mapOut;
};

#define OT(i)
#define OTP(i, th)
constexpr int O2_STAGES = 4;
#define O2_NL 16
constexpr int O2_GRID = 4 * O2_NL;
#define O2_FINE 8

constexpr uint32_t OB_FULL = 0, OB_EMPTY = 32, OB_ITEM = 64, OB_SLOT = 128, OB_STOP = 160;
__device__ __forceinline__ void out_init(uint32_t bars) {
    for (int i = 0; i < O2_STAGES; i++) {
        mbar_init(bars + OB_FULL + 8 * i, 1); mbar_init(bars + OB_EMPTY + 8 * i, 4); mbar_init(bars + OB_ITEM + 16 * i, 1); mbar_init(bars + OB_ITEM + 16 * i + 8, 1);
    }
    sts128(bars + OB_STOP, 0u, 0u, 0u, 0u);
}
__device__ __forceinline__ void out_map(int cid, int& pt, int& h0) {
    if (cid < 32) { pt = cid < 16 ? cid : 31 - cid; h0 = cid >= 16; }
    else if (cid < 34) { pt = 12 + (cid & 1); h0 = 2; }
    else { pt = 14 + (cid & 1); h0 = 63 - ((cid - 34) >> 1); }
}
__device__ __forceinline__ void out_finished() {
    if (atomicAdd(&g_ctr[CT_FIN], 1u) == M_GRID + O2_GRID - 1)
        for (int i = 0; i < CT_N / 4; i++) reinterpret_cast<uint4*>(g_ctr)[i] = make_uint4(0u, 0u, 0u, 0u);
}
__device__ __forceinline__ void out_producer(const OutParams& P, uint32_t sbase, uint32_t bars, uint32_t rank, int pt, int h0, bool lead, bool LATE, int tnext) {
    const uint32_t bar_full = bars + OB_FULL, bar_empty = bars + OB_EMPTY, bar_item = bars + OB_ITEM, slot = bars + OB_SLOT, stop = bars + OB_STOP;
    const int ne = (pt >> 1) == 6 ? 3 : 2, nh = pt >= 14 ? 64 - O2_NL : 64;
    const int mt = (pt >> 1) * 2 + (int)rank, m0 = mt * 128, n0 = (pt & 1) * 256;
    int s = 0, ready = LATE ? 16 : 0, q = h0 * 2, qe = q + 2; uint32_t ph = LATE;
    for (int ic = 0;; ic++) {
        if (lead && rank == 0) {
            const int t = tnext + ne;
            asm volatile("st.shared.s32 [%0], %1;" :: "r"(slot + (ic & 7) * 4), "r"(t) : "memory");
            mbar_arrive(bar_item + 8 * (ic & 7));
            st_async_b32(mapa_u32(slot + (ic & 7) * 4, 1), (uint32_t)t, mapa_u32(bar_item + 8 * (ic & 7), 1));
            if (t < nh + O2_FINE) tnext = take_ticket(CT_OT + pt);
        }
#pragma unroll 1
        for (; q < qe; q++) {
            const int b = q >> 6, head = (q >> 1) & 31, dk = (q & 1) * 64;
            mbar_wait(bar_empty + 8 * s, ph);
            const uint32_t sa = sbase + s * 49152;
            if (lead) {
                const int f = b ? 4 : head >> 3;
                if (!((ready >> f) & 1)) {
                    if (b && !(ready & 8)) { wait_ctr(CT_CA + mt * 4 + 3, 16u); ready |= 8; }
                    wait_ctr(b ? CT_CB + mt : CT_CA + mt * 4 + f, b ? 64u : 16u); ready |= 1 << f;
                }
                if (!LATE || ic > 0) {
                    mbar_expect_tx(bar_full + 8 * s, 49152);
                    tma_load_2d(sa, &P.mapCtx[b], bar_full + 8 * s, dk, head * SEQ + m0);
                }
            } else {
                for (int j = (int)rank * 2; j < (int)rank * 2 + 2; j++)
                    tma_load_2d_mc(sa + 16384 + j * 8192, &P.mapWo[b], bar_full + 8 * s, n0 + j * 64, head * HD + dk, (uint16_t)3);
            }
            if (++s == O2_STAGES) { s = 0; ph ^= 1; }
        }
        if (lead && rank == 1) mbar_expect_tx(bar_item + 8 * (ic & 7), 4);
        mbar_wait(bar_item + 8 * (ic & 7), (ic >> 3) & 1);
        int t;
        asm volatile("ld.shared.s32 %0, [%1];" : "=r"(t) : "r"(slot + (ic & 7) * 4) : "memory");
        if (t >= nh + O2_FINE) break;
        if (t < nh - O2_FINE) { q = 2 * t; qe = q + 2; } else { q = nh - O2_FINE + t; qe = q + 1; }
    }
    if (lead) {
        asm volatile("prefetch.tensormap [%0];" :: "l"(&P.mapOut) : "memory");
        if (!(ready & 8)) wait_ctr(CT_CA + mt * 4 + 3, 16u);
        mbar_wait(bar_empty + 8 * s, ph);
        asm volatile("st.shared.s32 [%0], %1;" :: "r"(stop + s * 4), "r"(1) : "memory");
        mbar_arrive(bar_full + 8 * s);
        out_finished();
        for (int i = 1; i < O2_STAGES; i++) {
            if (++s == O2_STAGES) { s = 0; ph ^= 1; }
            mbar_wait(bar_empty + 8 * s, ph);
        }
    }
}
__device__ __forceinline__ void out_consumer(const OutParams& P, uint32_t sbase, uint32_t bars, uint32_t rank, int pt, int warp) {
    const uint32_t bar_full = bars + OB_FULL, bar_empty = bars + OB_EMPTY, stop = bars + OB_STOP;
    const int m0 = ((pt >> 1) * 2 + (int)rank) * 128, n0 = (pt & 1) * 256;
    const int wg = warp >> 2, lane = threadIdx.x & 31;
    const bool elected = (threadIdx.x & 127) == 0;
    float acc[128];
#pragma unroll
    for (int i = 0; i < 128; i++) acc[i] = 0.f;
    int s = 0, sprev = 0; uint32_t ph = 0;
#pragma unroll 1
    for (int i = 0;; i++) {
        mbar_wait(bar_full + 8 * s, ph);
        int st;
        asm volatile("ld.shared.s32 %0, [%1];" : "=r"(st) : "r"(stop + s * 4) : "memory");
        if (st) break;
        if (i == 0) OT(1);
        const uint32_t sa = sbase + s * 49152 + wg * 8192, sb = sbase + s * 49152 + 16384;
        wgmma_fence();
#pragma unroll
        for (int kk = 0; kk < 4; kk++)
            wgmma_ss_n256_tb(acc, make_desc(sa + kk * 32, 16, 1024), make_desc(sb + kk * 2048, 8192, 1024), 1);
        wgmma_commit();
        if (i > 0) {
            wgmma_wait<1>();
            if (elected) { const uint32_t e = bar_empty + 8 * sprev; mbar_arrive_cl(mapa_u32(e, 0)); mbar_arrive_cl(mapa_u32(e, 1)); }
        }
        sprev = s;
        if (++s == O2_STAGES) { s = 0; ph ^= 1; }
    }
    wgmma_wait<0>();
    if (elected) { const uint32_t e = bar_empty + 8 * sprev; mbar_arrive_cl(mapa_u32(e, 0)); mbar_arrive_cl(mapa_u32(e, 1)); }
    asm volatile("bar.sync %0, 128;" :: "r"(1 + wg) : "memory");
    OT(3);
    const int row = (lane & 7) + ((lane >> 3) & 1) * 8;
#pragma unroll
    for (int bx = 0; bx < 4; bx++) {
        const uint32_t stg = sbase + bx * 49152 + warp * 2048;
#pragma unroll
        for (int j = 0; j < 8; j += 2) {
            const float* a = &acc[bx * 32 + j * 4];
            stmatrix_x4(stg + row * 128 + (((j + (lane >> 4)) ^ (row & 7)) << 4), pack_bf16(a[0], a[1]), pack_bf16(a[2], a[3]), pack_bf16(a[4], a[5]), pack_bf16(a[6], a[7]));
        }
        asm volatile("fence.proxy.async.shared::cta;" ::: "memory");
        __syncwarp();
        if (lane == 0)
            asm volatile("cp.reduce.async.bulk.tensor.2d.global.shared::cta.add.tile.bulk_group [%0, {%2, %3}], [%1];"
                         :: "l"((uint64_t)&P.mapOut), "r"(stg), "r"(n0 + bx * 64), "r"(m0 + warp * 16) : "memory");
    }
    OT(4);
    if (lane == 0) {
        asm volatile("cp.async.bulk.commit_group;" ::: "memory");
        asm volatile("cp.async.bulk.wait_group.read 0;" ::: "memory");
    }
}

constexpr int O2_SMEM = O2_STAGES * 49152 + 1024 + 256;
__global__ void __cluster_dims__(2, 1, 1) __launch_bounds__(320, 1)
out2_kernel(const __grid_constant__ OutParams P) {
    extern __shared__ uint8_t smem_raw[];
    const uint32_t sbase = (smem_u32(smem_raw) + 1023) & ~1023u;
    const uint32_t bars = sbase + O2_STAGES * 49152;
    const int warp = threadIdx.x >> 5, lane = threadIdx.x & 31;
    const uint32_t rank = cluster_ctarank();
    int pt, h0;
    out_map(M_GRID / 2 + (blockIdx.x >> 1), pt, h0);
    const int mt = (pt >> 1) * 2 + (int)rank;
    TS_BEGIN(4);
    OT(0);
    int tnext = 0;
    if (threadIdx.x == 256) {
        if (rank == 0) tnext = take_ticket(CT_OT + pt);
        out_init(bars);
        asm volatile("fence.mbarrier_init.release.cluster;" ::: "memory");
    }
    __syncwarp();
    asm volatile("barrier.cluster.arrive.relaxed.aligned;" ::: "memory");
    if (threadIdx.x == 256) {
        asm volatile("prefetch.tensormap [%0];" :: "l"(&P.mapCtx[1]) : "memory");
        wait_ctr(CT_CB + mt, 64u);
        for (int i = 0; i < 2; i++) {
            mbar_expect_tx(bars + OB_FULL + 8 * i, 49152);
            tma_load_2d(sbase + i * 49152, &P.mapCtx[1], bars + OB_FULL + 8 * i, i * 64, (h0 & 31) * SEQ + mt * 128);
        }
    }
    if (threadIdx.x == 288) asm volatile("prefetch.tensormap [%0];" :: "l"(&P.mapWo[1]) : "memory");
    __syncwarp();
    asm volatile("barrier.cluster.wait.aligned;" ::: "memory");
    if (warp >= 8) {
        if (lane == 0) out_producer(P, sbase, bars, rank, pt, h0, warp == 8, true, tnext);
    } else {
        out_consumer(P, sbase, bars, rank, pt, warp);
        TS_END(4);
    }
}

struct MainParams { Proj2Params p; AttnParams a; OutParams o; const bf16 *x, *gate_w; };
__device__ __forceinline__ int p2_apos(int k) { return k < 2 ? k : k < 6 ? k + 2 : k - 4; }
__global__ void __cluster_dims__(2, 1, 1) __launch_bounds__(384, 1) main_kernel(const __grid_constant__ MainParams MP) {
    const Proj2Params& P = MP.p;
    extern __shared__ uint8_t smem_raw[];
    const uint32_t rank = cluster_ctarank();
    const uint32_t sbase = (rank << 24) + SD;
    if (smem_u32(smem_raw) != sbase) __trap();
    const uint32_t sA = sbase, sB = sbase + 131072;
    const uint32_t bars = sbase + MO_BAR, obars = bars + 768;
    const uint32_t a_full = bars, a_empty = bars + 64, b_full = bars + 128, b_empty = b_full + 8 * P2_STAGES;
    const uint32_t item_bar = b_empty + 8 * P2_STAGES, item_in = item_bar + 16, slot = item_in + 16;
    const uint32_t note_bar = slot + 16, note_free = note_bar + 64, note = note_free + 64;
    const int warp = __shfl_sync(0xffffffff, threadIdx.x >> 5, 0), lane = threadIdx.x & 31;
    int pt, h0;
    out_map(blockIdx.x >> 1, pt, h0);
    TS_BEGIN(0);
    if (threadIdx.x == 0) {
        for (int i = 0; i < 8; i++) { mbar_init(a_full + 8 * i, 1); mbar_init(a_empty + 8 * i, 2); }
        for (int i = 0; i < P2_STAGES; i++) { mbar_init(b_full + 8 * i, 1); mbar_init(b_empty + 8 * i, 2); }
        mbar_init(item_bar, 1); mbar_init(item_bar + 8, 1); mbar_init(item_in, 2); mbar_init(item_in + 8, 2);
        for (int i = 0; i < 8; i++) { mbar_init(note_bar + 8 * i, 1); mbar_init(note_free + 8 * i, 1); }
        asm volatile("fence.mbarrier_init.release.cluster;" ::: "memory");
    }
    if (threadIdx.x == 32) {
        attn_init(sbase);
        asm volatile("fence.mbarrier_init.release.cluster;" ::: "memory");
    }
    if (threadIdx.x == 256) {
        out_init(obars);
        asm volatile("fence.mbarrier_init.release.cluster;" ::: "memory");
    }
    __syncthreads();
    asm volatile("barrier.cluster.arrive.relaxed.aligned;" ::: "memory");
    pdl_launch_dependents();
    if (warp >= 8) {
    asm volatile("setmaxnreg.dec.sync.aligned.u32 40;");
    asm volatile("barrier.cluster.wait.aligned;" ::: "memory");
    if (warp == 9) {
        if (lane == 0) {
            for (int n = 0;; n++) {
                const int e = (n & 1) * 4 + ((n >> 1) & 3);
                mbar_wait(note_bar + 8 * e, (n >> 3) & 1);
                int m;
                asm volatile("ld.shared.s32 %0, [%1];" : "=r"(m) : "r"(note + e * 4) : "memory");
                mbar_arrive(note_free + 8 * e);
                if (m < 0) break;
                signal_ctr(m);
            }
            attn_helper(MP.a, sbase, 0);
        }
    } else if (warp == 10) {
        if (lane == 0) {
            auto publish = [&](int ic, int tq) {
                const int t = tq < P2_ITEMS ? tq : -1;
                asm volatile("st.shared.s32 [%0], %1;" :: "r"(slot + (ic & 3) * 4), "r"(t) : "memory");
                mbar_arrive(item_bar + 8 * (ic & 1));
                st_async_b32(mapa_u32(slot + (ic & 3) * 4, 1), (uint32_t)t, mapa_u32(item_bar + 8 * (ic & 1), 1));
            };
            const int npair = M_GRID / 2, pair = (int)(blockIdx.x >> 1);
            if (rank == 0) publish(0, pair);
            for (int ic = 0;; ic++) {
                if (rank == 1) mbar_expect_tx(item_bar + 8 * (ic & 1), 4);
                mbar_wait(item_bar + 8 * (ic & 1), (ic >> 1) & 1);
                int t;
                asm volatile("ld.shared.s32 %0, [%1];" : "=r"(t) : "r"(slot + (ic & 3) * 4) : "memory");
                if (t < 0) break;
                int z0, mp, h0;
                p2_tile(t, 0, z0, mp, h0);
                const int aidx = z0 >= 1 ? 1 : 0;
                const int m0 = (2 * mp + (int)rank) * 128;
                for (int k = 0; k < 8; k++) {
                    mbar_wait(a_empty + 8 * k, (ic & 1) ^ 1);
                    if (P2_NOLOAD) mbar_arrive(a_full + 8 * k); else {
                    mbar_expect_tx(a_full + 8 * k, 16384);
                    tma_load_2d(sA + p2_apos(k) * 16384, &P.mapA[aidx], a_full + 8 * k, k * 64, m0); }
                }
                if (rank == 0) {
                    mbar_wait(item_in + 8 * (ic & 1), (ic >> 1) & 1);
                    publish(ic + 1, ic == 0 ? npair + pair : pair < P2_NP && ic + 1 >= P2_NI ? P2_ITEMS : 2 * npair + (int)atomicAdd(&g_ctr[CT_PROJ], 1u));
                }
            }
            attn_helper(MP.a, sbase, 1);
        }
    } else {
        if (lane == 0) {
            const int par2 = warp == 8 ? 0 : 1;
            int it = 0, ic = 0; uint32_t bph = 0;
            for (;; ic++) {
                mbar_wait(item_bar + 8 * (ic & 1), (ic >> 1) & 1);
                int t;
                asm volatile("ld.shared.s32 %0, [%1];" : "=r"(t) : "r"(slot + (ic & 3) * 4) : "memory");
                if (t < 0) break;
                const int nt = 2 * p2_reps(t);
                for (int w = 0; w < nt; w++) {
                    int z, mp, hd;
                    p2_tile(t, w, z, mp, hd);
                    for (int k = 0; k < 8; k++) {
                        const int s = it; const uint32_t phb = bph;
                        if (++it == P2_STAGES) { it = 0; bph ^= 1; }
                        if ((k & 1) != par2) continue;
                        mbar_wait(b_empty + 8 * s, phb ^ 1);
                        if (P2_NOLOAD) { mbar_arrive(b_full + 8 * s); continue; }
                        mbar_expect_tx(b_full + 8 * s, 16384);
                        tma_load_2d_mc(sB + s * 16384 + rank * 8192, &P.mapW[z], b_full + 8 * s, hd * 128 + (int)rank * 64, k * 64, (uint16_t)3);
                    }
                }
            }
            int tnext = 0;
            if (warp == 8) {
                attn_producer(MP.a, sbase, a_empty, ~ic & 1);
                TS_END2(1, 256); TS_BEGIN2(3, 256);
                if (rank == 0) tnext = take_ticket(CT_OT + pt);
                for (int i = 0; i < 4; i++) {
                    const uint32_t e = mapa_u32(obars + OB_EMPTY + 8 * (i & 1), i >> 1);
                    mbar_arrive_cl(e); mbar_arrive_cl(e);
                }
            }
            out_producer(MP.o, sbase, obars, rank, pt, h0, warp == 8, false, tnext);
            TS_END2(3, 256);
        }
    }
    } else {
        asm volatile("setmaxnreg.inc.sync.aligned.u32 232;");
        asm volatile("barrier.cluster.wait.aligned;" ::: "memory");
        const int wg = warp >> 2;
        float acc[2][64];
        const uint32_t a_lo = desc_lo(SD, 16), b_lo0 = desc_lo(SD + 131072, 8192);
        const bool elected = (threadIdx.x & 127) == 0;
        int s = (wg * 8) % P2_STAGES;
        uint32_t ph = ((wg * 8) / P2_STAGES) & 1;
        int nnote = 0;
        if (wg == 1) {
            asm volatile("bar.arrive 3, 256;" ::: "memory");
            if (blockIdx.x < 64) {
                const int r = blockIdx.x * 32 + (warp & 3) * 8 + (lane >> 2);
                float c[4] = {0.f, 0.f, 0.f, 0.f};
                uint4 xv[16], gv[16];
#pragma unroll
                for (int i = 0; i < 16; i++) {
                    xv[i] = __ldg(reinterpret_cast<const uint4*>(MP.x + (size_t)r * DM + i * 32 + (lane & 3) * 8));
                    gv[i] = __ldg(reinterpret_cast<const uint4*>(MP.gate_w + i * 32 + (lane & 3) * 8));
                }
                auto mul = [](uint32_t a, uint32_t b) { uint32_t p; asm("mul.rn.bf16x2 %0, %1, %2;" : "=r"(p) : "r"(a), "r"(b)); return p; };
#pragma unroll
                for (int i = 0; i < 16; i++)
                    mma_16816(c, mul(xv[i].x, gv[i].x), mul(xv[i].y, gv[i].y), mul(xv[i].z, gv[i].z), mul(xv[i].w, gv[i].w), 0x3f803f80u, 0x3f803f80u);
                if ((lane & 3) == 0) g_gate[r] = bf16r(__fdividef(1.f, 1.f + __expf(-bf16r(c[0] + c[2]))));
                __syncwarp();
                if (lane == 0) signal_ctr_generic(CT_GATE);
                __syncwarp();
            }
        }
        for (int ic = 0;; ic++) {
            mbar_wait(item_bar + 8 * (ic & 1), (ic >> 1) & 1);
            int t;
            asm volatile("ld.shared.s32 %0, [%1];" : "=r"(t) : "r"(slot + (ic & 3) * 4) : "memory");
            t = __shfl_sync(0xffffffff, t, 0);
            P2T(7);
            if (wg == 0 && t < 0) {
                if (elected) {
                    const int e = nnote & 3;
                    mbar_wait(note_free + 8 * e, ((nnote >> 2) & 1) ^ 1);
                    asm volatile("st.shared.s32 [%0], %1;" :: "r"(note + e * 4), "r"(-1) : "memory");
                    mbar_arrive(note_bar + 8 * e);
                }
            }
            if (t < 0) break;
            const int reps = p2_reps(t);
#pragma unroll 1
            for (int rp = 0; rp < reps; rp++) {
            const bool first = rp == 0, last = rp == reps - 1;
            int z, mp, head;
            p2_tile(t, rp * 2 + wg, z, mp, head);
            asm volatile("bar.sync %0, 256;" :: "r"(3 + wg) : "memory");
            P2T(0);
            if (wg == 1 && last && elected) mbar_arrive_cl(mapa_u32(item_in + 8 * (ic & 1), 0));
            int sprev = 0;
#pragma unroll
            for (int k = 0; k < 8; k++) {
                if (k == 0) P2T(5);
                if (wg == 0 && first) mbar_wait(a_full + 8 * k, ic & 1);
                if (k == 0) P2T(6);
                mbar_wait(b_full + 8 * s, ph);
                if (k == 7) asm volatile("bar.arrive %0, 256;" :: "r"(4 - wg) : "memory");
                if (k == 0) P2T(1);
                if (k == 7) P2T(2);
                const uint32_t b_lo = b_lo0 + s * 1024;
                wgmma_fence();
#pragma unroll
                for (int kk = 0; kk < (P2_NOMMA ? 1 : 4); kk++) {
                    wgmma_ss_n128_lo<1>(acc[0], a_lo + p2_apos(k) * 1024 + kk * 2, b_lo + kk * 128, (k | kk) != 0);
                    wgmma_ss_n128_lo<1>(acc[1], a_lo + p2_apos(k) * 1024 + 512 + kk * 2, b_lo + kk * 128, (k | kk) != 0);
                }
                wgmma_commit();
                if (k > 0) {
                    wgmma_wait<1>();
                    if (elected) {
                        const uint32_t e = b_empty + 8 * sprev;
                        mbar_arrive_cl(mapa_u32(e, 0)); mbar_arrive_cl(mapa_u32(e, 1));
                        if (last) mbar_arrive(a_empty + 8 * (k - 1));
                    }
                }
                sprev = s;
                if (++s == P2_STAGES) { s = 0; ph ^= 1; }
            }
            wgmma_wait<0>();
            P2T(3);
            if (elected) {
                const uint32_t e = b_empty + 8 * sprev;
                mbar_arrive_cl(mapa_u32(e, 0)); mbar_arrive_cl(mapa_u32(e, 1));
                if (last) mbar_arrive(a_empty + 8 * 7);
            }
            s += 8 % P2_STAGES; ph ^= (8 / P2_STAGES) & 1;
            if (s >= P2_STAGES) { s -= P2_STAGES; ph ^= 1; }
            const int m0 = (2 * mp + (int)rank) * 128;
            bf16* obase = P.out[z] + ((size_t)head * SEQ + m0 + (warp & 3) * 16 + (lane >> 2)) * HD + (lane & 3) * 8;
            store_frag_128<true, P2_PACE>(acc[0], obase, lane); store_frag_128<true, P2_PACE>(acc[1], obase + (size_t)64 * HD, lane);
            P2T(4);
            {
                asm volatile("bar.sync %0, 128;" :: "r"(1 + wg) : "memory");
                if (elected) {
                    const int e = wg * 4 + (nnote & 3);
                    mbar_wait(note_free + 8 * e, ((nnote >> 2) & 1) ^ 1);
                    asm volatile("st.shared.s32 [%0], %1;" :: "r"(note + e * 4), "r"(CT_AP + (head >> 1)) : "memory");
                    mbar_arrive(note_bar + 8 * e);
                }
                nnote++;
            }
            }
        }
        auto done = [&]() {
            if ((threadIdx.x & 127) == 0) for (int i = 0; i < 4; i++) mbar_arrive_cl(SD + MO_BAR + 768 + OB_EMPTY + 16 + 8 * (i & 1) + ((i >> 1) << 24));
        };
        asm volatile("bar.sync %0, 128;" :: "r"(1 + wg) : "memory");
        if (rank == 0) attn_consumer<SD>(MP.a, warp, done); else attn_consumer<SD + (1u << 24)>(MP.a, warp, done);
        OT(0);
        {
            const uint32_t rank2 = cluster_ctarank(), sb2 = (rank2 << 24) + SD;
            int cid;
            asm volatile("mov.u32 %0, %%clusterid.x;" : "=r"(cid));
            out_map(cid, pt, h0);
            out_consumer(MP.o, sb2, sb2 + MO_BAR + 768, rank2, pt, warp);
        }
    }
}

typedef CUresult (*PFN_encodeTiled)(CUtensorMap*, CUtensorMapDataType, cuuint32_t, void*, const cuuint64_t*,
                                    const cuuint64_t*, const cuuint32_t*, const cuuint32_t*, CUtensorMapInterleave,
                                    CUtensorMapSwizzle, CUtensorMapL2promotion, CUtensorMapFloatOOBfill);
static PFN_encodeTiled g_encode = nullptr;

static void make_map(CUtensorMap* m, const void* ptr, uint64_t rows, uint64_t cols, uint32_t box_rows, bool sw64 = false) {
    cuuint64_t dims[2] = {cols, rows};
    cuuint64_t strides[1] = {cols * 2};
    cuuint32_t box[2] = {sw64 ? 32u : 64u, box_rows};
    cuuint32_t es[2] = {1, 1};
    g_encode(m, CU_TENSOR_MAP_DATA_TYPE_BFLOAT16, 2, const_cast<void*>(ptr), dims, strides, box, es,
             CU_TENSOR_MAP_INTERLEAVE_NONE, sw64 ? CU_TENSOR_MAP_SWIZZLE_64B : CU_TENSOR_MAP_SWIZZLE_128B, CU_TENSOR_MAP_L2_PROMOTION_L2_256B,
             CU_TENSOR_MAP_FLOAT_OOB_FILL_NONE);
}

template <typename... KArgs, typename... Args>
static void launch_pdl(void (*kernel)(KArgs...), int grid, int block, size_t smem, cudaStream_t st, bool pdl, Args... args) {
    cudaLaunchConfig_t cfg = {};
    cfg.gridDim = dim3(grid); cfg.blockDim = dim3(block); cfg.dynamicSmemBytes = smem; cfg.stream = st;
    cudaLaunchAttribute at[1];
    at[0].id = cudaLaunchAttributeProgrammaticStreamSerialization;
    at[0].val.programmaticStreamSerializationAllowed = 1;
    cfg.attrs = at; cfg.numAttrs = pdl ? 1 : 0;
    cudaLaunchKernelEx(&cfg, kernel, KArgs(args)...);
}

extern "C" void kernel_launch(void* const* d_in, const int* in_sizes, int n_in, void* d_out, int out_size) {
    const bf16* x = (const bf16*)d_in[0];
    const bf16* ckv = (const bf16*)d_in[1];
    const bf16* wq = (const bf16*)d_in[2];
    const bf16* wuk = (const bf16*)d_in[3];
    const bf16* wuv = (const bf16*)d_in[4];
    const bf16* wo = (const bf16*)d_in[5];
    const bf16* mem0 = (const bf16*)d_in[7];
    const bf16* Wq = (const bf16*)d_in[8];
    const bf16* Wk = (const bf16*)d_in[9];
    const bf16* Wv = (const bf16*)d_in[10];
    const bf16* Wo = (const bf16*)d_in[11];
    const bf16* gate_w = (const bf16*)d_in[13];
    bf16* out = (bf16*)d_out;

    static MainParams MP;
    static ChainParams CP;
    Proj2Params& P2 = MP.p;
    AttnParams& AP = MP.a;
    OutParams& OP = MP.o;
    static bool init = false;
    static const void* last_in[14];
    static const void* last_out;
    bool same = init && last_out == d_out;
    for (int i = 0; i < 14 && same; i++) same = last_in[i] == d_in[i];
    if (!init) {
        cudaDriverEntryPointQueryResult qr;
        cudaGetDriverEntryPoint("cuTensorMapEncodeTiled", (void**)&g_encode, cudaEnableDefault, &qr);
        cudaFuncSetAttribute(main_kernel, cudaFuncAttributeMaxDynamicSharedMemorySize, M_SMEM);
        cudaFuncSetAttribute(out2_kernel, cudaFuncAttributeMaxDynamicSharedMemorySize, O2_SMEM);
        cudaFuncSetAttribute(chain_kernel, cudaFuncAttributeMaxDynamicSharedMemorySize, CH_SMEM);
        init = true;
    }
    if (!same) {
        for (int i = 0; i < 14; i++) last_in[i] = d_in[i];
        last_out = d_out;
        void *pQA, *pKA, *pVA, *pCA, *pCB;
        cudaGetSymbolAddress(&pQA, g_QA); cudaGetSymbolAddress(&pKA, g_KA); cudaGetSymbolAddress(&pVA, g_VA);
        cudaGetSymbolAddress(&pCA, g_ctxA); cudaGetSymbolAddress(&pCB, g_ctxB);
        make_map(&P2.mapA[0], x, SEQ, DM, 128);
        make_map(&P2.mapA[1], ckv, SEQ, DM, 128);
        const void* ws[3] = {wq, wuk, wuv};
        void* cs[3] = {pQA, pKA, pVA};
        for (int i = 0; i < 3; i++) { make_map(&P2.mapW[i], ws[i], DM, NQ, 64); P2.out[i] = (bf16*)cs[i]; }
        make_map(&CP.mapW[0], Wq, DM, NQ, 64); make_map(&CP.mapW[1], Wk, DM, NQ, 64); make_map(&CP.mapW[2], Wv, DM, NQ, 64);
        make_map(&CP.mapX, x, SEQ, DM, 32);
        make_map(&CP.mapWo, Wo, NQ, DM, 64);
        make_map(&CP.mapM, mem0, NMEM, DM, 8);
        MP.x = x; MP.gate_w = gate_w;
        make_map(&CP.mapC, pCB, NH * SEQ, HD, 32);
        make_map(&AP.mapQ, pQA, NH * SEQ, HD, 128);
        make_map(&AP.mapK, pKA, NH * SEQ, HD, 128);
        make_map(&AP.mapV, pVA, NH * SEQ, HD, 128);
        make_map(&AP.mapO, pCA, NH * SEQ, HD, 64);
        make_map(&OP.mapCtx[0], pCA, NH * SEQ, HD, 128);
        make_map(&OP.mapCtx[1], pCB, NH * SEQ, HD, 128);
        make_map(&OP.mapWo[0], wo, NQ, DM, 64);
        make_map(&OP.mapWo[1], Wo, NQ, DM, 64);
        make_map(&OP.mapOut, out, SEQ, DM, 16);
        AP.out = out;
    }
    cudaStream_t s1 = cudaStreamPerThread;
    const bool pdl = true;
    launch_pdl(chain_kernel, 64, CH_BLOCK, CH_SMEM, s1, false, CP);
    launch_pdl(main_kernel, M_GRID, 384, M_SMEM, s1, pdl, MP);
    launch_pdl(out2_kernel, O2_GRID, 320, O2_SMEM, s1, pdl, OP);
}
```

```cpp
#include <cuda_runtime.h>
#include <cuda_bf16.h>
#include <cuda.h>
#include <stdint.h>
#include <type_traits>

constexpr int SEQ = 2048;
constexpr int DM = 512;
constexpr int NH = 32;
constexpr int HD = 128;
constexpr int NQ = NH * HD;
constexpr int SEGL = 32;
constexpr int NMEM = 8;
constexpr int NSEG = SEQ / SEGL;

typedef __nv_bfloat16 bf16;

__device__ bf16 g_QA[SEQ * NQ];
__device__ bf16 g_KA[SEQ * NQ];
__device__ bf16 g_VA[SEQ * NQ];
__device__ bf16 g_ctxA[SEQ * NQ];
__device__ bf16 g_ctxB[SEQ * NQ];
constexpr int CT_PROJ = 0, CT_ATTN = 1, CT_FIN = 5;
constexpr int CT_AP = 64;
constexpr int CT_GATE = 96;
constexpr int CT_CA = 128;
constexpr int CT_CB = 193;
constexpr int CT_OT = 208;
constexpr int CT_N = 228;
__device__ __align__(16) unsigned int g_ctr[CT_N];
__device__ float g_gate[SEQ];
#define XB8(v) v, v, v, v, v, v, v, v
__device__ uint32_t g_xbuf[4 * 8 * 2048] = {XB8(XB8(XB8(XB8(XB8(~0u)))))};

#define FA_GRID 68

#define TS_BEGIN(id)
#define TS_END(id)
#define TS_BEGIN2(id, th)
#define TS_END2(id, th)
#define WAIT_LIMIT 200000
__device__ __forceinline__ void pdl_launch_dependents() { asm volatile("griddepcontrol.launch_dependents;" ::: "memory"); }
__device__ __forceinline__ void wait_ctr(int idx, unsigned int n) {
    unsigned int v; int it = 0;
    do { asm volatile("ld.acquire.gpu.global.u32 %0, [%1];" : "=r"(v) : "l"(&g_ctr[idx]) : "memory"); } while (v < n && ++it < WAIT_LIMIT);
    asm volatile("fence.proxy.async.shared::cta;" ::: "memory");
}
__device__ __forceinline__ int take_ticket(int idx) {
    int v;
    asm volatile("atom.relaxed.gpu.global.inc.u32 %0, [%1], 0x7fffffff;" : "=r"(v) : "l"(&g_ctr[idx]) : "memory");
    return v;
}
__device__ __forceinline__ void signal_ctr(int idx) {
    asm volatile("fence.proxy.async;" ::: "memory");
    __threadfence();
    atomicAdd(&g_ctr[idx], 1u);
}
__device__ __forceinline__ void signal_ctr_generic(int idx) {
    asm volatile("red.release.gpu.global.add.u32 [%0], 1;" :: "l"(&g_ctr[idx]) : "memory");
}
__device__ __forceinline__ uint32_t smem_u32(const void* p) {
    return (uint32_t)__cvta_generic_to_shared(p);
}
__device__ __forceinline__ void mbar_init(uint32_t bar, uint32_t count) {
    asm volatile("mbarrier.init.shared::cta.b64 [%0], %1;" :: "r"(bar), "r"(count));
}
__device__ __forceinline__ void mbar_expect_tx(uint32_t bar, uint32_t bytes) {
    asm volatile("mbarrier.arrive.expect_tx.shared::cta.b64 _, [%0], %1;" :: "r"(bar), "r"(bytes) : "memory");
}
__device__ __forceinline__ void mbar_arrive(uint32_t bar) {
    asm volatile("mbarrier.arrive.shared::cta.b64 _, [%0];" :: "r"(bar) : "memory");
}
__device__ __forceinline__ void mbar_wait(uint32_t bar, uint32_t parity) {
    asm volatile(
        "{\n"
        ".reg .pred p, q;\n"
        ".reg .u32 c;\n"
        "mov.u32 c, 0;\n"
        "WAIT_LOOP:\n"
        "mbarrier.try_wait.parity.shared::cta.b64 p, [%0], %1;\n"
        "@p bra WAIT_DONE;\n"
        "add.u32 c, c, 1;\n"
        "setp.lt.u32 q, c, %2;\n"
        "@q bra WAIT_LOOP;\n"
        "WAIT_DONE:\n"
        "}\n" :: "r"(bar), "r"(parity), "n"(WAIT_LIMIT) : "memory");
}
__device__ __forceinline__ uint32_t mbar_test(uint32_t bar, uint32_t parity) {
    uint32_t done;
    asm volatile(
        "{\n.reg .pred p;\n"
        "mbarrier.test_wait.parity.shared::cta.b64 p, [%1], %2;\n"
        "selp.u32 %0, 1, 0, p;\n}\n" : "=r"(done) : "r"(bar), "r"(parity) : "memory");
    return done;
}
__device__ __forceinline__ uint32_t mbar_try(uint32_t bar, uint32_t parity) {
    uint32_t done;
    asm volatile(
        "{\n.reg .pred p;\n"
        "mbarrier.try_wait.parity.shared::cta.b64 p, [%1], %2;\n"
        "selp.u32 %0, 1, 0, p;\n}\n" : "=r"(done) : "r"(bar), "r"(parity) : "memory");
    return done;
}
__device__ __forceinline__ void tma_load_2d(uint32_t dst, const CUtensorMap* map, uint32_t bar, int c0, int c1) {
    asm volatile(
        "cp.async.bulk.tensor.2d.shared::cluster.global.mbarrier::complete_tx::bytes [%0], [%1, {%3, %4}], [%2];"
        :: "r"(dst), "l"((uint64_t)map), "r"(bar), "r"(c0), "r"(c1) : "memory");
}
__device__ __forceinline__ void wgmma_fence() { asm volatile("wgmma.fence.sync.aligned;" ::: "memory"); }
__device__ __forceinline__ void wgmma_commit() { asm volatile("wgmma.commit_group.sync.aligned;" ::: "memory"); }
template <int N> __device__ __forceinline__ void wgmma_wait() {
    asm volatile("wgmma.wait_group.sync.aligned %0;" :: "n"(N) : "memory");
}
__device__ __forceinline__ uint64_t make_desc(uint32_t addr, uint32_t lbo, uint32_t sbo) {
    uint64_t d = 0;
    d |= (uint64_t)((addr & 0x3FFFF) >> 4);
    d |= (uint64_t)((lbo >> 4) & 0x3FFF) << 16;
    d |= (uint64_t)((sbo >> 4) & 0x3FFF) << 32;
    d |= (uint64_t)1 << 62;
    return d;
}

#define ACC64(d) \
    "+f"(d[0]), "+f"(d[1]), "+f"(d[2]), "+f"(d[3]), "+f"(d[4]), "+f"(d[5]), "+f"(d[6]), "+f"(d[7]), \
    "+f"(d[8]), "+f"(d[9]), "+f"(d[10]), "+f"(d[11]), "+f"(d[12]), "+f"(d[13]), "+f"(d[14]), "+f"(d[15]), \
    "+f"(d[16]), "+f"(d[17]), "+f"(d[18]), "+f"(d[19]), "+f"(d[20]), "+f"(d[21]), "+f"(d[22]), "+f"(d[23]), \
    "+f"(d[24]), "+f"(d[25]), "+f"(d[26]), "+f"(d[27]), "+f"(d[28]), "+f"(d[29]), "+f"(d[30]), "+f"(d[31]), \
    "+f"(d[32]), "+f"(d[33]), "+f"(d[34]), "+f"(d[35]), "+f"(d[36]), "+f"(d[37]), "+f"(d[38]), "+f"(d[39]), \
    "+f"(d[40]), "+f"(d[41]), "+f"(d[42]), "+f"(d[43]), "+f"(d[44]), "+f"(d[45]), "+f"(d[46]), "+f"(d[47]), \
    "+f"(d[48]), "+f"(d[49]), "+f"(d[50]), "+f"(d[51]), "+f"(d[52]), "+f"(d[53]), "+f"(d[54]), "+f"(d[55]), \
    "+f"(d[56]), "+f"(d[57]), "+f"(d[58]), "+f"(d[59]), "+f"(d[60]), "+f"(d[61]), "+f"(d[62]), "+f"(d[63])
#define ACC64_STR \
    "{%0, %1, %2, %3, %4, %5, %6, %7, %8, %9, %10, %11, %12, %13, %14, %15, " \
    "%16, %17, %18, %19, %20, %21, %22, %23, %24, %25, %26, %27, %28, %29, %30, %31, " \
    "%32, %33, %34, %35, %36, %37, %38, %39, %40, %41, %42, %43, %44, %45, %46, %47, " \
    "%48, %49, %50, %51, %52, %53, %54, %55, %56, %57, %58, %59, %60, %61, %62, %63}"

template <int TB>
__device__ __forceinline__ void wgmma_ss_n128(float (&d)[64], uint64_t da, uint64_t db, int scale_d) {
    asm volatile(
        "{\n.reg .pred p;\nsetp.ne.b32 p, %66, 0;\n"
        "wgmma.mma_async.sync.aligned.m64n128k16.f32.bf16.bf16 " ACC64_STR ", %64, %65, p, 1, 1, 0, %67;\n}\n"
        : ACC64(d) : "l"(da), "l"(db), "r"(scale_d), "n"(TB));
}
__device__ __forceinline__ uint32_t desc_lo(uint32_t addr, uint32_t lbo) { return ((addr & 0x3FFFF) >> 4) | ((lbo >> 4) << 16); }
template <int TB>
__device__ __forceinline__ void wgmma_ss_n128_lo(float (&d)[64], uint32_t da_lo, uint32_t db_lo, int scale_d) {
    asm volatile(
        "{\n.reg .pred p;\n.reg .b64 da, db;\nsetp.ne.b32 p, %66, 0;\n"
        "mov.b64 da, {%64, 0x40000040};\nmov.b64 db, {%65, 0x40000040};\n"
        "wgmma.mma_async.sync.aligned.m64n128k16.f32.bf16.bf16 " ACC64_STR ", da, db, p, 1, 1, 0, %67;\n}\n"
        : ACC64(d) : "r"(da_lo), "r"(db_lo), "r"(scale_d), "n"(TB));
}
__device__ __forceinline__ void wgmma_rs_n128_tb(float (&d)[64], uint32_t a0, uint32_t a1, uint32_t a2, uint32_t a3,
                                                 uint64_t db, int scale_d) {
    asm volatile(
        "{\n.reg .pred p;\nsetp.ne.b32 p, %69, 0;\n"
        "wgmma.mma_async.sync.aligned.m64n128k16.f32.bf16.bf16 " ACC64_STR ", {%64, %65, %66, %67}, %68, p, 1, 1, 1;\n}\n"
        : ACC64(d) : "r"(a0), "r"(a1), "r"(a2), "r"(a3), "l"(db), "r"(scale_d));
}
__device__ __forceinline__ void wgmma_rs_n80(float (&d)[40], const uint32_t (&a)[4], uint32_t db_lo, int scale_d) {
    asm volatile(
        "{\n.reg .pred p;\n.reg .b64 db;\nsetp.ne.b32 p, %45, 0;\nmov.b64 db, {%44, 0x40000040};\n"
        "wgmma.mma_async.sync.aligned.m64n80k16.f32.bf16.bf16 "
        "{%0, %1, %2, %3, %4, %5, %6, %7, %8, %9, %10, %11, %12, %13, %14, %15, %16, %17, %18, %19, %20, %21, %22, %23, %24, %25, %26, %27, %28, %29, %30, %31, %32, %33, %34, %35, %36, %37, %38, %39}, "
        "{%40, %41, %42, %43}, db, p, 1, 1, 0;\n}\n"
        : "+f"(d[0]), "+f"(d[1]), "+f"(d[2]), "+f"(d[3]), "+f"(d[4]), "+f"(d[5]), "+f"(d[6]), "+f"(d[7]), "+f"(d[8]), "+f"(d[9]), "+f"(d[10]), "+f"(d[11]), "+f"(d[12]), "+f"(d[13]), "+f"(d[14]), "+f"(d[15]), "+f"(d[16]), "+f"(d[17]), "+f"(d[18]), "+f"(d[19]), "+f"(d[20]), "+f"(d[21]), "+f"(d[22]), "+f"(d[23]), "+f"(d[24]), "+f"(d[25]), "+f"(d[26]), "+f"(d[27]), "+f"(d[28]), "+f"(d[29]), "+f"(d[30]), "+f"(d[31]), "+f"(d[32]), "+f"(d[33]), "+f"(d[34]), "+f"(d[35]), "+f"(d[36]), "+f"(d[37]), "+f"(d[38]), "+f"(d[39])
        : "r"(a[0]), "r"(a[1]), "r"(a[2]), "r"(a[3]), "r"(db_lo), "r"(scale_d));
}
__device__ __forceinline__ void wgmma_ss_n256_tb(float (&d)[128], uint64_t da, uint64_t db, int scale_d) {
    asm volatile(
        "{\n.reg .pred p;\nsetp.ne.b32 p, %130, 0;\n"
        "wgmma.mma_async.sync.aligned.m64n256k16.f32.bf16.bf16 {%0, %1, %2, %3, %4, %5, %6, %7, %8, %9, %10, %11, %12, %13, %14, %15, %16, %17, %18, %19, %20, %21, %22, %23, %24, %25, %26, %27, %28, %29, %30, %31, %32, %33, %34, %35, %36, %37, %38, %39, %40, %41, %42, %43, %44, %45, %46, %47, %48, %49, %50, %51, %52, %53, %54, %55, %56, %57, %58, %59, %60, %61, %62, %63, %64, %65, %66, %67, %68, %69, %70, %71, %72, %73, %74, %75, %76, %77, %78, %79, %80, %81, %82, %83, %84, %85, %86, %87, %88, %89, %90, %91, %92, %93, %94, %95, %96, %97, %98, %99, %100, %101, %102, %103, %104, %105, %106, %107, %108, %109, %110, %111, %112, %113, %114, %115, %116, %117, %118, %119, %120, %121, %122, %123, %124, %125, %126, %127}, %128, %129, p, 1, 1, 0, 1;\n}\n"
        : "+f"(d[0]), "+f"(d[1]), "+f"(d[2]), "+f"(d[3]), "+f"(d[4]), "+f"(d[5]), "+f"(d[6]), "+f"(d[7]), "+f"(d[8]), "+f"(d[9]), "+f"(d[10]), "+f"(d[11]), "+f"(d[12]), "+f"(d[13]), "+f"(d[14]), "+f"(d[15]), "+f"(d[16]), "+f"(d[17]), "+f"(d[18]), "+f"(d[19]), "+f"(d[20]), "+f"(d[21]), "+f"(d[22]), "+f"(d[23]), "+f"(d[24]), "+f"(d[25]), "+f"(d[26]), "+f"(d[27]), "+f"(d[28]), "+f"(d[29]), "+f"(d[30]), "+f"(d[31]), "+f"(d[32]), "+f"(d[33]), "+f"(d[34]), "+f"(d[35]), "+f"(d[36]), "+f"(d[37]), "+f"(d[38]), "+f"(d[39]), "+f"(d[40]), "+f"(d[41]), "+f"(d[42]), "+f"(d[43]), "+f"(d[44]), "+f"(d[45]), "+f"(d[46]), "+f"(d[47]), "+f"(d[48]), "+f"(d[49]), "+f"(d[50]), "+f"(d[51]), "+f"(d[52]), "+f"(d[53]), "+f"(d[54]), "+f"(d[55]), "+f"(d[56]), "+f"(d[57]), "+f"(d[58]), "+f"(d[59]), "+f"(d[60]), "+f"(d[61]), "+f"(d[62]), "+f"(d[63]), "+f"(d[64]), "+f"(d[65]), "+f"(d[66]), "+f"(d[67]), "+f"(d[68]), "+f"(d[69]), "+f"(d[70]), "+f"(d[71]), "+f"(d[72]), "+f"(d[73]), "+f"(d[74]), "+f"(d[75]), "+f"(d[76]), "+f"(d[77]), "+f"(d[78]), "+f"(d[79]), "+f"(d[80]), "+f"(d[81]), "+f"(d[82]), "+f"(d[83]), "+f"(d[84]), "+f"(d[85]), "+f"(d[86]), "+f"(d[87]), "+f"(d[88]), "+f"(d[89]), "+f"(d[90]), "+f"(d[91]), "+f"(d[92]), "+f"(d[93]), "+f"(d[94]), "+f"(d[95]), "+f"(d[96]), "+f"(d[97]), "+f"(d[98]), "+f"(d[99]), "+f"(d[100]), "+f"(d[101]), "+f"(d[102]), "+f"(d[103]), "+f"(d[104]), "+f"(d[105]), "+f"(d[106]), "+f"(d[107]), "+f"(d[108]), "+f"(d[109]), "+f"(d[110]), "+f"(d[111]), "+f"(d[112]), "+f"(d[113]), "+f"(d[114]), "+f"(d[115]), "+f"(d[116]), "+f"(d[117]), "+f"(d[118]), "+f"(d[119]), "+f"(d[120]), "+f"(d[121]), "+f"(d[122]), "+f"(d[123]), "+f"(d[124]), "+f"(d[125]), "+f"(d[126]), "+f"(d[127])
        : "l"(da), "l"(db), "r"(scale_d));
}
__device__ __forceinline__ void stmatrix_x4(uint32_t addr, uint32_t r0, uint32_t r1, uint32_t r2, uint32_t r3) {
    asm volatile("stmatrix.sync.aligned.m8n8.x4.shared.b16 [%0], {%1, %2, %3, %4};" :: "r"(addr), "r"(r0), "r"(r1), "r"(r2), "r"(r3) : "memory");
}
__device__ __forceinline__ void tma_store_2d(const CUtensorMap* map, uint32_t src, int c0, int c1) {
    asm volatile("cp.async.bulk.tensor.2d.global.shared::cta.bulk_group [%0, {%2, %3}], [%1];"
                 :: "l"((uint64_t)map), "r"(src), "r"(c0), "r"(c1) : "memory");
}
__device__ __forceinline__ float ex2f(float x) { float y; asm("ex2.approx.ftz.f32 %0, %1;" : "=f"(y) : "f"(x)); return y; }
__device__ __forceinline__ uint32_t pack_bf16(float lo, float hi) {
    __nv_bfloat162 v = __floats2bfloat162_rn(lo, hi);
    return *reinterpret_cast<uint32_t*>(&v);
}
__device__ __forceinline__ void mma_16816(float (&c)[4], uint32_t a0, uint32_t a1, uint32_t a2, uint32_t a3,
                                          uint32_t b0, uint32_t b1) {
    asm volatile(
        "mma.sync.aligned.m16n8k16.row.col.f32.bf16.bf16.f32 {%0,%1,%2,%3}, {%4,%5,%6,%7}, {%8,%9}, {%0,%1,%2,%3};"
        : "+f"(c[0]), "+f"(c[1]), "+f"(c[2]), "+f"(c[3])
        : "r"(a0), "r"(a1), "r"(a2), "r"(a3), "r"(b0), "r"(b1));
}
__device__ __forceinline__ void ldmatrix_x4_trans(uint32_t& r0, uint32_t& r1, uint32_t& r2, uint32_t& r3, uint32_t addr) {
    asm volatile("ldmatrix.sync.aligned.m8n8.x4.trans.shared.b16 {%0,%1,%2,%3}, [%4];"
                 : "=r"(r0), "=r"(r1), "=r"(r2), "=r"(r3) : "r"(addr));
}

struct AttnParams {
    CUtensorMap mapQ, mapK, mapV;
    CUtensorMap mapO;
    bf16* out;
};
constexpr int FA_ITEMS = 16 * NH;
__device__ __forceinline__ int fa_qt(int t) { return 15 - ((t & 127) >> 3); }
__device__ __forceinline__ int fa_head(int t) { return (t >> 7) * 8 + (t & 7); }
#define FA_TKA 2
#define FA_SPLIT 11

#define FA_P0 4
#define FA_HO 7
#define FA_LAG 2
#define FA_PK 3
#define FA_ST 4
#define FA_TG 16
#define FA_EARLY 0
#define FA_I0 0
static_assert(FA_GRID <= 104 && FA_HO >= FA_P0 && FA_P0 >= 1, "");
constexpr float FA_MARGIN = 16.f;
#define FAT(b, i)
__device__ __forceinline__ void mbar_arrive_if(uint32_t bar, bool c) {
    asm volatile("{\n.reg .pred p;\nsetp.ne.b32 p, %1, 0;\n@p mbarrier.arrive.shared::cta.b64 _, [%0];\n}" :: "r"(bar), "r"((int)c) : "memory");
}
__device__ __forceinline__ void sched_fence(int v, int id, const float* a, const float* b, const float* c) {
    asm volatile("{\n.reg .pred p;\nsetp.ne.s32 p, %0, %1;\n@p bra SF_SKIP;\nwgmma.wait_group.sync.aligned 0;\n"
                 "st.volatile.shared.f32 [%0], %2;\nst.volatile.shared.f32 [%0], %3;\nst.volatile.shared.f32 [%0], %4;\nst.volatile.shared.f32 [%0], %5;\n"
                 "st.volatile.shared.f32 [%0], %6;\nst.volatile.shared.f32 [%0], %7;\nst.volatile.shared.f32 [%0], %8;\nst.volatile.shared.f32 [%0], %9;\n"
                 "st.volatile.shared.f32 [%0], %10;\nst.volatile.shared.f32 [%0], %11;\nst.volatile.shared.f32 [%0], %12;\nst.volatile.shared.f32 [%0], %13;\n"
                 "exit;\nSF_SKIP:\n}" :: "r"(v), "r"(1000000 + id), "f"(a[0]), "f"(a[1]), "f"(a[2]), "f"(a[3]), "f"(b[0]), "f"(b[1]), "f"(b[2]), "f"(b[3]),
                 "f"(c[0]), "f"(c[1]), "f"(c[2]), "f"(c[3]) : "memory");
}
__device__ __forceinline__ float ex2v(float x) { float y; asm volatile("ex2.approx.ftz.f32 %0, %1;" : "=f"(y) : "f"(x)); return y; }
__device__ __forceinline__ void wgmma_rs_n128_tb_lo(float (&d)[64], const uint32_t* a, uint32_t db_lo, int scale_d) {
    asm volatile(
        "{\n.reg .pred p;\n.reg .b64 db;\nsetp.ne.b32 p, %69, 0;\nmov.b64 db, {%68, 0x40000040};\n"
        "wgmma.mma_async.sync.aligned.m64n128k16.f32.bf16.bf16 " ACC64_STR ", {%64, %65, %66, %67}, db, p, 1, 1, 1;\n}\n"
        : ACC64(d) : "r"(a[0]), "r"(a[1]), "r"(a[2]), "r"(a[3]), "r"(db_lo), "r"(scale_d));
}

constexpr int M_GRID = 68;
constexpr uint32_t SD = 1024;
constexpr uint32_t MO_BAR = 229376;
constexpr int M_SMEM = MO_BAR + 1024;
constexpr uint32_t FO_Q = 0, FO_KV = 65536, FO_O = FO_KV + 2 * 65536, FO_BAR = MO_BAR + 512;
constexpr uint32_t FB_QF = FO_BAR, FB_QE = FO_BAR + 16, FB_KF = FO_BAR + 32, FB_VF = FO_BAR + 48, FB_KE = FO_BAR + 64, FB_VE = FO_BAR + 80,
                   FB_OF = FO_BAR + 96, FB_OE = FO_BAR + 112, FB_SLOT = FO_BAR + 128, FB_OSLOT = FO_BAR + 136;
__device__ __forceinline__ void attn_init(uint32_t sb) {
    for (int i = 0; i < 2; i++) {
        mbar_init(sb + FB_QF + 8 * i, 1); mbar_init(sb + FB_QE + 8 * i, 8); mbar_init(sb + FB_KF + 8 * i, 1); mbar_init(sb + FB_VF + 8 * i, 1);
        mbar_init(sb + FB_KE + 8 * i, 8); mbar_init(sb + FB_VE + 8 * i, 8); mbar_init(sb + FB_OF + 8 * i, 4); mbar_init(sb + FB_OE + 8 * i, 1);
    }
}
__device__ __forceinline__ void attn_helper(const AttnParams& P, uint32_t sb, int wg) {
    const uint32_t stg = sb + FO_O + wg * 16384;
    for (int n = 0;; n++) {
        mbar_wait(sb + FB_OF + 8 * wg, n & 1);
        int t;
        asm volatile("ld.shared.s32 %0, [%1];" : "=r"(t) : "r"(sb + FB_OSLOT + wg * 4) : "memory");
        const int qt = fa_qt(t), h = fa_head(t & 1023);
        tma_store_2d(&P.mapO, stg, 0, h * SEQ + qt * 128 + wg * 64);
        tma_store_2d(&P.mapO, stg + 8192, 64, h * SEQ + qt * 128 + wg * 64);
        asm volatile("cp.async.bulk.commit_group;" ::: "memory");
        asm volatile("cp.async.bulk.wait_group.read 0;" ::: "memory");
        mbar_arrive(sb + FB_OE + 8 * wg);
        asm volatile("cp.async.bulk.wait_group 0;" ::: "memory");
        signal_ctr(CT_CA + qt * 4 + (h >> 3));
        if (t >= 1024) break;
    }
}
__device__ __forceinline__ void attn_producer(const AttnParams& P, uint32_t sb, uint32_t free_bar, uint32_t free_par) {
    const uint32_t sQ = sb + FO_Q, sKV = sb + FO_KV;
    int b = 0, hp_ready = 0, vrow = 0, t = blockIdx.x, item = 0;
    auto load_v = [&](int i) {
        const uint32_t sv = sKV + (i & 1) * 65536 + 32768, bar = sb + FB_VF + 8 * (i & 1);
        mbar_wait(sb + FB_VE + 8 * (i & 1), ((i >> 1) & 1) ^ 1);
        mbar_expect_tx(bar, 32768);
        tma_load_2d(sv, &P.mapV, bar, 0, vrow);
        tma_load_2d(sv + 16384, &P.mapV, bar, 64, vrow);
    };
    for (;; item++) {
        const bool valid = t < FA_ITEMS;
        const int qt = fa_qt(t), h = fa_head(t);
        if (valid && !((hp_ready >> (h >> 1)) & 1)) { wait_ctr(CT_AP + (h >> 1), 96u); hp_ready |= 1 << (h >> 1); }
        const uint32_t bq = sb + FB_QF + 8 * (item & 1);
        mbar_wait(item ? sb + FB_QE + 8 * (item & 1) : free_bar + 8, item ? ((item >> 1) & 1) ^ 1 : free_par);
        asm volatile("st.shared.s32 [%0], %1;" :: "r"(sb + FB_SLOT + (item & 1) * 4), "r"(valid ? t : -1) : "memory");
        if (!valid) { mbar_arrive(bq); break; }
        mbar_expect_tx(bq, 32768);
        tma_load_2d(sQ + (item & 1) * 32768, &P.mapQ, bq, 0, h * SEQ + qt * 128);
        tma_load_2d(sQ + (item & 1) * 32768 + 16384, &P.mapQ, bq, 64, h * SEQ + qt * 128);
#pragma unroll 1
        for (int j = 0; j <= qt; j++, b++) {
            const uint32_t sk = sKV + (b & 1) * 65536, bar = sb + FB_KF + 8 * (b & 1);
            mbar_wait(b >= 2 ? sb + FB_KE + 8 * (b & 1) : free_bar + 24 + 32 * b, b >= 2 ? ((b >> 1) & 1) ^ 1 : free_par);
            if (b == 1) { TS_END2(0, 256); TS_BEGIN2(1, 256); }
            if (b == 2) wait_ctr(CT_GATE, 256u);
            mbar_expect_tx(bar, 32768);
            tma_load_2d(sk, &P.mapK, bar, 0, h * SEQ + j * 128);
            tma_load_2d(sk + 16384, &P.mapK, bar, 64, h * SEQ + j * 128);
            if (j == max(qt - FA_TKA, 0)) t = take_ticket(CT_ATTN);
            if (b > 0) load_v(b - 1);
            vrow = h * SEQ + j * 128;
        }
        t += M_GRID;
    }
    load_v(b - 1);
    mbar_wait(sb + FB_KE + 8 * (~b & 1), ((b - 1) >> 1) & 1);
}
template <uint32_t sb, typename F>
__device__ __forceinline__ int attn_consumer(const AttnParams& P, int warp, F done) {
    constexpr uint32_t sQ = SD + FO_Q, sKV = SD + FO_KV;
    constexpr uint32_t sO = sb + FO_O;
    constexpr uint32_t bar_qf = sb + FB_QF, bar_qe = sb + FB_QE, bar_kf = sb + FB_KF, bar_vf = sb + FB_VF, bar_ke = sb + FB_KE, bar_ve = sb + FB_VE,
                   bar_of = sb + FB_OF, bar_oe = sb + FB_OE, slot = sb + FB_SLOT, oslot = sb + FB_OSLOT;
    {
        const int wg = warp >> 2;
        const int lane = threadIdx.x & 31;
        const float sc = 0.08838834764831845f * 1.4426950408889634f;
        const int r0 = wg * 64 + (warp & 3) * 16 + (lane >> 2);
        float o[64], s[64];
        uint32_t pa[32];
        float m0 = 0.f, m1 = 0.f, l0 = 0.f, l1 = 0.f, i0 = 0.f, i1 = 0.f, g0 = 0.f, g1 = 0.f;
        const uint32_t q_lo = desc_lo(sQ + wg * 8192, 16), k_lo = desc_lo(sKV, 16), v_lo = desc_lo(sKV + 32768, 16384);
        auto issue_qk = [&](int b, int item) {
            const uint32_t qd = q_lo + (item & 1) * 2048, kd = k_lo + (b & 1) * 4096;
            wgmma_fence();
#pragma unroll
            for (int kk = 0; kk < 8; kk++) wgmma_ss_n128_lo<0>(s, qd + (kk >> 2) * 1024 + (kk & 3) * 2, kd + (kk >> 2) * 1024 + (kk & 3) * 2, kk != 0);
            wgmma_commit();
        };
        auto issue_pv = [&](int b, bool acc, int n) {
            const uint32_t vd = v_lo + (b & 1) * 4096;
            mbar_wait(bar_vf + 8 * (b & 1), (b >> 1) & 1);
            wgmma_fence();
#pragma unroll
            for (int kk = 0; kk < 8; kk++) if (kk < n) wgmma_rs_n128_tb_lo(o, &pa[kk * 4], vd + kk * 128, kk ? 1 : (int)acc);
            wgmma_commit();
        };
        const int lim = r0 - (lane & 3) * 2;
        int item = -1, tnext = 0;
        uint32_t k_ready = 0, q_ready = 0;
        auto mask = [&](int i) { if ((i >> 2) * 8 + (i & 1) - ((i & 2) ? 8 : 0) > lim) s[i] = -INFINITY; };
        auto exps = [&](auto mode, int b, bool hand_over, float& u0, float& u1) {
            constexpr int MODE = decltype(mode)::value;
            float p[64], u[4] = {0.f, 0.f, 0.f, 0.f};
            const uint32_t vd = v_lo + ((b - 1) & 1) * 4096;
#pragma unroll
            for (int i = 0; i < 4; i++) p[i] = fmaf(s[i], sc, (i & 2) ? -m1 : -m0);
#pragma unroll
            for (int g = 0; g < 16 + FA_LAG; g++) {
                if (MODE && g >= FA_I0 && g - FA_I0 < 8 - FA_P0) {
                    const int kk = FA_P0 + g - FA_I0;
                    wgmma_fence();
                    wgmma_rs_n128_tb_lo(o, &pa[kk * 4], vd + kk * 128, 1);
                    wgmma_commit();
                    if (kk == FA_HO) asm volatile("{\n.reg .pred p;\nsetp.ne.b32 p, %1, 0;\n@p bar.arrive %0, 256;\n}" :: "r"(4 - wg), "r"((int)hand_over) : "memory");
                }
                if (MODE && g == FA_SPLIT) {
                    FAT(b, 2);
                    wgmma_wait<0>();
                    FAT(b - 1, 3);
                    mbar_arrive_if(bar_ve + 8 * ((b - 1) & 1), lane == 0);
                }
                if (MODE && g == FA_TG) {
                    k_ready = mbar_test(bar_kf + 8 * (~b & 1), ((b + 1) >> 1) & 1);
                    if (MODE == 2) {
                        q_ready = mbar_test(bar_qf + 8 * (~item & 1), ((item + 1) >> 1) & 1);
                        asm volatile("ld.shared.s32 %0, [%1];" : "=r"(tnext) : "r"(slot + (~item & 1) * 4) : "memory");
                    }
                }
#pragma unroll
                for (int j = 0; j < 4; j++) {
                    const int i = g * 4 + j;
                    if (g < 16) p[i] = ex2v(p[i]);
                    if (g < 15) {
                        if (MODE == 2) mask(i + 4);
                        p[i + 4] = fmaf(s[i + 4], sc, (i & 2) ? -m1 : -m0);
                    }
                    if (g >= FA_LAG) u[j] += p[i - FA_LAG * 4];
                }
#pragma unroll
                for (int gg = 0; gg < 16; gg++) {
                    const int at = MODE && gg + FA_LAG < FA_SPLIT + gg / FA_PK ? FA_SPLIT + gg / FA_PK : gg + FA_LAG;
                    if (at == g) { pa[gg * 2] = pack_bf16(p[gg * 4], p[gg * 4 + 1]); pa[gg * 2 + 1] = pack_bf16(p[gg * 4 + 2], p[gg * 4 + 3]); }
                }
                if (MODE && g < 16) sched_fence(b, g + MODE * 32, &p[g * 4], &p[(g < 15 ? g + 1 : g) * 4], u);
            }
            u0 = u[0] + u[1]; u1 = u[2] + u[3];
        };
        auto quad_max = [&](float& x0, float& x1) {
            x0 = fmaxf(x0, __shfl_xor_sync(0xffffffff, x0, 1)); x1 = fmaxf(x1, __shfl_xor_sync(0xffffffff, x1, 1));
            x0 = fmaxf(x0, __shfl_xor_sync(0xffffffff, x0, 2)); x1 = fmaxf(x1, __shfl_xor_sync(0xffffffff, x1, 2));
            x0 = fmaf(x0, sc, FA_MARGIN); x1 = fmaf(x1, sc, FA_MARGIN);
        };
        auto softmax_exact = [&](bool fresh, int b) {
            wgmma_wait<0>();
            float x[8];
#pragma unroll
            for (int i = 0; i < 8; i++) x[i] = fmaxf(s[i * 2], s[i * 2 + 1]);
#pragma unroll
            for (int i = 8; i < 32; i++) x[i & 7] = fmaxf(x[i & 7], fmaxf(s[i * 2], s[i * 2 + 1]));
            float x0 = fmaxf(fmaxf(x[0], x[2]), fmaxf(x[4], x[6])), x1 = fmaxf(fmaxf(x[1], x[3]), fmaxf(x[5], x[7]));
            quad_max(x0, x1);
            if (!fresh) {
                x0 = fmaxf(x0, m0); x1 = fmaxf(x1, m1);
                const float a0 = ex2f(m0 - x0), a1 = ex2f(m1 - x1);
                l0 *= a0; l1 *= a1;
#pragma unroll
                for (int i = 0; i < 16; i++) { o[i * 4 + 0] *= a0; o[i * 4 + 1] *= a0; o[i * 4 + 2] *= a1; o[i * 4 + 3] *= a1; }
            }
            m0 = x0; m1 = x1;
            float u0, u1;
            exps(std::integral_constant<int, 0>(), b, false, u0, u1);
            l0 += u0; l1 += u1;
        };
        auto finish_rows = [&]() {
            l0 += __shfl_xor_sync(0xffffffff, l0, 1); l1 += __shfl_xor_sync(0xffffffff, l1, 1);
            l0 += __shfl_xor_sync(0xffffffff, l0, 2); l1 += __shfl_xor_sync(0xffffffff, l1, 2);
            i0 = __fdividef(g0, l0); i1 = __fdividef(g1, l1);
        };
        auto clear_out = [&](int t) {
            if (t >= 384) {
                bf16* z = P.out + (size_t)(fa_qt(t) * 128 + wg * 64 + ((threadIdx.x & 127) >> 3)) * DM + (t & 7) * 64 + (lane & 7) * 8;
#pragma unroll
                for (int i = 0; i < 4; i++) *reinterpret_cast<uint4*>(z + i * 16 * DM) = make_uint4(0u, 0u, 0u, 0u);
            }
        };
        auto store_o = [&](int t, int n, int c0, int c1) {
            const uint32_t stg = sO + wg * 16384;
            if (c0 == 0) {
                mbar_wait(bar_oe + 8 * wg, (n & 1) ^ 1);
                asm volatile("st.shared.s32 [%0], %1;" :: "r"(oslot + wg * 4), "r"(t) : "memory");
            }
            const int row = (warp & 3) * 16 + (lane >> 2);
#pragma unroll
            for (int i = c0; i < c1; i++) {
                const int ch = i * 4 + (lane & 3);
                const uint32_t a = stg + (ch >> 3) * 8192 + row * 128 + (((ch & 7) ^ (row & 7)) << 4);
                const float* q = &o[i * 16];
                asm volatile("st.shared.v4.b32 [%0], {%1, %2, %3, %4};" :: "r"(a), "r"(pack_bf16(q[0] * i0, q[1] * i0)), "r"(pack_bf16(q[4] * i0, q[5] * i0)),
                             "r"(pack_bf16(q[8] * i0, q[9] * i0)), "r"(pack_bf16(q[12] * i0, q[13] * i0)) : "memory");
                asm volatile("st.shared.v4.b32 [%0], {%1, %2, %3, %4};" :: "r"(a + 1024), "r"(pack_bf16(q[2] * i1, q[3] * i1)), "r"(pack_bf16(q[6] * i1, q[7] * i1)),
                             "r"(pack_bf16(q[10] * i1, q[11] * i1)), "r"(pack_bf16(q[14] * i1, q[15] * i1)) : "memory");
            }
        };
        auto publish_o = [&]() {
            asm volatile("fence.proxy.async.shared::cta;" ::: "memory");
            __syncwarp();
            mbar_arrive_if(bar_of + 8 * wg, lane == 0);
        };
        int t = 0, left = 0, tdone = -1, b = 0, nout = 0;
        bool first = true, staged = false;
#pragma unroll 1
        for (;; b++) {
            const bool fresh = left == 0;
            const int tprev = t;
            FAT(b, 4);
            if (staged) { publish_o(); staged = false; }
            if (fresh) {
                item++;
                if (!q_ready) {
                    mbar_wait(bar_qf + 8 * (item & 1), (item >> 1) & 1);
                    asm volatile("ld.shared.s32 %0, [%1];" : "=r"(tnext) : "r"(slot + (item & 1) * 4) : "memory");
                }
                if (tnext < 0) break;
                t = tnext;
                left = fa_qt(t) + 1;
            }
            left--;
            if (tdone >= 0) store_o(tdone, nout, 0, FA_ST);
            FAT(b, 5);
            if (!k_ready) mbar_wait(bar_kf + 8 * (b & 1), (b >> 1) & 1);
            FAT(b, 6);
            asm volatile("bar.sync %0, 256;" :: "r"(3 + wg) : "memory");
            FAT(b, 0);
            issue_qk(b, item);
            bool early = false;
            if (!fresh && !first && left != 0) {
                issue_pv(b - 1, true, FA_P0);
                wgmma_wait<1>();
                FAT(b, 1);
                mbar_arrive_if(bar_ke + 8 * (b & 1), lane == 0);
            } else {
                early = (FA_EARLY && tdone >= 0) || b == 0;
                if (early) asm volatile("bar.arrive %0, 256;" :: "r"(4 - wg) : "memory");
                if (tdone >= 0) { wgmma_wait<1>(); store_o(tdone, nout++, FA_ST, 4); staged = true; }
                tdone = -1;
                if (fresh && b > 0) { finish_rows(); tdone = tprev; l0 = l1 = 0.f; }
                if (left == 0) { g0 = __ldcg(g_gate + fa_qt(t) * 128 + r0); g1 = __ldcg(g_gate + fa_qt(t) * 128 + r0 + 8); clear_out(t); }
                if (b > 0) issue_pv(b - 1, !first, FA_P0); else { wgmma_fence(); wgmma_commit(); }
                first = fresh;
                wgmma_wait<1>();
                FAT(b, 1);
                mbar_arrive_if(bar_ke + 8 * (b & 1), lane == 0);
                mbar_arrive_if(bar_qe + 8 * (item & 1), lane == 0 && left == 0);
                if (left == 0) { mask(0); mask(1); }
                if (fresh) { m0 = fmaxf(s[0], s[1]); m1 = fmaxf(s[2], s[3]); quad_max(m0, m1); }
            }
            if (b > 0) {
                float u0, u1;
                if (left == 0) exps(std::integral_constant<int, 2>(), b, !early, u0, u1);
                else exps(std::integral_constant<int, 1>(), b, !early, u0, u1);
                if (!__any_sync(0xffffffff, !(u0 + u1 < 1.f))) { l0 += u0; l1 += u1; continue; }
            }
            softmax_exact(fresh, b);
        }
        if (tdone >= 0) { store_o(tdone, nout++, 0, 4); publish_o(); }
        issue_pv(b - 1, !first, 8);
        finish_rows();
        wgmma_wait<0>();
        done();
        store_o(t + 1024, nout, 0, 4);
        publish_o();
        return nout;
    }
}

__device__ __forceinline__ uint32_t cluster_ctarank() {
    uint32_t r; asm volatile("mov.u32 %0, %%cluster_ctarank;" : "=r"(r)); return r;
}
__device__ __forceinline__ uint32_t mapa_u32(uint32_t addr, uint32_t rank) {
    uint32_t r; asm volatile("mapa.shared::cluster.u32 %0, %1, %2;" : "=r"(r) : "r"(addr), "r"(rank)); return r;
}
__device__ __forceinline__ void cluster_sync_all() {
    asm volatile("barrier.cluster.arrive.release.aligned;\nbarrier.cluster.wait.acquire.aligned;" ::: "memory");
}
__device__ __forceinline__ void st_async_v4(uint32_t addr, uint32_t a, uint32_t b, uint32_t c, uint32_t d, uint32_t mbar) {
    asm volatile("st.async.weak.shared::cluster.mbarrier::complete_tx::bytes.v4.b32 [%0], {%1, %2, %3, %4}, [%5];"
                 :: "r"(addr), "r"(a), "r"(b), "r"(c), "r"(d), "r"(mbar) : "memory");
}
__device__ __forceinline__ void st_async_v2(uint32_t addr, uint32_t a, uint32_t b, uint32_t mbar) {
    asm volatile("st.async.weak.shared::cluster.mbarrier::complete_tx::bytes.v2.b32 [%0], {%1, %2}, [%3];"
                 :: "r"(addr), "r"(a), "r"(b), "r"(mbar) : "memory");
}
__device__ __forceinline__ void st_async_b32(uint32_t addr, uint32_t a, uint32_t mbar) {
    asm volatile("st.async.weak.shared::cluster.mbarrier::complete_tx::bytes.b32 [%0], %1, [%2];" :: "r"(addr), "r"(a), "r"(mbar) : "memory");
}
__device__ __forceinline__ void pace(int cycles) {
    if (cycles > 0) {
        uint32_t t0, t;
        asm volatile("mov.u32 %0, %%clock;" : "=r"(t0));
        do { asm volatile("mov.u32 %0, %%clock;" : "=r"(t)); } while (t - t0 < (uint32_t)cycles);
    }
}
__device__ __forceinline__ void mbar_wait_cl(uint32_t bar, uint32_t parity) {
    uint32_t done = 0;
    for (int it = 0; it < WAIT_LIMIT && !done; it++) {
        asm volatile(
            "{\n.reg .pred p;\n"
            "mbarrier.try_wait.parity.shared::cta.b64 p, [%1], %2;\n"
            "selp.u32 %0, 1, 0, p;\n}\n" : "=r"(done) : "r"(bar), "r"(parity) : "memory");
    }
}
__device__ __forceinline__ void ldmatrix_x4(uint32_t& r0, uint32_t& r1, uint32_t& r2, uint32_t& r3, uint32_t addr) {
    asm volatile("ldmatrix.sync.aligned.m8n8.x4.shared.b16 {%0,%1,%2,%3}, [%4];"
                 : "=r"(r0), "=r"(r1), "=r"(r2), "=r"(r3) : "r"(addr));
}
__device__ __forceinline__ void cp_async16(uint32_t dst, const void* src) {
    asm volatile("cp.async.cg.shared.global [%0], [%1], 16;" :: "r"(dst), "l"(src) : "memory");
}
__device__ __forceinline__ float bf16r(float x) { return __uint_as_float(pack_bf16(0.f, x) & 0xffff0000u); }

#define DBGP(i, w, ok)
#define DBG(i, w)
#define DBGD(i, w, dep)
#define DBG_EXTRA 0
__device__ __forceinline__ void tma_load_2d_mc(uint32_t dst, const CUtensorMap* map, uint32_t bar, int c0, int c1, uint16_t mask) {
    asm volatile(
        "cp.async.bulk.tensor.2d.shared::cluster.global.mbarrier::complete_tx::bytes.multicast::cluster [%0], [%1, {%3, %4}], [%2], %5;"
        :: "r"(dst), "l"((uint64_t)map), "r"(bar), "r"(c0), "r"(c1), "h"(mask) : "memory");
}
__device__ __forceinline__ void stmatrix_x4_trans(uint32_t addr, uint32_t r0, uint32_t r1, uint32_t r2, uint32_t r3) {
    asm volatile("stmatrix.sync.aligned.m8n8.x4.trans.shared.b16 [%0], {%1, %2, %3, %4};" :: "r"(addr), "r"(r0), "r"(r1), "r"(r2), "r"(r3) : "memory");
}
__device__ __forceinline__ void stmatrix_x2_trans(uint32_t addr, uint32_t r0, uint32_t r1) {
    asm volatile("stmatrix.sync.aligned.m8n8.x2.trans.shared.b16 [%0], {%1, %2};" :: "r"(addr), "r"(r0), "r"(r1) : "memory");
}
__device__ __forceinline__ uint4 lds128(uint32_t a) {
    uint4 v; asm volatile("ld.shared.v4.u32 {%0, %1, %2, %3}, [%4];" : "=r"(v.x), "=r"(v.y), "=r"(v.z), "=r"(v.w) : "r"(a) : "memory"); return v;
}
__device__ __forceinline__ void sts128(uint32_t a, uint32_t x, uint32_t y, uint32_t z, uint32_t w) {
    asm volatile("st.shared.v4.b32 [%0], {%1, %2, %3, %4};" :: "r"(a), "r"(x), "r"(y), "r"(z), "r"(w) : "memory");
}
__device__ __forceinline__ float2 lds64f(uint32_t a) {
    float2 v; asm volatile("ld.shared.v2.f32 {%0, %1}, [%2];" : "=f"(v.x), "=f"(v.y) : "r"(a) : "memory"); return v;
}
__device__ __forceinline__ void fence_async_smem() { asm volatile("fence.proxy.async.shared::cta;" ::: "memory"); }
#define ACC16(d) "+f"(d[0]), "+f"(d[1]), "+f"(d[2]), "+f"(d[3]), "+f"(d[4]), "+f"(d[5]), "+f"(d[6]), "+f"(d[7]), "+f"(d[8]), "+f"(d[9]), "+f"(d[10]), "+f"(d[11]), "+f"(d[12]), "+f"(d[13]), "+f"(d[14]), "+f"(d[15])
template <int ND>
__device__ __forceinline__ void wgmma_rs_n32(float (&d)[ND], const uint32_t (&a)[4], uint32_t db_lo, int scale_d) {
    asm volatile(
        "{\n.reg .pred p;\n.reg .b64 db;\nsetp.ne.b32 p, %21, 0;\nmov.b64 db, {%20, 0x40000040};\n"
        "wgmma.mma_async.sync.aligned.m64n32k16.f32.bf16.bf16 {%0,%1,%2,%3,%4,%5,%6,%7,%8,%9,%10,%11,%12,%13,%14,%15}, {%16,%17,%18,%19}, db, p, 1, 1, 0;\n}\n"
        : ACC16(d) : "r"(a[0]), "r"(a[1]), "r"(a[2]), "r"(a[3]), "r"(db_lo), "r"(scale_d));
}
template <int ND>
__device__ __forceinline__ void wgmma_ss_n32(float (&d)[ND], uint32_t da_lo, uint32_t db_lo, int scale_d) {
    asm volatile(
        "{\n.reg .pred p;\n.reg .b64 da, db;\nsetp.ne.b32 p, %18, 0;\nmov.b64 da, {%16, 0x40000040};\nmov.b64 db, {%17, 0x40000040};\n"
        "wgmma.mma_async.sync.aligned.m64n32k16.f32.bf16.bf16 {%0,%1,%2,%3,%4,%5,%6,%7,%8,%9,%10,%11,%12,%13,%14,%15}, da, db, p, 1, 1, 1, 0;\n}\n"
        : ACC16(d) : "r"(da_lo), "r"(db_lo), "r"(scale_d));
}
__device__ __forceinline__ void wgmma_ss_n8(float (&d)[4], uint32_t da_lo, uint32_t db_lo, int scale_d) {
    asm volatile(
        "{\n.reg .pred p;\n.reg .b64 da, db;\nsetp.ne.b32 p, %6, 0;\nmov.b64 da, {%4, 0x40000040};\nmov.b64 db, {%5, 0x00000010};\n"
        "wgmma.mma_async.sync.aligned.m64n8k16.f32.bf16.bf16 {%0,%1,%2,%3}, da, db, p, 1, 1, 1, 0;\n}\n"
        : "+f"(d[0]), "+f"(d[1]), "+f"(d[2]), "+f"(d[3]) : "r"(da_lo), "r"(db_lo), "r"(scale_d));
}

#define SCHED_FENCE()
__device__ __forceinline__ void wgmma_ss_n32_p(float (&d)[16], uint32_t da_lo, uint32_t db_lo, int scale_d) {
    asm volatile(
        "{\n.reg .pred p;\n.reg .b64 da, db;\nsetp.ne.b32 p, %18, 0;\nmov.b64 da, {%16, 0x40000040};\nmov.b64 db, {%17, 0x00000030};\n"
        "wgmma.mma_async.sync.aligned.m64n32k16.f32.bf16.bf16 {%0,%1,%2,%3,%4,%5,%6,%7,%8,%9,%10,%11,%12,%13,%14,%15}, da, db, p, 1, 1, 1, 0;\n}\n"
        : ACC16(d) : "r"(da_lo), "r"(db_lo), "r"(scale_d));
}

#define ACC20(d) ACC16(d), "+f"(d[16]), "+f"(d[17]), "+f"(d[18]), "+f"(d[19])
#define ACC20_STR "{%0,%1,%2,%3,%4,%5,%6,%7,%8,%9,%10,%11,%12,%13,%14,%15,%16,%17,%18,%19}"
__device__ __forceinline__ void wgmma_rs_n40(float (&d)[20], const uint32_t (&a)[4], uint32_t db_lo, int scale_d) {
    asm volatile(
        "{\n.reg .pred p;\n.reg .b64 db;\nsetp.ne.b32 p, %25, 0;\nmov.b64 db, {%24, 0x40000040};\n"
        "wgmma.mma_async.sync.aligned.m64n40k16.f32.bf16.bf16 " ACC20_STR ", {%20,%21,%22,%23}, db, p, 1, 1, 0;\n}\n"
        : ACC20(d) : "r"(a[0]), "r"(a[1]), "r"(a[2]), "r"(a[3]), "r"(db_lo), "r"(scale_d));
}
template <int TA, int SBO>
__device__ __forceinline__ void wgmma_ss_n40(float (&d)[20], uint32_t da_lo, uint32_t db_lo, int scale_d) {
    asm volatile(
        "{\n.reg .pred p;\n.reg .b64 da, db;\nsetp.ne.b32 p, %22, 0;\nmov.b64 da, {%20, %23};\nmov.b64 db, {%21, 0x40000040};\n"
        "wgmma.mma_async.sync.aligned.m64n40k16.f32.bf16.bf16 " ACC20_STR ", da, db, p, 1, 1, %24, 0;\n}\n"
        : ACC20(d) : "r"(da_lo), "r"(db_lo), "r"(scale_d), "n"(0x40000000 + SBO / 16), "n"(TA));
}

#define PT(i, th)
struct ChainParams {
    CUtensorMap mapW[3];
    CUtensorMap mapX;
    CUtensorMap mapC;
    CUtensorMap mapWo;
    CUtensorMap mapM;
    CUtensorMap mapOut;
};
constexpr int CH_BLOCK = 384;
constexpr int CO_WO = 0;
constexpr int CH_XC = 5120, CH_XP = 8 * CH_XC;
constexpr int CO_XB = 65536;
constexpr int CO_OB = CO_XB + 2 * CH_XP;
constexpr int CO_P = CO_OB + 8192;
constexpr int CO_LS = CO_P + 3072;
constexpr int CO_SC = CO_LS + 8 * 1280;
constexpr int CH_TW = 6144 + 8192;
constexpr int CO_T = 21 * 8192;
constexpr int CO_WA = CO_T + 6144;
constexpr int CO_ST = CO_T + 3 * CH_TW + 6144;
constexpr int CO_OWN = CO_ST + 4096, CO_OWN2 = CO_SC + 1536;
constexpr int CO_BAR = CO_OWN + 4096;
constexpr int CH_SMEM = CO_BAR + 256 + DBG_EXTRA;
#define CH_NSM 4
static_assert(CO_OWN2 + 1024 <= CO_T && CH_NSM <= 4, "smem layout");
#define CH_POLL_DELAY 180
#define CH_VPOS 2
#define CH_OW 12
#define CH_OF 12
#define CH_Q0 0
#define CH_QI 12
#define CH_QX 0
#define CH_Q1 (CH_Q0 + CH_QI + CH_QX)
#define CH_VA 5
#define CH_SPOS 0
#define CH_LSW 1
#define CH_QE 32
#define CH_KE 32
#define CH_QD 0
#define CH_GAP 0
#define CH_QS (CH_Q1 + 6)
#define CH_KS 10
#define CH_VS 0
#define CH_A7 7
#define CH_RF 0
#define CH_LSS 2
#define CH_OS 1
#define CH_MS 1
#define CH_HA 15
#define CH_LD 4
#define CH_TWP 0
#define CH_SUMC 4
#define CH_ES 1
#define CH_ST 224
#define CH_KEEP 1
#define CH_PINB 0
#define CH_DRY 1
#define CH_D1 3000
#define CH_D2 10000
#define CH_CHAINS 4

constexpr float CH_SC = 0.08838834764831845f * 1.4426950408889634f;
__device__ __forceinline__ uint32_t pin(uint32_t v) { return __shfl_sync(0xffffffff, v, threadIdx.x & 31); }

__device__ __forceinline__ void out_finished() {
    if (atomicAdd(&g_ctr[CT_FIN], 1u) == M_GRID + 64 - 1)
        for (int i = 0; i < CT_N / 4; i++) reinterpret_cast<uint4*>(g_ctr)[i] = make_uint4(0u, 0u, 0u, 0u);
}
__device__ __forceinline__ void out_flush(const float (&acc)[128], const CUtensorMap* map, uint32_t stg0, uint32_t stg1, int tid, int bar, int n0, int m0) {
    const int lane = tid & 31, row = (lane & 7) + ((lane >> 3) & 1) * 8;
#pragma unroll
    for (int bx = 0; bx < 4; bx++)
#pragma unroll
        for (int j = 0; j < 8; j += 2) {
            const float* a = &acc[bx * 32 + j * 4];
            stmatrix_x4((bx < 2 ? stg0 : stg1) + (bx & 1) * 8192 + (((tid >> 5) & 3) * 16 + row) * 128 + (((j + (lane >> 4)) ^ (row & 7)) << 4),
                        pack_bf16(a[0], a[1]), pack_bf16(a[2], a[3]), pack_bf16(a[4], a[5]), pack_bf16(a[6], a[7]));
        }
    asm volatile("fence.proxy.async.shared::cta;\nbar.sync %0, 128;" :: "r"(bar) : "memory");
    asm volatile("{\n.reg .pred p;\nsetp.ne.b32 p, %0, 0;\n@p bra FL_SKIP;\n"
                 "cp.reduce.async.bulk.tensor.2d.global.shared::cta.add.tile.bulk_group [%1, {%4, %8}], [%2];\n"
                 "cp.reduce.async.bulk.tensor.2d.global.shared::cta.add.tile.bulk_group [%1, {%5, %8}], [%2 + 8192];\n"
                 "cp.reduce.async.bulk.tensor.2d.global.shared::cta.add.tile.bulk_group [%1, {%6, %8}], [%3];\n"
                 "cp.reduce.async.bulk.tensor.2d.global.shared::cta.add.tile.bulk_group [%1, {%7, %8}], [%3 + 8192];\n"
                 "cp.async.bulk.commit_group;\nFL_SKIP:\n}"
                 :: "r"(tid & 127), "l"((uint64_t)map), "r"(stg0), "r"(stg1), "r"(n0), "r"(n0 + 64), "r"(n0 + 128), "r"(n0 + 192), "r"(m0) : "memory");
    __syncwarp();
}

__global__ void __cluster_dims__(8, 1, 1) __launch_bounds__(CH_BLOCK, 1)
chain_kernel(const __grid_constant__ ChainParams P) {
    extern __shared__ uint8_t smem_raw[];
    const int tid = threadIdx.x, warp = __shfl_sync(0xffffffff, tid >> 5, 0), lane = tid & 31;
    const int rank = (int)cluster_ctarank();
    constexpr uint32_t sd = 1024;
    const uint32_t sb = ((uint32_t)rank << 24) + sd;
    if (smem_u32(smem_raw) != sb) __trap();
    const int C = blockIdx.x >> 3;
    const int h = C * 4 + (rank >> 1);
    const int qd = lane >> 2, qc = lane & 3;
    const int t4 = warp & 3, wg = warp >> 2;
    pdl_launch_dependents();
    uint32_t t_start;
    asm volatile("mov.u32 %0, %%clock;" : "=r"(t_start));
    t_start = __shfl_sync(0xffffffff, t_start, 0);
    TS_BEGIN(2);
    PT(0, 0);
    const uint32_t bar_mem = sb + CO_BAR, bar_o = bar_mem + 32, bar_sc = bar_o + 32, bar_x = bar_sc + 8, bar_l = bar_x + 16, bar_w = bar_l + 8;
    const uint32_t bar_wo = bar_o + 24;
    auto chunk = [&](int i) { return (uint32_t)((rank - (i >> 1) - 4 * (i & 1)) & 7); };
    const int wcol = h * HD + (rank & 1) * 64;
    auto wdst = [&](int g, int i) { return i == 0 ? CO_WA + g * CH_TW : g && i == 7 ? CO_ST : (g ? CO_XB + CH_XP : 0) + (i - 1) * 8192; };
    if ((tid & 127) == 0) {
        const uint32_t bar = wg == 2 ? bar_x : bar_w + 8 * wg;
        mbar_init(bar, 1);
        asm volatile("fence.mbarrier_init.release.cluster;" ::: "memory");
        mbar_expect_tx(bar, wg == 2 ? CH_XP : 65536);
#pragma unroll 1
        for (int i = 0; i < 8; i++) {
            if (wg == 2) {
                tma_load_2d(sb + CO_XB + i * CH_XC, &P.mapX, bar, i * 64, 0);
                tma_load_2d(sb + CO_XB + i * CH_XC + 4096, &P.mapM, bar, i * 64, 0);
            } else tma_load_2d(sb + wdst(wg, i), &P.mapW[wg], bar, wcol, chunk(i) * 64);
        }
    }
    if (warp == 9 && lane < 15 && lane != 9 && (lane >> 1) != 6) {
        mbar_init(bar_mem + 8 * lane, 1);
        asm volatile("fence.mbarrier_init.release.cluster;" ::: "memory");
    }
    __syncthreads();
    PT(1, 0);
    if (wg == 2) {
        const int t = tid - 256;
        asm volatile("bar.arrive 10, 384;" ::: "memory");
        sts128(sb + CO_T + (2 + (t >> 6)) * CH_TW + 5120 + (t & 63) * 16, 0u, 0u, 0u, 0u);
        if (t < 32) sts128(sb + CO_P + (t >> 3) * 768 + 640 + (t & 7) * 16, 0u, 0u, 0u, 0u);
    }
    const uint32_t wfrag = (((lane >> 4) << 3) + (lane & 7)) * 128 + (((t4 * 2 + ((lane >> 3) & 1)) ^ (lane & 7)) << 4);
    const uint32_t aO = pin(sb + wg * CH_TW + wfrag);
    const uint32_t aL = pin(sb + lane * 16);
    uint32_t w[32][4];
    auto load_w = [&](int g) {
#pragma unroll
        for (int e = CH_NSM; e < 32; e++) ldmatrix_x4_trans(w[e][0], w[e][1], w[e][2], w[e][3], aO + (wdst(g, e >> 2) - g * CH_TW + (e & 3) * 2048));
        fence_async_smem();
    };
    auto pass = [&](auto& d, int g, int b, int j0, int j1, int js, bool group = true) {
        const uint32_t lo = desc_lo(sd + CO_XB + b * CH_XP, 16);
        if (group) wgmma_fence();
#pragma unroll
        for (int j = 0; j < 32; j++) if (j >= j0 && j < j1) {
            const int e = j < js ? j + CH_NSM : j < js + CH_NSM ? j - js : j;
            const uint32_t db = lo + chunk(e >> 2) * (CH_XC / 16) + (e & 3) * 2, da = desc_lo(sd + CO_WA + g * CH_TW + e * 2048, 16);
            if constexpr (sizeof(d) == 64) { if (e < CH_NSM) wgmma_ss_n32(d, da, db, j != 0); else wgmma_rs_n32(d, w[e], db, j != 0); }
            else { if (e < CH_NSM) wgmma_ss_n40<1, 1024>(d, da, db, j != 0); else wgmma_rs_n40(d, w[e], db, j != 0); }
        }
        if (group) wgmma_commit();
    };
    auto uni = [](uint32_t v) { return __shfl_sync(0xffffffff, v, 0); };
    auto roff = [&](int j) { return (uint32_t)(((rank + j) & 7) - rank) << 24; };
    auto store32 = [&](const float* d, uint32_t a) {
        stmatrix_x4_trans(a, pack_bf16(d[0], d[1]), pack_bf16(d[2], d[3]), pack_bf16(d[4], d[5]), pack_bf16(d[6], d[7]));
        stmatrix_x4_trans(a + 2048, pack_bf16(d[8], d[9]), pack_bf16(d[10], d[11]), pack_bf16(d[12], d[13]), pack_bf16(d[14], d[15]));
    };
    auto scores = [&](float (&d)[20], auto sbo, uint32_t q) {
        wgmma_fence();
#pragma unroll
        for (int ks = 0; ks < 4; ks++) wgmma_ss_n40<0, decltype(sbo)::value>(d, desc_lo(sd + CO_T + q, 16) + ks * 2, desc_lo(sd + CO_T + CH_TW, 16) + ks * 2, ks != 0);
        wgmma_commit();
    };
    auto own_scores = [&](const float (&d)[20], float (&v)[10]) {
#pragma unroll
        for (int j = 0; j < 5; j++) { v[2 * j] = d[4 * j]; v[2 * j + 1] = d[4 * j + 1]; }
    };
    auto add_scores = [&](uint32_t a, uint32_t b, float (&v)[10]) {
        const uint4 a0 = lds128(a), a1 = lds128(a + 512);
        const float2 a2 = lds64f(b);
        v[0] += __uint_as_float(a0.x); v[1] += __uint_as_float(a0.y); v[2] += __uint_as_float(a0.z); v[3] += __uint_as_float(a0.w);
        v[4] += __uint_as_float(a1.x); v[5] += __uint_as_float(a1.y); v[6] += __uint_as_float(a1.z); v[7] += __uint_as_float(a1.w);
        v[8] += a2.x; v[9] += a2.y;
    };
    auto row_max = [&](const float (&v)[10]) {
        float mx = fmaxf(fmaxf(fmaxf(v[0], v[1]), fmaxf(v[2], v[3])), fmaxf(fmaxf(v[4], v[5]), fmaxf(v[6], v[7])));
        mx = fmaxf(mx, fmaxf(v[8], v[9]));
        mx = fmaxf(mx, __shfl_xor_sync(0xffffffff, mx, 1));
        return fmaxf(mx, __shfl_xor_sync(0xffffffff, mx, 2)) * CH_SC;
    };
    if (mapa_u32(bar_l, rank ^ 1) != (bar_l ^ (1u << 24)) || mapa_u32(bar_l, (rank + 3) & 7) != bar_l + roff(3)) __trap();
    asm volatile("bar.sync %0, 128;" :: "r"(12 + wg) : "memory");
    if (wg < 2) {
#pragma unroll 1
        for (int rep = CH_DRY ? 0 : 1; rep < 2; rep++) {
            if (rep) mbar_wait(bar_w + 8 * wg, 0);
            PT(3, 0);
            load_w(wg);
            if (rep) {
                asm volatile("bar.arrive %0, 160;" :: "r"(wg ? 2 : 15) : "memory");
                asm volatile("barrier.cluster.arrive.relaxed.aligned;" ::: "memory");
                mbar_wait(bar_x, 0);
            }
            asm volatile("bar.sync %0, 128;" :: "r"(12 + wg) : "memory");
            PT(7, 0);
            float d[16];
            pass(d, wg, 0, 0, 32, 0);
            wgmma_wait<0>();
            store32(d, aO + CO_T);
        }
    }
    PT(8, 0);
    TS_BEGIN(5);
    PT(9, 0);

    if (wg < 2) {
        const uint32_t aM = pin(sb + CO_XB + 4096 + (lane & 7) * 128 + (((lane >> 3) ^ (lane & 7)) << 4));
        uint32_t coff[8];
#pragma unroll
        for (int i = 0; i < 8; i++) coff[i] = uni(chunk(i) * CH_XC);
        auto mem_proj = [&](int s, int it) {
            const uint32_t par = s & 1;
            float acc[CH_CHAINS][4];
#pragma unroll
            for (int i = 0; i < CH_CHAINS; i++) acc[i][0] = acc[i][1] = acc[i][2] = acc[i][3] = 0.f;
            const uint32_t am = aM + par * CH_XP;
            uint32_t b[CH_LD][4], ok[4] = {1, 1, 1, 1}, a0 = am, a1 = am ^ 64;
            auto load = [&](int i) {
                if (i == 12) DBG(13, 0);
                if (i == 2 || (i && !(i & 3))) { a0 = ok[i >> 2] ? am : aL; a1 = a0 ^ 64; }
                uint32_t* r = b[i % CH_LD];
                ldmatrix_x4(r[0], r[1], r[2], r[3], ((i & 1) ? a1 : a0) + coff[i >> 1]);
                if (i == 1) ok[0] = mbar_try(bar_mem, par ^ 1);
                if (i == 2 || i == 4 || i == 8) ok[(i >> 2) + 1] = mbar_try(bar_mem + 8 * ((i >> 2) + 1), par ^ 1);
            };
            auto mma = [&](int i) {
                mma_16816(acc[(2 * i) % CH_CHAINS], w[2 * i][0], w[2 * i][1], w[2 * i][2], w[2 * i][3], b[i % CH_LD][0], b[i % CH_LD][1]);
                mma_16816(acc[(2 * i + 1) % CH_CHAINS], w[2 * i + 1][0], w[2 * i + 1][1], w[2 * i + 1][2], w[2 * i + 1][3], b[i % CH_LD][2], b[i % CH_LD][3]);
            };
#pragma unroll
            for (int e = 0; e < CH_NSM; e++) ldmatrix_x4_trans(w[e][0], w[e][1], w[e][2], w[e][3], aO + CO_WA + e * 2048);
            asm volatile("{\n.reg .pred p;\nsetp.eq.s32 p, %0, 0;\n@p bar.sync 10, 384;\n}" :: "r"(it) : "memory");
            DBG(11, 0);
            bool done = false;
            load(0); load(1); mma(0); mma(1);
            load(2); load(3); mma(2);
#pragma unroll
            for (int i = 4; i < 3 + CH_LD; i++) load(i);
#pragma unroll
            for (int i = 3; i < 16; i++) {
                mma(i);
                if (i + CH_LD < 16) load(i + CH_LD);
                if (i == 12 - CH_LD) done = __all_sync(0xffffffff, ok[0] & ok[1] & ok[2] & ok[3]);
                if (i == CH_HA) asm volatile("{\n.reg .pred p;\nsetp.ne.b32 p, %0, 0;\n@p bar.arrive 5, 384;\n}" :: "r"((int)done) : "memory");
            }
#pragma unroll
            for (int i = 0; i < 4; i++)
#pragma unroll
                for (int c = 1; c < CH_CHAINS; c++) acc[0][i] += acc[c][i];
            const uint32_t r0 = pack_bf16(acc[0][0], acc[0][1]);
            const uint32_t r1 = pack_bf16(acc[0][2], acc[0][3]);
            DBGD(40 + warp, warp, r0 ^ r1);
            stmatrix_x2_trans(aO + CO_T + 4096, r0, r1);
            fence_async_smem();
            return done;
        };
        if (wg == 0) {
#pragma unroll 1
            for (int s = 0; s < NSEG; s++) {
                const uint32_t par = s & 1;
#pragma unroll 1
                for (int it = 0; it < WAIT_LIMIT / 64; it++) if (mem_proj(s, it)) break;
                asm volatile("bar.arrive 1, 256;" ::: "memory");
                if (s == NSEG - 1) break;
                if (tid == 96) {
#pragma unroll
                    for (int j = 0; j < 4; j++) { mbar_expect_tx(bar_mem + 8 * j, j ? 2048 : 1024); if (j < 3) mbar_expect_tx(bar_o + 8 * j, 1024 << j); }
                }
                __syncwarp();
                uint32_t* wp = g_xbuf + (size_t)rank * 2048 + C * 256 + qc * 64 + t4 * 8 + qd;
                asm volatile("st.relaxed.gpu.global.u32 [%0], %1;" :: "l"(wp + ((s + 2) & 3) * 16384), "r"(~0u) : "memory");
                asm volatile("st.relaxed.gpu.global.u32 [%0], %1;" :: "l"(wp + ((s + 2) & 3) * 16384 + 32), "r"(~0u) : "memory");
                if (s == 0) {
                    asm volatile("barrier.cluster.wait.aligned;" ::: "memory");
                    mbar_wait(bar_wo, 0);
                    const int sr = (qd >> 2) * 2 + (qd & 1) + (qd & 2) * 4;
#pragma unroll 2
                    for (int ks = t4; ks < 32; ks += 4) {
                        const uint32_t a = sb + CO_WO + ks * 2048;
                        uint4 u[2][2];
#pragma unroll
                        for (int i = 0; i < 4; i++) { const int r = sr + (i >> 1) * 4; u[i >> 1][i & 1] = lds128(a + r * 128 + (((qc * 2 + (i & 1)) ^ (r & 7)) << 4)); }
                        __syncwarp();
#pragma unroll
                        for (int i = 0; i < 4; i++) {
                            const uint4 u0 = u[i >> 1][0], u1 = u[i >> 1][1];
                            const uint32_t sel = (i & 1) ? 0x7632 : 0x5410;
                            sts128(a + (qd + (i >> 1) * 8) * 128 + (((qc * 2 + (i & 1)) ^ qd) << 4),
                                   __byte_perm(u0.x, u0.y, sel), __byte_perm(u0.z, u0.w, sel), __byte_perm(u1.x, u1.y, sel), __byte_perm(u1.z, u1.w, sel));
                        }
                    }
                    fence_async_smem();
                }
                mbar_wait(bar_x + 8 * (par ^ 1), ((s + 1) >> 1) & 1);
                asm volatile("bar.sync 7, 384;" ::: "memory");
                float d[16];
                float c[4];
                const uint32_t alo = desc_lo(sd + CO_WO, 16), blo = desc_lo(sd + CO_OB, 128);
                wgmma_fence();
                pass(d, 0, par ^ 1, 0, CH_Q0, CH_QS, false);
                asm volatile("bar.sync 11, 256;" ::: "memory");
#pragma unroll
                for (int i = 0; i < 32; i++) {
                    if (i == 4) { pass(d, 0, par ^ 1, CH_Q0 + min(4, CH_QI), CH_Q0 + min(4, CH_QI) + CH_QX, CH_QS, false); mbar_wait_cl(bar_o, par); }
                    if (i == 8) mbar_wait_cl(bar_o + 8, par);
                    if (i == CH_OW) mbar_wait_cl(bar_o + 16, par);
                    wgmma_ss_n8(c, alo + i * 128, blo + i * 16, i != 0);
                    if (i < CH_QI) pass(d, 0, par ^ 1, CH_Q0 + i + (i < 4 ? 0 : CH_QX), CH_Q0 + i + (i < 4 ? 0 : CH_QX) + 1, CH_QS, false);
                }
                wgmma_commit();
                wgmma_wait<0>();
                asm volatile("st.relaxed.gpu.global.u32 [%0], %1;" :: "l"(wp + (s & 3) * 16384), "r"(pack_bf16(c[0], c[2])) : "memory");
                asm volatile("st.relaxed.gpu.global.u32 [%0], %1;" :: "l"(wp + (s & 3) * 16384 + 32), "r"(pack_bf16(c[1], c[3])) : "memory");
                asm volatile("bar.arrive 6, 384;" ::: "memory");
                pace(CH_QD);
                asm volatile("bar.arrive 4, 384;" ::: "memory");
                DBG(8, 0);
                pass(d, 0, par ^ 1, CH_Q1, CH_QE, CH_QS);
                DBG(21, 0);
                if (tid == 0) {
                    if (s + 2 < NSEG) {
                        mbar_expect_tx(bar_x + 8 * par, 32768);
                        tma_load_2d_mc(sb + CO_XB + par * CH_XP + rank * CH_XC, &P.mapX, bar_x + 8 * par, rank * 64, (s + 2) * SEGL, (uint16_t)0xff);
                    } else {
#pragma unroll 1
                        for (int i = 0; i < 8; i++) tma_load_2d(sb + CO_WO + i * 8192, &P.mapWo, bar_wo, (rank & 1) * 256 + (i & 3) * 64, h * HD + (i >> 2) * 64);
                    }
                }
                __syncwarp();
                asm volatile("bar.sync 9, 256;" ::: "memory");
                wgmma_wait<0>();
                DBG(0, 0);
                store32(d, aO + CO_T);
                DBG(22, 0);
            }
            *reinterpret_cast<uint2*>(g_xbuf + 16384 + blockIdx.x * 256 + tid * 2) = make_uint2(~0u, ~0u);
        PT(10, 0);
            const int n0 = (rank & 1) * 256;
            if (tid == 0) {
                mbar_expect_tx(bar_wo, 65536 + 16384);
                mbar_expect_tx(bar_w, 8192);
                asm volatile("prefetch.tensormap [%0];" :: "l"(&P.mapOut) : "memory");
                wait_ctr(CT_CA + 63, 16u);
            }
            __syncwarp();
#pragma unroll 1
            for (int r = 0; r < 2; r++) {
                float acc[128];
                mbar_wait(r ? bar_w : bar_wo, 1);
                asm volatile("bar.sync %0, 256;" :: "r"(15 - r) : "memory");
                wgmma_fence();
#pragma unroll
                for (int kk = 0; kk < 8; kk++)
                    wgmma_ss_n256_tb(acc, make_desc(sd + CO_XB + (kk >> 2) * 16384 + r * 8192 + (kk & 3) * 32, 16, 1024),
                                     make_desc(sd + CO_WO + (kk >> 2) * 32768 + (kk & 3) * 2048, 8192, 1024), kk);
                wgmma_commit();
                if (tid == 0) asm volatile("cp.async.bulk.wait_group.read 0;" ::: "memory");
                asm volatile("bar.sync 12, 128;" ::: "memory");
                wgmma_wait<0>();
                PT(5, 0);
                out_flush(acc, &P.mapOut, sb + CO_XB + CH_XP, sb + CO_XB + CH_XP + 16384, tid, 12, n0, SEQ - 128 + r * 64);
            }
            if (tid == 0) {
                asm volatile("cp.async.bulk.wait_group.read 0;" ::: "memory");
                PT(15, 0);
                out_finished();
            }
        } else {
            const uint32_t usc = uni(CO_SC + min(t4, 2) * 512 + roff((rank ^ 1) - rank)), uscb = uni(bar_sc ^ (1u << 24));
            const uint32_t vaddr = pin(sb + CO_T + 2 * CH_TW + (lane & 15) * 128 + (((t4 * 2 + (lane >> 4)) ^ (lane & 7)) << 4));
            const uint32_t dsta = pin(sb + CO_OB + t4 * 256 + (qc >> 1) * 128 + qd * 16 + (qc & 1) * 8);
            auto local_pv = [&](int s, int st) {
                float dc[16];
                wgmma_fence();
#pragma unroll
                for (int ks = 0; ks < 3; ks++) wgmma_ss_n32_p(dc, desc_lo(sd + CO_T + (2 + (s & 1)) * CH_TW + ks * 2048, 16), desc_lo(sd + CO_P + ks * 256, 128), ks != 0);
                wgmma_commit();
                wgmma_wait<0>();
                store32(dc, aO - CH_TW + st);
            };
            auto store_ctx = [&](int s) {
                if (tid == CH_ST && (uint32_t)s < NSEG - 3) {
                    tma_store_2d(&P.mapC, sb + CO_ST, (rank & 1) * 64, h * SEQ + s * SEGL);
                    asm volatile("cp.async.bulk.commit_group;" ::: "memory");
                }
                __syncwarp();
            };
            auto signal_ctx = [&](int s) {
                if (tid == CH_ST && (s & 3) == 1)
                    asm volatile("cp.async.bulk.wait_group 0;\nred.relaxed.gpu.global.add.u32 [%0], 1;" :: "l"(&g_ctr[CT_CB - 1 + (s >> 2)]) : "memory");
                __syncwarp();
            };
            uint32_t uo[8], ub[8];
#pragma unroll
            for (int i = 0; i < 8; i++) { uo[i] = uni(roff(i) + i * 1024); ub[i] = uni(roff(i) + bar_o + (i < 2 ? 0 : i < 4 ? 8 : 16)); }
#pragma unroll 1
            for (int s = 0; s < NSEG; s++) {
                const uint32_t par = s & 1;
#pragma unroll 1
                for (int it = 0; it < WAIT_LIMIT / 64; it++) if (mem_proj(s, it)) break;
                asm volatile("bar.sync 1, 256;" ::: "memory");
                float d[20];
                scores(d, std::integral_constant<int, 0>(), 4096);
                if (s == NSEG - 1) { wgmma_wait<0>(); break; }
                asm volatile("bar.arrive 8, 256;" ::: "memory");
                if (s == 0) asm volatile("barrier.cluster.wait.aligned;" ::: "memory");
                wgmma_wait<0>();
                {
                    const bool w0 = t4 == 0;
                    asm volatile("{\n.reg .pred p, q;\nsetp.lt.s32 p, %8, 2;\nsetp.eq.s32 q, %8, 2;\n"
                                 "@p st.async.weak.shared::cluster.mbarrier::complete_tx::bytes.v4.f32 [%0], {%2, %3, %4, %5}, [%1];\n"
                                 "@q st.async.weak.shared::cluster.mbarrier::complete_tx::bytes.v2.f32 [%0], {%6, %7}, [%1];\n}"
                                 :: "r"((aL | (s >> 10)) + usc), "r"(uscb), "f"(w0 ? d[0] : d[8]), "f"(w0 ? d[1] : d[9]),
                                    "f"(w0 ? d[4] : d[12]), "f"(w0 ? d[5] : d[13]), "f"(d[16]), "f"(d[17]), "r"(t4) : "memory");
                }
                DBG(3, 4);
                if (CH_ES) signal_ctx(s); else store_ctx(s - 2);
                uint32_t vb[3][4];
                auto load_v = [&]() {
                    asm volatile("bar.sync 3, 256;" ::: "memory");
#pragma unroll
                    for (int k = 0; k < 3; k++) ldmatrix_x4_trans(vb[k][0], vb[k][1], vb[k][2], vb[k][3], vaddr + par * CH_TW + k * 2048);
                };
                mbar_wait_cl(bar_sc, par);
                DBG(4, 4);
                float v[10];
                own_scores(d, v);
                add_scores(aL + CO_SC, aL + CO_SC + 1024, v);
                const float mx = row_max(v);
                if (CH_VPOS == 2) load_v();
#pragma unroll
                for (int j = 0; j < 10; j++) v[j] = ex2f(fmaf(v[j], CH_SC, -mx));
                uint32_t p[5];
#pragma unroll
                for (int j = 0; j < 5; j++) p[j] = pack_bf16(v[2 * j], v[2 * j + 1]);
                if (CH_VPOS == 3) load_v();
                DBG(19, 4);
                float c0[4] = {0.f, 0.f, 0.f, 0.f}, c1[4] = {0.f, 0.f, 0.f, 0.f}, cs[4] = {0.f, 0.f, 0.f, 0.f};
#pragma unroll
                for (int k = 0; k < 3; k++) {
                    const uint32_t p0 = p[2 * k], p1 = k < 2 ? p[2 * k + 1] : 0u;
                    mma_16816(cs, p0, 0u, p1, 0u, 0x3f803f80u, 0x3f803f80u);
                    mma_16816(c0, p0, 0u, p1, 0u, vb[k][0], vb[k][1]);
                    mma_16816(c1, p0, 0u, p1, 0u, vb[k][2], vb[k][3]);
                }
                float inv;
                asm volatile("rcp.approx.ftz.f32 %0, %1;" : "=f"(inv) : "f"(cs[0]));
                const uint32_t b0 = pack_bf16(c0[0] * inv, c0[1] * inv), b1 = pack_bf16(c1[0] * inv, c1[1] * inv);
                DBG(20, 4);
#pragma unroll
                for (int i = 1; i < 8; i++) {
                    st_async_v2((dsta | (s >> 10)) + uo[i], b0, b1, ub[i]);
                    if (i == CH_OS) asm volatile("st.shared.v2.b32 [%0], {%1, %2};" :: "r"(dsta), "r"(b0), "r"(b1) : "memory");
                }
                DBG(5, 4);
                asm volatile("cp.async.bulk.wait_group.read 0;" ::: "memory");
                asm volatile("bar.sync 7, 384;" ::: "memory");
                fence_async_smem();
                asm volatile("bar.arrive 11, 256;" ::: "memory");
                local_pv(s + 1, CO_ST);
                if (CH_ES) fence_async_smem();
                asm volatile("bar.arrive 6, 384;" ::: "memory");
                if (tid == 128) mbar_expect_tx(bar_sc, 1280);
                __syncwarp();
                mbar_wait(bar_x + 8 * (par ^ 1), ((s + 1) >> 1) & 1);
                asm volatile("bar.sync 4, 384;" ::: "memory");
                float dk[16];
                pass(dk, 1, par ^ 1, 0, CH_KE, CH_KS);
                if (CH_ES) store_ctx(s - 1); else signal_ctx(s);
                DBG(1, 4);
                wgmma_wait<0>();
                DBG(2, 4);
                store32(dk, aO + CO_T);
                DBG(29, 4);
            }
            asm volatile("bar.sync 8, 256;" ::: "memory");
            const uint32_t cx = CO_XB + (rank & 1) * 16384;
            auto copy = [&](uint32_t dst, uint32_t src, uint32_t bar) {
                asm volatile("cp.async.bulk.shared::cluster.shared::cta.mbarrier::complete_tx::bytes [%0], [%1], 4096, [%2];" :: "r"(dst), "r"(src), "r"(bar) : "memory");
            };
            if (tid == CH_ST) {
                copy(sb + cx + 4096, sb + CO_ST, bar_wo);
                copy((sb + cx + 4096) ^ (1u << 24), sb + CO_ST, bar_wo ^ (1u << 24));
                asm volatile("cp.async.bulk.wait_group 0;" ::: "memory");
                tma_load_2d_mc(sb + cx, &P.mapC, bar_wo, (rank & 1) * 64, h * SEQ + SEQ - 128, (uint16_t)(3 << (rank & 6)));
            }
            __syncwarp();
#pragma unroll 1
            for (int i = 0; i < 2; i++) {
                local_pv(i, cx + 8192 + i * 4096);
                fence_async_smem();
                asm volatile("bar.arrive %0, 256;" :: "r"(i ? 14 : 9) : "memory");
                asm volatile("bar.sync 2, 128;" ::: "memory");
                if (tid == 128) copy((sb + cx + 8192 + i * 4096) ^ (1u << 24), sb + cx + 8192 + i * 4096, bar_w ^ (1u << 24));
                __syncwarp();
                if (i == 0) asm volatile("bar.sync 3, 256;" ::: "memory");
            }
            PT(14, 128);
        }
    } else {
        float gs;
        auto load_gate = [&](int s) { asm volatile("ld.global.cg.f32 %0, [%1];" : "=f"(gs) : "l"(g_gate + s * SEGL + t4 * 8 + qd) : "memory"); };
        auto softmax = [&](int s) {
            float v[10];
            {
                const uint4 a0 = lds128(aL + CO_OWN + t4 * 1024), a1 = lds128(aL + CO_OWN + t4 * 1024 + 512);
                const float2 a2 = lds64f(aL + CO_OWN2 + t4 * 256 - lane * 8);
                v[0] = __uint_as_float(a0.x); v[1] = __uint_as_float(a0.y); v[2] = __uint_as_float(a0.z); v[3] = __uint_as_float(a0.w);
                v[4] = __uint_as_float(a1.x); v[5] = __uint_as_float(a1.y); v[6] = __uint_as_float(a1.z); v[7] = __uint_as_float(a1.w);
                v[8] = a2.x; v[9] = a2.y;
            }
            mbar_wait_cl(bar_l, s & 1);
            add_scores(aL + t4 * 1024 + CO_LS + (s & 1) * 5120, aL + t4 * 256 - lane * 8 + CO_LS + (s & 1) * 5120 + 4096, v);
            const int lim = t4 * 8 + qd - 2 * qc;
#pragma unroll
            for (int j = 0; j < 8; j++) if ((j >> 1) * 8 + (j & 1) > lim) v[j] = -INFINITY;
            const float mx = row_max(v);
#pragma unroll
            for (int j = 0; j < 10; j++) v[j] = ex2f(fmaf(v[j], CH_SC, -mx));
            float sum = (((v[0] + v[1]) + (v[2] + v[3])) + ((v[4] + v[5]) + (v[6] + v[7]))) + (v[8] + v[9]);
            sum += __shfl_xor_sync(0xffffffff, sum, 1);
            sum += __shfl_xor_sync(0xffffffff, sum, 2);
            asm("rcp.approx.ftz.f32 %0, %0;" : "+f"(sum));
            sum *= 1.f - gs;
            const uint32_t pa = aL + CO_P + t4 * 768;
            stmatrix_x4(pa, pack_bf16(v[0] * sum, v[1] * sum), pack_bf16(v[2] * sum, v[3] * sum), pack_bf16(v[4] * sum, v[5] * sum), pack_bf16(v[6] * sum, v[7] * sum));
            asm volatile("stmatrix.sync.aligned.m8n8.x1.shared.b16 [%0], {%1};" :: "r"(pa + 512), "r"(pack_bf16(v[8] * sum, v[9] * sum)) : "memory");
        };
        uint32_t um[8], ub[8];
#pragma unroll
        for (int i = 0; i < 8; i++) { um[i] = uni(roff((i & 1) * 4 + (i >> 1))); ub[i] = uni(roff((i & 1) * 4 + (i >> 1)) + bar_mem + 8 * (i >> 1)); }
        gs = 0.f;
#pragma unroll 1
        for (int s = 0; s < NSEG; s++) {
            const uint32_t par = s & 1;
            const bool last = s == NSEG - 1;
            if (s == 1) { wait_ctr(CT_GATE, 256u); load_gate(0); }
            softmax(s - 1);
            load_gate(s);
            if (s == 0) {
                PT(2, 256);
                int lane;
                asm volatile("mov.u32 %0, %%laneid;" : "=r"(lane));
                if (t4 >= 2) {
                    const CUtensorMap* map = t4 == 2 ? &P.mapWo : &P.mapW[2];
                    const uint32_t bar = t4 == 2 ? bar_wo : bar_w + 16;
                    const int c0 = t4 == 2 ? rank * 64 : wcol;
                    auto row = [&](int i) { return t4 == 2 ? C * 512 + ((rank - i) & 7) * 64 : (int)chunk(i) * 64; };
                    uint32_t now;
                    do { asm volatile("mov.u32 %0, %%clock;" : "=r"(now)); } while (now - t_start < (uint32_t)(t4 == 2 ? CH_D2 : CH_D1));
                    if (lane == 0) {
#pragma unroll 1
                        for (int i = 0; i < 8; i++) asm volatile("cp.async.bulk.prefetch.tensor.2d.L2.global [%0, {%1, %2}];" :: "l"(map), "r"(c0), "r"(row(i)) : "memory");
                        mbar_expect_tx(bar, 65536);
                    }
                    __syncwarp();
                    asm volatile("bar.sync %0, 160;" :: "r"(t4 == 2 ? 15 : 2) : "memory");
                    if (lane == 0) {
#pragma unroll 1
                        for (int i = 0; i < 8; i++) tma_load_2d(sb + (t4 == 2 ? CO_WO + i * 8192 : wdst(2, i)), map, bar, c0, row(i));
                    }
                } else if (t4 == 0 && lane == 0) {
                    asm volatile("cp.async.bulk.prefetch.tensor.2d.L2.global [%0, {%1, %2}];" :: "l"(&P.mapX), "r"(rank * 64), "r"(SEGL) : "memory");
                    asm volatile("prefetch.tensormap [%0];" :: "l"(&P.mapC) : "memory");
                    mbar_expect_tx(bar_sc, 1280);
                    mbar_expect_tx(bar_x + 8, 32768);
                }
                __syncwarp();
                mbar_wait(bar_w + 16, 0);
                PT(4, 256);
                load_w(2);
                asm volatile("bar.sync 14, 128;" ::: "memory");
                asm volatile("barrier.cluster.arrive.relaxed.aligned;" ::: "memory");
                if (t4 == 0 && lane == 0) {
#pragma unroll 1
                    for (int i = 0; i < 8; i++) tma_load_2d(sb + CO_XB + CH_XP + i * CH_XC, &P.mapX, bar_x + 8, i * 64, SEGL);
                }
                __syncwarp();
                PT(6, 256);
            }
            DBG(7, 8);
#pragma unroll 1
            for (int it = 0; it < (CH_RF ? WAIT_LIMIT / 64 : 0); it++)
                if (mbar_try(bar_mem, par ^ 1) & mbar_try(bar_mem + 8, par ^ 1) & mbar_try(bar_mem + 16, par ^ 1) & mbar_try(bar_mem + 24, par ^ 1)) break;
            fence_async_smem();
            asm volatile("bar.sync 5, 384;" ::: "memory");
            DBG(23, 8);
            float d[20];
            pass(d, 2, par, 0, CH_VA, CH_VS);
            asm volatile("bar.sync 8, 256;" ::: "memory");
            pass(d, 2, par, CH_VA, 32, CH_VS);
            wgmma_wait<0>();
            stmatrix_x2_trans(aO + par * CH_TW + CO_T + 4096, pack_bf16(d[16], d[17]), pack_bf16(d[18], d[19]));
            store32(d, aO + par * CH_TW + CO_T);
            DBG(24, 8);
            if (!last) asm volatile("bar.arrive 3, 256;\nbar.sync 7, 384;" ::: "memory");
            scores(d, std::integral_constant<int, 512>(), 0);
            asm volatile("{\n.reg .pred p;\nsetp.eq.s32 p, %1, 256;\n@p mbarrier.arrive.expect_tx.shared::cta.b64 _, [%0], 5120;\n}" :: "r"(bar_l), "r"(tid) : "memory");
            wgmma_wait<0>();
            auto send_scores = [&]() {
                const uint32_t a = aL + t4 * 1024, a2 = aL + t4 * 256 - lane * 8, r = roff((rank ^ 1) - rank) + CO_LS + par * 5120;
                asm volatile("st.async.weak.shared::cluster.mbarrier::complete_tx::bytes.v4.f32 [%0], {%3, %4, %5, %6}, [%2];\n"
                             "st.async.weak.shared::cluster.mbarrier::complete_tx::bytes.v4.f32 [%0 + 512], {%7, %8, %9, %10}, [%2];\n"
                             "st.async.weak.shared::cluster.mbarrier::complete_tx::bytes.v2.f32 [%1], {%11, %12}, [%2];"
                             :: "r"(a + r), "r"(a2 + r + 4096), "r"(bar_l ^ (1u << 24)), "f"(d[0]), "f"(d[1]), "f"(d[4]), "f"(d[5]),
                                "f"(d[8]), "f"(d[9]), "f"(d[12]), "f"(d[13]), "f"(d[16]), "f"(d[17]) : "memory");
            };
            auto keep_scores = [&]() {
                const uint32_t a = aL + t4 * 1024, a2 = aL + t4 * 256 - lane * 8;
                sts128(a + CO_OWN, __float_as_uint(d[0]), __float_as_uint(d[1]), __float_as_uint(d[4]), __float_as_uint(d[5]));
                sts128(a + CO_OWN + 512, __float_as_uint(d[8]), __float_as_uint(d[9]), __float_as_uint(d[12]), __float_as_uint(d[13]));
                asm volatile("st.shared.v2.f32 [%0], {%1, %2};" :: "r"(a2 + CO_OWN2), "f"(d[16]), "f"(d[17]) : "memory");
            };
            if (s == 0) asm volatile("barrier.cluster.wait.aligned;" ::: "memory");
            if (CH_LSS == 0) send_scores();
            if (CH_KEEP == 0) keep_scores();
            if (last) { if (CH_LSS) send_scores(); if (CH_KEEP) keep_scores(); break; }
            asm volatile("bar.arrive 4, 384;\nbar.arrive 9, 256;" ::: "memory");
            uint32_t t0, t1;
            if (!CH_PINB) asm volatile("bar.sync 6, 384;\nmov.u32 %0, %%clock;" : "=r"(t0) :: "memory");
            const int row = t4 * 2 + (lane >> 4);
            const uint32_t dsta = pin(sb + CO_XB + (par ^ 1) * CH_XP + rank * CH_XC + 4096 + row * 128 + ((((lane & 15) >> 1) ^ row) << 4) + (lane & 1) * 8);
            const uint32_t dst1 = pin(dsta + um[1]), bar1 = pin(ub[1] | (s >> 10));
            uint32_t sel = pin(((qd >> 1) == qc ? 0x3f80u << (qd & 1) * 16 : 0u) | (s >> 10));
            const uint2* xb = reinterpret_cast<const uint2*>(g_xbuf + (s & 3) * 16384 + (size_t)rank * 2048 + t4 * 64) + pin(lane | (s >> 10));
            if (CH_PINB) asm volatile("bar.sync %1, 384;\nmov.u32 %0, %%clock;" : "=r"(t0) : "r"(6 | (dst1 & sel & (uint32_t)(size_t)xb & (s >> 10))) : "memory");
            if (CH_LSS == 1) send_scores();
            uint2 p[8], q[8];
            do { asm volatile("mov.u32 %0, %%clock;" : "=r"(t1) :: "memory"); } while (t1 - t0 < CH_POLL_DELAY);
#pragma unroll
            for (int k = 0; k < 8; k++)
                asm volatile("ld.relaxed.gpu.global.v2.u32 {%0, %1}, [%2];" : "=r"(p[k].x), "=r"(p[k].y) : "l"(xb + k * 128) : "memory");
            DBG(17, 8);
            if (CH_LSS == 2) send_scores();
            if (CH_KEEP) keep_scores();
            {
                uint32_t z;
                asm volatile("mov.u32 %0, %%clock;" : "=r"(z) :: "memory");
#pragma unroll
                for (int i = 0; i < CH_GAP; i++) asm volatile("{\n.reg .f32 f;\nmov.b32 f, %0;\nex2.approx.ftz.f32 f, f;\nmov.b32 %0, f;\n}" : "+r"(z));
                asm volatile("and.b32 %0, %0, %1;" : "+r"(z) : "r"(s >> 10));
                xb += z;
            }
#pragma unroll
            for (int k = 0; k < 8; k++)
                asm volatile("ld.relaxed.gpu.global.v2.u32 {%0, %1}, [%2];" : "=r"(q[k].x), "=r"(q[k].y) : "l"(xb + k * 128) : "memory");
            uint32_t m0, m1;
            {
                uint32_t z;
                asm volatile("mov.u32 %0, %%clock;" : "=r"(z) :: "memory");
                sel |= z & (s >> 10);
            }
            auto sum = [&](const uint2 (&p)[8]) {
                float c[CH_SUMC][4];
#pragma unroll
                for (int k = 0; k < 4; k++) {
                    if (k < CH_SUMC) c[k][0] = c[k][1] = c[k][2] = c[k][3] = 0.f;
                    mma_16816(c[k % CH_SUMC], p[2 * k].x, p[2 * k].y, p[2 * k + 1].x, p[2 * k + 1].y, sel, sel);
                }
#pragma unroll
                for (int k = 1; k < CH_SUMC; k++) { c[0][0] += c[k][0]; c[0][1] += c[k][1]; c[0][2] += c[k][2]; c[0][3] += c[k][3]; }
                m0 = pack_bf16(c[0][0], c[0][1]);
                m1 = pack_bf16(c[0][2], c[0][3]);
                uint32_t ok;
                asm volatile("{\n.reg .pred p;\nsetp.num.f32 p, %1, %2;\nvote.sync.all.pred p, p, 0xffffffff;\nselp.u32 %0, 1, 0, p;\n}" : "=r"(ok) : "f"(c[0][0]), "f"(c[0][2]));
                return ok;
            };
            if (!sum(p)) {
                DBG(12, 8);
#pragma unroll 1
                for (int it = 0; it < WAIT_LIMIT / 4; it++) {
                    if (sum(q)) break;
                    uint32_t bad = 0;
#pragma unroll
                    for (int k = 0; k < 8; k++) bad |= (max(q[k].x, q[k].y) == ~0u ? 1u : 0u) << k;
                    if (__all_sync(0xffffffff, bad == 0u)) break;
                    if (it == 0) DBG(14, 8);
                    if (it == 1) DBG(15, 8);
#pragma unroll
                    for (int k = 0; k < 8; k++)
                        if (bad & (1u << k))
                            asm volatile("ld.relaxed.gpu.global.v2.u32 {%0, %1}, [%2];" : "=r"(q[k].x), "=r"(q[k].y) : "l"(xb + k * 128) : "memory");
                }
            }
            DBG(9, 8);
#pragma unroll
            for (int i = 1; i < 8; i++) {
                st_async_v2(i == 1 ? dst1 : dsta + um[i], m0, m1, i == 1 ? bar1 : ub[i]);
                if (i == CH_MS) asm volatile("st.shared.v2.b32 [%0], {%1, %2};\nbar.arrive 10, 384;" :: "r"(dsta), "r"(m0), "r"(m1) : "memory");
            }
            if (s == 1000000) {
#pragma unroll
                for (int k = 0; k < 8; k++) asm volatile("st.volatile.shared.v2.u32 [%0], {%1, %2};" :: "r"(s), "r"(q[k].x), "r"(q[k].y) : "memory");
            }
            DBG(10, 8);
        }
        PT(11, 256);
        asm volatile("bar.arrive 15, 256;\nbar.sync 9, 256;" ::: "memory");
        softmax(NSEG - 1);
        fence_async_smem();
        asm volatile("bar.arrive 3, 256;" ::: "memory");
    }
    __syncthreads();
    asm volatile("barrier.cluster.arrive.relaxed.aligned;\nbarrier.cluster.wait.aligned;" ::: "memory");
    TS_END(2);
}

struct Proj2Params {
    CUtensorMap mapA[2];
    CUtensorMap mapW[3];
    bf16* out[3];
};
#define P2T(i)
#define P2_NOMMA 0
#define P2_NOLOAD 0
#define P2_ROT 4
#define P2_NP 1
#define P2_NI 4
constexpr int P2_STAGES = 6;
constexpr int P2_ITEMS = 168 + 48;

__device__ __forceinline__ int p2_reps(int t) { return t >= 168 ? 1 : 2; }
__device__ __forceinline__ void p2_tile(int t, int w, int& z, int& mp, int& head) {
    if (t >= 168) { w += ((t - 168) & 1) * 2; t = 168 + ((t - 168) >> 1); }
    const int hq = (t / 24 + P2_ROT) & 7, v = t % 24;
    mp = v & 7;
    if (v < 16) { head = hq * 4 + (v >> 3) * 2 + (w >> 1); z = 1 + (w & 1); }
    else { head = hq * 4 + w; z = 0; }
}
__device__ __forceinline__ void mbar_arrive_remote(uint32_t bar_cluster_addr) {
    asm volatile("mbarrier.arrive.release.cluster.shared::cluster.b64 _, [%0];" :: "r"(bar_cluster_addr) : "memory");
}
__device__ __forceinline__ void mbar_arrive_cl(uint32_t bar_cluster_addr) {
    asm volatile("mbarrier.arrive.shared::cluster.b64 _, [%0];" :: "r"(bar_cluster_addr) : "memory");
}
__device__ __forceinline__ void mbar_wait_acq_cluster(uint32_t bar, uint32_t parity) {
    asm volatile(
        "{\n"
        ".reg .pred p, q;\n"
        ".reg .u32 c;\n"
        "mov.u32 c, 0;\n"
        "WAIT_LOOP_C:\n"
        "mbarrier.try_wait.parity.acquire.cluster.shared::cta.b64 p, [%0], %1;\n"
        "@p bra WAIT_DONE_C;\n"
        "add.u32 c, c, 1;\n"
        "setp.lt.u32 q, c, 4000000;\n"
        "@q bra WAIT_LOOP_C;\n"
        "WAIT_DONE_C:\n"
        "}\n" :: "r"(bar), "r"(parity) : "memory");
}
__device__ __forceinline__ uint4 quad_transpose(uint32_t p0, uint32_t p1, uint32_t p2, uint32_t p3, int lane) {
    const bool o1 = lane & 1, o2 = lane & 2;
    uint32_t s0 = o1 ? p0 : p1, s1 = o1 ? p2 : p3;
    s0 = __shfl_xor_sync(0xffffffff, s0, 1); s1 = __shfl_xor_sync(0xffffffff, s1, 1);
    const uint32_t a_lo = o1 ? s0 : p0, a_hi = o1 ? p1 : s0, b_lo = o1 ? s1 : p2, b_hi = o1 ? p3 : s1;
    uint32_t t0 = o2 ? a_lo : b_lo, t1 = o2 ? a_hi : b_hi;
    t0 = __shfl_xor_sync(0xffffffff, t0, 2); t1 = __shfl_xor_sync(0xffffffff, t1, 2);
    return o2 ? make_uint4(t0, t1, b_lo, b_hi) : make_uint4(a_lo, a_hi, t0, t1);
}
#define P2_PACE 35
#define P2_PACE2 0
template <bool PERM, int PACE = 0>
__device__ __forceinline__ void store_frag_128(const float (&acc)[64], bf16* obase, int lane) {
#pragma unroll
    for (int rr = 0; rr < 2; rr++)
#pragma unroll
        for (int g = 0; g < 4; g++) {
            const float* a = &acc[g * 16 + rr * 2];
            const uint32_t p0 = pack_bf16(a[0], a[1]), p1 = pack_bf16(a[4], a[5]), p2 = pack_bf16(a[8], a[9]), p3 = pack_bf16(a[12], a[13]);
            *reinterpret_cast<uint4*>(obase + (size_t)(rr * 8) * HD + g * 32) = PERM ? make_uint4(p0, p1, p2, p3) : quad_transpose(p0, p1, p2, p3, lane);
            pace(PACE);
        }
}
struct OutParams {
    CUtensorMap mapCtx[2];
    CUtensorMap mapWo[2];
    CUtensorMap mapOut;
};

#define OT(i)
#define OTP(i, th)
constexpr int O2_STAGES = 4;
constexpr int O2_GRID = 0;
#define O2_FINE 8
#define O2_Q0 10
#define O2_Q1 11
#define O2_QA 14

constexpr uint32_t OB_FULL = 0, OB_EMPTY = 32, OB_ITEM = 64, OB_SLOT = 128, OB_STOP = 160;
__device__ __forceinline__ void out_init(uint32_t bars) {
    for (int i = 0; i < O2_STAGES; i++) {
        mbar_init(bars + OB_FULL + 8 * i, 1); mbar_init(bars + OB_EMPTY + 8 * i, 4); mbar_init(bars + OB_ITEM + 16 * i, 1); mbar_init(bars + OB_ITEM + 16 * i + 8, 1);
    }
    sts128(bars + OB_STOP, 0u, 0u, 0u, 0u);
}
struct OutJob { int tg, q, qe, last, t0, nw, nq; };
__device__ __forceinline__ OutJob out_job(int cid, int j) {
    auto quota = [](int tg) { return tg & 2 ? O2_Q0 : O2_Q1; };
    if (cid < 28) { const int tg = cid % 14, h = cid >= 14, nq = 128 - quota(tg); return {tg, 2 * h, 2 * h + 2, 1, 2, nq / 2 - O2_FINE, nq}; }
    if (j == (cid < 30 ? 1 : 4)) return {16, 2 * cid + 8, 2 * cid + 10, 1, 38, 64 - O2_FINE, 128};
    if (cid < 30) return {cid - 14, O2_QA, 64, 0, 0, 0, 0};
    const int tg = (j * 4 + cid - 32) & 15;
    return {tg, tg >= 14 ? 0 : 128 - quota(tg), tg >= 14 ? O2_QA : 128, 0, 0, 0, 0};
}
__device__ __forceinline__ int out_mt(int tg, int rank) { return tg < 16 ? (tg & ~1) + rank : tg - 2; }
__device__ __forceinline__ int out_n0(int tg, int rank) { return (tg < 16 ? tg & 1 : rank) * 256; }
__device__ __forceinline__ void out_producer(const OutParams& P, uint32_t sbase, uint32_t bars, uint32_t rank, int cid, bool lead) {
    const uint32_t bar_full = bars + OB_FULL, bar_empty = bars + OB_EMPTY, bar_item = bars + OB_ITEM, slot = bars + OB_SLOT, stop = bars + OB_STOP;
    int s = 0, nb = 0; uint32_t ph = 0;
    if (lead) asm volatile("prefetch.tensormap [%0];" :: "l"(&P.mapOut) : "memory");
#pragma unroll 1
    for (int job = 0;; job++) {
        const OutJob J = out_job(cid, job);
        const int mt = out_mt(J.tg, rank), m0 = mt * 128, n0 = out_n0(J.tg, rank);
        int ready = 0, q = J.q, qe = J.qe, tnext = 0, nst = 0;
        if (lead && rank == 0 && J.last) tnext = take_ticket(CT_OT + J.tg);
#pragma unroll 1
        for (int ic = 0;; ic++) {
#pragma unroll 1
            for (bool first = true; q < qe; q++, first = false) {
                const int b = q >> 6, head = (q >> 1) & 31, dk = (q & 1) * 64;
                mbar_wait(bar_empty + 8 * s, ph);
                const uint32_t sa = sbase + s * 49152;
                if (lead) {
                    if (rank == 0 && J.last && first) {
                        const int t = tnext + J.t0;
                        asm volatile("st.shared.s32 [%0], %1;" :: "r"(slot + (ic & 7) * 4), "r"(t) : "memory");
                        mbar_arrive(bar_item + 8 * (ic & 7));
                        st_async_b32(mapa_u32(slot + (ic & 7) * 4, 1), (uint32_t)t, mapa_u32(bar_item + 8 * (ic & 7), 1));
                        if (J.nw + t < J.nq) tnext = take_ticket(CT_OT + J.tg);
                    }
                    if (b ? mt >= nb : !((ready >> (head >> 3)) & 1)) {
                        if (b) nb = max(mt, 11) + 1; else ready |= 1 << (head >> 3);
                        wait_ctr(b ? CT_CB + nb - 1 : CT_CA + mt * 4 + (head >> 3), b ? 64u : 16u);
                    }
                    asm volatile("st.shared.s32 [%0], %1;" :: "r"(stop + s * 4), "r"(0) : "memory");
                    mbar_expect_tx(bar_full + 8 * s, 49152);
                    tma_load_2d(sa, &P.mapCtx[b], bar_full + 8 * s, dk, head * SEQ + m0);
                    if (++nst == 6 && !(ready & 8)) { wait_ctr(CT_CA + mt * 4 + 3, 16u); ready |= 8; }
                } else if (J.tg < 16) {
                    for (int j = (int)rank * 2; j < (int)rank * 2 + 2; j++)
                        tma_load_2d_mc(sa + 16384 + j * 8192, &P.mapWo[b], bar_full + 8 * s, n0 + j * 64, head * HD + dk, (uint16_t)3);
                } else {
                    for (int j = 0; j < 4; j++) tma_load_2d(sa + 16384 + j * 8192, &P.mapWo[1], bar_full + 8 * s, n0 + j * 64, head * HD + dk);
                }
                if (++s == O2_STAGES) { s = 0; ph ^= 1; }
            }
            if (!J.last) break;
            if (lead && rank == 1) mbar_expect_tx(bar_item + 8 * (ic & 7), 4);
            mbar_wait(bar_item + 8 * (ic & 7), (ic >> 3) & 1);
            int t;
            asm volatile("ld.shared.s32 %0, [%1];" : "=r"(t) : "r"(slot + (ic & 7) * 4) : "memory");
            if (J.nw + t >= J.nq) break;
            if (t < J.nw) { q = 2 * t; qe = q + 2; } else { q = J.nw + t; qe = q + 1; }
        }
        if (lead) {
            if (!(ready & 8)) wait_ctr(CT_CA + mt * 4 + 3, 16u);
            mbar_wait(bar_empty + 8 * s, ph);
            asm volatile("st.shared.s32 [%0], %1;" :: "r"(stop + s * 4), "r"(1 + J.last + n0 + (m0 << 4)) : "memory");
            mbar_arrive(bar_full + 8 * s);
        }
        if (J.last) break;
        if (++s == O2_STAGES) { s = 0; ph ^= 1; }
    }
    if (lead) {
        out_finished();
        for (int i = 1; i < O2_STAGES; i++) {
            if (++s == O2_STAGES) { s = 0; ph ^= 1; }
            mbar_wait(bar_empty + 8 * s, ph);
        }
    }
}
__device__ __forceinline__ void out_consumer(const OutParams& P, uint32_t sbase, uint32_t bars, int warp, uint32_t opar) {
    const uint32_t bar_full = bars + OB_FULL, bar_empty = bars + OB_EMPTY, stop = bars + OB_STOP;
    int tid;
    asm volatile("mov.u32 %0, %%tid.x;" : "=r"(tid));
    const int wg = warp >> 2;
    const bool elected = (tid & 127) == 0;
    auto release = [&](int s) { if (elected) { const uint32_t e = bar_empty + 8 * s; mbar_arrive_cl(mapa_u32(e, 0)); mbar_arrive_cl(mapa_u32(e, 1)); } };
    float acc[128];
    int s = 0, sprev = 0, st, n = 0; uint32_t ph = 0;
#pragma unroll 1
    do {
#pragma unroll 1
        for (int i = 0;; i++, n++) {
            mbar_wait(bar_full + 8 * s, ph);
            asm volatile("ld.shared.s32 %0, [%1];" : "=r"(st) : "r"(stop + s * 4) : "memory");
            if (st) break;
            if (n == 0) OT(1);
            const uint32_t sa = sbase + s * 49152 + wg * 8192, sb = sbase + s * 49152 + 16384;
            wgmma_fence();
#pragma unroll
            for (int kk = 0; kk < 4; kk++)
                wgmma_ss_n256_tb(acc, make_desc(sa + kk * 32, 16, 1024), make_desc(sb + kk * 2048, 8192, 1024), kk ? 1 : i);
            wgmma_commit();
            if (i > 0) { wgmma_wait<1>(); release(sprev); }
            if (i == 1 && n > 1) {
                if (elected) asm volatile("cp.async.bulk.wait_group.read 0;" ::: "memory");
                release((s + 2) & 3);
            }
            sprev = s;
            if (++s == O2_STAGES) { s = 0; ph ^= 1; }
        }
        mbar_wait(sbase + FB_OE + 8 * wg, opar);
        wgmma_wait<0>();
        release(sprev);
        asm volatile("bar.sync %0, 128;" :: "r"(1 + wg) : "memory");
        OT(3);
        out_flush(acc, &P.mapOut, sbase + s * 49152 + wg * 16384, sbase + O2_STAGES * 49152 + wg * 16384, tid, 1 + wg, st & 256, (st >> 4 & ~127) + wg * 64);
        if (++s == O2_STAGES) { s = 0; ph ^= 1; }
    } while (!(st & 2));
    OT(4);
    if (elected) {
        asm volatile("cp.async.bulk.wait_group.read 0;" ::: "memory");
    }
}

struct MainParams { Proj2Params p; AttnParams a; OutParams o; const bf16 *x, *gate_w; };
__device__ __forceinline__ int p2_apos(int k) { return k < 2 ? k : k < 6 ? k + 2 : k - 4; }
__global__ void __cluster_dims__(2, 1, 1) __launch_bounds__(384, 1) main_kernel(const __grid_constant__ MainParams MP) {
    const Proj2Params& P = MP.p;
    extern __shared__ uint8_t smem_raw[];
    const uint32_t rank = cluster_ctarank();
    const uint32_t sbase = (rank << 24) + SD;
    if (smem_u32(smem_raw) != sbase) __trap();
    const uint32_t sA = sbase, sB = sbase + 131072;
    const uint32_t bars = sbase + MO_BAR, obars = bars + 768;
    const uint32_t a_full = bars, a_empty = bars + 64, b_full = bars + 128, b_empty = b_full + 8 * P2_STAGES;
    const uint32_t item_bar = b_empty + 8 * P2_STAGES, item_in = item_bar + 16, slot = item_in + 16;
    const uint32_t note_bar = slot + 16, note_free = note_bar + 64, note = note_free + 64;
    const int warp = __shfl_sync(0xffffffff, threadIdx.x >> 5, 0), lane = threadIdx.x & 31;
    TS_BEGIN(0);
    if (threadIdx.x == 0) {
        for (int i = 0; i < 8; i++) { mbar_init(a_full + 8 * i, 1); mbar_init(a_empty + 8 * i, 2); }
        for (int i = 0; i < P2_STAGES; i++) { mbar_init(b_full + 8 * i, 1); mbar_init(b_empty + 8 * i, 2); }
        mbar_init(item_bar, 1); mbar_init(item_bar + 8, 1); mbar_init(item_in, 2); mbar_init(item_in + 8, 2);
        for (int i = 0; i < 8; i++) { mbar_init(note_bar + 8 * i, 1); mbar_init(note_free + 8 * i, 1); }
        asm volatile("fence.mbarrier_init.release.cluster;" ::: "memory");
    }
    if (threadIdx.x == 32) {
        attn_init(sbase);
        asm volatile("fence.mbarrier_init.release.cluster;" ::: "memory");
    }
    if (threadIdx.x == 256) {
        out_init(obars);
        asm volatile("fence.mbarrier_init.release.cluster;" ::: "memory");
    }
    __syncthreads();
    asm volatile("barrier.cluster.arrive.relaxed.aligned;" ::: "memory");
    if (warp >= 8) {
    asm volatile("setmaxnreg.dec.sync.aligned.u32 40;");
    asm volatile("barrier.cluster.wait.aligned;" ::: "memory");
    if (warp == 9) {
        if (lane == 0) {
            for (int n = 0;; n++) {
                const int e = (n & 1) * 4 + ((n >> 1) & 3);
                mbar_wait(note_bar + 8 * e, (n >> 3) & 1);
                int m;
                asm volatile("ld.shared.s32 %0, [%1];" : "=r"(m) : "r"(note + e * 4) : "memory");
                mbar_arrive(note_free + 8 * e);
                if (m < 0) break;
                signal_ctr(m);
            }
            attn_helper(MP.a, sbase, 0);
        }
    } else if (warp == 10) {
        if (lane == 0) {
            auto publish = [&](int ic, int tq) {
                const int t = tq < P2_ITEMS ? tq : -1;
                asm volatile("st.shared.s32 [%0], %1;" :: "r"(slot + (ic & 3) * 4), "r"(t) : "memory");
                mbar_arrive(item_bar + 8 * (ic & 1));
                st_async_b32(mapa_u32(slot + (ic & 3) * 4, 1), (uint32_t)t, mapa_u32(item_bar + 8 * (ic & 1), 1));
            };
            const int npair = M_GRID / 2, pair = (int)(blockIdx.x >> 1);
            if (rank == 0) publish(0, pair);
            for (int ic = 0;; ic++) {
                if (rank == 1) mbar_expect_tx(item_bar + 8 * (ic & 1), 4);
                mbar_wait(item_bar + 8 * (ic & 1), (ic >> 1) & 1);
                int t;
                asm volatile("ld.shared.s32 %0, [%1];" : "=r"(t) : "r"(slot + (ic & 3) * 4) : "memory");
                if (t < 0) break;
                int z0, mp, h0;
                p2_tile(t, 0, z0, mp, h0);
                const int aidx = z0 >= 1 ? 1 : 0;
                const int m0 = (2 * mp + (int)rank) * 128;
                for (int k = 0; k < 8; k++) {
                    mbar_wait(a_empty + 8 * k, (ic & 1) ^ 1);
                    if (P2_NOLOAD) mbar_arrive(a_full + 8 * k); else {
                    mbar_expect_tx(a_full + 8 * k, 16384);
                    tma_load_2d(sA + p2_apos(k) * 16384, &P.mapA[aidx], a_full + 8 * k, k * 64, m0); }
                }
                if (rank == 0) {
                    mbar_wait(item_in + 8 * (ic & 1), (ic >> 1) & 1);
                    publish(ic + 1, ic == 0 ? npair + pair : pair < P2_NP && ic + 1 >= P2_NI ? P2_ITEMS : 2 * npair + (int)atomicAdd(&g_ctr[CT_PROJ], 1u));
                }
            }
            attn_helper(MP.a, sbase, 1);
        }
    } else {
        if (lane == 0) {
            const int par2 = warp == 8 ? 0 : 1;
            int it = 0, ic = 0; uint32_t bph = 0;
            for (;; ic++) {
                mbar_wait(item_bar + 8 * (ic & 1), (ic >> 1) & 1);
                int t;
                asm volatile("ld.shared.s32 %0, [%1];" : "=r"(t) : "r"(slot + (ic & 3) * 4) : "memory");
                if (t < 0) break;
                const int nt = 2 * p2_reps(t);
                for (int w = 0; w < nt; w++) {
                    int z, mp, hd;
                    p2_tile(t, w, z, mp, hd);
                    for (int k = 0; k < 8; k++) {
                        const int s = it; const uint32_t phb = bph;
                        if (++it == P2_STAGES) { it = 0; bph ^= 1; }
                        if ((k & 1) != par2) continue;
                        mbar_wait(b_empty + 8 * s, phb ^ 1);
                        if (P2_NOLOAD) { mbar_arrive(b_full + 8 * s); continue; }
                        mbar_expect_tx(b_full + 8 * s, 16384);
                        tma_load_2d_mc(sB + s * 16384 + rank * 8192, &P.mapW[z], b_full + 8 * s, hd * 128 + (int)rank * 64, k * 64, (uint16_t)3);
                    }
                }
            }
            if (warp == 8) {
                attn_producer(MP.a, sbase, a_empty, ~ic & 1);
                TS_END2(1, 256); TS_BEGIN2(3, 256);
                for (int i = 0; i < 4; i++) {
                    const uint32_t e = mapa_u32(obars + OB_EMPTY + 8 * (i & 1), i >> 1);
                    mbar_arrive_cl(e); mbar_arrive_cl(e);
                }
            }
            out_producer(MP.o, sbase, obars, rank, blockIdx.x >> 1, warp == 8);
            TS_END2(3, 256);
        }
    }
    } else {
        asm volatile("setmaxnreg.inc.sync.aligned.u32 232;");
        asm volatile("barrier.cluster.wait.aligned;" ::: "memory");
        const int wg = warp >> 2;
        float acc[2][64];
        const uint32_t a_lo = desc_lo(SD, 16), b_lo0 = desc_lo(SD + 131072, 8192);
        const bool elected = (threadIdx.x & 127) == 0;
        int s = (wg * 8) % P2_STAGES;
        uint32_t ph = ((wg * 8) / P2_STAGES) & 1;
        int nnote = 0;
        if (wg == 1) {
            asm volatile("bar.arrive 3, 256;" ::: "memory");
            if (blockIdx.x < 64) {
                const int r = blockIdx.x * 32 + (warp & 3) * 8 + (lane >> 2);
                float c[4] = {0.f, 0.f, 0.f, 0.f};
                uint4 xv[16], gv[16];
#pragma unroll
                for (int i = 0; i < 16; i++) {
                    xv[i] = __ldg(reinterpret_cast<const uint4*>(MP.x + (size_t)r * DM + i * 32 + (lane & 3) * 8));
                    gv[i] = __ldg(reinterpret_cast<const uint4*>(MP.gate_w + i * 32 + (lane & 3) * 8));
                }
                auto mul = [](uint32_t a, uint32_t b) { uint32_t p; asm("mul.rn.bf16x2 %0, %1, %2;" : "=r"(p) : "r"(a), "r"(b)); return p; };
#pragma unroll
                for (int i = 0; i < 16; i++)
                    mma_16816(c, mul(xv[i].x, gv[i].x), mul(xv[i].y, gv[i].y), mul(xv[i].z, gv[i].z), mul(xv[i].w, gv[i].w), 0x3f803f80u, 0x3f803f80u);
                if ((lane & 3) == 0) g_gate[r] = bf16r(__fdividef(1.f, 1.f + __expf(-bf16r(c[0] + c[2]))));
                __syncwarp();
                if (lane == 0) signal_ctr_generic(CT_GATE);
                __syncwarp();
            }
        }
        for (int ic = 0;; ic++) {
            mbar_wait(item_bar + 8 * (ic & 1), (ic >> 1) & 1);
            int t;
            asm volatile("ld.shared.s32 %0, [%1];" : "=r"(t) : "r"(slot + (ic & 3) * 4) : "memory");
            t = __shfl_sync(0xffffffff, t, 0);
            P2T(7);
            if (wg == 0 && t < 0) {
                if (elected) {
                    const int e = nnote & 3;
                    mbar_wait(note_free + 8 * e, ((nnote >> 2) & 1) ^ 1);
                    asm volatile("st.shared.s32 [%0], %1;" :: "r"(note + e * 4), "r"(-1) : "memory");
                    mbar_arrive(note_bar + 8 * e);
                }
            }
            if (t < 0) break;
            const int reps = p2_reps(t);
#pragma unroll 1
            for (int rp = 0; rp < reps; rp++) {
            const bool first = rp == 0, last = rp == reps - 1;
            int z, mp, head;
            p2_tile(t, rp * 2 + wg, z, mp, head);
            asm volatile("bar.sync %0, 256;" :: "r"(3 + wg) : "memory");
            P2T(0);
            if (wg == 1 && last && elected) mbar_arrive_cl(mapa_u32(item_in + 8 * (ic & 1), 0));
            int sprev = 0;
#pragma unroll
            for (int k = 0; k < 8; k++) {
                if (k == 0) P2T(5);
                if (wg == 0 && first) mbar_wait(a_full + 8 * k, ic & 1);
                if (k == 0) P2T(6);
                mbar_wait(b_full + 8 * s, ph);
                if (k == 7) asm volatile("bar.arrive %0, 256;" :: "r"(4 - wg) : "memory");
                if (k == 0) P2T(1);
                if (k == 7) P2T(2);
                const uint32_t b_lo = b_lo0 + s * 1024;
                wgmma_fence();
#pragma unroll
                for (int kk = 0; kk < (P2_NOMMA ? 1 : 4); kk++) {
                    wgmma_ss_n128_lo<1>(acc[0], a_lo + p2_apos(k) * 1024 + kk * 2, b_lo + kk * 128, (k | kk) != 0);
                    wgmma_ss_n128_lo<1>(acc[1], a_lo + p2_apos(k) * 1024 + 512 + kk * 2, b_lo + kk * 128, (k | kk) != 0);
                }
                wgmma_commit();
                if (k > 0) {
                    wgmma_wait<1>();
                    if (elected) {
                        const uint32_t e = b_empty + 8 * sprev;
                        mbar_arrive_cl(mapa_u32(e, 0)); mbar_arrive_cl(mapa_u32(e, 1));
                        if (last) mbar_arrive(a_empty + 8 * (k - 1));
                    }
                }
                sprev = s;
                if (++s == P2_STAGES) { s = 0; ph ^= 1; }
            }
            wgmma_wait<0>();
            P2T(3);
            if (elected) {
                const uint32_t e = b_empty + 8 * sprev;
                mbar_arrive_cl(mapa_u32(e, 0)); mbar_arrive_cl(mapa_u32(e, 1));
                if (last) mbar_arrive(a_empty + 8 * 7);
            }
            s += 8 % P2_STAGES; ph ^= (8 / P2_STAGES) & 1;
            if (s >= P2_STAGES) { s -= P2_STAGES; ph ^= 1; }
            const int m0 = (2 * mp + (int)rank) * 128;
            bf16* obase = P.out[z] + ((size_t)head * SEQ + m0 + (warp & 3) * 16 + (lane >> 2)) * HD + (lane & 3) * 8;
            store_frag_128<true, P2_PACE>(acc[0], obase, lane); store_frag_128<true, P2_PACE>(acc[1], obase + (size_t)64 * HD, lane);
            P2T(4);
            {
                asm volatile("bar.sync %0, 128;" :: "r"(1 + wg) : "memory");
                if (elected) {
                    const int e = wg * 4 + (nnote & 3);
                    mbar_wait(note_free + 8 * e, ((nnote >> 2) & 1) ^ 1);
                    asm volatile("st.shared.s32 [%0], %1;" :: "r"(note + e * 4), "r"(CT_AP + (head >> 1)) : "memory");
                    mbar_arrive(note_bar + 8 * e);
                }
                nnote++;
            }
            }
        }
        auto done = [&]() {
            if ((threadIdx.x & 127) == 0) for (int i = 0; i < 4; i++) mbar_arrive_cl(SD + MO_BAR + 768 + OB_EMPTY + 16 + 8 * (i & 1) + ((i >> 1) << 24));
        };
        asm volatile("bar.sync %0, 128;" :: "r"(1 + wg) : "memory");
        const int nout = rank == 0 ? attn_consumer<SD>(MP.a, warp, done) : attn_consumer<SD + (1u << 24)>(MP.a, warp, done);
        OT(0);
        const uint32_t sb2 = (cluster_ctarank() << 24) + SD;
        out_consumer(MP.o, sb2, sb2 + MO_BAR + 768, warp, nout & 1);
    }
}

typedef CUresult (*PFN_encodeTiled)(CUtensorMap*, CUtensorMapDataType, cuuint32_t, void*, const cuuint64_t*,
                                    const cuuint64_t*, const cuuint32_t*, const cuuint32_t*, CUtensorMapInterleave,
                                    CUtensorMapSwizzle, CUtensorMapL2promotion, CUtensorMapFloatOOBfill);
static PFN_encodeTiled g_encode = nullptr;

static void make_map(CUtensorMap* m, const void* ptr, uint64_t rows, uint64_t cols, uint32_t box_rows, bool sw64 = false) {
    cuuint64_t dims[2] = {cols, rows};
    cuuint64_t strides[1] = {cols * 2};
    cuuint32_t box[2] = {sw64 ? 32u : 64u, box_rows};
    cuuint32_t es[2] = {1, 1};
    g_encode(m, CU_TENSOR_MAP_DATA_TYPE_BFLOAT16, 2, const_cast<void*>(ptr), dims, strides, box, es,
             CU_TENSOR_MAP_INTERLEAVE_NONE, sw64 ? CU_TENSOR_MAP_SWIZZLE_64B : CU_TENSOR_MAP_SWIZZLE_128B, CU_TENSOR_MAP_L2_PROMOTION_L2_256B,
             CU_TENSOR_MAP_FLOAT_OOB_FILL_NONE);
}

template <typename... KArgs, typename... Args>
static void launch_pdl(void (*kernel)(KArgs...), int grid, int block, size_t smem, cudaStream_t st, bool pdl, Args... args) {
    cudaLaunchConfig_t cfg = {};
    cfg.gridDim = dim3(grid); cfg.blockDim = dim3(block); cfg.dynamicSmemBytes = smem; cfg.stream = st;
    cudaLaunchAttribute at[1];
    at[0].id = cudaLaunchAttributeProgrammaticStreamSerialization;
    at[0].val.programmaticStreamSerializationAllowed = 1;
    cfg.attrs = at; cfg.numAttrs = pdl ? 1 : 0;
    cudaLaunchKernelEx(&cfg, kernel, KArgs(args)...);
}

extern "C" void kernel_launch(void* const* d_in, const int* in_sizes, int n_in, void* d_out, int out_size) {
    const bf16* x = (const bf16*)d_in[0];
    const bf16* ckv = (const bf16*)d_in[1];
    const bf16* wq = (const bf16*)d_in[2];
    const bf16* wuk = (const bf16*)d_in[3];
    const bf16* wuv = (const bf16*)d_in[4];
    const bf16* wo = (const bf16*)d_in[5];
    const bf16* mem0 = (const bf16*)d_in[7];
    const bf16* Wq = (const bf16*)d_in[8];
    const bf16* Wk = (const bf16*)d_in[9];
    const bf16* Wv = (const bf16*)d_in[10];
    const bf16* Wo = (const bf16*)d_in[11];
    const bf16* gate_w = (const bf16*)d_in[13];
    bf16* out = (bf16*)d_out;

    static MainParams MP;
    static ChainParams CP;
    Proj2Params& P2 = MP.p;
    AttnParams& AP = MP.a;
    OutParams& OP = MP.o;
    static bool init = false;
    static const void* last_in[14];
    static const void* last_out;
    bool same = init && last_out == d_out;
    for (int i = 0; i < 14 && same; i++) same = last_in[i] == d_in[i];
    if (!init) {
        cudaDriverEntryPointQueryResult qr;
        cudaGetDriverEntryPoint("cuTensorMapEncodeTiled", (void**)&g_encode, cudaEnableDefault, &qr);
        cudaFuncSetAttribute(main_kernel, cudaFuncAttributeMaxDynamicSharedMemorySize, M_SMEM);
        cudaFuncSetAttribute(chain_kernel, cudaFuncAttributeMaxDynamicSharedMemorySize, CH_SMEM);
        init = true;
    }
    if (!same) {
        for (int i = 0; i < 14; i++) last_in[i] = d_in[i];
        last_out = d_out;
        void *pQA, *pKA, *pVA, *pCA, *pCB;
        cudaGetSymbolAddress(&pQA, g_QA); cudaGetSymbolAddress(&pKA, g_KA); cudaGetSymbolAddress(&pVA, g_VA);
        cudaGetSymbolAddress(&pCA, g_ctxA); cudaGetSymbolAddress(&pCB, g_ctxB);
        make_map(&P2.mapA[0], x, SEQ, DM, 128);
        make_map(&P2.mapA[1], ckv, SEQ, DM, 128);
        const void* ws[3] = {wq, wuk, wuv};
        void* cs[3] = {pQA, pKA, pVA};
        for (int i = 0; i < 3; i++) { make_map(&P2.mapW[i], ws[i], DM, NQ, 64); P2.out[i] = (bf16*)cs[i]; }
        make_map(&CP.mapW[0], Wq, DM, NQ, 64); make_map(&CP.mapW[1], Wk, DM, NQ, 64); make_map(&CP.mapW[2], Wv, DM, NQ, 64);
        make_map(&CP.mapX, x, SEQ, DM, 32);
        make_map(&CP.mapWo, Wo, NQ, DM, 64);
        make_map(&CP.mapM, mem0, NMEM, DM, 8);
        MP.x = x; MP.gate_w = gate_w;
        make_map(&CP.mapC, pCB, NH * SEQ, HD, 32);
        make_map(&AP.mapQ, pQA, NH * SEQ, HD, 128);
        make_map(&AP.mapK, pKA, NH * SEQ, HD, 128);
        make_map(&AP.mapV, pVA, NH * SEQ, HD, 128);
        make_map(&AP.mapO, pCA, NH * SEQ, HD, 64);
        make_map(&OP.mapCtx[0], pCA, NH * SEQ, HD, 128);
        make_map(&OP.mapCtx[1], pCB, NH * SEQ, HD, 128);
        make_map(&OP.mapWo[0], wo, NQ, DM, 64);
        make_map(&OP.mapWo[1], Wo, NQ, DM, 64);
        make_map(&OP.mapOut, out, SEQ, DM, 64);
        CP.mapOut = OP.mapOut;
        AP.out = out;
    }
    cudaStream_t s1 = cudaStreamPerThread;
    const bool pdl = true;
    launch_pdl(chain_kernel, 64, CH_BLOCK, CH_SMEM, s1, false, CP);
    launch_pdl(main_kernel, M_GRID, 384, M_SMEM, s1, pdl, MP);
}
```

```cpp
#include <cuda_runtime.h>
#include <cuda_bf16.h>
#include <cuda.h>
#include <stdint.h>
#include <type_traits>

constexpr int SEQ = 2048;
constexpr int DM = 512;
constexpr int NH = 32;
constexpr int HD = 128;
constexpr int NQ = NH * HD;
constexpr int SEGL = 32;
constexpr int NMEM = 8;
constexpr int NSEG = SEQ / SEGL;

typedef __nv_bfloat16 bf16;

__device__ bf16 g_QA[SEQ * NQ];
__device__ bf16 g_KA[SEQ * NQ];
__device__ bf16 g_VA[SEQ * NQ];
__device__ bf16 g_ctxA[SEQ * NQ];
__device__ bf16 g_ctxB[SEQ * NQ];
constexpr int CT_PROJ = 0, CT_ATTN = 1, CT_FIN = 5;
constexpr int CT_AP = 64;
constexpr int CT_GATE = 96;
constexpr int CT_CA = 128;
constexpr int CT_CB = 193;
constexpr int CT_OT = 208;
constexpr int CT_N = 228;
__device__ __align__(16) unsigned int g_ctr[CT_N];
__device__ float g_gate[SEQ];
#define XB8(v) v, v, v, v, v, v, v, v
__device__ uint32_t g_xbuf[4 * 8 * 2048] = {XB8(XB8(XB8(XB8(XB8(~0u)))))};

#define FA_GRID 68

#define TS_BEGIN(id)
#define TS_END(id)
#define TS_BEGIN2(id, th)
#define TS_END2(id, th)
#define WAIT_LIMIT 200000
__device__ __forceinline__ void pdl_launch_dependents() { asm volatile("griddepcontrol.launch_dependents;" ::: "memory"); }
__device__ __forceinline__ void wait_ctr(int idx, unsigned int n) {
    unsigned int v; int it = 0;
    do { asm volatile("ld.acquire.gpu.global.u32 %0, [%1];" : "=r"(v) : "l"(&g_ctr[idx]) : "memory"); } while (v < n && ++it < WAIT_LIMIT);
    asm volatile("fence.proxy.async.shared::cta;" ::: "memory");
}
__device__ __forceinline__ int take_ticket(int idx) {
    int v;
    asm volatile("atom.relaxed.gpu.global.inc.u32 %0, [%1], 0x7fffffff;" : "=r"(v) : "l"(&g_ctr[idx]) : "memory");
    return v;
}
__device__ __forceinline__ void signal_ctr(int idx) {
    asm volatile("fence.proxy.async;" ::: "memory");
    __threadfence();
    atomicAdd(&g_ctr[idx], 1u);
}
__device__ __forceinline__ void signal_ctr_generic(int idx) {
    asm volatile("red.release.gpu.global.add.u32 [%0], 1;" :: "l"(&g_ctr[idx]) : "memory");
}
__device__ __forceinline__ uint32_t smem_u32(const void* p) {
    return (uint32_t)__cvta_generic_to_shared(p);
}
__device__ __forceinline__ void mbar_init(uint32_t bar, uint32_t count) {
    asm volatile("mbarrier.init.shared::cta.b64 [%0], %1;" :: "r"(bar), "r"(count));
}
__device__ __forceinline__ void mbar_expect_tx(uint32_t bar, uint32_t bytes) {
    asm volatile("mbarrier.arrive.expect_tx.shared::cta.b64 _, [%0], %1;" :: "r"(bar), "r"(bytes) : "memory");
}
__device__ __forceinline__ void mbar_arrive(uint32_t bar) {
    asm volatile("mbarrier.arrive.shared::cta.b64 _, [%0];" :: "r"(bar) : "memory");
}
__device__ __forceinline__ void mbar_wait(uint32_t bar, uint32_t parity) {
    asm volatile(
        "{\n"
        ".reg .pred p, q;\n"
        ".reg .u32 c;\n"
        "mov.u32 c, 0;\n"
        "WAIT_LOOP:\n"
        "mbarrier.try_wait.parity.shared::cta.b64 p, [%0], %1;\n"
        "@p bra WAIT_DONE;\n"
        "add.u32 c, c, 1;\n"
        "setp.lt.u32 q, c, %2;\n"
        "@q bra WAIT_LOOP;\n"
        "WAIT_DONE:\n"
        "}\n" :: "r"(bar), "r"(parity), "n"(WAIT_LIMIT) : "memory");
}
__device__ __forceinline__ uint32_t mbar_test(uint32_t bar, uint32_t parity) {
    uint32_t done;
    asm volatile(
        "{\n.reg .pred p;\n"
        "mbarrier.test_wait.parity.shared::cta.b64 p, [%1], %2;\n"
        "selp.u32 %0, 1, 0, p;\n}\n" : "=r"(done) : "r"(bar), "r"(parity) : "memory");
    return done;
}
__device__ __forceinline__ uint32_t mbar_try(uint32_t bar, uint32_t parity) {
    uint32_t done;
    asm volatile(
        "{\n.reg .pred p;\n"
        "mbarrier.try_wait.parity.shared::cta.b64 p, [%1], %2;\n"
        "selp.u32 %0, 1, 0, p;\n}\n" : "=r"(done) : "r"(bar), "r"(parity) : "memory");
    return done;
}
__device__ __forceinline__ void tma_load_2d(uint32_t dst, const CUtensorMap* map, uint32_t bar, int c0, int c1) {
    asm volatile(
        "cp.async.bulk.tensor.2d.shared::cluster.global.mbarrier::complete_tx::bytes [%0], [%1, {%3, %4}], [%2];"
        :: "r"(dst), "l"((uint64_t)map), "r"(bar), "r"(c0), "r"(c1) : "memory");
}
__device__ __forceinline__ void wgmma_fence() { asm volatile("wgmma.fence.sync.aligned;" ::: "memory"); }
__device__ __forceinline__ void wgmma_commit() { asm volatile("wgmma.commit_group.sync.aligned;" ::: "memory"); }
template <int N> __device__ __forceinline__ void wgmma_wait() {
    asm volatile("wgmma.wait_group.sync.aligned %0;" :: "n"(N) : "memory");
}
__device__ __forceinline__ uint64_t make_desc(uint32_t addr, uint32_t lbo, uint32_t sbo) {
    uint64_t d = 0;
    d |= (uint64_t)((addr & 0x3FFFF) >> 4);
    d |= (uint64_t)((lbo >> 4) & 0x3FFF) << 16;
    d |= (uint64_t)((sbo >> 4) & 0x3FFF) << 32;
    d |= (uint64_t)1 << 62;
    return d;
}

#define ACC64(d) \
    "+f"(d[0]), "+f"(d[1]), "+f"(d[2]), "+f"(d[3]), "+f"(d[4]), "+f"(d[5]), "+f"(d[6]), "+f"(d[7]), \
    "+f"(d[8]), "+f"(d[9]), "+f"(d[10]), "+f"(d[11]), "+f"(d[12]), "+f"(d[13]), "+f"(d[14]), "+f"(d[15]), \
    "+f"(d[16]), "+f"(d[17]), "+f"(d[18]), "+f"(d[19]), "+f"(d[20]), "+f"(d[21]), "+f"(d[22]), "+f"(d[23]), \
    "+f"(d[24]), "+f"(d[25]), "+f"(d[26]), "+f"(d[27]), "+f"(d[28]), "+f"(d[29]), "+f"(d[30]), "+f"(d[31]), \
    "+f"(d[32]), "+f"(d[33]), "+f"(d[34]), "+f"(d[35]), "+f"(d[36]), "+f"(d[37]), "+f"(d[38]), "+f"(d[39]), \
    "+f"(d[40]), "+f"(d[41]), "+f"(d[42]), "+f"(d[43]), "+f"(d[44]), "+f"(d[45]), "+f"(d[46]), "+f"(d[47]), \
    "+f"(d[48]), "+f"(d[49]), "+f"(d[50]), "+f"(d[51]), "+f"(d[52]), "+f"(d[53]), "+f"(d[54]), "+f"(d[55]), \
    "+f"(d[56]), "+f"(d[57]), "+f"(d[58]), "+f"(d[59]), "+f"(d[60]), "+f"(d[61]), "+f"(d[62]), "+f"(d[63])
#define ACC64_STR \
    "{%0, %1, %2, %3, %4, %5, %6, %7, %8, %9, %10, %11, %12, %13, %14, %15, " \
    "%16, %17, %18, %19, %20, %21, %22, %23, %24, %25, %26, %27, %28, %29, %30, %31, " \
    "%32, %33, %34, %35, %36, %37, %38, %39, %40, %41, %42, %43, %44, %45, %46, %47, " \
    "%48, %49, %50, %51, %52, %53, %54, %55, %56, %57, %58, %59, %60, %61, %62, %63}"

template <int TB>
__device__ __forceinline__ void wgmma_ss_n128(float (&d)[64], uint64_t da, uint64_t db, int scale_d) {
    asm volatile(
        "{\n.reg .pred p;\nsetp.ne.b32 p, %66, 0;\n"
        "wgmma.mma_async.sync.aligned.m64n128k16.f32.bf16.bf16 " ACC64_STR ", %64, %65, p, 1, 1, 0, %67;\n}\n"
        : ACC64(d) : "l"(da), "l"(db), "r"(scale_d), "n"(TB));
}
__device__ __forceinline__ uint32_t desc_lo(uint32_t addr, uint32_t lbo) { return ((addr & 0x3FFFF) >> 4) | ((lbo >> 4) << 16); }
template <int TB>
__device__ __forceinline__ void wgmma_ss_n128_lo(float (&d)[64], uint32_t da_lo, uint32_t db_lo, int scale_d) {
    asm volatile(
        "{\n.reg .pred p;\n.reg .b64 da, db;\nsetp.ne.b32 p, %66, 0;\n"
        "mov.b64 da, {%64, 0x40000040};\nmov.b64 db, {%65, 0x40000040};\n"
        "wgmma.mma_async.sync.aligned.m64n128k16.f32.bf16.bf16 " ACC64_STR ", da, db, p, 1, 1, 0, %67;\n}\n"
        : ACC64(d) : "r"(da_lo), "r"(db_lo), "r"(scale_d), "n"(TB));
}
__device__ __forceinline__ void wgmma_rs_n128_tb(float (&d)[64], uint32_t a0, uint32_t a1, uint32_t a2, uint32_t a3,
                                                 uint64_t db, int scale_d) {
    asm volatile(
        "{\n.reg .pred p;\nsetp.ne.b32 p, %69, 0;\n"
        "wgmma.mma_async.sync.aligned.m64n128k16.f32.bf16.bf16 " ACC64_STR ", {%64, %65, %66, %67}, %68, p, 1, 1, 1;\n}\n"
        : ACC64(d) : "r"(a0), "r"(a1), "r"(a2), "r"(a3), "l"(db), "r"(scale_d));
}
__device__ __forceinline__ void wgmma_rs_n80(float (&d)[40], const uint32_t (&a)[4], uint32_t db_lo, int scale_d) {
    asm volatile(
        "{\n.reg .pred p;\n.reg .b64 db;\nsetp.ne.b32 p, %45, 0;\nmov.b64 db, {%44, 0x40000040};\n"
        "wgmma.mma_async.sync.aligned.m64n80k16.f32.bf16.bf16 "
        "{%0, %1, %2, %3, %4, %5, %6, %7, %8, %9, %10, %11, %12, %13, %14, %15, %16, %17, %18, %19, %20, %21, %22, %23, %24, %25, %26, %27, %28, %29, %30, %31, %32, %33, %34, %35, %36, %37, %38, %39}, "
        "{%40, %41, %42, %43}, db, p, 1, 1, 0;\n}\n"
        : "+f"(d[0]), "+f"(d[1]), "+f"(d[2]), "+f"(d[3]), "+f"(d[4]), "+f"(d[5]), "+f"(d[6]), "+f"(d[7]), "+f"(d[8]), "+f"(d[9]), "+f"(d[10]), "+f"(d[11]), "+f"(d[12]), "+f"(d[13]), "+f"(d[14]), "+f"(d[15]), "+f"(d[16]), "+f"(d[17]), "+f"(d[18]), "+f"(d[19]), "+f"(d[20]), "+f"(d[21]), "+f"(d[22]), "+f"(d[23]), "+f"(d[24]), "+f"(d[25]), "+f"(d[26]), "+f"(d[27]), "+f"(d[28]), "+f"(d[29]), "+f"(d[30]), "+f"(d[31]), "+f"(d[32]), "+f"(d[33]), "+f"(d[34]), "+f"(d[35]), "+f"(d[36]), "+f"(d[37]), "+f"(d[38]), "+f"(d[39])
        : "r"(a[0]), "r"(a[1]), "r"(a[2]), "r"(a[3]), "r"(db_lo), "r"(scale_d));
}
__device__ __forceinline__ void wgmma_ss_n256_tb(float (&d)[128], uint64_t da, uint64_t db, int scale_d) {
    asm volatile(
        "{\n.reg .pred p;\nsetp.ne.b32 p, %130, 0;\n"
        "wgmma.mma_async.sync.aligned.m64n256k16.f32.bf16.bf16 {%0, %1, %2, %3, %4, %5, %6, %7, %8, %9, %10, %11, %12, %13, %14, %15, %16, %17, %18, %19, %20, %21, %22, %23, %24, %25, %26, %27, %28, %29, %30, %31, %32, %33, %34, %35, %36, %37, %38, %39, %40, %41, %42, %43, %44, %45, %46, %47, %48, %49, %50, %51, %52, %53, %54, %55, %56, %57, %58, %59, %60, %61, %62, %63, %64, %65, %66, %67, %68, %69, %70, %71, %72, %73, %74, %75, %76, %77, %78, %79, %80, %81, %82, %83, %84, %85, %86, %87, %88, %89, %90, %91, %92, %93, %94, %95, %96, %97, %98, %99, %100, %101, %102, %103, %104, %105, %106, %107, %108, %109, %110, %111, %112, %113, %114, %115, %116, %117, %118, %119, %120, %121, %122, %123, %124, %125, %126, %127}, %128, %129, p, 1, 1, 0, 1;\n}\n"
        : "+f"(d[0]), "+f"(d[1]), "+f"(d[2]), "+f"(d[3]), "+f"(d[4]), "+f"(d[5]), "+f"(d[6]), "+f"(d[7]), "+f"(d[8]), "+f"(d[9]), "+f"(d[10]), "+f"(d[11]), "+f"(d[12]), "+f"(d[13]), "+f"(d[14]), "+f"(d[15]), "+f"(d[16]), "+f"(d[17]), "+f"(d[18]), "+f"(d[19]), "+f"(d[20]), "+f"(d[21]), "+f"(d[22]), "+f"(d[23]), "+f"(d[24]), "+f"(d[25]), "+f"(d[26]), "+f"(d[27]), "+f"(d[28]), "+f"(d[29]), "+f"(d[30]), "+f"(d[31]), "+f"(d[32]), "+f"(d[33]), "+f"(d[34]), "+f"(d[35]), "+f"(d[36]), "+f"(d[37]), "+f"(d[38]), "+f"(d[39]), "+f"(d[40]), "+f"(d[41]), "+f"(d[42]), "+f"(d[43]), "+f"(d[44]), "+f"(d[45]), "+f"(d[46]), "+f"(d[47]), "+f"(d[48]), "+f"(d[49]), "+f"(d[50]), "+f"(d[51]), "+f"(d[52]), "+f"(d[53]), "+f"(d[54]), "+f"(d[55]), "+f"(d[56]), "+f"(d[57]), "+f"(d[58]), "+f"(d[59]), "+f"(d[60]), "+f"(d[61]), "+f"(d[62]), "+f"(d[63]), "+f"(d[64]), "+f"(d[65]), "+f"(d[66]), "+f"(d[67]), "+f"(d[68]), "+f"(d[69]), "+f"(d[70]), "+f"(d[71]), "+f"(d[72]), "+f"(d[73]), "+f"(d[74]), "+f"(d[75]), "+f"(d[76]), "+f"(d[77]), "+f"(d[78]), "+f"(d[79]), "+f"(d[80]), "+f"(d[81]), "+f"(d[82]), "+f"(d[83]), "+f"(d[84]), "+f"(d[85]), "+f"(d[86]), "+f"(d[87]), "+f"(d[88]), "+f"(d[89]), "+f"(d[90]), "+f"(d[91]), "+f"(d[92]), "+f"(d[93]), "+f"(d[94]), "+f"(d[95]), "+f"(d[96]), "+f"(d[97]), "+f"(d[98]), "+f"(d[99]), "+f"(d[100]), "+f"(d[101]), "+f"(d[102]), "+f"(d[103]), "+f"(d[104]), "+f"(d[105]), "+f"(d[106]), "+f"(d[107]), "+f"(d[108]), "+f"(d[109]), "+f"(d[110]), "+f"(d[111]), "+f"(d[112]), "+f"(d[113]), "+f"(d[114]), "+f"(d[115]), "+f"(d[116]), "+f"(d[117]), "+f"(d[118]), "+f"(d[119]), "+f"(d[120]), "+f"(d[121]), "+f"(d[122]), "+f"(d[123]), "+f"(d[124]), "+f"(d[125]), "+f"(d[126]), "+f"(d[127])
        : "l"(da), "l"(db), "r"(scale_d));
}
__device__ __forceinline__ void stmatrix_x4(uint32_t addr, uint32_t r0, uint32_t r1, uint32_t r2, uint32_t r3) {
    asm volatile("stmatrix.sync.aligned.m8n8.x4.shared.b16 [%0], {%1, %2, %3, %4};" :: "r"(addr), "r"(r0), "r"(r1), "r"(r2), "r"(r3) : "memory");
}
__device__ __forceinline__ void tma_store_2d(const CUtensorMap* map, uint32_t src, int c0, int c1) {
    asm volatile("cp.async.bulk.tensor.2d.global.shared::cta.bulk_group [%0, {%2, %3}], [%1];"
                 :: "l"((uint64_t)map), "r"(src), "r"(c0), "r"(c1) : "memory");
}
__device__ __forceinline__ float ex2f(float x) { float y; asm("ex2.approx.ftz.f32 %0, %1;" : "=f"(y) : "f"(x)); return y; }
__device__ __forceinline__ uint32_t pack_bf16(float lo, float hi) {
    __nv_bfloat162 v = __floats2bfloat162_rn(lo, hi);
    return *reinterpret_cast<uint32_t*>(&v);
}
__device__ __forceinline__ void mma_16816(float (&c)[4], uint32_t a0, uint32_t a1, uint32_t a2, uint32_t a3,
                                          uint32_t b0, uint32_t b1) {
    asm volatile(
        "mma.sync.aligned.m16n8k16.row.col.f32.bf16.bf16.f32 {%0,%1,%2,%3}, {%4,%5,%6,%7}, {%8,%9}, {%0,%1,%2,%3};"
        : "+f"(c[0]), "+f"(c[1]), "+f"(c[2]), "+f"(c[3])
        : "r"(a0), "r"(a1), "r"(a2), "r"(a3), "r"(b0), "r"(b1));
}
__device__ __forceinline__ void ldmatrix_x4_trans(uint32_t& r0, uint32_t& r1, uint32_t& r2, uint32_t& r3, uint32_t addr) {
    asm volatile("ldmatrix.sync.aligned.m8n8.x4.trans.shared.b16 {%0,%1,%2,%3}, [%4];"
                 : "=r"(r0), "=r"(r1), "=r"(r2), "=r"(r3) : "r"(addr));
}

struct AttnParams {
    CUtensorMap mapQ, mapK, mapV;
    CUtensorMap mapO;
    bf16* out;
};
constexpr int FA_ITEMS = 16 * NH;
__device__ __forceinline__ int fa_qt(int t) { return 15 - ((t & 127) >> 3); }
__device__ __forceinline__ int fa_head(int t) { return (t >> 7) * 8 + (t & 7); }
#define FA_TKA 2
#define FA_SPLIT 11

#define FA_P0 4
#define FA_HO 7
#define FA_LAG 2
#define FA_PK 3
#define FA_ST 4
#define FA_TG 16
#define FA_EARLY 0
#define FA_I0 0
static_assert(FA_GRID <= 104 && FA_HO >= FA_P0 && FA_P0 >= 1, "");
constexpr float FA_MARGIN = 16.f;
#define FAT(b, i)
__device__ __forceinline__ void mbar_arrive_if(uint32_t bar, bool c) {
    asm volatile("{\n.reg .pred p;\nsetp.ne.b32 p, %1, 0;\n@p mbarrier.arrive.shared::cta.b64 _, [%0];\n}" :: "r"(bar), "r"((int)c) : "memory");
}
__device__ __forceinline__ void sched_fence(int v, int id, const float* a, const float* b, const float* c) {
    asm volatile("{\n.reg .pred p;\nsetp.ne.s32 p, %0, %1;\n@p bra SF_SKIP;\nwgmma.wait_group.sync.aligned 0;\n"
                 "st.volatile.shared.f32 [%0], %2;\nst.volatile.shared.f32 [%0], %3;\nst.volatile.shared.f32 [%0], %4;\nst.volatile.shared.f32 [%0], %5;\n"
                 "st.volatile.shared.f32 [%0], %6;\nst.volatile.shared.f32 [%0], %7;\nst.volatile.shared.f32 [%0], %8;\nst.volatile.shared.f32 [%0], %9;\n"
                 "st.volatile.shared.f32 [%0], %10;\nst.volatile.shared.f32 [%0], %11;\nst.volatile.shared.f32 [%0], %12;\nst.volatile.shared.f32 [%0], %13;\n"
                 "exit;\nSF_SKIP:\n}" :: "r"(v), "r"(1000000 + id), "f"(a[0]), "f"(a[1]), "f"(a[2]), "f"(a[3]), "f"(b[0]), "f"(b[1]), "f"(b[2]), "f"(b[3]),
                 "f"(c[0]), "f"(c[1]), "f"(c[2]), "f"(c[3]) : "memory");
}
__device__ __forceinline__ float ex2v(float x) { float y; asm volatile("ex2.approx.ftz.f32 %0, %1;" : "=f"(y) : "f"(x)); return y; }
__device__ __forceinline__ void wgmma_rs_n128_tb_lo(float (&d)[64], const uint32_t* a, uint32_t db_lo, int scale_d) {
    asm volatile(
        "{\n.reg .pred p;\n.reg .b64 db;\nsetp.ne.b32 p, %69, 0;\nmov.b64 db, {%68, 0x40000040};\n"
        "wgmma.mma_async.sync.aligned.m64n128k16.f32.bf16.bf16 " ACC64_STR ", {%64, %65, %66, %67}, db, p, 1, 1, 1;\n}\n"
        : ACC64(d) : "r"(a[0]), "r"(a[1]), "r"(a[2]), "r"(a[3]), "r"(db_lo), "r"(scale_d));
}

constexpr int M_GRID = 68;
constexpr uint32_t SD = 1024;
constexpr uint32_t MO_BAR = 229376;
constexpr int M_SMEM = MO_BAR + 1024;
constexpr uint32_t FO_Q = 0, FO_KV = 65536, FO_O = FO_KV + 2 * 65536, FO_BAR = MO_BAR + 512;
constexpr uint32_t FB_QF = FO_BAR, FB_QE = FO_BAR + 16, FB_KF = FO_BAR + 32, FB_VF = FO_BAR + 48, FB_KE = FO_BAR + 64, FB_VE = FO_BAR + 80,
                   FB_OF = FO_BAR + 96, FB_OE = FO_BAR + 112, FB_SLOT = FO_BAR + 128, FB_OSLOT = FO_BAR + 136;
__device__ __forceinline__ void attn_init(uint32_t sb) {
    for (int i = 0; i < 2; i++) {
        mbar_init(sb + FB_QF + 8 * i, 1); mbar_init(sb + FB_QE + 8 * i, 8); mbar_init(sb + FB_KF + 8 * i, 1); mbar_init(sb + FB_VF + 8 * i, 1);
        mbar_init(sb + FB_KE + 8 * i, 8); mbar_init(sb + FB_VE + 8 * i, 8); mbar_init(sb + FB_OF + 8 * i, 4); mbar_init(sb + FB_OE + 8 * i, 1);
    }
}
__device__ __forceinline__ void attn_helper(const AttnParams& P, uint32_t sb, int wg) {
    const uint32_t stg = sb + FO_O + wg * 16384;
    for (int n = 0;; n++) {
        mbar_wait(sb + FB_OF + 8 * wg, n & 1);
        int t;
        asm volatile("ld.shared.s32 %0, [%1];" : "=r"(t) : "r"(sb + FB_OSLOT + wg * 4) : "memory");
        const int qt = fa_qt(t), h = fa_head(t & 1023);
        tma_store_2d(&P.mapO, stg, 0, h * SEQ + qt * 128 + wg * 64);
        tma_store_2d(&P.mapO, stg + 8192, 64, h * SEQ + qt * 128 + wg * 64);
        asm volatile("cp.async.bulk.commit_group;" ::: "memory");
        asm volatile("cp.async.bulk.wait_group.read 0;" ::: "memory");
        mbar_arrive(sb + FB_OE + 8 * wg);
        asm volatile("cp.async.bulk.wait_group 0;" ::: "memory");
        signal_ctr(CT_CA + qt * 4 + (h >> 3));
        if (t >= 1024) break;
    }
}
__device__ __forceinline__ void attn_producer(const AttnParams& P, uint32_t sb, uint32_t free_bar, uint32_t free_par) {
    const uint32_t sQ = sb + FO_Q, sKV = sb + FO_KV;
    int b = 0, hp_ready = 0, vrow = 0, t = blockIdx.x, item = 0;
    auto load_v = [&](int i) {
        const uint32_t sv = sKV + (i & 1) * 65536 + 32768, bar = sb + FB_VF + 8 * (i & 1);
        mbar_wait(sb + FB_VE + 8 * (i & 1), ((i >> 1) & 1) ^ 1);
        mbar_expect_tx(bar, 32768);
        tma_load_2d(sv, &P.mapV, bar, 0, vrow);
        tma_load_2d(sv + 16384, &P.mapV, bar, 64, vrow);
    };
    for (;; item++) {
        const bool valid = t < FA_ITEMS;
        const int qt = fa_qt(t), h = fa_head(t);
        if (valid && !((hp_ready >> (h >> 1)) & 1)) { wait_ctr(CT_AP + (h >> 1), 96u); hp_ready |= 1 << (h >> 1); }
        const uint32_t bq = sb + FB_QF + 8 * (item & 1);
        mbar_wait(item ? sb + FB_QE + 8 * (item & 1) : free_bar + 8, item ? ((item >> 1) & 1) ^ 1 : free_par);
        asm volatile("st.shared.s32 [%0], %1;" :: "r"(sb + FB_SLOT + (item & 1) * 4), "r"(valid ? t : -1) : "memory");
        if (!valid) { mbar_arrive(bq); break; }
        mbar_expect_tx(bq, 32768);
        tma_load_2d(sQ + (item & 1) * 32768, &P.mapQ, bq, 0, h * SEQ + qt * 128);
        tma_load_2d(sQ + (item & 1) * 32768 + 16384, &P.mapQ, bq, 64, h * SEQ + qt * 128);
#pragma unroll 1
        for (int j = 0; j <= qt; j++, b++) {
            const uint32_t sk = sKV + (b & 1) * 65536, bar = sb + FB_KF + 8 * (b & 1);
            mbar_wait(b >= 2 ? sb + FB_KE + 8 * (b & 1) : free_bar + 24 + 32 * b, b >= 2 ? ((b >> 1) & 1) ^ 1 : free_par);
            if (b == 1) { TS_END2(0, 256); TS_BEGIN2(1, 256); }
            if (b == 2) wait_ctr(CT_GATE, 256u);
            mbar_expect_tx(bar, 32768);
            tma_load_2d(sk, &P.mapK, bar, 0, h * SEQ + j * 128);
            tma_load_2d(sk + 16384, &P.mapK, bar, 64, h * SEQ + j * 128);
            if (j == max(qt - FA_TKA, 0)) t = take_ticket(CT_ATTN);
            if (b > 0) load_v(b - 1);
            vrow = h * SEQ + j * 128;
        }
        t += M_GRID;
    }
    load_v(b - 1);
    mbar_wait(sb + FB_KE + 8 * (~b & 1), ((b - 1) >> 1) & 1);
}
template <uint32_t sb, typename F>
__device__ __forceinline__ int attn_consumer(const AttnParams& P, int warp, F done) {
    constexpr uint32_t sQ = SD + FO_Q, sKV = SD + FO_KV;
    constexpr uint32_t sO = sb + FO_O;
    constexpr uint32_t bar_qf = sb + FB_QF, bar_qe = sb + FB_QE, bar_kf = sb + FB_KF, bar_vf = sb + FB_VF, bar_ke = sb + FB_KE, bar_ve = sb + FB_VE,
                   bar_of = sb + FB_OF, bar_oe = sb + FB_OE, slot = sb + FB_SLOT, oslot = sb + FB_OSLOT;
    {
        const int wg = warp >> 2;
        const int lane = threadIdx.x & 31;
        const float sc = 0.08838834764831845f * 1.4426950408889634f;
        const int r0 = wg * 64 + (warp & 3) * 16 + (lane >> 2);
        float o[64], s[64];
        uint32_t pa[32];
        float m0 = 0.f, m1 = 0.f, l0 = 0.f, l1 = 0.f, i0 = 0.f, i1 = 0.f, g0 = 0.f, g1 = 0.f;
        const uint32_t q_lo = desc_lo(sQ + wg * 8192, 16), k_lo = desc_lo(sKV, 16), v_lo = desc_lo(sKV + 32768, 16384);
        auto issue_qk = [&](int b, int item) {
            const uint32_t qd = q_lo + (item & 1) * 2048, kd = k_lo + (b & 1) * 4096;
            wgmma_fence();
#pragma unroll
            for (int kk = 0; kk < 8; kk++) wgmma_ss_n128_lo<0>(s, qd + (kk >> 2) * 1024 + (kk & 3) * 2, kd + (kk >> 2) * 1024 + (kk & 3) * 2, kk != 0);
            wgmma_commit();
        };
        auto issue_pv = [&](int b, bool acc, int n) {
            const uint32_t vd = v_lo + (b & 1) * 4096;
            mbar_wait(bar_vf + 8 * (b & 1), (b >> 1) & 1);
            wgmma_fence();
#pragma unroll
            for (int kk = 0; kk < 8; kk++) if (kk < n) wgmma_rs_n128_tb_lo(o, &pa[kk * 4], vd + kk * 128, kk ? 1 : (int)acc);
            wgmma_commit();
        };
        const int lim = r0 - (lane & 3) * 2;
        int item = -1, tnext = 0;
        uint32_t k_ready = 0, q_ready = 0;
        auto mask = [&](int i) { if ((i >> 2) * 8 + (i & 1) - ((i & 2) ? 8 : 0) > lim) s[i] = -INFINITY; };
        auto exps = [&](auto mode, int b, bool hand_over, float& u0, float& u1) {
            constexpr int MODE = decltype(mode)::value;
            float p[64], u[4] = {0.f, 0.f, 0.f, 0.f};
            const uint32_t vd = v_lo + ((b - 1) & 1) * 4096;
#pragma unroll
            for (int i = 0; i < 4; i++) p[i] = fmaf(s[i], sc, (i & 2) ? -m1 : -m0);
#pragma unroll
            for (int g = 0; g < 16 + FA_LAG; g++) {
                if (MODE && g >= FA_I0 && g - FA_I0 < 8 - FA_P0) {
                    const int kk = FA_P0 + g - FA_I0;
                    wgmma_fence();
                    wgmma_rs_n128_tb_lo(o, &pa[kk * 4], vd + kk * 128, 1);
                    wgmma_commit();
                    if (kk == FA_HO) asm volatile("{\n.reg .pred p;\nsetp.ne.b32 p, %1, 0;\n@p bar.arrive %0, 256;\n}" :: "r"(4 - wg), "r"((int)hand_over) : "memory");
                }
                if (MODE && g == FA_SPLIT) {
                    FAT(b, 2);
                    wgmma_wait<0>();
                    FAT(b - 1, 3);
                    mbar_arrive_if(bar_ve + 8 * ((b - 1) & 1), lane == 0);
                }
                if (MODE && g == FA_TG) {
                    k_ready = mbar_test(bar_kf + 8 * (~b & 1), ((b + 1) >> 1) & 1);
                    if (MODE == 2) {
                        q_ready = mbar_test(bar_qf + 8 * (~item & 1), ((item + 1) >> 1) & 1);
                        asm volatile("ld.shared.s32 %0, [%1];" : "=r"(tnext) : "r"(slot + (~item & 1) * 4) : "memory");
                    }
                }
#pragma unroll
                for (int j = 0; j < 4; j++) {
                    const int i = g * 4 + j;
                    if (g < 16) p[i] = ex2v(p[i]);
                    if (g < 15) {
                        if (MODE == 2) mask(i + 4);
                        p[i + 4] = fmaf(s[i + 4], sc, (i & 2) ? -m1 : -m0);
                    }
                    if (g >= FA_LAG) u[j] += p[i - FA_LAG * 4];
                }
#pragma unroll
                for (int gg = 0; gg < 16; gg++) {
                    const int at = MODE && gg + FA_LAG < FA_SPLIT + gg / FA_PK ? FA_SPLIT + gg / FA_PK : gg + FA_LAG;
                    if (at == g) { pa[gg * 2] = pack_bf16(p[gg * 4], p[gg * 4 + 1]); pa[gg * 2 + 1] = pack_bf16(p[gg * 4 + 2], p[gg * 4 + 3]); }
                }
                if (MODE && g < 16) sched_fence(b, g + MODE * 32, &p[g * 4], &p[(g < 15 ? g + 1 : g) * 4], u);
            }
            u0 = u[0] + u[1]; u1 = u[2] + u[3];
        };
        auto quad_max = [&](float& x0, float& x1) {
            x0 = fmaxf(x0, __shfl_xor_sync(0xffffffff, x0, 1)); x1 = fmaxf(x1, __shfl_xor_sync(0xffffffff, x1, 1));
            x0 = fmaxf(x0, __shfl_xor_sync(0xffffffff, x0, 2)); x1 = fmaxf(x1, __shfl_xor_sync(0xffffffff, x1, 2));
            x0 = fmaf(x0, sc, FA_MARGIN); x1 = fmaf(x1, sc, FA_MARGIN);
        };
        auto softmax_exact = [&](bool fresh, int b) {
            wgmma_wait<0>();
            float x[8];
#pragma unroll
            for (int i = 0; i < 8; i++) x[i] = fmaxf(s[i * 2], s[i * 2 + 1]);
#pragma unroll
            for (int i = 8; i < 32; i++) x[i & 7] = fmaxf(x[i & 7], fmaxf(s[i * 2], s[i * 2 + 1]));
            float x0 = fmaxf(fmaxf(x[0], x[2]), fmaxf(x[4], x[6])), x1 = fmaxf(fmaxf(x[1], x[3]), fmaxf(x[5], x[7]));
            quad_max(x0, x1);
            if (!fresh) {
                x0 = fmaxf(x0, m0); x1 = fmaxf(x1, m1);
                const float a0 = ex2f(m0 - x0), a1 = ex2f(m1 - x1);
                l0 *= a0; l1 *= a1;
#pragma unroll
                for (int i = 0; i < 16; i++) { o[i * 4 + 0] *= a0; o[i * 4 + 1] *= a0; o[i * 4 + 2] *= a1; o[i * 4 + 3] *= a1; }
            }
            m0 = x0; m1 = x1;
            float u0, u1;
            exps(std::integral_constant<int, 0>(), b, false, u0, u1);
            l0 += u0; l1 += u1;
        };
        auto finish_rows = [&]() {
            l0 += __shfl_xor_sync(0xffffffff, l0, 1); l1 += __shfl_xor_sync(0xffffffff, l1, 1);
            l0 += __shfl_xor_sync(0xffffffff, l0, 2); l1 += __shfl_xor_sync(0xffffffff, l1, 2);
            i0 = __fdividef(g0, l0); i1 = __fdividef(g1, l1);
        };
        auto clear_out = [&](int t) {
            if (t >= 384) {
                bf16* z = P.out + (size_t)(fa_qt(t) * 128 + wg * 64 + ((threadIdx.x & 127) >> 3)) * DM + (t & 7) * 64 + (lane & 7) * 8;
#pragma unroll
                for (int i = 0; i < 4; i++) *reinterpret_cast<uint4*>(z + i * 16 * DM) = make_uint4(0u, 0u, 0u, 0u);
            }
        };
        auto store_o = [&](int t, int n, int c0, int c1) {
            const uint32_t stg = sO + wg * 16384;
            if (c0 == 0) {
                mbar_wait(bar_oe + 8 * wg, (n & 1) ^ 1);
                asm volatile("st.shared.s32 [%0], %1;" :: "r"(oslot + wg * 4), "r"(t) : "memory");
            }
            const int row = (warp & 3) * 16 + (lane >> 2);
#pragma unroll
            for (int i = c0; i < c1; i++) {
                const int ch = i * 4 + (lane & 3);
                const uint32_t a = stg + (ch >> 3) * 8192 + row * 128 + (((ch & 7) ^ (row & 7)) << 4);
                const float* q = &o[i * 16];
                asm volatile("st.shared.v4.b32 [%0], {%1, %2, %3, %4};" :: "r"(a), "r"(pack_bf16(q[0] * i0, q[1] * i0)), "r"(pack_bf16(q[4] * i0, q[5] * i0)),
                             "r"(pack_bf16(q[8] * i0, q[9] * i0)), "r"(pack_bf16(q[12] * i0, q[13] * i0)) : "memory");
                asm volatile("st.shared.v4.b32 [%0], {%1, %2, %3, %4};" :: "r"(a + 1024), "r"(pack_bf16(q[2] * i1, q[3] * i1)), "r"(pack_bf16(q[6] * i1, q[7] * i1)),
                             "r"(pack_bf16(q[10] * i1, q[11] * i1)), "r"(pack_bf16(q[14] * i1, q[15] * i1)) : "memory");
            }
        };
        auto publish_o = [&]() {
            asm volatile("fence.proxy.async.shared::cta;" ::: "memory");
            __syncwarp();
            mbar_arrive_if(bar_of + 8 * wg, lane == 0);
        };
        int t = 0, left = 0, tdone = -1, b = 0, nout = 0;
        bool first = true, staged = false;
#pragma unroll 1
        for (;; b++) {
            const bool fresh = left == 0;
            const int tprev = t;
            FAT(b, 4);
            if (staged) { publish_o(); staged = false; }
            if (fresh) {
                item++;
                if (!q_ready) {
                    mbar_wait(bar_qf + 8 * (item & 1), (item >> 1) & 1);
                    asm volatile("ld.shared.s32 %0, [%1];" : "=r"(tnext) : "r"(slot + (item & 1) * 4) : "memory");
                }
                if (tnext < 0) break;
                t = tnext;
                left = fa_qt(t) + 1;
            }
            left--;
            if (tdone >= 0) store_o(tdone, nout, 0, FA_ST);
            FAT(b, 5);
            if (!k_ready) mbar_wait(bar_kf + 8 * (b & 1), (b >> 1) & 1);
            FAT(b, 6);
            asm volatile("bar.sync %0, 256;" :: "r"(3 + wg) : "memory");
            FAT(b, 0);
            issue_qk(b, item);
            bool early = false;
            if (!fresh && !first && left != 0) {
                issue_pv(b - 1, true, FA_P0);
                wgmma_wait<1>();
                FAT(b, 1);
                mbar_arrive_if(bar_ke + 8 * (b & 1), lane == 0);
            } else {
                early = (FA_EARLY && tdone >= 0) || b == 0;
                if (early) asm volatile("bar.arrive %0, 256;" :: "r"(4 - wg) : "memory");
                if (tdone >= 0) { wgmma_wait<1>(); store_o(tdone, nout++, FA_ST, 4); staged = true; }
                tdone = -1;
                if (fresh && b > 0) { finish_rows(); tdone = tprev; l0 = l1 = 0.f; }
                if (left == 0) { g0 = __ldcg(g_gate + fa_qt(t) * 128 + r0); g1 = __ldcg(g_gate + fa_qt(t) * 128 + r0 + 8); clear_out(t); }
                if (b > 0) issue_pv(b - 1, !first, FA_P0); else { wgmma_fence(); wgmma_commit(); }
                first = fresh;
                wgmma_wait<1>();
                FAT(b, 1);
                mbar_arrive_if(bar_ke + 8 * (b & 1), lane == 0);
                mbar_arrive_if(bar_qe + 8 * (item & 1), lane == 0 && left == 0);
                if (left == 0) { mask(0); mask(1); }
                if (fresh) { m0 = fmaxf(s[0], s[1]); m1 = fmaxf(s[2], s[3]); quad_max(m0, m1); }
            }
            if (b > 0) {
                float u0, u1;
                if (left == 0) exps(std::integral_constant<int, 2>(), b, !early, u0, u1);
                else exps(std::integral_constant<int, 1>(), b, !early, u0, u1);
                if (!__any_sync(0xffffffff, !(u0 + u1 < 1.f))) { l0 += u0; l1 += u1; continue; }
            }
            softmax_exact(fresh, b);
        }
        if (tdone >= 0) { store_o(tdone, nout++, 0, 4); publish_o(); }
        issue_pv(b - 1, !first, 8);
        finish_rows();
        wgmma_wait<0>();
        done();
        store_o(t + 1024, nout, 0, 4);
        publish_o();
        return nout;
    }
}

__device__ __forceinline__ uint32_t cluster_ctarank() {
    uint32_t r; asm volatile("mov.u32 %0, %%cluster_ctarank;" : "=r"(r)); return r;
}
__device__ __forceinline__ uint32_t mapa_u32(uint32_t addr, uint32_t rank) {
    uint32_t r; asm volatile("mapa.shared::cluster.u32 %0, %1, %2;" : "=r"(r) : "r"(addr), "r"(rank)); return r;
}
__device__ __forceinline__ void cluster_sync_all() {
    asm volatile("barrier.cluster.arrive.release.aligned;\nbarrier.cluster.wait.acquire.aligned;" ::: "memory");
}
__device__ __forceinline__ void st_async_v4(uint32_t addr, uint32_t a, uint32_t b, uint32_t c, uint32_t d, uint32_t mbar) {
    asm volatile("st.async.weak.shared::cluster.mbarrier::complete_tx::bytes.v4.b32 [%0], {%1, %2, %3, %4}, [%5];"
                 :: "r"(addr), "r"(a), "r"(b), "r"(c), "r"(d), "r"(mbar) : "memory");
}
__device__ __forceinline__ void st_async_v2(uint32_t addr, uint32_t a, uint32_t b, uint32_t mbar) {
    asm volatile("st.async.weak.shared::cluster.mbarrier::complete_tx::bytes.v2.b32 [%0], {%1, %2}, [%3];"
                 :: "r"(addr), "r"(a), "r"(b), "r"(mbar) : "memory");
}
__device__ __forceinline__ void st_async_b32(uint32_t addr, uint32_t a, uint32_t mbar) {
    asm volatile("st.async.weak.shared::cluster.mbarrier::complete_tx::bytes.b32 [%0], %1, [%2];" :: "r"(addr), "r"(a), "r"(mbar) : "memory");
}
__device__ __forceinline__ void pace(int cycles) {
    if (cycles > 0) {
        uint32_t t0, t;
        asm volatile("mov.u32 %0, %%clock;" : "=r"(t0));
        do { asm volatile("mov.u32 %0, %%clock;" : "=r"(t)); } while (t - t0 < (uint32_t)cycles);
    }
}
__device__ __forceinline__ void mbar_wait_cl(uint32_t bar, uint32_t parity) {
    uint32_t done = 0;
    for (int it = 0; it < WAIT_LIMIT && !done; it++) {
        asm volatile(
            "{\n.reg .pred p;\n"
            "mbarrier.try_wait.parity.shared::cta.b64 p, [%1], %2;\n"
            "selp.u32 %0, 1, 0, p;\n}\n" : "=r"(done) : "r"(bar), "r"(parity) : "memory");
    }
}
__device__ __forceinline__ void ldmatrix_x4(uint32_t& r0, uint32_t& r1, uint32_t& r2, uint32_t& r3, uint32_t addr) {
    asm volatile("ldmatrix.sync.aligned.m8n8.x4.shared.b16 {%0,%1,%2,%3}, [%4];"
                 : "=r"(r0), "=r"(r1), "=r"(r2), "=r"(r3) : "r"(addr));
}
__device__ __forceinline__ void cp_async16(uint32_t dst, const void* src) {
    asm volatile("cp.async.cg.shared.global [%0], [%1], 16;" :: "r"(dst), "l"(src) : "memory");
}
__device__ __forceinline__ float bf16r(float x) { return __uint_as_float(pack_bf16(0.f, x) & 0xffff0000u); }

#define DBGP(i, w, ok)
#define DBG(i, w)
#define DBGD(i, w, dep)
#define DBG_EXTRA 0
__device__ __forceinline__ void tma_load_2d_mc(uint32_t dst, const CUtensorMap* map, uint32_t bar, int c0, int c1, uint16_t mask) {
    asm volatile(
        "cp.async.bulk.tensor.2d.shared::cluster.global.mbarrier::complete_tx::bytes.multicast::cluster [%0], [%1, {%3, %4}], [%2], %5;"
        :: "r"(dst), "l"((uint64_t)map), "r"(bar), "r"(c0), "r"(c1), "h"(mask) : "memory");
}
__device__ __forceinline__ void stmatrix_x4_trans(uint32_t addr, uint32_t r0, uint32_t r1, uint32_t r2, uint32_t r3) {
    asm volatile("stmatrix.sync.aligned.m8n8.x4.trans.shared.b16 [%0], {%1, %2, %3, %4};" :: "r"(addr), "r"(r0), "r"(r1), "r"(r2), "r"(r3) : "memory");
}
__device__ __forceinline__ void stmatrix_x2_trans(uint32_t addr, uint32_t r0, uint32_t r1) {
    asm volatile("stmatrix.sync.aligned.m8n8.x2.trans.shared.b16 [%0], {%1, %2};" :: "r"(addr), "r"(r0), "r"(r1) : "memory");
}
__device__ __forceinline__ uint4 lds128(uint32_t a) {
    uint4 v; asm volatile("ld.shared.v4.u32 {%0, %1, %2, %3}, [%4];" : "=r"(v.x), "=r"(v.y), "=r"(v.z), "=r"(v.w) : "r"(a) : "memory"); return v;
}
__device__ __forceinline__ void sts128(uint32_t a, uint32_t x, uint32_t y, uint32_t z, uint32_t w) {
    asm volatile("st.shared.v4.b32 [%0], {%1, %2, %3, %4};" :: "r"(a), "r"(x), "r"(y), "r"(z), "r"(w) : "memory");
}
__device__ __forceinline__ float2 lds64f(uint32_t a) {
    float2 v; asm volatile("ld.shared.v2.f32 {%0, %1}, [%2];" : "=f"(v.x), "=f"(v.y) : "r"(a) : "memory"); return v;
}
__device__ __forceinline__ void fence_async_smem() { asm volatile("fence.proxy.async.shared::cta;" ::: "memory"); }
#define ACC16(d) "+f"(d[0]), "+f"(d[1]), "+f"(d[2]), "+f"(d[3]), "+f"(d[4]), "+f"(d[5]), "+f"(d[6]), "+f"(d[7]), "+f"(d[8]), "+f"(d[9]), "+f"(d[10]), "+f"(d[11]), "+f"(d[12]), "+f"(d[13]), "+f"(d[14]), "+f"(d[15])
template <int ND>
__device__ __forceinline__ void wgmma_rs_n32(float (&d)[ND], const uint32_t (&a)[4], uint32_t db_lo, int scale_d) {
    asm volatile(
        "{\n.reg .pred p;\n.reg .b64 db;\nsetp.ne.b32 p, %21, 0;\nmov.b64 db, {%20, 0x40000040};\n"
        "wgmma.mma_async.sync.aligned.m64n32k16.f32.bf16.bf16 {%0,%1,%2,%3,%4,%5,%6,%7,%8,%9,%10,%11,%12,%13,%14,%15}, {%16,%17,%18,%19}, db, p, 1, 1, 0;\n}\n"
        : ACC16(d) : "r"(a[0]), "r"(a[1]), "r"(a[2]), "r"(a[3]), "r"(db_lo), "r"(scale_d));
}
template <int ND>
__device__ __forceinline__ void wgmma_ss_n32(float (&d)[ND], uint32_t da_lo, uint32_t db_lo, int scale_d) {
    asm volatile(
        "{\n.reg .pred p;\n.reg .b64 da, db;\nsetp.ne.b32 p, %18, 0;\nmov.b64 da, {%16, 0x40000040};\nmov.b64 db, {%17, 0x40000040};\n"
        "wgmma.mma_async.sync.aligned.m64n32k16.f32.bf16.bf16 {%0,%1,%2,%3,%4,%5,%6,%7,%8,%9,%10,%11,%12,%13,%14,%15}, da, db, p, 1, 1, 1, 0;\n}\n"
        : ACC16(d) : "r"(da_lo), "r"(db_lo), "r"(scale_d));
}
__device__ __forceinline__ void wgmma_ss_n8(float (&d)[4], uint32_t da_lo, uint32_t db_lo, int scale_d) {
    asm volatile(
        "{\n.reg .pred p;\n.reg .b64 da, db;\nsetp.ne.b32 p, %6, 0;\nmov.b64 da, {%4, 0x40000040};\nmov.b64 db, {%5, 0x00000010};\n"
        "wgmma.mma_async.sync.aligned.m64n8k16.f32.bf16.bf16 {%0,%1,%2,%3}, da, db, p, 1, 1, 1, 0;\n}\n"
        : "+f"(d[0]), "+f"(d[1]), "+f"(d[2]), "+f"(d[3]) : "r"(da_lo), "r"(db_lo), "r"(scale_d));
}

#define SCHED_FENCE()
__device__ __forceinline__ void wgmma_ss_n32_p(float (&d)[16], uint32_t da_lo, uint32_t db_lo, int scale_d) {
    asm volatile(
        "{\n.reg .pred p;\n.reg .b64 da, db;\nsetp.ne.b32 p, %18, 0;\nmov.b64 da, {%16, 0x40000040};\nmov.b64 db, {%17, 0x00000030};\n"
        "wgmma.mma_async.sync.aligned.m64n32k16.f32.bf16.bf16 {%0,%1,%2,%3,%4,%5,%6,%7,%8,%9,%10,%11,%12,%13,%14,%15}, da, db, p, 1, 1, 1, 0;\n}\n"
        : ACC16(d) : "r"(da_lo), "r"(db_lo), "r"(scale_d));
}

#define ACC20(d) ACC16(d), "+f"(d[16]), "+f"(d[17]), "+f"(d[18]), "+f"(d[19])
#define ACC20_STR "{%0,%1,%2,%3,%4,%5,%6,%7,%8,%9,%10,%11,%12,%13,%14,%15,%16,%17,%18,%19}"
__device__ __forceinline__ void wgmma_rs_n40(float (&d)[20], const uint32_t (&a)[4], uint32_t db_lo, int scale_d) {
    asm volatile(
        "{\n.reg .pred p;\n.reg .b64 db;\nsetp.ne.b32 p, %25, 0;\nmov.b64 db, {%24, 0x40000040};\n"
        "wgmma.mma_async.sync.aligned.m64n40k16.f32.bf16.bf16 " ACC20_STR ", {%20,%21,%22,%23}, db, p, 1, 1, 0;\n}\n"
        : ACC20(d) : "r"(a[0]), "r"(a[1]), "r"(a[2]), "r"(a[3]), "r"(db_lo), "r"(scale_d));
}
template <int TA, int SBO>
__device__ __forceinline__ void wgmma_ss_n40(float (&d)[20], uint32_t da_lo, uint32_t db_lo, int scale_d) {
    asm volatile(
        "{\n.reg .pred p;\n.reg .b64 da, db;\nsetp.ne.b32 p, %22, 0;\nmov.b64 da, {%20, %23};\nmov.b64 db, {%21, 0x40000040};\n"
        "wgmma.mma_async.sync.aligned.m64n40k16.f32.bf16.bf16 " ACC20_STR ", da, db, p, 1, 1, %24, 0;\n}\n"
        : ACC20(d) : "r"(da_lo), "r"(db_lo), "r"(scale_d), "n"(0x40000000 + SBO / 16), "n"(TA));
}
template <int SBO>
__device__ __forceinline__ void wgmma_ss_n48(float (&d)[24], uint32_t da_lo, uint32_t db_lo, int scale_d) {
    asm volatile(
        "{\n.reg .pred p;\n.reg .b64 da, db;\nsetp.ne.b32 p, %26, 0;\nmov.b64 da, {%24, %27};\nmov.b64 db, {%25, 0x40000040};\n"
        "wgmma.mma_async.sync.aligned.m64n48k16.f32.bf16.bf16 {%0,%1,%2,%3,%4,%5,%6,%7,%8,%9,%10,%11,%12,%13,%14,%15,%16,%17,%18,%19,%20,%21,%22,%23}, da, db, p, 1, 1, 0, 0;\n}\n"
        : ACC20(d), "+f"(d[20]), "+f"(d[21]), "+f"(d[22]), "+f"(d[23]) : "r"(da_lo), "r"(db_lo), "r"(scale_d), "n"(0x40000000 + SBO / 16));
}

#define PT(i, th)
struct ChainParams {
    CUtensorMap mapW[3];
    CUtensorMap mapX;
    CUtensorMap mapC;
    CUtensorMap mapWo;
    CUtensorMap mapM;
    CUtensorMap mapOut;
};
constexpr int CH_BLOCK = 384;
constexpr int CO_WO = 0;
constexpr int CH_XC = 5120, CH_XP = 8 * CH_XC;
constexpr int CO_XB = 65536;
constexpr int CO_OB = CO_XB + 2 * CH_XP;
constexpr int CO_P = CO_OB + 8192;
constexpr int CO_LS = CO_P + 3072;
constexpr int CO_SC = CO_LS + 8 * 1280;
constexpr int CH_TW = 6144 + 8192;
constexpr int CO_T = 21 * 8192;
constexpr int CO_WA = CO_T + 6144;
constexpr int CO_ST = CO_T + 3 * CH_TW + 6144;
constexpr int CO_OWN = CO_ST + 4096, CO_OWN2 = CO_SC + 1536;
constexpr int CO_BAR = CO_OWN + 4096;
constexpr int CH_SMEM = CO_BAR + 256 + DBG_EXTRA;
#define CH_GL 2
#define CH_A3 1
#define CH_D0 0
#define CH_PF 0
#define CH_XPF 0
#define CH_NSM 4
static_assert(CO_OWN2 + 1024 <= CO_T && CH_NSM <= 4, "smem layout");
#define CH_POLL_DELAY 280
#define CH_VPOS 2
#define CH_OW 12
#define CH_OF 12
#define CH_Q0 0
#define CH_QI 12
#define CH_QX 0
#define CH_Q1 (CH_Q0 + CH_QI + CH_QX)
#define CH_VA 5
#define CH_SPOS 0
#define CH_LSW 1
#define CH_QE 16
#define CH_KE 16
#define CH_QD 0
#define CH_GAP 0
#define CH_QS 0
#define CH_KS 0
#define CH_VS 4
#define CH_A7 7
#define CH_RF 0
#define CH_LSS 0
#define CH_OS 1
#define CH_MG 0
#define CH_MBT 0x76543210u
#define CH_MB(i) ((int)(CH_MBT >> 4 * (i)) & 7)
#define CH_AS 0x64207531u
#define CH_QL 16
#define CH_ML 0x112112
#define CH_DEP 1
#define CH_SP 2
#define CH_VD 1
#define CH_MP 1
#define CH_MP0 2
#define CH_OFE 3
#define CH_MS 1
#define CH_HA 3
#define CH_LD 4
#define CH_TWP 0
#define CH_SUMC 4
#define CH_ES 0
#define CH_ST 224
#define CH_KEEP 1
#define CH_PINB 0
#define CH_DRY 1
#define CH_D1 4500
#define CH_D2 11000
#define CH_CHAINS 4

constexpr float CH_SC = 0.08838834764831845f * 1.4426950408889634f;
__device__ __forceinline__ uint32_t pin(uint32_t v) { return __shfl_sync(0xffffffff, v, threadIdx.x & 31); }

__device__ __forceinline__ void out_finished() {
    if (atomicAdd(&g_ctr[CT_FIN], 1u) == M_GRID + 64 - 1)
        for (int i = 0; i < CT_N / 4; i++) reinterpret_cast<uint4*>(g_ctr)[i] = make_uint4(0u, 0u, 0u, 0u);
}
__device__ __forceinline__ void out_flush(const float (&acc)[128], const CUtensorMap* map, uint32_t stg0, uint32_t stg1, int tid, int bar, int n0, int m0) {
    const int lane = tid & 31, row = (lane & 7) + ((lane >> 3) & 1) * 8;
#pragma unroll
    for (int bx = 0; bx < 4; bx++)
#pragma unroll
        for (int j = 0; j < 8; j += 2) {
            const float* a = &acc[bx * 32 + j * 4];
            stmatrix_x4((bx < 2 ? stg0 : stg1) + (bx & 1) * 8192 + (((tid >> 5) & 3) * 16 + row) * 128 + (((j + (lane >> 4)) ^ (row & 7)) << 4),
                        pack_bf16(a[0], a[1]), pack_bf16(a[2], a[3]), pack_bf16(a[4], a[5]), pack_bf16(a[6], a[7]));
        }
    asm volatile("fence.proxy.async.shared::cta;\nbar.sync %0, 128;" :: "r"(bar) : "memory");
    asm volatile("{\n.reg .pred p;\nsetp.ne.b32 p, %0, 0;\n@p bra FL_SKIP;\n"
                 "cp.reduce.async.bulk.tensor.2d.global.shared::cta.add.tile.bulk_group [%1, {%4, %8}], [%2];\n"
                 "cp.reduce.async.bulk.tensor.2d.global.shared::cta.add.tile.bulk_group [%1, {%5, %8}], [%2 + 8192];\n"
                 "cp.reduce.async.bulk.tensor.2d.global.shared::cta.add.tile.bulk_group [%1, {%6, %8}], [%3];\n"
                 "cp.reduce.async.bulk.tensor.2d.global.shared::cta.add.tile.bulk_group [%1, {%7, %8}], [%3 + 8192];\n"
                 "cp.async.bulk.commit_group;\nFL_SKIP:\n}"
                 :: "r"(tid & 127), "l"((uint64_t)map), "r"(stg0), "r"(stg1), "r"(n0), "r"(n0 + 64), "r"(n0 + 128), "r"(n0 + 192), "r"(m0) : "memory");
    __syncwarp();
}

__global__ void __cluster_dims__(8, 1, 1) __launch_bounds__(CH_BLOCK, 1)
chain_kernel(const __grid_constant__ ChainParams P) {
    extern __shared__ uint8_t smem_raw[];
    const int tid = threadIdx.x, warp = __shfl_sync(0xffffffff, tid >> 5, 0), lane = tid & 31;
    const int rank = (int)cluster_ctarank();
    constexpr uint32_t sd = 1024;
    const uint32_t sb = ((uint32_t)rank << 24) + sd;
    if (smem_u32(smem_raw) != sb) __trap();
    const int C = blockIdx.x >> 3;
    const int h = C * 4 + (rank >> 1);
    const int qd = lane >> 2, qc = lane & 3;
    const int t4 = warp & 3, wg = warp >> 2;
    pdl_launch_dependents();
    uint32_t t_start;
    asm volatile("mov.u32 %0, %%clock;" : "=r"(t_start));
    t_start = __shfl_sync(0xffffffff, t_start, 0);
    TS_BEGIN(2);
    PT(0, 0);
    const uint32_t bar_mem = sb + CO_BAR + 128, bar_o = sb + CO_BAR + 32, bar_sc = bar_o + 32, bar_x = bar_sc + 8, bar_l = bar_x + 16, bar_w = bar_l + 8;
    const uint32_t bar_wo = bar_o + 24;
    auto chunk = [&](int i) { return (uint32_t)((rank - i) & 7); };
    auto mine = [](int g, int c) { return (int)((CH_AS >> (g * 16 + c * 4)) & 7); };
    const int wcol = h * HD + (rank & 1) * 64;
    auto wdst = [&](int g, int i) { return i == 0 ? CO_WA + g * CH_TW : g && i == 7 ? CO_ST : (g ? CO_XB + CH_XP : 0) + (i - 1) * 8192; };
    auto vdst = [&](int i) { return i >= 2 && i < 10 ? CO_XB + CH_XP + (i - 2) * CH_XC : (i < 2 ? CO_WA + 2 * CH_TW : i < 12 ? CO_OB : i < 14 ? CO_LS : CO_ST) + (i & 1) * 4096; };
    if ((tid & 127) == 0) {
        pace(CH_D0);
        const uint32_t bar = wg == 2 ? bar_x : bar_w + 8 * wg;
        mbar_init(bar, 1);
        asm volatile("fence.mbarrier_init.release.cluster;" ::: "memory");
        mbar_expect_tx(bar, wg == 2 ? CH_XP : 65536);
#pragma unroll 1
        for (int i = 0; i < 8; i++) {
            if (wg == 2) {
                tma_load_2d(sb + CO_XB + i * CH_XC, &P.mapX, bar, i * 64, 0);
                tma_load_2d(sb + CO_XB + i * CH_XC + 4096, &P.mapM, bar, i * 64, 0);
            } else tma_load_2d(sb + wdst(wg, i), &P.mapW[wg ^ (i & 1)], bar, wcol, chunk(mine(wg, i >> 1)) * 64);
        }
    }
    if (warp == 9 && lane < 24 && lane != 9 && (lane >> 1) != 6) {
        mbar_init(sb + CO_BAR + 8 * lane, 1);
        asm volatile("fence.mbarrier_init.release.cluster;" ::: "memory");
    }
    __syncthreads();
    PT(1, 0);
    if (wg == 2 || (wg == 0 && CH_QL < 16)) asm volatile("bar.arrive 10, %0;" :: "n"(CH_QL < 16 ? 384 : 256) : "memory");
    if (wg == 2) {
        const int t = tid - 256;
        sts128(sb + CO_T + (2 + (t >> 6)) * CH_TW + 5120 + (t & 63) * 16, 0u, 0u, 0u, 0u);
        if (t < 32) sts128(sb + CO_P + (t >> 3) * 768 + 640 + (t & 7) * 16, 0u, 0u, 0u, 0u);
    }
    const uint32_t wfrag = (((lane >> 4) << 3) + (lane & 7)) * 128 + (((t4 * 2 + ((lane >> 3) & 1)) ^ (lane & 7)) << 4);
    const uint32_t aO = pin(sb + wg * CH_TW + wfrag);
    const uint32_t aL = pin(sb + lane * 16);
    uint32_t w[32][4];
    auto load_w = [&](int g, bool v) {
#pragma unroll
        for (int e = CH_NSM; e < 32; e++) ldmatrix_x4_trans(w[e][0], w[e][1], w[e][2], w[e][3], aO + ((v ? vdst(e >> 1) + (e & 1) * 2048 : wdst(g, e >> 2) + (e & 3) * 2048) - g * CH_TW));
        fence_async_smem();
    };
    auto pass = [&](auto& d, int g, int b, int j0, int j1, int js, bool group = true) {
        const uint32_t lo = desc_lo(sd + CO_XB + b * CH_XP, 16);
        if (group) wgmma_fence();
#pragma unroll
        for (int j = 0; j < 32; j++) if (j >= j0 && j < j1) {
            const int f = js < 0 ? j : j < js ? j + CH_NSM : j < js + CH_NSM ? j - js : j;
            const int e = sizeof(d) == 64 ? (f >> 2) * 8 + (js < 0 ? 4 : 0) + (f & 3) : f;
            const uint32_t db = lo + chunk(sizeof(d) == 64 ? mine(g, f >> 2) : f >> 2) * (CH_XC / 16) + (e & 3) * 2, da = desc_lo(sd + CO_WA + g * CH_TW + e * 2048, 16);
            if constexpr (sizeof(d) == 64) { if (e < CH_NSM) wgmma_ss_n32(d, da, db, j != 0); else wgmma_rs_n32(d, w[e], db, j != 0); }
            else { if (e < CH_NSM) wgmma_ss_n40<1, 1024>(d, da, db, j != 0); else wgmma_rs_n40(d, w[e], db, j != 0); }
        }
        if (group) wgmma_commit();
    };
    auto uni = [](uint32_t v) { return __shfl_sync(0xffffffff, v, 0); };
    auto roff = [&](int j) { return (uint32_t)(((rank + j) & 7) - rank) << 24; };
    auto store32 = [&](const float* d, uint32_t a) {
        stmatrix_x4_trans(a, pack_bf16(d[0], d[1]), pack_bf16(d[2], d[3]), pack_bf16(d[4], d[5]), pack_bf16(d[6], d[7]));
        stmatrix_x4_trans(a + 2048, pack_bf16(d[8], d[9]), pack_bf16(d[10], d[11]), pack_bf16(d[12], d[13]), pack_bf16(d[14], d[15]));
    };
    auto load32 = [&](uint32_t (&r)[8], uint32_t a) {
        ldmatrix_x4_trans(r[0], r[1], r[2], r[3], a);
        ldmatrix_x4_trans(r[4], r[5], r[6], r[7], a + 2048);
    };
    auto add32 = [&](float* d, const uint32_t (&r)[8], uint32_t a) {
        wgmma_wait<0>();
#pragma unroll
        for (int i = 0; i < 8; i++) { d[2 * i] += __uint_as_float(r[i] << 16); d[2 * i + 1] += __uint_as_float(r[i] & 0xffff0000u); }
        store32(d, a);
    };
    auto scores = [&](float (&d)[24], auto sbo, uint32_t q) {
        wgmma_fence();
#pragma unroll
        for (int ks = 0; ks < 4; ks++) wgmma_ss_n48<decltype(sbo)::value>(d, desc_lo(sd + q, 16) + ks * 2, desc_lo(sd + CO_T + CH_TW, 16) + ks * 2, ks != 0);
        wgmma_commit();
    };
    auto add_scores = [&](uint32_t a, uint32_t b, float (&v)[10]) {
        const uint4 a0 = lds128(a), a1 = lds128(a + 512);
        const float2 a2 = lds64f(b);
        v[0] += __uint_as_float(a0.x); v[1] += __uint_as_float(a0.y); v[2] += __uint_as_float(a0.z); v[3] += __uint_as_float(a0.w);
        v[4] += __uint_as_float(a1.x); v[5] += __uint_as_float(a1.y); v[6] += __uint_as_float(a1.z); v[7] += __uint_as_float(a1.w);
        v[8] += a2.x; v[9] += a2.y;
    };
    auto row_max = [&](const float (&v)[10]) {
        float mx = fmaxf(fmaxf(fmaxf(v[0], v[1]), fmaxf(v[2], v[3])), fmaxf(fmaxf(v[4], v[5]), fmaxf(v[6], v[7])));
        mx = fmaxf(mx, fmaxf(v[8], v[9]));
        mx = fmaxf(mx, __shfl_xor_sync(0xffffffff, mx, 1));
        return fmaxf(mx, __shfl_xor_sync(0xffffffff, mx, 2)) * CH_SC;
    };
    auto local_pv = [&](int s, int st) {
        float dc[16];
        wgmma_fence();
#pragma unroll
        for (int ks = 0; ks < 3; ks++) wgmma_ss_n32_p(dc, desc_lo(sd + CO_T + (2 + (s & 1)) * CH_TW + ks * 2048, 16), desc_lo(sd + CO_P + ks * 256, 128), ks != 0);
        wgmma_commit();
        wgmma_wait<0>();
        store32(dc, aO - CH_TW + st);
    };
    float gs = 0.f;
    auto load_gate = [&](int s) { asm volatile("ld.global.cg.f32 %0, [%1];" : "=f"(gs) : "l"(g_gate + s * SEGL + t4 * 8 + qd) : "memory"); };
    auto softmax = [&](int s, float (&u)[11]) {
        float v[10];
        {
            const uint4 a0 = lds128(aL + CO_OWN + t4 * 1024), a1 = lds128(aL + CO_OWN + t4 * 1024 + 512);
            const float2 a2 = lds64f(aL + CO_OWN2 + t4 * 256 - lane * 8);
            v[0] = __uint_as_float(a0.x); v[1] = __uint_as_float(a0.y); v[2] = __uint_as_float(a0.z); v[3] = __uint_as_float(a0.w);
            v[4] = __uint_as_float(a1.x); v[5] = __uint_as_float(a1.y); v[6] = __uint_as_float(a1.z); v[7] = __uint_as_float(a1.w);
            v[8] = a2.x; v[9] = a2.y;
        }
        mbar_wait_cl(bar_l, s & 1);
        add_scores(aL + t4 * 1024 + CO_LS + (s & 1) * 5120, aL + t4 * 256 - lane * 8 + CO_LS + (s & 1) * 5120 + 4096, v);
        const int lim = t4 * 8 + qd - 2 * qc;
#pragma unroll
        for (int j = 0; j < 8; j++) if ((j >> 1) * 8 + (j & 1) > lim) v[j] = -INFINITY;
        const float mx = row_max(v);
#pragma unroll
        for (int j = 0; j < 10; j++) u[j] = v[j];
        u[10] = mx;
    };
    auto softmax1 = [&](float (&u)[11]) {
#pragma unroll
        for (int j = 0; j < 10; j++) u[j] = ex2f(fmaf(u[j], CH_SC, -u[10]));
        u[10] = (((u[0] + u[1]) + (u[2] + u[3])) + ((u[4] + u[5]) + (u[6] + u[7]))) + (u[8] + u[9]);
    };
    auto softmax2 = [&](float (&v)[11]) {
        float sum = v[10];
        sum += __shfl_xor_sync(0xffffffff, sum, 1);
        sum += __shfl_xor_sync(0xffffffff, sum, 2);
        asm("rcp.approx.ftz.f32 %0, %0;" : "+f"(sum));
        sum *= 1.f - gs;
        const uint32_t pa = aL + CO_P + t4 * 768;
        stmatrix_x4(pa, pack_bf16(v[0] * sum, v[1] * sum), pack_bf16(v[2] * sum, v[3] * sum), pack_bf16(v[4] * sum, v[5] * sum), pack_bf16(v[6] * sum, v[7] * sum));
        asm volatile("stmatrix.sync.aligned.m8n8.x1.shared.b16 [%0], {%1};" :: "r"(pa + 512), "r"(pack_bf16(v[8] * sum, v[9] * sum)) : "memory");
    };
    if (mapa_u32(bar_l, rank ^ 1) != (bar_l ^ (1u << 24)) || mapa_u32(bar_l, (rank + 3) & 7) != bar_l + roff(3)) __trap();
    asm volatile("bar.sync %0, 128;" :: "r"(12 + wg) : "memory");
    if (__shfl_sync(0xffffffff, tid, 1) < 256) {
#pragma unroll 1
        for (int rep = CH_DRY ? 0 : 1; rep < 2; rep++) {
            if (rep) mbar_wait(bar_w + 8 * wg, 0);
            PT(3, 0);
            load_w(wg, false);
            if (rep) {
                asm volatile("bar.arrive %0, 160;" :: "r"(wg ? 2 : 15) : "memory");
                asm volatile("barrier.cluster.arrive.relaxed.aligned;" ::: "memory");
                mbar_wait(bar_x, 0);
            }
            asm volatile("bar.sync 12, 256;" ::: "memory");
            PT(7, 0);
            float d[16];
            pass(d, wg, 0, 0, 16, -1);
            wgmma_wait<0>();
            store32(d, aO + CO_T + (1 - 2 * wg) * CH_TW);
            pass(d, wg, 0, 0, 16, 0);
            asm volatile("bar.sync 13, 256;" ::: "memory");
            uint32_t r[8];
            load32(r, aO + CO_T);
            add32(d, r, aO + CO_T);
        }
    }
    PT(8, 0);
    TS_BEGIN(5);
    PT(9, 0);

    if (wg < 2) {
        const uint32_t aM = pin(sb + CO_XB + 4096 + (lane & 7) * 128 + (((lane >> 3) ^ (lane & 7)) << 4));
        uint32_t coff[4];
#pragma unroll
        for (int i = 0; i < 4; i++) coff[i] = uni(chunk(mine(wg, i)) * CH_XC);
        auto mem_proj = [&](int s, auto gc) {
            constexpr int G = decltype(gc)::value;
            const uint32_t par = s & 1;
            float acc[4][4];
#pragma unroll
            for (int i = 0; i < 4; i++) acc[i][0] = acc[i][1] = acc[i][2] = acc[i][3] = 0.f;
            const uint32_t am = aM + par * CH_XP;
            uint32_t b[4][4], ok = 1;
            auto bar = [&](int c) { return bar_mem + 8 * CH_MB(mine(G, c)); };
            auto load = [&](int c) {
                if (c ? CH_MB(mine(G, c)) != CH_MB(mine(G, c - 1)) : G == 0)
                    asm volatile("{\n.reg .pred p, q;\n.reg .u32 c;\nsetp.ne.u32 p, %2, 0;\n@p bra MP_DONE;\nmov.u32 c, 0;\n"
                                 "MP_LOOP:\nmbarrier.try_wait.parity.shared::cta.b64 p, [%0], %1;\nadd.u32 c, c, 1;\nsetp.lt.and.u32 q, c, %3, !p;\n"
                                 "@q bra MP_LOOP;\nMP_DONE:\n}" :: "r"(bar(c)), "r"(par ^ 1), "r"(ok), "n"(WAIT_LIMIT / 64) : "memory");
                uint32_t* r = b[2 * c & 3];
                ldmatrix_x4(r[0], r[1], r[2], r[3], am + coff[c]);
                r = b[(2 * c + 1) & 3];
                ldmatrix_x4(r[0], r[1], r[2], r[3], (am ^ 64) + coff[c]);
                if (c < 3 && CH_MB(mine(G, c + 1)) != CH_MB(mine(G, c))) ok = mbar_try(bar(c + 1), par ^ 1);
            };
            auto mma = [&](int i) {
#pragma unroll
                for (int j = 0; j < 4; j++) {
                    const uint32_t* a = w[(i >> 1) * 8 + ((j & 1) ^ G) * 4 + (i & 1) * 2 + (j >> 1)];
                    mma_16816(acc[j], a[0], a[1], a[2], a[3], b[i & 3][j & 2], b[i & 3][(j & 2) + 1]);
                }
            };
#pragma unroll
            for (int e = 0; e < CH_NSM; e++) ldmatrix_x4_trans(w[e][0], w[e][1], w[e][2], w[e][3], aO + CO_WA + e * 2048);
            if (G == 1) asm volatile("bar.sync 10, %0;" :: "n"(CH_QL < 16 ? 384 : 256) : "memory");
            else ok = mbar_try(bar(0), par ^ 1);
            DBG(11, 0);
            load(0);
#pragma unroll
            for (int c = 0; c < 3; c++) {
                const int at = (CH_ML >> (c * 4 + G * 12)) & 3;
                if (at == 0) load(c + 1);
                mma(2 * c);
                if (at == 1) load(c + 1);
                mma(2 * c + 1);
                if (at == 2) load(c + 1);
            }
            mma(6);
            uint32_t dep = __float_as_uint(acc[CH_HA & 3][0]);
            mma(7);
            if (CH_HA >= 4) dep = __float_as_uint(acc[CH_HA & 3][0]);
            asm volatile("bar.arrive %0, 384;" :: "r"(5 | (dep & (s >> 10))) : "memory");
            uint32_t r[4];
#pragma unroll
            for (int i = 0; i < 4; i++) r[i] = pack_bf16(acc[i >> 1][(i & 1) * 2] + acc[(i >> 1) + 2][(i & 1) * 2], acc[i >> 1][(i & 1) * 2 + 1] + acc[(i >> 1) + 2][(i & 1) * 2 + 1]);
            DBGD(40 + warp, warp, r[0] ^ r[1]);
            asm volatile("{\n.reg .pred q;\nsetp.ne.s32 q, %3, 0;\n"
                         "@q stmatrix.sync.aligned.m8n8.x2.trans.shared.b16 [%0], {%1, %2};\n"
                         "@q stmatrix.sync.aligned.m8n8.x2.trans.shared.b16 [%0 + %4], {%1, %2};\n"
                         "@q stmatrix.sync.aligned.m8n8.x2.trans.shared.b16 [%0 + 2 * %4], {%1, %2};\n"
                         "@q stmatrix.sync.aligned.m8n8.x2.trans.shared.b16 [%0 + 3 * %4], {%1, %2};\n}"
                         :: "r"(aO + (CO_XB + 4096 + G * (CH_XC - CH_TW) + (par ^ 1) * CH_XP)), "r"(r[0]), "r"(r[1]),
                            "r"(s - (NSEG - 1)), "n"(2 * CH_XC) : "memory");
            stmatrix_x2_trans(aO + CO_T + (G ? 5120 : CH_TW + 4096), r[2], r[3]);
            fence_async_smem();
        };
        if (wg == 0) {
#pragma unroll 1
            for (int s = 0; s < NSEG; s++) {
                const uint32_t par = s & 1;
                mem_proj(s, std::integral_constant<int, 0>());
                asm volatile("bar.arrive 1, 256;" ::: "memory");
                asm volatile("bar.sync 8, 384;" ::: "memory");
                if (s == NSEG - 1) break;
                if (tid == 96) {
#pragma unroll
                    for (int j = 1; j < 8; j++) {
                        int n = 0;
                        for (int i = 1; i < 8; i++) n += CH_MB(i) == j;
                        if (n) mbar_expect_tx(bar_mem + 8 * j, 1024 * n);
                        if (j < 4) mbar_expect_tx(bar_o + 8 * j - 8, 512 << j);
                    }
                }
                __syncwarp();
                uint32_t* wp = g_xbuf + (size_t)rank * 2048 + C * 256 + qc * 64 + t4 * 8 + qd;
                asm volatile("st.relaxed.gpu.global.u32 [%0], %1;" :: "l"(wp + ((s + 2) & 3) * 16384), "r"(~0u) : "memory");
                asm volatile("st.relaxed.gpu.global.u32 [%0], %1;" :: "l"(wp + ((s + 2) & 3) * 16384 + 32), "r"(~0u) : "memory");
                if (__builtin_expect(s == 0, 0)) {
                    asm volatile("barrier.cluster.wait.aligned;" ::: "memory");
                    mbar_wait(bar_wo, 0);
                    const int sr = (qd >> 2) * 2 + (qd & 1) + (qd & 2) * 4;
#pragma unroll 2
                    for (int ks = t4; ks < 32; ks += 4) {
                        const uint32_t a = sb + CO_WO + ks * 2048;
                        uint4 u[2][2];
#pragma unroll
                        for (int i = 0; i < 4; i++) { const int r = sr + (i >> 1) * 4; u[i >> 1][i & 1] = lds128(a + r * 128 + (((qc * 2 + (i & 1)) ^ (r & 7)) << 4)); }
                        __syncwarp();
#pragma unroll
                        for (int i = 0; i < 4; i++) {
                            const uint4 u0 = u[i >> 1][0], u1 = u[i >> 1][1];
                            const uint32_t sel = (i & 1) ? 0x7632 : 0x5410;
                            sts128(a + (qd + (i >> 1) * 8) * 128 + (((qc * 2 + (i & 1)) ^ qd) << 4),
                                   __byte_perm(u0.x, u0.y, sel), __byte_perm(u0.z, u0.w, sel), __byte_perm(u1.x, u1.y, sel), __byte_perm(u1.z, u1.w, sel));
                        }
                    }
                    fence_async_smem();
                }
                mbar_wait(bar_x + 8 * (par ^ 1), ((s + 1) >> 1) & 1);
                asm volatile("bar.sync 7, 384;" ::: "memory");
                float d[16];
                float c[4];
                const uint32_t alo = desc_lo(sd + CO_WO, 16), blo = desc_lo(sd + CO_OB, 128);
                wgmma_fence();
                pass(d, 0, par ^ 1, 0, CH_Q0, -1, false);
                asm volatile("bar.sync 11, 256;" ::: "memory");
#pragma unroll
                for (int i = 0; i < 32; i++) {
                    if (i == 4) { pass(d, 0, par ^ 1, CH_Q0 + min(4, CH_QI), CH_Q0 + min(4, CH_QI) + CH_QX, -1, false); mbar_wait_cl(bar_o, par); }
                    if (i == 8) mbar_wait_cl(bar_o + 8, par);
                    if (i == CH_OW) mbar_wait_cl(bar_o + 16, par);
                    wgmma_ss_n8(c, alo + i * 128, blo + i * 16, i != 0);
                    if (i < CH_QI) pass(d, 0, par ^ 1, CH_Q0 + i + (i < 4 ? 0 : CH_QX), CH_Q0 + i + (i < 4 ? 0 : CH_QX) + 1, -1, false);
                }
                wgmma_commit();
                wgmma_wait<0>();
                asm volatile("st.relaxed.gpu.global.u32 [%0], %1;" :: "l"(wp + (s & 3) * 16384), "r"(pack_bf16(c[0], c[2])) : "memory");
                asm volatile("st.relaxed.gpu.global.u32 [%0], %1;" :: "l"(wp + (s & 3) * 16384 + 32), "r"(pack_bf16(c[1], c[3])) : "memory");
                asm volatile("bar.arrive 6, 384;" ::: "memory");
                pace(CH_QD);
                asm volatile("bar.arrive 4, 384;" ::: "memory");
                DBG(8, 0);
                if (CH_Q1 < 16) pass(d, 0, par ^ 1, CH_Q1, 16, -1);
                asm volatile("bar.sync 9, 256;" ::: "memory");
                wgmma_wait<0>();
                store32(d, aO + CO_T + CH_TW);
                asm volatile("bar.arrive 12, 256;" ::: "memory");
                if (CH_QL) pass(d, 0, (par ^ 1) + (s >> 10), 0, CH_QL, CH_QS);
                DBG(21, 0);
                if (tid == 0) {
                    if (s + 2 < NSEG) {
                        mbar_expect_tx(bar_x + 8 * par, 32768);
                        tma_load_2d_mc(sb + CO_XB + par * CH_XP + rank * CH_XC, &P.mapX, bar_x + 8 * par, rank * 64, (s + 2) * SEGL, (uint16_t)0xff);
                        if (CH_XPF) asm volatile("cp.async.bulk.prefetch.tensor.2d.L2.global [%0, {%1, %2}];" :: "l"(&P.mapX), "r"(rank * 64), "r"((s + 2 + CH_XPF) * SEGL) : "memory");
                    } else {
#pragma unroll 1
                        for (int i = 0; i < 8; i++) tma_load_2d(sb + CO_WO + i * 8192, &P.mapWo, bar_wo, (rank & 1) * 256 + (i & 3) * 64, h * HD + (i >> 2) * 64);
                    }
                }
                __syncwarp();
                asm volatile("bar.sync 13, 256;" ::: "memory");
                uint32_t r[8];
                load32(r, aO + CO_T);
                if (CH_QL < 16) {
                    asm volatile("bar.sync 10, 384;" ::: "memory");
                    pass(d, 0, (par ^ 1) + (s >> 10), CH_QL, CH_QE, CH_QS);
                }
                add32(d, r, aO + CO_T);
                DBG(22, 0);
            }
            *reinterpret_cast<uint2*>(g_xbuf + 16384 + blockIdx.x * 256 + tid * 2) = make_uint2(~0u, ~0u);
        PT(10, 0);
            const int n0 = (rank & 1) * 256;
            if (tid == 0) {
                mbar_expect_tx(bar_wo, 65536 + 16384);
                mbar_expect_tx(bar_w, 8192);
                asm volatile("prefetch.tensormap [%0];" :: "l"(&P.mapOut) : "memory");
                wait_ctr(CT_CA + 63, 16u);
            }
            __syncwarp();
#pragma unroll 1
            for (int r = 0; r < 2; r++) {
                float acc[128];
                mbar_wait(r ? bar_w : bar_wo, 1);
                asm volatile("bar.sync %0, 256;" :: "r"(15 - r) : "memory");
                wgmma_fence();
#pragma unroll
                for (int kk = 0; kk < 8; kk++)
                    wgmma_ss_n256_tb(acc, make_desc(sd + CO_XB + (kk >> 2) * 16384 + r * 8192 + (kk & 3) * 32, 16, 1024),
                                     make_desc(sd + CO_WO + (kk >> 2) * 32768 + (kk & 3) * 2048, 8192, 1024), kk);
                wgmma_commit();
                if (tid == 0) asm volatile("cp.async.bulk.wait_group.read 0;" ::: "memory");
                asm volatile("bar.sync 12, 128;" ::: "memory");
                wgmma_wait<0>();
                PT(5, 0);
                out_flush(acc, &P.mapOut, sb + CO_XB + CH_XP, sb + CO_XB + CH_XP + 16384, tid, 12, n0, SEQ - 128 + r * 64);
            }
            if (tid == 0) {
                asm volatile("cp.async.bulk.wait_group.read 0;" ::: "memory");
                PT(15, 0);
                out_finished();
            }
        } else {
            const uint32_t usc = uni(CO_SC + min(t4, 2) * 512 + roff((rank ^ 1) - rank)), uscb = uni(bar_sc ^ (1u << 24));
            const uint32_t vaddr = pin(sb + CO_T + 2 * CH_TW + (lane & 15) * 128 + (((t4 * 2 + (lane >> 4)) ^ (lane & 7)) << 4));
            const uint32_t dsta = pin(sb + CO_OB + t4 * 256 + (qc >> 1) * 128 + qd * 16 + (qc & 1) * 8);
            auto store_ctx = [&](int s) {
                if (tid == CH_ST && (uint32_t)s < NSEG - 3) {
                    tma_store_2d(&P.mapC, sb + CO_ST, (rank & 1) * 64, h * SEQ + s * SEGL);
                    asm volatile("cp.async.bulk.commit_group;" ::: "memory");
                }
                __syncwarp();
            };
            auto signal_ctx = [&](int s) {
                if (tid == CH_ST && (s & 3) == 1)
                    asm volatile("cp.async.bulk.wait_group 0;\nred.relaxed.gpu.global.add.u32 [%0], 1;" :: "l"(&g_ctr[CT_CB - 1 + (s >> 2)]) : "memory");
                __syncwarp();
            };
            uint32_t uo[8], ub[8];
#pragma unroll
            for (int i = 0; i < 8; i++) { uo[i] = uni(roff(i) + i * 1024); ub[i] = uni(roff(i) + bar_o + (i < 2 ? 0 : i < 4 ? 8 : 16)); }
#pragma unroll 1
            for (int s = 0; s < NSEG; s++) {
                const uint32_t par = s & 1;
                mem_proj(s, std::integral_constant<int, 1>());
                asm volatile("bar.sync 1, 256;" ::: "memory");
                float d[24];
                scores(d, std::integral_constant<int, CH_XC>(), CO_XB + 4096 + (par ^ 1) * CH_XP);
                if (s == NSEG - 1) { wgmma_wait<0>(); break; }
                asm volatile("bar.arrive 8, 384;" ::: "memory");
                if (s == 0) asm volatile("barrier.cluster.wait.aligned;" ::: "memory");
                const uint32_t sca = (aL | (s >> 10)) + usc;
                wgmma_wait<0>();
                float v[10], u[12];
#pragma unroll
                for (int j = 0; j < 12; j++) u[j] = d[(j >> 1) * 4 + (j & 1)] + d[(j >> 1) * 4 + (j & 1) + 2];
                if (t4 < 3) {
                    auto sel = [&](int j) { return t4 == 0 ? u[j] : t4 == 1 ? u[4 + j] : u[8 + j]; };
                    asm volatile("st.async.weak.shared::cluster.mbarrier::complete_tx::bytes.v4.f32 [%0], {%2, %3, %4, %5}, [%1];"
                                 :: "r"(sca), "r"(uscb), "f"(sel(0)), "f"(sel(1)), "f"(sel(2)), "f"(sel(3)) : "memory");
                }
#pragma unroll
                for (int j = 0; j < 10; j++) v[j] = j < 8 ? u[j] : u[j] + u[j + 2];
                DBG(3, 4);
                if (CH_ES) signal_ctx(s); else store_ctx(s - 2);
                uint32_t vb[3][4];
                auto load_v = [&](float dep) {
                    asm volatile("bar.sync %0, 256;" :: "r"(CH_VD ? 3 | (__float_as_uint(dep) & (s >> 10)) : 3) : "memory");
#pragma unroll
                    for (int k = 0; k < 3; k++) ldmatrix_x4_trans(vb[k][0], vb[k][1], vb[k][2], vb[k][3], vaddr + par * CH_TW + k * 2048);
                };
                mbar_wait_cl(bar_sc, par);
                DBG(4, 4);
                {
                    const uint4 a0 = lds128(aL + CO_SC), a1 = lds128(aL + CO_SC + 512), a2 = lds128(aL + CO_SC + 1024);
                    v[0] += __uint_as_float(a0.x); v[1] += __uint_as_float(a0.y); v[2] += __uint_as_float(a0.z); v[3] += __uint_as_float(a0.w);
                    v[4] += __uint_as_float(a1.x); v[5] += __uint_as_float(a1.y); v[6] += __uint_as_float(a1.z); v[7] += __uint_as_float(a1.w);
                    v[8] += __uint_as_float(a2.x) + __uint_as_float(a2.z); v[9] += __uint_as_float(a2.y) + __uint_as_float(a2.w);
                }
                const float mx = row_max(v);
                if (CH_VPOS == 2) load_v(mx);
#pragma unroll
                for (int j = 0; j < 10; j++) v[j] = ex2f(fmaf(v[j], CH_SC, -mx));
                uint32_t p[5];
#pragma unroll
                for (int j = 0; j < 5; j++) p[j] = pack_bf16(v[2 * j], v[2 * j + 1]);
                if (CH_VPOS == 3) load_v(v[CH_VD]);
                DBG(19, 4);
                float c0[4] = {0.f, 0.f, 0.f, 0.f}, c1[4] = {0.f, 0.f, 0.f, 0.f}, cs[4] = {0.f, 0.f, 0.f, 0.f};
#pragma unroll
                for (int k = 0; k < 3; k++) {
                    const uint32_t p0 = p[2 * k], p1 = k < 2 ? p[2 * k + 1] : 0u;
                    mma_16816(cs, p0, 0u, p1, 0u, 0x3f803f80u, 0x3f803f80u);
                    mma_16816(c0, p0, 0u, p1, 0u, vb[k][0], vb[k][1]);
                    mma_16816(c1, p0, 0u, p1, 0u, vb[k][2], vb[k][3]);
                }
                float inv;
                asm volatile("rcp.approx.ftz.f32 %0, %1;" : "=f"(inv) : "f"(cs[0]));
                const uint32_t b0 = pack_bf16(c0[0] * inv, c0[1] * inv), b1 = pack_bf16(c1[0] * inv, c1[1] * inv);
                DBG(20, 4);
#pragma unroll
                for (int i = 1; i < 8; i++) {
                    st_async_v2((dsta | (s >> 10)) + uo[i], b0, b1, ub[i]);
                    if (i == CH_OS) asm volatile("st.shared.v2.b32 [%0], {%1, %2};" :: "r"(dsta), "r"(b0), "r"(b1) : "memory");
                    if (i == CH_OFE) asm volatile("fence.proxy.async.shared::cta;\nbar.arrive 11, 256;" ::: "memory");
                }
                DBG(5, 4);
                asm volatile("cp.async.bulk.wait_group.read 0;" ::: "memory");
                asm volatile("bar.sync 7, 384;" ::: "memory");
                if (CH_OFE > 7) asm volatile("fence.proxy.async.shared::cta;\nbar.arrive 11, 256;" ::: "memory");
                local_pv(s + 1, CO_ST);
                if (CH_ES) fence_async_smem();
                asm volatile("bar.arrive 6, 384;" ::: "memory");
                if (tid == 128) mbar_expect_tx(bar_sc, 1536);
                __syncwarp();
                mbar_wait(bar_x + 8 * (par ^ 1), ((s + 1) >> 1) & 1);
                asm volatile("bar.sync 4, 384;" ::: "memory");
                float dk[16];
                pass(dk, 1, par ^ 1, 0, 16, -1);
                wgmma_wait<0>();
                store32(dk, aO + CO_T - CH_TW);
                asm volatile("bar.arrive 13, 256;" ::: "memory");
                pass(dk, 1, (par ^ 1) + (s >> 10), 0, CH_KE, CH_KS);
                if (CH_ES) store_ctx(s - 1); else signal_ctx(s);
                DBG(1, 4);
                asm volatile("bar.sync 12, 256;" ::: "memory");
                uint32_t r[8];
                load32(r, aO + CO_T);
                add32(dk, r, aO + CO_T);
                DBG(29, 4);
            }
        }
    } else {
        {
            PT(2, 256);
            int lane;
            asm volatile("mov.u32 %0, %%laneid;" : "=r"(lane));
            if (t4 >= 2) {
                const CUtensorMap* map = t4 == 2 ? &P.mapWo : &P.mapW[2];
                const uint32_t bar = t4 == 2 ? bar_wo : bar_w + 16;
                const int c0 = t4 == 2 ? rank * 64 : wcol;
                auto row = [&](int i) { return t4 == 2 ? C * 512 + ((rank - i) & 7) * 64 : (int)chunk(i >> 1) * 64 + (i & 1) * 32; };
                uint32_t now;
                do { asm volatile("mov.u32 %0, %%clock;" : "=r"(now)); } while (now - t_start < (uint32_t)(t4 == 2 ? CH_D2 : CH_D1));
                if (lane == 0) {
#pragma unroll 1
                    for (int i = 0; i < (CH_PF == 2 ? t4 * 8 - 8 : CH_PF * (t4 * 16 - 32)); i++) asm volatile("cp.async.bulk.prefetch.tensor.2d.L2.global [%0, {%1, %2}];" :: "l"(map), "r"(c0), "r"(row(i)) : "memory");
                    mbar_expect_tx(bar, 65536);
                }
                __syncwarp();
                asm volatile("bar.sync %0, 160;" :: "r"(t4 == 2 ? 15 : 2) : "memory");
                if (lane == 0) {
#pragma unroll 1
                    for (int i = 0; i < t4 * 8 - 8; i++) tma_load_2d(sb + (t4 == 2 ? CO_WO + i * 8192 : vdst(i)), map, bar, c0, row(i));
                }
            } else if (t4 == 0 && lane == 0) {
                asm volatile("cp.async.bulk.prefetch.tensor.2d.L2.global [%0, {%1, %2}];" :: "l"(&P.mapX), "r"(rank * 64), "r"(SEGL) : "memory");
                asm volatile("prefetch.tensormap [%0];" :: "l"(&P.mapC) : "memory");
                mbar_expect_tx(bar_sc, 1536);
                mbar_expect_tx(bar_x + 8, 32768);
            }
            __syncwarp();
            mbar_wait(bar_w + 16, 0);
            PT(4, 256);
            load_w(2, true);
            asm volatile("bar.sync 14, 128;" ::: "memory");
            asm volatile("barrier.cluster.arrive.relaxed.aligned;" ::: "memory");
            if (t4 == 0 && lane == 0) {
#pragma unroll 1
                for (int i = 0; i < 8; i++) tma_load_2d(sb + CO_XB + CH_XP + i * CH_XC, &P.mapX, bar_x + 8, i * 64, SEGL);
            }
            __syncwarp();
            PT(6, 256);
        }
#pragma unroll 1
        for (int s = 0; s < NSEG; s++) {
            const uint32_t par = s & 1;
            const bool last = s == NSEG - 1;
            if (CH_GL < 2) {
                if (s == 1) wait_ctr(CT_GATE, 256u);
                load_gate(max(s - 1, 0));
                if (CH_GL) asm volatile("prefetch.global.L2 [%0];" :: "l"(g_gate + ((s + 1) & (NSEG - 1)) * SEGL) : "memory");
            } else if (s == 1) { wait_ctr(CT_GATE, 256u); load_gate(0); }
            float v[11];
            if (CH_SP) fence_async_smem();
            softmax(s - 1, v);
            if (CH_SP < 2) softmax1(v);
            DBG(7, 8);
            if (!CH_SP) fence_async_smem();
            asm volatile("bar.sync %0, 384;" :: "r"(CH_SP ? 5 | (__float_as_uint(v[10]) & (s >> 10)) : 5) : "memory");
            DBG(23, 8);
            float dv[20], d[24];
            pass(dv, 2, par, 0, CH_VA, CH_VS);
            asm volatile("bar.sync 8, 384;" ::: "memory");
            pass(dv, 2, par, CH_VA, 32, CH_VS);
            if (CH_SP == 2) {
                uint32_t z;
                asm volatile("mov.u32 %0, %%clock;" : "=r"(z) :: "memory");
                v[10] = __uint_as_float(__float_as_uint(v[10]) | (z & (s >> 10)));
                softmax1(v);
                asm volatile("{\n.reg .pred p;\nsetp.ne.s32 p, %0, 1000001;\n@p bra SP_SKIP;\nwgmma.wait_group.sync.aligned 0;\n"
                             "st.volatile.shared.f32 [%0], %1;\nexit;\nSP_SKIP:\n}" :: "r"(s), "f"(v[10]) : "memory");
            }
            wgmma_wait<0>();
            stmatrix_x2_trans(aO + par * CH_TW + CO_T + 4096, pack_bf16(dv[16], dv[17]), pack_bf16(dv[18], dv[19]));
            store32(dv, aO + par * CH_TW + CO_T);
            DBG(24, 8);
            uint32_t z3 = __float_as_uint(dv[0]);
            if (CH_A3) asm volatile("{\n.reg .pred p;\nsetp.ne.s32 p, %1, %2;\n@p bar.arrive 3, 256;\nmov.u32 %0, %%clock;\n}" : "=r"(z3) : "r"(s), "n"(NSEG - 1) : "memory");
            else if (!last) asm volatile("bar.arrive 3, 256;" ::: "memory");
            if (CH_SP) { v[10] = __uint_as_float(__float_as_uint(v[10]) | (z3 & (s >> 10))); softmax2(v); fence_async_smem(); }
            if (CH_GL == 2) load_gate(s);
            if (last) asm volatile("bar.arrive 7, 256;" ::: "memory"); else asm volatile("bar.sync 7, 384;" ::: "memory");
            scores(d, std::integral_constant<int, 512>(), CO_T);
            asm volatile("{\n.reg .pred p;\nsetp.eq.s32 p, %1, 256;\n@p mbarrier.arrive.expect_tx.shared::cta.b64 _, [%0], 5120;\n}" :: "r"(bar_l), "r"(tid) : "memory");
            wgmma_wait<0>();
            d[16] += d[20]; d[17] += d[21];
            auto send_scores = [&]() {
                const uint32_t a = aL + t4 * 1024, a2 = aL + t4 * 256 - lane * 8, r = roff((rank ^ 1) - rank) + CO_LS + par * 5120;
                asm volatile("st.async.weak.shared::cluster.mbarrier::complete_tx::bytes.v4.f32 [%0], {%3, %4, %5, %6}, [%2];\n"
                             "st.async.weak.shared::cluster.mbarrier::complete_tx::bytes.v4.f32 [%0 + 512], {%7, %8, %9, %10}, [%2];\n"
                             "st.async.weak.shared::cluster.mbarrier::complete_tx::bytes.v2.f32 [%1], {%11, %12}, [%2];"
                             :: "r"(a + r), "r"(a2 + r + 4096), "r"(bar_l ^ (1u << 24)), "f"(d[0]), "f"(d[1]), "f"(d[4]), "f"(d[5]),
                                "f"(d[8]), "f"(d[9]), "f"(d[12]), "f"(d[13]), "f"(d[16]), "f"(d[17]) : "memory");
            };
            auto keep_scores = [&]() {
                const uint32_t a = aL + t4 * 1024, a2 = aL + t4 * 256 - lane * 8;
                sts128(a + CO_OWN, __float_as_uint(d[0]), __float_as_uint(d[1]), __float_as_uint(d[4]), __float_as_uint(d[5]));
                sts128(a + CO_OWN + 512, __float_as_uint(d[8]), __float_as_uint(d[9]), __float_as_uint(d[12]), __float_as_uint(d[13]));
                asm volatile("st.shared.v2.f32 [%0], {%1, %2};" :: "r"(a2 + CO_OWN2), "f"(d[16]), "f"(d[17]) : "memory");
            };
            if (s == 0) asm volatile("barrier.cluster.wait.aligned;" ::: "memory");
            if (CH_LSS == 0) send_scores();
            if (CH_KEEP == 0) keep_scores();
            if (last) { if (CH_LSS) send_scores(); if (CH_KEEP) keep_scores(); break; }
            asm volatile("bar.arrive 4, 384;\nbar.arrive 9, 256;" ::: "memory");
            uint32_t t0, t1;
            if (!CH_PINB) asm volatile("bar.sync 6, 384;\nmov.u32 %0, %%clock;" : "=r"(t0) :: "memory");
            const int row = t4 * 2 + (lane >> 4);
            const uint32_t dsta = pin(sb + CO_XB + (par ^ 1) * CH_XP + rank * CH_XC + 4096 + row * 128 + ((((lane & 15) >> 1) ^ row) << 4) + (lane & 1) * 8);
            uint32_t dst1 = pin(dsta + roff(1)), bar1 = pin((bar_mem + 8 + roff(1)) | (s >> 10));
            uint32_t sel = pin(((qd >> 1) == qc ? 0x3f80u << (qd & 1) * 16 : 0u) | (s >> 10));
            const uint2* xb = reinterpret_cast<const uint2*>(g_xbuf + (s & 3) * 16384 + (size_t)rank * 2048 + t4 * 64) + pin(lane | (s >> 10));
            if (CH_PINB) asm volatile("bar.sync %1, 384;\nmov.u32 %0, %%clock;" : "=r"(t0) : "r"(6 | (dst1 & sel & (uint32_t)(size_t)xb & (s >> 10))) : "memory");
            if (CH_LSS == 1) send_scores();
            if (CH_KEEP == 2) keep_scores();
            uint2 p[8], q[8];
            do { asm volatile("mov.u32 %0, %%clock;" : "=r"(t1) :: "memory"); } while (t1 - t0 < CH_POLL_DELAY);
#pragma unroll
            for (int k = 0; k < 8; k++)
                asm volatile("ld.relaxed.gpu.global.v2.u32 {%0, %1}, [%2];" : "=r"(p[k].x), "=r"(p[k].y) : "l"(xb + k * 128) : "memory");
            DBG(17, 8);
            if (CH_LSS == 2) send_scores();
            if (CH_KEEP == 1) keep_scores();
            {
                uint32_t z;
                asm volatile("mov.u32 %0, %%clock;" : "=r"(z) :: "memory");
#pragma unroll
                for (int i = 0; i < CH_GAP; i++) asm volatile("{\n.reg .f32 f;\nmov.b32 f, %0;\nex2.approx.ftz.f32 f, f;\nmov.b32 %0, f;\n}" : "+r"(z));
                asm volatile("and.b32 %0, %0, %1;" : "+r"(z) : "r"(s >> 10));
                xb += z;
            }
#pragma unroll
            for (int k = 0; k < 8; k++)
                asm volatile("ld.relaxed.gpu.global.v2.u32 {%0, %1}, [%2];" : "=r"(q[k].x), "=r"(q[k].y) : "l"(xb + k * 128) : "memory");
            if (CH_LSS == 3) send_scores();
            if (CH_KEEP == 3) keep_scores();
            uint32_t m0, m1;
            {
                uint32_t z;
                asm volatile("mov.u32 %0, %%clock;" : "=r"(z) :: "memory");
                sel |= z & (s >> 10);
            }
            auto sum = [&](const uint2 (&p)[8]) {
                float c[CH_SUMC][4];
#pragma unroll
                for (int k = 0; k < 4; k++) {
                    if (k < CH_SUMC) c[k][0] = c[k][1] = c[k][2] = c[k][3] = 0.f;
                    mma_16816(c[k % CH_SUMC], p[2 * k].x, p[2 * k].y, p[2 * k + 1].x, p[2 * k + 1].y, sel, sel);
                }
#pragma unroll
                for (int k = 1; k < CH_SUMC; k++) { c[0][0] += c[k][0]; c[0][1] += c[k][1]; c[0][2] += c[k][2]; c[0][3] += c[k][3]; }
                m0 = pack_bf16(c[0][0], c[0][1]);
                m1 = pack_bf16(c[0][2], c[0][3]);
                uint32_t ok;
                asm volatile("{\n.reg .pred p;\nsetp.num.f32 p, %1, %2;\nvote.sync.all.pred p, p, 0xffffffff;\nselp.u32 %0, 1, 0, p;\n}" : "=r"(ok) : "f"(c[0][0]), "f"(c[0][2]));
                return ok;
            };
            if (__builtin_expect(!sum(p), 0)) {
                DBG(12, 8);
#pragma unroll 1
                for (int it = 0; it < WAIT_LIMIT / 4; it++) {
                    if (sum(q)) break;
                    uint32_t bad = 0;
#pragma unroll
                    for (int k = 0; k < 8; k++) bad |= (max(q[k].x, q[k].y) == ~0u ? 1u : 0u) << k;
                    if (__all_sync(0xffffffff, bad == 0u)) break;
                    if (it == 0) DBG(14, 8);
                    if (it == 1) DBG(15, 8);
#pragma unroll
                    for (int k = 0; k < 8; k++)
                        if (bad & (1u << k))
                            asm volatile("ld.relaxed.gpu.global.v2.u32 {%0, %1}, [%2];" : "=r"(q[k].x), "=r"(q[k].y) : "l"(xb + k * 128) : "memory");
                }
            }
            DBG(9, 8);
            st_async_v2(dst1, m0, m1, bar1);
            asm volatile("st.shared.v2.b32 [%0], {%1, %2};\nbar.arrive 10, %3;" :: "r"(dsta), "r"(m0), "r"(m1), "n"(CH_QL < 16 ? 384 : 256) : "memory");
#pragma unroll 1
            for (int i = 0; i < 6; i += CH_MP) {
#pragma unroll
                for (int j = 0; j < CH_MP; j++) {
                    dst1 = (dst1 + (1u << 24)) & 0x7ffffffu; bar1 = (bar1 + (1u << 24) + 8) & 0x7ffffffu;
                    st_async_v2(dst1, m0, m1, bar1);
                }
            }
            if (s == 1000000) {
#pragma unroll
                for (int k = 0; k < 8; k++) asm volatile("st.volatile.shared.v2.u32 [%0], {%1, %2};" :: "r"(s), "r"(q[k].x), "r"(q[k].y) : "memory");
            }
            DBG(10, 8);
        }
    }
    const int wgt = __shfl_sync(0xffffffff, tid >> 7, 0);
    if (wgt == 1) {
        asm volatile("bar.arrive 8, 384;" ::: "memory");
        const uint32_t cx = CO_XB + (rank & 1) * 16384;
        auto copy = [&](uint32_t dst, uint32_t src, uint32_t bar) {
            asm volatile("cp.async.bulk.shared::cluster.shared::cta.mbarrier::complete_tx::bytes [%0], [%1], 4096, [%2];" :: "r"(dst), "r"(src), "r"(bar) : "memory");
        };
        if (tid == CH_ST) {
            copy(sb + cx + 4096, sb + CO_ST, bar_wo);
            copy((sb + cx + 4096) ^ (1u << 24), sb + CO_ST, bar_wo ^ (1u << 24));
            asm volatile("cp.async.bulk.wait_group 0;" ::: "memory");
            tma_load_2d_mc(sb + cx, &P.mapC, bar_wo, (rank & 1) * 64, h * SEQ + SEQ - 128, (uint16_t)(3 << (rank & 6)));
        }
        __syncwarp();
        asm volatile("bar.sync 7, 256;" ::: "memory");
#pragma unroll 1
        for (int i = 0; i < 2; i++) {
            local_pv(i, cx + 8192 + i * 4096);
            fence_async_smem();
            asm volatile("bar.arrive %0, 256;" :: "r"(i ? 14 : 9) : "memory");
            asm volatile("bar.sync 2, 128;" ::: "memory");
            if (tid == 128) copy((sb + cx + 8192 + i * 4096) ^ (1u << 24), sb + cx + 8192 + i * 4096, bar_w ^ (1u << 24));
            __syncwarp();
            if (i == 0) asm volatile("bar.sync 3, 256;" ::: "memory");
        }
        PT(14, 128);
    } else if (wgt == 2) {
        PT(11, 256);
        if (CH_GL < 2) load_gate(NSEG - 1);
        asm volatile("bar.arrive 15, 256;\nbar.sync 9, 256;" ::: "memory");
        float v[11];
        softmax(NSEG - 1, v);
        softmax1(v);
        softmax2(v);
        fence_async_smem();
        asm volatile("bar.arrive 3, 256;" ::: "memory");
    }
    __syncthreads();
    asm volatile("barrier.cluster.arrive.relaxed.aligned;\nbarrier.cluster.wait.aligned;" ::: "memory");
    TS_END(2);
}

struct Proj2Params {
    CUtensorMap mapA[2];
    CUtensorMap mapW[3];
    bf16* out[3];
};
#define P2T(i)
#define P2_NOMMA 0
#define P2_NOLOAD 0
#define P2_ROT 4
#define P2_NP 1
#define P2_NI 4
constexpr int P2_STAGES = 6;
constexpr int P2_ITEMS = 168 + 48;

__device__ __forceinline__ int p2_reps(int t) { return t >= 168 ? 1 : 2; }
__device__ __forceinline__ void p2_tile(int t, int w, int& z, int& mp, int& head) {
    if (t >= 168) { w += ((t - 168) & 1) * 2; t = 168 + ((t - 168) >> 1); }
    const int hq = (t / 24 + P2_ROT) & 7, v = t % 24;
    mp = v & 7;
    if (v < 16) { head = hq * 4 + (v >> 3) * 2 + (w >> 1); z = 1 + (w & 1); }
    else { head = hq * 4 + w; z = 0; }
}
__device__ __forceinline__ void mbar_arrive_remote(uint32_t bar_cluster_addr) {
    asm volatile("mbarrier.arrive.release.cluster.shared::cluster.b64 _, [%0];" :: "r"(bar_cluster_addr) : "memory");
}
__device__ __forceinline__ void mbar_arrive_cl(uint32_t bar_cluster_addr) {
    asm volatile("mbarrier.arrive.shared::cluster.b64 _, [%0];" :: "r"(bar_cluster_addr) : "memory");
}
__device__ __forceinline__ void mbar_wait_acq_cluster(uint32_t bar, uint32_t parity) {
    asm volatile(
        "{\n"
        ".reg .pred p, q;\n"
        ".reg .u32 c;\n"
        "mov.u32 c, 0;\n"
        "WAIT_LOOP_C:\n"
        "mbarrier.try_wait.parity.acquire.cluster.shared::cta.b64 p, [%0], %1;\n"
        "@p bra WAIT_DONE_C;\n"
        "add.u32 c, c, 1;\n"
        "setp.lt.u32 q, c, 4000000;\n"
        "@q bra WAIT_LOOP_C;\n"
        "WAIT_DONE_C:\n"
        "}\n" :: "r"(bar), "r"(parity) : "memory");
}
__device__ __forceinline__ uint4 quad_transpose(uint32_t p0, uint32_t p1, uint32_t p2, uint32_t p3, int lane) {
    const bool o1 = lane & 1, o2 = lane & 2;
    uint32_t s0 = o1 ? p0 : p1, s1 = o1 ? p2 : p3;
    s0 = __shfl_xor_sync(0xffffffff, s0, 1); s1 = __shfl_xor_sync(0xffffffff, s1, 1);
    const uint32_t a_lo = o1 ? s0 : p0, a_hi = o1 ? p1 : s0, b_lo = o1 ? s1 : p2, b_hi = o1 ? p3 : s1;
    uint32_t t0 = o2 ? a_lo : b_lo, t1 = o2 ? a_hi : b_hi;
    t0 = __shfl_xor_sync(0xffffffff, t0, 2); t1 = __shfl_xor_sync(0xffffffff, t1, 2);
    return o2 ? make_uint4(t0, t1, b_lo, b_hi) : make_uint4(a_lo, a_hi, t0, t1);
}
#define P2_PACE 35
#define P2_PACE2 0
#define P2_STM 1
#define P2_STQ ".L1::no_allocate"
#define P2_NOF 0
#define P2_HO 7
#define P2_PRE 0
template <int PACE>
__device__ __forceinline__ void store_frag_128(const float (&acc)[64], bf16* obase) {
    uint32_t p[32];
#pragma unroll
    for (int i = 0; i < 32; i++) p[i] = pack_bf16(acc[2 * i], acc[2 * i + 1]);
    if (P2_PRE) {
#pragma unroll
        for (int i = 0; i < 32; i += 8) asm volatile("" : "+r"(p[i]), "+r"(p[i + 1]), "+r"(p[i + 2]), "+r"(p[i + 3]), "+r"(p[i + 4]), "+r"(p[i + 5]), "+r"(p[i + 6]), "+r"(p[i + 7]));
    }
#pragma unroll
    for (int rr = 0; rr < 2; rr++)
#pragma unroll
        for (int g = 0; g < 4; g++) {
            const uint32_t* a = &p[g * 8 + rr];
            asm volatile("st.global" P2_STQ ".v4.b32 [%0], {%1, %2, %3, %4};" :: "l"(obase + (size_t)(rr * 8) * HD + g * 32), "r"(a[0]), "r"(a[2]), "r"(a[4]), "r"(a[6]) : "memory");
            pace(PACE);
        }
}
struct OutParams {
    CUtensorMap mapCtx[2];
    CUtensorMap mapWo[2];
    CUtensorMap mapOut;
};

#define OT(i)
#define OTP(i, th)
constexpr int O2_STAGES = 4;
constexpr int O2_GRID = 0;
#define O2_FINE 8
#define O2_Q0 8
#define O2_Q1 8
#define O2_QA 18

constexpr uint32_t OB_FULL = 0, OB_EMPTY = 32, OB_ITEM = 64, OB_SLOT = 128, OB_STOP = 160;
__device__ __forceinline__ void out_init(uint32_t bars) {
    for (int i = 0; i < O2_STAGES; i++) {
        mbar_init(bars + OB_FULL + 8 * i, 1); mbar_init(bars + OB_EMPTY + 8 * i, 4); mbar_init(bars + OB_ITEM + 16 * i, 1); mbar_init(bars + OB_ITEM + 16 * i + 8, 1);
    }
    sts128(bars + OB_STOP, 0u, 0u, 0u, 0u);
}
struct OutJob { int tg, q, qe, last, t0, nw, nq; };
__device__ __forceinline__ OutJob out_job(int cid, int j) {
    auto quota = [](int tg) { return tg & 2 ? O2_Q0 : O2_Q1; };
    if (cid < 28) { const int tg = cid % 14, h = cid >= 14, nq = 128 - quota(tg); return {tg, 2 * h, 2 * h + 2, 1, 2, nq / 2 - O2_FINE, nq}; }
    if (j == (cid < 30 ? 1 : 4)) return {16, 2 * cid + 8, 2 * cid + 10, 1, 38, 64 - O2_FINE, 128};
    if (cid < 30) return {cid - 14, O2_QA, 64, 0, 0, 0, 0};
    const int tg = (j * 4 + cid - 32) & 15;
    return {tg, tg >= 14 ? 0 : 128 - quota(tg), tg >= 14 ? O2_QA : 128, 0, 0, 0, 0};
}
__device__ __forceinline__ int out_mt(int tg, int rank) { return tg < 16 ? (tg & ~1) + rank : tg - 2; }
__device__ __forceinline__ int out_n0(int tg, int rank) { return (tg < 16 ? tg & 1 : rank) * 256; }
__device__ __forceinline__ void out_producer(const OutParams& P, uint32_t sbase, uint32_t bars, uint32_t rank, int cid, bool lead) {
    const uint32_t bar_full = bars + OB_FULL, bar_empty = bars + OB_EMPTY, bar_item = bars + OB_ITEM, slot = bars + OB_SLOT, stop = bars + OB_STOP;
    int s = 0, nb = 0; uint32_t ph = 0;
    if (lead) asm volatile("prefetch.tensormap [%0];" :: "l"(&P.mapOut) : "memory");
#pragma unroll 1
    for (int job = 0;; job++) {
        const OutJob J = out_job(cid, job);
        const int mt = out_mt(J.tg, rank), m0 = mt * 128, n0 = out_n0(J.tg, rank);
        int ready = 0, q = J.q, qe = J.qe, tnext = 0, nst = 0;
        if (lead && rank == 0 && J.last) tnext = take_ticket(CT_OT + J.tg);
#pragma unroll 1
        for (int ic = 0;; ic++) {
#pragma unroll 1
            for (bool first = true; q < qe; q++, first = false) {
                const int b = q >> 6, head = (q >> 1) & 31, dk = (q & 1) * 64;
                mbar_wait(bar_empty + 8 * s, ph);
                const uint32_t sa = sbase + s * 49152;
                if (lead) {
                    if (rank == 0 && J.last && first) {
                        const int t = tnext + J.t0;
                        asm volatile("st.shared.s32 [%0], %1;" :: "r"(slot + (ic & 7) * 4), "r"(t) : "memory");
                        mbar_arrive(bar_item + 8 * (ic & 7));
                        st_async_b32(mapa_u32(slot + (ic & 7) * 4, 1), (uint32_t)t, mapa_u32(bar_item + 8 * (ic & 7), 1));
                        if (J.nw + t < J.nq) tnext = take_ticket(CT_OT + J.tg);
                    }
                    if (b ? mt >= nb : !((ready >> (head >> 3)) & 1)) {
                        if (b) nb = max(mt, 11) + 1; else ready |= 1 << (head >> 3);
                        wait_ctr(b ? CT_CB + nb - 1 : CT_CA + mt * 4 + (head >> 3), b ? 64u : 16u);
                    }
                    asm volatile("st.shared.s32 [%0], %1;" :: "r"(stop + s * 4), "r"(0) : "memory");
                    mbar_expect_tx(bar_full + 8 * s, 49152);
                    tma_load_2d(sa, &P.mapCtx[b], bar_full + 8 * s, dk, head * SEQ + m0);
                    if (++nst == 6 && !(ready & 8)) { wait_ctr(CT_CA + mt * 4 + 3, 16u); ready |= 8; }
                } else if (J.tg < 16) {
                    for (int j = (int)rank * 2; j < (int)rank * 2 + 2; j++)
                        tma_load_2d_mc(sa + 16384 + j * 8192, &P.mapWo[b], bar_full + 8 * s, n0 + j * 64, head * HD + dk, (uint16_t)3);
                } else {
                    for (int j = 0; j < 4; j++) tma_load_2d(sa + 16384 + j * 8192, &P.mapWo[1], bar_full + 8 * s, n0 + j * 64, head * HD + dk);
                }
                if (++s == O2_STAGES) { s = 0; ph ^= 1; }
            }
            if (!J.last) break;
            if (lead && rank == 1) mbar_expect_tx(bar_item + 8 * (ic & 7), 4);
            mbar_wait(bar_item + 8 * (ic & 7), (ic >> 3) & 1);
            int t;
            asm volatile("ld.shared.s32 %0, [%1];" : "=r"(t) : "r"(slot + (ic & 7) * 4) : "memory");
            if (J.nw + t >= J.nq) break;
            if (t < J.nw) { q = 2 * t; qe = q + 2; } else { q = J.nw + t; qe = q + 1; }
        }
        if (lead) {
            if (!(ready & 8)) wait_ctr(CT_CA + mt * 4 + 3, 16u);
            mbar_wait(bar_empty + 8 * s, ph);
            asm volatile("st.shared.s32 [%0], %1;" :: "r"(stop + s * 4), "r"(1 + J.last + n0 + (m0 << 4)) : "memory");
            mbar_arrive(bar_full + 8 * s);
        }
        if (J.last) break;
        if (++s == O2_STAGES) { s = 0; ph ^= 1; }
    }
    if (lead) {
        out_finished();
        for (int i = 1; i < O2_STAGES; i++) {
            if (++s == O2_STAGES) { s = 0; ph ^= 1; }
            mbar_wait(bar_empty + 8 * s, ph);
        }
    }
}
__device__ __forceinline__ void out_consumer(const OutParams& P, uint32_t sbase, uint32_t bars, int warp, uint32_t opar) {
    const uint32_t bar_full = bars + OB_FULL, bar_empty = bars + OB_EMPTY, stop = bars + OB_STOP;
    int tid;
    asm volatile("mov.u32 %0, %%tid.x;" : "=r"(tid));
    const int wg = warp >> 2;
    const bool elected = (tid & 127) == 0;
    auto release = [&](int s) { if (elected) { const uint32_t e = bar_empty + 8 * s; mbar_arrive_cl(mapa_u32(e, 0)); mbar_arrive_cl(mapa_u32(e, 1)); } };
    float acc[128];
    int s = 0, sprev = 0, st, n = 0; uint32_t ph = 0;
#pragma unroll 1
    do {
#pragma unroll 1
        for (int i = 0;; i++, n++) {
            mbar_wait(bar_full + 8 * s, ph);
            asm volatile("ld.shared.s32 %0, [%1];" : "=r"(st) : "r"(stop + s * 4) : "memory");
            if (st) break;
            if (n == 0) OT(1);
            const uint32_t sa = sbase + s * 49152 + wg * 8192, sb = sbase + s * 49152 + 16384;
            wgmma_fence();
#pragma unroll
            for (int kk = 0; kk < 4; kk++)
                wgmma_ss_n256_tb(acc, make_desc(sa + kk * 32, 16, 1024), make_desc(sb + kk * 2048, 8192, 1024), kk ? 1 : i);
            wgmma_commit();
            if (i > 0) { wgmma_wait<1>(); release(sprev); }
            if (i == 1 && n > 1) {
                if (elected) asm volatile("cp.async.bulk.wait_group.read 0;" ::: "memory");
                release((s + 2) & 3);
            }
            sprev = s;
            if (++s == O2_STAGES) { s = 0; ph ^= 1; }
        }
        mbar_wait(sbase + FB_OE + 8 * wg, opar);
        wgmma_wait<0>();
        release(sprev);
        asm volatile("bar.sync %0, 128;" :: "r"(1 + wg) : "memory");
        OT(3);
        out_flush(acc, &P.mapOut, sbase + s * 49152 + wg * 16384, sbase + O2_STAGES * 49152 + wg * 16384, tid, 1 + wg, st & 256, (st >> 4 & ~127) + wg * 64);
        if (++s == O2_STAGES) { s = 0; ph ^= 1; }
    } while (!(st & 2));
    OT(4);
    if (elected) {
        asm volatile("cp.async.bulk.wait_group.read 0;" ::: "memory");
    }
}

struct MainParams { Proj2Params p; AttnParams a; OutParams o; const bf16 *x, *gate_w; };
__device__ __forceinline__ int p2_apos(int k) { return k < 2 ? k : k < 6 ? k + 2 : k - 4; }
__global__ void __cluster_dims__(2, 1, 1) __launch_bounds__(384, 1) main_kernel(const __grid_constant__ MainParams MP) {
    const Proj2Params& P = MP.p;
    extern __shared__ uint8_t smem_raw[];
    const uint32_t rank = cluster_ctarank();
    const uint32_t sbase = (rank << 24) + SD;
    if (smem_u32(smem_raw) != sbase) __trap();
    const uint32_t sA = sbase, sB = sbase + 131072;
    const uint32_t bars = sbase + MO_BAR, obars = bars + 768;
    const uint32_t a_full = bars, a_empty = bars + 64, b_full = bars + 128, b_empty = b_full + 8 * P2_STAGES;
    const uint32_t item_bar = b_empty + 8 * P2_STAGES, item_in = item_bar + 16, slot = item_in + 16;
    const uint32_t note_bar = slot + 16, note_free = note_bar + 64, note = note_free + 64;
    const int warp = __shfl_sync(0xffffffff, threadIdx.x >> 5, 0), lane = threadIdx.x & 31;
    TS_BEGIN(0);
    if (threadIdx.x == 0) {
        for (int i = 0; i < 8; i++) { mbar_init(a_full + 8 * i, 1); mbar_init(a_empty + 8 * i, 2); }
        for (int i = 0; i < P2_STAGES; i++) { mbar_init(b_full + 8 * i, 1); mbar_init(b_empty + 8 * i, 2); }
        mbar_init(item_bar, 1); mbar_init(item_bar + 8, 1); mbar_init(item_in, 2); mbar_init(item_in + 8, 2);
        for (int i = 0; i < 8; i++) { mbar_init(note_bar + 8 * i, 4); mbar_init(note_free + 8 * i, 1); }
        asm volatile("fence.mbarrier_init.release.cluster;" ::: "memory");
    }
    if (threadIdx.x == 32) {
        attn_init(sbase);
        asm volatile("fence.mbarrier_init.release.cluster;" ::: "memory");
    }
    if (threadIdx.x == 256) {
        out_init(obars);
        asm volatile("fence.mbarrier_init.release.cluster;" ::: "memory");
    }
    __syncthreads();
    asm volatile("barrier.cluster.arrive.relaxed.aligned;" ::: "memory");
    if (warp >= 8) {
    asm volatile("setmaxnreg.dec.sync.aligned.u32 40;");
    asm volatile("barrier.cluster.wait.aligned;" ::: "memory");
    if (warp == 9) {
        if (lane == 0) {
            for (int n = 0;; n++) {
                const int e = (n & 1) * 4 + ((n >> 1) & 3);
                mbar_wait(note_bar + 8 * e, (n >> 3) & 1);
                int m;
                asm volatile("ld.shared.s32 %0, [%1];" : "=r"(m) : "r"(note + e * 4) : "memory");
                mbar_arrive(note_free + 8 * e);
                if (m < 0) break;
                signal_ctr(m);
            }
            attn_helper(MP.a, sbase, 0);
        }
    } else if (warp == 10) {
        if (lane == 0) {
            auto publish = [&](int ic, int tq) {
                const int t = tq < P2_ITEMS ? tq : -1;
                asm volatile("st.shared.s32 [%0], %1;" :: "r"(slot + (ic & 3) * 4), "r"(t) : "memory");
                mbar_arrive(item_bar + 8 * (ic & 1));
                st_async_b32(mapa_u32(slot + (ic & 3) * 4, 1), (uint32_t)t, mapa_u32(item_bar + 8 * (ic & 1), 1));
            };
            const int npair = M_GRID / 2, pair = (int)(blockIdx.x >> 1);
            if (rank == 0) publish(0, pair);
            for (int ic = 0;; ic++) {
                if (rank == 1) mbar_expect_tx(item_bar + 8 * (ic & 1), 4);
                mbar_wait(item_bar + 8 * (ic & 1), (ic >> 1) & 1);
                int t;
                asm volatile("ld.shared.s32 %0, [%1];" : "=r"(t) : "r"(slot + (ic & 3) * 4) : "memory");
                if (t < 0) break;
                int z0, mp, h0;
                p2_tile(t, 0, z0, mp, h0);
                const int aidx = z0 >= 1 ? 1 : 0;
                const int m0 = (2 * mp + (int)rank) * 128;
                for (int k = 0; k < 8; k++) {
                    mbar_wait(a_empty + 8 * k, (ic & 1) ^ 1);
                    if (P2_NOLOAD) mbar_arrive(a_full + 8 * k); else {
                    mbar_expect_tx(a_full + 8 * k, 16384);
                    tma_load_2d(sA + p2_apos(k) * 16384, &P.mapA[aidx], a_full + 8 * k, k * 64, m0); }
                }
                if (rank == 0) {
                    mbar_wait(item_in + 8 * (ic & 1), (ic >> 1) & 1);
                    publish(ic + 1, ic == 0 ? npair + pair : pair < P2_NP && ic + 1 >= P2_NI ? P2_ITEMS : 2 * npair + (int)atomicAdd(&g_ctr[CT_PROJ], 1u));
                }
            }
            attn_helper(MP.a, sbase, 1);
        }
    } else {
        if (lane == 0) {
            const int par2 = warp == 8 ? 0 : 1;
            int it = 0, ic = 0; uint32_t bph = 0;
            for (;; ic++) {
                mbar_wait(item_bar + 8 * (ic & 1), (ic >> 1) & 1);
                int t;
                asm volatile("ld.shared.s32 %0, [%1];" : "=r"(t) : "r"(slot + (ic & 3) * 4) : "memory");
                if (t < 0) break;
                const int nt = 2 * p2_reps(t);
                for (int w = 0; w < nt; w++) {
                    int z, mp, hd;
                    p2_tile(t, w, z, mp, hd);
                    for (int k = 0; k < 8; k++) {
                        const int s = it; const uint32_t phb = bph;
                        if (++it == P2_STAGES) { it = 0; bph ^= 1; }
                        if ((k & 1) != par2) continue;
                        mbar_wait(b_empty + 8 * s, phb ^ 1);
                        if (P2_NOLOAD) { mbar_arrive(b_full + 8 * s); continue; }
                        mbar_expect_tx(b_full + 8 * s, 16384);
                        tma_load_2d_mc(sB + s * 16384 + rank * 8192, &P.mapW[z], b_full + 8 * s, hd * 128 + (int)rank * 64, k * 64, (uint16_t)3);
                    }
                }
            }
            if (warp == 8) {
                attn_producer(MP.a, sbase, a_empty, ~ic & 1);
                TS_END2(1, 256); TS_BEGIN2(3, 256);
                for (int i = 0; i < 4; i++) {
                    const uint32_t e = mapa_u32(obars + OB_EMPTY + 8 * (i & 1), i >> 1);
                    mbar_arrive_cl(e); mbar_arrive_cl(e);
                }
            }
            out_producer(MP.o, sbase, obars, rank, blockIdx.x >> 1, warp == 8);
            TS_END2(3, 256);
        }
    }
    } else {
        asm volatile("setmaxnreg.inc.sync.aligned.u32 232;");
        asm volatile("barrier.cluster.wait.aligned;" ::: "memory");
        const int wg = warp >> 2;
        float acc[2][64];
        const uint32_t a_lo = desc_lo(SD, 16), b_lo0 = desc_lo(SD + 131072, 8192);
        const bool elected = (threadIdx.x & 127) == 0;
        int s = (wg * 8) % P2_STAGES;
        uint32_t ph = ((wg * 8) / P2_STAGES) & 1;
        int nnote = 0;
        if (wg == 1) {
            asm volatile("bar.arrive 3, 256;" ::: "memory");
            if (blockIdx.x < 64) {
                const int r = blockIdx.x * 32 + (warp & 3) * 8 + (lane >> 2);
                float c[4] = {0.f, 0.f, 0.f, 0.f};
                uint4 xv[16], gv[16];
#pragma unroll
                for (int i = 0; i < 16; i++) {
                    xv[i] = __ldg(reinterpret_cast<const uint4*>(MP.x + (size_t)r * DM + i * 32 + (lane & 3) * 8));
                    gv[i] = __ldg(reinterpret_cast<const uint4*>(MP.gate_w + i * 32 + (lane & 3) * 8));
                }
                auto mul = [](uint32_t a, uint32_t b) { uint32_t p; asm("mul.rn.bf16x2 %0, %1, %2;" : "=r"(p) : "r"(a), "r"(b)); return p; };
#pragma unroll
                for (int i = 0; i < 16; i++)
                    mma_16816(c, mul(xv[i].x, gv[i].x), mul(xv[i].y, gv[i].y), mul(xv[i].z, gv[i].z), mul(xv[i].w, gv[i].w), 0x3f803f80u, 0x3f803f80u);
                if ((lane & 3) == 0) g_gate[r] = bf16r(__fdividef(1.f, 1.f + __expf(-bf16r(c[0] + c[2]))));
                __syncwarp();
                if (lane == 0) signal_ctr_generic(CT_GATE);
                __syncwarp();
            }
        }
        auto next_item = [&](int ic) {
            mbar_wait(item_bar + 8 * (ic & 1), (ic >> 1) & 1);
            int t;
            asm volatile("ld.shared.s32 %0, [%1];" : "=r"(t) : "r"(slot + (ic & 3) * 4) : "memory");
            return __shfl_sync(0xffffffff, t, 0);
        };
        int t = next_item(0), ic = 0, rp = 0;
#pragma unroll 1
        while (t >= 0) {
            const bool first = rp == 0, last = rp == p2_reps(t) - 1;
            asm volatile("bar.sync %0, 256;" :: "r"(3 + wg) : "memory");
            P2T(0);
            if (wg == 1 && last && elected) mbar_arrive_cl(mapa_u32(item_in + 8 * (ic & 1), 0));
            int sprev = 0;
#pragma unroll
            for (int k = 0; k < 8; k++) {
                if (k == 0) P2T(5);
                if ((wg == 0 || k > P2_HO) && first) mbar_wait(a_full + 8 * k, ic & 1);
                if (k == 0) P2T(6);
                mbar_wait(b_full + 8 * s, ph);
                if (k == P2_HO) asm volatile("bar.arrive %0, 256;" :: "r"(4 - wg) : "memory");
                if (k == 0) P2T(1);
                if (k == 7) P2T(2);
                const uint32_t b_lo = b_lo0 + s * 1024;
                if (k == 0 || !P2_NOF) wgmma_fence();
#pragma unroll
                for (int kk = 0; kk < (P2_NOMMA ? 1 : 4); kk++) {
                    wgmma_ss_n128_lo<1>(acc[0], a_lo + p2_apos(k) * 1024 + kk * 2, b_lo + kk * 128, (k | kk) != 0);
                    wgmma_ss_n128_lo<1>(acc[1], a_lo + p2_apos(k) * 1024 + 512 + kk * 2, b_lo + kk * 128, (k | kk) != 0);
                }
                wgmma_commit();
                if (k > 0) {
                    wgmma_wait<1>();
                    if (elected) {
                        const uint32_t e = b_empty + 8 * sprev;
                        mbar_arrive_cl(mapa_u32(e, 0)); mbar_arrive_cl(mapa_u32(e, 1));
                        if (last) mbar_arrive(a_empty + 8 * (k - 1));
                    }
                }
                sprev = s;
                if (++s == P2_STAGES) { s = 0; ph ^= 1; }
            }
            int z, mp, head;
            p2_tile(t, rp * 2 + wg, z, mp, head);
            const int m0 = (2 * mp + (int)rank) * 128, en = wg * 4 + (nnote & 3);
            bf16* obase = P.out[z] + ((size_t)head * SEQ + m0 + (warp & 3) * 16 + (lane >> 2)) * HD + (lane & 3) * 8;
            if (elected) {
                mbar_wait(note_free + 8 * en, ((nnote >> 2) & 1) ^ 1);
                asm volatile("st.shared.s32 [%0], %1;" :: "r"(note + en * 4), "r"(CT_AP + (head >> 1)) : "memory");
            }
            __syncwarp();
            nnote++;
            wgmma_wait<0>();
            P2T(3);
            if (elected) {
                const uint32_t e = b_empty + 8 * sprev;
                mbar_arrive_cl(mapa_u32(e, 0)); mbar_arrive_cl(mapa_u32(e, 1));
                if (last) mbar_arrive(a_empty + 8 * 7);
            }
            s += 8 % P2_STAGES; ph ^= (8 / P2_STAGES) & 1;
            if (s >= P2_STAGES) { s -= P2_STAGES; ph ^= 1; }
            store_frag_128<P2_PACE>(acc[0], obase);
            if (last) { t = next_item(++ic); rp = 0; P2T(7); } else rp++;
            store_frag_128<P2_PACE>(acc[1], obase + (size_t)64 * HD);
            __syncwarp();
            if (lane == 0) mbar_arrive(note_bar + 8 * en);
            __syncwarp();
        }
        if (wg == 0 && lane == 0) {
            const int e = nnote & 3;
            if (elected) {
                mbar_wait(note_free + 8 * e, ((nnote >> 2) & 1) ^ 1);
                asm volatile("st.shared.s32 [%0], %1;" :: "r"(note + e * 4), "r"(-1) : "memory");
            }
            mbar_arrive(note_bar + 8 * e);
        }
        auto done = [&]() {
            if ((threadIdx.x & 127) == 0) for (int i = 0; i < 4; i++) mbar_arrive_cl(SD + MO_BAR + 768 + OB_EMPTY + 16 + 8 * (i & 1) + ((i >> 1) << 24));
        };
        asm volatile("bar.sync %0, 128;" :: "r"(1 + wg) : "memory");
        const int nout = rank == 0 ? attn_consumer<SD>(MP.a, warp, done) : attn_consumer<SD + (1u << 24)>(MP.a, warp, done);
        OT(0);
        const uint32_t sb2 = (cluster_ctarank() << 24) + SD;
        out_consumer(MP.o, sb2, sb2 + MO_BAR + 768, warp, nout & 1);
    }
}

typedef CUresult (*PFN_encodeTiled)(CUtensorMap*, CUtensorMapDataType, cuuint32_t, void*, const cuuint64_t*,
                                    const cuuint64_t*, const cuuint32_t*, const cuuint32_t*, CUtensorMapInterleave,
                                    CUtensorMapSwizzle, CUtensorMapL2promotion, CUtensorMapFloatOOBfill);
static PFN_encodeTiled g_encode = nullptr;

static void make_map(CUtensorMap* m, const void* ptr, uint64_t rows, uint64_t cols, uint32_t box_rows, bool sw64 = false) {
    cuuint64_t dims[2] = {cols, rows};
    cuuint64_t strides[1] = {cols * 2};
    cuuint32_t box[2] = {sw64 ? 32u : 64u, box_rows};
    cuuint32_t es[2] = {1, 1};
    g_encode(m, CU_TENSOR_MAP_DATA_TYPE_BFLOAT16, 2, const_cast<void*>(ptr), dims, strides, box, es,
             CU_TENSOR_MAP_INTERLEAVE_NONE, sw64 ? CU_TENSOR_MAP_SWIZZLE_64B : CU_TENSOR_MAP_SWIZZLE_128B, CU_TENSOR_MAP_L2_PROMOTION_L2_256B,
             CU_TENSOR_MAP_FLOAT_OOB_FILL_NONE);
}

template <typename... KArgs, typename... Args>
static void launch_pdl(void (*kernel)(KArgs...), int grid, int block, size_t smem, cudaStream_t st, bool pdl, Args... args) {
    cudaLaunchConfig_t cfg = {};
    cfg.gridDim = dim3(grid); cfg.blockDim = dim3(block); cfg.dynamicSmemBytes = smem; cfg.stream = st;
    cudaLaunchAttribute at[1];
    at[0].id = cudaLaunchAttributeProgrammaticStreamSerialization;
    at[0].val.programmaticStreamSerializationAllowed = 1;
    cfg.attrs = at; cfg.numAttrs = pdl ? 1 : 0;
    cudaLaunchKernelEx(&cfg, kernel, KArgs(args)...);
}

extern "C" void kernel_launch(void* const* d_in, const int* in_sizes, int n_in, void* d_out, int out_size) {
    const bf16* x = (const bf16*)d_in[0];
    const bf16* ckv = (const bf16*)d_in[1];
    const bf16* wq = (const bf16*)d_in[2];
    const bf16* wuk = (const bf16*)d_in[3];
    const bf16* wuv = (const bf16*)d_in[4];
    const bf16* wo = (const bf16*)d_in[5];
    const bf16* mem0 = (const bf16*)d_in[7];
    const bf16* Wq = (const bf16*)d_in[8];
    const bf16* Wk = (const bf16*)d_in[9];
    const bf16* Wv = (const bf16*)d_in[10];
    const bf16* Wo = (const bf16*)d_in[11];
    const bf16* gate_w = (const bf16*)d_in[13];
    bf16* out = (bf16*)d_out;

    static MainParams MP;
    static ChainParams CP;
    Proj2Params& P2 = MP.p;
    AttnParams& AP = MP.a;
    OutParams& OP = MP.o;
    static bool init = false;
    static const void* last_in[14];
    static const void* last_out;
    bool same = init && last_out == d_out;
    for (int i = 0; i < 14 && same; i++) same = last_in[i] == d_in[i];
    if (!init) {
        cudaDriverEntryPointQueryResult qr;
        cudaGetDriverEntryPoint("cuTensorMapEncodeTiled", (void**)&g_encode, cudaEnableDefault, &qr);
        cudaFuncSetAttribute(main_kernel, cudaFuncAttributeMaxDynamicSharedMemorySize, M_SMEM);
        cudaFuncSetAttribute(chain_kernel, cudaFuncAttributeMaxDynamicSharedMemorySize, CH_SMEM);
        init = true;
    }
    if (!same) {
        for (int i = 0; i < 14; i++) last_in[i] = d_in[i];
        last_out = d_out;
        void *pQA, *pKA, *pVA, *pCA, *pCB;
        cudaGetSymbolAddress(&pQA, g_QA); cudaGetSymbolAddress(&pKA, g_KA); cudaGetSymbolAddress(&pVA, g_VA);
        cudaGetSymbolAddress(&pCA, g_ctxA); cudaGetSymbolAddress(&pCB, g_ctxB);
        make_map(&P2.mapA[0], x, SEQ, DM, 128);
        make_map(&P2.mapA[1], ckv, SEQ, DM, 128);
        const void* ws[3] = {wq, wuk, wuv};
        void* cs[3] = {pQA, pKA, pVA};
        for (int i = 0; i < 3; i++) { make_map(&P2.mapW[i], ws[i], DM, NQ, 64); P2.out[i] = (bf16*)cs[i]; }
        make_map(&CP.mapW[0], Wq, DM, NQ, 64); make_map(&CP.mapW[1], Wk, DM, NQ, 64); make_map(&CP.mapW[2], Wv, DM, NQ, 32);
        make_map(&CP.mapX, x, SEQ, DM, 32);
        make_map(&CP.mapWo, Wo, NQ, DM, 64);
        make_map(&CP.mapM, mem0, NMEM, DM, 8);
        MP.x = x; MP.gate_w = gate_w;
        make_map(&CP.mapC, pCB, NH * SEQ, HD, 32);
        make_map(&AP.mapQ, pQA, NH * SEQ, HD, 128);
        make_map(&AP.mapK, pKA, NH * SEQ, HD, 128);
        make_map(&AP.mapV, pVA, NH * SEQ, HD, 128);
        make_map(&AP.mapO, pCA, NH * SEQ, HD, 64);
        make_map(&OP.mapCtx[0], pCA, NH * SEQ, HD, 128);
        make_map(&OP.mapCtx[1], pCB, NH * SEQ, HD, 128);
        make_map(&OP.mapWo[0], wo, NQ, DM, 64);
        make_map(&OP.mapWo[1], Wo, NQ, DM, 64);
        make_map(&OP.mapOut, out, SEQ, DM, 64);
        CP.mapOut = OP.mapOut;
        AP.out = out;
    }
    cudaStream_t s1 = cudaStreamPerThread;
    const bool pdl = true;
    launch_pdl(chain_kernel, 64, CH_BLOCK, CH_SMEM, s1, false, CP);
    launch_pdl(main_kernel, M_GRID, 384, M_SMEM, s1, pdl, MP);
}
```

```cpp
#include <cuda_runtime.h>
#include <cuda_bf16.h>
#include <cuda.h>
#include <stdint.h>
#include <type_traits>

constexpr int SEQ = 2048;
constexpr int DM = 512;
constexpr int NH = 32;
constexpr int HD = 128;
constexpr int NQ = NH * HD;
constexpr int SEGL = 32;
constexpr int NMEM = 8;
constexpr int NSEG = SEQ / SEGL;

typedef __nv_bfloat16 bf16;

__device__ bf16 g_QA[SEQ * NQ];
__device__ bf16 g_KA[SEQ * NQ];
__device__ bf16 g_VA[SEQ * NQ];
__device__ bf16 g_ctxA[SEQ * NQ];
__device__ bf16 g_ctxB[SEQ * NQ];
constexpr int CT_PROJ = 0, CT_ATTN = 1, CT_FIN = 5;
constexpr int CT_AP = 64;
constexpr int CT_GATE = 96;
constexpr int CT_CA = 128;
constexpr int CT_CB = 193;
constexpr int CT_OT = 208;
constexpr int CT_N = 228;
__device__ __align__(16) unsigned int g_ctr[CT_N];
__device__ float g_gate[SEQ];
#define XB8(v) v, v, v, v, v, v, v, v
__device__ uint32_t g_xbuf[4 * 8 * 2048] = {XB8(XB8(XB8(XB8(XB8(~0u)))))};

#define FA_GRID 68

#define TS_BEGIN(id)
#define TS_END(id)
#define TS_BEGIN2(id, th)
#define TS_END2(id, th)
#define WAIT_LIMIT 200000
__device__ __forceinline__ void pdl_launch_dependents() { asm volatile("griddepcontrol.launch_dependents;" ::: "memory"); }
__device__ __forceinline__ void wait_ctr(int idx, unsigned int n) {
    unsigned int v; int it = 0;
    do { asm volatile("ld.acquire.gpu.global.u32 %0, [%1];" : "=r"(v) : "l"(&g_ctr[idx]) : "memory"); } while (v < n && ++it < WAIT_LIMIT);
    asm volatile("fence.proxy.async.shared::cta;" ::: "memory");
}
__device__ __forceinline__ int take_ticket(int idx) {
    int v;
    asm volatile("atom.relaxed.gpu.global.inc.u32 %0, [%1], 0x7fffffff;" : "=r"(v) : "l"(&g_ctr[idx]) : "memory");
    return v;
}
__device__ __forceinline__ void signal_ctr(int idx) {
    asm volatile("fence.proxy.async;" ::: "memory");
    __threadfence();
    atomicAdd(&g_ctr[idx], 1u);
}
__device__ __forceinline__ void signal_ctr_generic(int idx) {
    asm volatile("red.release.gpu.global.add.u32 [%0], 1;" :: "l"(&g_ctr[idx]) : "memory");
}
__device__ __forceinline__ uint32_t smem_u32(const void* p) {
    return (uint32_t)__cvta_generic_to_shared(p);
}
__device__ __forceinline__ void mbar_init(uint32_t bar, uint32_t count) {
    asm volatile("mbarrier.init.shared::cta.b64 [%0], %1;" :: "r"(bar), "r"(count));
}
__device__ __forceinline__ void mbar_expect_tx(uint32_t bar, uint32_t bytes) {
    asm volatile("mbarrier.arrive.expect_tx.shared::cta.b64 _, [%0], %1;" :: "r"(bar), "r"(bytes) : "memory");
}
__device__ __forceinline__ void mbar_arrive(uint32_t bar) {
    asm volatile("mbarrier.arrive.shared::cta.b64 _, [%0];" :: "r"(bar) : "memory");
}
__device__ __forceinline__ void mbar_wait(uint32_t bar, uint32_t parity) {
    asm volatile(
        "{\n"
        ".reg .pred p, q;\n"
        ".reg .u32 c;\n"
        "mov.u32 c, 0;\n"
        "WAIT_LOOP:\n"
        "mbarrier.try_wait.parity.shared::cta.b64 p, [%0], %1;\n"
        "@p bra WAIT_DONE;\n"
        "add.u32 c, c, 1;\n"
        "setp.lt.u32 q, c, %2;\n"
        "@q bra WAIT_LOOP;\n"
        "WAIT_DONE:\n"
        "}\n" :: "r"(bar), "r"(parity), "n"(WAIT_LIMIT) : "memory");
}
__device__ __forceinline__ uint32_t mbar_test(uint32_t bar, uint32_t parity) {
    uint32_t done;
    asm volatile(
        "{\n.reg .pred p;\n"
        "mbarrier.test_wait.parity.shared::cta.b64 p, [%1], %2;\n"
        "selp.u32 %0, 1, 0, p;\n}\n" : "=r"(done) : "r"(bar), "r"(parity) : "memory");
    return done;
}
__device__ __forceinline__ uint32_t mbar_try(uint32_t bar, uint32_t parity) {
    uint32_t done;
    asm volatile(
        "{\n.reg .pred p;\n"
        "mbarrier.try_wait.parity.shared::cta.b64 p, [%1], %2;\n"
        "selp.u32 %0, 1, 0, p;\n}\n" : "=r"(done) : "r"(bar), "r"(parity) : "memory");
    return done;
}
__device__ __forceinline__ void tma_load_2d(uint32_t dst, const CUtensorMap* map, uint32_t bar, int c0, int c1) {
    asm volatile(
        "cp.async.bulk.tensor.2d.shared::cluster.global.mbarrier::complete_tx::bytes [%0], [%1, {%3, %4}], [%2];"
        :: "r"(dst), "l"((uint64_t)map), "r"(bar), "r"(c0), "r"(c1) : "memory");
}
__device__ __forceinline__ void wgmma_fence() { asm volatile("wgmma.fence.sync.aligned;" ::: "memory"); }
__device__ __forceinline__ void wgmma_commit() { asm volatile("wgmma.commit_group.sync.aligned;" ::: "memory"); }
template <int N> __device__ __forceinline__ void wgmma_wait() {
    asm volatile("wgmma.wait_group.sync.aligned %0;" :: "n"(N) : "memory");
}
__device__ __forceinline__ uint64_t make_desc(uint32_t addr, uint32_t lbo, uint32_t sbo) {
    uint64_t d = 0;
    d |= (uint64_t)((addr & 0x3FFFF) >> 4);
    d |= (uint64_t)((lbo >> 4) & 0x3FFF) << 16;
    d |= (uint64_t)((sbo >> 4) & 0x3FFF) << 32;
    d |= (uint64_t)1 << 62;
    return d;
}

#define ACC64(d) \
    "+f"(d[0]), "+f"(d[1]), "+f"(d[2]), "+f"(d[3]), "+f"(d[4]), "+f"(d[5]), "+f"(d[6]), "+f"(d[7]), \
    "+f"(d[8]), "+f"(d[9]), "+f"(d[10]), "+f"(d[11]), "+f"(d[12]), "+f"(d[13]), "+f"(d[14]), "+f"(d[15]), \
    "+f"(d[16]), "+f"(d[17]), "+f"(d[18]), "+f"(d[19]), "+f"(d[20]), "+f"(d[21]), "+f"(d[22]), "+f"(d[23]), \
    "+f"(d[24]), "+f"(d[25]), "+f"(d[26]), "+f"(d[27]), "+f"(d[28]), "+f"(d[29]), "+f"(d[30]), "+f"(d[31]), \
    "+f"(d[32]), "+f"(d[33]), "+f"(d[34]), "+f"(d[35]), "+f"(d[36]), "+f"(d[37]), "+f"(d[38]), "+f"(d[39]), \
    "+f"(d[40]), "+f"(d[41]), "+f"(d[42]), "+f"(d[43]), "+f"(d[44]), "+f"(d[45]), "+f"(d[46]), "+f"(d[47]), \
    "+f"(d[48]), "+f"(d[49]), "+f"(d[50]), "+f"(d[51]), "+f"(d[52]), "+f"(d[53]), "+f"(d[54]), "+f"(d[55]), \
    "+f"(d[56]), "+f"(d[57]), "+f"(d[58]), "+f"(d[59]), "+f"(d[60]), "+f"(d[61]), "+f"(d[62]), "+f"(d[63])
#define ACC64_STR \
    "{%0, %1, %2, %3, %4, %5, %6, %7, %8, %9, %10, %11, %12, %13, %14, %15, " \
    "%16, %17, %18, %19, %20, %21, %22, %23, %24, %25, %26, %27, %28, %29, %30, %31, " \
    "%32, %33, %34, %35, %36, %37, %38, %39, %40, %41, %42, %43, %44, %45, %46, %47, " \
    "%48, %49, %50, %51, %52, %53, %54, %55, %56, %57, %58, %59, %60, %61, %62, %63}"

template <int TB>
__device__ __forceinline__ void wgmma_ss_n128(float (&d)[64], uint64_t da, uint64_t db, int scale_d) {
    asm volatile(
        "{\n.reg .pred p;\nsetp.ne.b32 p, %66, 0;\n"
        "wgmma.mma_async.sync.aligned.m64n128k16.f32.bf16.bf16 " ACC64_STR ", %64, %65, p, 1, 1, 0, %67;\n}\n"
        : ACC64(d) : "l"(da), "l"(db), "r"(scale_d), "n"(TB));
}
__device__ __forceinline__ uint32_t desc_lo(uint32_t addr, uint32_t lbo) { return ((addr & 0x3FFFF) >> 4) | ((lbo >> 4) << 16); }
template <int TB>
__device__ __forceinline__ void wgmma_ss_n128_lo(float (&d)[64], uint32_t da_lo, uint32_t db_lo, int scale_d) {
    asm volatile(
        "{\n.reg .pred p;\n.reg .b64 da, db;\nsetp.ne.b32 p, %66, 0;\n"
        "mov.b64 da, {%64, 0x40000040};\nmov.b64 db, {%65, 0x40000040};\n"
        "wgmma.mma_async.sync.aligned.m64n128k16.f32.bf16.bf16 " ACC64_STR ", da, db, p, 1, 1, 0, %67;\n}\n"
        : ACC64(d) : "r"(da_lo), "r"(db_lo), "r"(scale_d), "n"(TB));
}
__device__ __forceinline__ void wgmma_rs_n128_tb(float (&d)[64], uint32_t a0, uint32_t a1, uint32_t a2, uint32_t a3,
                                                 uint64_t db, int scale_d) {
    asm volatile(
        "{\n.reg .pred p;\nsetp.ne.b32 p, %69, 0;\n"
        "wgmma.mma_async.sync.aligned.m64n128k16.f32.bf16.bf16 " ACC64_STR ", {%64, %65, %66, %67}, %68, p, 1, 1, 1;\n}\n"
        : ACC64(d) : "r"(a0), "r"(a1), "r"(a2), "r"(a3), "l"(db), "r"(scale_d));
}
__device__ __forceinline__ void wgmma_rs_n80(float (&d)[40], const uint32_t (&a)[4], uint32_t db_lo, int scale_d) {
    asm volatile(
        "{\n.reg .pred p;\n.reg .b64 db;\nsetp.ne.b32 p, %45, 0;\nmov.b64 db, {%44, 0x40000040};\n"
        "wgmma.mma_async.sync.aligned.m64n80k16.f32.bf16.bf16 "
        "{%0, %1, %2, %3, %4, %5, %6, %7, %8, %9, %10, %11, %12, %13, %14, %15, %16, %17, %18, %19, %20, %21, %22, %23, %24, %25, %26, %27, %28, %29, %30, %31, %32, %33, %34, %35, %36, %37, %38, %39}, "
        "{%40, %41, %42, %43}, db, p, 1, 1, 0;\n}\n"
        : "+f"(d[0]), "+f"(d[1]), "+f"(d[2]), "+f"(d[3]), "+f"(d[4]), "+f"(d[5]), "+f"(d[6]), "+f"(d[7]), "+f"(d[8]), "+f"(d[9]), "+f"(d[10]), "+f"(d[11]), "+f"(d[12]), "+f"(d[13]), "+f"(d[14]), "+f"(d[15]), "+f"(d[16]), "+f"(d[17]), "+f"(d[18]), "+f"(d[19]), "+f"(d[20]), "+f"(d[21]), "+f"(d[22]), "+f"(d[23]), "+f"(d[24]), "+f"(d[25]), "+f"(d[26]), "+f"(d[27]), "+f"(d[28]), "+f"(d[29]), "+f"(d[30]), "+f"(d[31]), "+f"(d[32]), "+f"(d[33]), "+f"(d[34]), "+f"(d[35]), "+f"(d[36]), "+f"(d[37]), "+f"(d[38]), "+f"(d[39])
        : "r"(a[0]), "r"(a[1]), "r"(a[2]), "r"(a[3]), "r"(db_lo), "r"(scale_d));
}
__device__ __forceinline__ void wgmma_ss_n256_tb(float (&d)[128], uint64_t da, uint64_t db, int scale_d) {
    asm volatile(
        "{\n.reg .pred p;\nsetp.ne.b32 p, %130, 0;\n"
        "wgmma.mma_async.sync.aligned.m64n256k16.f32.bf16.bf16 {%0, %1, %2, %3, %4, %5, %6, %7, %8, %9, %10, %11, %12, %13, %14, %15, %16, %17, %18, %19, %20, %21, %22, %23, %24, %25, %26, %27, %28, %29, %30, %31, %32, %33, %34, %35, %36, %37, %38, %39, %40, %41, %42, %43, %44, %45, %46, %47, %48, %49, %50, %51, %52, %53, %54, %55, %56, %57, %58, %59, %60, %61, %62, %63, %64, %65, %66, %67, %68, %69, %70, %71, %72, %73, %74, %75, %76, %77, %78, %79, %80, %81, %82, %83, %84, %85, %86, %87, %88, %89, %90, %91, %92, %93, %94, %95, %96, %97, %98, %99, %100, %101, %102, %103, %104, %105, %106, %107, %108, %109, %110, %111, %112, %113, %114, %115, %116, %117, %118, %119, %120, %121, %122, %123, %124, %125, %126, %127}, %128, %129, p, 1, 1, 0, 1;\n}\n"
        : "+f"(d[0]), "+f"(d[1]), "+f"(d[2]), "+f"(d[3]), "+f"(d[4]), "+f"(d[5]), "+f"(d[6]), "+f"(d[7]), "+f"(d[8]), "+f"(d[9]), "+f"(d[10]), "+f"(d[11]), "+f"(d[12]), "+f"(d[13]), "+f"(d[14]), "+f"(d[15]), "+f"(d[16]), "+f"(d[17]), "+f"(d[18]), "+f"(d[19]), "+f"(d[20]), "+f"(d[21]), "+f"(d[22]), "+f"(d[23]), "+f"(d[24]), "+f"(d[25]), "+f"(d[26]), "+f"(d[27]), "+f"(d[28]), "+f"(d[29]), "+f"(d[30]), "+f"(d[31]), "+f"(d[32]), "+f"(d[33]), "+f"(d[34]), "+f"(d[35]), "+f"(d[36]), "+f"(d[37]), "+f"(d[38]), "+f"(d[39]), "+f"(d[40]), "+f"(d[41]), "+f"(d[42]), "+f"(d[43]), "+f"(d[44]), "+f"(d[45]), "+f"(d[46]), "+f"(d[47]), "+f"(d[48]), "+f"(d[49]), "+f"(d[50]), "+f"(d[51]), "+f"(d[52]), "+f"(d[53]), "+f"(d[54]), "+f"(d[55]), "+f"(d[56]), "+f"(d[57]), "+f"(d[58]), "+f"(d[59]), "+f"(d[60]), "+f"(d[61]), "+f"(d[62]), "+f"(d[63]), "+f"(d[64]), "+f"(d[65]), "+f"(d[66]), "+f"(d[67]), "+f"(d[68]), "+f"(d[69]), "+f"(d[70]), "+f"(d[71]), "+f"(d[72]), "+f"(d[73]), "+f"(d[74]), "+f"(d[75]), "+f"(d[76]), "+f"(d[77]), "+f"(d[78]), "+f"(d[79]), "+f"(d[80]), "+f"(d[81]), "+f"(d[82]), "+f"(d[83]), "+f"(d[84]), "+f"(d[85]), "+f"(d[86]), "+f"(d[87]), "+f"(d[88]), "+f"(d[89]), "+f"(d[90]), "+f"(d[91]), "+f"(d[92]), "+f"(d[93]), "+f"(d[94]), "+f"(d[95]), "+f"(d[96]), "+f"(d[97]), "+f"(d[98]), "+f"(d[99]), "+f"(d[100]), "+f"(d[101]), "+f"(d[102]), "+f"(d[103]), "+f"(d[104]), "+f"(d[105]), "+f"(d[106]), "+f"(d[107]), "+f"(d[108]), "+f"(d[109]), "+f"(d[110]), "+f"(d[111]), "+f"(d[112]), "+f"(d[113]), "+f"(d[114]), "+f"(d[115]), "+f"(d[116]), "+f"(d[117]), "+f"(d[118]), "+f"(d[119]), "+f"(d[120]), "+f"(d[121]), "+f"(d[122]), "+f"(d[123]), "+f"(d[124]), "+f"(d[125]), "+f"(d[126]), "+f"(d[127])
        : "l"(da), "l"(db), "r"(scale_d));
}
__device__ __forceinline__ void stmatrix_x4(uint32_t addr, uint32_t r0, uint32_t r1, uint32_t r2, uint32_t r3) {
    asm volatile("stmatrix.sync.aligned.m8n8.x4.shared.b16 [%0], {%1, %2, %3, %4};" :: "r"(addr), "r"(r0), "r"(r1), "r"(r2), "r"(r3) : "memory");
}
__device__ __forceinline__ void tma_store_2d(const CUtensorMap* map, uint32_t src, int c0, int c1) {
    asm volatile("cp.async.bulk.tensor.2d.global.shared::cta.bulk_group [%0, {%2, %3}], [%1];"
                 :: "l"((uint64_t)map), "r"(src), "r"(c0), "r"(c1) : "memory");
}
__device__ __forceinline__ float ex2f(float x) { float y; asm("ex2.approx.ftz.f32 %0, %1;" : "=f"(y) : "f"(x)); return y; }
__device__ __forceinline__ uint32_t pack_bf16(float lo, float hi) {
    __nv_bfloat162 v = __floats2bfloat162_rn(lo, hi);
    return *reinterpret_cast<uint32_t*>(&v);
}
__device__ __forceinline__ void mma_16816(float (&c)[4], uint32_t a0, uint32_t a1, uint32_t a2, uint32_t a3,
                                          uint32_t b0, uint32_t b1) {
    asm volatile(
        "mma.sync.aligned.m16n8k16.row.col.f32.bf16.bf16.f32 {%0,%1,%2,%3}, {%4,%5,%6,%7}, {%8,%9}, {%0,%1,%2,%3};"
        : "+f"(c[0]), "+f"(c[1]), "+f"(c[2]), "+f"(c[3])
        : "r"(a0), "r"(a1), "r"(a2), "r"(a3), "r"(b0), "r"(b1));
}
__device__ __forceinline__ void ldmatrix_x4_trans(uint32_t& r0, uint32_t& r1, uint32_t& r2, uint32_t& r3, uint32_t addr) {
    asm volatile("ldmatrix.sync.aligned.m8n8.x4.trans.shared.b16 {%0,%1,%2,%3}, [%4];"
                 : "=r"(r0), "=r"(r1), "=r"(r2), "=r"(r3) : "r"(addr));
}

struct AttnParams {
    CUtensorMap mapQ, mapK, mapV;
    CUtensorMap mapO;
    bf16* out;
};
constexpr int FA_ITEMS = 16 * NH;
__device__ __forceinline__ int fa_qt(int t) { return 15 - ((t & 127) >> 3); }
__device__ __forceinline__ int fa_head(int t) { return (t >> 7) * 8 + (t & 7); }
#define FA_TKA 2
#define FA_SPLIT 11

#define FA_P0 4
#define FA_HO 7
#define FA_LAG 2
#define FA_PK 3
#define FA_ST 4
#define FA_TG 16
#define FA_EARLY 0
#define FA_I0 0
static_assert(FA_GRID <= 104 && FA_HO >= FA_P0 && FA_P0 >= 1, "");
constexpr float FA_MARGIN = 16.f;
#define FAT(b, i)
__device__ __forceinline__ void mbar_arrive_if(uint32_t bar, bool c) {
    asm volatile("{\n.reg .pred p;\nsetp.ne.b32 p, %1, 0;\n@p mbarrier.arrive.shared::cta.b64 _, [%0];\n}" :: "r"(bar), "r"((int)c) : "memory");
}
__device__ __forceinline__ void sched_fence(int v, int id, const float* a, const float* b, const float* c) {
    asm volatile("{\n.reg .pred p;\nsetp.ne.s32 p, %0, %1;\n@p bra SF_SKIP;\nwgmma.wait_group.sync.aligned 0;\n"
                 "st.volatile.shared.f32 [%0], %2;\nst.volatile.shared.f32 [%0], %3;\nst.volatile.shared.f32 [%0], %4;\nst.volatile.shared.f32 [%0], %5;\n"
                 "st.volatile.shared.f32 [%0], %6;\nst.volatile.shared.f32 [%0], %7;\nst.volatile.shared.f32 [%0], %8;\nst.volatile.shared.f32 [%0], %9;\n"
                 "st.volatile.shared.f32 [%0], %10;\nst.volatile.shared.f32 [%0], %11;\nst.volatile.shared.f32 [%0], %12;\nst.volatile.shared.f32 [%0], %13;\n"
                 "exit;\nSF_SKIP:\n}" :: "r"(v), "r"(1000000 + id), "f"(a[0]), "f"(a[1]), "f"(a[2]), "f"(a[3]), "f"(b[0]), "f"(b[1]), "f"(b[2]), "f"(b[3]),
                 "f"(c[0]), "f"(c[1]), "f"(c[2]), "f"(c[3]) : "memory");
}
__device__ __forceinline__ float ex2v(float x) { float y; asm volatile("ex2.approx.ftz.f32 %0, %1;" : "=f"(y) : "f"(x)); return y; }
__device__ __forceinline__ void wgmma_rs_n128_tb_lo(float (&d)[64], const uint32_t* a, uint32_t db_lo, int scale_d) {
    asm volatile(
        "{\n.reg .pred p;\n.reg .b64 db;\nsetp.ne.b32 p, %69, 0;\nmov.b64 db, {%68, 0x40000040};\n"
        "wgmma.mma_async.sync.aligned.m64n128k16.f32.bf16.bf16 " ACC64_STR ", {%64, %65, %66, %67}, db, p, 1, 1, 1;\n}\n"
        : ACC64(d) : "r"(a[0]), "r"(a[1]), "r"(a[2]), "r"(a[3]), "r"(db_lo), "r"(scale_d));
}

constexpr int M_GRID = 68;
constexpr uint32_t SD = 1024;
constexpr uint32_t MO_BAR = 229376;
constexpr int M_SMEM = MO_BAR + 1024;
constexpr uint32_t FO_Q = 0, FO_KV = 65536, FO_O = FO_KV + 2 * 65536, FO_BAR = MO_BAR + 512;
constexpr uint32_t FB_QF = FO_BAR, FB_QE = FO_BAR + 16, FB_KF = FO_BAR + 32, FB_VF = FO_BAR + 48, FB_KE = FO_BAR + 64, FB_VE = FO_BAR + 80,
                   FB_OF = FO_BAR + 96, FB_OE = FO_BAR + 112, FB_SLOT = FO_BAR + 128, FB_OSLOT = FO_BAR + 136;
__device__ __forceinline__ void attn_init(uint32_t sb) {
    for (int i = 0; i < 2; i++) {
        mbar_init(sb + FB_QF + 8 * i, 1); mbar_init(sb + FB_QE + 8 * i, 8); mbar_init(sb + FB_KF + 8 * i, 1); mbar_init(sb + FB_VF + 8 * i, 1);
        mbar_init(sb + FB_KE + 8 * i, 8); mbar_init(sb + FB_VE + 8 * i, 8); mbar_init(sb + FB_OF + 8 * i, 4); mbar_init(sb + FB_OE + 8 * i, 1);
    }
}
__device__ __forceinline__ void attn_helper(const AttnParams& P, uint32_t sb, int wg) {
    const uint32_t stg = sb + FO_O + wg * 16384;
    for (int n = 0;; n++) {
        mbar_wait(sb + FB_OF + 8 * wg, n & 1);
        int t;
        asm volatile("ld.shared.s32 %0, [%1];" : "=r"(t) : "r"(sb + FB_OSLOT + wg * 4) : "memory");
        const int qt = fa_qt(t), h = fa_head(t & 1023);
        tma_store_2d(&P.mapO, stg, 0, h * SEQ + qt * 128 + wg * 64);
        tma_store_2d(&P.mapO, stg + 8192, 64, h * SEQ + qt * 128 + wg * 64);
        asm volatile("cp.async.bulk.commit_group;" ::: "memory");
        asm volatile("cp.async.bulk.wait_group.read 0;" ::: "memory");
        mbar_arrive(sb + FB_OE + 8 * wg);
        asm volatile("cp.async.bulk.wait_group 0;" ::: "memory");
        signal_ctr(CT_CA + qt * 4 + (h >> 3));
        if (t >= 1024) break;
    }
}
__device__ __forceinline__ void attn_producer(const AttnParams& P, uint32_t sb, uint32_t free_bar, uint32_t free_par) {
    const uint32_t sQ = sb + FO_Q, sKV = sb + FO_KV;
    int b = 0, hp_ready = 0, vrow = 0, t = blockIdx.x, item = 0;
    auto load_v = [&](int i) {
        const uint32_t sv = sKV + (i & 1) * 65536 + 32768, bar = sb + FB_VF + 8 * (i & 1);
        mbar_wait(sb + FB_VE + 8 * (i & 1), ((i >> 1) & 1) ^ 1);
        mbar_expect_tx(bar, 32768);
        tma_load_2d(sv, &P.mapV, bar, 0, vrow);
        tma_load_2d(sv + 16384, &P.mapV, bar, 64, vrow);
    };
    for (;; item++) {
        const bool valid = t < FA_ITEMS;
        const int qt = fa_qt(t), h = fa_head(t);
        if (valid && !((hp_ready >> (h >> 1)) & 1)) { wait_ctr(CT_AP + (h >> 1), 96u); hp_ready |= 1 << (h >> 1); }
        const uint32_t bq = sb + FB_QF + 8 * (item & 1);
        mbar_wait(item ? sb + FB_QE + 8 * (item & 1) : free_bar + 8, item ? ((item >> 1) & 1) ^ 1 : free_par);
        asm volatile("st.shared.s32 [%0], %1;" :: "r"(sb + FB_SLOT + (item & 1) * 4), "r"(valid ? t : -1) : "memory");
        if (!valid) { mbar_arrive(bq); break; }
        mbar_expect_tx(bq, 32768);
        tma_load_2d(sQ + (item & 1) * 32768, &P.mapQ, bq, 0, h * SEQ + qt * 128);
        tma_load_2d(sQ + (item & 1) * 32768 + 16384, &P.mapQ, bq, 64, h * SEQ + qt * 128);
#pragma unroll 1
        for (int j = 0; j <= qt; j++, b++) {
            const uint32_t sk = sKV + (b & 1) * 65536, bar = sb + FB_KF + 8 * (b & 1);
            mbar_wait(b >= 2 ? sb + FB_KE + 8 * (b & 1) : free_bar + 24 + 32 * b, b >= 2 ? ((b >> 1) & 1) ^ 1 : free_par);
            if (b == 1) { TS_END2(0, 256); TS_BEGIN2(1, 256); }
            if (b == 2) wait_ctr(CT_GATE, 256u);
            mbar_expect_tx(bar, 32768);
            tma_load_2d(sk, &P.mapK, bar, 0, h * SEQ + j * 128);
            tma_load_2d(sk + 16384, &P.mapK, bar, 64, h * SEQ + j * 128);
            if (j == max(qt - FA_TKA, 0)) t = take_ticket(CT_ATTN);
            if (b > 0) load_v(b - 1);
            vrow = h * SEQ + j * 128;
        }
        t += M_GRID;
    }
    load_v(b - 1);
    mbar_wait(sb + FB_KE + 8 * (~b & 1), ((b - 1) >> 1) & 1);
}
template <uint32_t sb, typename F>
__device__ __forceinline__ int attn_consumer(const AttnParams& P, int warp, F done) {
    constexpr uint32_t sQ = SD + FO_Q, sKV = SD + FO_KV;
    constexpr uint32_t sO = sb + FO_O;
    constexpr uint32_t bar_qf = sb + FB_QF, bar_qe = sb + FB_QE, bar_kf = sb + FB_KF, bar_vf = sb + FB_VF, bar_ke = sb + FB_KE, bar_ve = sb + FB_VE,
                   bar_of = sb + FB_OF, bar_oe = sb + FB_OE, slot = sb + FB_SLOT, oslot = sb + FB_OSLOT;
    {
        const int wg = warp >> 2;
        const int lane = threadIdx.x & 31;
        const float sc = 0.08838834764831845f * 1.4426950408889634f;
        const int r0 = wg * 64 + (warp & 3) * 16 + (lane >> 2);
        float o[64], s[64];
        uint32_t pa[32];
        float m0 = 0.f, m1 = 0.f, l0 = 0.f, l1 = 0.f, i0 = 0.f, i1 = 0.f, g0 = 0.f, g1 = 0.f;
        const uint32_t q_lo = desc_lo(sQ + wg * 8192, 16), k_lo = desc_lo(sKV, 16), v_lo = desc_lo(sKV + 32768, 16384);
        auto issue_qk = [&](int b, int item) {
            const uint32_t qd = q_lo + (item & 1) * 2048, kd = k_lo + (b & 1) * 4096;
            wgmma_fence();
#pragma unroll
            for (int kk = 0; kk < 8; kk++) wgmma_ss_n128_lo<0>(s, qd + (kk >> 2) * 1024 + (kk & 3) * 2, kd + (kk >> 2) * 1024 + (kk & 3) * 2, kk != 0);
            wgmma_commit();
        };
        auto issue_pv = [&](int b, bool acc, int n) {
            const uint32_t vd = v_lo + (b & 1) * 4096;
            mbar_wait(bar_vf + 8 * (b & 1), (b >> 1) & 1);
            wgmma_fence();
#pragma unroll
            for (int kk = 0; kk < 8; kk++) if (kk < n) wgmma_rs_n128_tb_lo(o, &pa[kk * 4], vd + kk * 128, kk ? 1 : (int)acc);
            wgmma_commit();
        };
        const int lim = r0 - (lane & 3) * 2;
        int item = -1, tnext = 0;
        uint32_t k_ready = 0, q_ready = 0;
        auto mask = [&](int i) { if ((i >> 2) * 8 + (i & 1) - ((i & 2) ? 8 : 0) > lim) s[i] = -INFINITY; };
        auto exps = [&](auto mode, int b, bool hand_over, float& u0, float& u1) {
            constexpr int MODE = decltype(mode)::value;
            float p[64], u[4] = {0.f, 0.f, 0.f, 0.f};
            const uint32_t vd = v_lo + ((b - 1) & 1) * 4096;
#pragma unroll
            for (int i = 0; i < 4; i++) p[i] = fmaf(s[i], sc, (i & 2) ? -m1 : -m0);
#pragma unroll
            for (int g = 0; g < 16 + FA_LAG; g++) {
                if (MODE && g >= FA_I0 && g - FA_I0 < 8 - FA_P0) {
                    const int kk = FA_P0 + g - FA_I0;
                    wgmma_fence();
                    wgmma_rs_n128_tb_lo(o, &pa[kk * 4], vd + kk * 128, 1);
                    wgmma_commit();
                    if (kk == FA_HO) asm volatile("{\n.reg .pred p;\nsetp.ne.b32 p, %1, 0;\n@p bar.arrive %0, 256;\n}" :: "r"(4 - wg), "r"((int)hand_over) : "memory");
                }
                if (MODE && g == FA_SPLIT) {
                    FAT(b, 2);
                    wgmma_wait<0>();
                    FAT(b - 1, 3);
                    mbar_arrive_if(bar_ve + 8 * ((b - 1) & 1), lane == 0);
                }
                if (MODE && g == FA_TG) {
                    k_ready = mbar_test(bar_kf + 8 * (~b & 1), ((b + 1) >> 1) & 1);
                    if (MODE == 2) {
                        q_ready = mbar_test(bar_qf + 8 * (~item & 1), ((item + 1) >> 1) & 1);
                        asm volatile("ld.shared.s32 %0, [%1];" : "=r"(tnext) : "r"(slot + (~item & 1) * 4) : "memory");
                    }
                }
#pragma unroll
                for (int j = 0; j < 4; j++) {
                    const int i = g * 4 + j;
                    if (g < 16) p[i] = ex2v(p[i]);
                    if (g < 15) {
                        if (MODE == 2) mask(i + 4);
                        p[i + 4] = fmaf(s[i + 4], sc, (i & 2) ? -m1 : -m0);
                    }
                    if (g >= FA_LAG) u[j] += p[i - FA_LAG * 4];
                }
#pragma unroll
                for (int gg = 0; gg < 16; gg++) {
                    const int at = MODE && gg + FA_LAG < FA_SPLIT + gg / FA_PK ? FA_SPLIT + gg / FA_PK : gg + FA_LAG;
                    if (at == g) { pa[gg * 2] = pack_bf16(p[gg * 4], p[gg * 4 + 1]); pa[gg * 2 + 1] = pack_bf16(p[gg * 4 + 2], p[gg * 4 + 3]); }
                }
                if (MODE && g < 16) sched_fence(b, g + MODE * 32, &p[g * 4], &p[(g < 15 ? g + 1 : g) * 4], u);
            }
            u0 = u[0] + u[1]; u1 = u[2] + u[3];
        };
        auto quad_max = [&](float& x0, float& x1) {
            x0 = fmaxf(x0, __shfl_xor_sync(0xffffffff, x0, 1)); x1 = fmaxf(x1, __shfl_xor_sync(0xffffffff, x1, 1));
            x0 = fmaxf(x0, __shfl_xor_sync(0xffffffff, x0, 2)); x1 = fmaxf(x1, __shfl_xor_sync(0xffffffff, x1, 2));
            x0 = fmaf(x0, sc, FA_MARGIN); x1 = fmaf(x1, sc, FA_MARGIN);
        };
        auto softmax_exact = [&](bool fresh, int b) {
            wgmma_wait<0>();
            float x[8];
#pragma unroll
            for (int i = 0; i < 8; i++) x[i] = fmaxf(s[i * 2], s[i * 2 + 1]);
#pragma unroll
            for (int i = 8; i < 32; i++) x[i & 7] = fmaxf(x[i & 7], fmaxf(s[i * 2], s[i * 2 + 1]));
            float x0 = fmaxf(fmaxf(x[0], x[2]), fmaxf(x[4], x[6])), x1 = fmaxf(fmaxf(x[1], x[3]), fmaxf(x[5], x[7]));
            quad_max(x0, x1);
            if (!fresh) {
                x0 = fmaxf(x0, m0); x1 = fmaxf(x1, m1);
                const float a0 = ex2f(m0 - x0), a1 = ex2f(m1 - x1);
                l0 *= a0; l1 *= a1;
#pragma unroll
                for (int i = 0; i < 16; i++) { o[i * 4 + 0] *= a0; o[i * 4 + 1] *= a0; o[i * 4 + 2] *= a1; o[i * 4 + 3] *= a1; }
            }
            m0 = x0; m1 = x1;
            float u0, u1;
            exps(std::integral_constant<int, 0>(), b, false, u0, u1);
            l0 += u0; l1 += u1;
        };
        auto finish_rows = [&]() {
            l0 += __shfl_xor_sync(0xffffffff, l0, 1); l1 += __shfl_xor_sync(0xffffffff, l1, 1);
            l0 += __shfl_xor_sync(0xffffffff, l0, 2); l1 += __shfl_xor_sync(0xffffffff, l1, 2);
            i0 = __fdividef(g0, l0); i1 = __fdividef(g1, l1);
        };
        auto clear_out = [&](int t) {
            if (t >= 384) {
                bf16* z = P.out + (size_t)(fa_qt(t) * 128 + wg * 64 + ((threadIdx.x & 127) >> 3)) * DM + (t & 7) * 64 + (lane & 7) * 8;
#pragma unroll
                for (int i = 0; i < 4; i++) *reinterpret_cast<uint4*>(z + i * 16 * DM) = make_uint4(0u, 0u, 0u, 0u);
            }
        };
        auto store_o = [&](int t, int n, int c0, int c1) {
            const uint32_t stg = sO + wg * 16384;
            if (c0 == 0) {
                mbar_wait(bar_oe + 8 * wg, (n & 1) ^ 1);
                asm volatile("st.shared.s32 [%0], %1;" :: "r"(oslot + wg * 4), "r"(t) : "memory");
            }
            const int row = (warp & 3) * 16 + (lane >> 2);
#pragma unroll
            for (int i = c0; i < c1; i++) {
                const int ch = i * 4 + (lane & 3);
                const uint32_t a = stg + (ch >> 3) * 8192 + row * 128 + (((ch & 7) ^ (row & 7)) << 4);
                const float* q = &o[i * 16];
                asm volatile("st.shared.v4.b32 [%0], {%1, %2, %3, %4};" :: "r"(a), "r"(pack_bf16(q[0] * i0, q[1] * i0)), "r"(pack_bf16(q[4] * i0, q[5] * i0)),
                             "r"(pack_bf16(q[8] * i0, q[9] * i0)), "r"(pack_bf16(q[12] * i0, q[13] * i0)) : "memory");
                asm volatile("st.shared.v4.b32 [%0], {%1, %2, %3, %4};" :: "r"(a + 1024), "r"(pack_bf16(q[2] * i1, q[3] * i1)), "r"(pack_bf16(q[6] * i1, q[7] * i1)),
                             "r"(pack_bf16(q[10] * i1, q[11] * i1)), "r"(pack_bf16(q[14] * i1, q[15] * i1)) : "memory");
            }
        };
        auto publish_o = [&]() {
            asm volatile("fence.proxy.async.shared::cta;" ::: "memory");
            __syncwarp();
            mbar_arrive_if(bar_of + 8 * wg, lane == 0);
        };
        int t = 0, left = 0, tdone = -1, b = 0, nout = 0;
        bool first = true, staged = false;
#pragma unroll 1
        for (;; b++) {
            const bool fresh = left == 0;
            const int tprev = t;
            FAT(b, 4);
            if (staged) { publish_o(); staged = false; }
            if (fresh) {
                item++;
                if (!q_ready) {
                    mbar_wait(bar_qf + 8 * (item & 1), (item >> 1) & 1);
                    asm volatile("ld.shared.s32 %0, [%1];" : "=r"(tnext) : "r"(slot + (item & 1) * 4) : "memory");
                }
                if (tnext < 0) break;
                t = tnext;
                left = fa_qt(t) + 1;
            }
            left--;
            if (tdone >= 0) store_o(tdone, nout, 0, FA_ST);
            FAT(b, 5);
            if (!k_ready) mbar_wait(bar_kf + 8 * (b & 1), (b >> 1) & 1);
            FAT(b, 6);
            asm volatile("bar.sync %0, 256;" :: "r"(3 + wg) : "memory");
            FAT(b, 0);
            issue_qk(b, item);
            bool early = false;
            if (!fresh && !first && left != 0) {
                issue_pv(b - 1, true, FA_P0);
                wgmma_wait<1>();
                FAT(b, 1);
                mbar_arrive_if(bar_ke + 8 * (b & 1), lane == 0);
            } else {
                early = (FA_EARLY && tdone >= 0) || b == 0;
                if (early) asm volatile("bar.arrive %0, 256;" :: "r"(4 - wg) : "memory");
                if (tdone >= 0) { wgmma_wait<1>(); store_o(tdone, nout++, FA_ST, 4); staged = true; }
                tdone = -1;
                if (fresh && b > 0) { finish_rows(); tdone = tprev; l0 = l1 = 0.f; }
                if (left == 0) { g0 = __ldcg(g_gate + fa_qt(t) * 128 + r0); g1 = __ldcg(g_gate + fa_qt(t) * 128 + r0 + 8); clear_out(t); }
                if (b > 0) issue_pv(b - 1, !first, FA_P0); else { wgmma_fence(); wgmma_commit(); }
                first = fresh;
                wgmma_wait<1>();
                FAT(b, 1);
                mbar_arrive_if(bar_ke + 8 * (b & 1), lane == 0);
                mbar_arrive_if(bar_qe + 8 * (item & 1), lane == 0 && left == 0);
                if (left == 0) { mask(0); mask(1); }
                if (fresh) { m0 = fmaxf(s[0], s[1]); m1 = fmaxf(s[2], s[3]); quad_max(m0, m1); }
            }
            if (b > 0) {
                float u0, u1;
                if (left == 0) exps(std::integral_constant<int, 2>(), b, !early, u0, u1);
                else exps(std::integral_constant<int, 1>(), b, !early, u0, u1);
                if (!__any_sync(0xffffffff, !(u0 + u1 < 1.f))) { l0 += u0; l1 += u1; continue; }
            }
            softmax_exact(fresh, b);
        }
        if (tdone >= 0) { store_o(tdone, nout++, 0, 4); publish_o(); }
        issue_pv(b - 1, !first, 8);
        finish_rows();
        wgmma_wait<0>();
        done();
        store_o(t + 1024, nout, 0, 4);
        publish_o();
        return nout;
    }
}

__device__ __forceinline__ uint32_t cluster_ctarank() {
    uint32_t r; asm volatile("mov.u32 %0, %%cluster_ctarank;" : "=r"(r)); return r;
}
__device__ __forceinline__ uint32_t mapa_u32(uint32_t addr, uint32_t rank) {
    uint32_t r; asm volatile("mapa.shared::cluster.u32 %0, %1, %2;" : "=r"(r) : "r"(addr), "r"(rank)); return r;
}
__device__ __forceinline__ void cluster_sync_all() {
    asm volatile("barrier.cluster.arrive.release.aligned;\nbarrier.cluster.wait.acquire.aligned;" ::: "memory");
}
__device__ __forceinline__ void st_async_v4(uint32_t addr, uint32_t a, uint32_t b, uint32_t c, uint32_t d, uint32_t mbar) {
    asm volatile("st.async.weak.shared::cluster.mbarrier::complete_tx::bytes.v4.b32 [%0], {%1, %2, %3, %4}, [%5];"
                 :: "r"(addr), "r"(a), "r"(b), "r"(c), "r"(d), "r"(mbar) : "memory");
}
__device__ __forceinline__ void st_async_v2(uint32_t addr, uint32_t a, uint32_t b, uint32_t mbar) {
    asm volatile("st.async.weak.shared::cluster.mbarrier::complete_tx::bytes.v2.b32 [%0], {%1, %2}, [%3];"
                 :: "r"(addr), "r"(a), "r"(b), "r"(mbar) : "memory");
}
__device__ __forceinline__ void st_async_b32(uint32_t addr, uint32_t a, uint32_t mbar) {
    asm volatile("st.async.weak.shared::cluster.mbarrier::complete_tx::bytes.b32 [%0], %1, [%2];" :: "r"(addr), "r"(a), "r"(mbar) : "memory");
}
__device__ __forceinline__ void pace(int cycles) {
    if (cycles > 0) {
        uint32_t t0, t;
        asm volatile("mov.u32 %0, %%clock;" : "=r"(t0));
        do { asm volatile("mov.u32 %0, %%clock;" : "=r"(t)); } while (t - t0 < (uint32_t)cycles);
    }
}
__device__ __forceinline__ void mbar_wait_cl(uint32_t bar, uint32_t parity) {
    uint32_t done = 0;
    for (int it = 0; it < WAIT_LIMIT && !done; it++) {
        asm volatile(
            "{\n.reg .pred p;\n"
            "mbarrier.try_wait.parity.shared::cta.b64 p, [%1], %2;\n"
            "selp.u32 %0, 1, 0, p;\n}\n" : "=r"(done) : "r"(bar), "r"(parity) : "memory");
    }
}
__device__ __forceinline__ void ldmatrix_x4(uint32_t& r0, uint32_t& r1, uint32_t& r2, uint32_t& r3, uint32_t addr) {
    asm volatile("ldmatrix.sync.aligned.m8n8.x4.shared.b16 {%0,%1,%2,%3}, [%4];"
                 : "=r"(r0), "=r"(r1), "=r"(r2), "=r"(r3) : "r"(addr));
}
__device__ __forceinline__ void cp_async16(uint32_t dst, const void* src) {
    asm volatile("cp.async.cg.shared.global [%0], [%1], 16;" :: "r"(dst), "l"(src) : "memory");
}
__device__ __forceinline__ float bf16r(float x) { return __uint_as_float(pack_bf16(0.f, x) & 0xffff0000u); }

#define DBGP(i, w, ok)
#define DBG(i, w)
#define DBGD(i, w, dep)
#define DBG_EXTRA 0
__device__ __forceinline__ void tma_load_2d_mc(uint32_t dst, const CUtensorMap* map, uint32_t bar, int c0, int c1, uint16_t mask) {
    asm volatile(
        "cp.async.bulk.tensor.2d.shared::cluster.global.mbarrier::complete_tx::bytes.multicast::cluster [%0], [%1, {%3, %4}], [%2], %5;"
        :: "r"(dst), "l"((uint64_t)map), "r"(bar), "r"(c0), "r"(c1), "h"(mask) : "memory");
}
__device__ __forceinline__ void stmatrix_x4_trans(uint32_t addr, uint32_t r0, uint32_t r1, uint32_t r2, uint32_t r3) {
    asm volatile("stmatrix.sync.aligned.m8n8.x4.trans.shared.b16 [%0], {%1, %2, %3, %4};" :: "r"(addr), "r"(r0), "r"(r1), "r"(r2), "r"(r3) : "memory");
}
__device__ __forceinline__ void stmatrix_x2_trans(uint32_t addr, uint32_t r0, uint32_t r1) {
    asm volatile("stmatrix.sync.aligned.m8n8.x2.trans.shared.b16 [%0], {%1, %2};" :: "r"(addr), "r"(r0), "r"(r1) : "memory");
}
__device__ __forceinline__ uint4 lds128(uint32_t a) {
    uint4 v; asm volatile("ld.shared.v4.u32 {%0, %1, %2, %3}, [%4];" : "=r"(v.x), "=r"(v.y), "=r"(v.z), "=r"(v.w) : "r"(a) : "memory"); return v;
}
__device__ __forceinline__ void sts128(uint32_t a, uint32_t x, uint32_t y, uint32_t z, uint32_t w) {
    asm volatile("st.shared.v4.b32 [%0], {%1, %2, %3, %4};" :: "r"(a), "r"(x), "r"(y), "r"(z), "r"(w) : "memory");
}
__device__ __forceinline__ float2 lds64f(uint32_t a) {
    float2 v; asm volatile("ld.shared.v2.f32 {%0, %1}, [%2];" : "=f"(v.x), "=f"(v.y) : "r"(a) : "memory"); return v;
}
__device__ __forceinline__ void fence_async_smem() { asm volatile("fence.proxy.async.shared::cta;" ::: "memory"); }
#define ACC16(d) "+f"(d[0]), "+f"(d[1]), "+f"(d[2]), "+f"(d[3]), "+f"(d[4]), "+f"(d[5]), "+f"(d[6]), "+f"(d[7]), "+f"(d[8]), "+f"(d[9]), "+f"(d[10]), "+f"(d[11]), "+f"(d[12]), "+f"(d[13]), "+f"(d[14]), "+f"(d[15])
template <int ND>
__device__ __forceinline__ void wgmma_rs_n32(float (&d)[ND], const uint32_t (&a)[4], uint32_t db_lo, int scale_d) {
    asm volatile(
        "{\n.reg .pred p;\n.reg .b64 db;\nsetp.ne.b32 p, %21, 0;\nmov.b64 db, {%20, 0x40000040};\n"
        "wgmma.mma_async.sync.aligned.m64n32k16.f32.bf16.bf16 {%0,%1,%2,%3,%4,%5,%6,%7,%8,%9,%10,%11,%12,%13,%14,%15}, {%16,%17,%18,%19}, db, p, 1, 1, 0;\n}\n"
        : ACC16(d) : "r"(a[0]), "r"(a[1]), "r"(a[2]), "r"(a[3]), "r"(db_lo), "r"(scale_d));
}
template <int ND>
__device__ __forceinline__ void wgmma_ss_n32(float (&d)[ND], uint32_t da_lo, uint32_t db_lo, int scale_d) {
    asm volatile(
        "{\n.reg .pred p;\n.reg .b64 da, db;\nsetp.ne.b32 p, %18, 0;\nmov.b64 da, {%16, 0x40000040};\nmov.b64 db, {%17, 0x40000040};\n"
        "wgmma.mma_async.sync.aligned.m64n32k16.f32.bf16.bf16 {%0,%1,%2,%3,%4,%5,%6,%7,%8,%9,%10,%11,%12,%13,%14,%15}, da, db, p, 1, 1, 1, 0;\n}\n"
        : ACC16(d) : "r"(da_lo), "r"(db_lo), "r"(scale_d));
}
__device__ __forceinline__ void wgmma_ss_n8(float (&d)[4], uint32_t da_lo, uint32_t db_lo, int scale_d) {
    asm volatile(
        "{\n.reg .pred p;\n.reg .b64 da, db;\nsetp.ne.b32 p, %6, 0;\nmov.b64 da, {%4, 0x40000040};\nmov.b64 db, {%5, 0x00000010};\n"
        "wgmma.mma_async.sync.aligned.m64n8k16.f32.bf16.bf16 {%0,%1,%2,%3}, da, db, p, 1, 1, 1, 0;\n}\n"
        : "+f"(d[0]), "+f"(d[1]), "+f"(d[2]), "+f"(d[3]) : "r"(da_lo), "r"(db_lo), "r"(scale_d));
}

#define SCHED_FENCE()
__device__ __forceinline__ void wgmma_ss_n32_p(float (&d)[16], uint32_t da_lo, uint32_t db_lo, int scale_d) {
    asm volatile(
        "{\n.reg .pred p;\n.reg .b64 da, db;\nsetp.ne.b32 p, %18, 0;\nmov.b64 da, {%16, 0x40000040};\nmov.b64 db, {%17, 0x00000030};\n"
        "wgmma.mma_async.sync.aligned.m64n32k16.f32.bf16.bf16 {%0,%1,%2,%3,%4,%5,%6,%7,%8,%9,%10,%11,%12,%13,%14,%15}, da, db, p, 1, 1, 1, 0;\n}\n"
        : ACC16(d) : "r"(da_lo), "r"(db_lo), "r"(scale_d));
}

#define ACC20(d) ACC16(d), "+f"(d[16]), "+f"(d[17]), "+f"(d[18]), "+f"(d[19])
#define ACC20_STR "{%0,%1,%2,%3,%4,%5,%6,%7,%8,%9,%10,%11,%12,%13,%14,%15,%16,%17,%18,%19}"
__device__ __forceinline__ void wgmma_rs_n40(float (&d)[20], const uint32_t (&a)[4], uint32_t db_lo, int scale_d) {
    asm volatile(
        "{\n.reg .pred p;\n.reg .b64 db;\nsetp.ne.b32 p, %25, 0;\nmov.b64 db, {%24, 0x40000040};\n"
        "wgmma.mma_async.sync.aligned.m64n40k16.f32.bf16.bf16 " ACC20_STR ", {%20,%21,%22,%23}, db, p, 1, 1, 0;\n}\n"
        : ACC20(d) : "r"(a[0]), "r"(a[1]), "r"(a[2]), "r"(a[3]), "r"(db_lo), "r"(scale_d));
}
template <int TA, int SBO>
__device__ __forceinline__ void wgmma_ss_n40(float (&d)[20], uint32_t da_lo, uint32_t db_lo, int scale_d) {
    asm volatile(
        "{\n.reg .pred p;\n.reg .b64 da, db;\nsetp.ne.b32 p, %22, 0;\nmov.b64 da, {%20, %23};\nmov.b64 db, {%21, 0x40000040};\n"
        "wgmma.mma_async.sync.aligned.m64n40k16.f32.bf16.bf16 " ACC20_STR ", da, db, p, 1, 1, %24, 0;\n}\n"
        : ACC20(d) : "r"(da_lo), "r"(db_lo), "r"(scale_d), "n"(0x40000000 + SBO / 16), "n"(TA));
}
template <int SBO>
__device__ __forceinline__ void wgmma_ss_n48(float (&d)[24], uint32_t da_lo, uint32_t db_lo, int scale_d) {
    asm volatile(
        "{\n.reg .pred p;\n.reg .b64 da, db;\nsetp.ne.b32 p, %26, 0;\nmov.b64 da, {%24, %27};\nmov.b64 db, {%25, 0x40000040};\n"
        "wgmma.mma_async.sync.aligned.m64n48k16.f32.bf16.bf16 {%0,%1,%2,%3,%4,%5,%6,%7,%8,%9,%10,%11,%12,%13,%14,%15,%16,%17,%18,%19,%20,%21,%22,%23}, da, db, p, 1, 1, 0, 0;\n}\n"
        : ACC20(d), "+f"(d[20]), "+f"(d[21]), "+f"(d[22]), "+f"(d[23]) : "r"(da_lo), "r"(db_lo), "r"(scale_d), "n"(0x40000000 + SBO / 16));
}

#define PT(i, th)
struct ChainParams {
    CUtensorMap mapW[3];
    CUtensorMap mapX;
    CUtensorMap mapC;
    CUtensorMap mapWo;
    CUtensorMap mapM;
    CUtensorMap mapOut;
};
constexpr int CH_BLOCK = 384;
constexpr int CO_WO = 0;
constexpr int CH_XC = 5120, CH_XP = 8 * CH_XC;
constexpr int CO_XB = 65536;
constexpr int CO_OB = CO_XB + 2 * CH_XP;
constexpr int CO_P = CO_OB + 8192;
constexpr int CO_LS = CO_P + 3072;
constexpr int CO_SC = CO_LS + 8 * 1280;
constexpr int CH_TW = 6144 + 8192;
constexpr int CO_T = 21 * 8192;
constexpr int CO_WA = CO_T + 6144;
constexpr int CO_ST = CO_T + 3 * CH_TW + 6144;
constexpr int CO_OWN = CO_ST + 4096, CO_OWN2 = CO_SC + 1536;
constexpr int CO_BAR = CO_OWN + 4096;
constexpr int CH_SMEM = CO_BAR + 256 + DBG_EXTRA;
#define CH_GL 2
#define CH_A3 1
#define CH_D0 0
#define CH_PF 0
#define CH_NA 0
#define CH_LQ ""
#define CH_SQ ""
#define CH_XPF 0
#define CH_NSM 4
static_assert(CO_OWN2 + 1024 <= CO_T && CH_NSM <= 4, "smem layout");
#define CH_POLL_DELAY 240
#define CH_VPOS 2
#define CH_OW 12
#define CH_OF 12
#define CH_Q0 0
#define CH_QI 12
#define CH_QX 0
#define CH_Q1 (CH_Q0 + CH_QI + CH_QX)
#define CH_VA 5
#define CH_SPOS 0
#define CH_LSW 1
#define CH_QE 16
#define CH_KE 16
#define CH_QD 0
#define CH_GAP 0
#define CH_QS 0
#define CH_KS 0
#define CH_VS 4
#define CH_A7 7
#define CH_RF 0
#define CH_LSS 0
#define CH_OS 1
#define CH_MG 0
#define CH_MBT 0x76543210u
#define CH_MB(i) ((int)(CH_MBT >> 4 * (i)) & 7)
#define CH_AS 0x64207531u
#define CH_QL 16
#define CH_ML 0x112112
#define CH_DEP 1
#define CH_SP 2
#define CH_VD 0
#define CH_MP 2
#define CH_MP0 2
#define CH_OFE 3
#define CH_MS 1
#define CH_HA 3
#define CH_LD 4
#define CH_TWP 0
#define CH_SUMC 4
#define CH_ES 0
#define CH_ST 224
#define CH_KEEP 1
#define CH_PINB 1
#define CH_DRY 1
#define CH_D1 4500
#define CH_D2 11000
#define CH_CHAINS 4

constexpr float CH_SC = 0.08838834764831845f * 1.4426950408889634f;
__device__ __forceinline__ uint32_t pin(uint32_t v) { return __shfl_sync(0xffffffff, v, threadIdx.x & 31); }

__device__ __forceinline__ void out_finished() {
    if (atomicAdd(&g_ctr[CT_FIN], 1u) == M_GRID + 64 - 1)
        for (int i = 0; i < CT_N / 4; i++) reinterpret_cast<uint4*>(g_ctr)[i] = make_uint4(0u, 0u, 0u, 0u);
}
__device__ __forceinline__ void out_flush(const float (&acc)[128], const CUtensorMap* map, uint32_t stg0, uint32_t stg1, int tid, int bar, int n0, int m0) {
    const int lane = tid & 31, row = (lane & 7) + ((lane >> 3) & 1) * 8;
#pragma unroll
    for (int hf = 0; hf < 2; hf++) {
#pragma unroll
        for (int j = 0; j < 16; j += 2) {
            const float* a = &acc[hf * 64 + j * 4];
            stmatrix_x4((hf ? stg1 : stg0) + (j >> 3) * 8192 + (((tid >> 5) & 3) * 16 + row) * 128 + ((((j & 7) + (lane >> 4)) ^ (row & 7)) << 4),
                        pack_bf16(a[0], a[1]), pack_bf16(a[2], a[3]), pack_bf16(a[4], a[5]), pack_bf16(a[6], a[7]));
        }
        asm volatile("fence.proxy.async.shared::cta;\nbar.sync %0, 128;" :: "r"(bar) : "memory");
        asm volatile("{\n.reg .pred p;\nsetp.ne.b32 p, %0, 0;\n@p bra FL_SKIP;\n"
                     "cp.reduce.async.bulk.tensor.2d.global.shared::cta.add.tile.bulk_group [%1, {%3, %5}], [%2];\n"
                     "cp.reduce.async.bulk.tensor.2d.global.shared::cta.add.tile.bulk_group [%1, {%4, %5}], [%2 + 8192];\n"
                     "cp.async.bulk.commit_group;\nFL_SKIP:\n}"
                     :: "r"(tid & 127), "l"((uint64_t)map), "r"(hf ? stg1 : stg0), "r"(n0 + hf * 128), "r"(n0 + hf * 128 + 64), "r"(m0) : "memory");
        __syncwarp();
    }
}

__global__ void __cluster_dims__(8, 1, 1) __launch_bounds__(CH_BLOCK, 1)
chain_kernel(const __grid_constant__ ChainParams P) {
    extern __shared__ uint8_t smem_raw[];
    const int tid = threadIdx.x, warp = __shfl_sync(0xffffffff, tid >> 5, 0), lane = tid & 31;
    const int rank = (int)cluster_ctarank();
    constexpr uint32_t sd = 1024;
    const uint32_t sb = ((uint32_t)rank << 24) + sd;
    if (smem_u32(smem_raw) != sb) __trap();
    const int C = blockIdx.x >> 3;
    const int h = C * 4 + (rank >> 1);
    const int qd = lane >> 2, qc = lane & 3;
    const int t4 = warp & 3, wg = warp >> 2;
    pdl_launch_dependents();
    uint32_t t_start;
    asm volatile("mov.u32 %0, %%clock;" : "=r"(t_start));
    t_start = __shfl_sync(0xffffffff, t_start, 0);
    TS_BEGIN(2);
    PT(0, 0);
    const uint32_t bar_mem = sb + CO_BAR + 128, bar_o = sb + CO_BAR + 32, bar_sc = bar_o + 32, bar_x = bar_sc + 8, bar_l = bar_x + 16, bar_w = bar_l + 8;
    const uint32_t bar_wo = bar_o + 24;
    auto chunk = [&](int i) { return (uint32_t)((rank - i) & 7); };
    auto mine = [](int g, int c) { return (int)((CH_AS >> (g * 16 + c * 4)) & 7); };
    const int wcol = h * HD + (rank & 1) * 64;
    auto wdst = [&](int g, int i) { return i == 0 ? CO_WA + g * CH_TW : g && i == 7 ? CO_ST : (g ? CO_XB + CH_XP : 0) + (i - 1) * 8192; };
    auto vdst = [&](int i) { return i >= 2 && i < 10 ? CO_XB + CH_XP + (i - 2) * CH_XC : (i < 2 ? CO_WA + 2 * CH_TW : i < 12 ? CO_OB : i < 14 ? CO_LS : CO_ST) + (i & 1) * 4096; };
    if ((tid & 127) == 0) {
        pace(CH_D0);
        const uint32_t bar = wg == 2 ? bar_x : bar_w + 8 * wg;
        mbar_init(bar, 1);
        asm volatile("fence.mbarrier_init.release.cluster;" ::: "memory");
        mbar_expect_tx(bar, wg == 2 ? CH_XP : 65536);
#pragma unroll 1
        for (int i = 0; i < 8; i++) {
            if (wg == 2) {
                tma_load_2d(sb + CO_XB + i * CH_XC, &P.mapX, bar, i * 64, 0);
                tma_load_2d(sb + CO_XB + i * CH_XC + 4096, &P.mapM, bar, i * 64, 0);
            } else tma_load_2d(sb + wdst(wg, i), &P.mapW[wg ^ (i & 1)], bar, wcol, chunk(mine(wg, i >> 1)) * 64);
        }
    }
    if (warp == 9 && lane < 24 && lane != 9 && (lane >> 1) != 6) {
        mbar_init(sb + CO_BAR + 8 * lane, 1);
        asm volatile("fence.mbarrier_init.release.cluster;" ::: "memory");
    }
    __syncthreads();
    PT(1, 0);
    if (wg == 2 || (wg == 0 && CH_QL < 16)) asm volatile("bar.arrive 10, %0;" :: "n"(CH_QL < 16 ? 384 : 256) : "memory");
    if (wg == 2) {
        const int t = tid - 256;
        sts128(sb + CO_T + (2 + (t >> 6)) * CH_TW + 5120 + (t & 63) * 16, 0u, 0u, 0u, 0u);
        if (t < 32) sts128(sb + CO_P + (t >> 3) * 768 + 640 + (t & 7) * 16, 0u, 0u, 0u, 0u);
    }
    const uint32_t wfrag = (((lane >> 4) << 3) + (lane & 7)) * 128 + (((t4 * 2 + ((lane >> 3) & 1)) ^ (lane & 7)) << 4);
    const uint32_t aO = pin(sb + wg * CH_TW + wfrag);
    const uint32_t aL = pin(sb + lane * 16);
    uint32_t w[32][4];
    auto load_w = [&](int g, bool v) {
#pragma unroll
        for (int e = CH_NSM; e < 32; e++) ldmatrix_x4_trans(w[e][0], w[e][1], w[e][2], w[e][3], aO + ((v ? vdst(e >> 1) + (e & 1) * 2048 : wdst(g, e >> 2) + (e & 3) * 2048) - g * CH_TW));
        fence_async_smem();
    };
    auto pass = [&](auto& d, int g, int b, int j0, int j1, int js, bool group = true) {
        const uint32_t lo = desc_lo(sd + CO_XB + b * CH_XP, 16);
        if (group) wgmma_fence();
#pragma unroll
        for (int j = 0; j < 32; j++) if (j >= j0 && j < j1) {
            const int f = js < 0 ? j : j < js ? j + CH_NSM : j < js + CH_NSM ? j - js : j;
            const int e = sizeof(d) == 64 ? (f >> 2) * 8 + (js < 0 ? 4 : 0) + (f & 3) : f;
            const uint32_t db = lo + chunk(sizeof(d) == 64 ? mine(g, f >> 2) : f >> 2) * (CH_XC / 16) + (e & 3) * 2, da = desc_lo(sd + CO_WA + g * CH_TW + e * 2048, 16);
            if constexpr (sizeof(d) == 64) { if (e < CH_NSM) wgmma_ss_n32(d, da, db, j != 0); else wgmma_rs_n32(d, w[e], db, j != 0); }
            else { if (e < CH_NSM) wgmma_ss_n40<1, 1024>(d, da, db, j != 0); else wgmma_rs_n40(d, w[e], db, j != 0); }
        }
        if (group) wgmma_commit();
    };
    auto uni = [](uint32_t v) { return __shfl_sync(0xffffffff, v, 0); };
    auto roff = [&](int j) { return (uint32_t)(((rank + j) & 7) - rank) << 24; };
    auto store32 = [&](const float* d, uint32_t a) {
        stmatrix_x4_trans(a, pack_bf16(d[0], d[1]), pack_bf16(d[2], d[3]), pack_bf16(d[4], d[5]), pack_bf16(d[6], d[7]));
        stmatrix_x4_trans(a + 2048, pack_bf16(d[8], d[9]), pack_bf16(d[10], d[11]), pack_bf16(d[12], d[13]), pack_bf16(d[14], d[15]));
    };
    auto load32 = [&](uint32_t (&r)[8], uint32_t a) {
        ldmatrix_x4_trans(r[0], r[1], r[2], r[3], a);
        ldmatrix_x4_trans(r[4], r[5], r[6], r[7], a + 2048);
    };
    auto add32 = [&](float* d, const uint32_t (&r)[8], uint32_t a) {
        wgmma_wait<0>();
#pragma unroll
        for (int i = 0; i < 8; i++) { d[2 * i] += __uint_as_float(r[i] << 16); d[2 * i + 1] += __uint_as_float(r[i] & 0xffff0000u); }
        store32(d, a);
    };
    auto scores = [&](float (&d)[24], auto sbo, uint32_t q) {
        wgmma_fence();
#pragma unroll
        for (int ks = 0; ks < 4; ks++) wgmma_ss_n48<decltype(sbo)::value>(d, desc_lo(sd + q, 16) + ks * 2, desc_lo(sd + CO_T + CH_TW, 16) + ks * 2, ks != 0);
        wgmma_commit();
    };
    auto add_scores = [&](uint32_t a, uint32_t b, float (&v)[10]) {
        const uint4 a0 = lds128(a), a1 = lds128(a + 512);
        const float2 a2 = lds64f(b);
        v[0] += __uint_as_float(a0.x); v[1] += __uint_as_float(a0.y); v[2] += __uint_as_float(a0.z); v[3] += __uint_as_float(a0.w);
        v[4] += __uint_as_float(a1.x); v[5] += __uint_as_float(a1.y); v[6] += __uint_as_float(a1.z); v[7] += __uint_as_float(a1.w);
        v[8] += a2.x; v[9] += a2.y;
    };
    auto row_max = [&](const float (&v)[10]) {
        float mx = fmaxf(fmaxf(fmaxf(v[0], v[1]), fmaxf(v[2], v[3])), fmaxf(fmaxf(v[4], v[5]), fmaxf(v[6], v[7])));
        mx = fmaxf(mx, fmaxf(v[8], v[9]));
        mx = fmaxf(mx, __shfl_xor_sync(0xffffffff, mx, 1));
        return fmaxf(mx, __shfl_xor_sync(0xffffffff, mx, 2)) * CH_SC;
    };
    auto local_pv = [&](int s, int st) {
        float dc[16];
        wgmma_fence();
#pragma unroll
        for (int ks = 0; ks < 3; ks++) wgmma_ss_n32_p(dc, desc_lo(sd + CO_T + (2 + (s & 1)) * CH_TW + ks * 2048, 16), desc_lo(sd + CO_P + ks * 256, 128), ks != 0);
        wgmma_commit();
        wgmma_wait<0>();
        store32(dc, aO - CH_TW + st);
    };
    float gs = 0.f;
    auto load_gate = [&](int s) { asm volatile("ld.global.cg.f32 %0, [%1];" : "=f"(gs) : "l"(g_gate + s * SEGL + t4 * 8 + qd) : "memory"); };
    auto softmax = [&](int s, float (&u)[11]) {
        float v[10];
        {
            const uint4 a0 = lds128(aL + CO_OWN + t4 * 1024), a1 = lds128(aL + CO_OWN + t4 * 1024 + 512);
            const float2 a2 = lds64f(aL + CO_OWN2 + t4 * 256 - lane * 8);
            v[0] = __uint_as_float(a0.x); v[1] = __uint_as_float(a0.y); v[2] = __uint_as_float(a0.z); v[3] = __uint_as_float(a0.w);
            v[4] = __uint_as_float(a1.x); v[5] = __uint_as_float(a1.y); v[6] = __uint_as_float(a1.z); v[7] = __uint_as_float(a1.w);
            v[8] = a2.x; v[9] = a2.y;
        }
        mbar_wait_cl(bar_l, s & 1);
        add_scores(aL + t4 * 1024 + CO_LS + (s & 1) * 5120, aL + t4 * 256 - lane * 8 + CO_LS + (s & 1) * 5120 + 4096, v);
        const int lim = t4 * 8 + qd - 2 * qc;
#pragma unroll
        for (int j = 0; j < 8; j++) if ((j >> 1) * 8 + (j & 1) > lim) v[j] = -INFINITY;
        const float mx = row_max(v);
#pragma unroll
        for (int j = 0; j < 10; j++) u[j] = v[j];
        u[10] = mx;
    };
    auto softmax1 = [&](float (&u)[11]) {
#pragma unroll
        for (int j = 0; j < 10; j++) u[j] = ex2f(fmaf(u[j], CH_SC, -u[10]));
        u[10] = (((u[0] + u[1]) + (u[2] + u[3])) + ((u[4] + u[5]) + (u[6] + u[7]))) + (u[8] + u[9]);
    };
    auto softmax2 = [&](float (&v)[11]) {
        float sum = v[10];
        sum += __shfl_xor_sync(0xffffffff, sum, 1);
        sum += __shfl_xor_sync(0xffffffff, sum, 2);
        asm("rcp.approx.ftz.f32 %0, %0;" : "+f"(sum));
        sum *= 1.f - gs;
        const uint32_t pa = aL + CO_P + t4 * 768;
        stmatrix_x4(pa, pack_bf16(v[0] * sum, v[1] * sum), pack_bf16(v[2] * sum, v[3] * sum), pack_bf16(v[4] * sum, v[5] * sum), pack_bf16(v[6] * sum, v[7] * sum));
        asm volatile("stmatrix.sync.aligned.m8n8.x1.shared.b16 [%0], {%1};" :: "r"(pa + 512), "r"(pack_bf16(v[8] * sum, v[9] * sum)) : "memory");
    };
    if (mapa_u32(bar_l, rank ^ 1) != (bar_l ^ (1u << 24)) || mapa_u32(bar_l, (rank + 3) & 7) != bar_l + roff(3)) __trap();
    asm volatile("bar.sync %0, 128;" :: "r"(12 + wg) : "memory");
    if (__shfl_sync(0xffffffff, tid, 1) < 256) {
#pragma unroll 1
        for (int rep = CH_DRY ? 0 : 1; rep < 2; rep++) {
            if (rep) mbar_wait(bar_w + 8 * wg, 0);
            PT(3, 0);
            load_w(wg, false);
            if (rep) {
                asm volatile("bar.arrive %0, 160;" :: "r"(wg ? 2 : 15) : "memory");
                asm volatile("barrier.cluster.arrive.relaxed.aligned;" ::: "memory");
                mbar_wait(bar_x, 0);
            }
            asm volatile("bar.sync 12, 256;" ::: "memory");
            PT(7, 0);
            float d[16];
            pass(d, wg, 0, 0, 16, -1);
            wgmma_wait<0>();
            store32(d, aO + CO_T + (1 - 2 * wg) * CH_TW);
            pass(d, wg, 0, 0, 16, 0);
            asm volatile("bar.sync 13, 256;" ::: "memory");
            uint32_t r[8];
            load32(r, aO + CO_T);
            add32(d, r, aO + CO_T);
        }
    }
    PT(8, 0);
    TS_BEGIN(5);
    PT(9, 0);

    if (wg < 2) {
        const uint32_t aM = pin(sb + CO_XB + 4096 + (lane & 7) * 128 + (((lane >> 3) ^ (lane & 7)) << 4));
        uint32_t coff[4];
#pragma unroll
        for (int i = 0; i < 4; i++) coff[i] = uni(chunk(mine(wg, i)) * CH_XC);
        auto mem_proj = [&](int s, auto gc) {
            constexpr int G = decltype(gc)::value;
            const uint32_t par = s & 1;
            float acc[4][4];
#pragma unroll
            for (int i = 0; i < 4; i++) acc[i][0] = acc[i][1] = acc[i][2] = acc[i][3] = 0.f;
            const uint32_t am = aM + par * CH_XP;
            uint32_t b[4][4], ok = 1;
            auto bar = [&](int c) { return bar_mem + 8 * CH_MB(mine(G, c)); };
            auto load = [&](int c) {
                if (c ? CH_MB(mine(G, c)) != CH_MB(mine(G, c - 1)) : G == 0)
                    asm volatile("{\n.reg .pred p, q;\n.reg .u32 c;\nsetp.ne.u32 p, %2, 0;\n@p bra MP_DONE;\nmov.u32 c, 0;\n"
                                 "MP_LOOP:\nmbarrier.try_wait.parity.shared::cta.b64 p, [%0], %1;\nadd.u32 c, c, 1;\nsetp.lt.and.u32 q, c, %3, !p;\n"
                                 "@q bra MP_LOOP;\nMP_DONE:\n}" :: "r"(bar(c)), "r"(par ^ 1), "r"(ok), "n"(WAIT_LIMIT / 64) : "memory");
                uint32_t* r = b[2 * c & 3];
                ldmatrix_x4(r[0], r[1], r[2], r[3], am + coff[c]);
                r = b[(2 * c + 1) & 3];
                ldmatrix_x4(r[0], r[1], r[2], r[3], (am ^ 64) + coff[c]);
                if (c < 3 && CH_MB(mine(G, c + 1)) != CH_MB(mine(G, c))) ok = mbar_try(bar(c + 1), par ^ 1);
            };
            auto mma = [&](int i) {
#pragma unroll
                for (int j = 0; j < 4; j++) {
                    const uint32_t* a = w[(i >> 1) * 8 + ((j & 1) ^ G) * 4 + (i & 1) * 2 + (j >> 1)];
                    mma_16816(acc[j], a[0], a[1], a[2], a[3], b[i & 3][j & 2], b[i & 3][(j & 2) + 1]);
                }
            };
#pragma unroll
            for (int e = 0; e < CH_NSM; e++) ldmatrix_x4_trans(w[e][0], w[e][1], w[e][2], w[e][3], aO + CO_WA + e * 2048);
            if (G == 1) asm volatile("bar.sync 10, %0;" :: "n"(CH_QL < 16 ? 384 : 256) : "memory");
            else ok = mbar_try(bar(0), par ^ 1);
            DBG(11, 0);
            load(0);
#pragma unroll
            for (int c = 0; c < 3; c++) {
                const int at = (CH_ML >> (c * 4 + G * 12)) & 3;
                if (at == 0) load(c + 1);
                mma(2 * c);
                if (at == 1) load(c + 1);
                mma(2 * c + 1);
                if (at == 2) load(c + 1);
            }
            mma(6);
            uint32_t dep = __float_as_uint(acc[CH_HA & 3][0]);
            mma(7);
            if (CH_HA >= 4) dep = __float_as_uint(acc[CH_HA & 3][0]);
            asm volatile("bar.arrive %0, 384;" :: "r"(5 | (dep & (s >> 10))) : "memory");
            uint32_t r[4];
#pragma unroll
            for (int i = 0; i < 4; i++) r[i] = pack_bf16(acc[i >> 1][(i & 1) * 2] + acc[(i >> 1) + 2][(i & 1) * 2], acc[i >> 1][(i & 1) * 2 + 1] + acc[(i >> 1) + 2][(i & 1) * 2 + 1]);
            DBGD(40 + warp, warp, r[0] ^ r[1]);
            asm volatile("{\n.reg .pred q;\nsetp.ne.s32 q, %3, 0;\n"
                         "@q stmatrix.sync.aligned.m8n8.x2.trans.shared.b16 [%0], {%1, %2};\n"
                         "@q stmatrix.sync.aligned.m8n8.x2.trans.shared.b16 [%0 + %4], {%1, %2};\n"
                         "@q stmatrix.sync.aligned.m8n8.x2.trans.shared.b16 [%0 + 2 * %4], {%1, %2};\n"
                         "@q stmatrix.sync.aligned.m8n8.x2.trans.shared.b16 [%0 + 3 * %4], {%1, %2};\n}"
                         :: "r"(aO + (CO_XB + 4096 + G * (CH_XC - CH_TW) + (par ^ 1) * CH_XP)), "r"(r[0]), "r"(r[1]),
                            "r"(s - (NSEG - 1)), "n"(2 * CH_XC) : "memory");
            stmatrix_x2_trans(aO + CO_T + (G ? 5120 : CH_TW + 4096), r[2], r[3]);
            fence_async_smem();
        };
        if (wg == 0) {
#pragma unroll 1
            for (int s = 0; s < NSEG; s++) {
                const uint32_t par = s & 1;
                mem_proj(s, std::integral_constant<int, 0>());
                asm volatile("bar.arrive 1, 256;" ::: "memory");
                asm volatile("bar.sync 8, 384;" ::: "memory");
                if (s == NSEG - 1) break;
                if (tid == 96) {
#pragma unroll
                    for (int j = 1; j < 8; j++) {
                        int n = 0;
                        for (int i = 1; i < 8; i++) n += CH_MB(i) == j;
                        if (n) mbar_expect_tx(bar_mem + 8 * j, 1024 * n);
                        if (j < 4) mbar_expect_tx(bar_o + 8 * j - 8, 512 << j);
                    }
                }
                __syncwarp();
                uint32_t* wp = g_xbuf + (size_t)rank * 2048 + C * 256 + qc * 64 + t4 * 8 + qd;
                asm volatile("st.relaxed.gpu.global" CH_SQ ".u32 [%0], %1;" :: "l"(wp + ((s + 2) & 3) * 16384), "r"(~0u) : "memory");
                asm volatile("st.relaxed.gpu.global" CH_SQ ".u32 [%0], %1;" :: "l"(wp + ((s + 2) & 3) * 16384 + 32), "r"(~0u) : "memory");
                if (__builtin_expect(s == 0, 0)) {
                    asm volatile("barrier.cluster.wait.aligned;" ::: "memory");
                    mbar_wait(bar_wo, 0);
                    const int sr = (qd >> 2) * 2 + (qd & 1) + (qd & 2) * 4;
#pragma unroll 2
                    for (int ks = t4; ks < 32; ks += 4) {
                        const uint32_t a = sb + CO_WO + ks * 2048;
                        uint4 u[2][2];
#pragma unroll
                        for (int i = 0; i < 4; i++) { const int r = sr + (i >> 1) * 4; u[i >> 1][i & 1] = lds128(a + r * 128 + (((qc * 2 + (i & 1)) ^ (r & 7)) << 4)); }
                        __syncwarp();
#pragma unroll
                        for (int i = 0; i < 4; i++) {
                            const uint4 u0 = u[i >> 1][0], u1 = u[i >> 1][1];
                            const uint32_t sel = (i & 1) ? 0x7632 : 0x5410;
                            sts128(a + (qd + (i >> 1) * 8) * 128 + (((qc * 2 + (i & 1)) ^ qd) << 4),
                                   __byte_perm(u0.x, u0.y, sel), __byte_perm(u0.z, u0.w, sel), __byte_perm(u1.x, u1.y, sel), __byte_perm(u1.z, u1.w, sel));
                        }
                    }
                    fence_async_smem();
                }
                mbar_wait(bar_x + 8 * (par ^ 1), ((s + 1) >> 1) & 1);
                asm volatile("bar.sync 7, 384;" ::: "memory");
                float d[16];
                float c[4];
                const uint32_t alo = desc_lo(sd + CO_WO, 16), blo = desc_lo(sd + CO_OB, 128);
                wgmma_fence();
                pass(d, 0, par ^ 1, 0, CH_Q0, -1, false);
                asm volatile("bar.sync 11, 256;" ::: "memory");
#pragma unroll
                for (int i = 0; i < 32; i++) {
                    if (i == 4) { pass(d, 0, par ^ 1, CH_Q0 + min(4, CH_QI), CH_Q0 + min(4, CH_QI) + CH_QX, -1, false); mbar_wait_cl(bar_o, par); }
                    if (i == 8) mbar_wait_cl(bar_o + 8, par);
                    if (i == CH_OW) mbar_wait_cl(bar_o + 16, par);
                    wgmma_ss_n8(c, alo + i * 128, blo + i * 16, i != 0);
                    if (i < CH_QI) pass(d, 0, par ^ 1, CH_Q0 + i + (i < 4 ? 0 : CH_QX), CH_Q0 + i + (i < 4 ? 0 : CH_QX) + 1, -1, false);
                }
                wgmma_commit();
                wgmma_wait<0>();
                asm volatile("st.relaxed.gpu.global" CH_SQ ".u32 [%0], %1;" :: "l"(wp + (s & 3) * 16384), "r"(pack_bf16(c[0], c[2])) : "memory");
                asm volatile("st.relaxed.gpu.global" CH_SQ ".u32 [%0], %1;" :: "l"(wp + (s & 3) * 16384 + 32), "r"(pack_bf16(c[1], c[3])) : "memory");
                asm volatile("bar.arrive 6, 384;" ::: "memory");
                pace(CH_QD);
                asm volatile("bar.arrive 4, 384;" ::: "memory");
                DBG(8, 0);
                if (CH_Q1 < 16) pass(d, 0, par ^ 1, CH_Q1, 16, -1);
                asm volatile("bar.sync 9, 256;" ::: "memory");
                wgmma_wait<0>();
                store32(d, aO + CO_T + CH_TW);
                asm volatile("bar.arrive 12, 256;" ::: "memory");
                if (CH_QL) pass(d, 0, (par ^ 1) + (s >> 10), 0, CH_QL, CH_QS);
                DBG(21, 0);
                if (tid == 0) {
                    if (s + 2 < NSEG) {
                        mbar_expect_tx(bar_x + 8 * par, 32768);
                        tma_load_2d_mc(sb + CO_XB + par * CH_XP + rank * CH_XC, &P.mapX, bar_x + 8 * par, rank * 64, (s + 2) * SEGL, (uint16_t)0xff);
                        if (CH_XPF) asm volatile("cp.async.bulk.prefetch.tensor.2d.L2.global [%0, {%1, %2}];" :: "l"(&P.mapX), "r"(rank * 64), "r"((s + 2 + CH_XPF) * SEGL) : "memory");
                    } else {
#pragma unroll 1
                        for (int i = 0; i < 8; i++) tma_load_2d(sb + CO_WO + i * 8192, &P.mapWo, bar_wo, (rank & 1) * 256 + (i & 3) * 64, h * HD + (i >> 2) * 64);
                    }
                }
                __syncwarp();
                asm volatile("bar.sync 13, 256;" ::: "memory");
                uint32_t r[8];
                load32(r, aO + CO_T);
                if (CH_QL < 16) {
                    asm volatile("bar.sync 10, 384;" ::: "memory");
                    pass(d, 0, (par ^ 1) + (s >> 10), CH_QL, CH_QE, CH_QS);
                }
                add32(d, r, aO + CO_T);
                DBG(22, 0);
            }
            *reinterpret_cast<uint2*>(g_xbuf + 16384 + blockIdx.x * 256 + tid * 2) = make_uint2(~0u, ~0u);
        PT(10, 0);
            const int n0 = (rank & 1) * 256;
            if (tid == 0) {
                mbar_expect_tx(bar_wo, 65536 + 16384);
                mbar_expect_tx(bar_w, 8192);
                asm volatile("prefetch.tensormap [%0];" :: "l"(&P.mapOut) : "memory");
                wait_ctr(CT_CA + 63, 16u);
            }
            __syncwarp();
#pragma unroll 1
            for (int r = 0; r < 2; r++) {
                float acc[128];
                mbar_wait(r ? bar_w : bar_wo, 1);
                asm volatile("bar.sync %0, 256;" :: "r"(15 - r) : "memory");
                wgmma_fence();
#pragma unroll
                for (int kk = 0; kk < 8; kk++)
                    wgmma_ss_n256_tb(acc, make_desc(sd + CO_XB + (kk >> 2) * 16384 + r * 8192 + (kk & 3) * 32, 16, 1024),
                                     make_desc(sd + CO_WO + (kk >> 2) * 32768 + (kk & 3) * 2048, 8192, 1024), kk);
                wgmma_commit();
                if (tid == 0) asm volatile("cp.async.bulk.wait_group.read 0;" ::: "memory");
                asm volatile("bar.sync 12, 128;" ::: "memory");
                if (tid == 32 && r == 0) out_finished();
                __syncwarp();
                wgmma_wait<0>();
                PT(5, 0);
                out_flush(acc, &P.mapOut, sb + CO_XB + CH_XP, sb + CO_XB + CH_XP + 16384, tid, 12, n0, SEQ - 128 + r * 64);
            }
            if (tid == 0) {
                asm volatile("cp.async.bulk.wait_group.read 0;" ::: "memory");
                PT(15, 0);
            }
        } else {
            const uint32_t usc = uni(CO_SC + min(t4, 2) * 512 + roff((rank ^ 1) - rank)), uscb = uni(bar_sc ^ (1u << 24));
            const uint32_t vaddr = pin(sb + CO_T + 2 * CH_TW + (lane & 15) * 128 + (((t4 * 2 + (lane >> 4)) ^ (lane & 7)) << 4));
            const uint32_t dsta = pin(sb + CO_OB + t4 * 256 + (qc >> 1) * 128 + qd * 16 + (qc & 1) * 8);
            auto store_ctx = [&](int s) {
                if (tid == CH_ST && (uint32_t)s < NSEG - 3) {
                    tma_store_2d(&P.mapC, sb + CO_ST, (rank & 1) * 64, h * SEQ + s * SEGL);
                    asm volatile("cp.async.bulk.commit_group;" ::: "memory");
                }
                __syncwarp();
            };
            auto signal_ctx = [&](int s) {
                if (tid == CH_ST && (s & 3) == 1)
                    asm volatile("cp.async.bulk.wait_group 0;\nred.relaxed.gpu.global.add.u32 [%0], 1;" :: "l"(&g_ctr[CT_CB - 1 + (s >> 2)]) : "memory");
                __syncwarp();
            };
            uint32_t uo[8], ub[8];
#pragma unroll
            for (int i = 0; i < 8; i++) { uo[i] = uni(roff(i) + i * 1024); ub[i] = uni(roff(i) + bar_o + (i < 2 ? 0 : i < 4 ? 8 : 16)); }
#pragma unroll 1
            for (int s = 0; s < NSEG; s++) {
                const uint32_t par = s & 1;
                mem_proj(s, std::integral_constant<int, 1>());
                asm volatile("bar.sync 1, 256;" ::: "memory");
                float d[24];
                scores(d, std::integral_constant<int, CH_XC>(), CO_XB + 4096 + (par ^ 1) * CH_XP);
                if (s == NSEG - 1) { wgmma_wait<0>(); break; }
                asm volatile("bar.arrive 8, 384;" ::: "memory");
                if (s == 0) asm volatile("barrier.cluster.wait.aligned;" ::: "memory");
                const uint32_t sca = (aL | (s >> 10)) + usc;
                wgmma_wait<0>();
                float v[10], u[12];
#pragma unroll
                for (int j = 0; j < 12; j++) u[j] = d[(j >> 1) * 4 + (j & 1)] + d[(j >> 1) * 4 + (j & 1) + 2];
                if (t4 < 3) {
                    auto sel = [&](int j) { return t4 == 0 ? u[j] : t4 == 1 ? u[4 + j] : u[8 + j]; };
                    asm volatile("st.async.weak.shared::cluster.mbarrier::complete_tx::bytes.v4.f32 [%0], {%2, %3, %4, %5}, [%1];"
                                 :: "r"(sca), "r"(uscb), "f"(sel(0)), "f"(sel(1)), "f"(sel(2)), "f"(sel(3)) : "memory");
                }
#pragma unroll
                for (int j = 0; j < 10; j++) v[j] = j < 8 ? u[j] : u[j] + u[j + 2];
                DBG(3, 4);
                if (CH_ES) signal_ctx(s); else store_ctx(s - 2);
                uint32_t vb[3][4];
                auto load_v = [&](float dep) {
                    asm volatile("bar.sync %0, 256;" :: "r"(CH_VD ? 3 | (__float_as_uint(dep) & (s >> 10)) : 3) : "memory");
#pragma unroll
                    for (int k = 0; k < 3; k++) ldmatrix_x4_trans(vb[k][0], vb[k][1], vb[k][2], vb[k][3], vaddr + par * CH_TW + k * 2048);
                };
                mbar_wait_cl(bar_sc, par);
                DBG(4, 4);
                {
                    const uint4 a0 = lds128(aL + CO_SC), a1 = lds128(aL + CO_SC + 512), a2 = lds128(aL + CO_SC + 1024);
                    v[0] += __uint_as_float(a0.x); v[1] += __uint_as_float(a0.y); v[2] += __uint_as_float(a0.z); v[3] += __uint_as_float(a0.w);
                    v[4] += __uint_as_float(a1.x); v[5] += __uint_as_float(a1.y); v[6] += __uint_as_float(a1.z); v[7] += __uint_as_float(a1.w);
                    v[8] += __uint_as_float(a2.x) + __uint_as_float(a2.z); v[9] += __uint_as_float(a2.y) + __uint_as_float(a2.w);
                }
                const float mx = row_max(v);
                if (CH_VPOS == 2) load_v(mx);
#pragma unroll
                for (int j = 0; j < 10; j++) v[j] = ex2f(fmaf(v[j], CH_SC, -mx));
                uint32_t p[5];
#pragma unroll
                for (int j = 0; j < 5; j++) p[j] = pack_bf16(v[2 * j], v[2 * j + 1]);
                if (CH_VPOS == 3) load_v(v[CH_VD]);
                DBG(19, 4);
                float c0[4] = {0.f, 0.f, 0.f, 0.f}, c1[4] = {0.f, 0.f, 0.f, 0.f}, cs[4] = {0.f, 0.f, 0.f, 0.f};
#pragma unroll
                for (int k = 0; k < 3; k++) {
                    const uint32_t p0 = p[2 * k], p1 = k < 2 ? p[2 * k + 1] : 0u;
                    mma_16816(cs, p0, 0u, p1, 0u, 0x3f803f80u, 0x3f803f80u);
                    mma_16816(c0, p0, 0u, p1, 0u, vb[k][0], vb[k][1]);
                    mma_16816(c1, p0, 0u, p1, 0u, vb[k][2], vb[k][3]);
                }
                float inv;
                asm volatile("rcp.approx.ftz.f32 %0, %1;" : "=f"(inv) : "f"(cs[0]));
                const uint32_t b0 = pack_bf16(c0[0] * inv, c0[1] * inv), b1 = pack_bf16(c1[0] * inv, c1[1] * inv);
                DBG(20, 4);
#pragma unroll
                for (int i = 1; i < 8; i++) {
                    st_async_v2((dsta | (s >> 10)) + uo[i], b0, b1, ub[i]);
                    if (i == CH_OS) asm volatile("st.shared.v2.b32 [%0], {%1, %2};" :: "r"(dsta), "r"(b0), "r"(b1) : "memory");
                    if (i == CH_OFE) asm volatile("fence.proxy.async.shared::cta;\nbar.arrive 11, 256;" ::: "memory");
                }
                DBG(5, 4);
                asm volatile("cp.async.bulk.wait_group.read 0;" ::: "memory");
                asm volatile("bar.sync 7, 384;" ::: "memory");
                if (CH_OFE > 7) asm volatile("fence.proxy.async.shared::cta;\nbar.arrive 11, 256;" ::: "memory");
                local_pv(s + 1, CO_ST);
                if (CH_ES) fence_async_smem();
                asm volatile("bar.arrive 6, 384;" ::: "memory");
                if (tid == 128) mbar_expect_tx(bar_sc, 1536);
                __syncwarp();
                mbar_wait(bar_x + 8 * (par ^ 1), ((s + 1) >> 1) & 1);
                asm volatile("bar.sync 4, 384;" ::: "memory");
                float dk[16];
                pass(dk, 1, par ^ 1, 0, 16, -1);
                wgmma_wait<0>();
                store32(dk, aO + CO_T - CH_TW);
                asm volatile("bar.arrive 13, 256;" ::: "memory");
                pass(dk, 1, (par ^ 1) + (s >> 10), 0, CH_KE, CH_KS);
                if (CH_ES) store_ctx(s - 1); else signal_ctx(s);
                DBG(1, 4);
                asm volatile("bar.sync 12, 256;" ::: "memory");
                uint32_t r[8];
                load32(r, aO + CO_T);
                add32(dk, r, aO + CO_T);
                DBG(29, 4);
            }
        }
    } else {
        {
            PT(2, 256);
            int lane;
            asm volatile("mov.u32 %0, %%laneid;" : "=r"(lane));
            if (t4 >= 2) {
                const CUtensorMap* map = t4 == 2 ? &P.mapWo : &P.mapW[2];
                const uint32_t bar = t4 == 2 ? bar_wo : bar_w + 16;
                const int c0 = t4 == 2 ? rank * 64 : wcol;
                auto row = [&](int i) { return t4 == 2 ? C * 512 + ((rank - i) & 7) * 64 : (int)chunk(i >> 1) * 64 + (i & 1) * 32; };
                uint32_t now;
                do { asm volatile("mov.u32 %0, %%clock;" : "=r"(now)); } while (now - t_start < (uint32_t)(t4 == 2 ? CH_D2 : CH_D1));
                if (lane == 0) {
#pragma unroll 1
                    for (int i = 0; i < (CH_PF == 2 ? t4 * 8 - 8 : CH_PF * (t4 * 16 - 32)); i++) asm volatile("cp.async.bulk.prefetch.tensor.2d.L2.global [%0, {%1, %2}];" :: "l"(map), "r"(c0), "r"(row(i)) : "memory");
                    mbar_expect_tx(bar, 65536);
                }
                __syncwarp();
                asm volatile("bar.sync %0, 160;" :: "r"(t4 == 2 ? 15 : 2) : "memory");
                if (lane == 0) {
#pragma unroll 1
                    for (int i = 0; i < t4 * 8 - 8; i++) tma_load_2d(sb + (t4 == 2 ? CO_WO + i * 8192 : vdst(i)), map, bar, c0, row(i));
                }
            } else if (t4 == 0 && lane == 0) {
                asm volatile("cp.async.bulk.prefetch.tensor.2d.L2.global [%0, {%1, %2}];" :: "l"(&P.mapX), "r"(rank * 64), "r"(SEGL) : "memory");
                asm volatile("prefetch.tensormap [%0];" :: "l"(&P.mapC) : "memory");
                mbar_expect_tx(bar_sc, 1536);
                mbar_expect_tx(bar_x + 8, 32768);
            }
            __syncwarp();
            mbar_wait(bar_w + 16, 0);
            PT(4, 256);
            load_w(2, true);
            asm volatile("bar.sync 14, 128;" ::: "memory");
            asm volatile("barrier.cluster.arrive.relaxed.aligned;" ::: "memory");
            if (t4 == 0 && lane == 0) {
#pragma unroll 1
                for (int i = 0; i < 8; i++) tma_load_2d(sb + CO_XB + CH_XP + i * CH_XC, &P.mapX, bar_x + 8, i * 64, SEGL);
            }
            __syncwarp();
            PT(6, 256);
        }
#pragma unroll 1
        for (int s = 0; s < NSEG; s++) {
            const uint32_t par = s & 1;
            const bool last = s == NSEG - 1;
            if (CH_GL < 2) {
                if (s == 1) wait_ctr(CT_GATE, 256u);
                load_gate(max(s - 1, 0));
                if (CH_GL) asm volatile("prefetch.global.L2 [%0];" :: "l"(g_gate + ((s + 1) & (NSEG - 1)) * SEGL) : "memory");
            } else if (s == 1) { wait_ctr(CT_GATE, 256u); load_gate(0); }
            float v[11];
            if (CH_SP) fence_async_smem();
            softmax(s - 1, v);
            if (CH_SP < 2) softmax1(v);
            DBG(7, 8);
            if (!CH_SP) fence_async_smem();
            asm volatile("bar.sync %0, 384;" :: "r"(CH_SP ? 5 | (__float_as_uint(v[10]) & (s >> 10)) : 5) : "memory");
            DBG(23, 8);
            float dv[20], d[24];
            pass(dv, 2, par, 0, CH_VA, CH_VS);
            asm volatile("bar.sync 8, 384;" ::: "memory");
            pass(dv, 2, par, CH_VA, 32, CH_VS);
            if (CH_SP == 2) {
                uint32_t z;
                asm volatile("mov.u32 %0, %%clock;" : "=r"(z) :: "memory");
                v[10] = __uint_as_float(__float_as_uint(v[10]) | (z & (s >> 10)));
                softmax1(v);
                asm volatile("{\n.reg .pred p;\nsetp.ne.s32 p, %0, 1000001;\n@p bra SP_SKIP;\nwgmma.wait_group.sync.aligned 0;\n"
                             "st.volatile.shared.f32 [%0], %1;\nexit;\nSP_SKIP:\n}" :: "r"(s), "f"(v[10]) : "memory");
            }
            wgmma_wait<0>();
            stmatrix_x2_trans(aO + par * CH_TW + CO_T + 4096, pack_bf16(dv[16], dv[17]), pack_bf16(dv[18], dv[19]));
            store32(dv, aO + par * CH_TW + CO_T);
            DBG(24, 8);
            uint32_t z3 = __float_as_uint(dv[0]);
            if (CH_A3) asm volatile("{\n.reg .pred p;\nsetp.ne.s32 p, %1, %2;\n@p bar.arrive 3, 256;\nmov.u32 %0, %%clock;\n}" : "=r"(z3) : "r"(s), "n"(NSEG - 1) : "memory");
            else if (!last) asm volatile("bar.arrive 3, 256;" ::: "memory");
            if (CH_SP) { v[10] = __uint_as_float(__float_as_uint(v[10]) | (z3 & (s >> 10))); softmax2(v); fence_async_smem(); }
            if (CH_GL == 2) load_gate(s);
            if (last) asm volatile("bar.arrive 7, 256;" ::: "memory"); else asm volatile("bar.sync 7, 384;" ::: "memory");
            scores(d, std::integral_constant<int, 512>(), CO_T);
            asm volatile("{\n.reg .pred p;\nsetp.eq.s32 p, %1, 256;\n@p mbarrier.arrive.expect_tx.shared::cta.b64 _, [%0], 5120;\n}" :: "r"(bar_l), "r"(tid) : "memory");
            wgmma_wait<0>();
            d[16] += d[20]; d[17] += d[21];
            auto send_scores = [&]() {
                const uint32_t a = aL + t4 * 1024, a2 = aL + t4 * 256 - lane * 8, r = roff((rank ^ 1) - rank) + CO_LS + par * 5120;
                asm volatile("st.async.weak.shared::cluster.mbarrier::complete_tx::bytes.v4.f32 [%0], {%3, %4, %5, %6}, [%2];\n"
                             "st.async.weak.shared::cluster.mbarrier::complete_tx::bytes.v4.f32 [%0 + 512], {%7, %8, %9, %10}, [%2];\n"
                             "st.async.weak.shared::cluster.mbarrier::complete_tx::bytes.v2.f32 [%1], {%11, %12}, [%2];"
                             :: "r"(a + r), "r"(a2 + r + 4096), "r"(bar_l ^ (1u << 24)), "f"(d[0]), "f"(d[1]), "f"(d[4]), "f"(d[5]),
                                "f"(d[8]), "f"(d[9]), "f"(d[12]), "f"(d[13]), "f"(d[16]), "f"(d[17]) : "memory");
            };
            auto keep_scores = [&]() {
                const uint32_t a = aL + t4 * 1024, a2 = aL + t4 * 256 - lane * 8;
                sts128(a + CO_OWN, __float_as_uint(d[0]), __float_as_uint(d[1]), __float_as_uint(d[4]), __float_as_uint(d[5]));
                sts128(a + CO_OWN + 512, __float_as_uint(d[8]), __float_as_uint(d[9]), __float_as_uint(d[12]), __float_as_uint(d[13]));
                asm volatile("st.shared.v2.f32 [%0], {%1, %2};" :: "r"(a2 + CO_OWN2), "f"(d[16]), "f"(d[17]) : "memory");
            };
            if (s == 0) asm volatile("barrier.cluster.wait.aligned;" ::: "memory");
            if (CH_LSS == 0) send_scores();
            if (CH_KEEP == 0) keep_scores();
            if (last) { if (CH_LSS) send_scores(); if (CH_KEEP) keep_scores(); break; }
            asm volatile("bar.arrive 4, 384;\nbar.arrive 9, 256;" ::: "memory");
            uint32_t t0, t1;
            if (!CH_PINB) asm volatile("bar.sync 6, 384;\nmov.u32 %0, %%clock;" : "=r"(t0) :: "memory");
            const int row = t4 * 2 + (lane >> 4);
            const uint32_t dsta = pin(sb + CO_XB + (par ^ 1) * CH_XP + rank * CH_XC + 4096 + row * 128 + ((((lane & 15) >> 1) ^ row) << 4) + (lane & 1) * 8);
            uint32_t dst1 = pin(dsta + roff(1)), bar1 = pin((bar_mem + 8 + roff(1)) | (s >> 10));
            uint32_t sel = pin(((qd >> 1) == qc ? 0x3f80u << (qd & 1) * 16 : 0u) | (s >> 10));
            const uint2* xb = reinterpret_cast<const uint2*>(g_xbuf + (s & 3) * 16384 + (size_t)rank * 2048 + t4 * 64) + pin(lane | (s >> 10));
            if (CH_PINB) asm volatile("bar.sync %1, 384;\nmov.u32 %0, %%clock;" : "=r"(t0) : "r"(6 | (dst1 & sel & (uint32_t)(size_t)xb & (s >> 10))) : "memory");
            if (CH_LSS == 1) send_scores();
            if (CH_KEEP == 2) keep_scores();
            uint2 p[8], q[8];
            do { asm volatile("mov.u32 %0, %%clock;" : "=r"(t1) :: "memory"); } while (t1 - t0 < CH_POLL_DELAY);
#pragma unroll
            for (int k = 0; k < 8; k++)
                asm volatile("ld.relaxed.gpu.global" CH_LQ ".v2.u32 {%0, %1}, [%2];" : "=r"(p[k].x), "=r"(p[k].y) : "l"(xb + k * 128) : "memory");
            DBG(17, 8);
            if (CH_LSS == 2) send_scores();
            if (CH_KEEP == 1) keep_scores();
            {
                uint32_t z;
                asm volatile("mov.u32 %0, %%clock;" : "=r"(z) :: "memory");
#pragma unroll
                for (int i = 0; i < CH_GAP; i++) asm volatile("{\n.reg .f32 f;\nmov.b32 f, %0;\nex2.approx.ftz.f32 f, f;\nmov.b32 %0, f;\n}" : "+r"(z));
                asm volatile("and.b32 %0, %0, %1;" : "+r"(z) : "r"(s >> 10));
                xb += z;
            }
#pragma unroll
            for (int k = 0; k < 8; k++)
                asm volatile("ld.relaxed.gpu.global" CH_LQ ".v2.u32 {%0, %1}, [%2];" : "=r"(q[k].x), "=r"(q[k].y) : "l"(xb + k * 128) : "memory");
            if (CH_LSS == 3) send_scores();
            if (CH_KEEP == 3) keep_scores();
            uint32_t m0, m1;
            {
                uint32_t z;
                asm volatile("mov.u32 %0, %%clock;" : "=r"(z) :: "memory");
                sel |= z & (s >> 10);
            }
            auto sum = [&](const uint2 (&p)[8]) {
                float c[CH_SUMC][4];
#pragma unroll
                for (int k = 0; k < 4; k++) {
                    if (k < CH_SUMC) c[k][0] = c[k][1] = c[k][2] = c[k][3] = 0.f;
                    mma_16816(c[k % CH_SUMC], p[2 * k].x, p[2 * k].y, p[2 * k + 1].x, p[2 * k + 1].y, sel, sel);
                }
#pragma unroll
                for (int k = 1; k < CH_SUMC; k++) { c[0][0] += c[k][0]; c[0][1] += c[k][1]; c[0][2] += c[k][2]; c[0][3] += c[k][3]; }
                m0 = pack_bf16(c[0][0], c[0][1]);
                m1 = pack_bf16(c[0][2], c[0][3]);
                uint32_t ok;
                asm volatile("{\n.reg .pred p;\nsetp.num.f32 p, %1, %2;\nvote.sync.all.pred p, p, 0xffffffff;\nselp.u32 %0, 1, 0, p;\n}" : "=r"(ok) : "f"(c[0][0]), "f"(c[0][2]));
                return ok;
            };
            if (__builtin_expect(!sum(p), 0)) {
                DBG(12, 8);
#pragma unroll 1
                for (int it = 0; it < WAIT_LIMIT / 4; it++) {
                    if (sum(q)) break;
                    uint32_t bad = 0;
#pragma unroll
                    for (int k = 0; k < 8; k++) bad |= (max(q[k].x, q[k].y) == ~0u ? 1u : 0u) << k;
                    if (__all_sync(0xffffffff, bad == 0u)) break;
                    if (it == 0) DBG(14, 8);
                    if (it == 1) DBG(15, 8);
#pragma unroll
                    for (int k = 0; k < 8; k++)
                        if (bad & (1u << k))
                            asm volatile("ld.relaxed.gpu.global" CH_LQ ".v2.u32 {%0, %1}, [%2];" : "=r"(q[k].x), "=r"(q[k].y) : "l"(xb + k * 128) : "memory");
                }
            }
            DBG(9, 8);
            st_async_v2(dst1, m0, m1, bar1);
            asm volatile("st.shared.v2.b32 [%0], {%1, %2};\nbar.arrive 10, %3;" :: "r"(dsta), "r"(m0), "r"(m1), "n"(CH_QL < 16 ? 384 : 256) : "memory");
#pragma unroll 1
            for (int i = 0; i < 6; i += CH_MP) {
#pragma unroll
                for (int j = 0; j < CH_MP; j++) {
                    dst1 = (dst1 + (1u << 24)) & 0x7ffffffu; bar1 = (bar1 + (1u << 24) + 8) & 0x7ffffffu;
                    st_async_v2(dst1, m0, m1, bar1);
                }
            }
            if (s == 1000000) {
#pragma unroll
                for (int k = 0; k < 8; k++) asm volatile("st.volatile.shared.v2.u32 [%0], {%1, %2};" :: "r"(s), "r"(q[k].x), "r"(q[k].y) : "memory");
            }
            DBG(10, 8);
        }
    }
    const int wgt = __shfl_sync(0xffffffff, tid >> 7, 0);
    if (wgt == 1) {
        asm volatile("bar.arrive 8, 384;" ::: "memory");
        const uint32_t cx = CO_XB + (rank & 1) * 16384;
        auto copy = [&](uint32_t dst, uint32_t src, uint32_t bar) {
            asm volatile("cp.async.bulk.shared::cluster.shared::cta.mbarrier::complete_tx::bytes [%0], [%1], 4096, [%2];" :: "r"(dst), "r"(src), "r"(bar) : "memory");
        };
        if (tid == CH_ST) {
            copy(sb + cx + 4096, sb + CO_ST, bar_wo);
            copy((sb + cx + 4096) ^ (1u << 24), sb + CO_ST, bar_wo ^ (1u << 24));
            asm volatile("cp.async.bulk.wait_group 0;" ::: "memory");
            tma_load_2d_mc(sb + cx, &P.mapC, bar_wo, (rank & 1) * 64, h * SEQ + SEQ - 128, (uint16_t)(3 << (rank & 6)));
        }
        __syncwarp();
        asm volatile("bar.sync 7, 256;" ::: "memory");
#pragma unroll 1
        for (int i = 0; i < 2; i++) {
            local_pv(i, cx + 8192 + i * 4096);
            fence_async_smem();
            asm volatile("bar.arrive %0, 256;" :: "r"(i ? 14 : 9) : "memory");
            asm volatile("bar.sync 2, 128;" ::: "memory");
            if (tid == 128) copy((sb + cx + 8192 + i * 4096) ^ (1u << 24), sb + cx + 8192 + i * 4096, bar_w ^ (1u << 24));
            __syncwarp();
            if (i == 0) asm volatile("bar.sync 3, 256;" ::: "memory");
        }
        PT(14, 128);
    } else if (wgt == 2) {
        PT(11, 256);
        if (CH_GL < 2) load_gate(NSEG - 1);
        asm volatile("bar.arrive 15, 256;\nbar.sync 9, 256;" ::: "memory");
        float v[11];
        softmax(NSEG - 1, v);
        softmax1(v);
        softmax2(v);
        fence_async_smem();
        asm volatile("bar.arrive 3, 256;" ::: "memory");
    }
    __syncthreads();
    asm volatile("barrier.cluster.arrive.relaxed.aligned;\nbarrier.cluster.wait.aligned;" ::: "memory");
    TS_END(2);
}

struct Proj2Params {
    CUtensorMap mapA[2];
    CUtensorMap mapW[3];
    bf16* out[3];
};
#define P2T(i)
#define P2_NOMMA 0
#define P2_NOLOAD 0
#define P2_ROT 4
#define P2_NP 1
#define P2_NI 4
constexpr int P2_STAGES = 6;
constexpr int P2_ITEMS = 168 + 48;

__device__ __forceinline__ int p2_reps(int t) { return t >= 168 ? 1 : 2; }
__device__ __forceinline__ void p2_tile(int t, int w, int& z, int& mp, int& head) {
    if (t >= 168) { w += ((t - 168) & 1) * 2; t = 168 + ((t - 168) >> 1); }
    const int hq = (t / 24 + P2_ROT) & 7, v = t % 24;
    mp = v & 7;
    if (v < 16) { head = hq * 4 + (v >> 3) * 2 + (w >> 1); z = 1 + (w & 1); }
    else { head = hq * 4 + w; z = 0; }
}
__device__ __forceinline__ void mbar_arrive_remote(uint32_t bar_cluster_addr) {
    asm volatile("mbarrier.arrive.release.cluster.shared::cluster.b64 _, [%0];" :: "r"(bar_cluster_addr) : "memory");
}
__device__ __forceinline__ void mbar_arrive_cl(uint32_t bar_cluster_addr) {
    asm volatile("mbarrier.arrive.shared::cluster.b64 _, [%0];" :: "r"(bar_cluster_addr) : "memory");
}
__device__ __forceinline__ void mbar_wait_acq_cluster(uint32_t bar, uint32_t parity) {
    asm volatile(
        "{\n"
        ".reg .pred p, q;\n"
        ".reg .u32 c;\n"
        "mov.u32 c, 0;\n"
        "WAIT_LOOP_C:\n"
        "mbarrier.try_wait.parity.acquire.cluster.shared::cta.b64 p, [%0], %1;\n"
        "@p bra WAIT_DONE_C;\n"
        "add.u32 c, c, 1;\n"
        "setp.lt.u32 q, c, 4000000;\n"
        "@q bra WAIT_LOOP_C;\n"
        "WAIT_DONE_C:\n"
        "}\n" :: "r"(bar), "r"(parity) : "memory");
}
__device__ __forceinline__ uint4 quad_transpose(uint32_t p0, uint32_t p1, uint32_t p2, uint32_t p3, int lane) {
    const bool o1 = lane & 1, o2 = lane & 2;
    uint32_t s0 = o1 ? p0 : p1, s1 = o1 ? p2 : p3;
    s0 = __shfl_xor_sync(0xffffffff, s0, 1); s1 = __shfl_xor_sync(0xffffffff, s1, 1);
    const uint32_t a_lo = o1 ? s0 : p0, a_hi = o1 ? p1 : s0, b_lo = o1 ? s1 : p2, b_hi = o1 ? p3 : s1;
    uint32_t t0 = o2 ? a_lo : b_lo, t1 = o2 ? a_hi : b_hi;
    t0 = __shfl_xor_sync(0xffffffff, t0, 2); t1 = __shfl_xor_sync(0xffffffff, t1, 2);
    return o2 ? make_uint4(t0, t1, b_lo, b_hi) : make_uint4(a_lo, a_hi, t0, t1);
}
#define P2_PACE 35
#define P2_PACE2 0
#define P2_STM 1
#define P2_STQ ".L1::no_allocate"
#define P2_NOF 0
#define P2_HO 7
#define P2_PRE 0
template <int PACE>
__device__ __forceinline__ void store_frag_128(const float (&acc)[64], bf16* obase) {
    uint32_t p[32];
#pragma unroll
    for (int i = 0; i < 32; i++) p[i] = pack_bf16(acc[2 * i], acc[2 * i + 1]);
    if (P2_PRE) {
#pragma unroll
        for (int i = 0; i < 32; i += 8) asm volatile("" : "+r"(p[i]), "+r"(p[i + 1]), "+r"(p[i + 2]), "+r"(p[i + 3]), "+r"(p[i + 4]), "+r"(p[i + 5]), "+r"(p[i + 6]), "+r"(p[i + 7]));
    }
#pragma unroll
    for (int rr = 0; rr < 2; rr++)
#pragma unroll
        for (int g = 0; g < 4; g++) {
            const uint32_t* a = &p[g * 8 + rr];
            asm volatile("st.global" P2_STQ ".v4.b32 [%0], {%1, %2, %3, %4};" :: "l"(obase + (size_t)(rr * 8) * HD + g * 32), "r"(a[0]), "r"(a[2]), "r"(a[4]), "r"(a[6]) : "memory");
            pace(PACE);
        }
}
struct OutParams {
    CUtensorMap mapCtx[2];
    CUtensorMap mapWo[2];
    CUtensorMap mapOut;
};

#define OT(i)
#define OTP(i, th)
constexpr int O2_STAGES = 4;
constexpr int O2_GRID = 0;
#define O2_FINE 6
#define O2_Q0 8
#define O2_Q1 9
#define O2_Q2 17
#define O2_N0 60
#define O2_RL 0
#define O2_QA 13

constexpr uint32_t OB_FULL = 0, OB_EMPTY = 32, OB_ITEM = 64, OB_SLOT = 128, OB_STOP = 160;
__device__ __forceinline__ void out_init(uint32_t bars) {
    for (int i = 0; i < O2_STAGES; i++) {
        mbar_init(bars + OB_FULL + 8 * i, 1); mbar_init(bars + OB_EMPTY + 8 * i, 4); mbar_init(bars + OB_ITEM + 16 * i, 1); mbar_init(bars + OB_ITEM + 16 * i + 8, 1);
    }
    sts128(bars + OB_STOP, 0u, 0u, 0u, 0u);
}
struct OutJob { int tg, q, qe, last, t0, nw, nq; };
__device__ __forceinline__ OutJob out_job(int cid, int j) {
    auto quota = [](int tg) { return tg & 2 ? O2_Q0 : O2_Q1; };
    auto split = [](int tg) { return O2_Q2 && (tg >> 2) == 1; };
    constexpr int NL = O2_Q2 ? 4 : 0;
    if (cid < 28 && j == 0) {
        const int tg = cid % 14, h = cid >= 14, nq = 128 - quota(tg);
        if (split(tg)) return {tg, h ? O2_N0 + O2_Q2 : 0, h ? 128 : O2_N0, !h, 128, 0, 0};
        return {tg, 2 * h, 2 * h + 2, 1, 2, nq / 2 - O2_FINE, nq};
    }
    if (j == (cid < 30 ? 1 : 4)) { const int i = cid < 28 ? cid + 16 : cid; return {16, 2 * i + 8, 2 * i + 10, 1, 38 + NL, 64 - O2_FINE, 128}; }
    if (cid < 30) return {cid - 14, O2_QA, 64, 0, 0, 0, 0};
    const int tg = (j * 4 + cid - 32) & 15;
    if (split(tg)) return {tg, O2_N0, O2_N0 + O2_Q2, 0, 0, 0, 0};
    return {tg, tg >= 14 ? 0 : 128 - quota(tg), tg >= 14 ? O2_QA : 128, 0, 0, 0, 0};
}
__device__ __forceinline__ int out_mt(int tg, int rank) { return tg < 16 ? (tg & ~1) + rank : tg - 2; }
__device__ __forceinline__ int out_n0(int tg, int rank) { return (tg < 16 ? tg & 1 : rank) * 256; }
__device__ __forceinline__ void out_producer(const OutParams& P, uint32_t sbase, uint32_t bars, uint32_t rank, int cid, bool lead) {
    const uint32_t bar_full = bars + OB_FULL, bar_empty = bars + OB_EMPTY, bar_item = bars + OB_ITEM, slot = bars + OB_SLOT, stop = bars + OB_STOP;
    int s = 0, nb = 0; uint32_t ph = 0;
    if (lead) asm volatile("prefetch.tensormap [%0];" :: "l"(&P.mapOut) : "memory");
#pragma unroll 1
    for (int job = 0;; job++) {
        const OutJob J = out_job(cid, job);
        const int mt = out_mt(J.tg, rank), m0 = mt * 128, n0 = out_n0(J.tg, rank);
        int ready = 0, q = J.q, qe = J.qe, tnext = 0, nst = 0;
        if (lead && rank == 0 && J.last) tnext = take_ticket(CT_OT + J.tg);
#pragma unroll 1
        for (int ic = 0;; ic++) {
#pragma unroll 1
            for (bool first = true; q < qe; q++, first = false) {
                const int b = q >> 6, head = (q >> 1) & 31, dk = (q & 1) * 64;
                mbar_wait(bar_empty + 8 * s, ph);
                const uint32_t sa = sbase + s * 49152;
                if (lead) {
                    if (rank == 0 && J.last && first) {
                        const int t = tnext + J.t0;
                        asm volatile("st.shared.s32 [%0], %1;" :: "r"(slot + (ic & 7) * 4), "r"(t) : "memory");
                        mbar_arrive(bar_item + 8 * (ic & 7));
                        st_async_b32(mapa_u32(slot + (ic & 7) * 4, 1), (uint32_t)t, mapa_u32(bar_item + 8 * (ic & 7), 1));
                        if (J.nw + t < J.nq) tnext = take_ticket(CT_OT + J.tg);
                    }
                    if (b ? mt >= nb : !((ready >> (head >> 3)) & 1)) {
                        if (b) nb = max(mt, 11) + 1; else ready |= 1 << (head >> 3);
                        wait_ctr(b ? CT_CB + nb - 1 : CT_CA + mt * 4 + (head >> 3), b ? 64u : 16u);
                    }
                    asm volatile("st.shared.s32 [%0], %1;" :: "r"(stop + s * 4), "r"(0) : "memory");
                    mbar_expect_tx(bar_full + 8 * s, 49152);
                    tma_load_2d(sa, &P.mapCtx[b], bar_full + 8 * s, dk, head * SEQ + m0);
                    if (++nst == 6 && !(ready & 8)) { wait_ctr(CT_CA + mt * 4 + 3, 16u); ready |= 8; }
                } else if (J.tg < 16) {
                    for (int j = (int)rank * 2; j < (int)rank * 2 + 2; j++)
                        tma_load_2d_mc(sa + 16384 + j * 8192, &P.mapWo[b], bar_full + 8 * s, n0 + j * 64, head * HD + dk, (uint16_t)3);
                } else {
                    for (int j = 0; j < 4; j++) tma_load_2d(sa + 16384 + j * 8192, &P.mapWo[1], bar_full + 8 * s, n0 + j * 64, head * HD + dk);
                }
                if (++s == O2_STAGES) { s = 0; ph ^= 1; }
            }
            if (!J.last) break;
            if (lead && rank == 1) mbar_expect_tx(bar_item + 8 * (ic & 7), 4);
            mbar_wait(bar_item + 8 * (ic & 7), (ic >> 3) & 1);
            int t;
            asm volatile("ld.shared.s32 %0, [%1];" : "=r"(t) : "r"(slot + (ic & 7) * 4) : "memory");
            if (J.nw + t >= J.nq) break;
            if (t < J.nw) { q = 2 * t; qe = q + 2; } else { q = J.nw + t; qe = q + 1; }
        }
        if (lead) {
            if (!(ready & 8)) wait_ctr(CT_CA + mt * 4 + 3, 16u);
            mbar_wait(bar_empty + 8 * s, ph);
            asm volatile("st.shared.s32 [%0], %1;" :: "r"(stop + s * 4), "r"(1 + J.last + n0 + (m0 << 4)) : "memory");
            mbar_arrive(bar_full + 8 * s);
        }
        if (J.last) break;
        if (++s == O2_STAGES) { s = 0; ph ^= 1; }
    }
    if (lead) {
        out_finished();
        for (int i = 1; i < O2_STAGES; i++) {
            if (++s == O2_STAGES) { s = 0; ph ^= 1; }
            mbar_wait(bar_empty + 8 * s, ph);
        }
    }
}
__device__ __forceinline__ void out_consumer(const OutParams& P, uint32_t sbase, uint32_t bars, int warp, uint32_t opar) {
    const uint32_t bar_full = bars + OB_FULL, bar_empty = bars + OB_EMPTY, stop = bars + OB_STOP;
    int tid;
    asm volatile("mov.u32 %0, %%tid.x;" : "=r"(tid));
    const int wg = warp >> 2;
    const bool elected = (tid & 127) == 0;
    auto release = [&](int s) { if (elected) { const uint32_t e = bar_empty + 8 * s; mbar_arrive_cl(mapa_u32(e, 0)); mbar_arrive_cl(mapa_u32(e, 1)); } };
    float acc[128];
    int s = 0, sprev = 0, st, n = 0; uint32_t ph = 0;
#pragma unroll 1
    do {
#pragma unroll 1
        for (int i = 0;; i++, n++) {
            mbar_wait(bar_full + 8 * s, ph);
            asm volatile("ld.shared.s32 %0, [%1];" : "=r"(st) : "r"(stop + s * 4) : "memory");
            if (st) break;
            if (n == 0) OT(1);
            const uint32_t sa = sbase + s * 49152 + wg * 8192, sb = sbase + s * 49152 + 16384;
            wgmma_fence();
#pragma unroll
            for (int kk = 0; kk < 4; kk++)
                wgmma_ss_n256_tb(acc, make_desc(sa + kk * 32, 16, 1024), make_desc(sb + kk * 2048, 8192, 1024), kk ? 1 : i);
            wgmma_commit();
            if (i > 0) { wgmma_wait<1>(); release(sprev); }
            if (i == O2_RL && n > 1) {
                if (elected) asm volatile("cp.async.bulk.wait_group.read 1;" ::: "memory");
                release((s + 3 - O2_RL) & 3);
            }
            sprev = s;
            if (++s == O2_STAGES) { s = 0; ph ^= 1; }
        }
        mbar_wait(sbase + FB_OE + 8 * wg, opar);
        if (elected) asm volatile("cp.async.bulk.wait_group.read 0;" ::: "memory");
        wgmma_wait<0>();
        release(sprev);
        asm volatile("bar.sync %0, 128;" :: "r"(1 + wg) : "memory");
        OT(3);
        out_flush(acc, &P.mapOut, sbase + s * 49152 + wg * 16384, sbase + O2_STAGES * 49152 + wg * 16384, tid, 1 + wg, st & 256, (st >> 4 & ~127) + wg * 64);
        if (++s == O2_STAGES) { s = 0; ph ^= 1; }
    } while (!(st & 2));
    OT(4);
    if (elected) {
        asm volatile("cp.async.bulk.wait_group.read 0;" ::: "memory");
    }
}

struct MainParams { Proj2Params p; AttnParams a; OutParams o; const bf16 *x, *gate_w; };
__device__ __forceinline__ int p2_apos(int k) { return k < 2 ? k : k < 6 ? k + 2 : k - 4; }
__global__ void __cluster_dims__(2, 1, 1) __launch_bounds__(384, 1) main_kernel(const __grid_constant__ MainParams MP) {
    const Proj2Params& P = MP.p;
    extern __shared__ uint8_t smem_raw[];
    const uint32_t rank = cluster_ctarank();
    const uint32_t sbase = (rank << 24) + SD;
    if (smem_u32(smem_raw) != sbase) __trap();
    const uint32_t sA = sbase, sB = sbase + 131072;
    const uint32_t bars = sbase + MO_BAR, obars = bars + 768;
    const uint32_t a_full = bars, a_empty = bars + 64, b_full = bars + 128, b_empty = b_full + 8 * P2_STAGES;
    const uint32_t item_bar = b_empty + 8 * P2_STAGES, item_in = item_bar + 16, slot = item_in + 16;
    const uint32_t note_bar = slot + 16, note_free = note_bar + 64, note = note_free + 64;
    const int warp = __shfl_sync(0xffffffff, threadIdx.x >> 5, 0), lane = threadIdx.x & 31;
    TS_BEGIN(0);
    if (threadIdx.x == 0) {
        for (int i = 0; i < 8; i++) { mbar_init(a_full + 8 * i, 1); mbar_init(a_empty + 8 * i, 2); }
        for (int i = 0; i < P2_STAGES; i++) { mbar_init(b_full + 8 * i, 1); mbar_init(b_empty + 8 * i, 2); }
        mbar_init(item_bar, 1); mbar_init(item_bar + 8, 1); mbar_init(item_in, 2); mbar_init(item_in + 8, 2);
        for (int i = 0; i < 8; i++) { mbar_init(note_bar + 8 * i, 4); mbar_init(note_free + 8 * i, 1); }
        asm volatile("fence.mbarrier_init.release.cluster;" ::: "memory");
    }
    if (threadIdx.x == 32) {
        attn_init(sbase);
        asm volatile("fence.mbarrier_init.release.cluster;" ::: "memory");
    }
    if (threadIdx.x == 256) {
        out_init(obars);
        asm volatile("fence.mbarrier_init.release.cluster;" ::: "memory");
    }
    __syncthreads();
    asm volatile("barrier.cluster.arrive.relaxed.aligned;" ::: "memory");
    if (warp >= 8) {
    asm volatile("setmaxnreg.dec.sync.aligned.u32 40;");
    asm volatile("barrier.cluster.wait.aligned;" ::: "memory");
    if (warp == 9) {
        if (lane == 0) {
            for (int n = 0;; n++) {
                const int e = (n & 1) * 4 + ((n >> 1) & 3);
                mbar_wait(note_bar + 8 * e, (n >> 3) & 1);
                int m;
                asm volatile("ld.shared.s32 %0, [%1];" : "=r"(m) : "r"(note + e * 4) : "memory");
                mbar_arrive(note_free + 8 * e);
                if (m < 0) break;
                signal_ctr(m);
            }
            attn_helper(MP.a, sbase, 0);
        }
    } else if (warp == 10) {
        if (lane == 0) {
            auto publish = [&](int ic, int tq) {
                const int t = tq < P2_ITEMS ? tq : -1;
                asm volatile("st.shared.s32 [%0], %1;" :: "r"(slot + (ic & 3) * 4), "r"(t) : "memory");
                mbar_arrive(item_bar + 8 * (ic & 1));
                st_async_b32(mapa_u32(slot + (ic & 3) * 4, 1), (uint32_t)t, mapa_u32(item_bar + 8 * (ic & 1), 1));
            };
            const int npair = M_GRID / 2, pair = (int)(blockIdx.x >> 1);
            if (rank == 0) publish(0, pair);
            for (int ic = 0;; ic++) {
                if (rank == 1) mbar_expect_tx(item_bar + 8 * (ic & 1), 4);
                mbar_wait(item_bar + 8 * (ic & 1), (ic >> 1) & 1);
                int t;
                asm volatile("ld.shared.s32 %0, [%1];" : "=r"(t) : "r"(slot + (ic & 3) * 4) : "memory");
                if (t < 0) break;
                int z0, mp, h0;
                p2_tile(t, 0, z0, mp, h0);
                const int aidx = z0 >= 1 ? 1 : 0;
                const int m0 = (2 * mp + (int)rank) * 128;
                for (int k = 0; k < 8; k++) {
                    mbar_wait(a_empty + 8 * k, (ic & 1) ^ 1);
                    if (P2_NOLOAD) mbar_arrive(a_full + 8 * k); else {
                    mbar_expect_tx(a_full + 8 * k, 16384);
                    tma_load_2d(sA + p2_apos(k) * 16384, &P.mapA[aidx], a_full + 8 * k, k * 64, m0); }
                }
                if (rank == 0) {
                    mbar_wait(item_in + 8 * (ic & 1), (ic >> 1) & 1);
                    publish(ic + 1, ic == 0 ? npair + pair : pair < P2_NP && ic + 1 >= P2_NI ? P2_ITEMS : 2 * npair + (int)atomicAdd(&g_ctr[CT_PROJ], 1u));
                }
            }
            attn_helper(MP.a, sbase, 1);
        }
    } else {
        if (lane == 0) {
            const int par2 = warp == 8 ? 0 : 1;
            int it = 0, ic = 0; uint32_t bph = 0;
            for (;; ic++) {
                mbar_wait(item_bar + 8 * (ic & 1), (ic >> 1) & 1);
                int t;
                asm volatile("ld.shared.s32 %0, [%1];" : "=r"(t) : "r"(slot + (ic & 3) * 4) : "memory");
                if (t < 0) break;
                const int nt = 2 * p2_reps(t);
                for (int w = 0; w < nt; w++) {
                    int z, mp, hd;
                    p2_tile(t, w, z, mp, hd);
                    for (int k = 0; k < 8; k++) {
                        const int s = it; const uint32_t phb = bph;
                        if (++it == P2_STAGES) { it = 0; bph ^= 1; }
                        if ((k & 1) != par2) continue;
                        mbar_wait(b_empty + 8 * s, phb ^ 1);
                        if (P2_NOLOAD) { mbar_arrive(b_full + 8 * s); continue; }
                        mbar_expect_tx(b_full + 8 * s, 16384);
                        tma_load_2d_mc(sB + s * 16384 + rank * 8192, &P.mapW[z], b_full + 8 * s, hd * 128 + (int)rank * 64, k * 64, (uint16_t)3);
                    }
                }
            }
            if (warp == 8) {
                attn_producer(MP.a, sbase, a_empty, ~ic & 1);
                TS_END2(1, 256); TS_BEGIN2(3, 256);
                for (int i = 0; i < 4; i++) {
                    const uint32_t e = mapa_u32(obars + OB_EMPTY + 8 * (i & 1), i >> 1);
                    mbar_arrive_cl(e); mbar_arrive_cl(e);
                }
            }
            out_producer(MP.o, sbase, obars, rank, blockIdx.x >> 1, warp == 8);
            TS_END2(3, 256);
        }
    }
    } else {
        asm volatile("setmaxnreg.inc.sync.aligned.u32 232;");
        asm volatile("barrier.cluster.wait.aligned;" ::: "memory");
        const int wg = warp >> 2;
        float acc[2][64];
        const uint32_t a_lo = desc_lo(SD, 16), b_lo0 = desc_lo(SD + 131072, 8192);
        const bool elected = (threadIdx.x & 127) == 0;
        int s = (wg * 8) % P2_STAGES;
        uint32_t ph = ((wg * 8) / P2_STAGES) & 1;
        int nnote = 0;
        if (wg == 1) {
            asm volatile("bar.arrive 3, 256;" ::: "memory");
            if (blockIdx.x < 64) {
                const int r = blockIdx.x * 32 + (warp & 3) * 8 + (lane >> 2);
                float c[4] = {0.f, 0.f, 0.f, 0.f};
                uint4 xv[16], gv[16];
#pragma unroll
                for (int i = 0; i < 16; i++) {
                    xv[i] = __ldg(reinterpret_cast<const uint4*>(MP.x + (size_t)r * DM + i * 32 + (lane & 3) * 8));
                    gv[i] = __ldg(reinterpret_cast<const uint4*>(MP.gate_w + i * 32 + (lane & 3) * 8));
                }
                auto mul = [](uint32_t a, uint32_t b) { uint32_t p; asm("mul.rn.bf16x2 %0, %1, %2;" : "=r"(p) : "r"(a), "r"(b)); return p; };
#pragma unroll
                for (int i = 0; i < 16; i++)
                    mma_16816(c, mul(xv[i].x, gv[i].x), mul(xv[i].y, gv[i].y), mul(xv[i].z, gv[i].z), mul(xv[i].w, gv[i].w), 0x3f803f80u, 0x3f803f80u);
                if ((lane & 3) == 0) g_gate[r] = bf16r(__fdividef(1.f, 1.f + __expf(-bf16r(c[0] + c[2]))));
                __syncwarp();
                if (lane == 0) signal_ctr_generic(CT_GATE);
                __syncwarp();
            }
        }
        auto next_item = [&](int ic) {
            mbar_wait(item_bar + 8 * (ic & 1), (ic >> 1) & 1);
            int t;
            asm volatile("ld.shared.s32 %0, [%1];" : "=r"(t) : "r"(slot + (ic & 3) * 4) : "memory");
            return __shfl_sync(0xffffffff, t, 0);
        };
        int t = next_item(0), ic = 0, rp = 0;
#pragma unroll 1
        while (t >= 0) {
            const bool first = rp == 0, last = rp == p2_reps(t) - 1;
            asm volatile("bar.sync %0, 256;" :: "r"(3 + wg) : "memory");
            P2T(0);
            if (wg == 1 && last && elected) mbar_arrive_cl(mapa_u32(item_in + 8 * (ic & 1), 0));
            int sprev = 0;
#pragma unroll
            for (int k = 0; k < 8; k++) {
                if (k == 0) P2T(5);
                if ((wg == 0 || k > P2_HO) && first) mbar_wait(a_full + 8 * k, ic & 1);
                if (k == 0) P2T(6);
                mbar_wait(b_full + 8 * s, ph);
                if (k == P2_HO) asm volatile("bar.arrive %0, 256;" :: "r"(4 - wg) : "memory");
                if (k == 0) P2T(1);
                if (k == 7) P2T(2);
                const uint32_t b_lo = b_lo0 + s * 1024;
                if (k == 0 || !P2_NOF) wgmma_fence();
#pragma unroll
                for (int kk = 0; kk < (P2_NOMMA ? 1 : 4); kk++) {
                    wgmma_ss_n128_lo<1>(acc[0], a_lo + p2_apos(k) * 1024 + kk * 2, b_lo + kk * 128, (k | kk) != 0);
                    wgmma_ss_n128_lo<1>(acc[1], a_lo + p2_apos(k) * 1024 + 512 + kk * 2, b_lo + kk * 128, (k | kk) != 0);
                }
                wgmma_commit();
                if (k > 0) {
                    wgmma_wait<1>();
                    if (elected) {
                        const uint32_t e = b_empty + 8 * sprev;
                        mbar_arrive_cl(mapa_u32(e, 0)); mbar_arrive_cl(mapa_u32(e, 1));
                        if (last) mbar_arrive(a_empty + 8 * (k - 1));
                    }
                }
                sprev = s;
                if (++s == P2_STAGES) { s = 0; ph ^= 1; }
            }
            int z, mp, head;
            p2_tile(t, rp * 2 + wg, z, mp, head);
            const int m0 = (2 * mp + (int)rank) * 128, en = wg * 4 + (nnote & 3);
            bf16* obase = P.out[z] + ((size_t)head * SEQ + m0 + (warp & 3) * 16 + (lane >> 2)) * HD + (lane & 3) * 8;
            if (elected) {
                mbar_wait(note_free + 8 * en, ((nnote >> 2) & 1) ^ 1);
                asm volatile("st.shared.s32 [%0], %1;" :: "r"(note + en * 4), "r"(CT_AP + (head >> 1)) : "memory");
            }
            __syncwarp();
            nnote++;
            wgmma_wait<0>();
            P2T(3);
            if (elected) {
                const uint32_t e = b_empty + 8 * sprev;
                mbar_arrive_cl(mapa_u32(e, 0)); mbar_arrive_cl(mapa_u32(e, 1));
                if (last) mbar_arrive(a_empty + 8 * 7);
            }
            s += 8 % P2_STAGES; ph ^= (8 / P2_STAGES) & 1;
            if (s >= P2_STAGES) { s -= P2_STAGES; ph ^= 1; }
            store_frag_128<P2_PACE>(acc[0], obase);
            if (last) { t = next_item(++ic); rp = 0; P2T(7); } else rp++;
            store_frag_128<P2_PACE>(acc[1], obase + (size_t)64 * HD);
            __syncwarp();
            if (lane == 0) mbar_arrive(note_bar + 8 * en);
            __syncwarp();
        }
        if (wg == 0 && lane == 0) {
            const int e = nnote & 3;
            if (elected) {
                mbar_wait(note_free + 8 * e, ((nnote >> 2) & 1) ^ 1);
                asm volatile("st.shared.s32 [%0], %1;" :: "r"(note + e * 4), "r"(-1) : "memory");
            }
            mbar_arrive(note_bar + 8 * e);
        }
        auto done = [&]() {
            if ((threadIdx.x & 127) == 0) for (int i = 0; i < 4; i++) mbar_arrive_cl(SD + MO_BAR + 768 + OB_EMPTY + 16 + 8 * (i & 1) + ((i >> 1) << 24));
        };
        asm volatile("bar.sync %0, 128;" :: "r"(1 + wg) : "memory");
        const int nout = rank == 0 ? attn_consumer<SD>(MP.a, warp, done) : attn_consumer<SD + (1u << 24)>(MP.a, warp, done);
        OT(0);
        const uint32_t sb2 = (cluster_ctarank() << 24) + SD;
        out_consumer(MP.o, sb2, sb2 + MO_BAR + 768, warp, nout & 1);
    }
}

typedef CUresult (*PFN_encodeTiled)(CUtensorMap*, CUtensorMapDataType, cuuint32_t, void*, const cuuint64_t*,
                                    const cuuint64_t*, const cuuint32_t*, const cuuint32_t*, CUtensorMapInterleave,
                                    CUtensorMapSwizzle, CUtensorMapL2promotion, CUtensorMapFloatOOBfill);
static PFN_encodeTiled g_encode = nullptr;

static void make_map(CUtensorMap* m, const void* ptr, uint64_t rows, uint64_t cols, uint32_t box_rows, bool sw64 = false) {
    cuuint64_t dims[2] = {cols, rows};
    cuuint64_t strides[1] = {cols * 2};
    cuuint32_t box[2] = {sw64 ? 32u : 64u, box_rows};
    cuuint32_t es[2] = {1, 1};
    g_encode(m, CU_TENSOR_MAP_DATA_TYPE_BFLOAT16, 2, const_cast<void*>(ptr), dims, strides, box, es,
             CU_TENSOR_MAP_INTERLEAVE_NONE, sw64 ? CU_TENSOR_MAP_SWIZZLE_64B : CU_TENSOR_MAP_SWIZZLE_128B, CU_TENSOR_MAP_L2_PROMOTION_L2_256B,
             CU_TENSOR_MAP_FLOAT_OOB_FILL_NONE);
}

template <typename... KArgs, typename... Args>
static void launch_pdl(void (*kernel)(KArgs...), int grid, int block, size_t smem, cudaStream_t st, bool pdl, Args... args) {
    cudaLaunchConfig_t cfg = {};
    cfg.gridDim = dim3(grid); cfg.blockDim = dim3(block); cfg.dynamicSmemBytes = smem; cfg.stream = st;
    cudaLaunchAttribute at[1];
    at[0].id = cudaLaunchAttributeProgrammaticStreamSerialization;
    at[0].val.programmaticStreamSerializationAllowed = 1;
    cfg.attrs = at; cfg.numAttrs = pdl ? 1 : 0;
    cudaLaunchKernelEx(&cfg, kernel, KArgs(args)...);
}

extern "C" void kernel_launch(void* const* d_in, const int* in_sizes, int n_in, void* d_out, int out_size) {
    const bf16* x = (const bf16*)d_in[0];
    const bf16* ckv = (const bf16*)d_in[1];
    const bf16* wq = (const bf16*)d_in[2];
    const bf16* wuk = (const bf16*)d_in[3];
    const bf16* wuv = (const bf16*)d_in[4];
    const bf16* wo = (const bf16*)d_in[5];
    const bf16* mem0 = (const bf16*)d_in[7];
    const bf16* Wq = (const bf16*)d_in[8];
    const bf16* Wk = (const bf16*)d_in[9];
    const bf16* Wv = (const bf16*)d_in[10];
    const bf16* Wo = (const bf16*)d_in[11];
    const bf16* gate_w = (const bf16*)d_in[13];
    bf16* out = (bf16*)d_out;

    static MainParams MP;
    static ChainParams CP;
    Proj2Params& P2 = MP.p;
    AttnParams& AP = MP.a;
    OutParams& OP = MP.o;
    static bool init = false;
    static const void* last_in[14];
    static const void* last_out;
    bool same = init && last_out == d_out;
    for (int i = 0; i < 14 && same; i++) same = last_in[i] == d_in[i];
    if (!init) {
        cudaDriverEntryPointQueryResult qr;
        cudaGetDriverEntryPoint("cuTensorMapEncodeTiled", (void**)&g_encode, cudaEnableDefault, &qr);
        cudaFuncSetAttribute(main_kernel, cudaFuncAttributeMaxDynamicSharedMemorySize, M_SMEM);
        cudaFuncSetAttribute(chain_kernel, cudaFuncAttributeMaxDynamicSharedMemorySize, CH_SMEM);
        init = true;
    }
    if (!same) {
        for (int i = 0; i < 14; i++) last_in[i] = d_in[i];
        last_out = d_out;
        void *pQA, *pKA, *pVA, *pCA, *pCB;
        cudaGetSymbolAddress(&pQA, g_QA); cudaGetSymbolAddress(&pKA, g_KA); cudaGetSymbolAddress(&pVA, g_VA);
        cudaGetSymbolAddress(&pCA, g_ctxA); cudaGetSymbolAddress(&pCB, g_ctxB);
        make_map(&P2.mapA[0], x, SEQ, DM, 128);
        make_map(&P2.mapA[1], ckv, SEQ, DM, 128);
        const void* ws[3] = {wq, wuk, wuv};
        void* cs[3] = {pQA, pKA, pVA};
        for (int i = 0; i < 3; i++) { make_map(&P2.mapW[i], ws[i], DM, NQ, 64); P2.out[i] = (bf16*)cs[i]; }
        make_map(&CP.mapW[0], Wq, DM, NQ, 64); make_map(&CP.mapW[1], Wk, DM, NQ, 64); make_map(&CP.mapW[2], Wv, DM, NQ, 32);
        make_map(&CP.mapX, x, SEQ, DM, 32);
        make_map(&CP.mapWo, Wo, NQ, DM, 64);
        make_map(&CP.mapM, mem0, NMEM, DM, 8);
        MP.x = x; MP.gate_w = gate_w;
        make_map(&CP.mapC, pCB, NH * SEQ, HD, 32);
        make_map(&AP.mapQ, pQA, NH * SEQ, HD, 128);
        make_map(&AP.mapK, pKA, NH * SEQ, HD, 128);
        make_map(&AP.mapV, pVA, NH * SEQ, HD, 128);
        make_map(&AP.mapO, pCA, NH * SEQ, HD, 64);
        make_map(&OP.mapCtx[0], pCA, NH * SEQ, HD, 128);
        make_map(&OP.mapCtx[1], pCB, NH * SEQ, HD, 128);
        make_map(&OP.mapWo[0], wo, NQ, DM, 64);
        make_map(&OP.mapWo[1], Wo, NQ, DM, 64);
        make_map(&OP.mapOut, out, SEQ, DM, 64);
        CP.mapOut = OP.mapOut;
        AP.out = out;
    }
    cudaStream_t s1 = cudaStreamPerThread;
    const bool pdl = true;
    launch_pdl(chain_kernel, 64, CH_BLOCK, CH_SMEM, s1, false, CP);
    launch_pdl(main_kernel, M_GRID, 384, M_SMEM, s1, pdl, MP);
}
```

```cpp
#include <cuda_runtime.h>
#include <cuda_bf16.h>
#include <cuda.h>
#include <stdint.h>
#include <type_traits>

constexpr int SEQ = 2048;
constexpr int DM = 512;
constexpr int NH = 32;
constexpr int HD = 128;
constexpr int NQ = NH * HD;
constexpr int SEGL = 32;
constexpr int NMEM = 8;
constexpr int NSEG = SEQ / SEGL;

typedef __nv_bfloat16 bf16;

__device__ bf16 g_QA[SEQ * NQ];
__device__ bf16 g_KA[SEQ * NQ];
__device__ bf16 g_VA[SEQ * NQ];
__device__ bf16 g_ctxA[SEQ * NQ];
__device__ bf16 g_ctxB[SEQ * NQ];
constexpr int CT_PROJ = 0, CT_ATTN = 1, CT_FIN = 5;
constexpr int CT_AP = 64;
constexpr int CT_GATE = 96;
constexpr int CT_CA = 128;
constexpr int CT_CB = 193;
constexpr int CT_OT = 208;
constexpr int CT_N = 228;
__device__ __align__(16) unsigned int g_ctr[CT_N];
__device__ float g_gate[SEQ];
#define XB8(v) v, v, v, v, v, v, v, v
__device__ uint32_t g_xbuf[4 * 8 * 2048] = {XB8(XB8(XB8(XB8(XB8(~0u)))))};

#define FA_GRID 68

#define TS_BEGIN(id)
#define TS_END(id)
#define TS_BEGIN2(id, th)
#define TS_END2(id, th)
#define WAIT_LIMIT 200000
__device__ __forceinline__ void pdl_launch_dependents() { asm volatile("griddepcontrol.launch_dependents;" ::: "memory"); }
__device__ __forceinline__ void wait_ctr(int idx, unsigned int n) {
    unsigned int v; int it = 0;
    do { asm volatile("ld.acquire.gpu.global.u32 %0, [%1];" : "=r"(v) : "l"(&g_ctr[idx]) : "memory"); } while (v < n && ++it < WAIT_LIMIT);
    asm volatile("fence.proxy.async.shared::cta;" ::: "memory");
}
__device__ __forceinline__ int take_ticket(int idx) {
    int v;
    asm volatile("atom.relaxed.gpu.global.inc.u32 %0, [%1], 0x7fffffff;" : "=r"(v) : "l"(&g_ctr[idx]) : "memory");
    return v;
}
__device__ __forceinline__ void signal_ctr(int idx) {
    asm volatile("fence.proxy.async;" ::: "memory");
    __threadfence();
    atomicAdd(&g_ctr[idx], 1u);
}
__device__ __forceinline__ void signal_ctr_generic(int idx) {
    asm volatile("red.release.gpu.global.add.u32 [%0], 1;" :: "l"(&g_ctr[idx]) : "memory");
}
__device__ __forceinline__ uint32_t smem_u32(const void* p) {
    return (uint32_t)__cvta_generic_to_shared(p);
}
__device__ __forceinline__ void mbar_init(uint32_t bar, uint32_t count) {
    asm volatile("mbarrier.init.shared::cta.b64 [%0], %1;" :: "r"(bar), "r"(count));
}
__device__ __forceinline__ void mbar_expect_tx(uint32_t bar, uint32_t bytes) {
    asm volatile("mbarrier.arrive.expect_tx.shared::cta.b64 _, [%0], %1;" :: "r"(bar), "r"(bytes) : "memory");
}
__device__ __forceinline__ void mbar_arrive(uint32_t bar) {
    asm volatile("mbarrier.arrive.shared::cta.b64 _, [%0];" :: "r"(bar) : "memory");
}
__device__ __forceinline__ void mbar_wait(uint32_t bar, uint32_t parity) {
    asm volatile(
        "{\n"
        ".reg .pred p, q;\n"
        ".reg .u32 c;\n"
        "mov.u32 c, 0;\n"
        "WAIT_LOOP:\n"
        "mbarrier.try_wait.parity.shared::cta.b64 p, [%0], %1;\n"
        "@p bra WAIT_DONE;\n"
        "add.u32 c, c, 1;\n"
        "setp.lt.u32 q, c, %2;\n"
        "@q bra WAIT_LOOP;\n"
        "WAIT_DONE:\n"
        "}\n" :: "r"(bar), "r"(parity), "n"(WAIT_LIMIT) : "memory");
}
__device__ __forceinline__ uint32_t mbar_test(uint32_t bar, uint32_t parity) {
    uint32_t done;
    asm volatile(
        "{\n.reg .pred p;\n"
        "mbarrier.test_wait.parity.shared::cta.b64 p, [%1], %2;\n"
        "selp.u32 %0, 1, 0, p;\n}\n" : "=r"(done) : "r"(bar), "r"(parity) : "memory");
    return done;
}
__device__ __forceinline__ uint32_t mbar_try(uint32_t bar, uint32_t parity) {
    uint32_t done;
    asm volatile(
        "{\n.reg .pred p;\n"
        "mbarrier.try_wait.parity.shared::cta.b64 p, [%1], %2;\n"
        "selp.u32 %0, 1, 0, p;\n}\n" : "=r"(done) : "r"(bar), "r"(parity) : "memory");
    return done;
}
__device__ __forceinline__ void tma_load_2d(uint32_t dst, const CUtensorMap* map, uint32_t bar, int c0, int c1) {
    asm volatile(
        "cp.async.bulk.tensor.2d.shared::cluster.global.mbarrier::complete_tx::bytes [%0], [%1, {%3, %4}], [%2];"
        :: "r"(dst), "l"((uint64_t)map), "r"(bar), "r"(c0), "r"(c1) : "memory");
}
__device__ __forceinline__ void wgmma_fence() { asm volatile("wgmma.fence.sync.aligned;" ::: "memory"); }
__device__ __forceinline__ void wgmma_commit() { asm volatile("wgmma.commit_group.sync.aligned;" ::: "memory"); }
template <int N> __device__ __forceinline__ void wgmma_wait() {
    asm volatile("wgmma.wait_group.sync.aligned %0;" :: "n"(N) : "memory");
}
__device__ __forceinline__ uint64_t make_desc(uint32_t addr, uint32_t lbo, uint32_t sbo) {
    uint64_t d = 0;
    d |= (uint64_t)((addr & 0x3FFFF) >> 4);
    d |= (uint64_t)((lbo >> 4) & 0x3FFF) << 16;
    d |= (uint64_t)((sbo >> 4) & 0x3FFF) << 32;
    d |= (uint64_t)1 << 62;
    return d;
}

#define ACC64(d) \
    "+f"(d[0]), "+f"(d[1]), "+f"(d[2]), "+f"(d[3]), "+f"(d[4]), "+f"(d[5]), "+f"(d[6]), "+f"(d[7]), \
    "+f"(d[8]), "+f"(d[9]), "+f"(d[10]), "+f"(d[11]), "+f"(d[12]), "+f"(d[13]), "+f"(d[14]), "+f"(d[15]), \
    "+f"(d[16]), "+f"(d[17]), "+f"(d[18]), "+f"(d[19]), "+f"(d[20]), "+f"(d[21]), "+f"(d[22]), "+f"(d[23]), \
    "+f"(d[24]), "+f"(d[25]), "+f"(d[26]), "+f"(d[27]), "+f"(d[28]), "+f"(d[29]), "+f"(d[30]), "+f"(d[31]), \
    "+f"(d[32]), "+f"(d[33]), "+f"(d[34]), "+f"(d[35]), "+f"(d[36]), "+f"(d[37]), "+f"(d[38]), "+f"(d[39]), \
    "+f"(d[40]), "+f"(d[41]), "+f"(d[42]), "+f"(d[43]), "+f"(d[44]), "+f"(d[45]), "+f"(d[46]), "+f"(d[47]), \
    "+f"(d[48]), "+f"(d[49]), "+f"(d[50]), "+f"(d[51]), "+f"(d[52]), "+f"(d[53]), "+f"(d[54]), "+f"(d[55]), \
    "+f"(d[56]), "+f"(d[57]), "+f"(d[58]), "+f"(d[59]), "+f"(d[60]), "+f"(d[61]), "+f"(d[62]), "+f"(d[63])
#define ACC64_STR \
    "{%0, %1, %2, %3, %4, %5, %6, %7, %8, %9, %10, %11, %12, %13, %14, %15, " \
    "%16, %17, %18, %19, %20, %21, %22, %23, %24, %25, %26, %27, %28, %29, %30, %31, " \
    "%32, %33, %34, %35, %36, %37, %38, %39, %40, %41, %42, %43, %44, %45, %46, %47, " \
    "%48, %49, %50, %51, %52, %53, %54, %55, %56, %57, %58, %59, %60, %61, %62, %63}"

template <int TB>
__device__ __forceinline__ void wgmma_ss_n128(float (&d)[64], uint64_t da, uint64_t db, int scale_d) {
    asm volatile(
        "{\n.reg .pred p;\nsetp.ne.b32 p, %66, 0;\n"
        "wgmma.mma_async.sync.aligned.m64n128k16.f32.bf16.bf16 " ACC64_STR ", %64, %65, p, 1, 1, 0, %67;\n}\n"
        : ACC64(d) : "l"(da), "l"(db), "r"(scale_d), "n"(TB));
}
__device__ __forceinline__ uint32_t desc_lo(uint32_t addr, uint32_t lbo) { return ((addr & 0x3FFFF) >> 4) | ((lbo >> 4) << 16); }
template <int TB>
__device__ __forceinline__ void wgmma_ss_n128_lo(float (&d)[64], uint32_t da_lo, uint32_t db_lo, int scale_d) {
    asm volatile(
        "{\n.reg .pred p;\n.reg .b64 da, db;\nsetp.ne.b32 p, %66, 0;\n"
        "mov.b64 da, {%64, 0x40000040};\nmov.b64 db, {%65, 0x40000040};\n"
        "wgmma.mma_async.sync.aligned.m64n128k16.f32.bf16.bf16 " ACC64_STR ", da, db, p, 1, 1, 0, %67;\n}\n"
        : ACC64(d) : "r"(da_lo), "r"(db_lo), "r"(scale_d), "n"(TB));
}
__device__ __forceinline__ void wgmma_rs_n128_tb(float (&d)[64], uint32_t a0, uint32_t a1, uint32_t a2, uint32_t a3,
                                                 uint64_t db, int scale_d) {
    asm volatile(
        "{\n.reg .pred p;\nsetp.ne.b32 p, %69, 0;\n"
        "wgmma.mma_async.sync.aligned.m64n128k16.f32.bf16.bf16 " ACC64_STR ", {%64, %65, %66, %67}, %68, p, 1, 1, 1;\n}\n"
        : ACC64(d) : "r"(a0), "r"(a1), "r"(a2), "r"(a3), "l"(db), "r"(scale_d));
}
__device__ __forceinline__ void wgmma_rs_n80(float (&d)[40], const uint32_t (&a)[4], uint32_t db_lo, int scale_d) {
    asm volatile(
        "{\n.reg .pred p;\n.reg .b64 db;\nsetp.ne.b32 p, %45, 0;\nmov.b64 db, {%44, 0x40000040};\n"
        "wgmma.mma_async.sync.aligned.m64n80k16.f32.bf16.bf16 "
        "{%0, %1, %2, %3, %4, %5, %6, %7, %8, %9, %10, %11, %12, %13, %14, %15, %16, %17, %18, %19, %20, %21, %22, %23, %24, %25, %26, %27, %28, %29, %30, %31, %32, %33, %34, %35, %36, %37, %38, %39}, "
        "{%40, %41, %42, %43}, db, p, 1, 1, 0;\n}\n"
        : "+f"(d[0]), "+f"(d[1]), "+f"(d[2]), "+f"(d[3]), "+f"(d[4]), "+f"(d[5]), "+f"(d[6]), "+f"(d[7]), "+f"(d[8]), "+f"(d[9]), "+f"(d[10]), "+f"(d[11]), "+f"(d[12]), "+f"(d[13]), "+f"(d[14]), "+f"(d[15]), "+f"(d[16]), "+f"(d[17]), "+f"(d[18]), "+f"(d[19]), "+f"(d[20]), "+f"(d[21]), "+f"(d[22]), "+f"(d[23]), "+f"(d[24]), "+f"(d[25]), "+f"(d[26]), "+f"(d[27]), "+f"(d[28]), "+f"(d[29]), "+f"(d[30]), "+f"(d[31]), "+f"(d[32]), "+f"(d[33]), "+f"(d[34]), "+f"(d[35]), "+f"(d[36]), "+f"(d[37]), "+f"(d[38]), "+f"(d[39])
        : "r"(a[0]), "r"(a[1]), "r"(a[2]), "r"(a[3]), "r"(db_lo), "r"(scale_d));
}
__device__ __forceinline__ void wgmma_ss_n256_tb(float (&d)[128], uint64_t da, uint64_t db, int scale_d) {
    asm volatile(
        "{\n.reg .pred p;\nsetp.ne.b32 p, %130, 0;\n"
        "wgmma.mma_async.sync.aligned.m64n256k16.f32.bf16.bf16 {%0, %1, %2, %3, %4, %5, %6, %7, %8, %9, %10, %11, %12, %13, %14, %15, %16, %17, %18, %19, %20, %21, %22, %23, %24, %25, %26, %27, %28, %29, %30, %31, %32, %33, %34, %35, %36, %37, %38, %39, %40, %41, %42, %43, %44, %45, %46, %47, %48, %49, %50, %51, %52, %53, %54, %55, %56, %57, %58, %59, %60, %61, %62, %63, %64, %65, %66, %67, %68, %69, %70, %71, %72, %73, %74, %75, %76, %77, %78, %79, %80, %81, %82, %83, %84, %85, %86, %87, %88, %89, %90, %91, %92, %93, %94, %95, %96, %97, %98, %99, %100, %101, %102, %103, %104, %105, %106, %107, %108, %109, %110, %111, %112, %113, %114, %115, %116, %117, %118, %119, %120, %121, %122, %123, %124, %125, %126, %127}, %128, %129, p, 1, 1, 0, 1;\n}\n"
        : "+f"(d[0]), "+f"(d[1]), "+f"(d[2]), "+f"(d[3]), "+f"(d[4]), "+f"(d[5]), "+f"(d[6]), "+f"(d[7]), "+f"(d[8]), "+f"(d[9]), "+f"(d[10]), "+f"(d[11]), "+f"(d[12]), "+f"(d[13]), "+f"(d[14]), "+f"(d[15]), "+f"(d[16]), "+f"(d[17]), "+f"(d[18]), "+f"(d[19]), "+f"(d[20]), "+f"(d[21]), "+f"(d[22]), "+f"(d[23]), "+f"(d[24]), "+f"(d[25]), "+f"(d[26]), "+f"(d[27]), "+f"(d[28]), "+f"(d[29]), "+f"(d[30]), "+f"(d[31]), "+f"(d[32]), "+f"(d[33]), "+f"(d[34]), "+f"(d[35]), "+f"(d[36]), "+f"(d[37]), "+f"(d[38]), "+f"(d[39]), "+f"(d[40]), "+f"(d[41]), "+f"(d[42]), "+f"(d[43]), "+f"(d[44]), "+f"(d[45]), "+f"(d[46]), "+f"(d[47]), "+f"(d[48]), "+f"(d[49]), "+f"(d[50]), "+f"(d[51]), "+f"(d[52]), "+f"(d[53]), "+f"(d[54]), "+f"(d[55]), "+f"(d[56]), "+f"(d[57]), "+f"(d[58]), "+f"(d[59]), "+f"(d[60]), "+f"(d[61]), "+f"(d[62]), "+f"(d[63]), "+f"(d[64]), "+f"(d[65]), "+f"(d[66]), "+f"(d[67]), "+f"(d[68]), "+f"(d[69]), "+f"(d[70]), "+f"(d[71]), "+f"(d[72]), "+f"(d[73]), "+f"(d[74]), "+f"(d[75]), "+f"(d[76]), "+f"(d[77]), "+f"(d[78]), "+f"(d[79]), "+f"(d[80]), "+f"(d[81]), "+f"(d[82]), "+f"(d[83]), "+f"(d[84]), "+f"(d[85]), "+f"(d[86]), "+f"(d[87]), "+f"(d[88]), "+f"(d[89]), "+f"(d[90]), "+f"(d[91]), "+f"(d[92]), "+f"(d[93]), "+f"(d[94]), "+f"(d[95]), "+f"(d[96]), "+f"(d[97]), "+f"(d[98]), "+f"(d[99]), "+f"(d[100]), "+f"(d[101]), "+f"(d[102]), "+f"(d[103]), "+f"(d[104]), "+f"(d[105]), "+f"(d[106]), "+f"(d[107]), "+f"(d[108]), "+f"(d[109]), "+f"(d[110]), "+f"(d[111]), "+f"(d[112]), "+f"(d[113]), "+f"(d[114]), "+f"(d[115]), "+f"(d[116]), "+f"(d[117]), "+f"(d[118]), "+f"(d[119]), "+f"(d[120]), "+f"(d[121]), "+f"(d[122]), "+f"(d[123]), "+f"(d[124]), "+f"(d[125]), "+f"(d[126]), "+f"(d[127])
        : "l"(da), "l"(db), "r"(scale_d));
}
__device__ __forceinline__ void stmatrix_x4(uint32_t addr, uint32_t r0, uint32_t r1, uint32_t r2, uint32_t r3) {
    asm volatile("stmatrix.sync.aligned.m8n8.x4.shared.b16 [%0], {%1, %2, %3, %4};" :: "r"(addr), "r"(r0), "r"(r1), "r"(r2), "r"(r3) : "memory");
}
__device__ __forceinline__ void tma_store_2d(const CUtensorMap* map, uint32_t src, int c0, int c1) {
    asm volatile("cp.async.bulk.tensor.2d.global.shared::cta.bulk_group [%0, {%2, %3}], [%1];"
                 :: "l"((uint64_t)map), "r"(src), "r"(c0), "r"(c1) : "memory");
}
__device__ __forceinline__ float ex2f(float x) { float y; asm("ex2.approx.ftz.f32 %0, %1;" : "=f"(y) : "f"(x)); return y; }
__device__ __forceinline__ uint32_t pack_bf16(float lo, float hi) {
    __nv_bfloat162 v = __floats2bfloat162_rn(lo, hi);
    return *reinterpret_cast<uint32_t*>(&v);
}
__device__ __forceinline__ void mma_16816(float (&c)[4], uint32_t a0, uint32_t a1, uint32_t a2, uint32_t a3,
                                          uint32_t b0, uint32_t b1) {
    asm volatile(
        "mma.sync.aligned.m16n8k16.row.col.f32.bf16.bf16.f32 {%0,%1,%2,%3}, {%4,%5,%6,%7}, {%8,%9}, {%0,%1,%2,%3};"
        : "+f"(c[0]), "+f"(c[1]), "+f"(c[2]), "+f"(c[3])
        : "r"(a0), "r"(a1), "r"(a2), "r"(a3), "r"(b0), "r"(b1));
}
__device__ __forceinline__ void ldmatrix_x4_trans(uint32_t& r0, uint32_t& r1, uint32_t& r2, uint32_t& r3, uint32_t addr) {
    asm volatile("ldmatrix.sync.aligned.m8n8.x4.trans.shared.b16 {%0,%1,%2,%3}, [%4];"
                 : "=r"(r0), "=r"(r1), "=r"(r2), "=r"(r3) : "r"(addr));
}

struct AttnParams {
    CUtensorMap mapQ, mapK, mapV;
    CUtensorMap mapO;
    bf16* out;
};
constexpr int FA_ITEMS = 16 * NH;
__device__ __forceinline__ int fa_qt(int t) { return 15 - ((t & 127) >> 3); }
__device__ __forceinline__ int fa_head(int t) { return (t >> 7) * 8 + (t & 7); }
#define FA_TKA 2
#define FA_SPLIT 11

#define FA_P0 4
#define FA_HO 7
#define FA_LAG 2
#define FA_PK 3
#define FA_ST 4
#define FA_TG 16
#define FA_EARLY 0
#define FA_TRIM 1
#define FA_TE 0
#define FA_B0 1
#define FA_ONE 1
#define FA_V2 1
#define FA_I0 0
static_assert(FA_GRID <= 104 && FA_HO >= FA_P0 && FA_P0 >= 1 && (!FA_TRIM || (FA_P0 == 4 && FA_SPLIT >= 8 && FA_I0 <= 4)), "");
constexpr float FA_MARGIN = 16.f;
#define FAT(b, i)
__device__ __forceinline__ void mbar_arrive_if(uint32_t bar, bool c) {
    asm volatile("{\n.reg .pred p;\nsetp.ne.b32 p, %1, 0;\n@p mbarrier.arrive.shared::cta.b64 _, [%0];\n}" :: "r"(bar), "r"((int)c) : "memory");
}
__device__ __forceinline__ void sched_fence(int v, int id, const float* a, const float* b, const float* c) {
    asm volatile("{\n.reg .pred p;\nsetp.ne.s32 p, %0, %1;\n@p bra SF_SKIP;\nwgmma.wait_group.sync.aligned 0;\n"
                 "st.volatile.shared.f32 [%0], %2;\nst.volatile.shared.f32 [%0], %3;\nst.volatile.shared.f32 [%0], %4;\nst.volatile.shared.f32 [%0], %5;\n"
                 "st.volatile.shared.f32 [%0], %6;\nst.volatile.shared.f32 [%0], %7;\nst.volatile.shared.f32 [%0], %8;\nst.volatile.shared.f32 [%0], %9;\n"
                 "st.volatile.shared.f32 [%0], %10;\nst.volatile.shared.f32 [%0], %11;\nst.volatile.shared.f32 [%0], %12;\nst.volatile.shared.f32 [%0], %13;\n"
                 "exit;\nSF_SKIP:\n}" :: "r"(v), "r"(1000000 + id), "f"(a[0]), "f"(a[1]), "f"(a[2]), "f"(a[3]), "f"(b[0]), "f"(b[1]), "f"(b[2]), "f"(b[3]),
                 "f"(c[0]), "f"(c[1]), "f"(c[2]), "f"(c[3]) : "memory");
}
#define QK_FULL "wgmma.mma_async.sync.aligned.m64n128k16.f32.bf16.bf16 " ACC64_STR
#define QK_HALF "wgmma.mma_async.sync.aligned.m64n64k16.f32.bf16.bf16 {%32,%33,%34,%35,%36,%37,%38,%39,%40,%41,%42,%43,%44,%45,%46,%47,%48,%49,%50,%51,%52,%53,%54,%55,%56,%57,%58,%59,%60,%61,%62,%63}"
__device__ __forceinline__ void wgmma_qk(float (&d)[64], uint32_t da_lo, uint32_t db_lo, int half) {
    asm volatile(
        "{\n.reg .pred p, t, f;\n.reg .b32 a, b;\n.reg .b64 da, db;\nsetp.eq.b32 t, 0, 0;\nsetp.ne.b32 f, 0, 0;\nsetp.ne.b32 p, %66, 0;\n@p bra.uni QK_H;\nwgmma.fence.sync.aligned;\n"
        "add.u32 a, %64, 0;\nadd.u32 b, %65, 0;\nmov.b64 da, {a, 0x40000040};\nmov.b64 db, {b, 0x40000040};\n" QK_FULL ", da, db, f, 1, 1, 0, 0;\n"
        "add.u32 a, %64, 2;\nadd.u32 b, %65, 2;\nmov.b64 da, {a, 0x40000040};\nmov.b64 db, {b, 0x40000040};\n" QK_FULL ", da, db, t, 1, 1, 0, 0;\n"
        "add.u32 a, %64, 4;\nadd.u32 b, %65, 4;\nmov.b64 da, {a, 0x40000040};\nmov.b64 db, {b, 0x40000040};\n" QK_FULL ", da, db, t, 1, 1, 0, 0;\n"
        "add.u32 a, %64, 6;\nadd.u32 b, %65, 6;\nmov.b64 da, {a, 0x40000040};\nmov.b64 db, {b, 0x40000040};\n" QK_FULL ", da, db, t, 1, 1, 0, 0;\n"
        "add.u32 a, %64, 1024;\nadd.u32 b, %65, 1024;\nmov.b64 da, {a, 0x40000040};\nmov.b64 db, {b, 0x40000040};\n" QK_FULL ", da, db, t, 1, 1, 0, 0;\n"
        "add.u32 a, %64, 1026;\nadd.u32 b, %65, 1026;\nmov.b64 da, {a, 0x40000040};\nmov.b64 db, {b, 0x40000040};\n" QK_FULL ", da, db, t, 1, 1, 0, 0;\n"
        "add.u32 a, %64, 1028;\nadd.u32 b, %65, 1028;\nmov.b64 da, {a, 0x40000040};\nmov.b64 db, {b, 0x40000040};\n" QK_FULL ", da, db, t, 1, 1, 0, 0;\n"
        "add.u32 a, %64, 1030;\nadd.u32 b, %65, 1030;\nmov.b64 da, {a, 0x40000040};\nmov.b64 db, {b, 0x40000040};\n" QK_FULL ", da, db, t, 1, 1, 0, 0;\n"
        "wgmma.commit_group.sync.aligned;\nbra.uni QK_E;\nQK_H:\nwgmma.fence.sync.aligned;\n"
        "add.u32 a, %64, 0;\nadd.u32 b, %65, 0;\nmov.b64 da, {a, 0x40000040};\nmov.b64 db, {b, 0x40000040};\n" QK_HALF ", da, db, f, 1, 1, 0, 0;\n"
        "add.u32 a, %64, 2;\nadd.u32 b, %65, 2;\nmov.b64 da, {a, 0x40000040};\nmov.b64 db, {b, 0x40000040};\n" QK_HALF ", da, db, t, 1, 1, 0, 0;\n"
        "add.u32 a, %64, 4;\nadd.u32 b, %65, 4;\nmov.b64 da, {a, 0x40000040};\nmov.b64 db, {b, 0x40000040};\n" QK_HALF ", da, db, t, 1, 1, 0, 0;\n"
        "add.u32 a, %64, 6;\nadd.u32 b, %65, 6;\nmov.b64 da, {a, 0x40000040};\nmov.b64 db, {b, 0x40000040};\n" QK_HALF ", da, db, t, 1, 1, 0, 0;\n"
        "add.u32 a, %64, 1024;\nadd.u32 b, %65, 1024;\nmov.b64 da, {a, 0x40000040};\nmov.b64 db, {b, 0x40000040};\n" QK_HALF ", da, db, t, 1, 1, 0, 0;\n"
        "add.u32 a, %64, 1026;\nadd.u32 b, %65, 1026;\nmov.b64 da, {a, 0x40000040};\nmov.b64 db, {b, 0x40000040};\n" QK_HALF ", da, db, t, 1, 1, 0, 0;\n"
        "add.u32 a, %64, 1028;\nadd.u32 b, %65, 1028;\nmov.b64 da, {a, 0x40000040};\nmov.b64 db, {b, 0x40000040};\n" QK_HALF ", da, db, t, 1, 1, 0, 0;\n"
        "add.u32 a, %64, 1030;\nadd.u32 b, %65, 1030;\nmov.b64 da, {a, 0x40000040};\nmov.b64 db, {b, 0x40000040};\n" QK_HALF ", da, db, t, 1, 1, 0, 0;\n"
        "wgmma.commit_group.sync.aligned;\nQK_E:\n}"
        : ACC64(d) : "r"(da_lo), "r"(db_lo), "r"(half) : "memory");
}
__device__ __forceinline__ float ex2v(float x) { float y; asm volatile("ex2.approx.ftz.f32 %0, %1;" : "=f"(y) : "f"(x)); return y; }
__device__ __forceinline__ void wgmma_rs_n128_tb_lo(float (&d)[64], const uint32_t* a, uint32_t db_lo, int scale_d) {
    asm volatile(
        "{\n.reg .pred p;\n.reg .b64 db;\nsetp.ne.b32 p, %69, 0;\nmov.b64 db, {%68, 0x40000040};\n"
        "wgmma.mma_async.sync.aligned.m64n128k16.f32.bf16.bf16 " ACC64_STR ", {%64, %65, %66, %67}, db, p, 1, 1, 1;\n}\n"
        : ACC64(d) : "r"(a[0]), "r"(a[1]), "r"(a[2]), "r"(a[3]), "r"(db_lo), "r"(scale_d));
}

constexpr int M_GRID = 68;
constexpr uint32_t SD = 1024;
constexpr uint32_t MO_BAR = 229376;
constexpr int M_SMEM = MO_BAR + 1024;
constexpr uint32_t FO_Q = 0, FO_KV = 65536, FO_O = FO_KV + 2 * 65536, FO_BAR = MO_BAR + 512;
constexpr uint32_t FB_QF = FO_BAR, FB_QE = FO_BAR + 16, FB_KF = FO_BAR + 32, FB_VF = FO_BAR + 48, FB_KE = FO_BAR + 64, FB_VE = FO_BAR + 80,
                   FB_OF = FO_BAR + 96, FB_OE = FO_BAR + 112, FB_SLOT = FO_BAR + 128, FB_OSLOT = FO_BAR + 136;
__device__ __forceinline__ void attn_init(uint32_t sb) {
    for (int i = 0; i < 2; i++) {
        mbar_init(sb + FB_QF + 8 * i, 1); mbar_init(sb + FB_QE + 8 * i, 8); mbar_init(sb + FB_KF + 8 * i, 1); mbar_init(sb + FB_VF + 8 * i, 1);
        mbar_init(sb + FB_KE + 8 * i, 8); mbar_init(sb + FB_VE + 8 * i, 8); mbar_init(sb + FB_OF + 8 * i, 4); mbar_init(sb + FB_OE + 8 * i, 1);
    }
}
__device__ __forceinline__ void attn_helper(const AttnParams& P, uint32_t sb, int wg) {
    const uint32_t stg = sb + FO_O + wg * 16384;
    for (int n = 0;; n++) {
        mbar_wait(sb + FB_OF + 8 * wg, n & 1);
        int t;
        asm volatile("ld.shared.s32 %0, [%1];" : "=r"(t) : "r"(sb + FB_OSLOT + wg * 4) : "memory");
        const int qt = fa_qt(t), h = fa_head(t & 1023);
        tma_store_2d(&P.mapO, stg, 0, h * SEQ + qt * 128 + wg * 64);
        tma_store_2d(&P.mapO, stg + 8192, 64, h * SEQ + qt * 128 + wg * 64);
        asm volatile("cp.async.bulk.commit_group;" ::: "memory");
        asm volatile("cp.async.bulk.wait_group.read 0;" ::: "memory");
        mbar_arrive(sb + FB_OE + 8 * wg);
        asm volatile("cp.async.bulk.wait_group 0;" ::: "memory");
        signal_ctr(CT_CA + qt * 4 + (h >> 3));
        if (t >= 1024) break;
    }
}
__device__ __forceinline__ void attn_producer(const AttnParams& P, uint32_t sb, uint32_t free_bar, uint32_t free_par) {
    const uint32_t sQ = sb + FO_Q, sKV = sb + FO_KV;
    int b = 0, hp_ready = 0, vrow = 0, t = blockIdx.x, item = 0;
    auto load_v = [&](int i) {
        const uint32_t sv = sKV + (i & 1) * 65536 + 32768, bar = sb + FB_VF + 8 * (i & 1);
        mbar_wait(sb + FB_VE + 8 * (i & 1), ((i >> 1) & 1) ^ (FA_B0 ? ~i & 1 : 1));
        mbar_expect_tx(bar, 32768);
        tma_load_2d(sv, &P.mapV, bar, 0, vrow);
        tma_load_2d(sv + 16384, &P.mapV, bar, 64, vrow);
    };
    for (;; item++) {
        const bool valid = t < FA_ITEMS;
        const int qt = fa_qt(t), h = fa_head(t);
        if (valid && !((hp_ready >> (h >> 1)) & 1)) { wait_ctr(CT_AP + (h >> 1), 96u); hp_ready |= 1 << (h >> 1); }
        const uint32_t bq = sb + FB_QF + 8 * (item & 1);
        mbar_wait(item ? sb + FB_QE + 8 * (item & 1) : free_bar + 8, item ? ((item >> 1) & 1) ^ 1 : free_par);
        asm volatile("st.shared.s32 [%0], %1;" :: "r"(sb + FB_SLOT + (item & 1) * 4), "r"(valid ? t : -1) : "memory");
        if (!valid) { mbar_arrive(bq); break; }
        mbar_expect_tx(bq, 32768);
        tma_load_2d(sQ + (item & 1) * 32768, &P.mapQ, bq, 0, h * SEQ + qt * 128);
        tma_load_2d(sQ + (item & 1) * 32768 + 16384, &P.mapQ, bq, 64, h * SEQ + qt * 128);
#pragma unroll 1
        for (int j = 0; j <= qt; j++, b++) {
            const uint32_t sk = sKV + (b & 1) * 65536, bar = sb + FB_KF + 8 * (b & 1);
            mbar_wait(b >= 2 ? sb + FB_KE + 8 * (b & 1) : free_bar + 24 + 32 * b, b >= 2 ? ((b >> 1) & 1) ^ 1 : free_par);
            if (b == 1) { TS_END2(0, 256); TS_BEGIN2(1, 256); }
            if (b == 2) wait_ctr(CT_GATE, 256u);
            mbar_expect_tx(bar, 32768);
            tma_load_2d(sk, &P.mapK, bar, 0, h * SEQ + j * 128);
            tma_load_2d(sk + 16384, &P.mapK, bar, 64, h * SEQ + j * 128);
            if (j == max(qt - FA_TKA, 0)) t = take_ticket(CT_ATTN);
            if (b > 0) load_v(b - 1);
            vrow = h * SEQ + j * 128;
        }
        t += M_GRID;
    }
    load_v(b - 1);
    mbar_wait(sb + FB_KE + 8 * (~b & 1), ((b - 1) >> 1) & 1);
}
template <typename F>
__device__ __forceinline__ int attn_consumer(const AttnParams& P, int warp, F done, const uint32_t sb) {
    constexpr uint32_t sQ = SD + FO_Q, sKV = SD + FO_KV;
    const uint32_t sO = sb + FO_O;
    const uint32_t bar_qf = sb + FB_QF, bar_qe = sb + FB_QE, bar_kf = sb + FB_KF, bar_vf = sb + FB_VF, bar_ke = sb + FB_KE, bar_ve = sb + FB_VE,
                   bar_of = sb + FB_OF, bar_oe = sb + FB_OE, slot = sb + FB_SLOT, oslot = sb + FB_OSLOT;
    {
        const int wg = warp >> 2;
        const int lane = threadIdx.x & 31;
        const float sc = 0.08838834764831845f * 1.4426950408889634f;
        const int r0 = wg * 64 + (warp & 3) * 16 + (lane >> 2);
        float o[64], s[64];
        uint32_t pa[32];
        float m0 = 0.f, m1 = 0.f, l0 = 0.f, l1 = 0.f, i0 = 0.f, i1 = 0.f, g0 = 0.f, g1 = 0.f, gn0 = 0.f, gn1 = 0.f;
        const uint32_t q_lo = desc_lo(sQ + wg * 8192, 16), k_lo = desc_lo(sKV, 16), v_lo = desc_lo(sKV + 32768, 16384);
        auto issue_qk = [&](int b, int item, bool half) {
            const uint32_t qd = q_lo + (item & 1) * 2048, kd = k_lo + (b & 1) * 4096;
            const uint32_t kd2 = half ? kd - 512 : kd;
            wgmma_fence();
#pragma unroll
            for (int kk = 0; kk < 8; kk++) wgmma_ss_n128_lo<0>(s, qd + (kk >> 2) * 1024 + (kk & 3) * 2, kd2 + (kk >> 2) * 1024 + (kk & 3) * 2, kk != 0);
            wgmma_commit();
        };
        auto issue_pv = [&](int b, bool acc, int n, bool half) {
            const uint32_t vd = v_lo + (b & 1) * 4096;
            mbar_wait(bar_vf + 8 * (b & 1), (b >> 1) & 1);
            if (half) {
                asm volatile("wgmma.fence.sync.aligned;  // half" ::: "memory");
#pragma unroll
                for (int kk = 4; kk < 8; kk++) if (kk < n) wgmma_rs_n128_tb_lo(o, &pa[kk * 4], vd + (kk - 4) * 128, kk > 4 ? 1 : (int)acc);
                asm volatile("wgmma.commit_group.sync.aligned;  // half" ::: "memory");
                return;
            }
            wgmma_fence();
#pragma unroll
            for (int kk = 0; kk < 8; kk++) if (kk < n) wgmma_rs_n128_tb_lo(o, &pa[kk * 4], vd + kk * 128, kk ? 1 : (int)acc);
            wgmma_commit();
        };
        const int lim = (FA_TRIM ? (r0 | 64) : r0) - (lane & 3) * 2;
        uint32_t v_hi = v_lo;
        int acc_hi = 1;
        int item = -1, tnext = 0;
        uint32_t k_ready = 0, q_ready = 0;
        auto mask = [&](int i) { if ((i >> 2) * 8 + (i & 1) - ((i & 2) ? 8 : 0) > lim) s[i] = -INFINITY; };
        auto exps = [&](auto mode, int b, bool hand_over, float& u0, float& u1) {
            constexpr int MODE = decltype(mode)::value;
            float p[64], u[4] = {0.f, 0.f, 0.f, 0.f};
            const uint32_t vd = v_hi + ((b - 1) & 1) * 4096;
            constexpr int R = FA_TRIM && MODE == 2 ? 32 : 0;
#pragma unroll
            for (int i = 0; i < 4; i++) p[i] = fmaf(s[i ^ R], sc, (i & 2) ? -m1 : -m0);
#pragma unroll
            for (int g = 0; g < 16 + FA_LAG; g++) {
                if (MODE && g >= FA_I0 && g - FA_I0 < 8 - FA_P0) {
                    const int kk = FA_P0 + g - FA_I0;
                    wgmma_fence();
                    wgmma_rs_n128_tb_lo(o, &pa[kk * 4], vd + kk * 128, FA_TRIM && kk == 4 ? acc_hi : 1);
                    wgmma_commit();
                    if (kk == FA_HO) asm volatile("{\n.reg .pred p;\nsetp.ne.b32 p, %1, 0;\n@p bar.arrive %0, 256;\n}" :: "r"(4 - wg), "r"((int)hand_over) : "memory");
                }
                if (R && g == 8 && wg == 0) {
                    wgmma_wait<0>();
                    mbar_arrive_if(bar_ve + 8 * ((b - 1) & 1), lane == 0);
                    k_ready = q_ready = 0;
#pragma unroll
                    for (int i = 32 - FA_LAG * 4; i < 32; i++) u[i & 3] += p[i];
#pragma unroll
                    for (int i = 0; i < 16; i++) pa[16 + i] = pack_bf16(p[i * 2], p[i * 2 + 1]);
                    break;
                }
                if (MODE && g == FA_SPLIT) {
                    FAT(b, 2);
                    wgmma_wait<0>();
                    FAT(b - 1, 3);
                    mbar_arrive_if(bar_ve + 8 * ((b - 1) & 1), lane == 0);
                }
                if (MODE && g == FA_TG) {
                    k_ready = mbar_test(bar_kf + 8 * (~b & 1), ((b + 1) >> 1) & 1);
                    if (MODE == 2) {
                        q_ready = mbar_test(bar_qf + 8 * (~item & 1), ((item + 1) >> 1) & 1);
                        asm volatile("ld.shared.s32 %0, [%1];" : "=r"(tnext) : "r"(slot + (~item & 1) * 4) : "memory");
                    }
                }
#pragma unroll
                for (int j = 0; j < 4; j++) {
                    const int i = g * 4 + j;
                    if (g < 16) p[i] = ex2v(p[i]);
                    if (g < 15) {
                        if (MODE == 2 && (!R || i + 4 < 32)) mask((i + 4) ^ R);
                        p[i + 4] = fmaf(s[(i + 4) ^ R], sc, (i & 2) ? -m1 : -m0);
                    }
                    if (g >= FA_LAG) u[j] += p[i - FA_LAG * 4];
                }
#pragma unroll
                for (int gg = 0; gg < 16; gg++) {
                    const int at = MODE && gg + FA_LAG < FA_SPLIT + gg / FA_PK ? FA_SPLIT + gg / FA_PK : gg + FA_LAG;
                    if (at == g) { pa[(gg * 2) ^ (R / 2)] = pack_bf16(p[gg * 4], p[gg * 4 + 1]); pa[(gg * 2 + 1) ^ (R / 2)] = pack_bf16(p[gg * 4 + 2], p[gg * 4 + 3]); }
                }
                if (MODE && g < 16) sched_fence(b, g + MODE * 32, &p[g * 4], &p[(g < 15 ? g + 1 : g) * 4], u);
            }
            u0 = u[0] + u[1]; u1 = u[2] + u[3];
        };
        auto quad_max = [&](float& x0, float& x1) {
            x0 = fmaxf(x0, __shfl_xor_sync(0xffffffff, x0, 1)); x1 = fmaxf(x1, __shfl_xor_sync(0xffffffff, x1, 1));
            x0 = fmaxf(x0, __shfl_xor_sync(0xffffffff, x0, 2)); x1 = fmaxf(x1, __shfl_xor_sync(0xffffffff, x1, 2));
            x0 = fmaf(x0, sc, FA_MARGIN); x1 = fmaf(x1, sc, FA_MARGIN);
        };
        auto softmax_exact = [&](bool fresh, bool half, int b) {
            wgmma_wait<0>();
            if (half) {
#pragma unroll
                for (int i = 0; i < 32; i++) s[i] = -INFINITY;
            }
            float x[8];
#pragma unroll
            for (int i = 0; i < 8; i++) x[i] = fmaxf(s[i * 2], s[i * 2 + 1]);
#pragma unroll
            for (int i = 8; i < 32; i++) x[i & 7] = fmaxf(x[i & 7], fmaxf(s[i * 2], s[i * 2 + 1]));
            float x0 = fmaxf(fmaxf(x[0], x[2]), fmaxf(x[4], x[6])), x1 = fmaxf(fmaxf(x[1], x[3]), fmaxf(x[5], x[7]));
            quad_max(x0, x1);
            if (!fresh) {
                x0 = fmaxf(x0, m0); x1 = fmaxf(x1, m1);
                const float a0 = ex2f(m0 - x0), a1 = ex2f(m1 - x1);
                l0 *= a0; l1 *= a1;
#pragma unroll
                for (int i = 0; i < 16; i++) { o[i * 4 + 0] *= a0; o[i * 4 + 1] *= a0; o[i * 4 + 2] *= a1; o[i * 4 + 3] *= a1; }
            }
            m0 = x0; m1 = x1;
            float u0, u1;
            exps(std::integral_constant<int, 0>(), b, false, u0, u1);
            l0 += u0; l1 += u1;
        };
        auto finish_rows = [&]() {
            l0 += __shfl_xor_sync(0xffffffff, l0, 1); l1 += __shfl_xor_sync(0xffffffff, l1, 1);
            l0 += __shfl_xor_sync(0xffffffff, l0, 2); l1 += __shfl_xor_sync(0xffffffff, l1, 2);
            asm("rcp.approx.ftz.f32 %0, %1;" : "=f"(i0) : "f"(l0));
            asm("rcp.approx.ftz.f32 %0, %1;" : "=f"(i1) : "f"(l1));
            i0 *= g0; i1 *= g1;
        };
        auto clear_out = [&](int t) {
            if (t >= 384) {
                bf16* z = P.out + (size_t)(fa_qt(t) * 128 + wg * 64 + ((threadIdx.x & 127) >> 3)) * DM + (t & 7) * 64 + (lane & 7) * 8;
#pragma unroll
                for (int i = 0; i < 4; i++) *reinterpret_cast<uint4*>(z + i * 16 * DM) = make_uint4(0u, 0u, 0u, 0u);
            }
        };
        auto store_o = [&](int t, int n, int c0, int c1) {
            const uint32_t stg = sO + wg * 16384;
            if (c0 == 0) {
                mbar_wait(bar_oe + 8 * wg, (n & 1) ^ 1);
                asm volatile("st.shared.s32 [%0], %1;" :: "r"(oslot + wg * 4), "r"(t) : "memory");
            }
            const int row = (warp & 3) * 16 + (lane >> 2);
#pragma unroll
            for (int i = c0; i < c1; i++) {
                const int ch = i * 4 + (lane & 3);
                const uint32_t a = stg + (ch >> 3) * 8192 + row * 128 + (((ch & 7) ^ (row & 7)) << 4);
                const float* q = &o[i * 16];
                asm volatile("st.shared.v4.b32 [%0], {%1, %2, %3, %4};" :: "r"(a), "r"(pack_bf16(q[0] * i0, q[1] * i0)), "r"(pack_bf16(q[4] * i0, q[5] * i0)),
                             "r"(pack_bf16(q[8] * i0, q[9] * i0)), "r"(pack_bf16(q[12] * i0, q[13] * i0)) : "memory");
                asm volatile("st.shared.v4.b32 [%0], {%1, %2, %3, %4};" :: "r"(a + 1024), "r"(pack_bf16(q[2] * i1, q[3] * i1)), "r"(pack_bf16(q[6] * i1, q[7] * i1)),
                             "r"(pack_bf16(q[10] * i1, q[11] * i1)), "r"(pack_bf16(q[14] * i1, q[15] * i1)) : "memory");
            }
        };
        auto store_o_late = [&](int v) {
            uint32_t w[32];
#pragma unroll
            for (int i = FA_ST * 8; i < 32; i++) {
                const float* q = &o[(i >> 3) * 16 + (i & 3) * 4 + ((i >> 2) & 1) * 2];
                const float f = (i & 4) ? i1 : i0;
                w[i] = pack_bf16(q[0] * f, q[1] * f);
            }
            const int row = (warp & 3) * 16 + (lane >> 2);
            if (v == 1000000) {
#pragma unroll
                for (int i = FA_ST * 2; i < 8; i++)
                    asm volatile("st.volatile.shared.v4.b32 [%0], {%1, %2, %3, %4};" :: "r"(v), "r"(w[i * 4]), "r"(w[i * 4 + 1]), "r"(w[i * 4 + 2]), "r"(w[i * 4 + 3]) : "memory");
                asm volatile("wgmma.wait_group.sync.aligned 0;\nexit;" ::: "memory");
            }
#pragma unroll
            for (int i = FA_ST * 2; i < 8; i++) {
                const int ch = (i >> 1) * 4 + (lane & 3);
                const uint32_t a = sO + wg * 16384 + (ch >> 3) * 8192 + row * 128 + (((ch & 7) ^ (row & 7)) << 4) + (i & 1) * 1024;
                asm volatile("st.shared.v4.b32 [%0], {%1, %2, %3, %4};" :: "r"(a), "r"(w[i * 4]), "r"(w[i * 4 + 1]), "r"(w[i * 4 + 2]), "r"(w[i * 4 + 3]) : "memory");
            }
        };
        auto publish_o = [&]() {
            asm volatile("fence.proxy.async.shared::cta;" ::: "memory");
            __syncwarp();
            mbar_arrive_if(bar_of + 8 * wg, lane == 0);
        };
        int t = 0, left = 0, tdone = -1, b = 0, nout = 0;
        bool first = true, staged = false;
#pragma unroll 1
        for (;; b++) {
            const bool fresh = left == 0;
            const int tprev = t;
            FAT(b, 4);
            if (staged) { publish_o(); staged = false; }
            if (fresh) {
                item++;
                if (!q_ready) {
                    mbar_wait(bar_qf + 8 * (item & 1), (item >> 1) & 1);
                    asm volatile("ld.shared.s32 %0, [%1];" : "=r"(tnext) : "r"(slot + (item & 1) * 4) : "memory");
                }
                if (tnext < 0) break;
                t = tnext;
                left = fa_qt(t) + 1;
            }
            left--;
            if (fresh || first || left == 0) {
                if (tdone >= 0) store_o(tdone, nout, 0, FA_ST);
                if (fresh) { g0 = gn0; g1 = gn1; }
                if (left == 0) { gn0 = __ldcg(g_gate + fa_qt(t) * 128 + r0); gn1 = __ldcg(g_gate + fa_qt(t) * 128 + r0 + 8); clear_out(t); }
            }
            FAT(b, 5);
            if (!k_ready) mbar_wait(bar_kf + 8 * (b & 1), (b >> 1) & 1);
            FAT(b, 6);
            asm volatile("bar.sync %0, 256;" :: "r"(3 + wg) : "memory");
            FAT(b, 0);
            issue_qk(b, item, FA_TRIM && wg == 0 && left == 0);
            FAT(b, 7);
            bool early = false;
            if (!fresh && !first && left != 0) {
                issue_pv(b - 1, true, FA_P0, false);
                wgmma_wait<1>();
                FAT(b, 1);
                mbar_arrive_if(bar_ke + 8 * (b & 1), lane == 0);
            } else {
                const bool hprev = FA_TRIM && fresh && wg == 0;
                early = (FA_EARLY && tdone >= 0) || b == 0 || (FA_TE && hprev);
                if (early) asm volatile("bar.arrive %0, 256;" :: "r"(4 - wg) : "memory");
                if (tdone >= 0) { wgmma_wait<1>(); if (FA_ST < 4) store_o_late(b); nout++; staged = true; }
                tdone = fresh && b > 0 ? tprev : -1;
                v_hi = hprev ? v_lo - 512 : v_lo;
                acc_hi = !(hprev && first);
                if (b > 0) issue_pv(b - 1, !first, FA_P0, hprev); else { wgmma_fence(); wgmma_commit(); }
                first = fresh;
                wgmma_wait<1>();
                FAT(b, 1);
                mbar_arrive_if(bar_ke + 8 * (b & 1), lane == 0);
                mbar_arrive_if(bar_qe + 8 * (item & 1), lane == 0 && left == 0);
                if (left == 0) { mask(FA_TRIM ? 32 : 0); mask(FA_TRIM ? 33 : 1); }
                if (fresh) {
                    m0 = fmaxf(s[0], s[1]); m1 = fmaxf(s[2], s[3]);
                    if (FA_TRIM && left == 0) { m0 = fmaxf(s[32], s[33]); m1 = fmaxf(s[34], s[35]); }
                    quad_max(m0, m1);
                    if (FA_V2) { finish_rows(); l0 = l1 = 0.f; }
                }
            }
            if (FA_B0 || b > 0) {
                float u0, u1;
                if (left == 0) exps(std::integral_constant<int, 2>(), b, !early, u0, u1);
                else exps(std::integral_constant<int, 1>(), b, !early, u0, u1);
                if (!__any_sync(0xffffffff, !(u0 + u1 < 1.f))) { l0 += u0; l1 += u1; continue; }
            }
            softmax_exact(fresh, FA_TRIM && wg == 0 && left == 0, b);
        }
        if (tdone >= 0) { store_o(tdone, nout++, 0, 4); publish_o(); }
        issue_pv(b - 1, !first, 8, FA_TRIM && wg == 0);
        if (FA_V2) { g0 = gn0; g1 = gn1; }
        finish_rows();
        wgmma_wait<0>();
        done();
        store_o(t + 1024, nout, 0, 4);
        publish_o();
        return nout;
    }
}

__device__ __forceinline__ uint32_t cluster_ctarank() {
    uint32_t r; asm volatile("mov.u32 %0, %%cluster_ctarank;" : "=r"(r)); return r;
}
__device__ __forceinline__ uint32_t mapa_u32(uint32_t addr, uint32_t rank) {
    uint32_t r; asm volatile("mapa.shared::cluster.u32 %0, %1, %2;" : "=r"(r) : "r"(addr), "r"(rank)); return r;
}
__device__ __forceinline__ void cluster_sync_all() {
    asm volatile("barrier.cluster.arrive.release.aligned;\nbarrier.cluster.wait.acquire.aligned;" ::: "memory");
}
__device__ __forceinline__ void st_async_v4(uint32_t addr, uint32_t a, uint32_t b, uint32_t c, uint32_t d, uint32_t mbar) {
    asm volatile("st.async.weak.shared::cluster.mbarrier::complete_tx::bytes.v4.b32 [%0], {%1, %2, %3, %4}, [%5];"
                 :: "r"(addr), "r"(a), "r"(b), "r"(c), "r"(d), "r"(mbar) : "memory");
}
__device__ __forceinline__ void st_async_v2(uint32_t addr, uint32_t a, uint32_t b, uint32_t mbar) {
    asm volatile("st.async.weak.shared::cluster.mbarrier::complete_tx::bytes.v2.b32 [%0], {%1, %2}, [%3];"
                 :: "r"(addr), "r"(a), "r"(b), "r"(mbar) : "memory");
}
__device__ __forceinline__ void st_async_b32(uint32_t addr, uint32_t a, uint32_t mbar) {
    asm volatile("st.async.weak.shared::cluster.mbarrier::complete_tx::bytes.b32 [%0], %1, [%2];" :: "r"(addr), "r"(a), "r"(mbar) : "memory");
}
__device__ __forceinline__ void pace(int cycles) {
    if (cycles > 0) {
        uint32_t t0, t;
        asm volatile("mov.u32 %0, %%clock;" : "=r"(t0));
        do { asm volatile("mov.u32 %0, %%clock;" : "=r"(t)); } while (t - t0 < (uint32_t)cycles);
    }
}
__device__ __forceinline__ void mbar_wait_cl(uint32_t bar, uint32_t parity) {
    uint32_t done = 0;
    for (int it = 0; it < WAIT_LIMIT && !done; it++) {
        asm volatile(
            "{\n.reg .pred p;\n"
            "mbarrier.try_wait.parity.shared::cta.b64 p, [%1], %2;\n"
            "selp.u32 %0, 1, 0, p;\n}\n" : "=r"(done) : "r"(bar), "r"(parity) : "memory");
    }
}
__device__ __forceinline__ void ldmatrix_x4(uint32_t& r0, uint32_t& r1, uint32_t& r2, uint32_t& r3, uint32_t addr) {
    asm volatile("ldmatrix.sync.aligned.m8n8.x4.shared.b16 {%0,%1,%2,%3}, [%4];"
                 : "=r"(r0), "=r"(r1), "=r"(r2), "=r"(r3) : "r"(addr));
}
__device__ __forceinline__ void cp_async16(uint32_t dst, const void* src) {
    asm volatile("cp.async.cg.shared.global [%0], [%1], 16;" :: "r"(dst), "l"(src) : "memory");
}
__device__ __forceinline__ float bf16r(float x) { return __uint_as_float(pack_bf16(0.f, x) & 0xffff0000u); }

#define DBGP(i, w, ok)
#define DBG(i, w)
#define DBGD(i, w, dep)
#define DBG_EXTRA 0
__device__ __forceinline__ void tma_load_2d_mc(uint32_t dst, const CUtensorMap* map, uint32_t bar, int c0, int c1, uint16_t mask) {
    asm volatile(
        "cp.async.bulk.tensor.2d.shared::cluster.global.mbarrier::complete_tx::bytes.multicast::cluster [%0], [%1, {%3, %4}], [%2], %5;"
        :: "r"(dst), "l"((uint64_t)map), "r"(bar), "r"(c0), "r"(c1), "h"(mask) : "memory");
}
__device__ __forceinline__ void stmatrix_x4_trans(uint32_t addr, uint32_t r0, uint32_t r1, uint32_t r2, uint32_t r3) {
    asm volatile("stmatrix.sync.aligned.m8n8.x4.trans.shared.b16 [%0], {%1, %2, %3, %4};" :: "r"(addr), "r"(r0), "r"(r1), "r"(r2), "r"(r3) : "memory");
}
__device__ __forceinline__ void stmatrix_x2_trans(uint32_t addr, uint32_t r0, uint32_t r1) {
    asm volatile("stmatrix.sync.aligned.m8n8.x2.trans.shared.b16 [%0], {%1, %2};" :: "r"(addr), "r"(r0), "r"(r1) : "memory");
}
__device__ __forceinline__ uint4 lds128(uint32_t a) {
    uint4 v; asm volatile("ld.shared.v4.u32 {%0, %1, %2, %3}, [%4];" : "=r"(v.x), "=r"(v.y), "=r"(v.z), "=r"(v.w) : "r"(a) : "memory"); return v;
}
__device__ __forceinline__ void sts128(uint32_t a, uint32_t x, uint32_t y, uint32_t z, uint32_t w) {
    asm volatile("st.shared.v4.b32 [%0], {%1, %2, %3, %4};" :: "r"(a), "r"(x), "r"(y), "r"(z), "r"(w) : "memory");
}
__device__ __forceinline__ float2 lds64f(uint32_t a) {
    float2 v; asm volatile("ld.shared.v2.f32 {%0, %1}, [%2];" : "=f"(v.x), "=f"(v.y) : "r"(a) : "memory"); return v;
}
__device__ __forceinline__ void fence_async_smem() { asm volatile("fence.proxy.async.shared::cta;" ::: "memory"); }
#define ACC16(d) "+f"(d[0]), "+f"(d[1]), "+f"(d[2]), "+f"(d[3]), "+f"(d[4]), "+f"(d[5]), "+f"(d[6]), "+f"(d[7]), "+f"(d[8]), "+f"(d[9]), "+f"(d[10]), "+f"(d[11]), "+f"(d[12]), "+f"(d[13]), "+f"(d[14]), "+f"(d[15])
template <int ND>
__device__ __forceinline__ void wgmma_rs_n32(float (&d)[ND], const uint32_t (&a)[4], uint32_t db_lo, int scale_d) {
    asm volatile(
        "{\n.reg .pred p;\n.reg .b64 db;\nsetp.ne.b32 p, %21, 0;\nmov.b64 db, {%20, 0x40000040};\n"
        "wgmma.mma_async.sync.aligned.m64n32k16.f32.bf16.bf16 {%0,%1,%2,%3,%4,%5,%6,%7,%8,%9,%10,%11,%12,%13,%14,%15}, {%16,%17,%18,%19}, db, p, 1, 1, 0;\n}\n"
        : ACC16(d) : "r"(a[0]), "r"(a[1]), "r"(a[2]), "r"(a[3]), "r"(db_lo), "r"(scale_d));
}
template <int ND>
__device__ __forceinline__ void wgmma_ss_n32(float (&d)[ND], uint32_t da_lo, uint32_t db_lo, int scale_d) {
    asm volatile(
        "{\n.reg .pred p;\n.reg .b64 da, db;\nsetp.ne.b32 p, %18, 0;\nmov.b64 da, {%16, 0x40000040};\nmov.b64 db, {%17, 0x40000040};\n"
        "wgmma.mma_async.sync.aligned.m64n32k16.f32.bf16.bf16 {%0,%1,%2,%3,%4,%5,%6,%7,%8,%9,%10,%11,%12,%13,%14,%15}, da, db, p, 1, 1, 1, 0;\n}\n"
        : ACC16(d) : "r"(da_lo), "r"(db_lo), "r"(scale_d));
}
__device__ __forceinline__ void wgmma_ss_n8(float (&d)[4], uint32_t da_lo, uint32_t db_lo, int scale_d) {
    asm volatile(
        "{\n.reg .pred p;\n.reg .b64 da, db;\nsetp.ne.b32 p, %6, 0;\nmov.b64 da, {%4, 0x40000040};\nmov.b64 db, {%5, 0x00000010};\n"
        "wgmma.mma_async.sync.aligned.m64n8k16.f32.bf16.bf16 {%0,%1,%2,%3}, da, db, p, 1, 1, 1, 0;\n}\n"
        : "+f"(d[0]), "+f"(d[1]), "+f"(d[2]), "+f"(d[3]) : "r"(da_lo), "r"(db_lo), "r"(scale_d));
}

#define SCHED_FENCE()
__device__ __forceinline__ void wgmma_ss_n32_p(float (&d)[16], uint32_t da_lo, uint32_t db_lo, int scale_d) {
    asm volatile(
        "{\n.reg .pred p;\n.reg .b64 da, db;\nsetp.ne.b32 p, %18, 0;\nmov.b64 da, {%16, 0x40000040};\nmov.b64 db, {%17, 0x00000030};\n"
        "wgmma.mma_async.sync.aligned.m64n32k16.f32.bf16.bf16 {%0,%1,%2,%3,%4,%5,%6,%7,%8,%9,%10,%11,%12,%13,%14,%15}, da, db, p, 1, 1, 1, 0;\n}\n"
        : ACC16(d) : "r"(da_lo), "r"(db_lo), "r"(scale_d));
}

#define ACC20(d) ACC16(d), "+f"(d[16]), "+f"(d[17]), "+f"(d[18]), "+f"(d[19])
#define ACC20_STR "{%0,%1,%2,%3,%4,%5,%6,%7,%8,%9,%10,%11,%12,%13,%14,%15,%16,%17,%18,%19}"
__device__ __forceinline__ void wgmma_rs_n40(float (&d)[20], const uint32_t (&a)[4], uint32_t db_lo, int scale_d) {
    asm volatile(
        "{\n.reg .pred p;\n.reg .b64 db;\nsetp.ne.b32 p, %25, 0;\nmov.b64 db, {%24, 0x40000040};\n"
        "wgmma.mma_async.sync.aligned.m64n40k16.f32.bf16.bf16 " ACC20_STR ", {%20,%21,%22,%23}, db, p, 1, 1, 0;\n}\n"
        : ACC20(d) : "r"(a[0]), "r"(a[1]), "r"(a[2]), "r"(a[3]), "r"(db_lo), "r"(scale_d));
}
template <int TA, int SBO>
__device__ __forceinline__ void wgmma_ss_n40(float (&d)[20], uint32_t da_lo, uint32_t db_lo, int scale_d) {
    asm volatile(
        "{\n.reg .pred p;\n.reg .b64 da, db;\nsetp.ne.b32 p, %22, 0;\nmov.b64 da, {%20, %23};\nmov.b64 db, {%21, 0x40000040};\n"
        "wgmma.mma_async.sync.aligned.m64n40k16.f32.bf16.bf16 " ACC20_STR ", da, db, p, 1, 1, %24, 0;\n}\n"
        : ACC20(d) : "r"(da_lo), "r"(db_lo), "r"(scale_d), "n"(0x40000000 + SBO / 16), "n"(TA));
}
template <int SBO>
__device__ __forceinline__ void wgmma_ss_n48(float (&d)[24], uint32_t da_lo, uint32_t db_lo, int scale_d) {
    asm volatile(
        "{\n.reg .pred p;\n.reg .b64 da, db;\nsetp.ne.b32 p, %26, 0;\nmov.b64 da, {%24, %27};\nmov.b64 db, {%25, 0x40000040};\n"
        "wgmma.mma_async.sync.aligned.m64n48k16.f32.bf16.bf16 {%0,%1,%2,%3,%4,%5,%6,%7,%8,%9,%10,%11,%12,%13,%14,%15,%16,%17,%18,%19,%20,%21,%22,%23}, da, db, p, 1, 1, 0, 0;\n}\n"
        : ACC20(d), "+f"(d[20]), "+f"(d[21]), "+f"(d[22]), "+f"(d[23]) : "r"(da_lo), "r"(db_lo), "r"(scale_d), "n"(0x40000000 + SBO / 16));
}

#define PT(i, th)
struct ChainParams {
    CUtensorMap mapW[3];
    CUtensorMap mapX;
    CUtensorMap mapC;
    CUtensorMap mapWo;
    CUtensorMap mapM;
    CUtensorMap mapOut;
};
constexpr int CH_BLOCK = 384;
constexpr int CO_WO = 0;
constexpr int CH_XC = 5120, CH_XP = 8 * CH_XC;
constexpr int CO_XB = 65536;
constexpr int CO_OB = CO_XB + 2 * CH_XP;
constexpr int CO_P = CO_OB + 8192;
constexpr int CO_LS = CO_P + 3072;
constexpr int CO_SC = CO_LS + 8 * 1280;
constexpr int CH_TW = 6144 + 8192;
constexpr int CO_T = 21 * 8192;
constexpr int CO_WA = CO_T + 6144;
constexpr int CO_ST = CO_T + 3 * CH_TW + 6144;
constexpr int CO_OWN = CO_ST + 4096, CO_OWN2 = CO_SC + 1536;
constexpr int CO_BAR = CO_OWN + 4096;
constexpr int CH_SMEM = CO_BAR + 256 + DBG_EXTRA;
#define CH_GL 2
#define CH_A3 1
#define CH_D0 0
#define CH_PF 0
#define CH_NA 0
#define CH_LQ ""
#define CH_SQ ""
#define CH_XPF 0
#define CH_NSM 4
static_assert(CO_OWN2 + 1024 <= CO_T && CH_NSM <= 4, "smem layout");
#define CH_T3 1
#define CH_POLL_DELAY 240
#define CH_VPOS 2
#define CH_OW 12
#define CH_OF 12
#define CH_Q0 0
#define CH_QI 12
#define CH_QX 0
#define CH_Q1 (CH_Q0 + CH_QI + CH_QX)
#define CH_VA 5
#define CH_SPOS 0
#define CH_LSW 1
#define CH_QE 16
#define CH_KE 16
#define CH_QD 0
#define CH_GAP 0
#define CH_QS 0
#define CH_KS 0
#define CH_VS 4
#define CH_A7 7
#define CH_RF 0
#define CH_LSS 0
#define CH_OS 1
#define CH_MG 0
#define CH_MBT 0x76543210u
#define CH_MB(i) ((int)(CH_MBT >> 4 * (i)) & 7)
#define CH_AS 0x64207531u
#define CH_QL 16
#define CH_ML 0x112112
#define CH_DEP 1
#define CH_SP 2
#define CH_VD 0
#define CH_MP 2
#define CH_MP0 2
#define CH_OFE 3
#define CH_MS 1
#define CH_HA 3
#define CH_LD 4
#define CH_TWP 0
#define CH_SUMC 4
#define CH_ES 0
#define CH_ST 224
#define CH_KEEP 1
#define CH_PINB 1
#define CH_DRY 1
#define CH_D1 4500
#define CH_D2 11000
#define CH_CHAINS 4

constexpr float CH_SC = 0.08838834764831845f * 1.4426950408889634f;
__device__ __forceinline__ uint32_t pin(uint32_t v) { return __shfl_sync(0xffffffff, v, threadIdx.x & 31); }

__device__ __forceinline__ void out_finished() {
    if (atomicAdd(&g_ctr[CT_FIN], 1u) == M_GRID + 64 - 1)
        for (int i = 0; i < CT_N / 4; i++) reinterpret_cast<uint4*>(g_ctr)[i] = make_uint4(0u, 0u, 0u, 0u);
}
__device__ __forceinline__ void out_flush_half(const float* acc, const CUtensorMap* map, uint32_t stg, int tid, int bar, int n0, int m0) {
    const int lane = tid & 31, row = (lane & 7) + ((lane >> 3) & 1) * 8;
#pragma unroll
    for (int j = 0; j < 16; j += 2) {
        const float* a = &acc[j * 4];
        stmatrix_x4(stg + (j >> 3) * 8192 + (((tid >> 5) & 3) * 16 + row) * 128 + ((((j & 7) + (lane >> 4)) ^ (row & 7)) << 4),
                    pack_bf16(a[0], a[1]), pack_bf16(a[2], a[3]), pack_bf16(a[4], a[5]), pack_bf16(a[6], a[7]));
    }
    asm volatile("fence.proxy.async.shared::cta;\nbar.sync %0, 128;" :: "r"(bar) : "memory");
    asm volatile("{\n.reg .pred p;\nsetp.ne.b32 p, %0, 0;\n@p bra FL_SKIP;\n"
                 "cp.reduce.async.bulk.tensor.2d.global.shared::cta.add.tile.bulk_group [%1, {%3, %5}], [%2];\n"
                 "cp.reduce.async.bulk.tensor.2d.global.shared::cta.add.tile.bulk_group [%1, {%4, %5}], [%2 + 8192];\n"
                 "cp.async.bulk.commit_group;\nFL_SKIP:\n}"
                 :: "r"(tid & 127), "l"((uint64_t)map), "r"(stg), "r"(n0), "r"(n0 + 64), "r"(m0) : "memory");
    __syncwarp();
}
__device__ __forceinline__ void out_flush(const float (&acc)[128], const CUtensorMap* map, uint32_t stg0, uint32_t stg1, int tid, int bar, int n0, int m0) {
    out_flush_half(acc, map, stg0, tid, bar, n0, m0);
    out_flush_half(acc + 64, map, stg1, tid, bar, n0 + 128, m0);
}

__global__ void __cluster_dims__(8, 1, 1) __launch_bounds__(CH_BLOCK, 1)
chain_kernel(const __grid_constant__ ChainParams P) {
    extern __shared__ uint8_t smem_raw[];
    const int tid = threadIdx.x, warp = __shfl_sync(0xffffffff, tid >> 5, 0), lane = tid & 31;
    const int rank = (int)cluster_ctarank();
    constexpr uint32_t sd = 1024;
    const uint32_t sb = ((uint32_t)rank << 24) + sd;
    if (smem_u32(smem_raw) != sb) __trap();
    const int C = blockIdx.x >> 3;
    const int h = C * 4 + (rank >> 1);
    const int qd = lane >> 2, qc = lane & 3;
    const int t4 = warp & 3, wg = warp >> 2;
    pdl_launch_dependents();
    uint32_t t_start;
    asm volatile("mov.u32 %0, %%clock;" : "=r"(t_start));
    t_start = __shfl_sync(0xffffffff, t_start, 0);
    TS_BEGIN(2);
    PT(0, 0);
    const uint32_t bar_mem = sb + CO_BAR + 128, bar_o = sb + CO_BAR + 32, bar_sc = bar_o + 32, bar_x = bar_sc + 8, bar_l = bar_x + 16, bar_w = bar_l + 8;
    const uint32_t bar_wo = bar_o + 24;
    auto chunk = [&](int i) { return (uint32_t)((rank - i) & 7); };
    auto mine = [](int g, int c) { return (int)((CH_AS >> (g * 16 + c * 4)) & 7); };
    const int wcol = h * HD + (rank & 1) * 64;
    auto wdst = [&](int g, int i) { return i == 0 ? CO_WA + g * CH_TW : g && i == 7 ? CO_ST : (g ? CO_XB + CH_XP : 0) + (i - 1) * 8192; };
    auto vdst = [&](int i) { return i >= 2 && i < 10 ? CO_XB + CH_XP + (i - 2) * CH_XC : (i < 2 ? CO_WA + 2 * CH_TW : i < 12 ? CO_OB : i < 14 ? CO_LS : CO_ST) + (i & 1) * 4096; };
    if ((tid & 127) == 0) {
        pace(CH_D0);
        const uint32_t bar = wg == 2 ? bar_x : bar_w + 8 * wg;
        mbar_init(bar, 1);
        asm volatile("fence.mbarrier_init.release.cluster;" ::: "memory");
        mbar_expect_tx(bar, wg == 2 ? CH_XP : 65536);
#pragma unroll 1
        for (int i = 0; i < 8; i++) {
            if (wg == 2) {
                tma_load_2d(sb + CO_XB + i * CH_XC, &P.mapX, bar, i * 64, 0);
                tma_load_2d(sb + CO_XB + i * CH_XC + 4096, &P.mapM, bar, i * 64, 0);
            } else tma_load_2d(sb + wdst(wg, i), &P.mapW[wg ^ (i & 1)], bar, wcol, chunk(mine(wg, i >> 1)) * 64);
        }
    }
    if (warp == 9 && lane < 24 && lane != 9 && (lane >> 1) != 6) {
        mbar_init(sb + CO_BAR + 8 * lane, 1);
        asm volatile("fence.mbarrier_init.release.cluster;" ::: "memory");
    }
    __syncthreads();
    PT(1, 0);
    if (wg == 2 || (wg == 0 && CH_QL < 16)) asm volatile("bar.arrive 10, %0;" :: "n"(CH_QL < 16 ? 384 : 256) : "memory");
    if (wg == 2) {
        const int t = tid - 256;
        sts128(sb + CO_T + (2 + (t >> 6)) * CH_TW + 5120 + (t & 63) * 16, 0u, 0u, 0u, 0u);
        if (t < 32) sts128(sb + CO_P + (t >> 3) * 768 + 640 + (t & 7) * 16, 0u, 0u, 0u, 0u);
    }
    const uint32_t wfrag = (((lane >> 4) << 3) + (lane & 7)) * 128 + (((t4 * 2 + ((lane >> 3) & 1)) ^ (lane & 7)) << 4);
    const uint32_t aO = pin(sb + wg * CH_TW + wfrag);
    const uint32_t aL = pin(sb + lane * 16);
    uint32_t w[32][4];
    auto load_w = [&](int g, bool v) {
#pragma unroll
        for (int e = CH_NSM; e < 32; e++) ldmatrix_x4_trans(w[e][0], w[e][1], w[e][2], w[e][3], aO + ((v ? vdst(e >> 1) + (e & 1) * 2048 : wdst(g, e >> 2) + (e & 3) * 2048) - g * CH_TW));
        fence_async_smem();
    };
    auto pass = [&](auto& d, int g, int b, int j0, int j1, int js, bool group = true) {
        const uint32_t lo = desc_lo(sd + CO_XB + b * CH_XP, 16);
        if (group) wgmma_fence();
#pragma unroll
        for (int j = 0; j < 32; j++) if (j >= j0 && j < j1) {
            const int f = js < 0 ? j : j < js ? j + CH_NSM : j < js + CH_NSM ? j - js : j;
            const int e = sizeof(d) == 64 ? (f >> 2) * 8 + (js < 0 ? 4 : 0) + (f & 3) : f;
            const uint32_t db = lo + chunk(sizeof(d) == 64 ? mine(g, f >> 2) : f >> 2) * (CH_XC / 16) + (e & 3) * 2, da = desc_lo(sd + CO_WA + g * CH_TW + e * 2048, 16);
            if constexpr (sizeof(d) == 64) { if (e < CH_NSM) wgmma_ss_n32(d, da, db, j != 0); else wgmma_rs_n32(d, w[e], db, j != 0); }
            else { if (e < CH_NSM) wgmma_ss_n40<1, 1024>(d, da, db, j != 0); else wgmma_rs_n40(d, w[e], db, j != 0); }
        }
        if (group) wgmma_commit();
    };
    auto uni = [](uint32_t v) { return __shfl_sync(0xffffffff, v, 0); };
    auto roff = [&](int j) { return (uint32_t)(((rank + j) & 7) - rank) << 24; };
    auto store32 = [&](const float* d, uint32_t a) {
        stmatrix_x4_trans(a, pack_bf16(d[0], d[1]), pack_bf16(d[2], d[3]), pack_bf16(d[4], d[5]), pack_bf16(d[6], d[7]));
        stmatrix_x4_trans(a + 2048, pack_bf16(d[8], d[9]), pack_bf16(d[10], d[11]), pack_bf16(d[12], d[13]), pack_bf16(d[14], d[15]));
    };
    auto load32 = [&](uint32_t (&r)[8], uint32_t a) {
        ldmatrix_x4_trans(r[0], r[1], r[2], r[3], a);
        ldmatrix_x4_trans(r[4], r[5], r[6], r[7], a + 2048);
    };
    auto add32 = [&](float* d, const uint32_t (&r)[8], uint32_t a) {
        wgmma_wait<0>();
#pragma unroll
        for (int i = 0; i < 8; i++) { d[2 * i] += __uint_as_float(r[i] << 16); d[2 * i + 1] += __uint_as_float(r[i] & 0xffff0000u); }
        store32(d, a);
    };
    auto scores = [&](float (&d)[24], auto sbo, uint32_t q) {
        wgmma_fence();
#pragma unroll
        for (int ks = 0; ks < 4; ks++) wgmma_ss_n48<decltype(sbo)::value>(d, desc_lo(sd + q, 16) + ks * 2, desc_lo(sd + CO_T + CH_TW, 16) + ks * 2, ks != 0);
        wgmma_commit();
    };
    auto add_scores = [&](uint32_t a, uint32_t b, float (&v)[10]) {
        const uint4 a0 = lds128(a), a1 = lds128(a + 512);
        const float2 a2 = lds64f(b);
        v[0] += __uint_as_float(a0.x); v[1] += __uint_as_float(a0.y); v[2] += __uint_as_float(a0.z); v[3] += __uint_as_float(a0.w);
        v[4] += __uint_as_float(a1.x); v[5] += __uint_as_float(a1.y); v[6] += __uint_as_float(a1.z); v[7] += __uint_as_float(a1.w);
        v[8] += a2.x; v[9] += a2.y;
    };
    auto row_max = [&](const float (&v)[10]) {
        float mx = fmaxf(fmaxf(fmaxf(v[0], v[1]), fmaxf(v[2], v[3])), fmaxf(fmaxf(v[4], v[5]), fmaxf(v[6], v[7])));
        mx = fmaxf(mx, fmaxf(v[8], v[9]));
        mx = fmaxf(mx, __shfl_xor_sync(0xffffffff, mx, 1));
        return fmaxf(mx, __shfl_xor_sync(0xffffffff, mx, 2)) * CH_SC;
    };
    auto local_pv = [&](int s, int st) {
        float dc[16];
        wgmma_fence();
#pragma unroll
        for (int ks = 0; ks < 3; ks++) wgmma_ss_n32_p(dc, desc_lo(sd + CO_T + (2 + (s & 1)) * CH_TW + ks * 2048, 16), desc_lo(sd + CO_P + ks * 256, 128), ks != 0);
        wgmma_commit();
        wgmma_wait<0>();
        store32(dc, aO - CH_TW + st);
    };
    float gs = 0.f;
    auto load_gate = [&](int s) { asm volatile("ld.global.cg.f32 %0, [%1];" : "=f"(gs) : "l"(g_gate + s * SEGL + t4 * 8 + qd) : "memory"); };
    auto softmax = [&](int s, float (&u)[11]) {
        float v[10];
        {
            const uint4 a0 = lds128(aL + CO_OWN + t4 * 1024), a1 = lds128(aL + CO_OWN + t4 * 1024 + 512);
            const float2 a2 = lds64f(aL + CO_OWN2 + t4 * 256 - lane * 8);
            v[0] = __uint_as_float(a0.x); v[1] = __uint_as_float(a0.y); v[2] = __uint_as_float(a0.z); v[3] = __uint_as_float(a0.w);
            v[4] = __uint_as_float(a1.x); v[5] = __uint_as_float(a1.y); v[6] = __uint_as_float(a1.z); v[7] = __uint_as_float(a1.w);
            v[8] = a2.x; v[9] = a2.y;
        }
        mbar_wait_cl(bar_l, s & 1);
        add_scores(aL + t4 * 1024 + CO_LS + (s & 1) * 5120, aL + t4 * 256 - lane * 8 + CO_LS + (s & 1) * 5120 + 4096, v);
        const int lim = t4 * 8 + qd - 2 * qc;
#pragma unroll
        for (int j = 0; j < 8; j++) if ((j >> 1) * 8 + (j & 1) > lim) v[j] = -INFINITY;
        const float mx = row_max(v);
#pragma unroll
        for (int j = 0; j < 10; j++) u[j] = v[j];
        u[10] = mx;
    };
    auto softmax1 = [&](float (&u)[11]) {
#pragma unroll
        for (int j = 0; j < 10; j++) u[j] = ex2f(fmaf(u[j], CH_SC, -u[10]));
        u[10] = (((u[0] + u[1]) + (u[2] + u[3])) + ((u[4] + u[5]) + (u[6] + u[7]))) + (u[8] + u[9]);
    };
    auto softmax2 = [&](float (&v)[11]) {
        float sum = v[10];
        sum += __shfl_xor_sync(0xffffffff, sum, 1);
        sum += __shfl_xor_sync(0xffffffff, sum, 2);
        asm("rcp.approx.ftz.f32 %0, %0;" : "+f"(sum));
        sum *= 1.f - gs;
        const uint32_t pa = aL + CO_P + t4 * 768;
        stmatrix_x4(pa, pack_bf16(v[0] * sum, v[1] * sum), pack_bf16(v[2] * sum, v[3] * sum), pack_bf16(v[4] * sum, v[5] * sum), pack_bf16(v[6] * sum, v[7] * sum));
        asm volatile("stmatrix.sync.aligned.m8n8.x1.shared.b16 [%0], {%1};" :: "r"(pa + 512), "r"(pack_bf16(v[8] * sum, v[9] * sum)) : "memory");
    };
    if (mapa_u32(bar_l, rank ^ 1) != (bar_l ^ (1u << 24)) || mapa_u32(bar_l, (rank + 3) & 7) != bar_l + roff(3)) __trap();
    asm volatile("bar.sync %0, 128;" :: "r"(12 + wg) : "memory");
    if (__shfl_sync(0xffffffff, tid, 1) < 256) {
#pragma unroll 1
        for (int rep = CH_DRY ? 0 : 1; rep < 2; rep++) {
            if (rep) mbar_wait(bar_w + 8 * wg, 0);
            PT(3, 0);
            load_w(wg, false);
            if (rep) {
                asm volatile("bar.arrive %0, 160;" :: "r"(wg ? 2 : 15) : "memory");
                asm volatile("barrier.cluster.arrive.relaxed.aligned;" ::: "memory");
                mbar_wait(bar_x, 0);
            }
            asm volatile("bar.sync 12, 256;" ::: "memory");
            PT(7, 0);
            float d[16];
            pass(d, wg, 0, 0, 16, -1);
            wgmma_wait<0>();
            store32(d, aO + CO_T + (1 - 2 * wg) * CH_TW);
            pass(d, wg, 0, 0, 16, 0);
            asm volatile("bar.sync 13, 256;" ::: "memory");
            uint32_t r[8];
            load32(r, aO + CO_T);
            add32(d, r, aO + CO_T);
        }
    }
    PT(8, 0);
    TS_BEGIN(5);
    PT(9, 0);

    if (wg < 2) {
        const uint32_t aM = pin(sb + CO_XB + 4096 + (lane & 7) * 128 + (((lane >> 3) ^ (lane & 7)) << 4));
        uint32_t coff[4];
#pragma unroll
        for (int i = 0; i < 4; i++) coff[i] = uni(chunk(mine(wg, i)) * CH_XC);
        auto mem_proj = [&](int s, auto gc) {
            constexpr int G = decltype(gc)::value;
            const uint32_t par = s & 1;
            float acc[4][4];
#pragma unroll
            for (int i = 0; i < 4; i++) acc[i][0] = acc[i][1] = acc[i][2] = acc[i][3] = 0.f;
            const uint32_t am = aM + par * CH_XP;
            uint32_t b[4][4], ok = 1;
            auto bar = [&](int c) { return bar_mem + 8 * CH_MB(mine(G, c)); };
            auto load = [&](int c) {
                if (c ? CH_MB(mine(G, c)) != CH_MB(mine(G, c - 1)) : G == 0)
                    asm volatile("{\n.reg .pred p, q;\n.reg .u32 c;\nsetp.ne.u32 p, %2, 0;\n@p bra MP_DONE;\nmov.u32 c, 0;\n"
                                 "MP_LOOP:\nmbarrier.try_wait.parity.shared::cta.b64 p, [%0], %1;\nadd.u32 c, c, 1;\nsetp.lt.and.u32 q, c, %3, !p;\n"
                                 "@q bra MP_LOOP;\nMP_DONE:\n}" :: "r"(bar(c)), "r"(par ^ 1), "r"(ok), "n"(WAIT_LIMIT / 64) : "memory");
                uint32_t* r = b[2 * c & 3];
                ldmatrix_x4(r[0], r[1], r[2], r[3], am + coff[c]);
                r = b[(2 * c + 1) & 3];
                ldmatrix_x4(r[0], r[1], r[2], r[3], (am ^ 64) + coff[c]);
                if (c < 3 && CH_MB(mine(G, c + 1)) != CH_MB(mine(G, c))) ok = mbar_try(bar(c + 1), par ^ 1);
            };
            auto mma = [&](int i) {
#pragma unroll
                for (int j = 0; j < 4; j++) {
                    const uint32_t* a = w[(i >> 1) * 8 + ((j & 1) ^ G) * 4 + (i & 1) * 2 + (j >> 1)];
                    mma_16816(acc[j], a[0], a[1], a[2], a[3], b[i & 3][j & 2], b[i & 3][(j & 2) + 1]);
                }
            };
#pragma unroll
            for (int e = 0; e < CH_NSM; e++) ldmatrix_x4_trans(w[e][0], w[e][1], w[e][2], w[e][3], aO + CO_WA + e * 2048);
            if (G == 1) asm volatile("bar.sync 10, %0;" :: "n"(CH_QL < 16 ? 384 : 256) : "memory");
            else ok = mbar_try(bar(0), par ^ 1);
            DBG(11, 0);
            load(0);
#pragma unroll
            for (int c = 0; c < 3; c++) {
                const int at = (CH_ML >> (c * 4 + G * 12)) & 3;
                if (at == 0) load(c + 1);
                mma(2 * c);
                if (at == 1) load(c + 1);
                mma(2 * c + 1);
                if (at == 2) load(c + 1);
            }
            mma(6);
            uint32_t dep = __float_as_uint(acc[CH_HA & 3][0]);
            mma(7);
            if (CH_HA >= 4) dep = __float_as_uint(acc[CH_HA & 3][0]);
            asm volatile("bar.arrive %0, 384;" :: "r"(5 | (dep & (s >> 10))) : "memory");
            uint32_t r[4];
#pragma unroll
            for (int i = 0; i < 4; i++) r[i] = pack_bf16(acc[i >> 1][(i & 1) * 2] + acc[(i >> 1) + 2][(i & 1) * 2], acc[i >> 1][(i & 1) * 2 + 1] + acc[(i >> 1) + 2][(i & 1) * 2 + 1]);
            DBGD(40 + warp, warp, r[0] ^ r[1]);
            asm volatile("{\n.reg .pred q;\nsetp.ne.s32 q, %3, 0;\n"
                         "@q stmatrix.sync.aligned.m8n8.x2.trans.shared.b16 [%0], {%1, %2};\n"
                         "@q stmatrix.sync.aligned.m8n8.x2.trans.shared.b16 [%0 + %4], {%1, %2};\n"
                         "@q stmatrix.sync.aligned.m8n8.x2.trans.shared.b16 [%0 + 2 * %4], {%1, %2};\n"
                         "@q stmatrix.sync.aligned.m8n8.x2.trans.shared.b16 [%0 + 3 * %4], {%1, %2};\n}"
                         :: "r"(aO + (CO_XB + 4096 + G * (CH_XC - CH_TW) + (par ^ 1) * CH_XP)), "r"(r[0]), "r"(r[1]),
                            "r"(s - (NSEG - 1)), "n"(2 * CH_XC) : "memory");
            stmatrix_x2_trans(aO + CO_T + (G ? 5120 : CH_TW + 4096), r[2], r[3]);
            fence_async_smem();
        };
        if (wg == 0) {
#pragma unroll 1
            for (int s = 0; s < NSEG; s++) {
                const uint32_t par = s & 1;
                mem_proj(s, std::integral_constant<int, 0>());
                asm volatile("bar.arrive 1, 256;" ::: "memory");
                asm volatile("bar.sync 8, 384;" ::: "memory");
                if (s == NSEG - 1) break;
                if (tid == 96) {
#pragma unroll
                    for (int j = 1; j < 8; j++) {
                        int n = 0;
                        for (int i = 1; i < 8; i++) n += CH_MB(i) == j;
                        if (n) mbar_expect_tx(bar_mem + 8 * j, 1024 * n);
                        if (j < 4) mbar_expect_tx(bar_o + 8 * j - 8, 512 << j);
                    }
                }
                __syncwarp();
                uint32_t* wp = g_xbuf + (size_t)rank * 2048 + C * 256 + qc * 64 + t4 * 8 + qd;
                asm volatile("st.relaxed.gpu.global" CH_SQ ".u32 [%0], %1;" :: "l"(wp + ((s + 2) & 3) * 16384), "r"(~0u) : "memory");
                asm volatile("st.relaxed.gpu.global" CH_SQ ".u32 [%0], %1;" :: "l"(wp + ((s + 2) & 3) * 16384 + 32), "r"(~0u) : "memory");
                if (__builtin_expect(s == 0, 0)) {
                    asm volatile("barrier.cluster.wait.aligned;" ::: "memory");
                    mbar_wait(bar_wo, 0);
                    const int sr = (qd >> 2) * 2 + (qd & 1) + (qd & 2) * 4;
#pragma unroll 2
                    for (int ks = t4; ks < 32; ks += 4) {
                        const uint32_t a = sb + CO_WO + ks * 2048;
                        uint4 u[2][2];
#pragma unroll
                        for (int i = 0; i < 4; i++) { const int r = sr + (i >> 1) * 4; u[i >> 1][i & 1] = lds128(a + r * 128 + (((qc * 2 + (i & 1)) ^ (r & 7)) << 4)); }
                        __syncwarp();
#pragma unroll
                        for (int i = 0; i < 4; i++) {
                            const uint4 u0 = u[i >> 1][0], u1 = u[i >> 1][1];
                            const uint32_t sel = (i & 1) ? 0x7632 : 0x5410;
                            sts128(a + (qd + (i >> 1) * 8) * 128 + (((qc * 2 + (i & 1)) ^ qd) << 4),
                                   __byte_perm(u0.x, u0.y, sel), __byte_perm(u0.z, u0.w, sel), __byte_perm(u1.x, u1.y, sel), __byte_perm(u1.z, u1.w, sel));
                        }
                    }
                    fence_async_smem();
                }
                mbar_wait(bar_x + 8 * (par ^ 1), ((s + 1) >> 1) & 1);
                asm volatile("bar.sync 7, 384;" ::: "memory");
                float d[16];
                float c[4];
                const uint32_t alo = desc_lo(sd + CO_WO, 16), blo = desc_lo(sd + CO_OB, 128);
                wgmma_fence();
                pass(d, 0, par ^ 1, 0, CH_Q0, -1, false);
                asm volatile("bar.sync 11, 256;" ::: "memory");
#pragma unroll
                for (int i = 0; i < 32; i++) {
                    if (i == 4) { pass(d, 0, par ^ 1, CH_Q0 + min(4, CH_QI), CH_Q0 + min(4, CH_QI) + CH_QX, -1, false); mbar_wait_cl(bar_o, par); }
                    if (i == 8) mbar_wait_cl(bar_o + 8, par);
                    if (i == CH_OW) mbar_wait_cl(bar_o + 16, par);
                    wgmma_ss_n8(c, alo + i * 128, blo + i * 16, i != 0);
                    if (i < CH_QI) pass(d, 0, par ^ 1, CH_Q0 + i + (i < 4 ? 0 : CH_QX), CH_Q0 + i + (i < 4 ? 0 : CH_QX) + 1, -1, false);
                }
                wgmma_commit();
                wgmma_wait<0>();
                asm volatile("st.relaxed.gpu.global" CH_SQ ".u32 [%0], %1;" :: "l"(wp + (s & 3) * 16384), "r"(pack_bf16(c[0], c[2])) : "memory");
                asm volatile("st.relaxed.gpu.global" CH_SQ ".u32 [%0], %1;" :: "l"(wp + (s & 3) * 16384 + 32), "r"(pack_bf16(c[1], c[3])) : "memory");
                asm volatile("bar.arrive 6, 384;" ::: "memory");
                pace(CH_QD);
                asm volatile("bar.arrive 4, 384;" ::: "memory");
                DBG(8, 0);
                if (CH_Q1 < 16) pass(d, 0, par ^ 1, CH_Q1, 16, -1);
                asm volatile("bar.sync 9, 256;" ::: "memory");
                wgmma_wait<0>();
                store32(d, aO + CO_T + CH_TW);
                asm volatile("bar.arrive 12, 256;" ::: "memory");
                if (CH_QL) pass(d, 0, (par ^ 1) + (s >> 10), 0, CH_QL, CH_QS);
                DBG(21, 0);
                if (tid == 0) {
                    if (s + 2 < NSEG) {
                        mbar_expect_tx(bar_x + 8 * par, 32768);
                        tma_load_2d_mc(sb + CO_XB + par * CH_XP + rank * CH_XC, &P.mapX, bar_x + 8 * par, rank * 64, (s + 2) * SEGL, (uint16_t)0xff);
                        if (CH_XPF) asm volatile("cp.async.bulk.prefetch.tensor.2d.L2.global [%0, {%1, %2}];" :: "l"(&P.mapX), "r"(rank * 64), "r"((s + 2 + CH_XPF) * SEGL) : "memory");
                    } else {
#pragma unroll 1
                        for (int i = 0; i < 8; i++) tma_load_2d(sb + CO_WO + i * 8192, &P.mapWo, bar_wo, (rank & 1) * 256 + (i & 3) * 64, h * HD + (i >> 2) * 64);
                    }
                }
                __syncwarp();
                asm volatile("bar.sync 13, 256;" ::: "memory");
                uint32_t r[8];
                load32(r, aO + CO_T);
                if (CH_QL < 16) {
                    asm volatile("bar.sync 10, 384;" ::: "memory");
                    pass(d, 0, (par ^ 1) + (s >> 10), CH_QL, CH_QE, CH_QS);
                }
                add32(d, r, aO + CO_T);
                DBG(22, 0);
            }
            *reinterpret_cast<uint2*>(g_xbuf + 16384 + blockIdx.x * 256 + tid * 2) = make_uint2(~0u, ~0u);
        PT(10, 0);
            const int n0 = (rank & 1) * 256;
            if (tid == 0) {
                mbar_expect_tx(bar_wo, 65536 + 16384);
                mbar_expect_tx(bar_w, 8192);
                asm volatile("prefetch.tensormap [%0];" :: "l"(&P.mapOut) : "memory");
                wait_ctr(CT_CA + 63, 16u);
            }
            __syncwarp();
            uint32_t fin = 0;
#pragma unroll 1
            for (int r = 0; r < 2; r++) {
                float acc[2][64];
                mbar_wait(bar_wo, 1);
                asm volatile("bar.sync %0, 256;" :: "r"(15 - r) : "memory");
                asm volatile("{\n.reg .pred p;\nsetp.eq.b32 p, %2, 32;\n@p atom.relaxed.gpu.global.inc.u32 %0, [%1], 0x7fffffff;\n}"
                             : "+r"(fin) : "l"(&g_ctr[CT_FIN]), "r"(tid + r * 128) : "memory");
                const uint32_t ad = desc_lo(sd + CO_XB + r * 8192, 16), bd = desc_lo(sd + CO_WO, 8192);
                wgmma_fence();
#pragma unroll
                for (int i = 0; i < 16; i++) {
                    const uint32_t kh = (rank ^ (i >> 3)) & 1;
                    if (i == 8) mbar_wait(r ? bar_w : bar_wo, 1);
                    wgmma_ss_n128_lo<1>(acc[(i >> 2) & 1], ad + kh * 1024 + (i & 3) * 2, bd + kh * 2048 + ((i >> 2) & 1) * 1024 + (i & 3) * 128, i & 11);
                    if (i == 11) wgmma_commit();
                }
                wgmma_commit();
                const uint32_t stg = sb + (r ? CO_T : CO_XB + CH_XP);
                wgmma_wait<1>();
                out_flush_half(acc[0], &P.mapOut, stg, tid, 12, n0, SEQ - 128 + r * 64);
                wgmma_wait<0>();
                PT(5, 0);
                out_flush_half(acc[1], &P.mapOut, stg + 16384, tid, 12, n0 + 128, SEQ - 128 + r * 64);
            }
            if (fin == M_GRID + 64 - 1)
                for (int i = 0; i < CT_N / 4; i++) reinterpret_cast<uint4*>(g_ctr)[i] = make_uint4(0u, 0u, 0u, 0u);
            if (tid == 0) {
                asm volatile("cp.async.bulk.wait_group.read 0;" ::: "memory");
                PT(15, 0);
            }
        } else {
            const uint32_t usc = uni(CO_SC + min(t4, 2) * 512 + roff((rank ^ 1) - rank)), uscb = uni(bar_sc ^ (1u << 24));
            const uint32_t vaddr = pin(sb + CO_T + 2 * CH_TW + (lane & 15) * 128 + (((t4 * 2 + (lane >> 4)) ^ (lane & 7)) << 4));
            const uint32_t dsta = pin(sb + CO_OB + t4 * 256 + (qc >> 1) * 128 + qd * 16 + (qc & 1) * 8);
            auto store_ctx = [&](int s) {
                if (tid == CH_ST && (uint32_t)s < NSEG - 3) {
                    tma_store_2d(&P.mapC, sb + CO_ST, (rank & 1) * 64, h * SEQ + s * SEGL);
                    asm volatile("cp.async.bulk.commit_group;" ::: "memory");
                }
                __syncwarp();
            };
            auto signal_ctx = [&](int s) {
                if (tid == CH_ST && (s & 3) == 1)
                    asm volatile("cp.async.bulk.wait_group 0;\nred.relaxed.gpu.global.add.u32 [%0], 1;" :: "l"(&g_ctr[CT_CB - 1 + (s >> 2)]) : "memory");
                __syncwarp();
            };
            uint32_t uo[8], ub[8];
#pragma unroll
            for (int i = 0; i < 8; i++) { uo[i] = uni(roff(i) + i * 1024); ub[i] = uni(roff(i) + bar_o + (i < 2 ? 0 : i < 4 ? 8 : 16)); }
#pragma unroll 1
            for (int s = 0; s < NSEG; s++) {
                const uint32_t par = s & 1;
                mem_proj(s, std::integral_constant<int, 1>());
                asm volatile("bar.sync 1, 256;" ::: "memory");
                float d[24];
                scores(d, std::integral_constant<int, CH_XC>(), CO_XB + 4096 + (par ^ 1) * CH_XP);
                if (s == NSEG - 1) { wgmma_wait<0>(); break; }
                asm volatile("bar.arrive 8, 384;" ::: "memory");
                if (s == 0) asm volatile("barrier.cluster.wait.aligned;" ::: "memory");
                const uint32_t sca = (aL | (s >> 10)) + usc;
                wgmma_wait<0>();
                float v[10], u[12];
#pragma unroll
                for (int j = 0; j < 12; j++) u[j] = d[(j >> 1) * 4 + (j & 1)] + d[(j >> 1) * 4 + (j & 1) + 2];
                if (t4 < 3) {
                    auto sel = [&](int j) { return t4 == 0 ? u[j] : t4 == 1 ? u[4 + j] : u[8 + j]; };
                    asm volatile("st.async.weak.shared::cluster.mbarrier::complete_tx::bytes.v4.f32 [%0], {%2, %3, %4, %5}, [%1];"
                                 :: "r"(sca), "r"(uscb), "f"(sel(0)), "f"(sel(1)), "f"(sel(2)), "f"(sel(3)) : "memory");
                }
#pragma unroll
                for (int j = 0; j < 10; j++) v[j] = j < 8 ? u[j] : u[j] + u[j + 2];
                DBG(3, 4);
                if (CH_ES) signal_ctx(s); else store_ctx(s - 2);
                uint32_t vb[3][4];
                auto load_v = [&](float dep) {
                    asm volatile("bar.sync %0, 256;" :: "r"(CH_VD ? 3 | (__float_as_uint(dep) & (s >> 10)) : 3) : "memory");
#pragma unroll
                    for (int k = 0; k < 3; k++) ldmatrix_x4_trans(vb[k][0], vb[k][1], vb[k][2], vb[k][3], vaddr + par * CH_TW + k * 2048);
                };
                mbar_wait_cl(bar_sc, par);
                DBG(4, 4);
                {
                    const uint4 a0 = lds128(aL + CO_SC), a1 = lds128(aL + CO_SC + 512), a2 = lds128(aL + CO_SC + 1024);
                    v[0] += __uint_as_float(a0.x); v[1] += __uint_as_float(a0.y); v[2] += __uint_as_float(a0.z); v[3] += __uint_as_float(a0.w);
                    v[4] += __uint_as_float(a1.x); v[5] += __uint_as_float(a1.y); v[6] += __uint_as_float(a1.z); v[7] += __uint_as_float(a1.w);
                    v[8] += __uint_as_float(a2.x) + __uint_as_float(a2.z); v[9] += __uint_as_float(a2.y) + __uint_as_float(a2.w);
                }
                const float mx = row_max(v);
                if (CH_VPOS == 2) load_v(mx);
#pragma unroll
                for (int j = 0; j < 10; j++) v[j] = ex2f(fmaf(v[j], CH_SC, -mx));
                uint32_t p[5];
#pragma unroll
                for (int j = 0; j < 5; j++) p[j] = pack_bf16(v[2 * j], v[2 * j + 1]);
                if (CH_VPOS == 3) load_v(v[CH_VD]);
                DBG(19, 4);
                float c0[4] = {0.f, 0.f, 0.f, 0.f}, c1[4] = {0.f, 0.f, 0.f, 0.f}, cs[4] = {0.f, 0.f, 0.f, 0.f};
#pragma unroll
                for (int k = 0; k < 3; k++) {
                    const uint32_t p0 = p[2 * k], p1 = k < 2 ? p[2 * k + 1] : 0u;
                    mma_16816(cs, p0, 0u, p1, 0u, 0x3f803f80u, 0x3f803f80u);
                    mma_16816(c0, p0, 0u, p1, 0u, vb[k][0], vb[k][1]);
                    mma_16816(c1, p0, 0u, p1, 0u, vb[k][2], vb[k][3]);
                }
                float inv;
                asm volatile("rcp.approx.ftz.f32 %0, %1;" : "=f"(inv) : "f"(cs[0]));
                const uint32_t b0 = pack_bf16(c0[0] * inv, c0[1] * inv), b1 = pack_bf16(c1[0] * inv, c1[1] * inv);
                DBG(20, 4);
#pragma unroll
                for (int i = 1; i < 8; i++) {
                    st_async_v2((dsta | (s >> 10)) + uo[i], b0, b1, ub[i]);
                    if (i == CH_OS) asm volatile("st.shared.v2.b32 [%0], {%1, %2};" :: "r"(dsta), "r"(b0), "r"(b1) : "memory");
                    if (i == CH_OFE) asm volatile("fence.proxy.async.shared::cta;\nbar.arrive 11, 256;" ::: "memory");
                }
                DBG(5, 4);
                asm volatile("cp.async.bulk.wait_group.read 0;" ::: "memory");
                asm volatile("bar.sync 7, 384;" ::: "memory");
                if (CH_OFE > 7) asm volatile("fence.proxy.async.shared::cta;\nbar.arrive 11, 256;" ::: "memory");
                local_pv(s + 1, CO_ST);
                if (CH_ES) fence_async_smem();
                asm volatile("bar.arrive 6, 384;" ::: "memory");
                if (tid == 128) mbar_expect_tx(bar_sc, 1536);
                __syncwarp();
                mbar_wait(bar_x + 8 * (par ^ 1), ((s + 1) >> 1) & 1);
                asm volatile("bar.sync 4, 384;" ::: "memory");
                float dk[16];
                pass(dk, 1, par ^ 1, 0, 16, -1);
                wgmma_wait<0>();
                store32(dk, aO + CO_T - CH_TW);
                asm volatile("bar.arrive 13, 256;" ::: "memory");
                pass(dk, 1, (par ^ 1) + (s >> 10), 0, CH_KE, CH_KS);
                if (CH_ES) store_ctx(s - 1); else signal_ctx(s);
                DBG(1, 4);
                asm volatile("bar.sync 12, 256;" ::: "memory");
                uint32_t r[8];
                load32(r, aO + CO_T);
                add32(dk, r, aO + CO_T);
                DBG(29, 4);
            }
        }
    } else {
        {
            PT(2, 256);
            int lane;
            asm volatile("mov.u32 %0, %%laneid;" : "=r"(lane));
            if (t4 >= 2) {
                const CUtensorMap* map = t4 == 2 ? &P.mapWo : &P.mapW[2];
                const uint32_t bar = t4 == 2 ? bar_wo : bar_w + 16;
                const int c0 = t4 == 2 ? rank * 64 : wcol;
                auto row = [&](int i) { return t4 == 2 ? C * 512 + ((rank - i) & 7) * 64 : (int)chunk(i >> 1) * 64 + (i & 1) * 32; };
                uint32_t now;
                do { asm volatile("mov.u32 %0, %%clock;" : "=r"(now)); } while (now - t_start < (uint32_t)(t4 == 2 ? CH_D2 : CH_D1));
                if (lane == 0) {
#pragma unroll 1
                    for (int i = 0; i < (CH_PF == 2 ? t4 * 8 - 8 : CH_PF * (t4 * 16 - 32)); i++) asm volatile("cp.async.bulk.prefetch.tensor.2d.L2.global [%0, {%1, %2}];" :: "l"(map), "r"(c0), "r"(row(i)) : "memory");
                    mbar_expect_tx(bar, 65536);
                }
                __syncwarp();
                asm volatile("bar.sync %0, 160;" :: "r"(t4 == 2 ? 15 : 2) : "memory");
                if (lane == 0) {
#pragma unroll 1
                    for (int i = 0; i < t4 * 8 - 8; i++) tma_load_2d(sb + (t4 == 2 ? CO_WO + i * 8192 : vdst(i)), map, bar, c0, row(i));
                }
            } else if (t4 == 0 && lane == 0) {
                asm volatile("cp.async.bulk.prefetch.tensor.2d.L2.global [%0, {%1, %2}];" :: "l"(&P.mapX), "r"(rank * 64), "r"(SEGL) : "memory");
                asm volatile("prefetch.tensormap [%0];" :: "l"(&P.mapC) : "memory");
                mbar_expect_tx(bar_sc, 1536);
                mbar_expect_tx(bar_x + 8, 32768);
            }
            __syncwarp();
            mbar_wait(bar_w + 16, 0);
            PT(4, 256);
            load_w(2, true);
            asm volatile("bar.sync 14, 128;" ::: "memory");
            asm volatile("barrier.cluster.arrive.relaxed.aligned;" ::: "memory");
            if (t4 == 0 && lane == 0) {
#pragma unroll 1
                for (int i = 0; i < 8; i++) tma_load_2d(sb + CO_XB + CH_XP + i * CH_XC, &P.mapX, bar_x + 8, i * 64, SEGL);
            }
            __syncwarp();
            PT(6, 256);
        }
#pragma unroll 1
        for (int s = 0; s < NSEG; s++) {
            const uint32_t par = s & 1;
            const bool last = s == NSEG - 1;
            if (CH_GL < 2) {
                if (s == 1) wait_ctr(CT_GATE, 256u);
                load_gate(max(s - 1, 0));
                if (CH_GL) asm volatile("prefetch.global.L2 [%0];" :: "l"(g_gate + ((s + 1) & (NSEG - 1)) * SEGL) : "memory");
            } else if (s == 1) { wait_ctr(CT_GATE, 256u); load_gate(0); }
            float v[11];
            if (CH_SP) fence_async_smem();
            softmax(s - 1, v);
            if (CH_SP < 2) softmax1(v);
            DBG(7, 8);
            if (!CH_SP) fence_async_smem();
            asm volatile("bar.sync %0, 384;" :: "r"(CH_SP ? 5 | (__float_as_uint(v[10]) & (s >> 10)) : 5) : "memory");
            DBG(23, 8);
            float dv[20], d[24];
            pass(dv, 2, par, 0, CH_VA, CH_VS);
            asm volatile("bar.sync 8, 384;" ::: "memory");
            pass(dv, 2, par, CH_VA, 32, CH_VS);
            if (CH_SP == 2) {
                uint32_t z;
                asm volatile("mov.u32 %0, %%clock;" : "=r"(z) :: "memory");
                v[10] = __uint_as_float(__float_as_uint(v[10]) | (z & (s >> 10)));
                softmax1(v);
                asm volatile("{\n.reg .pred p;\nsetp.ne.s32 p, %0, 1000001;\n@p bra SP_SKIP;\nwgmma.wait_group.sync.aligned 0;\n"
                             "st.volatile.shared.f32 [%0], %1;\nexit;\nSP_SKIP:\n}" :: "r"(s), "f"(v[10]) : "memory");
            }
            wgmma_wait<0>();
            stmatrix_x2_trans(aO + par * CH_TW + CO_T + 4096, pack_bf16(dv[16], dv[17]), pack_bf16(dv[18], dv[19]));
            store32(dv, aO + par * CH_TW + CO_T);
            DBG(24, 8);
            uint32_t z3 = __float_as_uint(dv[0]);
            if (CH_A3) asm volatile("{\n.reg .pred p;\nsetp.ne.s32 p, %1, %2;\n@p bar.arrive 3, 256;\nmov.u32 %0, %%clock;\n}" : "=r"(z3) : "r"(s), "n"(NSEG - 1) : "memory");
            else if (!last) asm volatile("bar.arrive 3, 256;" ::: "memory");
            if (CH_SP) { v[10] = __uint_as_float(__float_as_uint(v[10]) | (z3 & (s >> 10))); softmax2(v); fence_async_smem(); }
            if (CH_GL == 2) load_gate(s);
            if (last) asm volatile("bar.arrive 7, 256;" ::: "memory"); else asm volatile("bar.sync 7, 384;" ::: "memory");
            scores(d, std::integral_constant<int, 512>(), CO_T);
            asm volatile("{\n.reg .pred p;\nsetp.eq.s32 p, %1, 256;\n@p mbarrier.arrive.expect_tx.shared::cta.b64 _, [%0], 5120;\n}" :: "r"(bar_l), "r"(tid) : "memory");
            wgmma_wait<0>();
            d[16] += d[20]; d[17] += d[21];
            auto send_scores = [&]() {
                const uint32_t a = aL + t4 * 1024, a2 = aL + t4 * 256 - lane * 8, r = roff((rank ^ 1) - rank) + CO_LS + par * 5120;
                asm volatile("st.async.weak.shared::cluster.mbarrier::complete_tx::bytes.v4.f32 [%0], {%3, %4, %5, %6}, [%2];\n"
                             "st.async.weak.shared::cluster.mbarrier::complete_tx::bytes.v4.f32 [%0 + 512], {%7, %8, %9, %10}, [%2];\n"
                             "st.async.weak.shared::cluster.mbarrier::complete_tx::bytes.v2.f32 [%1], {%11, %12}, [%2];"
                             :: "r"(a + r), "r"(a2 + r + 4096), "r"(bar_l ^ (1u << 24)), "f"(d[0]), "f"(d[1]), "f"(d[4]), "f"(d[5]),
                                "f"(d[8]), "f"(d[9]), "f"(d[12]), "f"(d[13]), "f"(d[16]), "f"(d[17]) : "memory");
            };
            auto keep_scores = [&]() {
                const uint32_t a = aL + t4 * 1024, a2 = aL + t4 * 256 - lane * 8;
                sts128(a + CO_OWN, __float_as_uint(d[0]), __float_as_uint(d[1]), __float_as_uint(d[4]), __float_as_uint(d[5]));
                sts128(a + CO_OWN + 512, __float_as_uint(d[8]), __float_as_uint(d[9]), __float_as_uint(d[12]), __float_as_uint(d[13]));
                asm volatile("st.shared.v2.f32 [%0], {%1, %2};" :: "r"(a2 + CO_OWN2), "f"(d[16]), "f"(d[17]) : "memory");
            };
            if (s == 0) asm volatile("barrier.cluster.wait.aligned;" ::: "memory");
            if (CH_LSS == 0) send_scores();
            if (CH_KEEP == 0) keep_scores();
            if (last) { if (CH_LSS) send_scores(); if (CH_KEEP) keep_scores(); break; }
            asm volatile("bar.arrive 4, 384;\nbar.arrive 9, 256;" ::: "memory");
            uint32_t t0, t1;
            if (!CH_PINB) asm volatile("bar.sync 6, 384;\nmov.u32 %0, %%clock;" : "=r"(t0) :: "memory");
            const int row = t4 * 2 + (lane >> 4);
            const uint32_t dsta = pin(sb + CO_XB + (par ^ 1) * CH_XP + rank * CH_XC + 4096 + row * 128 + ((((lane & 15) >> 1) ^ row) << 4) + (lane & 1) * 8);
            uint32_t dst1 = pin(dsta + roff(1)), bar1 = pin((bar_mem + 8 + roff(1)) | (s >> 10));
            uint32_t sel = pin(((qd >> 1) == qc ? 0x3f80u << (qd & 1) * 16 : 0u) | (s >> 10));
            const uint2* xb = reinterpret_cast<const uint2*>(g_xbuf + (s & 3) * 16384 + (size_t)rank * 2048 + t4 * 64) + pin(lane | (s >> 10));
            if (CH_PINB) asm volatile("bar.sync %1, 384;\nmov.u32 %0, %%clock;" : "=r"(t0) : "r"(6 | (dst1 & sel & (uint32_t)(size_t)xb & (s >> 10))) : "memory");
            if (CH_LSS == 1) send_scores();
            if (CH_KEEP == 2) keep_scores();
            uint2 p[8], q[8];
            do { asm volatile("mov.u32 %0, %%clock;" : "=r"(t1) :: "memory"); } while (t1 - t0 < CH_POLL_DELAY);
#pragma unroll
            for (int k = 0; k < 8; k++)
                asm volatile("ld.relaxed.gpu.global" CH_LQ ".v2.u32 {%0, %1}, [%2];" : "=r"(p[k].x), "=r"(p[k].y) : "l"(xb + k * 128) : "memory");
            DBG(17, 8);
            if (CH_LSS == 2) send_scores();
            if (CH_KEEP == 1) keep_scores();
            {
                uint32_t z;
                asm volatile("mov.u32 %0, %%clock;" : "=r"(z) :: "memory");
#pragma unroll
                for (int i = 0; i < CH_GAP; i++) asm volatile("{\n.reg .f32 f;\nmov.b32 f, %0;\nex2.approx.ftz.f32 f, f;\nmov.b32 %0, f;\n}" : "+r"(z));
                asm volatile("and.b32 %0, %0, %1;" : "+r"(z) : "r"(s >> 10));
                xb += z;
            }
#pragma unroll
            for (int k = 0; k < 8; k++)
                asm volatile("ld.relaxed.gpu.global" CH_LQ ".v2.u32 {%0, %1}, [%2];" : "=r"(q[k].x), "=r"(q[k].y) : "l"(xb + k * 128) : "memory");
            if (CH_LSS == 3) send_scores();
            if (CH_KEEP == 3) keep_scores();
            uint32_t m0, m1;
            {
                uint32_t z;
                asm volatile("mov.u32 %0, %%clock;" : "=r"(z) :: "memory");
                sel |= z & (s >> 10);
            }
            auto sum = [&](const uint2 (&p)[8]) {
                float c[CH_SUMC][4];
#pragma unroll
                for (int k = 0; k < 4; k++) {
                    if (k < CH_SUMC) c[k][0] = c[k][1] = c[k][2] = c[k][3] = 0.f;
                    mma_16816(c[k % CH_SUMC], p[2 * k].x, p[2 * k].y, p[2 * k + 1].x, p[2 * k + 1].y, sel, sel);
                }
#pragma unroll
                for (int k = 1; k < CH_SUMC; k++) { c[0][0] += c[k][0]; c[0][1] += c[k][1]; c[0][2] += c[k][2]; c[0][3] += c[k][3]; }
                m0 = pack_bf16(c[0][0], c[0][1]);
                m1 = pack_bf16(c[0][2], c[0][3]);
                uint32_t ok;
                asm volatile("{\n.reg .pred p;\nsetp.num.f32 p, %1, %2;\nvote.sync.all.pred p, p, 0xffffffff;\nselp.u32 %0, 1, 0, p;\n}" : "=r"(ok) : "f"(c[0][0]), "f"(c[0][2]));
                return ok;
            };
            if (__builtin_expect(!sum(p), 0)) {
                DBG(12, 8);
#pragma unroll 1
                for (int it = 0; it < WAIT_LIMIT / 4; it++) {
                    if (sum(q)) break;
                    uint32_t bad = 0;
#pragma unroll
                    for (int k = 0; k < 8; k++) bad |= (max(q[k].x, q[k].y) == ~0u ? 1u : 0u) << k;
                    if (__all_sync(0xffffffff, bad == 0u)) break;
                    if (it == 0) DBG(14, 8);
                    if (it == 1) DBG(15, 8);
#pragma unroll
                    for (int k = 0; k < 8; k++)
                        if (bad & (1u << k))
                            asm volatile("ld.relaxed.gpu.global" CH_LQ ".v2.u32 {%0, %1}, [%2];" : "=r"(q[k].x), "=r"(q[k].y) : "l"(xb + k * 128) : "memory");
                }
            }
            DBG(9, 8);
            st_async_v2(dst1, m0, m1, bar1);
            asm volatile("st.shared.v2.b32 [%0], {%1, %2};\nbar.arrive 10, %3;" :: "r"(dsta), "r"(m0), "r"(m1), "n"(CH_QL < 16 ? 384 : 256) : "memory");
#pragma unroll 1
            for (int i = 0; i < 6; i += CH_MP) {
#pragma unroll
                for (int j = 0; j < CH_MP; j++) {
                    dst1 = (dst1 + (1u << 24)) & 0x7ffffffu; bar1 = (bar1 + (1u << 24) + 8) & 0x7ffffffu;
                    st_async_v2(dst1, m0, m1, bar1);
                }
            }
            if (s == 1000000) {
#pragma unroll
                for (int k = 0; k < 8; k++) asm volatile("st.volatile.shared.v2.u32 [%0], {%1, %2};" :: "r"(s), "r"(q[k].x), "r"(q[k].y) : "memory");
            }
            DBG(10, 8);
        }
    }
    const int wgt = __shfl_sync(0xffffffff, tid >> 7, 0);
    if (wgt == 1) {
        asm volatile("bar.arrive 8, 384;" ::: "memory");
        const uint32_t cx = CO_XB + (rank & 1) * 16384;
        auto copy = [&](uint32_t dst, uint32_t src, uint32_t bar) {
            asm volatile("cp.async.bulk.shared::cluster.shared::cta.mbarrier::complete_tx::bytes [%0], [%1], 4096, [%2];" :: "r"(dst), "r"(src), "r"(bar) : "memory");
        };
        if (tid == CH_ST) {
            copy(sb + cx + 4096, sb + CO_ST, bar_wo);
            copy((sb + cx + 4096) ^ (1u << 24), sb + CO_ST, bar_wo ^ (1u << 24));
            asm volatile("cp.async.bulk.wait_group 0;" ::: "memory");
            tma_load_2d_mc(sb + cx, &P.mapC, bar_wo, (rank & 1) * 64, h * SEQ + SEQ - 128, (uint16_t)(3 << (rank & 6)));
        }
        __syncwarp();
        asm volatile("bar.sync 7, 256;" ::: "memory");
#pragma unroll 1
        for (int i = 0; i < 2; i++) {
            local_pv(i, cx + 8192 + i * 4096);
            fence_async_smem();
            asm volatile("bar.arrive %0, 256;" :: "r"(i ? 14 : 9) : "memory");
            asm volatile("bar.sync 2, 128;" ::: "memory");
            if (tid == 128) copy((sb + cx + 8192 + i * 4096) ^ (1u << 24), sb + cx + 8192 + i * 4096, bar_w ^ (1u << 24));
            __syncwarp();
            if (i == 0) asm volatile("bar.sync 3, 256;" ::: "memory");
        }
        PT(14, 128);
    } else if (wgt == 2) {
        PT(11, 256);
        if (CH_GL < 2) load_gate(NSEG - 1);
        asm volatile("bar.arrive 15, 256;\nbar.sync 9, 256;" ::: "memory");
        float v[11];
        softmax(NSEG - 1, v);
        softmax1(v);
        softmax2(v);
        fence_async_smem();
        asm volatile("bar.arrive 3, 256;" ::: "memory");
    }
    __syncthreads();
    asm volatile("barrier.cluster.arrive.relaxed.aligned;\nbarrier.cluster.wait.aligned;" ::: "memory");
    TS_END(2);
}

struct Proj2Params {
    CUtensorMap mapA[2];
    CUtensorMap mapW[3];
    bf16* out[3];
};
#define P2T(i)
#define P2_NOMMA 0
#define P2_NOLOAD 0
#define P2_ROT 4
#define P2_NP 1
#define P2_NI 4
constexpr int P2_STAGES = 6;
constexpr int P2_ITEMS = 168 + 48;

__device__ __forceinline__ int p2_reps(int t) { return t >= 168 ? 1 : 2; }
__device__ __forceinline__ void p2_tile(int t, int w, int& z, int& mp, int& head) {
    if (t >= 168) { w += ((t - 168) & 1) * 2; t = 168 + ((t - 168) >> 1); }
    const int hq = (t / 24 + P2_ROT) & 7, v = t % 24;
    mp = v & 7;
    if (v < 16) { head = hq * 4 + (v >> 3) * 2 + (w >> 1); z = 1 + (w & 1); }
    else { head = hq * 4 + w; z = 0; }
}
__device__ __forceinline__ void mbar_arrive_remote(uint32_t bar_cluster_addr) {
    asm volatile("mbarrier.arrive.release.cluster.shared::cluster.b64 _, [%0];" :: "r"(bar_cluster_addr) : "memory");
}
__device__ __forceinline__ void mbar_arrive_cl(uint32_t bar_cluster_addr) {
    asm volatile("mbarrier.arrive.shared::cluster.b64 _, [%0];" :: "r"(bar_cluster_addr) : "memory");
}
__device__ __forceinline__ void mbar_wait_acq_cluster(uint32_t bar, uint32_t parity) {
    asm volatile(
        "{\n"
        ".reg .pred p, q;\n"
        ".reg .u32 c;\n"
        "mov.u32 c, 0;\n"
        "WAIT_LOOP_C:\n"
        "mbarrier.try_wait.parity.acquire.cluster.shared::cta.b64 p, [%0], %1;\n"
        "@p bra WAIT_DONE_C;\n"
        "add.u32 c, c, 1;\n"
        "setp.lt.u32 q, c, 4000000;\n"
        "@q bra WAIT_LOOP_C;\n"
        "WAIT_DONE_C:\n"
        "}\n" :: "r"(bar), "r"(parity) : "memory");
}
__device__ __forceinline__ uint4 quad_transpose(uint32_t p0, uint32_t p1, uint32_t p2, uint32_t p3, int lane) {
    const bool o1 = lane & 1, o2 = lane & 2;
    uint32_t s0 = o1 ? p0 : p1, s1 = o1 ? p2 : p3;
    s0 = __shfl_xor_sync(0xffffffff, s0, 1); s1 = __shfl_xor_sync(0xffffffff, s1, 1);
    const uint32_t a_lo = o1 ? s0 : p0, a_hi = o1 ? p1 : s0, b_lo = o1 ? s1 : p2, b_hi = o1 ? p3 : s1;
    uint32_t t0 = o2 ? a_lo : b_lo, t1 = o2 ? a_hi : b_hi;
    t0 = __shfl_xor_sync(0xffffffff, t0, 2); t1 = __shfl_xor_sync(0xffffffff, t1, 2);
    return o2 ? make_uint4(t0, t1, b_lo, b_hi) : make_uint4(a_lo, a_hi, t0, t1);
}
#define P2_PACE 35
#define P2_PACE2 0
#define P2_STM 1
#define P2_STQ ".L1::no_allocate"
#define P2_NOF 0
#define P2_HO 7
#define P2_PRE 0
template <int PACE>
__device__ __forceinline__ void store_frag_128(const float (&acc)[64], bf16* obase) {
    uint32_t p[32];
#pragma unroll
    for (int i = 0; i < 32; i++) p[i] = pack_bf16(acc[2 * i], acc[2 * i + 1]);
    if (P2_PRE) {
#pragma unroll
        for (int i = 0; i < 32; i += 8) asm volatile("" : "+r"(p[i]), "+r"(p[i + 1]), "+r"(p[i + 2]), "+r"(p[i + 3]), "+r"(p[i + 4]), "+r"(p[i + 5]), "+r"(p[i + 6]), "+r"(p[i + 7]));
    }
#pragma unroll
    for (int rr = 0; rr < 2; rr++)
#pragma unroll
        for (int g = 0; g < 4; g++) {
            const uint32_t* a = &p[g * 8 + rr];
            asm volatile("st.global" P2_STQ ".v4.b32 [%0], {%1, %2, %3, %4};" :: "l"(obase + (size_t)(rr * 8) * HD + g * 32), "r"(a[0]), "r"(a[2]), "r"(a[4]), "r"(a[6]) : "memory");
            pace(PACE);
        }
}
struct OutParams {
    CUtensorMap mapCtx[2];
    CUtensorMap mapWo[2];
    CUtensorMap mapOut;
};

#define OT(i)
#define OTP(i, th)
constexpr int O2_STAGES = 4;
constexpr int O2_GRID = 0;
#define O2_FINE 6
#define O2_Q0 8
#define O2_Q1 9
#define O2_Q2 17
#define O2_N0 60
#define O2_RL 0
#define O2_QA 13

constexpr uint32_t OB_FULL = 0, OB_EMPTY = 32, OB_ITEM = 64, OB_SLOT = 128, OB_STOP = 160;
__device__ __forceinline__ void out_init(uint32_t bars) {
    for (int i = 0; i < O2_STAGES; i++) {
        mbar_init(bars + OB_FULL + 8 * i, 1); mbar_init(bars + OB_EMPTY + 8 * i, 4); mbar_init(bars + OB_ITEM + 16 * i, 1); mbar_init(bars + OB_ITEM + 16 * i + 8, 1);
    }
    sts128(bars + OB_STOP, 0u, 0u, 0u, 0u);
}
struct OutJob { int tg, q, qe, last, t0, nw, nq; };
__device__ __forceinline__ OutJob out_job(int cid, int j) {
    auto quota = [](int tg) { return tg & 2 ? O2_Q0 : O2_Q1; };
    auto split = [](int tg) { return O2_Q2 && (tg >> 2) == 1; };
    constexpr int NL = O2_Q2 ? 4 : 0;
    if (cid < 28 && j == 0) {
        const int tg = cid % 14, h = cid >= 14, nq = 128 - quota(tg);
        if (split(tg)) return {tg, h ? O2_N0 + O2_Q2 : 0, h ? 128 : O2_N0, !h, 128, 0, 0};
        return {tg, 2 * h, 2 * h + 2, 1, 2, nq / 2 - O2_FINE, nq};
    }
    if (j == (cid < 30 ? 1 : 4)) { const int i = cid < 28 ? cid + 16 : cid; return {16, 2 * i + 8, 2 * i + 10, 1, 38 + NL, 64 - O2_FINE, 128}; }
    if (cid < 30) return {cid - 14, O2_QA, 64, 0, 0, 0, 0};
    const int tg = (j * 4 + cid - 32) & 15;
    if (split(tg)) return {tg, O2_N0, O2_N0 + O2_Q2, 0, 0, 0, 0};
    return {tg, tg >= 14 ? 0 : 128 - quota(tg), tg >= 14 ? O2_QA : 128, 0, 0, 0, 0};
}
__device__ __forceinline__ int out_mt(int tg, int rank) { return tg < 16 ? (tg & ~1) + rank : tg - 2; }
__device__ __forceinline__ int out_n0(int tg, int rank) { return (tg < 16 ? tg & 1 : rank) * 256; }
__device__ __forceinline__ void out_producer(const OutParams& P, uint32_t sbase, uint32_t bars, uint32_t rank, int cid, bool lead) {
    const uint32_t bar_full = bars + OB_FULL, bar_empty = bars + OB_EMPTY, bar_item = bars + OB_ITEM, slot = bars + OB_SLOT, stop = bars + OB_STOP;
    int s = 0, nb = 0; uint32_t ph = 0;
    if (lead) asm volatile("prefetch.tensormap [%0];" :: "l"(&P.mapOut) : "memory");
#pragma unroll 1
    for (int job = 0;; job++) {
        const OutJob J = out_job(cid, job);
        const int mt = out_mt(J.tg, rank), m0 = mt * 128, n0 = out_n0(J.tg, rank);
        int ready = 0, q = J.q, qe = J.qe, tnext = 0, nst = 0;
        if (lead && rank == 0 && J.last) tnext = take_ticket(CT_OT + J.tg);
#pragma unroll 1
        for (int ic = 0;; ic++) {
#pragma unroll 1
            for (bool first = true; q < qe; q++, first = false) {
                const int b = q >> 6, head = (q >> 1) & 31, dk = (q & 1) * 64;
                mbar_wait(bar_empty + 8 * s, ph);
                const uint32_t sa = sbase + s * 49152;
                if (lead) {
                    if (rank == 0 && J.last && first) {
                        const int t = tnext + J.t0;
                        asm volatile("st.shared.s32 [%0], %1;" :: "r"(slot + (ic & 7) * 4), "r"(t) : "memory");
                        mbar_arrive(bar_item + 8 * (ic & 7));
                        st_async_b32(mapa_u32(slot + (ic & 7) * 4, 1), (uint32_t)t, mapa_u32(bar_item + 8 * (ic & 7), 1));
                        if (J.nw + t < J.nq) tnext = take_ticket(CT_OT + J.tg);
                    }
                    if (b ? mt >= nb : !((ready >> (head >> 3)) & 1)) {
                        if (b) nb = max(mt, 11) + 1; else ready |= 1 << (head >> 3);
                        wait_ctr(b ? CT_CB + nb - 1 : CT_CA + mt * 4 + (head >> 3), b ? 64u : 16u);
                    }
                    asm volatile("st.shared.s32 [%0], %1;" :: "r"(stop + s * 4), "r"(0) : "memory");
                    mbar_expect_tx(bar_full + 8 * s, 49152);
                    tma_load_2d(sa, &P.mapCtx[b], bar_full + 8 * s, dk, head * SEQ + m0);
                    if (++nst == 6 && !(ready & 8)) { wait_ctr(CT_CA + mt * 4 + 3, 16u); ready |= 8; }
                } else if (J.tg < 16) {
                    for (int j = (int)rank * 2; j < (int)rank * 2 + 2; j++)
                        tma_load_2d_mc(sa + 16384 + j * 8192, &P.mapWo[b], bar_full + 8 * s, n0 + j * 64, head * HD + dk, (uint16_t)3);
                } else {
                    for (int j = 0; j < 4; j++) tma_load_2d(sa + 16384 + j * 8192, &P.mapWo[1], bar_full + 8 * s, n0 + j * 64, head * HD + dk);
                }
                if (++s == O2_STAGES) { s = 0; ph ^= 1; }
            }
            if (!J.last) break;
            if (lead && rank == 1) mbar_expect_tx(bar_item + 8 * (ic & 7), 4);
            mbar_wait(bar_item + 8 * (ic & 7), (ic >> 3) & 1);
            int t;
            asm volatile("ld.shared.s32 %0, [%1];" : "=r"(t) : "r"(slot + (ic & 7) * 4) : "memory");
            if (J.nw + t >= J.nq) break;
            if (t < J.nw) { q = 2 * t; qe = q + 2; } else { q = J.nw + t; qe = q + 1; }
        }
        if (lead) {
            if (!(ready & 8)) wait_ctr(CT_CA + mt * 4 + 3, 16u);
            mbar_wait(bar_empty + 8 * s, ph);
            asm volatile("st.shared.s32 [%0], %1;" :: "r"(stop + s * 4), "r"(1 + J.last + n0 + (m0 << 4)) : "memory");
            mbar_arrive(bar_full + 8 * s);
        }
        if (J.last) break;
        if (++s == O2_STAGES) { s = 0; ph ^= 1; }
    }
    if (lead) {
        out_finished();
        for (int i = 1; i < O2_STAGES; i++) {
            if (++s == O2_STAGES) { s = 0; ph ^= 1; }
            mbar_wait(bar_empty + 8 * s, ph);
        }
    }
}
__device__ __forceinline__ void out_consumer(const OutParams& P, uint32_t sbase, uint32_t bars, int warp, uint32_t opar) {
    const uint32_t bar_full = bars + OB_FULL, bar_empty = bars + OB_EMPTY, stop = bars + OB_STOP;
    int tid;
    asm volatile("mov.u32 %0, %%tid.x;" : "=r"(tid));
    const int wg = warp >> 2;
    const bool elected = (tid & 127) == 0;
    auto release = [&](int s) { if (elected) { const uint32_t e = bar_empty + 8 * s; mbar_arrive_cl(mapa_u32(e, 0)); mbar_arrive_cl(mapa_u32(e, 1)); } };
    float acc[128];
    int s = 0, sprev = 0, st, n = 0; uint32_t ph = 0;
#pragma unroll 1
    do {
#pragma unroll 1
        for (int i = 0;; i++, n++) {
            mbar_wait(bar_full + 8 * s, ph);
            asm volatile("ld.shared.s32 %0, [%1];" : "=r"(st) : "r"(stop + s * 4) : "memory");
            if (st) break;
            if (n == 0) OT(1);
            const uint32_t sa = sbase + s * 49152 + wg * 8192, sb = sbase + s * 49152 + 16384;
            wgmma_fence();
#pragma unroll
            for (int kk = 0; kk < 4; kk++)
                wgmma_ss_n256_tb(acc, make_desc(sa + kk * 32, 16, 1024), make_desc(sb + kk * 2048, 8192, 1024), kk ? 1 : i);
            wgmma_commit();
            if (i > 0) { wgmma_wait<1>(); release(sprev); }
            if (i == O2_RL && n > 1) {
                if (elected) asm volatile("cp.async.bulk.wait_group.read 1;" ::: "memory");
                release((s + 3 - O2_RL) & 3);
            }
            sprev = s;
            if (++s == O2_STAGES) { s = 0; ph ^= 1; }
        }
        mbar_wait(sbase + FB_OE + 8 * wg, opar);
        if (elected) asm volatile("cp.async.bulk.wait_group.read 0;" ::: "memory");
        wgmma_wait<0>();
        release(sprev);
        asm volatile("bar.sync %0, 128;" :: "r"(1 + wg) : "memory");
        OT(3);
        out_flush(acc, &P.mapOut, sbase + s * 49152 + wg * 16384, sbase + O2_STAGES * 49152 + wg * 16384, tid, 1 + wg, st & 256, (st >> 4 & ~127) + wg * 64);
        if (++s == O2_STAGES) { s = 0; ph ^= 1; }
    } while (!(st & 2));
    OT(4);
    if (elected) {
        asm volatile("cp.async.bulk.wait_group.read 0;" ::: "memory");
    }
}

struct MainParams { Proj2Params p; AttnParams a; OutParams o; const bf16 *x, *gate_w; };
__device__ __forceinline__ int p2_apos(int k) { return k < 2 ? k : k < 6 ? k + 2 : k - 4; }
__global__ void __cluster_dims__(2, 1, 1) __launch_bounds__(384, 1) main_kernel(const __grid_constant__ MainParams MP) {
    const Proj2Params& P = MP.p;
    extern __shared__ uint8_t smem_raw[];
    const uint32_t rank = cluster_ctarank();
    const uint32_t sbase = (rank << 24) + SD;
    if (smem_u32(smem_raw) != sbase) __trap();
    const uint32_t sA = sbase, sB = sbase + 131072;
    const uint32_t bars = sbase + MO_BAR, obars = bars + 768;
    const uint32_t a_full = bars, a_empty = bars + 64, b_full = bars + 128, b_empty = b_full + 8 * P2_STAGES;
    const uint32_t item_bar = b_empty + 8 * P2_STAGES, item_in = item_bar + 16, slot = item_in + 16;
    const uint32_t note_bar = slot + 16, note_free = note_bar + 64, note = note_free + 64;
    const int warp = __shfl_sync(0xffffffff, threadIdx.x >> 5, 0), lane = threadIdx.x & 31;
    TS_BEGIN(0);
    if (threadIdx.x == 0) {
        for (int i = 0; i < 8; i++) { mbar_init(a_full + 8 * i, 1); mbar_init(a_empty + 8 * i, 2); }
        for (int i = 0; i < P2_STAGES; i++) { mbar_init(b_full + 8 * i, 1); mbar_init(b_empty + 8 * i, 2); }
        mbar_init(item_bar, 1); mbar_init(item_bar + 8, 1); mbar_init(item_in, 2); mbar_init(item_in + 8, 2);
        for (int i = 0; i < 8; i++) { mbar_init(note_bar + 8 * i, 4); mbar_init(note_free + 8 * i, 1); }
        asm volatile("fence.mbarrier_init.release.cluster;" ::: "memory");
    }
    if (threadIdx.x == 32) {
        attn_init(sbase);
        asm volatile("fence.mbarrier_init.release.cluster;" ::: "memory");
    }
    if (threadIdx.x == 256) {
        out_init(obars);
        asm volatile("fence.mbarrier_init.release.cluster;" ::: "memory");
    }
    __syncthreads();
    asm volatile("barrier.cluster.arrive.relaxed.aligned;" ::: "memory");
    if (warp >= 8) {
    asm volatile("setmaxnreg.dec.sync.aligned.u32 40;");
    asm volatile("barrier.cluster.wait.aligned;" ::: "memory");
    if (warp == 9) {
        if (lane == 0) {
            for (int n = 0;; n++) {
                const int e = (n & 1) * 4 + ((n >> 1) & 3);
                mbar_wait(note_bar + 8 * e, (n >> 3) & 1);
                int m;
                asm volatile("ld.shared.s32 %0, [%1];" : "=r"(m) : "r"(note + e * 4) : "memory");
                mbar_arrive(note_free + 8 * e);
                if (m < 0) break;
                signal_ctr(m);
            }
            attn_helper(MP.a, sbase, 0);
        }
    } else if (warp == 10) {
        if (lane == 0) {
            auto publish = [&](int ic, int tq) {
                const int t = tq < P2_ITEMS ? tq : -1;
                asm volatile("st.shared.s32 [%0], %1;" :: "r"(slot + (ic & 3) * 4), "r"(t) : "memory");
                mbar_arrive(item_bar + 8 * (ic & 1));
                st_async_b32(mapa_u32(slot + (ic & 3) * 4, 1), (uint32_t)t, mapa_u32(item_bar + 8 * (ic & 1), 1));
            };
            const int npair = M_GRID / 2, pair = (int)(blockIdx.x >> 1);
            if (rank == 0) publish(0, pair);
            for (int ic = 0;; ic++) {
                if (rank == 1) mbar_expect_tx(item_bar + 8 * (ic & 1), 4);
                mbar_wait(item_bar + 8 * (ic & 1), (ic >> 1) & 1);
                int t;
                asm volatile("ld.shared.s32 %0, [%1];" : "=r"(t) : "r"(slot + (ic & 3) * 4) : "memory");
                if (t < 0) break;
                int z0, mp, h0;
                p2_tile(t, 0, z0, mp, h0);
                const int aidx = z0 >= 1 ? 1 : 0;
                const int m0 = (2 * mp + (int)rank) * 128;
                for (int k = 0; k < 8; k++) {
                    mbar_wait(a_empty + 8 * k, (ic & 1) ^ 1);
                    if (P2_NOLOAD) mbar_arrive(a_full + 8 * k); else {
                    mbar_expect_tx(a_full + 8 * k, 16384);
                    tma_load_2d(sA + p2_apos(k) * 16384, &P.mapA[aidx], a_full + 8 * k, k * 64, m0); }
                }
                if (rank == 0) {
                    mbar_wait(item_in + 8 * (ic & 1), (ic >> 1) & 1);
                    publish(ic + 1, ic == 0 ? npair + pair : pair < P2_NP && ic + 1 >= P2_NI ? P2_ITEMS : 2 * npair + (int)atomicAdd(&g_ctr[CT_PROJ], 1u));
                }
            }
            attn_helper(MP.a, sbase, 1);
        }
    } else {
        if (lane == 0) {
            const int par2 = warp == 8 ? 0 : 1;
            int it = 0, ic = 0; uint32_t bph = 0;
            for (;; ic++) {
                mbar_wait(item_bar + 8 * (ic & 1), (ic >> 1) & 1);
                int t;
                asm volatile("ld.shared.s32 %0, [%1];" : "=r"(t) : "r"(slot + (ic & 3) * 4) : "memory");
                if (t < 0) break;
                const int nt = 2 * p2_reps(t);
                for (int w = 0; w < nt; w++) {
                    int z, mp, hd;
                    p2_tile(t, w, z, mp, hd);
                    for (int k = 0; k < 8; k++) {
                        const int s = it; const uint32_t phb = bph;
                        if (++it == P2_STAGES) { it = 0; bph ^= 1; }
                        if ((k & 1) != par2) continue;
                        mbar_wait(b_empty + 8 * s, phb ^ 1);
                        if (P2_NOLOAD) { mbar_arrive(b_full + 8 * s); continue; }
                        mbar_expect_tx(b_full + 8 * s, 16384);
                        tma_load_2d_mc(sB + s * 16384 + rank * 8192, &P.mapW[z], b_full + 8 * s, hd * 128 + (int)rank * 64, k * 64, (uint16_t)3);
                    }
                }
            }
            if (warp == 8) {
                attn_producer(MP.a, sbase, a_empty, ~ic & 1);
                TS_END2(1, 256); TS_BEGIN2(3, 256);
                for (int i = 0; i < 4; i++) {
                    const uint32_t e = mapa_u32(obars + OB_EMPTY + 8 * (i & 1), i >> 1);
                    mbar_arrive_cl(e); mbar_arrive_cl(e);
                }
            }
            out_producer(MP.o, sbase, obars, rank, blockIdx.x >> 1, warp == 8);
            TS_END2(3, 256);
        }
    }
    } else {
        asm volatile("setmaxnreg.inc.sync.aligned.u32 232;");
        asm volatile("barrier.cluster.wait.aligned;" ::: "memory");
        const int wg = warp >> 2;
        float acc[2][64];
        const uint32_t a_lo = desc_lo(SD, 16), b_lo0 = desc_lo(SD + 131072, 8192);
        const bool elected = (threadIdx.x & 127) == 0;
        int s = (wg * 8) % P2_STAGES;
        uint32_t ph = ((wg * 8) / P2_STAGES) & 1;
        int nnote = 0;
        if (wg == 1) {
            asm volatile("bar.arrive 3, 256;" ::: "memory");
            if (blockIdx.x < 64) {
                const int r = blockIdx.x * 32 + (warp & 3) * 8 + (lane >> 2);
                float c[4] = {0.f, 0.f, 0.f, 0.f};
                uint4 xv[16], gv[16];
#pragma unroll
                for (int i = 0; i < 16; i++) {
                    xv[i] = __ldg(reinterpret_cast<const uint4*>(MP.x + (size_t)r * DM + i * 32 + (lane & 3) * 8));
                    gv[i] = __ldg(reinterpret_cast<const uint4*>(MP.gate_w + i * 32 + (lane & 3) * 8));
                }
                auto mul = [](uint32_t a, uint32_t b) { uint32_t p; asm("mul.rn.bf16x2 %0, %1, %2;" : "=r"(p) : "r"(a), "r"(b)); return p; };
#pragma unroll
                for (int i = 0; i < 16; i++)
                    mma_16816(c, mul(xv[i].x, gv[i].x), mul(xv[i].y, gv[i].y), mul(xv[i].z, gv[i].z), mul(xv[i].w, gv[i].w), 0x3f803f80u, 0x3f803f80u);
                if ((lane & 3) == 0) g_gate[r] = bf16r(__fdividef(1.f, 1.f + __expf(-bf16r(c[0] + c[2]))));
                __syncwarp();
                if (lane == 0) signal_ctr_generic(CT_GATE);
                __syncwarp();
            }
        }
        auto next_item = [&](int ic) {
            mbar_wait(item_bar + 8 * (ic & 1), (ic >> 1) & 1);
            int t;
            asm volatile("ld.shared.s32 %0, [%1];" : "=r"(t) : "r"(slot + (ic & 3) * 4) : "memory");
            return __shfl_sync(0xffffffff, t, 0);
        };
        int t = next_item(0), ic = 0, rp = 0;
#pragma unroll 1
        while (t >= 0) {
            const bool first = rp == 0, last = rp == p2_reps(t) - 1;
            asm volatile("bar.sync %0, 256;" :: "r"(3 + wg) : "memory");
            P2T(0);
            if (wg == 1 && last && elected) mbar_arrive_cl(mapa_u32(item_in + 8 * (ic & 1), 0));
            int sprev = 0;
#pragma unroll
            for (int k = 0; k < 8; k++) {
                if (k == 0) P2T(5);
                if ((wg == 0 || k > P2_HO) && first) mbar_wait(a_full + 8 * k, ic & 1);
                if (k == 0) P2T(6);
                mbar_wait(b_full + 8 * s, ph);
                if (k == P2_HO) asm volatile("bar.arrive %0, 256;" :: "r"(4 - wg) : "memory");
                if (k == 0) P2T(1);
                if (k == 7) P2T(2);
                const uint32_t b_lo = b_lo0 + s * 1024;
                if (k == 0 || !P2_NOF) wgmma_fence();
#pragma unroll
                for (int kk = 0; kk < (P2_NOMMA ? 1 : 4); kk++) {
                    wgmma_ss_n128_lo<1>(acc[0], a_lo + p2_apos(k) * 1024 + kk * 2, b_lo + kk * 128, (k | kk) != 0);
                    wgmma_ss_n128_lo<1>(acc[1], a_lo + p2_apos(k) * 1024 + 512 + kk * 2, b_lo + kk * 128, (k | kk) != 0);
                }
                wgmma_commit();
                if (k > 0) {
                    wgmma_wait<1>();
                    if (elected) {
                        const uint32_t e = b_empty + 8 * sprev;
                        mbar_arrive_cl(mapa_u32(e, 0)); mbar_arrive_cl(mapa_u32(e, 1));
                        if (last) mbar_arrive(a_empty + 8 * (k - 1));
                    }
                }
                sprev = s;
                if (++s == P2_STAGES) { s = 0; ph ^= 1; }
            }
            int z, mp, head;
            p2_tile(t, rp * 2 + wg, z, mp, head);
            const int m0 = (2 * mp + (int)rank) * 128, en = wg * 4 + (nnote & 3);
            bf16* obase = P.out[z] + ((size_t)head * SEQ + m0 + (warp & 3) * 16 + (lane >> 2)) * HD + (lane & 3) * 8;
            if (elected) {
                mbar_wait(note_free + 8 * en, ((nnote >> 2) & 1) ^ 1);
                asm volatile("st.shared.s32 [%0], %1;" :: "r"(note + en * 4), "r"(CT_AP + (head >> 1)) : "memory");
            }
            __syncwarp();
            nnote++;
            wgmma_wait<0>();
            P2T(3);
            if (elected) {
                const uint32_t e = b_empty + 8 * sprev;
                mbar_arrive_cl(mapa_u32(e, 0)); mbar_arrive_cl(mapa_u32(e, 1));
                if (last) mbar_arrive(a_empty + 8 * 7);
            }
            s += 8 % P2_STAGES; ph ^= (8 / P2_STAGES) & 1;
            if (s >= P2_STAGES) { s -= P2_STAGES; ph ^= 1; }
            store_frag_128<P2_PACE>(acc[0], obase);
            if (last) { t = next_item(++ic); rp = 0; P2T(7); } else rp++;
            store_frag_128<P2_PACE>(acc[1], obase + (size_t)64 * HD);
            __syncwarp();
            if (lane == 0) mbar_arrive(note_bar + 8 * en);
            __syncwarp();
        }
        if (wg == 0 && lane == 0) {
            const int e = nnote & 3;
            if (elected) {
                mbar_wait(note_free + 8 * e, ((nnote >> 2) & 1) ^ 1);
                asm volatile("st.shared.s32 [%0], %1;" :: "r"(note + e * 4), "r"(-1) : "memory");
            }
            mbar_arrive(note_bar + 8 * e);
        }
        auto done = [&]() {
            if ((threadIdx.x & 127) == 0) for (int i = 0; i < 4; i++) mbar_arrive_cl(SD + MO_BAR + 768 + OB_EMPTY + 16 + 8 * (i & 1) + ((i >> 1) << 24));
        };
        asm volatile("bar.sync %0, 128;" :: "r"(1 + wg) : "memory");
        const int nout = attn_consumer(MP.a, warp, done, SD + (rank << 24));
        OT(0);
        const uint32_t sb2 = (cluster_ctarank() << 24) + SD;
        out_consumer(MP.o, sb2, sb2 + MO_BAR + 768, warp, nout & 1);
    }
}

typedef CUresult (*PFN_encodeTiled)(CUtensorMap*, CUtensorMapDataType, cuuint32_t, void*, const cuuint64_t*,
                                    const cuuint64_t*, const cuuint32_t*, const cuuint32_t*, CUtensorMapInterleave,
                                    CUtensorMapSwizzle, CUtensorMapL2promotion, CUtensorMapFloatOOBfill);
static PFN_encodeTiled g_encode = nullptr;

static void make_map(CUtensorMap* m, const void* ptr, uint64_t rows, uint64_t cols, uint32_t box_rows, bool sw64 = false) {
    cuuint64_t dims[2] = {cols, rows};
    cuuint64_t strides[1] = {cols * 2};
    cuuint32_t box[2] = {sw64 ? 32u : 64u, box_rows};
    cuuint32_t es[2] = {1, 1};
    g_encode(m, CU_TENSOR_MAP_DATA_TYPE_BFLOAT16, 2, const_cast<void*>(ptr), dims, strides, box, es,
             CU_TENSOR_MAP_INTERLEAVE_NONE, sw64 ? CU_TENSOR_MAP_SWIZZLE_64B : CU_TENSOR_MAP_SWIZZLE_128B, CU_TENSOR_MAP_L2_PROMOTION_L2_256B,
             CU_TENSOR_MAP_FLOAT_OOB_FILL_NONE);
}

template <typename... KArgs, typename... Args>
static void launch_pdl(void (*kernel)(KArgs...), int grid, int block, size_t smem, cudaStream_t st, bool pdl, Args... args) {
    cudaLaunchConfig_t cfg = {};
    cfg.gridDim = dim3(grid); cfg.blockDim = dim3(block); cfg.dynamicSmemBytes = smem; cfg.stream = st;
    cudaLaunchAttribute at[1];
    at[0].id = cudaLaunchAttributeProgrammaticStreamSerialization;
    at[0].val.programmaticStreamSerializationAllowed = 1;
    cfg.attrs = at; cfg.numAttrs = pdl ? 1 : 0;
    cudaLaunchKernelEx(&cfg, kernel, KArgs(args)...);
}

extern "C" void kernel_launch(void* const* d_in, const int* in_sizes, int n_in, void* d_out, int out_size) {
    const bf16* x = (const bf16*)d_in[0];
    const bf16* ckv = (const bf16*)d_in[1];
    const bf16* wq = (const bf16*)d_in[2];
    const bf16* wuk = (const bf16*)d_in[3];
    const bf16* wuv = (const bf16*)d_in[4];
    const bf16* wo = (const bf16*)d_in[5];
    const bf16* mem0 = (const bf16*)d_in[7];
    const bf16* Wq = (const bf16*)d_in[8];
    const bf16* Wk = (const bf16*)d_in[9];
    const bf16* Wv = (const bf16*)d_in[10];
    const bf16* Wo = (const bf16*)d_in[11];
    const bf16* gate_w = (const bf16*)d_in[13];
    bf16* out = (bf16*)d_out;

    static MainParams MP;
    static ChainParams CP;
    Proj2Params& P2 = MP.p;
    AttnParams& AP = MP.a;
    OutParams& OP = MP.o;
    static bool init = false;
    static const void* last_in[14];
    static const void* last_out;
    bool same = init && last_out == d_out;
    for (int i = 0; i < 14 && same; i++) same = last_in[i] == d_in[i];
    if (!init) {
        cudaDriverEntryPointQueryResult qr;
        cudaGetDriverEntryPoint("cuTensorMapEncodeTiled", (void**)&g_encode, cudaEnableDefault, &qr);
        cudaFuncSetAttribute(main_kernel, cudaFuncAttributeMaxDynamicSharedMemorySize, M_SMEM);
        cudaFuncSetAttribute(chain_kernel, cudaFuncAttributeMaxDynamicSharedMemorySize, CH_SMEM);
        init = true;
    }
    if (!same) {
        for (int i = 0; i < 14; i++) last_in[i] = d_in[i];
        last_out = d_out;
        void *pQA, *pKA, *pVA, *pCA, *pCB;
        cudaGetSymbolAddress(&pQA, g_QA); cudaGetSymbolAddress(&pKA, g_KA); cudaGetSymbolAddress(&pVA, g_VA);
        cudaGetSymbolAddress(&pCA, g_ctxA); cudaGetSymbolAddress(&pCB, g_ctxB);
        make_map(&P2.mapA[0], x, SEQ, DM, 128);
        make_map(&P2.mapA[1], ckv, SEQ, DM, 128);
        const void* ws[3] = {wq, wuk, wuv};
        void* cs[3] = {pQA, pKA, pVA};
        for (int i = 0; i < 3; i++) { make_map(&P2.mapW[i], ws[i], DM, NQ, 64); P2.out[i] = (bf16*)cs[i]; }
        make_map(&CP.mapW[0], Wq, DM, NQ, 64); make_map(&CP.mapW[1], Wk, DM, NQ, 64); make_map(&CP.mapW[2], Wv, DM, NQ, 32);
        make_map(&CP.mapX, x, SEQ, DM, 32);
        make_map(&CP.mapWo, Wo, NQ, DM, 64);
        make_map(&CP.mapM, mem0, NMEM, DM, 8);
        MP.x = x; MP.gate_w = gate_w;
        make_map(&CP.mapC, pCB, NH * SEQ, HD, 32);
        make_map(&AP.mapQ, pQA, NH * SEQ, HD, 128);
        make_map(&AP.mapK, pKA, NH * SEQ, HD, 128);
        make_map(&AP.mapV, pVA, NH * SEQ, HD, 128);
        make_map(&AP.mapO, pCA, NH * SEQ, HD, 64);
        make_map(&OP.mapCtx[0], pCA, NH * SEQ, HD, 128);
        make_map(&OP.mapCtx[1], pCB, NH * SEQ, HD, 128);
        make_map(&OP.mapWo[0], wo, NQ, DM, 64);
        make_map(&OP.mapWo[1], Wo, NQ, DM, 64);
        make_map(&OP.mapOut, out, SEQ, DM, 64);
        CP.mapOut = OP.mapOut;
        AP.out = out;
    }
    cudaStream_t s1 = cudaStreamPerThread;
    const bool pdl = true;
    launch_pdl(chain_kernel, 64, CH_BLOCK, CH_SMEM, s1, false, CP);
    launch_pdl(main_kernel, M_GRID, 384, M_SMEM, s1, pdl, MP);
}
```

```cpp
#include <cuda_runtime.h>
#include <cuda_bf16.h>
#include <cuda.h>
#include <stdint.h>
#include <type_traits>

constexpr int SEQ = 2048;
constexpr int DM = 512;
constexpr int NH = 32;
constexpr int HD = 128;
constexpr int NQ = NH * HD;
constexpr int SEGL = 32;
constexpr int NMEM = 8;
constexpr int NSEG = SEQ / SEGL;

typedef __nv_bfloat16 bf16;

__device__ bf16 g_QA[SEQ * NQ];
__device__ bf16 g_KA[SEQ * NQ];
__device__ bf16 g_VA[SEQ * NQ];
__device__ bf16 g_ctxA[SEQ * NQ];
__device__ bf16 g_ctxB[SEQ * NQ];
constexpr int CT_PROJ = 0, CT_ATTN = 1, CT_FIN = 5;
constexpr int CT_AP = 64;
constexpr int CT_GATE = 96;
constexpr int CT_CA = 128;
constexpr int CT_CB = 193;
constexpr int CT_OT = 208;
constexpr int CT_N = 228;
__device__ __align__(16) unsigned int g_ctr[CT_N];
__device__ float g_gate[SEQ];
#define XB8(v) v, v, v, v, v, v, v, v
__device__ uint32_t g_xbuf[4 * 8 * 2048] = {XB8(XB8(XB8(XB8(XB8(~0u)))))};

#define FA_GRID 68

#define TS_BEGIN(id)
#define TS_END(id)
#define TS_BEGIN2(id, th)
#define TS_END2(id, th)
#define WAIT_LIMIT 200000
__device__ __forceinline__ void pdl_launch_dependents() { asm volatile("griddepcontrol.launch_dependents;" ::: "memory"); }
__device__ __forceinline__ void wait_ctr(int idx, unsigned int n) {
    unsigned int v; int it = 0;
    do { asm volatile("ld.acquire.gpu.global.u32 %0, [%1];" : "=r"(v) : "l"(&g_ctr[idx]) : "memory"); } while (v < n && ++it < WAIT_LIMIT);
    asm volatile("fence.proxy.async.shared::cta;" ::: "memory");
}
__device__ __forceinline__ int take_ticket(int idx) {
    int v;
    asm volatile("atom.relaxed.gpu.global.inc.u32 %0, [%1], 0x7fffffff;" : "=r"(v) : "l"(&g_ctr[idx]) : "memory");
    return v;
}
__device__ __forceinline__ void signal_ctr(int idx) {
    asm volatile("fence.proxy.async;" ::: "memory");
    __threadfence();
    atomicAdd(&g_ctr[idx], 1u);
}
__device__ __forceinline__ void signal_ctr_generic(int idx) {
    asm volatile("red.release.gpu.global.add.u32 [%0], 1;" :: "l"(&g_ctr[idx]) : "memory");
}
__device__ __forceinline__ uint32_t smem_u32(const void* p) {
    return (uint32_t)__cvta_generic_to_shared(p);
}
__device__ __forceinline__ void mbar_init(uint32_t bar, uint32_t count) {
    asm volatile("mbarrier.init.shared::cta.b64 [%0], %1;" :: "r"(bar), "r"(count));
}
__device__ __forceinline__ void mbar_expect_tx(uint32_t bar, uint32_t bytes) {
    asm volatile("mbarrier.arrive.expect_tx.shared::cta.b64 _, [%0], %1;" :: "r"(bar), "r"(bytes) : "memory");
}
__device__ __forceinline__ void mbar_arrive(uint32_t bar) {
    asm volatile("mbarrier.arrive.shared::cta.b64 _, [%0];" :: "r"(bar) : "memory");
}
__device__ __forceinline__ void mbar_wait(uint32_t bar, uint32_t parity) {
    asm volatile(
        "{\n"
        ".reg .pred p, q;\n"
        ".reg .u32 c;\n"
        "mov.u32 c, 0;\n"
        "WAIT_LOOP:\n"
        "mbarrier.try_wait.parity.shared::cta.b64 p, [%0], %1;\n"
        "@p bra WAIT_DONE;\n"
        "add.u32 c, c, 1;\n"
        "setp.lt.u32 q, c, %2;\n"
        "@q bra WAIT_LOOP;\n"
        "WAIT_DONE:\n"
        "}\n" :: "r"(bar), "r"(parity), "n"(WAIT_LIMIT) : "memory");
}
__device__ __forceinline__ uint32_t mbar_test(uint32_t bar, uint32_t parity) {
    uint32_t done;
    asm volatile(
        "{\n.reg .pred p;\n"
        "mbarrier.test_wait.parity.shared::cta.b64 p, [%1], %2;\n"
        "selp.u32 %0, 1, 0, p;\n}\n" : "=r"(done) : "r"(bar), "r"(parity) : "memory");
    return done;
}
__device__ __forceinline__ uint32_t mbar_try(uint32_t bar, uint32_t parity) {
    uint32_t done;
    asm volatile(
        "{\n.reg .pred p;\n"
        "mbarrier.try_wait.parity.shared::cta.b64 p, [%1], %2;\n"
        "selp.u32 %0, 1, 0, p;\n}\n" : "=r"(done) : "r"(bar), "r"(parity) : "memory");
    return done;
}
__device__ __forceinline__ void tma_load_2d(uint32_t dst, const CUtensorMap* map, uint32_t bar, int c0, int c1) {
    asm volatile(
        "cp.async.bulk.tensor.2d.shared::cluster.global.mbarrier::complete_tx::bytes [%0], [%1, {%3, %4}], [%2];"
        :: "r"(dst), "l"((uint64_t)map), "r"(bar), "r"(c0), "r"(c1) : "memory");
}
__device__ __forceinline__ void wgmma_fence() { asm volatile("wgmma.fence.sync.aligned;" ::: "memory"); }
__device__ __forceinline__ void wgmma_commit() { asm volatile("wgmma.commit_group.sync.aligned;" ::: "memory"); }
template <int N> __device__ __forceinline__ void wgmma_wait() {
    asm volatile("wgmma.wait_group.sync.aligned %0;" :: "n"(N) : "memory");
}
__device__ __forceinline__ uint64_t make_desc(uint32_t addr, uint32_t lbo, uint32_t sbo) {
    uint64_t d = 0;
    d |= (uint64_t)((addr & 0x3FFFF) >> 4);
    d |= (uint64_t)((lbo >> 4) & 0x3FFF) << 16;
    d |= (uint64_t)((sbo >> 4) & 0x3FFF) << 32;
    d |= (uint64_t)1 << 62;
    return d;
}

#define ACC64(d) \
    "+f"(d[0]), "+f"(d[1]), "+f"(d[2]), "+f"(d[3]), "+f"(d[4]), "+f"(d[5]), "+f"(d[6]), "+f"(d[7]), \
    "+f"(d[8]), "+f"(d[9]), "+f"(d[10]), "+f"(d[11]), "+f"(d[12]), "+f"(d[13]), "+f"(d[14]), "+f"(d[15]), \
    "+f"(d[16]), "+f"(d[17]), "+f"(d[18]), "+f"(d[19]), "+f"(d[20]), "+f"(d[21]), "+f"(d[22]), "+f"(d[23]), \
    "+f"(d[24]), "+f"(d[25]), "+f"(d[26]), "+f"(d[27]), "+f"(d[28]), "+f"(d[29]), "+f"(d[30]), "+f"(d[31]), \
    "+f"(d[32]), "+f"(d[33]), "+f"(d[34]), "+f"(d[35]), "+f"(d[36]), "+f"(d[37]), "+f"(d[38]), "+f"(d[39]), \
    "+f"(d[40]), "+f"(d[41]), "+f"(d[42]), "+f"(d[43]), "+f"(d[44]), "+f"(d[45]), "+f"(d[46]), "+f"(d[47]), \
    "+f"(d[48]), "+f"(d[49]), "+f"(d[50]), "+f"(d[51]), "+f"(d[52]), "+f"(d[53]), "+f"(d[54]), "+f"(d[55]), \
    "+f"(d[56]), "+f"(d[57]), "+f"(d[58]), "+f"(d[59]), "+f"(d[60]), "+f"(d[61]), "+f"(d[62]), "+f"(d[63])
#define ACC64_STR \
    "{%0, %1, %2, %3, %4, %5, %6, %7, %8, %9, %10, %11, %12, %13, %14, %15, " \
    "%16, %17, %18, %19, %20, %21, %22, %23, %24, %25, %26, %27, %28, %29, %30, %31, " \
    "%32, %33, %34, %35, %36, %37, %38, %39, %40, %41, %42, %43, %44, %45, %46, %47, " \
    "%48, %49, %50, %51, %52, %53, %54, %55, %56, %57, %58, %59, %60, %61, %62, %63}"

template <int TB>
__device__ __forceinline__ void wgmma_ss_n128(float (&d)[64], uint64_t da, uint64_t db, int scale_d) {
    asm volatile(
        "{\n.reg .pred p;\nsetp.ne.b32 p, %66, 0;\n"
        "wgmma.mma_async.sync.aligned.m64n128k16.f32.bf16.bf16 " ACC64_STR ", %64, %65, p, 1, 1, 0, %67;\n}\n"
        : ACC64(d) : "l"(da), "l"(db), "r"(scale_d), "n"(TB));
}
__device__ __forceinline__ uint32_t desc_lo(uint32_t addr, uint32_t lbo) { return ((addr & 0x3FFFF) >> 4) | ((lbo >> 4) << 16); }
template <int TB>
__device__ __forceinline__ void wgmma_ss_n128_lo(float (&d)[64], uint32_t da_lo, uint32_t db_lo, int scale_d) {
    asm volatile(
        "{\n.reg .pred p;\n.reg .b64 da, db;\nsetp.ne.b32 p, %66, 0;\n"
        "mov.b64 da, {%64, 0x40000040};\nmov.b64 db, {%65, 0x40000040};\n"
        "wgmma.mma_async.sync.aligned.m64n128k16.f32.bf16.bf16 " ACC64_STR ", da, db, p, 1, 1, 0, %67;\n}\n"
        : ACC64(d) : "r"(da_lo), "r"(db_lo), "r"(scale_d), "n"(TB));
}
__device__ __forceinline__ void wgmma_rs_n128_tb(float (&d)[64], uint32_t a0, uint32_t a1, uint32_t a2, uint32_t a3,
                                                 uint64_t db, int scale_d) {
    asm volatile(
        "{\n.reg .pred p;\nsetp.ne.b32 p, %69, 0;\n"
        "wgmma.mma_async.sync.aligned.m64n128k16.f32.bf16.bf16 " ACC64_STR ", {%64, %65, %66, %67}, %68, p, 1, 1, 1;\n}\n"
        : ACC64(d) : "r"(a0), "r"(a1), "r"(a2), "r"(a3), "l"(db), "r"(scale_d));
}
__device__ __forceinline__ void wgmma_rs_n80(float (&d)[40], const uint32_t (&a)[4], uint32_t db_lo, int scale_d) {
    asm volatile(
        "{\n.reg .pred p;\n.reg .b64 db;\nsetp.ne.b32 p, %45, 0;\nmov.b64 db, {%44, 0x40000040};\n"
        "wgmma.mma_async.sync.aligned.m64n80k16.f32.bf16.bf16 "
        "{%0, %1, %2, %3, %4, %5, %6, %7, %8, %9, %10, %11, %12, %13, %14, %15, %16, %17, %18, %19, %20, %21, %22, %23, %24, %25, %26, %27, %28, %29, %30, %31, %32, %33, %34, %35, %36, %37, %38, %39}, "
        "{%40, %41, %42, %43}, db, p, 1, 1, 0;\n}\n"
        : "+f"(d[0]), "+f"(d[1]), "+f"(d[2]), "+f"(d[3]), "+f"(d[4]), "+f"(d[5]), "+f"(d[6]), "+f"(d[7]), "+f"(d[8]), "+f"(d[9]), "+f"(d[10]), "+f"(d[11]), "+f"(d[12]), "+f"(d[13]), "+f"(d[14]), "+f"(d[15]), "+f"(d[16]), "+f"(d[17]), "+f"(d[18]), "+f"(d[19]), "+f"(d[20]), "+f"(d[21]), "+f"(d[22]), "+f"(d[23]), "+f"(d[24]), "+f"(d[25]), "+f"(d[26]), "+f"(d[27]), "+f"(d[28]), "+f"(d[29]), "+f"(d[30]), "+f"(d[31]), "+f"(d[32]), "+f"(d[33]), "+f"(d[34]), "+f"(d[35]), "+f"(d[36]), "+f"(d[37]), "+f"(d[38]), "+f"(d[39])
        : "r"(a[0]), "r"(a[1]), "r"(a[2]), "r"(a[3]), "r"(db_lo), "r"(scale_d));
}
__device__ __forceinline__ void wgmma_ss_n256_tb(float (&d)[128], uint64_t da, uint64_t db, int scale_d) {
    asm volatile(
        "{\n.reg .pred p;\nsetp.ne.b32 p, %130, 0;\n"
        "wgmma.mma_async.sync.aligned.m64n256k16.f32.bf16.bf16 {%0, %1, %2, %3, %4, %5, %6, %7, %8, %9, %10, %11, %12, %13, %14, %15, %16, %17, %18, %19, %20, %21, %22, %23, %24, %25, %26, %27, %28, %29, %30, %31, %32, %33, %34, %35, %36, %37, %38, %39, %40, %41, %42, %43, %44, %45, %46, %47, %48, %49, %50, %51, %52, %53, %54, %55, %56, %57, %58, %59, %60, %61, %62, %63, %64, %65, %66, %67, %68, %69, %70, %71, %72, %73, %74, %75, %76, %77, %78, %79, %80, %81, %82, %83, %84, %85, %86, %87, %88, %89, %90, %91, %92, %93, %94, %95, %96, %97, %98, %99, %100, %101, %102, %103, %104, %105, %106, %107, %108, %109, %110, %111, %112, %113, %114, %115, %116, %117, %118, %119, %120, %121, %122, %123, %124, %125, %126, %127}, %128, %129, p, 1, 1, 0, 1;\n}\n"
        : "+f"(d[0]), "+f"(d[1]), "+f"(d[2]), "+f"(d[3]), "+f"(d[4]), "+f"(d[5]), "+f"(d[6]), "+f"(d[7]), "+f"(d[8]), "+f"(d[9]), "+f"(d[10]), "+f"(d[11]), "+f"(d[12]), "+f"(d[13]), "+f"(d[14]), "+f"(d[15]), "+f"(d[16]), "+f"(d[17]), "+f"(d[18]), "+f"(d[19]), "+f"(d[20]), "+f"(d[21]), "+f"(d[22]), "+f"(d[23]), "+f"(d[24]), "+f"(d[25]), "+f"(d[26]), "+f"(d[27]), "+f"(d[28]), "+f"(d[29]), "+f"(d[30]), "+f"(d[31]), "+f"(d[32]), "+f"(d[33]), "+f"(d[34]), "+f"(d[35]), "+f"(d[36]), "+f"(d[37]), "+f"(d[38]), "+f"(d[39]), "+f"(d[40]), "+f"(d[41]), "+f"(d[42]), "+f"(d[43]), "+f"(d[44]), "+f"(d[45]), "+f"(d[46]), "+f"(d[47]), "+f"(d[48]), "+f"(d[49]), "+f"(d[50]), "+f"(d[51]), "+f"(d[52]), "+f"(d[53]), "+f"(d[54]), "+f"(d[55]), "+f"(d[56]), "+f"(d[57]), "+f"(d[58]), "+f"(d[59]), "+f"(d[60]), "+f"(d[61]), "+f"(d[62]), "+f"(d[63]), "+f"(d[64]), "+f"(d[65]), "+f"(d[66]), "+f"(d[67]), "+f"(d[68]), "+f"(d[69]), "+f"(d[70]), "+f"(d[71]), "+f"(d[72]), "+f"(d[73]), "+f"(d[74]), "+f"(d[75]), "+f"(d[76]), "+f"(d[77]), "+f"(d[78]), "+f"(d[79]), "+f"(d[80]), "+f"(d[81]), "+f"(d[82]), "+f"(d[83]), "+f"(d[84]), "+f"(d[85]), "+f"(d[86]), "+f"(d[87]), "+f"(d[88]), "+f"(d[89]), "+f"(d[90]), "+f"(d[91]), "+f"(d[92]), "+f"(d[93]), "+f"(d[94]), "+f"(d[95]), "+f"(d[96]), "+f"(d[97]), "+f"(d[98]), "+f"(d[99]), "+f"(d[100]), "+f"(d[101]), "+f"(d[102]), "+f"(d[103]), "+f"(d[104]), "+f"(d[105]), "+f"(d[106]), "+f"(d[107]), "+f"(d[108]), "+f"(d[109]), "+f"(d[110]), "+f"(d[111]), "+f"(d[112]), "+f"(d[113]), "+f"(d[114]), "+f"(d[115]), "+f"(d[116]), "+f"(d[117]), "+f"(d[118]), "+f"(d[119]), "+f"(d[120]), "+f"(d[121]), "+f"(d[122]), "+f"(d[123]), "+f"(d[124]), "+f"(d[125]), "+f"(d[126]), "+f"(d[127])
        : "l"(da), "l"(db), "r"(scale_d));
}
__device__ __forceinline__ void stmatrix_x4(uint32_t addr, uint32_t r0, uint32_t r1, uint32_t r2, uint32_t r3) {
    asm volatile("stmatrix.sync.aligned.m8n8.x4.shared.b16 [%0], {%1, %2, %3, %4};" :: "r"(addr), "r"(r0), "r"(r1), "r"(r2), "r"(r3) : "memory");
}
__device__ __forceinline__ void tma_store_2d(const CUtensorMap* map, uint32_t src, int c0, int c1) {
    asm volatile("cp.async.bulk.tensor.2d.global.shared::cta.bulk_group [%0, {%2, %3}], [%1];"
                 :: "l"((uint64_t)map), "r"(src), "r"(c0), "r"(c1) : "memory");
}
__device__ __forceinline__ float ex2f(float x) { float y; asm("ex2.approx.ftz.f32 %0, %1;" : "=f"(y) : "f"(x)); return y; }
__device__ __forceinline__ uint32_t pack_bf16(float lo, float hi) {
    __nv_bfloat162 v = __floats2bfloat162_rn(lo, hi);
    return *reinterpret_cast<uint32_t*>(&v);
}
__device__ __forceinline__ void mma_16816(float (&c)[4], uint32_t a0, uint32_t a1, uint32_t a2, uint32_t a3,
                                          uint32_t b0, uint32_t b1) {
    asm volatile(
        "mma.sync.aligned.m16n8k16.row.col.f32.bf16.bf16.f32 {%0,%1,%2,%3}, {%4,%5,%6,%7}, {%8,%9}, {%0,%1,%2,%3};"
        : "+f"(c[0]), "+f"(c[1]), "+f"(c[2]), "+f"(c[3])
        : "r"(a0), "r"(a1), "r"(a2), "r"(a3), "r"(b0), "r"(b1));
}
__device__ __forceinline__ void ldmatrix_x4_trans(uint32_t& r0, uint32_t& r1, uint32_t& r2, uint32_t& r3, uint32_t addr) {
    asm volatile("ldmatrix.sync.aligned.m8n8.x4.trans.shared.b16 {%0,%1,%2,%3}, [%4];"
                 : "=r"(r0), "=r"(r1), "=r"(r2), "=r"(r3) : "r"(addr));
}

struct AttnParams {
    CUtensorMap mapQ, mapK, mapV;
    CUtensorMap mapO;
    bf16* out;
};
constexpr int FA_ITEMS = 16 * NH;
__device__ __forceinline__ int fa_qt(int t) { return 15 - ((t & 127) >> 3); }
__device__ __forceinline__ int fa_head(int t) { return (t >> 7) * 8 + (t & 7); }
#define FA_TKA 2
#define FA_SPLIT 11

#define FA_P0 4
#define FA_HO 7
#define FA_LAG 2
#define FA_PK 3
#define FA_ST 4
#define FA_TG 16
#define FA_EARLY 0
#define FA_TRIM 1
#define FA_TE 0
#define FA_B0 1
#define FA_ONE 1
#define FA_V2 1
#define FA_I0 0
static_assert(FA_GRID <= 104 && FA_HO >= FA_P0 && FA_P0 >= 1 && (!FA_TRIM || (FA_P0 == 4 && FA_SPLIT >= 8 && FA_I0 <= 4)), "");
constexpr float FA_MARGIN = 16.f;
#define FAT(b, i)
__device__ __forceinline__ void mbar_arrive_if(uint32_t bar, bool c) {
    asm volatile("{\n.reg .pred p;\nsetp.ne.b32 p, %1, 0;\n@p mbarrier.arrive.shared::cta.b64 _, [%0];\n}" :: "r"(bar), "r"((int)c) : "memory");
}
__device__ __forceinline__ void sched_fence(int v, int id, const float* a, const float* b, const float* c) {
    asm volatile("{\n.reg .pred p;\nsetp.ne.s32 p, %0, %1;\n@p bra SF_SKIP;\nwgmma.wait_group.sync.aligned 0;\n"
                 "st.volatile.shared.f32 [%0], %2;\nst.volatile.shared.f32 [%0], %3;\nst.volatile.shared.f32 [%0], %4;\nst.volatile.shared.f32 [%0], %5;\n"
                 "st.volatile.shared.f32 [%0], %6;\nst.volatile.shared.f32 [%0], %7;\nst.volatile.shared.f32 [%0], %8;\nst.volatile.shared.f32 [%0], %9;\n"
                 "st.volatile.shared.f32 [%0], %10;\nst.volatile.shared.f32 [%0], %11;\nst.volatile.shared.f32 [%0], %12;\nst.volatile.shared.f32 [%0], %13;\n"
                 "exit;\nSF_SKIP:\n}" :: "r"(v), "r"(1000000 + id), "f"(a[0]), "f"(a[1]), "f"(a[2]), "f"(a[3]), "f"(b[0]), "f"(b[1]), "f"(b[2]), "f"(b[3]),
                 "f"(c[0]), "f"(c[1]), "f"(c[2]), "f"(c[3]) : "memory");
}
#define QK_FULL "wgmma.mma_async.sync.aligned.m64n128k16.f32.bf16.bf16 " ACC64_STR
#define QK_HALF "wgmma.mma_async.sync.aligned.m64n64k16.f32.bf16.bf16 {%32,%33,%34,%35,%36,%37,%38,%39,%40,%41,%42,%43,%44,%45,%46,%47,%48,%49,%50,%51,%52,%53,%54,%55,%56,%57,%58,%59,%60,%61,%62,%63}"
__device__ __forceinline__ void wgmma_qk(float (&d)[64], uint32_t da_lo, uint32_t db_lo, int half) {
    asm volatile(
        "{\n.reg .pred p, t, f;\n.reg .b32 a, b;\n.reg .b64 da, db;\nsetp.eq.b32 t, 0, 0;\nsetp.ne.b32 f, 0, 0;\nsetp.ne.b32 p, %66, 0;\n@p bra.uni QK_H;\nwgmma.fence.sync.aligned;\n"
        "add.u32 a, %64, 0;\nadd.u32 b, %65, 0;\nmov.b64 da, {a, 0x40000040};\nmov.b64 db, {b, 0x40000040};\n" QK_FULL ", da, db, f, 1, 1, 0, 0;\n"
        "add.u32 a, %64, 2;\nadd.u32 b, %65, 2;\nmov.b64 da, {a, 0x40000040};\nmov.b64 db, {b, 0x40000040};\n" QK_FULL ", da, db, t, 1, 1, 0, 0;\n"
        "add.u32 a, %64, 4;\nadd.u32 b, %65, 4;\nmov.b64 da, {a, 0x40000040};\nmov.b64 db, {b, 0x40000040};\n" QK_FULL ", da, db, t, 1, 1, 0, 0;\n"
        "add.u32 a, %64, 6;\nadd.u32 b, %65, 6;\nmov.b64 da, {a, 0x40000040};\nmov.b64 db, {b, 0x40000040};\n" QK_FULL ", da, db, t, 1, 1, 0, 0;\n"
        "add.u32 a, %64, 1024;\nadd.u32 b, %65, 1024;\nmov.b64 da, {a, 0x40000040};\nmov.b64 db, {b, 0x40000040};\n" QK_FULL ", da, db, t, 1, 1, 0, 0;\n"
        "add.u32 a, %64, 1026;\nadd.u32 b, %65, 1026;\nmov.b64 da, {a, 0x40000040};\nmov.b64 db, {b, 0x40000040};\n" QK_FULL ", da, db, t, 1, 1, 0, 0;\n"
        "add.u32 a, %64, 1028;\nadd.u32 b, %65, 1028;\nmov.b64 da, {a, 0x40000040};\nmov.b64 db, {b, 0x40000040};\n" QK_FULL ", da, db, t, 1, 1, 0, 0;\n"
        "add.u32 a, %64, 1030;\nadd.u32 b, %65, 1030;\nmov.b64 da, {a, 0x40000040};\nmov.b64 db, {b, 0x40000040};\n" QK_FULL ", da, db, t, 1, 1, 0, 0;\n"
        "wgmma.commit_group.sync.aligned;\nbra.uni QK_E;\nQK_H:\nwgmma.fence.sync.aligned;\n"
        "add.u32 a, %64, 0;\nadd.u32 b, %65, 0;\nmov.b64 da, {a, 0x40000040};\nmov.b64 db, {b, 0x40000040};\n" QK_HALF ", da, db, f, 1, 1, 0, 0;\n"
        "add.u32 a, %64, 2;\nadd.u32 b, %65, 2;\nmov.b64 da, {a, 0x40000040};\nmov.b64 db, {b, 0x40000040};\n" QK_HALF ", da, db, t, 1, 1, 0, 0;\n"
        "add.u32 a, %64, 4;\nadd.u32 b, %65, 4;\nmov.b64 da, {a, 0x40000040};\nmov.b64 db, {b, 0x40000040};\n" QK_HALF ", da, db, t, 1, 1, 0, 0;\n"
        "add.u32 a, %64, 6;\nadd.u32 b, %65, 6;\nmov.b64 da, {a, 0x40000040};\nmov.b64 db, {b, 0x40000040};\n" QK_HALF ", da, db, t, 1, 1, 0, 0;\n"
        "add.u32 a, %64, 1024;\nadd.u32 b, %65, 1024;\nmov.b64 da, {a, 0x40000040};\nmov.b64 db, {b, 0x40000040};\n" QK_HALF ", da, db, t, 1, 1, 0, 0;\n"
        "add.u32 a, %64, 1026;\nadd.u32 b, %65, 1026;\nmov.b64 da, {a, 0x40000040};\nmov.b64 db, {b, 0x40000040};\n" QK_HALF ", da, db, t, 1, 1, 0, 0;\n"
        "add.u32 a, %64, 1028;\nadd.u32 b, %65, 1028;\nmov.b64 da, {a, 0x40000040};\nmov.b64 db, {b, 0x40000040};\n" QK_HALF ", da, db, t, 1, 1, 0, 0;\n"
        "add.u32 a, %64, 1030;\nadd.u32 b, %65, 1030;\nmov.b64 da, {a, 0x40000040};\nmov.b64 db, {b, 0x40000040};\n" QK_HALF ", da, db, t, 1, 1, 0, 0;\n"
        "wgmma.commit_group.sync.aligned;\nQK_E:\n}"
        : ACC64(d) : "r"(da_lo), "r"(db_lo), "r"(half) : "memory");
}
__device__ __forceinline__ float ex2v(float x) { float y; asm volatile("ex2.approx.ftz.f32 %0, %1;" : "=f"(y) : "f"(x)); return y; }
__device__ __forceinline__ void wgmma_rs_n128_tb_lo(float (&d)[64], const uint32_t* a, uint32_t db_lo, int scale_d) {
    asm volatile(
        "{\n.reg .pred p;\n.reg .b64 db;\nsetp.ne.b32 p, %69, 0;\nmov.b64 db, {%68, 0x40000040};\n"
        "wgmma.mma_async.sync.aligned.m64n128k16.f32.bf16.bf16 " ACC64_STR ", {%64, %65, %66, %67}, db, p, 1, 1, 1;\n}\n"
        : ACC64(d) : "r"(a[0]), "r"(a[1]), "r"(a[2]), "r"(a[3]), "r"(db_lo), "r"(scale_d));
}

constexpr int M_GRID = 68;
constexpr uint32_t SD = 1024;
constexpr uint32_t MO_BAR = 229376;
constexpr int M_SMEM = MO_BAR + 1024;
constexpr uint32_t FO_Q = 0, FO_KV = 65536, FO_O = FO_KV + 2 * 65536, FO_BAR = MO_BAR + 512;
constexpr uint32_t FB_QF = FO_BAR, FB_QE = FO_BAR + 16, FB_KF = FO_BAR + 32, FB_VF = FO_BAR + 48, FB_KE = FO_BAR + 64, FB_VE = FO_BAR + 80,
                   FB_OF = FO_BAR + 96, FB_OE = FO_BAR + 112, FB_SLOT = FO_BAR + 128, FB_OSLOT = FO_BAR + 136;
__device__ __forceinline__ void attn_init(uint32_t sb) {
    for (int i = 0; i < 2; i++) {
        mbar_init(sb + FB_QF + 8 * i, 1); mbar_init(sb + FB_QE + 8 * i, 8); mbar_init(sb + FB_KF + 8 * i, 1); mbar_init(sb + FB_VF + 8 * i, 1);
        mbar_init(sb + FB_KE + 8 * i, 8); mbar_init(sb + FB_VE + 8 * i, 8); mbar_init(sb + FB_OF + 8 * i, 4); mbar_init(sb + FB_OE + 8 * i, 1);
    }
}
__device__ __forceinline__ void attn_helper(const AttnParams& P, uint32_t sb, int wg) {
    const uint32_t stg = sb + FO_O + wg * 16384;
    for (int n = 0;; n++) {
        mbar_wait(sb + FB_OF + 8 * wg, n & 1);
        int t;
        asm volatile("ld.shared.s32 %0, [%1];" : "=r"(t) : "r"(sb + FB_OSLOT + wg * 4) : "memory");
        const int qt = fa_qt(t), h = fa_head(t & 1023);
        tma_store_2d(&P.mapO, stg, 0, h * SEQ + qt * 128 + wg * 64);
        tma_store_2d(&P.mapO, stg + 8192, 64, h * SEQ + qt * 128 + wg * 64);
        asm volatile("cp.async.bulk.commit_group;" ::: "memory");
        asm volatile("cp.async.bulk.wait_group.read 0;" ::: "memory");
        mbar_arrive(sb + FB_OE + 8 * wg);
        asm volatile("cp.async.bulk.wait_group 0;" ::: "memory");
        signal_ctr(CT_CA + qt * 4 + (h >> 3));
        if (t >= 1024) break;
    }
}
__device__ __forceinline__ void attn_producer(const AttnParams& P, uint32_t sb, uint32_t free_bar, uint32_t free_par) {
    const uint32_t sQ = sb + FO_Q, sKV = sb + FO_KV;
    int b = 0, hp_ready = 0, vrow = 0, t = blockIdx.x, item = 0;
    auto load_v = [&](int i) {
        const uint32_t sv = sKV + (i & 1) * 65536 + 32768, bar = sb + FB_VF + 8 * (i & 1);
        mbar_wait(sb + FB_VE + 8 * (i & 1), ((i >> 1) & 1) ^ (FA_B0 ? ~i & 1 : 1));
        mbar_expect_tx(bar, 32768);
        tma_load_2d(sv, &P.mapV, bar, 0, vrow);
        tma_load_2d(sv + 16384, &P.mapV, bar, 64, vrow);
    };
    for (;; item++) {
        const bool valid = t < FA_ITEMS;
        const int qt = fa_qt(t), h = fa_head(t);
        if (valid && !((hp_ready >> (h >> 1)) & 1)) { wait_ctr(CT_AP + (h >> 1), 96u); hp_ready |= 1 << (h >> 1); }
        const uint32_t bq = sb + FB_QF + 8 * (item & 1);
        mbar_wait(item ? sb + FB_QE + 8 * (item & 1) : free_bar + 8, item ? ((item >> 1) & 1) ^ 1 : free_par);
        asm volatile("st.shared.s32 [%0], %1;" :: "r"(sb + FB_SLOT + (item & 1) * 4), "r"(valid ? t : -1) : "memory");
        if (!valid) { mbar_arrive(bq); break; }
        mbar_expect_tx(bq, 32768);
        tma_load_2d(sQ + (item & 1) * 32768, &P.mapQ, bq, 0, h * SEQ + qt * 128);
        tma_load_2d(sQ + (item & 1) * 32768 + 16384, &P.mapQ, bq, 64, h * SEQ + qt * 128);
#pragma unroll 1
        for (int j = 0; j <= qt; j++, b++) {
            const uint32_t sk = sKV + (b & 1) * 65536, bar = sb + FB_KF + 8 * (b & 1);
            mbar_wait(b >= 2 ? sb + FB_KE + 8 * (b & 1) : free_bar + 24 + 32 * b, b >= 2 ? ((b >> 1) & 1) ^ 1 : free_par);
            if (b == 1) { TS_END2(0, 256); TS_BEGIN2(1, 256); }
            if (b == 2) wait_ctr(CT_GATE, 256u);
            mbar_expect_tx(bar, 32768);
            tma_load_2d(sk, &P.mapK, bar, 0, h * SEQ + j * 128);
            tma_load_2d(sk + 16384, &P.mapK, bar, 64, h * SEQ + j * 128);
            if (j == max(qt - FA_TKA, 0)) t = take_ticket(CT_ATTN);
            if (b > 0) load_v(b - 1);
            vrow = h * SEQ + j * 128;
        }
        t += M_GRID;
    }
    load_v(b - 1);
    mbar_wait(sb + FB_KE + 8 * (~b & 1), ((b - 1) >> 1) & 1);
}
template <typename F>
__device__ __forceinline__ int attn_consumer(const AttnParams& P, int warp, F done, const uint32_t sb) {
    constexpr uint32_t sQ = SD + FO_Q, sKV = SD + FO_KV;
    const uint32_t sO = sb + FO_O;
    const uint32_t bar_qf = sb + FB_QF, bar_qe = sb + FB_QE, bar_kf = sb + FB_KF, bar_vf = sb + FB_VF, bar_ke = sb + FB_KE, bar_ve = sb + FB_VE,
                   bar_of = sb + FB_OF, bar_oe = sb + FB_OE, slot = sb + FB_SLOT, oslot = sb + FB_OSLOT;
    {
        const int wg = warp >> 2;
        const int lane = threadIdx.x & 31;
        const float sc = 0.08838834764831845f * 1.4426950408889634f;
        const int r0 = wg * 64 + (warp & 3) * 16 + (lane >> 2);
        float o[64], s[64];
        uint32_t pa[32];
        float m0 = 0.f, m1 = 0.f, l0 = 0.f, l1 = 0.f, i0 = 0.f, i1 = 0.f, g0 = 0.f, g1 = 0.f, gn0 = 0.f, gn1 = 0.f;
        const uint32_t q_lo = desc_lo(sQ + wg * 8192, 16), k_lo = desc_lo(sKV, 16), v_lo = desc_lo(sKV + 32768, 16384);
        auto issue_qk = [&](int b, int item, bool half) {
            const uint32_t qd = q_lo + (item & 1) * 2048, kd = k_lo + (b & 1) * 4096;
            const uint32_t kd2 = half ? kd - 512 : kd;
            wgmma_fence();
#pragma unroll
            for (int kk = 0; kk < 8; kk++) wgmma_ss_n128_lo<0>(s, qd + (kk >> 2) * 1024 + (kk & 3) * 2, kd2 + (kk >> 2) * 1024 + (kk & 3) * 2, kk != 0);
            wgmma_commit();
        };
        auto issue_pv = [&](int b, bool acc, int n, bool half) {
            const uint32_t vd = v_lo + (b & 1) * 4096;
            mbar_wait(bar_vf + 8 * (b & 1), (b >> 1) & 1);
            if (half) {
                asm volatile("wgmma.fence.sync.aligned;  // half" ::: "memory");
#pragma unroll
                for (int kk = 4; kk < 8; kk++) if (kk < n) wgmma_rs_n128_tb_lo(o, &pa[kk * 4], vd + (kk - 4) * 128, kk > 4 ? 1 : (int)acc);
                asm volatile("wgmma.commit_group.sync.aligned;  // half" ::: "memory");
                return;
            }
            wgmma_fence();
#pragma unroll
            for (int kk = 0; kk < 8; kk++) if (kk < n) wgmma_rs_n128_tb_lo(o, &pa[kk * 4], vd + kk * 128, kk ? 1 : (int)acc);
            wgmma_commit();
        };
        const int lim = (FA_TRIM ? (r0 | 64) : r0) - (lane & 3) * 2;
        uint32_t v_hi = v_lo;
        int acc_hi = 1;
        int item = -1, tnext = 0;
        uint32_t k_ready = 0, q_ready = 0;
        auto mask = [&](int i) { if ((i >> 2) * 8 + (i & 1) - ((i & 2) ? 8 : 0) > lim) s[i] = -INFINITY; };
        auto exps = [&](auto mode, int b, bool hand_over, float& u0, float& u1) {
            constexpr int MODE = decltype(mode)::value;
            float p[64], u[4] = {0.f, 0.f, 0.f, 0.f};
            const uint32_t vd = v_hi + ((b - 1) & 1) * 4096;
            constexpr int R = FA_TRIM && MODE == 2 ? 32 : 0;
#pragma unroll
            for (int i = 0; i < 4; i++) p[i] = fmaf(s[i ^ R], sc, (i & 2) ? -m1 : -m0);
#pragma unroll
            for (int g = 0; g < 16 + FA_LAG; g++) {
                if (MODE && g >= FA_I0 && g - FA_I0 < 8 - FA_P0) {
                    const int kk = FA_P0 + g - FA_I0;
                    wgmma_fence();
                    wgmma_rs_n128_tb_lo(o, &pa[kk * 4], vd + kk * 128, FA_TRIM && kk == 4 ? acc_hi : 1);
                    wgmma_commit();
                    if (kk == FA_HO) asm volatile("{\n.reg .pred p;\nsetp.ne.b32 p, %1, 0;\n@p bar.arrive %0, 256;\n}" :: "r"(4 - wg), "r"((int)hand_over) : "memory");
                }
                if (R && g == 8 && wg == 0) {
                    wgmma_wait<0>();
                    mbar_arrive_if(bar_ve + 8 * ((b - 1) & 1), lane == 0);
                    k_ready = q_ready = 0;
#pragma unroll
                    for (int i = 32 - FA_LAG * 4; i < 32; i++) u[i & 3] += p[i];
#pragma unroll
                    for (int i = 0; i < 16; i++) pa[16 + i] = pack_bf16(p[i * 2], p[i * 2 + 1]);
                    break;
                }
                if (MODE && g == FA_SPLIT) {
                    FAT(b, 2);
                    wgmma_wait<0>();
                    FAT(b - 1, 3);
                    mbar_arrive_if(bar_ve + 8 * ((b - 1) & 1), lane == 0);
                }
                if (MODE && g == FA_TG) {
                    k_ready = mbar_test(bar_kf + 8 * (~b & 1), ((b + 1) >> 1) & 1);
                    if (MODE == 2) {
                        q_ready = mbar_test(bar_qf + 8 * (~item & 1), ((item + 1) >> 1) & 1);
                        asm volatile("ld.shared.s32 %0, [%1];" : "=r"(tnext) : "r"(slot + (~item & 1) * 4) : "memory");
                    }
                }
#pragma unroll
                for (int j = 0; j < 4; j++) {
                    const int i = g * 4 + j;
                    if (g < 16) p[i] = ex2v(p[i]);
                    if (g < 15) {
                        if (MODE == 2 && (!R || i + 4 < 32)) mask((i + 4) ^ R);
                        p[i + 4] = fmaf(s[(i + 4) ^ R], sc, (i & 2) ? -m1 : -m0);
                    }
                    if (g >= FA_LAG) u[j] += p[i - FA_LAG * 4];
                }
#pragma unroll
                for (int gg = 0; gg < 16; gg++) {
                    const int at = MODE && gg + FA_LAG < FA_SPLIT + gg / FA_PK ? FA_SPLIT + gg / FA_PK : gg + FA_LAG;
                    if (at == g) { pa[(gg * 2) ^ (R / 2)] = pack_bf16(p[gg * 4], p[gg * 4 + 1]); pa[(gg * 2 + 1) ^ (R / 2)] = pack_bf16(p[gg * 4 + 2], p[gg * 4 + 3]); }
                }
                if (MODE && g < 16) sched_fence(b, g + MODE * 32, &p[g * 4], &p[(g < 15 ? g + 1 : g) * 4], u);
            }
            u0 = u[0] + u[1]; u1 = u[2] + u[3];
        };
        auto quad_max = [&](float& x0, float& x1) {
            x0 = fmaxf(x0, __shfl_xor_sync(0xffffffff, x0, 1)); x1 = fmaxf(x1, __shfl_xor_sync(0xffffffff, x1, 1));
            x0 = fmaxf(x0, __shfl_xor_sync(0xffffffff, x0, 2)); x1 = fmaxf(x1, __shfl_xor_sync(0xffffffff, x1, 2));
            x0 = fmaf(x0, sc, FA_MARGIN); x1 = fmaf(x1, sc, FA_MARGIN);
        };
        auto softmax_exact = [&](bool fresh, bool half, int b) {
            wgmma_wait<0>();
            if (half) {
#pragma unroll
                for (int i = 0; i < 32; i++) s[i] = -INFINITY;
            }
            float x[8];
#pragma unroll
            for (int i = 0; i < 8; i++) x[i] = fmaxf(s[i * 2], s[i * 2 + 1]);
#pragma unroll
            for (int i = 8; i < 32; i++) x[i & 7] = fmaxf(x[i & 7], fmaxf(s[i * 2], s[i * 2 + 1]));
            float x0 = fmaxf(fmaxf(x[0], x[2]), fmaxf(x[4], x[6])), x1 = fmaxf(fmaxf(x[1], x[3]), fmaxf(x[5], x[7]));
            quad_max(x0, x1);
            if (!fresh) {
                x0 = fmaxf(x0, m0); x1 = fmaxf(x1, m1);
                const float a0 = ex2f(m0 - x0), a1 = ex2f(m1 - x1);
                l0 *= a0; l1 *= a1;
#pragma unroll
                for (int i = 0; i < 16; i++) { o[i * 4 + 0] *= a0; o[i * 4 + 1] *= a0; o[i * 4 + 2] *= a1; o[i * 4 + 3] *= a1; }
            }
            m0 = x0; m1 = x1;
            float u0, u1;
            exps(std::integral_constant<int, 0>(), b, false, u0, u1);
            l0 += u0; l1 += u1;
        };
        auto finish_rows = [&]() {
            l0 += __shfl_xor_sync(0xffffffff, l0, 1); l1 += __shfl_xor_sync(0xffffffff, l1, 1);
            l0 += __shfl_xor_sync(0xffffffff, l0, 2); l1 += __shfl_xor_sync(0xffffffff, l1, 2);
            asm("rcp.approx.ftz.f32 %0, %1;" : "=f"(i0) : "f"(l0));
            asm("rcp.approx.ftz.f32 %0, %1;" : "=f"(i1) : "f"(l1));
            i0 *= g0; i1 *= g1;
        };
        auto clear_out = [&](int t) {
            if (t >= 384) {
                bf16* z = P.out + (size_t)(fa_qt(t) * 128 + wg * 64 + ((threadIdx.x & 127) >> 3)) * DM + (t & 7) * 64 + (lane & 7) * 8;
#pragma unroll
                for (int i = 0; i < 4; i++) *reinterpret_cast<uint4*>(z + i * 16 * DM) = make_uint4(0u, 0u, 0u, 0u);
            }
        };
        auto store_o = [&](int t, int n, int c0, int c1) {
            const uint32_t stg = sO + wg * 16384;
            if (c0 == 0) {
                mbar_wait(bar_oe + 8 * wg, (n & 1) ^ 1);
                asm volatile("st.shared.s32 [%0], %1;" :: "r"(oslot + wg * 4), "r"(t) : "memory");
            }
            const int row = (warp & 3) * 16 + (lane >> 2);
#pragma unroll
            for (int i = c0; i < c1; i++) {
                const int ch = i * 4 + (lane & 3);
                const uint32_t a = stg + (ch >> 3) * 8192 + row * 128 + (((ch & 7) ^ (row & 7)) << 4);
                const float* q = &o[i * 16];
                asm volatile("st.shared.v4.b32 [%0], {%1, %2, %3, %4};" :: "r"(a), "r"(pack_bf16(q[0] * i0, q[1] * i0)), "r"(pack_bf16(q[4] * i0, q[5] * i0)),
                             "r"(pack_bf16(q[8] * i0, q[9] * i0)), "r"(pack_bf16(q[12] * i0, q[13] * i0)) : "memory");
                asm volatile("st.shared.v4.b32 [%0], {%1, %2, %3, %4};" :: "r"(a + 1024), "r"(pack_bf16(q[2] * i1, q[3] * i1)), "r"(pack_bf16(q[6] * i1, q[7] * i1)),
                             "r"(pack_bf16(q[10] * i1, q[11] * i1)), "r"(pack_bf16(q[14] * i1, q[15] * i1)) : "memory");
            }
        };
        auto store_o_late = [&](int v) {
            uint32_t w[32];
#pragma unroll
            for (int i = FA_ST * 8; i < 32; i++) {
                const float* q = &o[(i >> 3) * 16 + (i & 3) * 4 + ((i >> 2) & 1) * 2];
                const float f = (i & 4) ? i1 : i0;
                w[i] = pack_bf16(q[0] * f, q[1] * f);
            }
            const int row = (warp & 3) * 16 + (lane >> 2);
            if (v == 1000000) {
#pragma unroll
                for (int i = FA_ST * 2; i < 8; i++)
                    asm volatile("st.volatile.shared.v4.b32 [%0], {%1, %2, %3, %4};" :: "r"(v), "r"(w[i * 4]), "r"(w[i * 4 + 1]), "r"(w[i * 4 + 2]), "r"(w[i * 4 + 3]) : "memory");
                asm volatile("wgmma.wait_group.sync.aligned 0;\nexit;" ::: "memory");
            }
#pragma unroll
            for (int i = FA_ST * 2; i < 8; i++) {
                const int ch = (i >> 1) * 4 + (lane & 3);
                const uint32_t a = sO + wg * 16384 + (ch >> 3) * 8192 + row * 128 + (((ch & 7) ^ (row & 7)) << 4) + (i & 1) * 1024;
                asm volatile("st.shared.v4.b32 [%0], {%1, %2, %3, %4};" :: "r"(a), "r"(w[i * 4]), "r"(w[i * 4 + 1]), "r"(w[i * 4 + 2]), "r"(w[i * 4 + 3]) : "memory");
            }
        };
        auto publish_o = [&]() {
            asm volatile("fence.proxy.async.shared::cta;" ::: "memory");
            __syncwarp();
            mbar_arrive_if(bar_of + 8 * wg, lane == 0);
        };
        int t = 0, left = 0, tdone = -1, b = 0, nout = 0;
        bool first = true, staged = false;
#pragma unroll 1
        for (;; b++) {
            const bool fresh = left == 0;
            const int tprev = t;
            FAT(b, 4);
            if (staged) { publish_o(); staged = false; }
            if (fresh) {
                item++;
                if (!q_ready) {
                    mbar_wait(bar_qf + 8 * (item & 1), (item >> 1) & 1);
                    asm volatile("ld.shared.s32 %0, [%1];" : "=r"(tnext) : "r"(slot + (item & 1) * 4) : "memory");
                }
                if (tnext < 0) break;
                t = tnext;
                left = fa_qt(t) + 1;
            }
            left--;
            if (fresh || first || left == 0) {
                if (tdone >= 0) store_o(tdone, nout, 0, FA_ST);
                if (fresh) { g0 = gn0; g1 = gn1; }
                if (left == 0) { gn0 = __ldcg(g_gate + fa_qt(t) * 128 + r0); gn1 = __ldcg(g_gate + fa_qt(t) * 128 + r0 + 8); clear_out(t); }
            }
            FAT(b, 5);
            if (!k_ready) mbar_wait(bar_kf + 8 * (b & 1), (b >> 1) & 1);
            FAT(b, 6);
            asm volatile("bar.sync %0, 256;" :: "r"(3 + wg) : "memory");
            FAT(b, 0);
            issue_qk(b, item, FA_TRIM && wg == 0 && left == 0);
            FAT(b, 7);
            bool early = false;
            if (!fresh && !first && left != 0) {
                issue_pv(b - 1, true, FA_P0, false);
                wgmma_wait<1>();
                FAT(b, 1);
                mbar_arrive_if(bar_ke + 8 * (b & 1), lane == 0);
            } else {
                const bool hprev = FA_TRIM && fresh && wg == 0;
                early = (FA_EARLY && tdone >= 0) || b == 0 || (FA_TE && hprev);
                if (early) asm volatile("bar.arrive %0, 256;" :: "r"(4 - wg) : "memory");
                if (tdone >= 0) { wgmma_wait<1>(); if (FA_ST < 4) store_o_late(b); nout++; staged = true; }
                tdone = fresh && b > 0 ? tprev : -1;
                v_hi = hprev ? v_lo - 512 : v_lo;
                acc_hi = !(hprev && first);
                if (b > 0) issue_pv(b - 1, !first, FA_P0, hprev); else { wgmma_fence(); wgmma_commit(); }
                first = fresh;
                wgmma_wait<1>();
                FAT(b, 1);
                mbar_arrive_if(bar_ke + 8 * (b & 1), lane == 0);
                mbar_arrive_if(bar_qe + 8 * (item & 1), lane == 0 && left == 0);
                if (left == 0) { mask(FA_TRIM ? 32 : 0); mask(FA_TRIM ? 33 : 1); }
                if (fresh) {
                    m0 = fmaxf(s[0], s[1]); m1 = fmaxf(s[2], s[3]);
                    if (FA_TRIM && left == 0) { m0 = fmaxf(s[32], s[33]); m1 = fmaxf(s[34], s[35]); }
                    quad_max(m0, m1);
                    if (FA_V2) { finish_rows(); l0 = l1 = 0.f; }
                }
            }
            if (FA_B0 || b > 0) {
                float u0, u1;
                if (left == 0) exps(std::integral_constant<int, 2>(), b, !early, u0, u1);
                else exps(std::integral_constant<int, 1>(), b, !early, u0, u1);
                if (!__any_sync(0xffffffff, !(u0 + u1 < 1.f))) { l0 += u0; l1 += u1; continue; }
            }
            softmax_exact(fresh, FA_TRIM && wg == 0 && left == 0, b);
        }
        if (tdone >= 0) { store_o(tdone, nout++, 0, 4); publish_o(); }
        issue_pv(b - 1, !first, 8, FA_TRIM && wg == 0);
        if (FA_V2) { g0 = gn0; g1 = gn1; }
        finish_rows();
        wgmma_wait<0>();
        done();
        store_o(t + 1024, nout, 0, 4);
        publish_o();
        return nout;
    }
}

__device__ __forceinline__ uint32_t cluster_ctarank() {
    uint32_t r; asm volatile("mov.u32 %0, %%cluster_ctarank;" : "=r"(r)); return r;
}
__device__ __forceinline__ uint32_t mapa_u32(uint32_t addr, uint32_t rank) {
    uint32_t r; asm volatile("mapa.shared::cluster.u32 %0, %1, %2;" : "=r"(r) : "r"(addr), "r"(rank)); return r;
}
__device__ __forceinline__ void cluster_sync_all() {
    asm volatile("barrier.cluster.arrive.release.aligned;\nbarrier.cluster.wait.acquire.aligned;" ::: "memory");
}
__device__ __forceinline__ void st_async_v4(uint32_t addr, uint32_t a, uint32_t b, uint32_t c, uint32_t d, uint32_t mbar) {
    asm volatile("st.async.weak.shared::cluster.mbarrier::complete_tx::bytes.v4.b32 [%0], {%1, %2, %3, %4}, [%5];"
                 :: "r"(addr), "r"(a), "r"(b), "r"(c), "r"(d), "r"(mbar) : "memory");
}
__device__ __forceinline__ void st_async_v2(uint32_t addr, uint32_t a, uint32_t b, uint32_t mbar) {
    asm volatile("st.async.weak.shared::cluster.mbarrier::complete_tx::bytes.v2.b32 [%0], {%1, %2}, [%3];"
                 :: "r"(addr), "r"(a), "r"(b), "r"(mbar) : "memory");
}
__device__ __forceinline__ void st_async_b32(uint32_t addr, uint32_t a, uint32_t mbar) {
    asm volatile("st.async.weak.shared::cluster.mbarrier::complete_tx::bytes.b32 [%0], %1, [%2];" :: "r"(addr), "r"(a), "r"(mbar) : "memory");
}
__device__ __forceinline__ void pace(int cycles) {
    if (cycles > 0) {
        uint32_t t0, t;
        asm volatile("mov.u32 %0, %%clock;" : "=r"(t0));
        do { asm volatile("mov.u32 %0, %%clock;" : "=r"(t)); } while (t - t0 < (uint32_t)cycles);
    }
}
__device__ __forceinline__ void mbar_wait_cl(uint32_t bar, uint32_t parity) {
    uint32_t done = 0;
    for (int it = 0; it < WAIT_LIMIT && !done; it++) {
        asm volatile(
            "{\n.reg .pred p;\n"
            "mbarrier.try_wait.parity.shared::cta.b64 p, [%1], %2;\n"
            "selp.u32 %0, 1, 0, p;\n}\n" : "=r"(done) : "r"(bar), "r"(parity) : "memory");
    }
}
__device__ __forceinline__ void ldmatrix_x4(uint32_t& r0, uint32_t& r1, uint32_t& r2, uint32_t& r3, uint32_t addr) {
    asm volatile("ldmatrix.sync.aligned.m8n8.x4.shared.b16 {%0,%1,%2,%3}, [%4];"
                 : "=r"(r0), "=r"(r1), "=r"(r2), "=r"(r3) : "r"(addr));
}
__device__ __forceinline__ void cp_async16(uint32_t dst, const void* src) {
    asm volatile("cp.async.cg.shared.global [%0], [%1], 16;" :: "r"(dst), "l"(src) : "memory");
}
__device__ __forceinline__ float bf16r(float x) { return __uint_as_float(pack_bf16(0.f, x) & 0xffff0000u); }

#define DBGP(i, w, ok)
#define DBG(i, w)
#define DBGD(i, w, dep)
#define DBG_EXTRA 0
__device__ __forceinline__ void tma_load_2d_mc(uint32_t dst, const CUtensorMap* map, uint32_t bar, int c0, int c1, uint16_t mask) {
    asm volatile(
        "cp.async.bulk.tensor.2d.shared::cluster.global.mbarrier::complete_tx::bytes.multicast::cluster [%0], [%1, {%3, %4}], [%2], %5;"
        :: "r"(dst), "l"((uint64_t)map), "r"(bar), "r"(c0), "r"(c1), "h"(mask) : "memory");
}
__device__ __forceinline__ void stmatrix_x4_trans(uint32_t addr, uint32_t r0, uint32_t r1, uint32_t r2, uint32_t r3) {
    asm volatile("stmatrix.sync.aligned.m8n8.x4.trans.shared.b16 [%0], {%1, %2, %3, %4};" :: "r"(addr), "r"(r0), "r"(r1), "r"(r2), "r"(r3) : "memory");
}
__device__ __forceinline__ void stmatrix_x2_trans(uint32_t addr, uint32_t r0, uint32_t r1) {
    asm volatile("stmatrix.sync.aligned.m8n8.x2.trans.shared.b16 [%0], {%1, %2};" :: "r"(addr), "r"(r0), "r"(r1) : "memory");
}
__device__ __forceinline__ uint4 lds128(uint32_t a) {
    uint4 v; asm volatile("ld.shared.v4.u32 {%0, %1, %2, %3}, [%4];" : "=r"(v.x), "=r"(v.y), "=r"(v.z), "=r"(v.w) : "r"(a) : "memory"); return v;
}
__device__ __forceinline__ void sts128(uint32_t a, uint32_t x, uint32_t y, uint32_t z, uint32_t w) {
    asm volatile("st.shared.v4.b32 [%0], {%1, %2, %3, %4};" :: "r"(a), "r"(x), "r"(y), "r"(z), "r"(w) : "memory");
}
__device__ __forceinline__ float2 lds64f(uint32_t a) {
    float2 v; asm volatile("ld.shared.v2.f32 {%0, %1}, [%2];" : "=f"(v.x), "=f"(v.y) : "r"(a) : "memory"); return v;
}
__device__ __forceinline__ void fence_async_smem() { asm volatile("fence.proxy.async.shared::cta;" ::: "memory"); }
#define ACC16(d) "+f"(d[0]), "+f"(d[1]), "+f"(d[2]), "+f"(d[3]), "+f"(d[4]), "+f"(d[5]), "+f"(d[6]), "+f"(d[7]), "+f"(d[8]), "+f"(d[9]), "+f"(d[10]), "+f"(d[11]), "+f"(d[12]), "+f"(d[13]), "+f"(d[14]), "+f"(d[15])
template <int ND>
__device__ __forceinline__ void wgmma_rs_n32(float (&d)[ND], const uint32_t (&a)[4], uint32_t db_lo, int scale_d) {
    asm volatile(
        "{\n.reg .pred p;\n.reg .b64 db;\nsetp.ne.b32 p, %21, 0;\nmov.b64 db, {%20, 0x40000040};\n"
        "wgmma.mma_async.sync.aligned.m64n32k16.f32.bf16.bf16 {%0,%1,%2,%3,%4,%5,%6,%7,%8,%9,%10,%11,%12,%13,%14,%15}, {%16,%17,%18,%19}, db, p, 1, 1, 0;\n}\n"
        : ACC16(d) : "r"(a[0]), "r"(a[1]), "r"(a[2]), "r"(a[3]), "r"(db_lo), "r"(scale_d));
}
template <int ND>
__device__ __forceinline__ void wgmma_ss_n32(float (&d)[ND], uint32_t da_lo, uint32_t db_lo, int scale_d) {
    asm volatile(
        "{\n.reg .pred p;\n.reg .b64 da, db;\nsetp.ne.b32 p, %18, 0;\nmov.b64 da, {%16, 0x40000040};\nmov.b64 db, {%17, 0x40000040};\n"
        "wgmma.mma_async.sync.aligned.m64n32k16.f32.bf16.bf16 {%0,%1,%2,%3,%4,%5,%6,%7,%8,%9,%10,%11,%12,%13,%14,%15}, da, db, p, 1, 1, 1, 0;\n}\n"
        : ACC16(d) : "r"(da_lo), "r"(db_lo), "r"(scale_d));
}
__device__ __forceinline__ void wgmma_ss_n8(float (&d)[4], uint32_t da_lo, uint32_t db_lo, int scale_d) {
    asm volatile(
        "{\n.reg .pred p;\n.reg .b64 da, db;\nsetp.ne.b32 p, %6, 0;\nmov.b64 da, {%4, 0x40000040};\nmov.b64 db, {%5, 0x00000010};\n"
        "wgmma.mma_async.sync.aligned.m64n8k16.f32.bf16.bf16 {%0,%1,%2,%3}, da, db, p, 1, 1, 1, 0;\n}\n"
        : "+f"(d[0]), "+f"(d[1]), "+f"(d[2]), "+f"(d[3]) : "r"(da_lo), "r"(db_lo), "r"(scale_d));
}

#define SCHED_FENCE()
__device__ __forceinline__ void wgmma_ss_n32_p(float (&d)[16], uint32_t da_lo, uint32_t db_lo, int scale_d) {
    asm volatile(
        "{\n.reg .pred p;\n.reg .b64 da, db;\nsetp.ne.b32 p, %18, 0;\nmov.b64 da, {%16, 0x40000040};\nmov.b64 db, {%17, 0x00000030};\n"
        "wgmma.mma_async.sync.aligned.m64n32k16.f32.bf16.bf16 {%0,%1,%2,%3,%4,%5,%6,%7,%8,%9,%10,%11,%12,%13,%14,%15}, da, db, p, 1, 1, 1, 0;\n}\n"
        : ACC16(d) : "r"(da_lo), "r"(db_lo), "r"(scale_d));
}

#define ACC20(d) ACC16(d), "+f"(d[16]), "+f"(d[17]), "+f"(d[18]), "+f"(d[19])
#define ACC20_STR "{%0,%1,%2,%3,%4,%5,%6,%7,%8,%9,%10,%11,%12,%13,%14,%15,%16,%17,%18,%19}"
__device__ __forceinline__ void wgmma_rs_n40(float (&d)[20], const uint32_t (&a)[4], uint32_t db_lo, int scale_d) {
    asm volatile(
        "{\n.reg .pred p;\n.reg .b64 db;\nsetp.ne.b32 p, %25, 0;\nmov.b64 db, {%24, 0x40000040};\n"
        "wgmma.mma_async.sync.aligned.m64n40k16.f32.bf16.bf16 " ACC20_STR ", {%20,%21,%22,%23}, db, p, 1, 1, 0;\n}\n"
        : ACC20(d) : "r"(a[0]), "r"(a[1]), "r"(a[2]), "r"(a[3]), "r"(db_lo), "r"(scale_d));
}
template <int TA, int SBO>
__device__ __forceinline__ void wgmma_ss_n40(float (&d)[20], uint32_t da_lo, uint32_t db_lo, int scale_d) {
    asm volatile(
        "{\n.reg .pred p;\n.reg .b64 da, db;\nsetp.ne.b32 p, %22, 0;\nmov.b64 da, {%20, %23};\nmov.b64 db, {%21, 0x40000040};\n"
        "wgmma.mma_async.sync.aligned.m64n40k16.f32.bf16.bf16 " ACC20_STR ", da, db, p, 1, 1, %24, 0;\n}\n"
        : ACC20(d) : "r"(da_lo), "r"(db_lo), "r"(scale_d), "n"(0x40000000 + SBO / 16), "n"(TA));
}
template <int SBO>
__device__ __forceinline__ void wgmma_ss_n48(float (&d)[24], uint32_t da_lo, uint32_t db_lo, int scale_d) {
    asm volatile(
        "{\n.reg .pred p;\n.reg .b64 da, db;\nsetp.ne.b32 p, %26, 0;\nmov.b64 da, {%24, %27};\nmov.b64 db, {%25, 0x40000040};\n"
        "wgmma.mma_async.sync.aligned.m64n48k16.f32.bf16.bf16 {%0,%1,%2,%3,%4,%5,%6,%7,%8,%9,%10,%11,%12,%13,%14,%15,%16,%17,%18,%19,%20,%21,%22,%23}, da, db, p, 1, 1, 0, 0;\n}\n"
        : ACC20(d), "+f"(d[20]), "+f"(d[21]), "+f"(d[22]), "+f"(d[23]) : "r"(da_lo), "r"(db_lo), "r"(scale_d), "n"(0x40000000 + SBO / 16));
}

#define PT(i, th)
struct ChainParams {
    CUtensorMap mapW[3];
    CUtensorMap mapX;
    CUtensorMap mapC;
    CUtensorMap mapWo;
    CUtensorMap mapM;
    CUtensorMap mapOut;
};
constexpr int CH_BLOCK = 384;
constexpr int CO_WO = 0;
constexpr int CH_XC = 5120, CH_XP = 8 * CH_XC;
constexpr int CO_XB = 65536;
constexpr int CO_OB = CO_XB + 2 * CH_XP;
constexpr int CO_P = CO_OB + 8192;
constexpr int CO_LS = CO_P + 3072;
constexpr int CO_SC = CO_LS + 8 * 1280;
constexpr int CH_TW = 6144 + 8192;
constexpr int CO_T = 21 * 8192;
constexpr int CO_WA = CO_T + 6144;
constexpr int CO_ST = CO_T + 3 * CH_TW + 6144;
constexpr int CO_OWN = CO_ST + 4096, CO_OWN2 = CO_SC + 1536;
constexpr int CO_BAR = CO_OWN + 4096;
constexpr int CH_SMEM = CO_BAR + 256 + DBG_EXTRA;
#define CH_GL 2
#define CH_A3 1
#define CH_D0 0
#define CH_PF 0
#define CH_NA 0
#define CH_LQ ""
#define CH_SQ ""
#define CH_XPF 0
#define CH_NSM 4
static_assert(CO_OWN2 + 1024 <= CO_T && CH_NSM <= 4, "smem layout");
#define CH_POLL_DELAY 240
#define CH_VPOS 2
#define CH_OW 12
#define CH_OF 12
#define CH_Q0 0
#define CH_QI 12
#define CH_QX 0
#define CH_Q1 (CH_Q0 + CH_QI + CH_QX)
#define CH_VA 5
#define CH_SPOS 0
#define CH_LSW 1
#define CH_QE 16
#define CH_KE 16
#define CH_QD 0
#define CH_GAP 0
#define CH_QS 0
#define CH_KS 0
#define CH_VS 4
#define CH_A7 7
#define CH_RF 0
#define CH_LSS 0
#define CH_OS 1
#define CH_MG 0
#define CH_MBT 0x76543210u
#define CH_MB(i) ((int)(CH_MBT >> 4 * (i)) & 7)
#define CH_AS 0x64207531u
#define CH_QL 16
#define CH_ML 0x112112
#define CH_DEP 1
#define CH_SP 2
#define CH_VD 0
#define CH_MP 2
#define CH_MP0 2
#define CH_OFE 3
#define CH_MS 1
#define CH_HA 3
#define CH_LD 4
#define CH_TWP 0
#define CH_SUMC 4
#define CH_ES 0
#define CH_ST 224
#define CH_KEEP 1
#define CH_PINB 1
#define CH_DRY 1
#define CH_D1 4500
#define CH_D2 11000
#define CH_CHAINS 4

constexpr float CH_SC = 0.08838834764831845f * 1.4426950408889634f;
__device__ __forceinline__ uint32_t pin(uint32_t v) { return __shfl_sync(0xffffffff, v, threadIdx.x & 31); }

__device__ __forceinline__ void out_finished() {
    if (atomicAdd(&g_ctr[CT_FIN], 1u) == M_GRID + 64 - 1)
        for (int i = 0; i < CT_N / 4; i++) reinterpret_cast<uint4*>(g_ctr)[i] = make_uint4(0u, 0u, 0u, 0u);
}
__device__ __forceinline__ uint32_t tail_a(uint32_t c) { return c < 3 ? CO_XB + 2 * CH_XC + c * 8192 : CO_OB; }
__device__ __forceinline__ void out_flush_half(const float* acc, const CUtensorMap* map, uint32_t stg, int tid, int bar, int n0, int m0) {
    const int lane = tid & 31, row = (lane & 7) + ((lane >> 3) & 1) * 8;
#pragma unroll
    for (int j = 0; j < 16; j += 2) {
        const float* a = &acc[j * 4];
        stmatrix_x4(stg + (j >> 3) * 8192 + (((tid >> 5) & 3) * 16 + row) * 128 + ((((j & 7) + (lane >> 4)) ^ (row & 7)) << 4),
                    pack_bf16(a[0], a[1]), pack_bf16(a[2], a[3]), pack_bf16(a[4], a[5]), pack_bf16(a[6], a[7]));
    }
    asm volatile("fence.proxy.async.shared::cta;\nbar.sync %0, 128;" :: "r"(bar) : "memory");
    asm volatile("{\n.reg .pred p;\nsetp.ne.b32 p, %0, 0;\n@p bra FL_SKIP;\n"
                 "cp.reduce.async.bulk.tensor.2d.global.shared::cta.add.tile.bulk_group [%1, {%3, %5}], [%2];\n"
                 "cp.reduce.async.bulk.tensor.2d.global.shared::cta.add.tile.bulk_group [%1, {%4, %5}], [%2 + 8192];\n"
                 "cp.async.bulk.commit_group;\nFL_SKIP:\n}"
                 :: "r"(tid & 127), "l"((uint64_t)map), "r"(stg), "r"(n0), "r"(n0 + 64), "r"(m0) : "memory");
    __syncwarp();
}
__device__ __forceinline__ void out_flush(const float (&acc)[128], const CUtensorMap* map, uint32_t stg0, uint32_t stg1, int tid, int bar, int n0, int m0) {
    out_flush_half(acc, map, stg0, tid, bar, n0, m0);
    out_flush_half(acc + 64, map, stg1, tid, bar, n0 + 128, m0);
}

__global__ void __cluster_dims__(8, 1, 1) __launch_bounds__(CH_BLOCK, 1)
chain_kernel(const __grid_constant__ ChainParams P) {
    extern __shared__ uint8_t smem_raw[];
    const int tid = threadIdx.x, warp = __shfl_sync(0xffffffff, tid >> 5, 0), lane = tid & 31;
    const int rank = (int)cluster_ctarank();
    constexpr uint32_t sd = 1024;
    const uint32_t sb = ((uint32_t)rank << 24) + sd;
    if (smem_u32(smem_raw) != sb) __trap();
    const int C = blockIdx.x >> 3;
    const int h = C * 4 + (rank >> 1);
    const int qd = lane >> 2, qc = lane & 3;
    const int t4 = warp & 3, wg = warp >> 2;
    pdl_launch_dependents();
    uint32_t t_start;
    asm volatile("mov.u32 %0, %%clock;" : "=r"(t_start));
    t_start = __shfl_sync(0xffffffff, t_start, 0);
    TS_BEGIN(2);
    PT(0, 0);
    const uint32_t bar_mem = sb + CO_BAR + 128, bar_o = sb + CO_BAR + 32, bar_sc = bar_o + 32, bar_x = bar_sc + 8, bar_l = bar_x + 16, bar_w = bar_l + 8;
    const uint32_t bar_wo = bar_o + 24;
    auto chunk = [&](int i) { return (uint32_t)((rank - i) & 7); };
    auto mine = [](int g, int c) { return (int)((CH_AS >> (g * 16 + c * 4)) & 7); };
    const int wcol = h * HD + (rank & 1) * 64;
    auto wdst = [&](int g, int i) { return i == 0 ? CO_WA + g * CH_TW : g && i == 7 ? CO_ST : (g ? CO_XB + CH_XP : 0) + (i - 1) * 8192; };
    auto vdst = [&](int i) { return i >= 2 && i < 10 ? CO_XB + CH_XP + (i - 2) * CH_XC : (i < 2 ? CO_WA + 2 * CH_TW : i < 12 ? CO_OB : i < 14 ? CO_LS : CO_ST) + (i & 1) * 4096; };
    if ((tid & 127) == 0) {
        pace(CH_D0);
        const uint32_t bar = wg == 2 ? bar_x : bar_w + 8 * wg;
        mbar_init(bar, 1);
        asm volatile("fence.mbarrier_init.release.cluster;" ::: "memory");
        mbar_expect_tx(bar, wg == 2 ? CH_XP : 65536);
#pragma unroll 1
        for (int i = 0; i < 8; i++) {
            if (wg == 2) {
                tma_load_2d(sb + CO_XB + i * CH_XC, &P.mapX, bar, i * 64, 0);
                tma_load_2d(sb + CO_XB + i * CH_XC + 4096, &P.mapM, bar, i * 64, 0);
            } else tma_load_2d(sb + wdst(wg, i), &P.mapW[wg ^ (i & 1)], bar, wcol, chunk(mine(wg, i >> 1)) * 64);
        }
    }
    if (warp == 9 && lane < 24 && lane != 9 && (lane >> 1) != 6) {
        mbar_init(sb + CO_BAR + 8 * lane, lane == 15 ? 16 : 1);
        asm volatile("fence.mbarrier_init.release.cluster;" ::: "memory");
    }
    __syncthreads();
    PT(1, 0);
    if (wg == 2 || (wg == 0 && CH_QL < 16)) asm volatile("bar.arrive 10, %0;" :: "n"(CH_QL < 16 ? 384 : 256) : "memory");
    if (wg == 2) {
        const int t = tid - 256;
        sts128(sb + CO_T + (2 + (t >> 6)) * CH_TW + 5120 + (t & 63) * 16, 0u, 0u, 0u, 0u);
        if (t < 32) sts128(sb + CO_P + (t >> 3) * 768 + 640 + (t & 7) * 16, 0u, 0u, 0u, 0u);
    }
    const uint32_t wfrag = (((lane >> 4) << 3) + (lane & 7)) * 128 + (((t4 * 2 + ((lane >> 3) & 1)) ^ (lane & 7)) << 4);
    const uint32_t aO = pin(sb + wg * CH_TW + wfrag);
    const uint32_t aL = pin(sb + lane * 16);
    uint32_t w[32][4];
    auto load_w = [&](int g, bool v) {
#pragma unroll
        for (int e = CH_NSM; e < 32; e++) ldmatrix_x4_trans(w[e][0], w[e][1], w[e][2], w[e][3], aO + ((v ? vdst(e >> 1) + (e & 1) * 2048 : wdst(g, e >> 2) + (e & 3) * 2048) - g * CH_TW));
        fence_async_smem();
    };
    auto pass = [&](auto& d, int g, int b, int j0, int j1, int js, bool group = true) {
        const uint32_t lo = desc_lo(sd + CO_XB + b * CH_XP, 16);
        if (group) wgmma_fence();
#pragma unroll
        for (int j = 0; j < 32; j++) if (j >= j0 && j < j1) {
            const int f = js < 0 ? j : j < js ? j + CH_NSM : j < js + CH_NSM ? j - js : j;
            const int e = sizeof(d) == 64 ? (f >> 2) * 8 + (js < 0 ? 4 : 0) + (f & 3) : f;
            const uint32_t db = lo + chunk(sizeof(d) == 64 ? mine(g, f >> 2) : f >> 2) * (CH_XC / 16) + (e & 3) * 2, da = desc_lo(sd + CO_WA + g * CH_TW + e * 2048, 16);
            if constexpr (sizeof(d) == 64) { if (e < CH_NSM) wgmma_ss_n32(d, da, db, j != 0); else wgmma_rs_n32(d, w[e], db, j != 0); }
            else { if (e < CH_NSM) wgmma_ss_n40<1, 1024>(d, da, db, j != 0); else wgmma_rs_n40(d, w[e], db, j != 0); }
        }
        if (group) wgmma_commit();
    };
    auto uni = [](uint32_t v) { return __shfl_sync(0xffffffff, v, 0); };
    auto roff = [&](int j) { return (uint32_t)(((rank + j) & 7) - rank) << 24; };
    auto store32 = [&](const float* d, uint32_t a) {
        stmatrix_x4_trans(a, pack_bf16(d[0], d[1]), pack_bf16(d[2], d[3]), pack_bf16(d[4], d[5]), pack_bf16(d[6], d[7]));
        stmatrix_x4_trans(a + 2048, pack_bf16(d[8], d[9]), pack_bf16(d[10], d[11]), pack_bf16(d[12], d[13]), pack_bf16(d[14], d[15]));
    };
    auto load32 = [&](uint32_t (&r)[8], uint32_t a) {
        ldmatrix_x4_trans(r[0], r[1], r[2], r[3], a);
        ldmatrix_x4_trans(r[4], r[5], r[6], r[7], a + 2048);
    };
    auto add32 = [&](float* d, const uint32_t (&r)[8], uint32_t a) {
        wgmma_wait<0>();
#pragma unroll
        for (int i = 0; i < 8; i++) { d[2 * i] += __uint_as_float(r[i] << 16); d[2 * i + 1] += __uint_as_float(r[i] & 0xffff0000u); }
        store32(d, a);
    };
    auto scores = [&](float (&d)[24], auto sbo, uint32_t q) {
        wgmma_fence();
#pragma unroll
        for (int ks = 0; ks < 4; ks++) wgmma_ss_n48<decltype(sbo)::value>(d, desc_lo(sd + q, 16) + ks * 2, desc_lo(sd + CO_T + CH_TW, 16) + ks * 2, ks != 0);
        wgmma_commit();
    };
    auto add_scores = [&](uint32_t a, uint32_t b, float (&v)[10]) {
        const uint4 a0 = lds128(a), a1 = lds128(a + 512);
        const float2 a2 = lds64f(b);
        v[0] += __uint_as_float(a0.x); v[1] += __uint_as_float(a0.y); v[2] += __uint_as_float(a0.z); v[3] += __uint_as_float(a0.w);
        v[4] += __uint_as_float(a1.x); v[5] += __uint_as_float(a1.y); v[6] += __uint_as_float(a1.z); v[7] += __uint_as_float(a1.w);
        v[8] += a2.x; v[9] += a2.y;
    };
    auto row_max = [&](const float (&v)[10]) {
        float mx = fmaxf(fmaxf(fmaxf(v[0], v[1]), fmaxf(v[2], v[3])), fmaxf(fmaxf(v[4], v[5]), fmaxf(v[6], v[7])));
        mx = fmaxf(mx, fmaxf(v[8], v[9]));
        mx = fmaxf(mx, __shfl_xor_sync(0xffffffff, mx, 1));
        return fmaxf(mx, __shfl_xor_sync(0xffffffff, mx, 2)) * CH_SC;
    };
    auto local_pv = [&](int s, int st) {
        float dc[16];
        wgmma_fence();
#pragma unroll
        for (int ks = 0; ks < 3; ks++) wgmma_ss_n32_p(dc, desc_lo(sd + CO_T + (2 + (s & 1)) * CH_TW + ks * 2048, 16), desc_lo(sd + CO_P + ks * 256, 128), ks != 0);
        wgmma_commit();
        wgmma_wait<0>();
        store32(dc, aO - CH_TW + st);
    };
    float gs = 0.f;
    auto load_gate = [&](int s) { asm volatile("ld.global.cg.f32 %0, [%1];" : "=f"(gs) : "l"(g_gate + s * SEGL + t4 * 8 + qd) : "memory"); };
    auto softmax = [&](int s, float (&u)[11]) {
        float v[10];
        {
            const uint4 a0 = lds128(aL + CO_OWN + t4 * 1024), a1 = lds128(aL + CO_OWN + t4 * 1024 + 512);
            const float2 a2 = lds64f(aL + CO_OWN2 + t4 * 256 - lane * 8);
            v[0] = __uint_as_float(a0.x); v[1] = __uint_as_float(a0.y); v[2] = __uint_as_float(a0.z); v[3] = __uint_as_float(a0.w);
            v[4] = __uint_as_float(a1.x); v[5] = __uint_as_float(a1.y); v[6] = __uint_as_float(a1.z); v[7] = __uint_as_float(a1.w);
            v[8] = a2.x; v[9] = a2.y;
        }
        mbar_wait_cl(bar_l, s & 1);
        add_scores(aL + t4 * 1024 + CO_LS + (s & 1) * 5120, aL + t4 * 256 - lane * 8 + CO_LS + (s & 1) * 5120 + 4096, v);
        const int lim = t4 * 8 + qd - 2 * qc;
#pragma unroll
        for (int j = 0; j < 8; j++) if ((j >> 1) * 8 + (j & 1) > lim) v[j] = -INFINITY;
        const float mx = row_max(v);
#pragma unroll
        for (int j = 0; j < 10; j++) u[j] = v[j];
        u[10] = mx;
    };
    auto softmax1 = [&](float (&u)[11]) {
#pragma unroll
        for (int j = 0; j < 10; j++) u[j] = ex2f(fmaf(u[j], CH_SC, -u[10]));
        u[10] = (((u[0] + u[1]) + (u[2] + u[3])) + ((u[4] + u[5]) + (u[6] + u[7]))) + (u[8] + u[9]);
    };
    auto softmax2 = [&](float (&v)[11]) {
        float sum = v[10];
        sum += __shfl_xor_sync(0xffffffff, sum, 1);
        sum += __shfl_xor_sync(0xffffffff, sum, 2);
        asm("rcp.approx.ftz.f32 %0, %0;" : "+f"(sum));
        sum *= 1.f - gs;
        const uint32_t pa = aL + CO_P + t4 * 768;
        stmatrix_x4(pa, pack_bf16(v[0] * sum, v[1] * sum), pack_bf16(v[2] * sum, v[3] * sum), pack_bf16(v[4] * sum, v[5] * sum), pack_bf16(v[6] * sum, v[7] * sum));
        asm volatile("stmatrix.sync.aligned.m8n8.x1.shared.b16 [%0], {%1};" :: "r"(pa + 512), "r"(pack_bf16(v[8] * sum, v[9] * sum)) : "memory");
    };
    if (mapa_u32(bar_l, rank ^ 1) != (bar_l ^ (1u << 24)) || mapa_u32(bar_l, (rank + 3) & 7) != bar_l + roff(3)) __trap();
    asm volatile("bar.sync %0, 128;" :: "r"(12 + wg) : "memory");
    if (__shfl_sync(0xffffffff, tid, 1) < 256) {
#pragma unroll 1
        for (int rep = CH_DRY ? 0 : 1; rep < 2; rep++) {
            if (rep) mbar_wait(bar_w + 8 * wg, 0);
            PT(3, 0);
            load_w(wg, false);
            if (rep) {
                asm volatile("bar.arrive %0, 160;" :: "r"(wg ? 2 : 15) : "memory");
                asm volatile("barrier.cluster.arrive.relaxed.aligned;" ::: "memory");
                mbar_wait(bar_x, 0);
            }
            asm volatile("bar.sync 12, 256;" ::: "memory");
            PT(7, 0);
            float d[16];
            pass(d, wg, 0, 0, 16, -1);
            wgmma_wait<0>();
            store32(d, aO + CO_T + (1 - 2 * wg) * CH_TW);
            pass(d, wg, 0, 0, 16, 0);
            asm volatile("bar.sync 13, 256;" ::: "memory");
            uint32_t r[8];
            load32(r, aO + CO_T);
            add32(d, r, aO + CO_T);
        }
    }
    PT(8, 0);
    TS_BEGIN(5);
    PT(9, 0);

    if (wg < 2) {
        const uint32_t aM = pin(sb + CO_XB + 4096 + (lane & 7) * 128 + (((lane >> 3) ^ (lane & 7)) << 4));
        uint32_t coff[4];
#pragma unroll
        for (int i = 0; i < 4; i++) coff[i] = uni(chunk(mine(wg, i)) * CH_XC);
        auto mem_proj = [&](int s, auto gc) {
            constexpr int G = decltype(gc)::value;
            const uint32_t par = s & 1;
            float acc[4][4];
#pragma unroll
            for (int i = 0; i < 4; i++) acc[i][0] = acc[i][1] = acc[i][2] = acc[i][3] = 0.f;
            const uint32_t am = aM + par * CH_XP;
            uint32_t b[4][4], ok = 1;
            auto bar = [&](int c) { return bar_mem + 8 * CH_MB(mine(G, c)); };
            auto load = [&](int c) {
                if (c ? CH_MB(mine(G, c)) != CH_MB(mine(G, c - 1)) : G == 0)
                    asm volatile("{\n.reg .pred p, q;\n.reg .u32 c;\nsetp.ne.u32 p, %2, 0;\n@p bra MP_DONE;\nmov.u32 c, 0;\n"
                                 "MP_LOOP:\nmbarrier.try_wait.parity.shared::cta.b64 p, [%0], %1;\nadd.u32 c, c, 1;\nsetp.lt.and.u32 q, c, %3, !p;\n"
                                 "@q bra MP_LOOP;\nMP_DONE:\n}" :: "r"(bar(c)), "r"(par ^ 1), "r"(ok), "n"(WAIT_LIMIT / 64) : "memory");
                uint32_t* r = b[2 * c & 3];
                ldmatrix_x4(r[0], r[1], r[2], r[3], am + coff[c]);
                r = b[(2 * c + 1) & 3];
                ldmatrix_x4(r[0], r[1], r[2], r[3], (am ^ 64) + coff[c]);
                if (c < 3 && CH_MB(mine(G, c + 1)) != CH_MB(mine(G, c))) ok = mbar_try(bar(c + 1), par ^ 1);
            };
            auto mma = [&](int i) {
#pragma unroll
                for (int j = 0; j < 4; j++) {
                    const uint32_t* a = w[(i >> 1) * 8 + ((j & 1) ^ G) * 4 + (i & 1) * 2 + (j >> 1)];
                    mma_16816(acc[j], a[0], a[1], a[2], a[3], b[i & 3][j & 2], b[i & 3][(j & 2) + 1]);
                }
            };
#pragma unroll
            for (int e = 0; e < CH_NSM; e++) ldmatrix_x4_trans(w[e][0], w[e][1], w[e][2], w[e][3], aO + CO_WA + e * 2048);
            if (G == 1) asm volatile("bar.sync 10, %0;" :: "n"(CH_QL < 16 ? 384 : 256) : "memory");
            else ok = mbar_try(bar(0), par ^ 1);
            DBG(11, 0);
            load(0);
#pragma unroll
            for (int c = 0; c < 3; c++) {
                const int at = (CH_ML >> (c * 4 + G * 12)) & 3;
                if (at == 0) load(c + 1);
                mma(2 * c);
                if (at == 1) load(c + 1);
                mma(2 * c + 1);
                if (at == 2) load(c + 1);
            }
            mma(6);
            uint32_t dep = __float_as_uint(acc[CH_HA & 3][0]);
            mma(7);
            if (CH_HA >= 4) dep = __float_as_uint(acc[CH_HA & 3][0]);
            asm volatile("bar.arrive %0, 384;" :: "r"(5 | (dep & (s >> 10))) : "memory");
            uint32_t r[4];
#pragma unroll
            for (int i = 0; i < 4; i++) r[i] = pack_bf16(acc[i >> 1][(i & 1) * 2] + acc[(i >> 1) + 2][(i & 1) * 2], acc[i >> 1][(i & 1) * 2 + 1] + acc[(i >> 1) + 2][(i & 1) * 2 + 1]);
            DBGD(40 + warp, warp, r[0] ^ r[1]);
            asm volatile("{\n.reg .pred q;\nsetp.ne.s32 q, %3, 0;\n"
                         "@q stmatrix.sync.aligned.m8n8.x2.trans.shared.b16 [%0], {%1, %2};\n"
                         "@q stmatrix.sync.aligned.m8n8.x2.trans.shared.b16 [%0 + %4], {%1, %2};\n"
                         "@q stmatrix.sync.aligned.m8n8.x2.trans.shared.b16 [%0 + 2 * %4], {%1, %2};\n"
                         "@q stmatrix.sync.aligned.m8n8.x2.trans.shared.b16 [%0 + 3 * %4], {%1, %2};\n}"
                         :: "r"(aO + (CO_XB + 4096 + G * (CH_XC - CH_TW) + (par ^ 1) * CH_XP)), "r"(r[0]), "r"(r[1]),
                            "r"(s - (NSEG - 1)), "n"(2 * CH_XC) : "memory");
            stmatrix_x2_trans(aO + CO_T + (G ? 5120 : CH_TW + 4096), r[2], r[3]);
            fence_async_smem();
        };
        if (wg == 0) {
#pragma unroll 1
            for (int s = 0; s < NSEG; s++) {
                const uint32_t par = s & 1;
                mem_proj(s, std::integral_constant<int, 0>());
                asm volatile("bar.arrive 1, 256;" ::: "memory");
                asm volatile("bar.sync 8, 384;" ::: "memory");
                if (s == NSEG - 1) break;
                if (tid == 96) {
#pragma unroll
                    for (int j = 1; j < 8; j++) {
                        int n = 0;
                        for (int i = 1; i < 8; i++) n += CH_MB(i) == j;
                        if (n) mbar_expect_tx(bar_mem + 8 * j, 1024 * n);
                        if (j < 4) mbar_expect_tx(bar_o + 8 * j - 8, 512 << j);
                    }
                }
                __syncwarp();
                uint32_t* wp = g_xbuf + (size_t)rank * 2048 + C * 256 + qc * 64 + t4 * 8 + qd;
                asm volatile("st.relaxed.gpu.global" CH_SQ ".u32 [%0], %1;" :: "l"(wp + ((s + 2) & 3) * 16384), "r"(~0u) : "memory");
                asm volatile("st.relaxed.gpu.global" CH_SQ ".u32 [%0], %1;" :: "l"(wp + ((s + 2) & 3) * 16384 + 32), "r"(~0u) : "memory");
                if (__builtin_expect(s == 0, 0)) {
                    asm volatile("barrier.cluster.wait.aligned;" ::: "memory");
                    mbar_wait(bar_wo, 0);
                    const int sr = (qd >> 2) * 2 + (qd & 1) + (qd & 2) * 4;
#pragma unroll 2
                    for (int ks = t4; ks < 32; ks += 4) {
                        const uint32_t a = sb + CO_WO + ks * 2048;
                        uint4 u[2][2];
#pragma unroll
                        for (int i = 0; i < 4; i++) { const int r = sr + (i >> 1) * 4; u[i >> 1][i & 1] = lds128(a + r * 128 + (((qc * 2 + (i & 1)) ^ (r & 7)) << 4)); }
                        __syncwarp();
#pragma unroll
                        for (int i = 0; i < 4; i++) {
                            const uint4 u0 = u[i >> 1][0], u1 = u[i >> 1][1];
                            const uint32_t sel = (i & 1) ? 0x7632 : 0x5410;
                            sts128(a + (qd + (i >> 1) * 8) * 128 + (((qc * 2 + (i & 1)) ^ qd) << 4),
                                   __byte_perm(u0.x, u0.y, sel), __byte_perm(u0.z, u0.w, sel), __byte_perm(u1.x, u1.y, sel), __byte_perm(u1.z, u1.w, sel));
                        }
                    }
                    fence_async_smem();
                }
                mbar_wait(bar_x + 8 * (par ^ 1), ((s + 1) >> 1) & 1);
                asm volatile("bar.sync 7, 384;" ::: "memory");
                float d[16];
                float c[4];
                const uint32_t alo = desc_lo(sd + CO_WO, 16), blo = desc_lo(sd + CO_OB, 128);
                wgmma_fence();
                pass(d, 0, par ^ 1, 0, CH_Q0, -1, false);
                asm volatile("bar.sync 11, 256;" ::: "memory");
#pragma unroll
                for (int i = 0; i < 32; i++) {
                    if (i == 4) { pass(d, 0, par ^ 1, CH_Q0 + min(4, CH_QI), CH_Q0 + min(4, CH_QI) + CH_QX, -1, false); mbar_wait_cl(bar_o, par); }
                    if (i == 8) mbar_wait_cl(bar_o + 8, par);
                    if (i == CH_OW) mbar_wait_cl(bar_o + 16, par);
                    wgmma_ss_n8(c, alo + i * 128, blo + i * 16, i != 0);
                    if (i < CH_QI) pass(d, 0, par ^ 1, CH_Q0 + i + (i < 4 ? 0 : CH_QX), CH_Q0 + i + (i < 4 ? 0 : CH_QX) + 1, -1, false);
                }
                wgmma_commit();
                wgmma_wait<0>();
                asm volatile("st.relaxed.gpu.global" CH_SQ ".u32 [%0], %1;" :: "l"(wp + (s & 3) * 16384), "r"(pack_bf16(c[0], c[2])) : "memory");
                asm volatile("st.relaxed.gpu.global" CH_SQ ".u32 [%0], %1;" :: "l"(wp + (s & 3) * 16384 + 32), "r"(pack_bf16(c[1], c[3])) : "memory");
                asm volatile("bar.arrive 6, 384;" ::: "memory");
                pace(CH_QD);
                asm volatile("bar.arrive 4, 384;" ::: "memory");
                DBG(8, 0);
                if (CH_Q1 < 16) pass(d, 0, par ^ 1, CH_Q1, 16, -1);
                asm volatile("bar.sync 9, 256;" ::: "memory");
                wgmma_wait<0>();
                store32(d, aO + CO_T + CH_TW);
                asm volatile("bar.arrive 12, 256;" ::: "memory");
                if (CH_QL) pass(d, 0, (par ^ 1) + (s >> 10), 0, CH_QL, CH_QS);
                DBG(21, 0);
                if (tid == 0) {
                    if (s + 2 < NSEG) {
                        mbar_expect_tx(bar_x + 8 * par, 32768);
                        tma_load_2d_mc(sb + CO_XB + par * CH_XP + rank * CH_XC, &P.mapX, bar_x + 8 * par, rank * 64, (s + 2) * SEGL, (uint16_t)0xff);
                        if (CH_XPF) asm volatile("cp.async.bulk.prefetch.tensor.2d.L2.global [%0, {%1, %2}];" :: "l"(&P.mapX), "r"(rank * 64), "r"((s + 2 + CH_XPF) * SEGL) : "memory");
                    } else {
#pragma unroll 1
                        for (int i = 0; i < 8; i++) tma_load_2d(sb + CO_WO + i * 8192, &P.mapWo, bar_wo, (rank & 3) * 128 + (i & 1) * 64, (h & ~1) * HD + (i >> 1) * 64);
                    }
                }
                __syncwarp();
                asm volatile("bar.sync 13, 256;" ::: "memory");
                uint32_t r[8];
                load32(r, aO + CO_T);
                if (CH_QL < 16) {
                    asm volatile("bar.sync 10, 384;" ::: "memory");
                    pass(d, 0, (par ^ 1) + (s >> 10), CH_QL, CH_QE, CH_QS);
                }
                add32(d, r, aO + CO_T);
                DBG(22, 0);
            }
            *reinterpret_cast<uint2*>(g_xbuf + 16384 + blockIdx.x * 256 + tid * 2) = make_uint2(~0u, ~0u);
        PT(10, 0);
            if (tid == 0) {
                mbar_expect_tx(bar_wo, 65536 + 32768);
                mbar_expect_tx(bar_w, 24576);
                asm volatile("prefetch.tensormap [%0];" :: "l"(&P.mapOut) : "memory");
                wait_ctr(CT_CA + 63, 16u);
            }
            __syncwarp();
            uint32_t fin = 0;
#pragma unroll 1
            for (int r = 0; r < 2; r++) {
                float acc[64];
                mbar_wait(bar_wo, 1);
                asm volatile("bar.sync %0, 256;" :: "r"(15 - r) : "memory");
                asm volatile("{\n.reg .pred p;\nsetp.eq.b32 p, %2, 32;\n@p atom.relaxed.gpu.global.inc.u32 %0, [%1], 0x7fffffff;\n}"
                             : "+r"(fin) : "l"(&g_ctr[CT_FIN]), "r"(tid + r * 128) : "memory");
                wgmma_fence();
#pragma unroll
                for (int i = 0; i < 16; i++) {
                    const uint32_t c = (rank + (i >> 2)) & 3;
                    const uint32_t a = r == 0 ? tail_a(c) : i < 4 ? CO_WA + CH_TW : CO_XB + CH_XP + c * 8192;
                    if (i == 4) mbar_wait(r ? bar_w : bar_wo, 1);
                    wgmma_ss_n128_lo<1>(acc, desc_lo(sd + a, 16) + (i & 3) * 2, desc_lo(sd + CO_WO, 8192) + c * 1024 + (i & 3) * 128, i);
                }
                wgmma_commit();
                wgmma_wait<0>();
                PT(5, 0);
                out_flush_half(acc, &P.mapOut, sb + (r ? tail_a(0) : CO_T), tid, 12, (rank & 3) * 128, SEQ - 128 + r * 64);
            }
            if (fin == M_GRID + 64 - 1)
                for (int i = 0; i < CT_N / 4; i++) reinterpret_cast<uint4*>(g_ctr)[i] = make_uint4(0u, 0u, 0u, 0u);
            if (tid == 0) {
                asm volatile("cp.async.bulk.wait_group.read 0;" ::: "memory");
                PT(15, 0);
            }
        } else {
            const uint32_t usc = uni(CO_SC + min(t4, 2) * 512 + roff((rank ^ 1) - rank)), uscb = uni(bar_sc ^ (1u << 24));
            const uint32_t vaddr = pin(sb + CO_T + 2 * CH_TW + (lane & 15) * 128 + (((t4 * 2 + (lane >> 4)) ^ (lane & 7)) << 4));
            const uint32_t dsta = pin(sb + CO_OB + t4 * 256 + (qc >> 1) * 128 + qd * 16 + (qc & 1) * 8);
            auto store_ctx = [&](int s) {
                if (tid == CH_ST && (uint32_t)s < NSEG - 3) {
                    tma_store_2d(&P.mapC, sb + CO_ST, (rank & 1) * 64, h * SEQ + s * SEGL);
                    asm volatile("cp.async.bulk.commit_group;" ::: "memory");
                }
                __syncwarp();
            };
            auto signal_ctx = [&](int s) {
                if (tid == CH_ST && (s & 3) == 1)
                    asm volatile("cp.async.bulk.wait_group 0;\nred.relaxed.gpu.global.add.u32 [%0], 1;" :: "l"(&g_ctr[CT_CB - 1 + (s >> 2)]) : "memory");
                __syncwarp();
            };
            uint32_t uo[8], ub[8];
#pragma unroll
            for (int i = 0; i < 8; i++) { uo[i] = uni(roff(i) + i * 1024); ub[i] = uni(roff(i) + bar_o + (i < 2 ? 0 : i < 4 ? 8 : 16)); }
#pragma unroll 1
            for (int s = 0; s < NSEG; s++) {
                const uint32_t par = s & 1;
                mem_proj(s, std::integral_constant<int, 1>());
                asm volatile("bar.sync 1, 256;" ::: "memory");
                float d[24];
                scores(d, std::integral_constant<int, CH_XC>(), CO_XB + 4096 + (par ^ 1) * CH_XP);
                if (s == NSEG - 1) { wgmma_wait<0>(); break; }
                asm volatile("bar.arrive 8, 384;" ::: "memory");
                if (s == 0) asm volatile("barrier.cluster.wait.aligned;" ::: "memory");
                const uint32_t sca = (aL | (s >> 10)) + usc;
                wgmma_wait<0>();
                float v[10], u[12];
#pragma unroll
                for (int j = 0; j < 12; j++) u[j] = d[(j >> 1) * 4 + (j & 1)] + d[(j >> 1) * 4 + (j & 1) + 2];
                if (t4 < 3) {
                    auto sel = [&](int j) { return t4 == 0 ? u[j] : t4 == 1 ? u[4 + j] : u[8 + j]; };
                    asm volatile("st.async.weak.shared::cluster.mbarrier::complete_tx::bytes.v4.f32 [%0], {%2, %3, %4, %5}, [%1];"
                                 :: "r"(sca), "r"(uscb), "f"(sel(0)), "f"(sel(1)), "f"(sel(2)), "f"(sel(3)) : "memory");
                }
#pragma unroll
                for (int j = 0; j < 10; j++) v[j] = j < 8 ? u[j] : u[j] + u[j + 2];
                DBG(3, 4);
                if (CH_ES) signal_ctx(s); else store_ctx(s - 2);
                uint32_t vb[3][4];
                auto load_v = [&](float dep) {
                    asm volatile("bar.sync %0, 256;" :: "r"(CH_VD ? 3 | (__float_as_uint(dep) & (s >> 10)) : 3) : "memory");
#pragma unroll
                    for (int k = 0; k < 3; k++) ldmatrix_x4_trans(vb[k][0], vb[k][1], vb[k][2], vb[k][3], vaddr + par * CH_TW + k * 2048);
                };
                mbar_wait_cl(bar_sc, par);
                DBG(4, 4);
                {
                    const uint4 a0 = lds128(aL + CO_SC), a1 = lds128(aL + CO_SC + 512), a2 = lds128(aL + CO_SC + 1024);
                    v[0] += __uint_as_float(a0.x); v[1] += __uint_as_float(a0.y); v[2] += __uint_as_float(a0.z); v[3] += __uint_as_float(a0.w);
                    v[4] += __uint_as_float(a1.x); v[5] += __uint_as_float(a1.y); v[6] += __uint_as_float(a1.z); v[7] += __uint_as_float(a1.w);
                    v[8] += __uint_as_float(a2.x) + __uint_as_float(a2.z); v[9] += __uint_as_float(a2.y) + __uint_as_float(a2.w);
                }
                const float mx = row_max(v);
                if (CH_VPOS == 2) load_v(mx);
#pragma unroll
                for (int j = 0; j < 10; j++) v[j] = ex2f(fmaf(v[j], CH_SC, -mx));
                uint32_t p[5];
#pragma unroll
                for (int j = 0; j < 5; j++) p[j] = pack_bf16(v[2 * j], v[2 * j + 1]);
                if (CH_VPOS == 3) load_v(v[CH_VD]);
                DBG(19, 4);
                float c0[4] = {0.f, 0.f, 0.f, 0.f}, c1[4] = {0.f, 0.f, 0.f, 0.f}, cs[4] = {0.f, 0.f, 0.f, 0.f};
#pragma unroll
                for (int k = 0; k < 3; k++) {
                    const uint32_t p0 = p[2 * k], p1 = k < 2 ? p[2 * k + 1] : 0u;
                    mma_16816(cs, p0, 0u, p1, 0u, 0x3f803f80u, 0x3f803f80u);
                    mma_16816(c0, p0, 0u, p1, 0u, vb[k][0], vb[k][1]);
                    mma_16816(c1, p0, 0u, p1, 0u, vb[k][2], vb[k][3]);
                }
                float inv;
                asm volatile("rcp.approx.ftz.f32 %0, %1;" : "=f"(inv) : "f"(cs[0]));
                const uint32_t b0 = pack_bf16(c0[0] * inv, c0[1] * inv), b1 = pack_bf16(c1[0] * inv, c1[1] * inv);
                DBG(20, 4);
#pragma unroll
                for (int i = 1; i < 8; i++) {
                    st_async_v2((dsta | (s >> 10)) + uo[i], b0, b1, ub[i]);
                    if (i == CH_OS) asm volatile("st.shared.v2.b32 [%0], {%1, %2};" :: "r"(dsta), "r"(b0), "r"(b1) : "memory");
                    if (i == CH_OFE) asm volatile("fence.proxy.async.shared::cta;\nbar.arrive 11, 256;" ::: "memory");
                }
                DBG(5, 4);
                asm volatile("cp.async.bulk.wait_group.read 0;" ::: "memory");
                asm volatile("bar.sync 7, 384;" ::: "memory");
                if (CH_OFE > 7) asm volatile("fence.proxy.async.shared::cta;\nbar.arrive 11, 256;" ::: "memory");
                local_pv(s + 1, CO_ST);
                if (CH_ES) fence_async_smem();
                asm volatile("bar.arrive 6, 384;" ::: "memory");
                if (tid == 128) mbar_expect_tx(bar_sc, 1536);
                __syncwarp();
                mbar_wait(bar_x + 8 * (par ^ 1), ((s + 1) >> 1) & 1);
                asm volatile("bar.sync 4, 384;" ::: "memory");
                float dk[16];
                pass(dk, 1, par ^ 1, 0, 16, -1);
                wgmma_wait<0>();
                store32(dk, aO + CO_T - CH_TW);
                asm volatile("bar.arrive 13, 256;" ::: "memory");
                pass(dk, 1, (par ^ 1) + (s >> 10), 0, CH_KE, CH_KS);
                if (CH_ES) store_ctx(s - 1); else signal_ctx(s);
                DBG(1, 4);
                asm volatile("bar.sync 12, 256;" ::: "memory");
                uint32_t r[8];
                load32(r, aO + CO_T);
                add32(dk, r, aO + CO_T);
                DBG(29, 4);
            }
        }
    } else {
        {
            PT(2, 256);
            int lane;
            asm volatile("mov.u32 %0, %%laneid;" : "=r"(lane));
            if (t4 >= 2) {
                const CUtensorMap* map = t4 == 2 ? &P.mapWo : &P.mapW[2];
                const uint32_t bar = t4 == 2 ? bar_wo : bar_w + 16;
                const int c0 = t4 == 2 ? rank * 64 : wcol;
                auto row = [&](int i) { return t4 == 2 ? C * 512 + ((rank - i) & 7) * 64 : (int)chunk(i >> 1) * 64 + (i & 1) * 32; };
                uint32_t now;
                do { asm volatile("mov.u32 %0, %%clock;" : "=r"(now)); } while (now - t_start < (uint32_t)(t4 == 2 ? CH_D2 : CH_D1));
                if (lane == 0) {
#pragma unroll 1
                    for (int i = 0; i < (CH_PF == 2 ? t4 * 8 - 8 : CH_PF * (t4 * 16 - 32)); i++) asm volatile("cp.async.bulk.prefetch.tensor.2d.L2.global [%0, {%1, %2}];" :: "l"(map), "r"(c0), "r"(row(i)) : "memory");
                    mbar_expect_tx(bar, 65536);
                }
                __syncwarp();
                asm volatile("bar.sync %0, 160;" :: "r"(t4 == 2 ? 15 : 2) : "memory");
                if (lane == 0) {
#pragma unroll 1
                    for (int i = 0; i < t4 * 8 - 8; i++) tma_load_2d(sb + (t4 == 2 ? CO_WO + i * 8192 : vdst(i)), map, bar, c0, row(i));
                }
            } else if (t4 == 0 && lane == 0) {
                asm volatile("cp.async.bulk.prefetch.tensor.2d.L2.global [%0, {%1, %2}];" :: "l"(&P.mapX), "r"(rank * 64), "r"(SEGL) : "memory");
                asm volatile("prefetch.tensormap [%0];" :: "l"(&P.mapC) : "memory");
                mbar_expect_tx(bar_sc, 1536);
                mbar_expect_tx(bar_x + 8, 32768);
            }
            __syncwarp();
            mbar_wait(bar_w + 16, 0);
            PT(4, 256);
            load_w(2, true);
            asm volatile("bar.sync 14, 128;" ::: "memory");
            asm volatile("barrier.cluster.arrive.relaxed.aligned;" ::: "memory");
            if (t4 == 0 && lane == 0) {
#pragma unroll 1
                for (int i = 0; i < 8; i++) tma_load_2d(sb + CO_XB + CH_XP + i * CH_XC, &P.mapX, bar_x + 8, i * 64, SEGL);
            }
            __syncwarp();
            PT(6, 256);
        }
#pragma unroll 1
        for (int s = 0; s < NSEG; s++) {
            const uint32_t par = s & 1;
            const bool last = s == NSEG - 1;
            if (CH_GL < 2) {
                if (s == 1) wait_ctr(CT_GATE, 256u);
                load_gate(max(s - 1, 0));
                if (CH_GL) asm volatile("prefetch.global.L2 [%0];" :: "l"(g_gate + ((s + 1) & (NSEG - 1)) * SEGL) : "memory");
            } else if (s == 1) { wait_ctr(CT_GATE, 256u); load_gate(0); }
            float v[11];
            if (CH_SP) fence_async_smem();
            softmax(s - 1, v);
            if (CH_SP < 2) softmax1(v);
            DBG(7, 8);
            if (!CH_SP) fence_async_smem();
            asm volatile("bar.sync %0, 384;" :: "r"(CH_SP ? 5 | (__float_as_uint(v[10]) & (s >> 10)) : 5) : "memory");
            DBG(23, 8);
            float dv[20], d[24];
            pass(dv, 2, par, 0, CH_VA, CH_VS);
            asm volatile("bar.sync 8, 384;" ::: "memory");
            pass(dv, 2, par, CH_VA, 32, CH_VS);
            if (CH_SP == 2) {
                uint32_t z;
                asm volatile("mov.u32 %0, %%clock;" : "=r"(z) :: "memory");
                v[10] = __uint_as_float(__float_as_uint(v[10]) | (z & (s >> 10)));
                softmax1(v);
                asm volatile("{\n.reg .pred p;\nsetp.ne.s32 p, %0, 1000001;\n@p bra SP_SKIP;\nwgmma.wait_group.sync.aligned 0;\n"
                             "st.volatile.shared.f32 [%0], %1;\nexit;\nSP_SKIP:\n}" :: "r"(s), "f"(v[10]) : "memory");
            }
            wgmma_wait<0>();
            stmatrix_x2_trans(aO + par * CH_TW + CO_T + 4096, pack_bf16(dv[16], dv[17]), pack_bf16(dv[18], dv[19]));
            store32(dv, aO + par * CH_TW + CO_T);
            DBG(24, 8);
            uint32_t z3 = __float_as_uint(dv[0]);
            if (CH_A3) asm volatile("{\n.reg .pred p;\nsetp.ne.s32 p, %1, %2;\n@p bar.arrive 3, 256;\nmov.u32 %0, %%clock;\n}" : "=r"(z3) : "r"(s), "n"(NSEG - 1) : "memory");
            else if (!last) asm volatile("bar.arrive 3, 256;" ::: "memory");
            if (CH_SP) { v[10] = __uint_as_float(__float_as_uint(v[10]) | (z3 & (s >> 10))); softmax2(v); fence_async_smem(); }
            if (CH_GL == 2) load_gate(s);
            if (last) asm volatile("bar.arrive 7, 256;" ::: "memory"); else asm volatile("bar.sync 7, 384;" ::: "memory");
            scores(d, std::integral_constant<int, 512>(), CO_T);
            asm volatile("{\n.reg .pred p;\nsetp.eq.s32 p, %1, 256;\n@p mbarrier.arrive.expect_tx.shared::cta.b64 _, [%0], 5120;\n}" :: "r"(bar_l), "r"(tid) : "memory");
            wgmma_wait<0>();
            d[16] += d[20]; d[17] += d[21];
            auto send_scores = [&]() {
                const uint32_t a = aL + t4 * 1024, a2 = aL + t4 * 256 - lane * 8, r = roff((rank ^ 1) - rank) + CO_LS + par * 5120;
                asm volatile("st.async.weak.shared::cluster.mbarrier::complete_tx::bytes.v4.f32 [%0], {%3, %4, %5, %6}, [%2];\n"
                             "st.async.weak.shared::cluster.mbarrier::complete_tx::bytes.v4.f32 [%0 + 512], {%7, %8, %9, %10}, [%2];\n"
                             "st.async.weak.shared::cluster.mbarrier::complete_tx::bytes.v2.f32 [%1], {%11, %12}, [%2];"
                             :: "r"(a + r), "r"(a2 + r + 4096), "r"(bar_l ^ (1u << 24)), "f"(d[0]), "f"(d[1]), "f"(d[4]), "f"(d[5]),
                                "f"(d[8]), "f"(d[9]), "f"(d[12]), "f"(d[13]), "f"(d[16]), "f"(d[17]) : "memory");
            };
            auto keep_scores = [&]() {
                const uint32_t a = aL + t4 * 1024, a2 = aL + t4 * 256 - lane * 8;
                sts128(a + CO_OWN, __float_as_uint(d[0]), __float_as_uint(d[1]), __float_as_uint(d[4]), __float_as_uint(d[5]));
                sts128(a + CO_OWN + 512, __float_as_uint(d[8]), __float_as_uint(d[9]), __float_as_uint(d[12]), __float_as_uint(d[13]));
                asm volatile("st.shared.v2.f32 [%0], {%1, %2};" :: "r"(a2 + CO_OWN2), "f"(d[16]), "f"(d[17]) : "memory");
            };
            if (s == 0) asm volatile("barrier.cluster.wait.aligned;" ::: "memory");
            if (CH_LSS == 0) send_scores();
            if (CH_KEEP == 0) keep_scores();
            if (last) { if (CH_LSS) send_scores(); if (CH_KEEP) keep_scores(); break; }
            asm volatile("bar.arrive 4, 384;\nbar.arrive 9, 256;" ::: "memory");
            uint32_t t0, t1;
            if (!CH_PINB) asm volatile("bar.sync 6, 384;\nmov.u32 %0, %%clock;" : "=r"(t0) :: "memory");
            const int row = t4 * 2 + (lane >> 4);
            const uint32_t dsta = pin(sb + CO_XB + (par ^ 1) * CH_XP + rank * CH_XC + 4096 + row * 128 + ((((lane & 15) >> 1) ^ row) << 4) + (lane & 1) * 8);
            uint32_t dst1 = pin(dsta + roff(1)), bar1 = pin((bar_mem + 8 + roff(1)) | (s >> 10));
            uint32_t sel = pin(((qd >> 1) == qc ? 0x3f80u << (qd & 1) * 16 : 0u) | (s >> 10));
            const uint2* xb = reinterpret_cast<const uint2*>(g_xbuf + (s & 3) * 16384 + (size_t)rank * 2048 + t4 * 64) + pin(lane | (s >> 10));
            if (CH_PINB) asm volatile("bar.sync %1, 384;\nmov.u32 %0, %%clock;" : "=r"(t0) : "r"(6 | (dst1 & sel & (uint32_t)(size_t)xb & (s >> 10))) : "memory");
            if (CH_LSS == 1) send_scores();
            if (CH_KEEP == 2) keep_scores();
            uint2 p[8], q[8];
            do { asm volatile("mov.u32 %0, %%clock;" : "=r"(t1) :: "memory"); } while (t1 - t0 < CH_POLL_DELAY);
#pragma unroll
            for (int k = 0; k < 8; k++)
                asm volatile("ld.relaxed.gpu.global" CH_LQ ".v2.u32 {%0, %1}, [%2];" : "=r"(p[k].x), "=r"(p[k].y) : "l"(xb + k * 128) : "memory");
            DBG(17, 8);
            if (CH_LSS == 2) send_scores();
            if (CH_KEEP == 1) keep_scores();
            {
                uint32_t z;
                asm volatile("mov.u32 %0, %%clock;" : "=r"(z) :: "memory");
#pragma unroll
                for (int i = 0; i < CH_GAP; i++) asm volatile("{\n.reg .f32 f;\nmov.b32 f, %0;\nex2.approx.ftz.f32 f, f;\nmov.b32 %0, f;\n}" : "+r"(z));
                asm volatile("and.b32 %0, %0, %1;" : "+r"(z) : "r"(s >> 10));
                xb += z;
            }
#pragma unroll
            for (int k = 0; k < 8; k++)
                asm volatile("ld.relaxed.gpu.global" CH_LQ ".v2.u32 {%0, %1}, [%2];" : "=r"(q[k].x), "=r"(q[k].y) : "l"(xb + k * 128) : "memory");
            if (CH_LSS == 3) send_scores();
            if (CH_KEEP == 3) keep_scores();
            uint32_t m0, m1;
            {
                uint32_t z;
                asm volatile("mov.u32 %0, %%clock;" : "=r"(z) :: "memory");
                sel |= z & (s >> 10);
            }
            auto sum = [&](const uint2 (&p)[8]) {
                float c[CH_SUMC][4];
#pragma unroll
                for (int k = 0; k < 4; k++) {
                    if (k < CH_SUMC) c[k][0] = c[k][1] = c[k][2] = c[k][3] = 0.f;
                    mma_16816(c[k % CH_SUMC], p[2 * k].x, p[2 * k].y, p[2 * k + 1].x, p[2 * k + 1].y, sel, sel);
                }
#pragma unroll
                for (int k = 1; k < CH_SUMC; k++) { c[0][0] += c[k][0]; c[0][1] += c[k][1]; c[0][2] += c[k][2]; c[0][3] += c[k][3]; }
                m0 = pack_bf16(c[0][0], c[0][1]);
                m1 = pack_bf16(c[0][2], c[0][3]);
                uint32_t ok;
                asm volatile("{\n.reg .pred p;\nsetp.num.f32 p, %1, %2;\nvote.sync.all.pred p, p, 0xffffffff;\nselp.u32 %0, 1, 0, p;\n}" : "=r"(ok) : "f"(c[0][0]), "f"(c[0][2]));
                return ok;
            };
            if (__builtin_expect(!sum(p), 0)) {
                DBG(12, 8);
#pragma unroll 1
                for (int it = 0; it < WAIT_LIMIT / 4; it++) {
                    if (sum(q)) break;
                    uint32_t bad = 0;
#pragma unroll
                    for (int k = 0; k < 8; k++) bad |= (max(q[k].x, q[k].y) == ~0u ? 1u : 0u) << k;
                    if (__all_sync(0xffffffff, bad == 0u)) break;
                    if (it == 0) DBG(14, 8);
                    if (it == 1) DBG(15, 8);
#pragma unroll
                    for (int k = 0; k < 8; k++)
                        if (bad & (1u << k))
                            asm volatile("ld.relaxed.gpu.global" CH_LQ ".v2.u32 {%0, %1}, [%2];" : "=r"(q[k].x), "=r"(q[k].y) : "l"(xb + k * 128) : "memory");
                }
            }
            DBG(9, 8);
            st_async_v2(dst1, m0, m1, bar1);
            asm volatile("st.shared.v2.b32 [%0], {%1, %2};\nbar.arrive 10, %3;" :: "r"(dsta), "r"(m0), "r"(m1), "n"(CH_QL < 16 ? 384 : 256) : "memory");
#pragma unroll 1
            for (int i = 0; i < 6; i += CH_MP) {
#pragma unroll
                for (int j = 0; j < CH_MP; j++) {
                    dst1 = (dst1 + (1u << 24)) & 0x7ffffffu; bar1 = (bar1 + (1u << 24) + 8) & 0x7ffffffu;
                    st_async_v2(dst1, m0, m1, bar1);
                }
            }
            if (s == 1000000) {
#pragma unroll
                for (int k = 0; k < 8; k++) asm volatile("st.volatile.shared.v2.u32 [%0], {%1, %2};" :: "r"(s), "r"(q[k].x), "r"(q[k].y) : "memory");
            }
            DBG(10, 8);
        }
    }
    const int wgt = __shfl_sync(0xffffffff, tid >> 7, 0);
    if (wgt == 1) {
        asm volatile("bar.arrive 8, 384;" ::: "memory");
        auto copy = [&](uint32_t dst, uint32_t src, uint32_t bar) {
            asm volatile("cp.async.bulk.shared::cluster.shared::cta.mbarrier::complete_tx::bytes [%0], [%1], 4096, [%2];" :: "r"(dst), "r"(src), "r"(bar) : "memory");
        };
        const uint32_t peer = (uint32_t)(tid & 3) << 24;
        if ((tid & ~3) == CH_ST) {
            copy((sb + tail_a(rank & 3) + 4096) ^ peer, sb + CO_ST, bar_wo ^ peer);
            if (tid == CH_ST) {
                asm volatile("cp.async.bulk.wait_group 0;" ::: "memory");
                tma_load_2d_mc(sb + tail_a(rank & 3), &P.mapC, bar_wo, (rank & 1) * 64, h * SEQ + SEQ - 128, (uint16_t)(15 << (rank & 4)));
            }
        }
        __syncwarp();
        asm volatile("bar.sync 7, 256;" ::: "memory");
#pragma unroll 1
        for (int i = 0; i < 2; i++) {
            local_pv(i, CO_WA + CH_TW + i * 4096);
            fence_async_smem();
            asm volatile("bar.arrive %0, 256;" :: "r"(i ? 14 : 9) : "memory");
            asm volatile("bar.sync 2, 128;" ::: "memory");
            if (tid > 128 && tid < 132) {
                mbar_wait(sb + CO_BAR + 120, 0);
                copy((sb + CO_XB + CH_XP + (rank & 3) * 8192 + i * 4096) ^ peer, sb + CO_WA + CH_TW + i * 4096, bar_w ^ peer);
            }
            __syncwarp();
            if (i == 0) asm volatile("bar.sync 3, 256;" ::: "memory");
        }
        PT(14, 128);
    } else if (wgt == 2) {
        PT(11, 256);
        if (CH_GL < 2) load_gate(NSEG - 1);
        if ((tid & 31) < 4) asm volatile("mbarrier.arrive.relaxed.cluster.shared::cluster.b64 _, [%0];" :: "r"((sb + CO_BAR + 120) ^ ((tid & 3) << 24)) : "memory");
        asm volatile("bar.arrive 15, 256;\nbar.sync 9, 256;" ::: "memory");
        float v[11];
        softmax(NSEG - 1, v);
        softmax1(v);
        softmax2(v);
        fence_async_smem();
        asm volatile("bar.arrive 3, 256;" ::: "memory");
    }
    __syncthreads();
    asm volatile("barrier.cluster.arrive.relaxed.aligned;\nbarrier.cluster.wait.aligned;" ::: "memory");
    TS_END(2);
}

struct Proj2Params {
    CUtensorMap mapA[2];
    CUtensorMap mapW[3];
    bf16* out[3];
};
#define P2T(i)
#define P2_NOMMA 0
#define P2_NOLOAD 0
#define P2_ROT 4
#define P2_NP 1
#define P2_NI 4
constexpr int P2_STAGES = 6;
constexpr int P2_ITEMS = 168 + 48;

__device__ __forceinline__ int p2_reps(int t) { return t >= 168 ? 1 : 2; }
__device__ __forceinline__ void p2_tile(int t, int w, int& z, int& mp, int& head) {
    if (t >= 168) { w += ((t - 168) & 1) * 2; t = 168 + ((t - 168) >> 1); }
    const int hq = (t / 24 + P2_ROT) & 7, v = t % 24;
    mp = v & 7;
    if (v < 16) { head = hq * 4 + (v >> 3) * 2 + (w >> 1); z = 1 + (w & 1); }
    else { head = hq * 4 + w; z = 0; }
}
__device__ __forceinline__ void mbar_arrive_remote(uint32_t bar_cluster_addr) {
    asm volatile("mbarrier.arrive.release.cluster.shared::cluster.b64 _, [%0];" :: "r"(bar_cluster_addr) : "memory");
}
__device__ __forceinline__ void mbar_arrive_cl(uint32_t bar_cluster_addr) {
    asm volatile("mbarrier.arrive.shared::cluster.b64 _, [%0];" :: "r"(bar_cluster_addr) : "memory");
}
__device__ __forceinline__ void mbar_wait_acq_cluster(uint32_t bar, uint32_t parity) {
    asm volatile(
        "{\n"
        ".reg .pred p, q;\n"
        ".reg .u32 c;\n"
        "mov.u32 c, 0;\n"
        "WAIT_LOOP_C:\n"
        "mbarrier.try_wait.parity.acquire.cluster.shared::cta.b64 p, [%0], %1;\n"
        "@p bra WAIT_DONE_C;\n"
        "add.u32 c, c, 1;\n"
        "setp.lt.u32 q, c, 4000000;\n"
        "@q bra WAIT_LOOP_C;\n"
        "WAIT_DONE_C:\n"
        "}\n" :: "r"(bar), "r"(parity) : "memory");
}
__device__ __forceinline__ uint4 quad_transpose(uint32_t p0, uint32_t p1, uint32_t p2, uint32_t p3, int lane) {
    const bool o1 = lane & 1, o2 = lane & 2;
    uint32_t s0 = o1 ? p0 : p1, s1 = o1 ? p2 : p3;
    s0 = __shfl_xor_sync(0xffffffff, s0, 1); s1 = __shfl_xor_sync(0xffffffff, s1, 1);
    const uint32_t a_lo = o1 ? s0 : p0, a_hi = o1 ? p1 : s0, b_lo = o1 ? s1 : p2, b_hi = o1 ? p3 : s1;
    uint32_t t0 = o2 ? a_lo : b_lo, t1 = o2 ? a_hi : b_hi;
    t0 = __shfl_xor_sync(0xffffffff, t0, 2); t1 = __shfl_xor_sync(0xffffffff, t1, 2);
    return o2 ? make_uint4(t0, t1, b_lo, b_hi) : make_uint4(a_lo, a_hi, t0, t1);
}
#define P2_PACE 35
#define P2_PACE2 0
#define P2_STM 1
#define P2_STQ ".L1::no_allocate"
#define P2_NOF 0
#define P2_HO 7
#define P2_PRE 0
template <int PACE>
__device__ __forceinline__ void store_frag_128(const float (&acc)[64], bf16* obase) {
    uint32_t p[32];
#pragma unroll
    for (int i = 0; i < 32; i++) p[i] = pack_bf16(acc[2 * i], acc[2 * i + 1]);
    if (P2_PRE) {
#pragma unroll
        for (int i = 0; i < 32; i += 8) asm volatile("" : "+r"(p[i]), "+r"(p[i + 1]), "+r"(p[i + 2]), "+r"(p[i + 3]), "+r"(p[i + 4]), "+r"(p[i + 5]), "+r"(p[i + 6]), "+r"(p[i + 7]));
    }
#pragma unroll
    for (int rr = 0; rr < 2; rr++)
#pragma unroll
        for (int g = 0; g < 4; g++) {
            const uint32_t* a = &p[g * 8 + rr];
            asm volatile("st.global" P2_STQ ".v4.b32 [%0], {%1, %2, %3, %4};" :: "l"(obase + (size_t)(rr * 8) * HD + g * 32), "r"(a[0]), "r"(a[2]), "r"(a[4]), "r"(a[6]) : "memory");
            pace(PACE);
        }
}
struct OutParams {
    CUtensorMap mapCtx[2];
    CUtensorMap mapWo[2];
    CUtensorMap mapOut;
};

#define OT(i)
#define OTP(i, th)
constexpr int O2_STAGES = 4;
constexpr int O2_GRID = 0;
#define O2_FINE 6
#define O2_Q0 8
#define O2_Q1 9
#define O2_Q2 17
#define O2_N0 60
#define O2_RL 0
#define O2_QA 13

constexpr uint32_t OB_FULL = 0, OB_EMPTY = 32, OB_ITEM = 64, OB_SLOT = 128, OB_STOP = 160;
__device__ __forceinline__ void out_init(uint32_t bars) {
    for (int i = 0; i < O2_STAGES; i++) {
        mbar_init(bars + OB_FULL + 8 * i, 1); mbar_init(bars + OB_EMPTY + 8 * i, 4); mbar_init(bars + OB_ITEM + 16 * i, 1); mbar_init(bars + OB_ITEM + 16 * i + 8, 1);
    }
    sts128(bars + OB_STOP, 0u, 0u, 0u, 0u);
}
struct OutJob { int tg, q, qe, last, t0, nw, nq; };
__device__ __forceinline__ OutJob out_job(int cid, int j) {
    auto quota = [](int tg) { return tg & 2 ? O2_Q0 : O2_Q1; };
    auto split = [](int tg) { return O2_Q2 && (tg >> 2) == 1; };
    constexpr int NL = O2_Q2 ? 4 : 0;
    if (cid < 28 && j == 0) {
        const int tg = cid % 14, h = cid >= 14, nq = 128 - quota(tg);
        if (split(tg)) return {tg, h ? O2_N0 + O2_Q2 : 0, h ? 128 : O2_N0, !h, 128, 0, 0};
        return {tg, 2 * h, 2 * h + 2, 1, 2, nq / 2 - O2_FINE, nq};
    }
    if (j == (cid < 30 ? 1 : 4)) { const int i = cid < 28 ? cid + 16 : cid; return {16, 2 * i + 8, 2 * i + 10, 1, 38 + NL, 64 - O2_FINE, 128}; }
    if (cid < 30) return {cid - 14, O2_QA, 64, 0, 0, 0, 0};
    const int tg = (j * 4 + cid - 32) & 15;
    if (split(tg)) return {tg, O2_N0, O2_N0 + O2_Q2, 0, 0, 0, 0};
    return {tg, tg >= 14 ? 0 : 128 - quota(tg), tg >= 14 ? O2_QA : 128, 0, 0, 0, 0};
}
__device__ __forceinline__ int out_mt(int tg, int rank) { return tg < 16 ? (tg & ~1) + rank : tg - 2; }
__device__ __forceinline__ int out_n0(int tg, int rank) { return (tg < 16 ? tg & 1 : rank) * 256; }
__device__ __forceinline__ void out_producer(const OutParams& P, uint32_t sbase, uint32_t bars, uint32_t rank, int cid, bool lead) {
    const uint32_t bar_full = bars + OB_FULL, bar_empty = bars + OB_EMPTY, bar_item = bars + OB_ITEM, slot = bars + OB_SLOT, stop = bars + OB_STOP;
    int s = 0, nb = 0; uint32_t ph = 0;
    if (lead) asm volatile("prefetch.tensormap [%0];" :: "l"(&P.mapOut) : "memory");
#pragma unroll 1
    for (int job = 0;; job++) {
        const OutJob J = out_job(cid, job);
        const int mt = out_mt(J.tg, rank), m0 = mt * 128, n0 = out_n0(J.tg, rank);
        int ready = 0, q = J.q, qe = J.qe, tnext = 0, nst = 0;
        if (lead && rank == 0 && J.last) tnext = take_ticket(CT_OT + J.tg);
#pragma unroll 1
        for (int ic = 0;; ic++) {
#pragma unroll 1
            for (bool first = true; q < qe; q++, first = false) {
                const int b = q >> 6, head = (q >> 1) & 31, dk = (q & 1) * 64;
                mbar_wait(bar_empty + 8 * s, ph);
                const uint32_t sa = sbase + s * 49152;
                if (lead) {
                    if (rank == 0 && J.last && first) {
                        const int t = tnext + J.t0;
                        asm volatile("st.shared.s32 [%0], %1;" :: "r"(slot + (ic & 7) * 4), "r"(t) : "memory");
                        mbar_arrive(bar_item + 8 * (ic & 7));
                        st_async_b32(mapa_u32(slot + (ic & 7) * 4, 1), (uint32_t)t, mapa_u32(bar_item + 8 * (ic & 7), 1));
                        if (J.nw + t < J.nq) tnext = take_ticket(CT_OT + J.tg);
                    }
                    if (b ? mt >= nb : !((ready >> (head >> 3)) & 1)) {
                        if (b) nb = max(mt, 11) + 1; else ready |= 1 << (head >> 3);
                        wait_ctr(b ? CT_CB + nb - 1 : CT_CA + mt * 4 + (head >> 3), b ? 64u : 16u);
                    }
                    asm volatile("st.shared.s32 [%0], %1;" :: "r"(stop + s * 4), "r"(0) : "memory");
                    mbar_expect_tx(bar_full + 8 * s, 49152);
                    tma_load_2d(sa, &P.mapCtx[b], bar_full + 8 * s, dk, head * SEQ + m0);
                    if (++nst == 6 && !(ready & 8)) { wait_ctr(CT_CA + mt * 4 + 3, 16u); ready |= 8; }
                } else if (J.tg < 16) {
                    for (int j = (int)rank * 2; j < (int)rank * 2 + 2; j++)
                        tma_load_2d_mc(sa + 16384 + j * 8192, &P.mapWo[b], bar_full + 8 * s, n0 + j * 64, head * HD + dk, (uint16_t)3);
                } else {
                    for (int j = 0; j < 4; j++) tma_load_2d(sa + 16384 + j * 8192, &P.mapWo[1], bar_full + 8 * s, n0 + j * 64, head * HD + dk);
                }
                if (++s == O2_STAGES) { s = 0; ph ^= 1; }
            }
            if (!J.last) break;
            if (lead && rank == 1) mbar_expect_tx(bar_item + 8 * (ic & 7), 4);
            mbar_wait(bar_item + 8 * (ic & 7), (ic >> 3) & 1);
            int t;
            asm volatile("ld.shared.s32 %0, [%1];" : "=r"(t) : "r"(slot + (ic & 7) * 4) : "memory");
            if (J.nw + t >= J.nq) break;
            if (t < J.nw) { q = 2 * t; qe = q + 2; } else { q = J.nw + t; qe = q + 1; }
        }
        if (lead) {
            if (!(ready & 8)) wait_ctr(CT_CA + mt * 4 + 3, 16u);
            mbar_wait(bar_empty + 8 * s, ph);
            asm volatile("st.shared.s32 [%0], %1;" :: "r"(stop + s * 4), "r"(1 + J.last + n0 + (m0 << 4)) : "memory");
            mbar_arrive(bar_full + 8 * s);
        }
        if (J.last) break;
        if (++s == O2_STAGES) { s = 0; ph ^= 1; }
    }
    if (lead) {
        out_finished();
        for (int i = 1; i < O2_STAGES; i++) {
            if (++s == O2_STAGES) { s = 0; ph ^= 1; }
            mbar_wait(bar_empty + 8 * s, ph);
        }
    }
}
__device__ __forceinline__ void out_consumer(const OutParams& P, uint32_t sbase, uint32_t bars, int warp, uint32_t opar) {
    const uint32_t bar_full = bars + OB_FULL, bar_empty = bars + OB_EMPTY, stop = bars + OB_STOP;
    int tid;
    asm volatile("mov.u32 %0, %%tid.x;" : "=r"(tid));
    const int wg = warp >> 2;
    const bool elected = (tid & 127) == 0;
    auto release = [&](int s) { if (elected) { const uint32_t e = bar_empty + 8 * s; mbar_arrive_cl(mapa_u32(e, 0)); mbar_arrive_cl(mapa_u32(e, 1)); } };
    float acc[128];
    int s = 0, sprev = 0, st, n = 0; uint32_t ph = 0;
#pragma unroll 1
    do {
#pragma unroll 1
        for (int i = 0;; i++, n++) {
            mbar_wait(bar_full + 8 * s, ph);
            asm volatile("ld.shared.s32 %0, [%1];" : "=r"(st) : "r"(stop + s * 4) : "memory");
            if (st) break;
            if (n == 0) OT(1);
            const uint32_t sa = sbase + s * 49152 + wg * 8192, sb = sbase + s * 49152 + 16384;
            wgmma_fence();
#pragma unroll
            for (int kk = 0; kk < 4; kk++)
                wgmma_ss_n256_tb(acc, make_desc(sa + kk * 32, 16, 1024), make_desc(sb + kk * 2048, 8192, 1024), kk ? 1 : i);
            wgmma_commit();
            if (i > 0) { wgmma_wait<1>(); release(sprev); }
            if (i == O2_RL && n > 1) {
                if (elected) asm volatile("cp.async.bulk.wait_group.read 1;" ::: "memory");
                release((s + 3 - O2_RL) & 3);
            }
            sprev = s;
            if (++s == O2_STAGES) { s = 0; ph ^= 1; }
        }
        mbar_wait(sbase + FB_OE + 8 * wg, opar);
        if (elected) asm volatile("cp.async.bulk.wait_group.read 0;" ::: "memory");
        wgmma_wait<0>();
        release(sprev);
        asm volatile("bar.sync %0, 128;" :: "r"(1 + wg) : "memory");
        OT(3);
        out_flush(acc, &P.mapOut, sbase + s * 49152 + wg * 16384, sbase + O2_STAGES * 49152 + wg * 16384, tid, 1 + wg, st & 256, (st >> 4 & ~127) + wg * 64);
        if (++s == O2_STAGES) { s = 0; ph ^= 1; }
    } while (!(st & 2));
    OT(4);
    if (elected) {
        asm volatile("cp.async.bulk.wait_group.read 0;" ::: "memory");
    }
}

struct MainParams { Proj2Params p; AttnParams a; OutParams o; const bf16 *x, *gate_w; };
__device__ __forceinline__ int p2_apos(int k) { return k < 2 ? k : k < 6 ? k + 2 : k - 4; }
__global__ void __cluster_dims__(2, 1, 1) __launch_bounds__(384, 1) main_kernel(const __grid_constant__ MainParams MP) {
    const Proj2Params& P = MP.p;
    extern __shared__ uint8_t smem_raw[];
    const uint32_t rank = cluster_ctarank();
    const uint32_t sbase = (rank << 24) + SD;
    if (smem_u32(smem_raw) != sbase) __trap();
    const uint32_t sA = sbase, sB = sbase + 131072;
    const uint32_t bars = sbase + MO_BAR, obars = bars + 768;
    const uint32_t a_full = bars, a_empty = bars + 64, b_full = bars + 128, b_empty = b_full + 8 * P2_STAGES;
    const uint32_t item_bar = b_empty + 8 * P2_STAGES, item_in = item_bar + 16, slot = item_in + 16;
    const uint32_t note_bar = slot + 16, note_free = note_bar + 64, note = note_free + 64;
    const int warp = __shfl_sync(0xffffffff, threadIdx.x >> 5, 0), lane = threadIdx.x & 31;
    TS_BEGIN(0);
    if (threadIdx.x == 0) {
        for (int i = 0; i < 8; i++) { mbar_init(a_full + 8 * i, 1); mbar_init(a_empty + 8 * i, 2); }
        for (int i = 0; i < P2_STAGES; i++) { mbar_init(b_full + 8 * i, 1); mbar_init(b_empty + 8 * i, 2); }
        mbar_init(item_bar, 1); mbar_init(item_bar + 8, 1); mbar_init(item_in, 2); mbar_init(item_in + 8, 2);
        for (int i = 0; i < 8; i++) { mbar_init(note_bar + 8 * i, 4); mbar_init(note_free + 8 * i, 1); }
        asm volatile("fence.mbarrier_init.release.cluster;" ::: "memory");
    }
    if (threadIdx.x == 32) {
        attn_init(sbase);
        asm volatile("fence.mbarrier_init.release.cluster;" ::: "memory");
    }
    if (threadIdx.x == 256) {
        out_init(obars);
        asm volatile("fence.mbarrier_init.release.cluster;" ::: "memory");
    }
    __syncthreads();
    asm volatile("barrier.cluster.arrive.relaxed.aligned;" ::: "memory");
    if (warp >= 8) {
    asm volatile("setmaxnreg.dec.sync.aligned.u32 40;");
    asm volatile("barrier.cluster.wait.aligned;" ::: "memory");
    if (warp == 9) {
        if (lane == 0) {
            for (int n = 0;; n++) {
                const int e = (n & 1) * 4 + ((n >> 1) & 3);
                mbar_wait(note_bar + 8 * e, (n >> 3) & 1);
                int m;
                asm volatile("ld.shared.s32 %0, [%1];" : "=r"(m) : "r"(note + e * 4) : "memory");
                mbar_arrive(note_free + 8 * e);
                if (m < 0) break;
                signal_ctr(m);
            }
            attn_helper(MP.a, sbase, 0);
        }
    } else if (warp == 10) {
        if (lane == 0) {
            auto publish = [&](int ic, int tq) {
                const int t = tq < P2_ITEMS ? tq : -1;
                asm volatile("st.shared.s32 [%0], %1;" :: "r"(slot + (ic & 3) * 4), "r"(t) : "memory");
                mbar_arrive(item_bar + 8 * (ic & 1));
                st_async_b32(mapa_u32(slot + (ic & 3) * 4, 1), (uint32_t)t, mapa_u32(item_bar + 8 * (ic & 1), 1));
            };
            const int npair = M_GRID / 2, pair = (int)(blockIdx.x >> 1);
            if (rank == 0) publish(0, pair);
            for (int ic = 0;; ic++) {
                if (rank == 1) mbar_expect_tx(item_bar + 8 * (ic & 1), 4);
                mbar_wait(item_bar + 8 * (ic & 1), (ic >> 1) & 1);
                int t;
                asm volatile("ld.shared.s32 %0, [%1];" : "=r"(t) : "r"(slot + (ic & 3) * 4) : "memory");
                if (t < 0) break;
                int z0, mp, h0;
                p2_tile(t, 0, z0, mp, h0);
                const int aidx = z0 >= 1 ? 1 : 0;
                const int m0 = (2 * mp + (int)rank) * 128;
                for (int k = 0; k < 8; k++) {
                    mbar_wait(a_empty + 8 * k, (ic & 1) ^ 1);
                    if (P2_NOLOAD) mbar_arrive(a_full + 8 * k); else {
                    mbar_expect_tx(a_full + 8 * k, 16384);
                    tma_load_2d(sA + p2_apos(k) * 16384, &P.mapA[aidx], a_full + 8 * k, k * 64, m0); }
                }
                if (rank == 0) {
                    mbar_wait(item_in + 8 * (ic & 1), (ic >> 1) & 1);
                    publish(ic + 1, ic == 0 ? npair + pair : pair < P2_NP && ic + 1 >= P2_NI ? P2_ITEMS : 2 * npair + (int)atomicAdd(&g_ctr[CT_PROJ], 1u));
                }
            }
            attn_helper(MP.a, sbase, 1);
        }
    } else {
        if (lane == 0) {
            const int par2 = warp == 8 ? 0 : 1;
            int it = 0, ic = 0; uint32_t bph = 0;
            for (;; ic++) {
                mbar_wait(item_bar + 8 * (ic & 1), (ic >> 1) & 1);
                int t;
                asm volatile("ld.shared.s32 %0, [%1];" : "=r"(t) : "r"(slot + (ic & 3) * 4) : "memory");
                if (t < 0) break;
                const int nt = 2 * p2_reps(t);
                for (int w = 0; w < nt; w++) {
                    int z, mp, hd;
                    p2_tile(t, w, z, mp, hd);
                    for (int k = 0; k < 8; k++) {
                        const int s = it; const uint32_t phb = bph;
                        if (++it == P2_STAGES) { it = 0; bph ^= 1; }
                        if ((k & 1) != par2) continue;
                        mbar_wait(b_empty + 8 * s, phb ^ 1);
                        if (P2_NOLOAD) { mbar_arrive(b_full + 8 * s); continue; }
                        mbar_expect_tx(b_full + 8 * s, 16384);
                        tma_load_2d_mc(sB + s * 16384 + rank * 8192, &P.mapW[z], b_full + 8 * s, hd * 128 + (int)rank * 64, k * 64, (uint16_t)3);
                    }
                }
            }
            if (warp == 8) {
                attn_producer(MP.a, sbase, a_empty, ~ic & 1);
                TS_END2(1, 256); TS_BEGIN2(3, 256);
                for (int i = 0; i < 4; i++) {
                    const uint32_t e = mapa_u32(obars + OB_EMPTY + 8 * (i & 1), i >> 1);
                    mbar_arrive_cl(e); mbar_arrive_cl(e);
                }
            }
            out_producer(MP.o, sbase, obars, rank, blockIdx.x >> 1, warp == 8);
            TS_END2(3, 256);
        }
    }
    } else {
        asm volatile("setmaxnreg.inc.sync.aligned.u32 232;");
        asm volatile("barrier.cluster.wait.aligned;" ::: "memory");
        const int wg = warp >> 2;
        float acc[2][64];
        const uint32_t a_lo = desc_lo(SD, 16), b_lo0 = desc_lo(SD + 131072, 8192);
        const bool elected = (threadIdx.x & 127) == 0;
        int s = (wg * 8) % P2_STAGES;
        uint32_t ph = ((wg * 8) / P2_STAGES) & 1;
        int nnote = 0;
        if (wg == 1) {
            asm volatile("bar.arrive 3, 256;" ::: "memory");
            if (blockIdx.x < 64) {
                const int r = blockIdx.x * 32 + (warp & 3) * 8 + (lane >> 2);
                float c[4] = {0.f, 0.f, 0.f, 0.f};
                uint4 xv[16], gv[16];
#pragma unroll
                for (int i = 0; i < 16; i++) {
                    xv[i] = __ldg(reinterpret_cast<const uint4*>(MP.x + (size_t)r * DM + i * 32 + (lane & 3) * 8));
                    gv[i] = __ldg(reinterpret_cast<const uint4*>(MP.gate_w + i * 32 + (lane & 3) * 8));
                }
                auto mul = [](uint32_t a, uint32_t b) { uint32_t p; asm("mul.rn.bf16x2 %0, %1, %2;" : "=r"(p) : "r"(a), "r"(b)); return p; };
#pragma unroll
                for (int i = 0; i < 16; i++)
                    mma_16816(c, mul(xv[i].x, gv[i].x), mul(xv[i].y, gv[i].y), mul(xv[i].z, gv[i].z), mul(xv[i].w, gv[i].w), 0x3f803f80u, 0x3f803f80u);
                if ((lane & 3) == 0) g_gate[r] = bf16r(__fdividef(1.f, 1.f + __expf(-bf16r(c[0] + c[2]))));
                __syncwarp();
                if (lane == 0) signal_ctr_generic(CT_GATE);
                __syncwarp();
            }
        }
        auto next_item = [&](int ic) {
            mbar_wait(item_bar + 8 * (ic & 1), (ic >> 1) & 1);
            int t;
            asm volatile("ld.shared.s32 %0, [%1];" : "=r"(t) : "r"(slot + (ic & 3) * 4) : "memory");
            return __shfl_sync(0xffffffff, t, 0);
        };
        int t = next_item(0), ic = 0, rp = 0;
#pragma unroll 1
        while (t >= 0) {
            const bool first = rp == 0, last = rp == p2_reps(t) - 1;
            asm volatile("bar.sync %0, 256;" :: "r"(3 + wg) : "memory");
            P2T(0);
            if (wg == 1 && last && elected) mbar_arrive_cl(mapa_u32(item_in + 8 * (ic & 1), 0));
            int sprev = 0;
#pragma unroll
            for (int k = 0; k < 8; k++) {
                if (k == 0) P2T(5);
                if ((wg == 0 || k > P2_HO) && first) mbar_wait(a_full + 8 * k, ic & 1);
                if (k == 0) P2T(6);
                mbar_wait(b_full + 8 * s, ph);
                if (k == P2_HO) asm volatile("bar.arrive %0, 256;" :: "r"(4 - wg) : "memory");
                if (k == 0) P2T(1);
                if (k == 7) P2T(2);
                const uint32_t b_lo = b_lo0 + s * 1024;
                if (k == 0 || !P2_NOF) wgmma_fence();
#pragma unroll
                for (int kk = 0; kk < (P2_NOMMA ? 1 : 4); kk++) {
                    wgmma_ss_n128_lo<1>(acc[0], a_lo + p2_apos(k) * 1024 + kk * 2, b_lo + kk * 128, (k | kk) != 0);
                    wgmma_ss_n128_lo<1>(acc[1], a_lo + p2_apos(k) * 1024 + 512 + kk * 2, b_lo + kk * 128, (k | kk) != 0);
                }
                wgmma_commit();
                if (k > 0) {
                    wgmma_wait<1>();
                    if (elected) {
                        const uint32_t e = b_empty + 8 * sprev;
                        mbar_arrive_cl(mapa_u32(e, 0)); mbar_arrive_cl(mapa_u32(e, 1));
                        if (last) mbar_arrive(a_empty + 8 * (k - 1));
                    }
                }
                sprev = s;
                if (++s == P2_STAGES) { s = 0; ph ^= 1; }
            }
            int z, mp, head;
            p2_tile(t, rp * 2 + wg, z, mp, head);
            const int m0 = (2 * mp + (int)rank) * 128, en = wg * 4 + (nnote & 3);
            bf16* obase = P.out[z] + ((size_t)head * SEQ + m0 + (warp & 3) * 16 + (lane >> 2)) * HD + (lane & 3) * 8;
            if (elected) {
                mbar_wait(note_free + 8 * en, ((nnote >> 2) & 1) ^ 1);
                asm volatile("st.shared.s32 [%0], %1;" :: "r"(note + en * 4), "r"(CT_AP + (head >> 1)) : "memory");
            }
            __syncwarp();
            nnote++;
            wgmma_wait<0>();
            P2T(3);
            if (elected) {
                const uint32_t e = b_empty + 8 * sprev;
                mbar_arrive_cl(mapa_u32(e, 0)); mbar_arrive_cl(mapa_u32(e, 1));
                if (last) mbar_arrive(a_empty + 8 * 7);
            }
            s += 8 % P2_STAGES; ph ^= (8 / P2_STAGES) & 1;
            if (s >= P2_STAGES) { s -= P2_STAGES; ph ^= 1; }
            store_frag_128<P2_PACE>(acc[0], obase);
            if (last) { t = next_item(++ic); rp = 0; P2T(7); } else rp++;
            store_frag_128<P2_PACE>(acc[1], obase + (size_t)64 * HD);
            __syncwarp();
            if (lane == 0) mbar_arrive(note_bar + 8 * en);
            __syncwarp();
        }
        if (wg == 0 && lane == 0) {
            const int e = nnote & 3;
            if (elected) {
                mbar_wait(note_free + 8 * e, ((nnote >> 2) & 1) ^ 1);
                asm volatile("st.shared.s32 [%0], %1;" :: "r"(note + e * 4), "r"(-1) : "memory");
            }
            mbar_arrive(note_bar + 8 * e);
        }
        auto done = [&]() {
            if ((threadIdx.x & 127) == 0) for (int i = 0; i < 4; i++) mbar_arrive_cl(SD + MO_BAR + 768 + OB_EMPTY + 16 + 8 * (i & 1) + ((i >> 1) << 24));
        };
        asm volatile("bar.sync %0, 128;" :: "r"(1 + wg) : "memory");
        const int nout = attn_consumer(MP.a, warp, done, SD + (rank << 24));
        OT(0);
        const uint32_t sb2 = (cluster_ctarank() << 24) + SD;
        out_consumer(MP.o, sb2, sb2 + MO_BAR + 768, warp, nout & 1);
    }
}

typedef CUresult (*PFN_encodeTiled)(CUtensorMap*, CUtensorMapDataType, cuuint32_t, void*, const cuuint64_t*,
                                    const cuuint64_t*, const cuuint32_t*, const cuuint32_t*, CUtensorMapInterleave,
                                    CUtensorMapSwizzle, CUtensorMapL2promotion, CUtensorMapFloatOOBfill);
static PFN_encodeTiled g_encode = nullptr;

static void make_map(CUtensorMap* m, const void* ptr, uint64_t rows, uint64_t cols, uint32_t box_rows, bool sw64 = false) {
    cuuint64_t dims[2] = {cols, rows};
    cuuint64_t strides[1] = {cols * 2};
    cuuint32_t box[2] = {sw64 ? 32u : 64u, box_rows};
    cuuint32_t es[2] = {1, 1};
    g_encode(m, CU_TENSOR_MAP_DATA_TYPE_BFLOAT16, 2, const_cast<void*>(ptr), dims, strides, box, es,
             CU_TENSOR_MAP_INTERLEAVE_NONE, sw64 ? CU_TENSOR_MAP_SWIZZLE_64B : CU_TENSOR_MAP_SWIZZLE_128B, CU_TENSOR_MAP_L2_PROMOTION_L2_256B,
             CU_TENSOR_MAP_FLOAT_OOB_FILL_NONE);
}

template <typename... KArgs, typename... Args>
static void launch_pdl(void (*kernel)(KArgs...), int grid, int block, size_t smem, cudaStream_t st, bool pdl, Args... args) {
    cudaLaunchConfig_t cfg = {};
    cfg.gridDim = dim3(grid); cfg.blockDim = dim3(block); cfg.dynamicSmemBytes = smem; cfg.stream = st;
    cudaLaunchAttribute at[1];
    at[0].id = cudaLaunchAttributeProgrammaticStreamSerialization;
    at[0].val.programmaticStreamSerializationAllowed = 1;
    cfg.attrs = at; cfg.numAttrs = pdl ? 1 : 0;
    cudaLaunchKernelEx(&cfg, kernel, KArgs(args)...);
}

extern "C" void kernel_launch(void* const* d_in, const int* in_sizes, int n_in, void* d_out, int out_size) {
    const bf16* x = (const bf16*)d_in[0];
    const bf16* ckv = (const bf16*)d_in[1];
    const bf16* wq = (const bf16*)d_in[2];
    const bf16* wuk = (const bf16*)d_in[3];
    const bf16* wuv = (const bf16*)d_in[4];
    const bf16* wo = (const bf16*)d_in[5];
    const bf16* mem0 = (const bf16*)d_in[7];
    const bf16* Wq = (const bf16*)d_in[8];
    const bf16* Wk = (const bf16*)d_in[9];
    const bf16* Wv = (const bf16*)d_in[10];
    const bf16* Wo = (const bf16*)d_in[11];
    const bf16* gate_w = (const bf16*)d_in[13];
    bf16* out = (bf16*)d_out;

    static MainParams MP;
    static ChainParams CP;
    Proj2Params& P2 = MP.p;
    AttnParams& AP = MP.a;
    OutParams& OP = MP.o;
    static bool init = false;
    static const void* last_in[14];
    static const void* last_out;
    bool same = init && last_out == d_out;
    for (int i = 0; i < 14 && same; i++) same = last_in[i] == d_in[i];
    if (!init) {
        cudaDriverEntryPointQueryResult qr;
        cudaGetDriverEntryPoint("cuTensorMapEncodeTiled", (void**)&g_encode, cudaEnableDefault, &qr);
        cudaFuncSetAttribute(main_kernel, cudaFuncAttributeMaxDynamicSharedMemorySize, M_SMEM);
        cudaFuncSetAttribute(chain_kernel, cudaFuncAttributeMaxDynamicSharedMemorySize, CH_SMEM);
        init = true;
    }
    if (!same) {
        for (int i = 0; i < 14; i++) last_in[i] = d_in[i];
        last_out = d_out;
        void *pQA, *pKA, *pVA, *pCA, *pCB;
        cudaGetSymbolAddress(&pQA, g_QA); cudaGetSymbolAddress(&pKA, g_KA); cudaGetSymbolAddress(&pVA, g_VA);
        cudaGetSymbolAddress(&pCA, g_ctxA); cudaGetSymbolAddress(&pCB, g_ctxB);
        make_map(&P2.mapA[0], x, SEQ, DM, 128);
        make_map(&P2.mapA[1], ckv, SEQ, DM, 128);
        const void* ws[3] = {wq, wuk, wuv};
        void* cs[3] = {pQA, pKA, pVA};
        for (int i = 0; i < 3; i++) { make_map(&P2.mapW[i], ws[i], DM, NQ, 64); P2.out[i] = (bf16*)cs[i]; }
        make_map(&CP.mapW[0], Wq, DM, NQ, 64); make_map(&CP.mapW[1], Wk, DM, NQ, 64); make_map(&CP.mapW[2], Wv, DM, NQ, 32);
        make_map(&CP.mapX, x, SEQ, DM, 32);
        make_map(&CP.mapWo, Wo, NQ, DM, 64);
        make_map(&CP.mapM, mem0, NMEM, DM, 8);
        MP.x = x; MP.gate_w = gate_w;
        make_map(&CP.mapC, pCB, NH * SEQ, HD, 32);
        make_map(&AP.mapQ, pQA, NH * SEQ, HD, 128);
        make_map(&AP.mapK, pKA, NH * SEQ, HD, 128);
        make_map(&AP.mapV, pVA, NH * SEQ, HD, 128);
        make_map(&AP.mapO, pCA, NH * SEQ, HD, 64);
        make_map(&OP.mapCtx[0], pCA, NH * SEQ, HD, 128);
        make_map(&OP.mapCtx[1], pCB, NH * SEQ, HD, 128);
        make_map(&OP.mapWo[0], wo, NQ, DM, 64);
        make_map(&OP.mapWo[1], Wo, NQ, DM, 64);
        make_map(&OP.mapOut, out, SEQ, DM, 64);
        CP.mapOut = OP.mapOut;
        AP.out = out;
    }
    cudaStream_t s1 = cudaStreamPerThread;
    const bool pdl = true;
    launch_pdl(chain_kernel, 64, CH_BLOCK, CH_SMEM, s1, false, CP);
    launch_pdl(main_kernel, M_GRID, 384, M_SMEM, s1, pdl, MP);
}
```

```cpp
#include <cuda_runtime.h>
#include <cuda_bf16.h>
#include <cuda.h>
#include <stdint.h>
#include <type_traits>

constexpr int SEQ = 2048;
constexpr int DM = 512;
constexpr int NH = 32;
constexpr int HD = 128;
constexpr int NQ = NH * HD;
constexpr int SEGL = 32;
constexpr int NMEM = 8;
constexpr int NSEG = SEQ / SEGL;

typedef __nv_bfloat16 bf16;

__device__ bf16 g_QA[SEQ * NQ];
__device__ bf16 g_KA[SEQ * NQ];
__device__ bf16 g_VA[SEQ * NQ];
__device__ bf16 g_ctxA[SEQ * NQ];
__device__ bf16 g_ctxB[SEQ * NQ];
constexpr int CT_PROJ = 0, CT_ATTN = 1, CT_FIN = 5;
constexpr int CT_AP = 64;
constexpr int CT_GATE = 96;
constexpr int CT_CA = 128;
constexpr int CT_CB = 193;
constexpr int CT_OT = 208;
constexpr int CT_N = 228;
__device__ __align__(16) unsigned int g_ctr[CT_N];
__device__ float g_gate[SEQ];
#define XB8(v) v, v, v, v, v, v, v, v
__device__ uint32_t g_xbuf[4 * 8 * 2048] = {XB8(XB8(XB8(XB8(XB8(~0u)))))};

#define FA_GRID 68

#define TS_BEGIN(id)
#define TS_END(id)
#define TS_BEGIN2(id, th)
#define TS_END2(id, th)
#define WAIT_LIMIT 200000
__device__ __forceinline__ void pdl_launch_dependents() { asm volatile("griddepcontrol.launch_dependents;" ::: "memory"); }
__device__ __forceinline__ void wait_ctr(int idx, unsigned int n) {
    unsigned int v; int it = 0;
    do { asm volatile("ld.acquire.gpu.global.u32 %0, [%1];" : "=r"(v) : "l"(&g_ctr[idx]) : "memory"); } while (v < n && ++it < WAIT_LIMIT);
    asm volatile("fence.proxy.async.shared::cta;" ::: "memory");
}
__device__ __forceinline__ int take_ticket(int idx) {
    int v;
    asm volatile("atom.relaxed.gpu.global.inc.u32 %0, [%1], 0x7fffffff;" : "=r"(v) : "l"(&g_ctr[idx]) : "memory");
    return v;
}
__device__ __forceinline__ void signal_ctr(int idx) {
    asm volatile("fence.proxy.async;" ::: "memory");
    __threadfence();
    atomicAdd(&g_ctr[idx], 1u);
}
__device__ __forceinline__ void signal_ctr_generic(int idx) {
    asm volatile("red.release.gpu.global.add.u32 [%0], 1;" :: "l"(&g_ctr[idx]) : "memory");
}
__device__ __forceinline__ uint32_t smem_u32(const void* p) {
    return (uint32_t)__cvta_generic_to_shared(p);
}
__device__ __forceinline__ void mbar_init(uint32_t bar, uint32_t count) {
    asm volatile("mbarrier.init.shared::cta.b64 [%0], %1;" :: "r"(bar), "r"(count));
}
__device__ __forceinline__ void mbar_expect_tx(uint32_t bar, uint32_t bytes) {
    asm volatile("mbarrier.arrive.expect_tx.shared::cta.b64 _, [%0], %1;" :: "r"(bar), "r"(bytes) : "memory");
}
__device__ __forceinline__ void mbar_arrive(uint32_t bar) {
    asm volatile("mbarrier.arrive.shared::cta.b64 _, [%0];" :: "r"(bar) : "memory");
}
__device__ __forceinline__ void mbar_wait(uint32_t bar, uint32_t parity) {
    asm volatile(
        "{\n"
        ".reg .pred p, q;\n"
        ".reg .u32 c;\n"
        "mov.u32 c, 0;\n"
        "WAIT_LOOP:\n"
        "mbarrier.try_wait.parity.shared::cta.b64 p, [%0], %1;\n"
        "@p bra WAIT_DONE;\n"
        "add.u32 c, c, 1;\n"
        "setp.lt.u32 q, c, %2;\n"
        "@q bra WAIT_LOOP;\n"
        "WAIT_DONE:\n"
        "}\n" :: "r"(bar), "r"(parity), "n"(WAIT_LIMIT) : "memory");
}
__device__ __forceinline__ uint32_t mbar_test(uint32_t bar, uint32_t parity) {
    uint32_t done;
    asm volatile(
        "{\n.reg .pred p;\n"
        "mbarrier.test_wait.parity.shared::cta.b64 p, [%1], %2;\n"
        "selp.u32 %0, 1, 0, p;\n}\n" : "=r"(done) : "r"(bar), "r"(parity) : "memory");
    return done;
}
__device__ __forceinline__ uint32_t mbar_try(uint32_t bar, uint32_t parity) {
    uint32_t done;
    asm volatile(
        "{\n.reg .pred p;\n"
        "mbarrier.try_wait.parity.shared::cta.b64 p, [%1], %2;\n"
        "selp.u32 %0, 1, 0, p;\n}\n" : "=r"(done) : "r"(bar), "r"(parity) : "memory");
    return done;
}
__device__ __forceinline__ void tma_load_2d(uint32_t dst, const CUtensorMap* map, uint32_t bar, int c0, int c1) {
    asm volatile(
        "cp.async.bulk.tensor.2d.shared::cluster.global.mbarrier::complete_tx::bytes [%0], [%1, {%3, %4}], [%2];"
        :: "r"(dst), "l"((uint64_t)map), "r"(bar), "r"(c0), "r"(c1) : "memory");
}
__device__ __forceinline__ void wgmma_fence() { asm volatile("wgmma.fence.sync.aligned;" ::: "memory"); }
__device__ __forceinline__ void wgmma_commit() { asm volatile("wgmma.commit_group.sync.aligned;" ::: "memory"); }
template <int N> __device__ __forceinline__ void wgmma_wait() {
    asm volatile("wgmma.wait_group.sync.aligned %0;" :: "n"(N) : "memory");
}
__device__ __forceinline__ uint64_t make_desc(uint32_t addr, uint32_t lbo, uint32_t sbo) {
    uint64_t d = 0;
    d |= (uint64_t)((addr & 0x3FFFF) >> 4);
    d |= (uint64_t)((lbo >> 4) & 0x3FFF) << 16;
    d |= (uint64_t)((sbo >> 4) & 0x3FFF) << 32;
    d |= (uint64_t)1 << 62;
    return d;
}

#define ACC64(d) \
    "+f"(d[0]), "+f"(d[1]), "+f"(d[2]), "+f"(d[3]), "+f"(d[4]), "+f"(d[5]), "+f"(d[6]), "+f"(d[7]), \
    "+f"(d[8]), "+f"(d[9]), "+f"(d[10]), "+f"(d[11]), "+f"(d[12]), "+f"(d[13]), "+f"(d[14]), "+f"(d[15]), \
    "+f"(d[16]), "+f"(d[17]), "+f"(d[18]), "+f"(d[19]), "+f"(d[20]), "+f"(d[21]), "+f"(d[22]), "+f"(d[23]), \
    "+f"(d[24]), "+f"(d[25]), "+f"(d[26]), "+f"(d[27]), "+f"(d[28]), "+f"(d[29]), "+f"(d[30]), "+f"(d[31]), \
    "+f"(d[32]), "+f"(d[33]), "+f"(d[34]), "+f"(d[35]), "+f"(d[36]), "+f"(d[37]), "+f"(d[38]), "+f"(d[39]), \
    "+f"(d[40]), "+f"(d[41]), "+f"(d[42]), "+f"(d[43]), "+f"(d[44]), "+f"(d[45]), "+f"(d[46]), "+f"(d[47]), \
    "+f"(d[48]), "+f"(d[49]), "+f"(d[50]), "+f"(d[51]), "+f"(d[52]), "+f"(d[53]), "+f"(d[54]), "+f"(d[55]), \
    "+f"(d[56]), "+f"(d[57]), "+f"(d[58]), "+f"(d[59]), "+f"(d[60]), "+f"(d[61]), "+f"(d[62]), "+f"(d[63])
#define ACC64_STR \
    "{%0, %1, %2, %3, %4, %5, %6, %7, %8, %9, %10, %11, %12, %13, %14, %15, " \
    "%16, %17, %18, %19, %20, %21, %22, %23, %24, %25, %26, %27, %28, %29, %30, %31, " \
    "%32, %33, %34, %35, %36, %37, %38, %39, %40, %41, %42, %43, %44, %45, %46, %47, " \
    "%48, %49, %50, %51, %52, %53, %54, %55, %56, %57, %58, %59, %60, %61, %62, %63}"

template <int TB>
__device__ __forceinline__ void wgmma_ss_n128(float (&d)[64], uint64_t da, uint64_t db, int scale_d) {
    asm volatile(
        "{\n.reg .pred p;\nsetp.ne.b32 p, %66, 0;\n"
        "wgmma.mma_async.sync.aligned.m64n128k16.f32.bf16.bf16 " ACC64_STR ", %64, %65, p, 1, 1, 0, %67;\n}\n"
        : ACC64(d) : "l"(da), "l"(db), "r"(scale_d), "n"(TB));
}
__device__ __forceinline__ uint32_t desc_lo(uint32_t addr, uint32_t lbo) { return ((addr & 0x3FFFF) >> 4) | ((lbo >> 4) << 16); }
template <int TB>
__device__ __forceinline__ void wgmma_ss_n128_lo(float (&d)[64], uint32_t da_lo, uint32_t db_lo, int scale_d) {
    asm volatile(
        "{\n.reg .pred p;\n.reg .b64 da, db;\nsetp.ne.b32 p, %66, 0;\n"
        "mov.b64 da, {%64, 0x40000040};\nmov.b64 db, {%65, 0x40000040};\n"
        "wgmma.mma_async.sync.aligned.m64n128k16.f32.bf16.bf16 " ACC64_STR ", da, db, p, 1, 1, 0, %67;\n}\n"
        : ACC64(d) : "r"(da_lo), "r"(db_lo), "r"(scale_d), "n"(TB));
}
__device__ __forceinline__ void wgmma_rs_n128_tb(float (&d)[64], uint32_t a0, uint32_t a1, uint32_t a2, uint32_t a3,
                                                 uint64_t db, int scale_d) {
    asm volatile(
        "{\n.reg .pred p;\nsetp.ne.b32 p, %69, 0;\n"
        "wgmma.mma_async.sync.aligned.m64n128k16.f32.bf16.bf16 " ACC64_STR ", {%64, %65, %66, %67}, %68, p, 1, 1, 1;\n}\n"
        : ACC64(d) : "r"(a0), "r"(a1), "r"(a2), "r"(a3), "l"(db), "r"(scale_d));
}
__device__ __forceinline__ void wgmma_rs_n80(float (&d)[40], const uint32_t (&a)[4], uint32_t db_lo, int scale_d) {
    asm volatile(
        "{\n.reg .pred p;\n.reg .b64 db;\nsetp.ne.b32 p, %45, 0;\nmov.b64 db, {%44, 0x40000040};\n"
        "wgmma.mma_async.sync.aligned.m64n80k16.f32.bf16.bf16 "
        "{%0, %1, %2, %3, %4, %5, %6, %7, %8, %9, %10, %11, %12, %13, %14, %15, %16, %17, %18, %19, %20, %21, %22, %23, %24, %25, %26, %27, %28, %29, %30, %31, %32, %33, %34, %35, %36, %37, %38, %39}, "
        "{%40, %41, %42, %43}, db, p, 1, 1, 0;\n}\n"
        : "+f"(d[0]), "+f"(d[1]), "+f"(d[2]), "+f"(d[3]), "+f"(d[4]), "+f"(d[5]), "+f"(d[6]), "+f"(d[7]), "+f"(d[8]), "+f"(d[9]), "+f"(d[10]), "+f"(d[11]), "+f"(d[12]), "+f"(d[13]), "+f"(d[14]), "+f"(d[15]), "+f"(d[16]), "+f"(d[17]), "+f"(d[18]), "+f"(d[19]), "+f"(d[20]), "+f"(d[21]), "+f"(d[22]), "+f"(d[23]), "+f"(d[24]), "+f"(d[25]), "+f"(d[26]), "+f"(d[27]), "+f"(d[28]), "+f"(d[29]), "+f"(d[30]), "+f"(d[31]), "+f"(d[32]), "+f"(d[33]), "+f"(d[34]), "+f"(d[35]), "+f"(d[36]), "+f"(d[37]), "+f"(d[38]), "+f"(d[39])
        : "r"(a[0]), "r"(a[1]), "r"(a[2]), "r"(a[3]), "r"(db_lo), "r"(scale_d));
}
__device__ __forceinline__ void wgmma_ss_n256_tb(float (&d)[128], uint64_t da, uint64_t db, int scale_d) {
    asm volatile(
        "{\n.reg .pred p;\nsetp.ne.b32 p, %130, 0;\n"
        "wgmma.mma_async.sync.aligned.m64n256k16.f32.bf16.bf16 {%0, %1, %2, %3, %4, %5, %6, %7, %8, %9, %10, %11, %12, %13, %14, %15, %16, %17, %18, %19, %20, %21, %22, %23, %24, %25, %26, %27, %28, %29, %30, %31, %32, %33, %34, %35, %36, %37, %38, %39, %40, %41, %42, %43, %44, %45, %46, %47, %48, %49, %50, %51, %52, %53, %54, %55, %56, %57, %58, %59, %60, %61, %62, %63, %64, %65, %66, %67, %68, %69, %70, %71, %72, %73, %74, %75, %76, %77, %78, %79, %80, %81, %82, %83, %84, %85, %86, %87, %88, %89, %90, %91, %92, %93, %94, %95, %96, %97, %98, %99, %100, %101, %102, %103, %104, %105, %106, %107, %108, %109, %110, %111, %112, %113, %114, %115, %116, %117, %118, %119, %120, %121, %122, %123, %124, %125, %126, %127}, %128, %129, p, 1, 1, 0, 1;\n}\n"
        : "+f"(d[0]), "+f"(d[1]), "+f"(d[2]), "+f"(d[3]), "+f"(d[4]), "+f"(d[5]), "+f"(d[6]), "+f"(d[7]), "+f"(d[8]), "+f"(d[9]), "+f"(d[10]), "+f"(d[11]), "+f"(d[12]), "+f"(d[13]), "+f"(d[14]), "+f"(d[15]), "+f"(d[16]), "+f"(d[17]), "+f"(d[18]), "+f"(d[19]), "+f"(d[20]), "+f"(d[21]), "+f"(d[22]), "+f"(d[23]), "+f"(d[24]), "+f"(d[25]), "+f"(d[26]), "+f"(d[27]), "+f"(d[28]), "+f"(d[29]), "+f"(d[30]), "+f"(d[31]), "+f"(d[32]), "+f"(d[33]), "+f"(d[34]), "+f"(d[35]), "+f"(d[36]), "+f"(d[37]), "+f"(d[38]), "+f"(d[39]), "+f"(d[40]), "+f"(d[41]), "+f"(d[42]), "+f"(d[43]), "+f"(d[44]), "+f"(d[45]), "+f"(d[46]), "+f"(d[47]), "+f"(d[48]), "+f"(d[49]), "+f"(d[50]), "+f"(d[51]), "+f"(d[52]), "+f"(d[53]), "+f"(d[54]), "+f"(d[55]), "+f"(d[56]), "+f"(d[57]), "+f"(d[58]), "+f"(d[59]), "+f"(d[60]), "+f"(d[61]), "+f"(d[62]), "+f"(d[63]), "+f"(d[64]), "+f"(d[65]), "+f"(d[66]), "+f"(d[67]), "+f"(d[68]), "+f"(d[69]), "+f"(d[70]), "+f"(d[71]), "+f"(d[72]), "+f"(d[73]), "+f"(d[74]), "+f"(d[75]), "+f"(d[76]), "+f"(d[77]), "+f"(d[78]), "+f"(d[79]), "+f"(d[80]), "+f"(d[81]), "+f"(d[82]), "+f"(d[83]), "+f"(d[84]), "+f"(d[85]), "+f"(d[86]), "+f"(d[87]), "+f"(d[88]), "+f"(d[89]), "+f"(d[90]), "+f"(d[91]), "+f"(d[92]), "+f"(d[93]), "+f"(d[94]), "+f"(d[95]), "+f"(d[96]), "+f"(d[97]), "+f"(d[98]), "+f"(d[99]), "+f"(d[100]), "+f"(d[101]), "+f"(d[102]), "+f"(d[103]), "+f"(d[104]), "+f"(d[105]), "+f"(d[106]), "+f"(d[107]), "+f"(d[108]), "+f"(d[109]), "+f"(d[110]), "+f"(d[111]), "+f"(d[112]), "+f"(d[113]), "+f"(d[114]), "+f"(d[115]), "+f"(d[116]), "+f"(d[117]), "+f"(d[118]), "+f"(d[119]), "+f"(d[120]), "+f"(d[121]), "+f"(d[122]), "+f"(d[123]), "+f"(d[124]), "+f"(d[125]), "+f"(d[126]), "+f"(d[127])
        : "l"(da), "l"(db), "r"(scale_d));
}
__device__ __forceinline__ void stmatrix_x4(uint32_t addr, uint32_t r0, uint32_t r1, uint32_t r2, uint32_t r3) {
    asm volatile("stmatrix.sync.aligned.m8n8.x4.shared.b16 [%0], {%1, %2, %3, %4};" :: "r"(addr), "r"(r0), "r"(r1), "r"(r2), "r"(r3) : "memory");
}
__device__ __forceinline__ void tma_store_2d(const CUtensorMap* map, uint32_t src, int c0, int c1) {
    asm volatile("cp.async.bulk.tensor.2d.global.shared::cta.bulk_group [%0, {%2, %3}], [%1];"
                 :: "l"((uint64_t)map), "r"(src), "r"(c0), "r"(c1) : "memory");
}
__device__ __forceinline__ float ex2f(float x) { float y; asm("ex2.approx.ftz.f32 %0, %1;" : "=f"(y) : "f"(x)); return y; }
__device__ __forceinline__ uint32_t pack_bf16(float lo, float hi) {
    __nv_bfloat162 v = __floats2bfloat162_rn(lo, hi);
    return *reinterpret_cast<uint32_t*>(&v);
}
__device__ __forceinline__ void mma_16816(float (&c)[4], uint32_t a0, uint32_t a1, uint32_t a2, uint32_t a3,
                                          uint32_t b0, uint32_t b1) {
    asm volatile(
        "mma.sync.aligned.m16n8k16.row.col.f32.bf16.bf16.f32 {%0,%1,%2,%3}, {%4,%5,%6,%7}, {%8,%9}, {%0,%1,%2,%3};"
        : "+f"(c[0]), "+f"(c[1]), "+f"(c[2]), "+f"(c[3])
        : "r"(a0), "r"(a1), "r"(a2), "r"(a3), "r"(b0), "r"(b1));
}
__device__ __forceinline__ void ldmatrix_x4_trans(uint32_t& r0, uint32_t& r1, uint32_t& r2, uint32_t& r3, uint32_t addr) {
    asm volatile("ldmatrix.sync.aligned.m8n8.x4.trans.shared.b16 {%0,%1,%2,%3}, [%4];"
                 : "=r"(r0), "=r"(r1), "=r"(r2), "=r"(r3) : "r"(addr));
}

struct AttnParams {
    CUtensorMap mapQ, mapK, mapV;
    CUtensorMap mapO;
    bf16* out;
};
constexpr int FA_ITEMS = 16 * NH;
__device__ __forceinline__ int fa_qt(int t) { return 15 - ((t & 127) >> 3); }
__device__ __forceinline__ int fa_head(int t) { return (t >> 7) * 8 + (t & 7); }
#define FA_TKA 2
#define FA_SPLIT 11

#define FA_P0 4
#define FA_HO 6
#define FA_LAG 3
#define FA_PK 3
#define FA_TG 16
#define FA_EARLY 0
#define FA_TRIM 1
#define FA_TE 0
#define FA_B0 1
#define FA_ONE 1
#define FA_I0 0
static_assert(FA_GRID <= 104 && FA_HO >= FA_P0 && FA_P0 >= 1 && (!FA_TRIM || (FA_P0 == 4 && FA_SPLIT >= 8 && FA_I0 <= 4)), "");
constexpr float FA_MARGIN = 16.f;
#define FAT(b, i)
__device__ __forceinline__ void mbar_arrive_if(uint32_t bar, bool c) {
    asm volatile("{\n.reg .pred p;\nsetp.ne.b32 p, %1, 0;\n@p mbarrier.arrive.shared::cta.b64 _, [%0];\n}" :: "r"(bar), "r"((int)c) : "memory");
}
__device__ __forceinline__ void sched_fence(int v, int id, const float* a, const float* b, const float* c) {
    asm volatile("{\n.reg .pred p;\nsetp.ne.s32 p, %0, %1;\n@p bra SF_SKIP;\nwgmma.wait_group.sync.aligned 0;\n"
                 "st.volatile.shared.f32 [%0], %2;\nst.volatile.shared.f32 [%0], %3;\nst.volatile.shared.f32 [%0], %4;\nst.volatile.shared.f32 [%0], %5;\n"
                 "st.volatile.shared.f32 [%0], %6;\nst.volatile.shared.f32 [%0], %7;\nst.volatile.shared.f32 [%0], %8;\nst.volatile.shared.f32 [%0], %9;\n"
                 "st.volatile.shared.f32 [%0], %10;\nst.volatile.shared.f32 [%0], %11;\nst.volatile.shared.f32 [%0], %12;\nst.volatile.shared.f32 [%0], %13;\n"
                 "exit;\nSF_SKIP:\n}" :: "r"(v), "r"(1000000 + id), "f"(a[0]), "f"(a[1]), "f"(a[2]), "f"(a[3]), "f"(b[0]), "f"(b[1]), "f"(b[2]), "f"(b[3]),
                 "f"(c[0]), "f"(c[1]), "f"(c[2]), "f"(c[3]) : "memory");
}
__device__ __forceinline__ float ex2v(float x) { float y; asm volatile("ex2.approx.ftz.f32 %0, %1;" : "=f"(y) : "f"(x)); return y; }
__device__ __forceinline__ void wgmma_rs_n128_tb_lo(float (&d)[64], const uint32_t* a, uint32_t db_lo, int scale_d) {
    asm volatile(
        "{\n.reg .pred p;\n.reg .b64 db;\nsetp.ne.b32 p, %69, 0;\nmov.b64 db, {%68, 0x40000040};\n"
        "wgmma.mma_async.sync.aligned.m64n128k16.f32.bf16.bf16 " ACC64_STR ", {%64, %65, %66, %67}, db, p, 1, 1, 1;\n}\n"
        : ACC64(d) : "r"(a[0]), "r"(a[1]), "r"(a[2]), "r"(a[3]), "r"(db_lo), "r"(scale_d));
}

constexpr int M_GRID = 68;
constexpr uint32_t SD = 1024;
constexpr uint32_t MO_BAR = 229376;
constexpr int M_SMEM = MO_BAR + 1024;
constexpr uint32_t FO_Q = 0, FO_KV = 65536, FO_O = FO_KV + 2 * 65536, FO_BAR = MO_BAR + 512;
constexpr uint32_t FB_QF = FO_BAR, FB_QE = FO_BAR + 16, FB_KF = FO_BAR + 32, FB_VF = FO_BAR + 48, FB_KE = FO_BAR + 64, FB_VE = FO_BAR + 80,
                   FB_OF = FO_BAR + 96, FB_OE = FO_BAR + 112, FB_SLOT = FO_BAR + 128, FB_OSLOT = FO_BAR + 136;
__device__ __forceinline__ void attn_init(uint32_t sb) {
    for (int i = 0; i < 2; i++) {
        mbar_init(sb + FB_QF + 8 * i, 1); mbar_init(sb + FB_QE + 8 * i, 8); mbar_init(sb + FB_KF + 8 * i, 1); mbar_init(sb + FB_VF + 8 * i, 1);
        mbar_init(sb + FB_KE + 8 * i, 8); mbar_init(sb + FB_VE + 8 * i, 8); mbar_init(sb + FB_OF + 8 * i, 4); mbar_init(sb + FB_OE + 8 * i, 1);
    }
}
__device__ __forceinline__ void attn_helper(const AttnParams& P, uint32_t sb, int wg) {
    const uint32_t stg = sb + FO_O + wg * 16384;
    for (int n = 0;; n++) {
        mbar_wait(sb + FB_OF + 8 * wg, n & 1);
        int t;
        asm volatile("ld.shared.s32 %0, [%1];" : "=r"(t) : "r"(sb + FB_OSLOT + wg * 4) : "memory");
        const int qt = fa_qt(t), h = fa_head(t & 1023);
        tma_store_2d(&P.mapO, stg, 0, h * SEQ + qt * 128 + wg * 64);
        tma_store_2d(&P.mapO, stg + 8192, 64, h * SEQ + qt * 128 + wg * 64);
        asm volatile("cp.async.bulk.commit_group;" ::: "memory");
        asm volatile("cp.async.bulk.wait_group.read 0;" ::: "memory");
        mbar_arrive(sb + FB_OE + 8 * wg);
        asm volatile("cp.async.bulk.wait_group 0;" ::: "memory");
        signal_ctr(CT_CA + qt * 4 + (h >> 3));
        if (t >= 1024) break;
    }
}
__device__ __forceinline__ void attn_producer(const AttnParams& P, uint32_t sb, uint32_t free_bar, uint32_t free_par) {
    const uint32_t sQ = sb + FO_Q, sKV = sb + FO_KV;
    int b = 0, hp_ready = 0, vrow = 0, t = blockIdx.x, item = 0;
    auto load_v = [&](int i) {
        const uint32_t sv = sKV + (i & 1) * 65536 + 32768, bar = sb + FB_VF + 8 * (i & 1);
        mbar_wait(sb + FB_VE + 8 * (i & 1), ((i >> 1) & 1) ^ (FA_B0 ? ~i & 1 : 1));
        mbar_expect_tx(bar, 32768);
        tma_load_2d(sv, &P.mapV, bar, 0, vrow);
        tma_load_2d(sv + 16384, &P.mapV, bar, 64, vrow);
    };
    for (;; item++) {
        const bool valid = t < FA_ITEMS;
        const int qt = fa_qt(t), h = fa_head(t);
        if (valid && !((hp_ready >> (h >> 1)) & 1)) { wait_ctr(CT_AP + (h >> 1), 96u); hp_ready |= 1 << (h >> 1); }
        const uint32_t bq = sb + FB_QF + 8 * (item & 1);
        mbar_wait(item ? sb + FB_QE + 8 * (item & 1) : free_bar + 8, item ? ((item >> 1) & 1) ^ 1 : free_par);
        asm volatile("st.shared.s32 [%0], %1;" :: "r"(sb + FB_SLOT + (item & 1) * 4), "r"(valid ? t : -1) : "memory");
        if (!valid) { mbar_arrive(bq); break; }
        mbar_expect_tx(bq, 32768);
        tma_load_2d(sQ + (item & 1) * 32768, &P.mapQ, bq, 0, h * SEQ + qt * 128);
        tma_load_2d(sQ + (item & 1) * 32768 + 16384, &P.mapQ, bq, 64, h * SEQ + qt * 128);
#pragma unroll 1
        for (int j = 0; j <= qt; j++, b++) {
            const uint32_t sk = sKV + (b & 1) * 65536, bar = sb + FB_KF + 8 * (b & 1);
            mbar_wait(b >= 2 ? sb + FB_KE + 8 * (b & 1) : free_bar + 24 + 32 * b, b >= 2 ? ((b >> 1) & 1) ^ 1 : free_par);
            if (b == 1) { TS_END2(0, 256); TS_BEGIN2(1, 256); }
            if (b == 2) wait_ctr(CT_GATE, 256u);
            mbar_expect_tx(bar, 32768);
            tma_load_2d(sk, &P.mapK, bar, 0, h * SEQ + j * 128);
            tma_load_2d(sk + 16384, &P.mapK, bar, 64, h * SEQ + j * 128);
            if (j == max(qt - FA_TKA, 0)) t = take_ticket(CT_ATTN);
            if (b > 0) load_v(b - 1);
            vrow = h * SEQ + j * 128;
        }
        t += M_GRID;
    }
    load_v(b - 1);
    mbar_wait(sb + FB_KE + 8 * (~b & 1), ((b - 1) >> 1) & 1);
}
template <typename F>
__device__ __forceinline__ int attn_consumer(const AttnParams& P, int warp, F done, const uint32_t sb) {
    constexpr uint32_t sQ = SD + FO_Q, sKV = SD + FO_KV;
    const uint32_t sO = sb + FO_O;
    const uint32_t bar_qf = sb + FB_QF, bar_qe = sb + FB_QE, bar_kf = sb + FB_KF, bar_vf = sb + FB_VF, bar_ke = sb + FB_KE, bar_ve = sb + FB_VE,
                   bar_of = sb + FB_OF, bar_oe = sb + FB_OE, slot = sb + FB_SLOT, oslot = sb + FB_OSLOT;
    {
        const int wg = warp >> 2;
        const int lane = threadIdx.x & 31;
        const float sc = 0.08838834764831845f * 1.4426950408889634f;
        const int r0 = wg * 64 + (warp & 3) * 16 + (lane >> 2);
        float o[64], s[64];
        uint32_t pa[32];
        float m0 = 0.f, m1 = 0.f, l0 = 0.f, l1 = 0.f, i0 = 0.f, i1 = 0.f, g0 = 0.f, g1 = 0.f, gn0 = 0.f, gn1 = 0.f;
        const uint32_t q_lo = desc_lo(sQ + wg * 8192, 16), k_lo = desc_lo(sKV, 16), v_lo = desc_lo(sKV + 32768, 16384);
        auto issue_qk = [&](int b, int item, bool half) {
            const uint32_t qd = q_lo + (item & 1) * 2048, kd = k_lo + (b & 1) * 4096;
            const uint32_t kd2 = half ? kd - 512 : kd;
            wgmma_fence();
#pragma unroll
            for (int kk = 0; kk < 8; kk++) wgmma_ss_n128_lo<0>(s, qd + (kk >> 2) * 1024 + (kk & 3) * 2, kd2 + (kk >> 2) * 1024 + (kk & 3) * 2, kk != 0);
            wgmma_commit();
        };
        auto issue_pv = [&](int b, bool acc, int n, bool half) {
            const uint32_t vd = v_lo + (b & 1) * 4096;
            mbar_wait(bar_vf + 8 * (b & 1), (b >> 1) & 1);
            if (half) {
                asm volatile("wgmma.fence.sync.aligned;  // half" ::: "memory");
#pragma unroll
                for (int kk = 4; kk < 8; kk++) if (kk < n) wgmma_rs_n128_tb_lo(o, &pa[kk * 4], vd + (kk - 4) * 128, kk > 4 ? 1 : (int)acc);
                asm volatile("wgmma.commit_group.sync.aligned;  // half" ::: "memory");
                return;
            }
            wgmma_fence();
#pragma unroll
            for (int kk = 0; kk < 8; kk++) if (kk < n) wgmma_rs_n128_tb_lo(o, &pa[kk * 4], vd + kk * 128, kk ? 1 : (int)acc);
            wgmma_commit();
        };
        const int lim = (FA_TRIM ? (r0 | 64) : r0) - (lane & 3) * 2;
        uint32_t v_hi = v_lo;
        int acc_hi = 1;
        int item = -1, tnext = 0;
        uint32_t k_ready = 0, q_ready = 0;
        auto mask = [&](int i) { if ((i >> 2) * 8 + (i & 1) - ((i & 2) ? 8 : 0) > lim) s[i] = -INFINITY; };
        auto exps = [&](auto mode, int b, bool hand_over, float& u0, float& u1) {
            constexpr int MODE = decltype(mode)::value;
            float p[64], u[4] = {0.f, 0.f, 0.f, 0.f};
            const uint32_t vd = v_hi + ((b - 1) & 1) * 4096;
            constexpr int R = FA_TRIM && MODE == 2 ? 32 : 0;
#pragma unroll
            for (int i = 0; i < 4; i++) p[i] = fmaf(s[i ^ R], sc, (i & 2) ? -m1 : -m0);
#pragma unroll
            for (int g = 0; g < 16 + FA_LAG; g++) {
                if (MODE && g >= FA_I0 && g - FA_I0 < 8 - FA_P0) {
                    const int kk = FA_P0 + g - FA_I0;
                    wgmma_fence();
                    wgmma_rs_n128_tb_lo(o, &pa[kk * 4], vd + kk * 128, FA_TRIM && kk == 4 ? acc_hi : 1);
                    wgmma_commit();
                    if (kk == FA_HO) asm volatile("{\n.reg .pred p;\nsetp.ne.b32 p, %1, 0;\n@p bar.arrive %0, 256;\n}" :: "r"(4 - wg), "r"((int)hand_over) : "memory");
                }
                if (R && g == 8 && wg == 0) {
                    wgmma_wait<0>();
                    mbar_arrive_if(bar_ve + 8 * ((b - 1) & 1), lane == 0);
                    k_ready = q_ready = 0;
#pragma unroll
                    for (int i = 32 - FA_LAG * 4; i < 32; i++) u[i & 3] += p[i];
#pragma unroll
                    for (int i = 0; i < 16; i++) pa[16 + i] = pack_bf16(p[i * 2], p[i * 2 + 1]);
                    break;
                }
                if (MODE && g == FA_SPLIT) {
                    FAT(b, 2);
                    wgmma_wait<0>();
                    FAT(b - 1, 3);
                    mbar_arrive_if(bar_ve + 8 * ((b - 1) & 1), lane == 0);
                }
                if (MODE && g == FA_TG) {
                    k_ready = mbar_test(bar_kf + 8 * (~b & 1), ((b + 1) >> 1) & 1);
                    if (MODE == 2) {
                        q_ready = mbar_test(bar_qf + 8 * (~item & 1), ((item + 1) >> 1) & 1);
                        asm volatile("ld.shared.s32 %0, [%1];" : "=r"(tnext) : "r"(slot + (~item & 1) * 4) : "memory");
                    }
                }
#pragma unroll
                for (int j = 0; j < 4; j++) {
                    const int i = g * 4 + j;
                    if (g < 16) p[i] = ex2v(p[i]);
                    if (g < 15) {
                        if (MODE == 2 && (!R || i + 4 < 32)) mask((i + 4) ^ R);
                        p[i + 4] = fmaf(s[(i + 4) ^ R], sc, (i & 2) ? -m1 : -m0);
                    }
                    if (g >= FA_LAG) u[j] += p[i - FA_LAG * 4];
                }
#pragma unroll
                for (int gg = 0; gg < 16; gg++) {
                    const int at = MODE && gg + FA_LAG < FA_SPLIT + gg / FA_PK ? FA_SPLIT + gg / FA_PK : gg + FA_LAG;
                    if (at == g) { pa[(gg * 2) ^ (R / 2)] = pack_bf16(p[gg * 4], p[gg * 4 + 1]); pa[(gg * 2 + 1) ^ (R / 2)] = pack_bf16(p[gg * 4 + 2], p[gg * 4 + 3]); }
                }
                if (MODE && g < 16) sched_fence(b, g + MODE * 32, &p[g * 4], &p[(g < 15 ? g + 1 : g) * 4], u);
            }
            u0 = u[0] + u[1]; u1 = u[2] + u[3];
        };
        auto quad_max = [&](float& x0, float& x1) {
            x0 = fmaxf(x0, __shfl_xor_sync(0xffffffff, x0, 1)); x1 = fmaxf(x1, __shfl_xor_sync(0xffffffff, x1, 1));
            x0 = fmaxf(x0, __shfl_xor_sync(0xffffffff, x0, 2)); x1 = fmaxf(x1, __shfl_xor_sync(0xffffffff, x1, 2));
            x0 = fmaf(x0, sc, FA_MARGIN); x1 = fmaf(x1, sc, FA_MARGIN);
        };
        auto softmax_exact = [&](bool fresh, bool half, int b) {
            wgmma_wait<0>();
            if (half) {
#pragma unroll
                for (int i = 0; i < 32; i++) s[i] = -INFINITY;
            }
            float x[8];
#pragma unroll
            for (int i = 0; i < 8; i++) x[i] = fmaxf(s[i * 2], s[i * 2 + 1]);
#pragma unroll
            for (int i = 8; i < 32; i++) x[i & 7] = fmaxf(x[i & 7], fmaxf(s[i * 2], s[i * 2 + 1]));
            float x0 = fmaxf(fmaxf(x[0], x[2]), fmaxf(x[4], x[6])), x1 = fmaxf(fmaxf(x[1], x[3]), fmaxf(x[5], x[7]));
            quad_max(x0, x1);
            if (!fresh) {
                x0 = fmaxf(x0, m0); x1 = fmaxf(x1, m1);
                const float a0 = ex2f(m0 - x0), a1 = ex2f(m1 - x1);
                l0 *= a0; l1 *= a1;
#pragma unroll
                for (int i = 0; i < 16; i++) { o[i * 4 + 0] *= a0; o[i * 4 + 1] *= a0; o[i * 4 + 2] *= a1; o[i * 4 + 3] *= a1; }
            }
            m0 = x0; m1 = x1;
            float u0, u1;
            exps(std::integral_constant<int, 0>(), b, false, u0, u1);
            l0 += u0; l1 += u1;
        };
        auto finish_rows = [&]() {
            l0 += __shfl_xor_sync(0xffffffff, l0, 1); l1 += __shfl_xor_sync(0xffffffff, l1, 1);
            l0 += __shfl_xor_sync(0xffffffff, l0, 2); l1 += __shfl_xor_sync(0xffffffff, l1, 2);
            asm("rcp.approx.ftz.f32 %0, %1;" : "=f"(i0) : "f"(l0));
            asm("rcp.approx.ftz.f32 %0, %1;" : "=f"(i1) : "f"(l1));
            i0 *= g0; i1 *= g1;
        };
        auto clear_out = [&](int t) {
            if (t >= 384) {
                bf16* z = P.out + (size_t)(fa_qt(t) * 128 + wg * 64 + ((threadIdx.x & 127) >> 3)) * DM + (t & 7) * 64 + (lane & 7) * 8;
#pragma unroll
                for (int i = 0; i < 4; i++) *reinterpret_cast<uint4*>(z + i * 16 * DM) = make_uint4(0u, 0u, 0u, 0u);
            }
        };
        auto store_o = [&](int t, int n) {
            const uint32_t stg = sO + wg * 16384;
            {
                mbar_wait(bar_oe + 8 * wg, (n & 1) ^ 1);
                asm volatile("st.shared.s32 [%0], %1;" :: "r"(oslot + wg * 4), "r"(t) : "memory");
            }
            const int row = (warp & 3) * 16 + (lane >> 2);
#pragma unroll
            for (int i = 0; i < 4; i++) {
                const int ch = i * 4 + (lane & 3);
                const uint32_t a = stg + (ch >> 3) * 8192 + row * 128 + (((ch & 7) ^ (row & 7)) << 4);
                const float* q = &o[i * 16];
                asm volatile("st.shared.v4.b32 [%0], {%1, %2, %3, %4};" :: "r"(a), "r"(pack_bf16(q[0] * i0, q[1] * i0)), "r"(pack_bf16(q[4] * i0, q[5] * i0)),
                             "r"(pack_bf16(q[8] * i0, q[9] * i0)), "r"(pack_bf16(q[12] * i0, q[13] * i0)) : "memory");
                asm volatile("st.shared.v4.b32 [%0], {%1, %2, %3, %4};" :: "r"(a + 1024), "r"(pack_bf16(q[2] * i1, q[3] * i1)), "r"(pack_bf16(q[6] * i1, q[7] * i1)),
                             "r"(pack_bf16(q[10] * i1, q[11] * i1)), "r"(pack_bf16(q[14] * i1, q[15] * i1)) : "memory");
            }
        };
        auto publish_o = [&]() {
            asm volatile("fence.proxy.async.shared::cta;" ::: "memory");
            __syncwarp();
            mbar_arrive_if(bar_of + 8 * wg, lane == 0);
        };
        int t = 0, left = 0, tdone = -1, b = 0, nout = 0;
        bool first = true, staged = false;
#pragma unroll 1
        for (;; b++) {
            const bool fresh = left == 0;
            const int tprev = t;
            FAT(b, 4);
            if (staged) { publish_o(); staged = false; }
            if (fresh) {
                item++;
                if (!q_ready) {
                    mbar_wait(bar_qf + 8 * (item & 1), (item >> 1) & 1);
                    asm volatile("ld.shared.s32 %0, [%1];" : "=r"(tnext) : "r"(slot + (item & 1) * 4) : "memory");
                }
                if (tnext < 0) break;
                t = tnext;
                left = fa_qt(t) + 1;
            }
            left--;
            if (fresh || first || left == 0) {
                if (tdone >= 0) store_o(tdone, nout);
                if (fresh) { g0 = gn0; g1 = gn1; }
                if (left == 0) { gn0 = __ldcg(g_gate + fa_qt(t) * 128 + r0); gn1 = __ldcg(g_gate + fa_qt(t) * 128 + r0 + 8); clear_out(t); }
            }
            FAT(b, 5);
            if (!k_ready) mbar_wait(bar_kf + 8 * (b & 1), (b >> 1) & 1);
            FAT(b, 6);
            asm volatile("bar.sync %0, 256;" :: "r"(3 + wg) : "memory");
            FAT(b, 0);
            issue_qk(b, item, FA_TRIM && wg == 0 && left == 0);
            FAT(b, 7);
            bool early = false;
            if (!fresh && !first && left != 0) {
                issue_pv(b - 1, true, FA_P0, false);
                wgmma_wait<1>();
                FAT(b, 1);
                mbar_arrive_if(bar_ke + 8 * (b & 1), lane == 0);
            } else {
                const bool hprev = FA_TRIM && fresh && wg == 0;
                early = (FA_EARLY && tdone >= 0) || b == 0 || (FA_TE && hprev);
                if (early) asm volatile("bar.arrive %0, 256;" :: "r"(4 - wg) : "memory");
                if (tdone >= 0) { nout++; staged = true; }
                tdone = fresh && b > 0 ? tprev : -1;
                v_hi = hprev ? v_lo - 512 : v_lo;
                acc_hi = !(hprev && first);
                if (b > 0) issue_pv(b - 1, !first, FA_P0, hprev); else { wgmma_fence(); wgmma_commit(); }
                first = fresh;
                wgmma_wait<1>();
                FAT(b, 1);
                mbar_arrive_if(bar_ke + 8 * (b & 1), lane == 0);
                mbar_arrive_if(bar_qe + 8 * (item & 1), lane == 0 && left == 0);
                if (left == 0) { mask(FA_TRIM ? 32 : 0); mask(FA_TRIM ? 33 : 1); }
                if (fresh) {
                    finish_rows();
                    l0 = l1 = 0.f;
                    m0 = fmaxf(s[0], s[1]); m1 = fmaxf(s[2], s[3]);
                    if (FA_TRIM && left == 0) { m0 = fmaxf(s[32], s[33]); m1 = fmaxf(s[34], s[35]); }
                    quad_max(m0, m1);
                }
            }
            if (FA_B0 || b > 0) {
                float u0, u1;
                if (left == 0) exps(std::integral_constant<int, 2>(), b, !early, u0, u1);
                else exps(std::integral_constant<int, 1>(), b, !early, u0, u1);
                if (!__any_sync(0xffffffff, !(u0 + u1 < 1.f))) { l0 += u0; l1 += u1; continue; }
            }
            softmax_exact(fresh, FA_TRIM && wg == 0 && left == 0, b);
        }
        if (tdone >= 0) { store_o(tdone, nout++); publish_o(); }
        issue_pv(b - 1, !first, 8, FA_TRIM && wg == 0);
        g0 = gn0; g1 = gn1;
        finish_rows();
        wgmma_wait<0>();
        done();
        store_o(t + 1024, nout);
        publish_o();
        return nout;
    }
}

__device__ __forceinline__ uint32_t cluster_ctarank() {
    uint32_t r; asm volatile("mov.u32 %0, %%cluster_ctarank;" : "=r"(r)); return r;
}
__device__ __forceinline__ uint32_t mapa_u32(uint32_t addr, uint32_t rank) {
    uint32_t r; asm volatile("mapa.shared::cluster.u32 %0, %1, %2;" : "=r"(r) : "r"(addr), "r"(rank)); return r;
}
__device__ __forceinline__ void cluster_sync_all() {
    asm volatile("barrier.cluster.arrive.release.aligned;\nbarrier.cluster.wait.acquire.aligned;" ::: "memory");
}
__device__ __forceinline__ void st_async_v4(uint32_t addr, uint32_t a, uint32_t b, uint32_t c, uint32_t d, uint32_t mbar) {
    asm volatile("st.async.weak.shared::cluster.mbarrier::complete_tx::bytes.v4.b32 [%0], {%1, %2, %3, %4}, [%5];"
                 :: "r"(addr), "r"(a), "r"(b), "r"(c), "r"(d), "r"(mbar) : "memory");
}
__device__ __forceinline__ void st_async_v2(uint32_t addr, uint32_t a, uint32_t b, uint32_t mbar) {
    asm volatile("st.async.weak.shared::cluster.mbarrier::complete_tx::bytes.v2.b32 [%0], {%1, %2}, [%3];"
                 :: "r"(addr), "r"(a), "r"(b), "r"(mbar) : "memory");
}
__device__ __forceinline__ void st_async_b32(uint32_t addr, uint32_t a, uint32_t mbar) {
    asm volatile("st.async.weak.shared::cluster.mbarrier::complete_tx::bytes.b32 [%0], %1, [%2];" :: "r"(addr), "r"(a), "r"(mbar) : "memory");
}
__device__ __forceinline__ void pace(int cycles) {
    if (cycles > 0) {
        uint32_t t0, t;
        asm volatile("mov.u32 %0, %%clock;" : "=r"(t0));
        do { asm volatile("mov.u32 %0, %%clock;" : "=r"(t)); } while (t - t0 < (uint32_t)cycles);
    }
}
__device__ __forceinline__ void mbar_wait_cl(uint32_t bar, uint32_t parity) {
    uint32_t done = 0;
    for (int it = 0; it < WAIT_LIMIT && !done; it++) {
        asm volatile(
            "{\n.reg .pred p;\n"
            "mbarrier.try_wait.parity.shared::cta.b64 p, [%1], %2;\n"
            "selp.u32 %0, 1, 0, p;\n}\n" : "=r"(done) : "r"(bar), "r"(parity) : "memory");
    }
}
__device__ __forceinline__ void ldmatrix_x4(uint32_t& r0, uint32_t& r1, uint32_t& r2, uint32_t& r3, uint32_t addr) {
    asm volatile("ldmatrix.sync.aligned.m8n8.x4.shared.b16 {%0,%1,%2,%3}, [%4];"
                 : "=r"(r0), "=r"(r1), "=r"(r2), "=r"(r3) : "r"(addr));
}
__device__ __forceinline__ void cp_async16(uint32_t dst, const void* src) {
    asm volatile("cp.async.cg.shared.global [%0], [%1], 16;" :: "r"(dst), "l"(src) : "memory");
}
__device__ __forceinline__ float bf16r(float x) { return __uint_as_float(pack_bf16(0.f, x) & 0xffff0000u); }

#define DBGP(i, w, ok)
#define DBG(i, w)
#define DBGD(i, w, dep)
#define DBG_EXTRA 0
__device__ __forceinline__ void tma_load_2d_mc(uint32_t dst, const CUtensorMap* map, uint32_t bar, int c0, int c1, uint16_t mask) {
    asm volatile(
        "cp.async.bulk.tensor.2d.shared::cluster.global.mbarrier::complete_tx::bytes.multicast::cluster [%0], [%1, {%3, %4}], [%2], %5;"
        :: "r"(dst), "l"((uint64_t)map), "r"(bar), "r"(c0), "r"(c1), "h"(mask) : "memory");
}
__device__ __forceinline__ void stmatrix_x4_trans(uint32_t addr, uint32_t r0, uint32_t r1, uint32_t r2, uint32_t r3) {
    asm volatile("stmatrix.sync.aligned.m8n8.x4.trans.shared.b16 [%0], {%1, %2, %3, %4};" :: "r"(addr), "r"(r0), "r"(r1), "r"(r2), "r"(r3) : "memory");
}
__device__ __forceinline__ void stmatrix_x2_trans(uint32_t addr, uint32_t r0, uint32_t r1) {
    asm volatile("stmatrix.sync.aligned.m8n8.x2.trans.shared.b16 [%0], {%1, %2};" :: "r"(addr), "r"(r0), "r"(r1) : "memory");
}
__device__ __forceinline__ uint4 lds128(uint32_t a) {
    uint4 v; asm volatile("ld.shared.v4.u32 {%0, %1, %2, %3}, [%4];" : "=r"(v.x), "=r"(v.y), "=r"(v.z), "=r"(v.w) : "r"(a) : "memory"); return v;
}
__device__ __forceinline__ void sts128(uint32_t a, uint32_t x, uint32_t y, uint32_t z, uint32_t w) {
    asm volatile("st.shared.v4.b32 [%0], {%1, %2, %3, %4};" :: "r"(a), "r"(x), "r"(y), "r"(z), "r"(w) : "memory");
}
__device__ __forceinline__ float2 lds64f(uint32_t a) {
    float2 v; asm volatile("ld.shared.v2.f32 {%0, %1}, [%2];" : "=f"(v.x), "=f"(v.y) : "r"(a) : "memory"); return v;
}
__device__ __forceinline__ void fence_async_smem() { asm volatile("fence.proxy.async.shared::cta;" ::: "memory"); }
#define ACC16(d) "+f"(d[0]), "+f"(d[1]), "+f"(d[2]), "+f"(d[3]), "+f"(d[4]), "+f"(d[5]), "+f"(d[6]), "+f"(d[7]), "+f"(d[8]), "+f"(d[9]), "+f"(d[10]), "+f"(d[11]), "+f"(d[12]), "+f"(d[13]), "+f"(d[14]), "+f"(d[15])
template <int ND>
__device__ __forceinline__ void wgmma_rs_n32(float (&d)[ND], const uint32_t (&a)[4], uint32_t db_lo, int scale_d) {
    asm volatile(
        "{\n.reg .pred p;\n.reg .b64 db;\nsetp.ne.b32 p, %21, 0;\nmov.b64 db, {%20, 0x40000040};\n"
        "wgmma.mma_async.sync.aligned.m64n32k16.f32.bf16.bf16 {%0,%1,%2,%3,%4,%5,%6,%7,%8,%9,%10,%11,%12,%13,%14,%15}, {%16,%17,%18,%19}, db, p, 1, 1, 0;\n}\n"
        : ACC16(d) : "r"(a[0]), "r"(a[1]), "r"(a[2]), "r"(a[3]), "r"(db_lo), "r"(scale_d));
}
template <int ND>
__device__ __forceinline__ void wgmma_ss_n32(float (&d)[ND], uint32_t da_lo, uint32_t db_lo, int scale_d) {
    asm volatile(
        "{\n.reg .pred p;\n.reg .b64 da, db;\nsetp.ne.b32 p, %18, 0;\nmov.b64 da, {%16, 0x40000040};\nmov.b64 db, {%17, 0x40000040};\n"
        "wgmma.mma_async.sync.aligned.m64n32k16.f32.bf16.bf16 {%0,%1,%2,%3,%4,%5,%6,%7,%8,%9,%10,%11,%12,%13,%14,%15}, da, db, p, 1, 1, 1, 0;\n}\n"
        : ACC16(d) : "r"(da_lo), "r"(db_lo), "r"(scale_d));
}
__device__ __forceinline__ void wgmma_ss_n8(float (&d)[4], uint32_t da_lo, uint32_t db_lo, int scale_d) {
    asm volatile(
        "{\n.reg .pred p;\n.reg .b64 da, db;\nsetp.ne.b32 p, %6, 0;\nmov.b64 da, {%4, 0x40000040};\nmov.b64 db, {%5, 0x00000010};\n"
        "wgmma.mma_async.sync.aligned.m64n8k16.f32.bf16.bf16 {%0,%1,%2,%3}, da, db, p, 1, 1, 1, 0;\n}\n"
        : "+f"(d[0]), "+f"(d[1]), "+f"(d[2]), "+f"(d[3]) : "r"(da_lo), "r"(db_lo), "r"(scale_d));
}

#define SCHED_FENCE()
__device__ __forceinline__ void wgmma_ss_n32_p(float (&d)[16], uint32_t da_lo, uint32_t db_lo, int scale_d) {
    asm volatile(
        "{\n.reg .pred p;\n.reg .b64 da, db;\nsetp.ne.b32 p, %18, 0;\nmov.b64 da, {%16, 0x40000040};\nmov.b64 db, {%17, 0x00000030};\n"
        "wgmma.mma_async.sync.aligned.m64n32k16.f32.bf16.bf16 {%0,%1,%2,%3,%4,%5,%6,%7,%8,%9,%10,%11,%12,%13,%14,%15}, da, db, p, 1, 1, 1, 0;\n}\n"
        : ACC16(d) : "r"(da_lo), "r"(db_lo), "r"(scale_d));
}

#define ACC20(d) ACC16(d), "+f"(d[16]), "+f"(d[17]), "+f"(d[18]), "+f"(d[19])
#define ACC20_STR "{%0,%1,%2,%3,%4,%5,%6,%7,%8,%9,%10,%11,%12,%13,%14,%15,%16,%17,%18,%19}"
__device__ __forceinline__ void wgmma_rs_n40(float (&d)[20], const uint32_t (&a)[4], uint32_t db_lo, int scale_d) {
    asm volatile(
        "{\n.reg .pred p;\n.reg .b64 db;\nsetp.ne.b32 p, %25, 0;\nmov.b64 db, {%24, 0x40000040};\n"
        "wgmma.mma_async.sync.aligned.m64n40k16.f32.bf16.bf16 " ACC20_STR ", {%20,%21,%22,%23}, db, p, 1, 1, 0;\n}\n"
        : ACC20(d) : "r"(a[0]), "r"(a[1]), "r"(a[2]), "r"(a[3]), "r"(db_lo), "r"(scale_d));
}
template <int TA, int SBO>
__device__ __forceinline__ void wgmma_ss_n40(float (&d)[20], uint32_t da_lo, uint32_t db_lo, int scale_d) {
    asm volatile(
        "{\n.reg .pred p;\n.reg .b64 da, db;\nsetp.ne.b32 p, %22, 0;\nmov.b64 da, {%20, %23};\nmov.b64 db, {%21, 0x40000040};\n"
        "wgmma.mma_async.sync.aligned.m64n40k16.f32.bf16.bf16 " ACC20_STR ", da, db, p, 1, 1, %24, 0;\n}\n"
        : ACC20(d) : "r"(da_lo), "r"(db_lo), "r"(scale_d), "n"(0x40000000 + SBO / 16), "n"(TA));
}
template <int SBO>
__device__ __forceinline__ void wgmma_ss_n48(float (&d)[24], uint32_t da_lo, uint32_t db_lo, int scale_d) {
    asm volatile(
        "{\n.reg .pred p;\n.reg .b64 da, db;\nsetp.ne.b32 p, %26, 0;\nmov.b64 da, {%24, %27};\nmov.b64 db, {%25, 0x40000040};\n"
        "wgmma.mma_async.sync.aligned.m64n48k16.f32.bf16.bf16 {%0,%1,%2,%3,%4,%5,%6,%7,%8,%9,%10,%11,%12,%13,%14,%15,%16,%17,%18,%19,%20,%21,%22,%23}, da, db, p, 1, 1, 0, 0;\n}\n"
        : ACC20(d), "+f"(d[20]), "+f"(d[21]), "+f"(d[22]), "+f"(d[23]) : "r"(da_lo), "r"(db_lo), "r"(scale_d), "n"(0x40000000 + SBO / 16));
}

#define PT(i, th)
struct ChainParams {
    CUtensorMap mapW[3];
    CUtensorMap mapX;
    CUtensorMap mapC;
    CUtensorMap mapWo;
    CUtensorMap mapM;
    CUtensorMap mapOut;
};
constexpr int CH_BLOCK = 384;
constexpr int CO_WO = 0;
constexpr int CH_XC = 5120, CH_XP = 8 * CH_XC;
constexpr int CO_XB = 65536;
constexpr int CO_OB = CO_XB + 2 * CH_XP;
constexpr int CO_P = CO_OB + 8192;
constexpr int CO_LS = CO_P + 3072;
constexpr int CO_SC = CO_LS + 8 * 1280;
constexpr int CH_TW = 6144 + 8192;
constexpr int CO_T = 21 * 8192;
constexpr int CO_WA = CO_T + 6144;
constexpr int CO_ST = CO_T + 3 * CH_TW + 6144;
constexpr int CO_OWN = CO_ST + 4096, CO_OWN2 = CO_SC + 1536;
constexpr int CO_BAR = CO_OWN + 4096;
constexpr int CH_SMEM = CO_BAR + 256 + DBG_EXTRA;
#define CH_GL 2
#define CH_A3 1
#define CH_D0 0
#define CH_PF 0
#define CH_NA 0
#define CH_LQ ""
#define CH_SQ ""
#define CH_XPF 0
#define CH_NSM 4
static_assert(CO_OWN2 + 1024 <= CO_T && CH_NSM <= 4, "smem layout");
#ifndef M_D0
#define M_D0 0
#endif
#define CH_POLL_DELAY 220
#define CH_VPOS 2
#define CH_OW 12
#define CH_OF 12
#define CH_Q0 0
#define CH_QI 12
#define CH_QX 0
#define CH_Q1 (CH_Q0 + CH_QI + CH_QX)
#define CH_VA 5
#define CH_SPOS 0
#define CH_LSW 1
#define CH_QE 16
#define CH_KE 16
#define CH_QD 0
#define CH_GAP 0
#define CH_QS 0
#define CH_KS 0
#define CH_VS 4
#define CH_A7 7
#define CH_RF 0
#define CH_LSS 0
#define CH_OS 1
#define CH_MG 0
#define CH_MBT 0x76543210u
#define CH_MB(i) ((int)(CH_MBT >> 4 * (i)) & 7)
#define CH_AS 0x64207531u
#define CH_QL 16
#define CH_ML 0x112112
#define CH_DEP 1
#define CH_SP 2
#define CH_VD 0
#define CH_MP 2
#define CH_MP0 2
#define CH_OFE 3
#define CH_MS 1
#define CH_HA 3
#define CH_LD 4
#define CH_TWP 0
#define CH_SUMC 2
#define CH_ES 0
#define CH_ST 224
#define CH_KEEP 1
#define CH_PINB 1
#define CH_DRY 1
#define CH_D1 4500
#define CH_D2 11000
#define CH_CHAINS 4

constexpr float CH_SC = 0.08838834764831845f * 1.4426950408889634f;
__device__ __forceinline__ uint32_t pin(uint32_t v) { return __shfl_sync(0xffffffff, v, threadIdx.x & 31); }

__device__ __forceinline__ void out_finished() {
    if (atomicAdd(&g_ctr[CT_FIN], 1u) == M_GRID + 64 - 1)
        for (int i = 0; i < CT_N / 4; i++) reinterpret_cast<uint4*>(g_ctr)[i] = make_uint4(0u, 0u, 0u, 0u);
}
__device__ __forceinline__ uint32_t tail_a(uint32_t c) { return c < 3 ? CO_XB + 2 * CH_XC + c * 8192 : CO_OB; }
__device__ __forceinline__ void out_flush_half(const float* acc, const CUtensorMap* map, uint32_t stg, int tid, int bar, int n0, int m0) {
    const int lane = tid & 31, row = (lane & 7) + ((lane >> 3) & 1) * 8;
#pragma unroll
    for (int j = 0; j < 16; j += 2) {
        const float* a = &acc[j * 4];
        stmatrix_x4(stg + (j >> 3) * 8192 + (((tid >> 5) & 3) * 16 + row) * 128 + ((((j & 7) + (lane >> 4)) ^ (row & 7)) << 4),
                    pack_bf16(a[0], a[1]), pack_bf16(a[2], a[3]), pack_bf16(a[4], a[5]), pack_bf16(a[6], a[7]));
    }
    asm volatile("fence.proxy.async.shared::cta;\nbar.sync %0, 128;" :: "r"(bar) : "memory");
    asm volatile("{\n.reg .pred p;\nsetp.ne.b32 p, %0, 0;\n@p bra FL_SKIP;\n"
                 "cp.reduce.async.bulk.tensor.2d.global.shared::cta.add.tile.bulk_group [%1, {%3, %5}], [%2];\n"
                 "cp.reduce.async.bulk.tensor.2d.global.shared::cta.add.tile.bulk_group [%1, {%4, %5}], [%2 + 8192];\n"
                 "cp.async.bulk.commit_group;\nFL_SKIP:\n}"
                 :: "r"(tid & 127), "l"((uint64_t)map), "r"(stg), "r"(n0), "r"(n0 + 64), "r"(m0) : "memory");
    __syncwarp();
}
__device__ __forceinline__ void out_flush(const float (&acc)[128], const CUtensorMap* map, uint32_t stg0, uint32_t stg1, int tid, int bar, int n0, int m0) {
    out_flush_half(acc, map, stg0, tid, bar, n0, m0);
    out_flush_half(acc + 64, map, stg1, tid, bar, n0 + 128, m0);
}

__global__ void __cluster_dims__(8, 1, 1) __launch_bounds__(CH_BLOCK, 1)
chain_kernel(const __grid_constant__ ChainParams P) {
    extern __shared__ uint8_t smem_raw[];
    const int tid = threadIdx.x, warp = __shfl_sync(0xffffffff, tid >> 5, 0), lane = tid & 31;
    const int rank = (int)cluster_ctarank();
    constexpr uint32_t sd = 1024;
    const uint32_t sb = ((uint32_t)rank << 24) + sd;
    if (smem_u32(smem_raw) != sb) __trap();
    const int C = blockIdx.x >> 3;
    const int h = C * 4 + (rank >> 1);
    const int qd = lane >> 2, qc = lane & 3;
    const int t4 = warp & 3, wg = warp >> 2;
    pdl_launch_dependents();
    uint32_t t_start;
    asm volatile("mov.u32 %0, %%clock;" : "=r"(t_start));
    t_start = __shfl_sync(0xffffffff, t_start, 0);
    TS_BEGIN(2);
    PT(0, 0);
    const uint32_t bar_mem = sb + CO_BAR + 128, bar_o = sb + CO_BAR + 32, bar_sc = bar_o + 32, bar_x = bar_sc + 8, bar_l = bar_x + 16, bar_w = bar_l + 8;
    const uint32_t bar_wo = bar_o + 24;
    auto chunk = [&](int i) { return (uint32_t)((rank - i) & 7); };
    auto mine = [](int g, int c) { return (int)((CH_AS >> (g * 16 + c * 4)) & 7); };
    const int wcol = h * HD + (rank & 1) * 64;
    auto wdst = [&](int g, int i) { return i == 0 ? CO_WA + g * CH_TW : g && i == 7 ? CO_ST : (g ? CO_XB + CH_XP : 0) + (i - 1) * 8192; };
    auto vdst = [&](int i) { return i >= 2 && i < 10 ? CO_XB + CH_XP + (i - 2) * CH_XC : (i < 2 ? CO_WA + 2 * CH_TW : i < 12 ? CO_OB : i < 14 ? CO_LS : CO_ST) + (i & 1) * 4096; };
    if ((tid & 127) == 0) {
        pace(CH_D0);
        const uint32_t bar = wg == 2 ? bar_x : bar_w + 8 * wg;
        mbar_init(bar, 1);
        asm volatile("fence.mbarrier_init.release.cluster;" ::: "memory");
        mbar_expect_tx(bar, wg == 2 ? CH_XP : 65536);
#pragma unroll 1
        for (int i = 0; i < 8; i++) {
            if (wg == 2) {
                tma_load_2d(sb + CO_XB + i * CH_XC, &P.mapX, bar, i * 64, 0);
                tma_load_2d(sb + CO_XB + i * CH_XC + 4096, &P.mapM, bar, i * 64, 0);
            } else tma_load_2d(sb + wdst(wg, i), &P.mapW[wg ^ (i & 1)], bar, wcol, chunk(mine(wg, i >> 1)) * 64);
        }
    }
    if (warp == 9 && lane < 24 && lane != 9 && (lane >> 1) != 6) {
        mbar_init(sb + CO_BAR + 8 * lane, lane == 15 ? 16 : 1);
        asm volatile("fence.mbarrier_init.release.cluster;" ::: "memory");
    }
    __syncthreads();
    PT(1, 0);
    if (wg == 2 || (wg == 0 && CH_QL < 16)) asm volatile("bar.arrive 10, %0;" :: "n"(CH_QL < 16 ? 384 : 256) : "memory");
    if (wg == 2) {
        const int t = tid - 256;
        sts128(sb + CO_T + (2 + (t >> 6)) * CH_TW + 5120 + (t & 63) * 16, 0u, 0u, 0u, 0u);
        if (t < 32) sts128(sb + CO_P + (t >> 3) * 768 + 640 + (t & 7) * 16, 0u, 0u, 0u, 0u);
    }
    const uint32_t wfrag = (((lane >> 4) << 3) + (lane & 7)) * 128 + (((t4 * 2 + ((lane >> 3) & 1)) ^ (lane & 7)) << 4);
    const uint32_t aO = pin(sb + wg * CH_TW + wfrag);
    const uint32_t aL = pin(sb + lane * 16);
    uint32_t w[32][4];
    auto load_w = [&](int g, bool v) {
#pragma unroll
        for (int e = CH_NSM; e < 32; e++) ldmatrix_x4_trans(w[e][0], w[e][1], w[e][2], w[e][3], aO + ((v ? vdst(e >> 1) + (e & 1) * 2048 : wdst(g, e >> 2) + (e & 3) * 2048) - g * CH_TW));
        fence_async_smem();
    };
    auto pass = [&](auto& d, int g, int b, int j0, int j1, int js, bool group = true) {
        const uint32_t lo = desc_lo(sd + CO_XB + b * CH_XP, 16);
        if (group) wgmma_fence();
#pragma unroll
        for (int j = 0; j < 32; j++) if (j >= j0 && j < j1) {
            const int f = js < 0 ? j : j < js ? j + CH_NSM : j < js + CH_NSM ? j - js : j;
            const int e = sizeof(d) == 64 ? (f >> 2) * 8 + (js < 0 ? 4 : 0) + (f & 3) : f;
            const uint32_t db = lo + chunk(sizeof(d) == 64 ? mine(g, f >> 2) : f >> 2) * (CH_XC / 16) + (e & 3) * 2, da = desc_lo(sd + CO_WA + g * CH_TW + e * 2048, 16);
            if constexpr (sizeof(d) == 64) { if (e < CH_NSM) wgmma_ss_n32(d, da, db, j != 0); else wgmma_rs_n32(d, w[e], db, j != 0); }
            else { if (e < CH_NSM) wgmma_ss_n40<1, 1024>(d, da, db, j != 0); else wgmma_rs_n40(d, w[e], db, j != 0); }
        }
        if (group) wgmma_commit();
    };
    auto uni = [](uint32_t v) { return __shfl_sync(0xffffffff, v, 0); };
    auto roff = [&](int j) { return (uint32_t)(((rank + j) & 7) - rank) << 24; };
    auto store32 = [&](const float* d, uint32_t a) {
        stmatrix_x4_trans(a, pack_bf16(d[0], d[1]), pack_bf16(d[2], d[3]), pack_bf16(d[4], d[5]), pack_bf16(d[6], d[7]));
        stmatrix_x4_trans(a + 2048, pack_bf16(d[8], d[9]), pack_bf16(d[10], d[11]), pack_bf16(d[12], d[13]), pack_bf16(d[14], d[15]));
    };
    auto load32 = [&](uint32_t (&r)[8], uint32_t a) {
        ldmatrix_x4_trans(r[0], r[1], r[2], r[3], a);
        ldmatrix_x4_trans(r[4], r[5], r[6], r[7], a + 2048);
    };
    auto add32 = [&](float* d, const uint32_t (&r)[8], uint32_t a) {
        wgmma_wait<0>();
#pragma unroll
        for (int i = 0; i < 8; i++) { d[2 * i] += __uint_as_float(r[i] << 16); d[2 * i + 1] += __uint_as_float(r[i] & 0xffff0000u); }
        store32(d, a);
    };
    auto scores = [&](float (&d)[24], auto sbo, uint32_t q) {
        wgmma_fence();
#pragma unroll
        for (int ks = 0; ks < 4; ks++) wgmma_ss_n48<decltype(sbo)::value>(d, desc_lo(sd + q, 16) + ks * 2, desc_lo(sd + CO_T + CH_TW, 16) + ks * 2, ks != 0);
        wgmma_commit();
    };
    auto add_scores = [&](uint32_t a, uint32_t b, float (&v)[10]) {
        const uint4 a0 = lds128(a), a1 = lds128(a + 512);
        const float2 a2 = lds64f(b);
        v[0] += __uint_as_float(a0.x); v[1] += __uint_as_float(a0.y); v[2] += __uint_as_float(a0.z); v[3] += __uint_as_float(a0.w);
        v[4] += __uint_as_float(a1.x); v[5] += __uint_as_float(a1.y); v[6] += __uint_as_float(a1.z); v[7] += __uint_as_float(a1.w);
        v[8] += a2.x; v[9] += a2.y;
    };
    auto row_max = [&](const float (&v)[10]) {
        float mx = fmaxf(fmaxf(fmaxf(v[0], v[1]), fmaxf(v[2], v[3])), fmaxf(fmaxf(v[4], v[5]), fmaxf(v[6], v[7])));
        mx = fmaxf(mx, fmaxf(v[8], v[9]));
        mx = fmaxf(mx, __shfl_xor_sync(0xffffffff, mx, 1));
        return fmaxf(mx, __shfl_xor_sync(0xffffffff, mx, 2)) * CH_SC;
    };
    auto local_pv = [&](int s, int st) {
        float dc[16];
        wgmma_fence();
#pragma unroll
        for (int ks = 0; ks < 3; ks++) wgmma_ss_n32_p(dc, desc_lo(sd + CO_T + (2 + (s & 1)) * CH_TW + ks * 2048, 16), desc_lo(sd + CO_P + ks * 256, 128), ks != 0);
        wgmma_commit();
        wgmma_wait<0>();
        store32(dc, aO - CH_TW + st);
    };
    float gs = 0.f;
    auto load_gate = [&](int s) { asm volatile("ld.global.cg.f32 %0, [%1];" : "=f"(gs) : "l"(g_gate + s * SEGL + t4 * 8 + qd) : "memory"); };
    auto softmax = [&](int s, float (&u)[11]) {
        float v[10];
        {
            const uint4 a0 = lds128(aL + CO_OWN + t4 * 1024), a1 = lds128(aL + CO_OWN + t4 * 1024 + 512);
            const float2 a2 = lds64f(aL + CO_OWN2 + t4 * 256 - lane * 8);
            v[0] = __uint_as_float(a0.x); v[1] = __uint_as_float(a0.y); v[2] = __uint_as_float(a0.z); v[3] = __uint_as_float(a0.w);
            v[4] = __uint_as_float(a1.x); v[5] = __uint_as_float(a1.y); v[6] = __uint_as_float(a1.z); v[7] = __uint_as_float(a1.w);
            v[8] = a2.x; v[9] = a2.y;
        }
        mbar_wait_cl(bar_l, s & 1);
        add_scores(aL + t4 * 1024 + CO_LS + (s & 1) * 5120, aL + t4 * 256 - lane * 8 + CO_LS + (s & 1) * 5120 + 4096, v);
        const int lim = t4 * 8 + qd - 2 * qc;
#pragma unroll
        for (int j = 0; j < 8; j++) if ((j >> 1) * 8 + (j & 1) > lim) v[j] = -INFINITY;
        const float mx = row_max(v);
#pragma unroll
        for (int j = 0; j < 10; j++) u[j] = v[j];
        u[10] = mx;
    };
    auto softmax1 = [&](float (&u)[11]) {
#pragma unroll
        for (int j = 0; j < 10; j++) u[j] = ex2f(fmaf(u[j], CH_SC, -u[10]));
        u[10] = (((u[0] + u[1]) + (u[2] + u[3])) + ((u[4] + u[5]) + (u[6] + u[7]))) + (u[8] + u[9]);
    };
    auto softmax2 = [&](float (&v)[11]) {
        float sum = v[10];
        sum += __shfl_xor_sync(0xffffffff, sum, 1);
        sum += __shfl_xor_sync(0xffffffff, sum, 2);
        asm("rcp.approx.ftz.f32 %0, %0;" : "+f"(sum));
        sum *= 1.f - gs;
        const uint32_t pa = aL + CO_P + t4 * 768;
        stmatrix_x4(pa, pack_bf16(v[0] * sum, v[1] * sum), pack_bf16(v[2] * sum, v[3] * sum), pack_bf16(v[4] * sum, v[5] * sum), pack_bf16(v[6] * sum, v[7] * sum));
        asm volatile("stmatrix.sync.aligned.m8n8.x1.shared.b16 [%0], {%1};" :: "r"(pa + 512), "r"(pack_bf16(v[8] * sum, v[9] * sum)) : "memory");
    };
    if (mapa_u32(bar_l, rank ^ 1) != (bar_l ^ (1u << 24)) || mapa_u32(bar_l, (rank + 3) & 7) != bar_l + roff(3)) __trap();
    asm volatile("bar.sync %0, 128;" :: "r"(12 + wg) : "memory");
    if (__shfl_sync(0xffffffff, tid, 1) < 256) {
#pragma unroll 1
        for (int rep = CH_DRY ? 0 : 1; rep < 2; rep++) {
            if (rep) mbar_wait(bar_w + 8 * wg, 0);
            PT(3, 0);
            load_w(wg, false);
            if (rep) {
                asm volatile("bar.arrive %0, 160;" :: "r"(wg ? 2 : 15) : "memory");
                asm volatile("barrier.cluster.arrive.relaxed.aligned;" ::: "memory");
                mbar_wait(bar_x, 0);
            }
            asm volatile("bar.sync 12, 256;" ::: "memory");
            PT(7, 0);
            float d[16];
            pass(d, wg, 0, 0, 16, -1);
            wgmma_wait<0>();
            store32(d, aO + CO_T + (1 - 2 * wg) * CH_TW);
            pass(d, wg, 0, 0, 16, 0);
            asm volatile("bar.sync 13, 256;" ::: "memory");
            uint32_t r[8];
            load32(r, aO + CO_T);
            add32(d, r, aO + CO_T);
        }
    }
    PT(8, 0);
    TS_BEGIN(5);
    PT(9, 0);

    if (wg < 2) {
        const uint32_t aM = pin(sb + CO_XB + 4096 + (lane & 7) * 128 + (((lane >> 3) ^ (lane & 7)) << 4));
        uint32_t coff[4];
#pragma unroll
        for (int i = 0; i < 4; i++) coff[i] = uni(chunk(mine(wg, i)) * CH_XC);
        auto mem_proj = [&](int s, auto gc) {
            constexpr int G = decltype(gc)::value;
            const uint32_t par = s & 1;
            float acc[4][4];
#pragma unroll
            for (int i = 0; i < 4; i++) acc[i][0] = acc[i][1] = acc[i][2] = acc[i][3] = 0.f;
            const uint32_t am = aM + par * CH_XP;
            uint32_t b[4][4], ok = 1;
            auto bar = [&](int c) { return bar_mem + 8 * CH_MB(mine(G, c)); };
            auto load = [&](int c) {
                if (c ? CH_MB(mine(G, c)) != CH_MB(mine(G, c - 1)) : G == 0)
                    asm volatile("{\n.reg .pred p, q;\n.reg .u32 c;\nsetp.ne.u32 p, %2, 0;\n@p bra MP_DONE;\nmov.u32 c, 0;\n"
                                 "MP_LOOP:\nmbarrier.try_wait.parity.shared::cta.b64 p, [%0], %1;\nadd.u32 c, c, 1;\nsetp.lt.and.u32 q, c, %3, !p;\n"
                                 "@q bra MP_LOOP;\nMP_DONE:\n}" :: "r"(bar(c)), "r"(par ^ 1), "r"(ok), "n"(WAIT_LIMIT / 64) : "memory");
                uint32_t* r = b[2 * c & 3];
                ldmatrix_x4(r[0], r[1], r[2], r[3], am + coff[c]);
                r = b[(2 * c + 1) & 3];
                ldmatrix_x4(r[0], r[1], r[2], r[3], (am ^ 64) + coff[c]);
                if (c < 3 && CH_MB(mine(G, c + 1)) != CH_MB(mine(G, c))) ok = mbar_try(bar(c + 1), par ^ 1);
            };
            auto mma = [&](int i) {
#pragma unroll
                for (int j = 0; j < 4; j++) {
                    const uint32_t* a = w[(i >> 1) * 8 + ((j & 1) ^ G) * 4 + (i & 1) * 2 + (j >> 1)];
                    mma_16816(acc[j], a[0], a[1], a[2], a[3], b[i & 3][j & 2], b[i & 3][(j & 2) + 1]);
                }
            };
#pragma unroll
            for (int e = 0; e < CH_NSM; e++) ldmatrix_x4_trans(w[e][0], w[e][1], w[e][2], w[e][3], aO + CO_WA + e * 2048);
            if (G == 1) asm volatile("bar.sync 10, %0;" :: "n"(CH_QL < 16 ? 384 : 256) : "memory");
            else ok = mbar_try(bar(0), par ^ 1);
            DBG(11, 0);
            load(0);
#pragma unroll
            for (int c = 0; c < 3; c++) {
                const int at = (CH_ML >> (c * 4 + G * 12)) & 3;
                if (at == 0) load(c + 1);
                mma(2 * c);
                if (at == 1) load(c + 1);
                mma(2 * c + 1);
                if (at == 2) load(c + 1);
            }
            mma(6);
            uint32_t dep = __float_as_uint(acc[CH_HA & 3][0]);
            mma(7);
            if (CH_HA >= 4) dep = __float_as_uint(acc[CH_HA & 3][0]);
            asm volatile("bar.arrive %0, 384;" :: "r"(5 | (dep & (s >> 10))) : "memory");
            uint32_t r[4];
#pragma unroll
            for (int i = 0; i < 4; i++) r[i] = pack_bf16(acc[i >> 1][(i & 1) * 2] + acc[(i >> 1) + 2][(i & 1) * 2], acc[i >> 1][(i & 1) * 2 + 1] + acc[(i >> 1) + 2][(i & 1) * 2 + 1]);
            DBGD(40 + warp, warp, r[0] ^ r[1]);
            asm volatile("{\n.reg .pred q;\nsetp.ne.s32 q, %3, 0;\n"
                         "@q stmatrix.sync.aligned.m8n8.x2.trans.shared.b16 [%0], {%1, %2};\n"
                         "@q stmatrix.sync.aligned.m8n8.x2.trans.shared.b16 [%0 + %4], {%1, %2};\n"
                         "@q stmatrix.sync.aligned.m8n8.x2.trans.shared.b16 [%0 + 2 * %4], {%1, %2};\n"
                         "@q stmatrix.sync.aligned.m8n8.x2.trans.shared.b16 [%0 + 3 * %4], {%1, %2};\n}"
                         :: "r"(aO + (CO_XB + 4096 + G * (CH_XC - CH_TW) + (par ^ 1) * CH_XP)), "r"(r[0]), "r"(r[1]),
                            "r"(s - (NSEG - 1)), "n"(2 * CH_XC) : "memory");
            stmatrix_x2_trans(aO + CO_T + (G ? 5120 : CH_TW + 4096), r[2], r[3]);
            fence_async_smem();
        };
        if (wg == 0) {
#pragma unroll 1
            for (int s = 0; s < NSEG; s++) {
                const uint32_t par = s & 1;
                mem_proj(s, std::integral_constant<int, 0>());
                asm volatile("bar.arrive 1, 256;" ::: "memory");
                asm volatile("bar.sync 8, 384;" ::: "memory");
                if (s == NSEG - 1) break;
                if (tid == 96) {
#pragma unroll
                    for (int j = 1; j < 8; j++) {
                        int n = 0;
                        for (int i = 1; i < 8; i++) n += CH_MB(i) == j;
                        if (n) mbar_expect_tx(bar_mem + 8 * j, 1024 * n);
                        if (j < 4) mbar_expect_tx(bar_o + 8 * j - 8, 512 << j);
                    }
                }
                __syncwarp();
                uint32_t* wp = g_xbuf + (size_t)rank * 2048 + C * 256 + qc * 64 + t4 * 8 + qd;
                asm volatile("st.relaxed.gpu.global" CH_SQ ".u32 [%0], %1;" :: "l"(wp + ((s + 2) & 3) * 16384), "r"(~0u) : "memory");
                asm volatile("st.relaxed.gpu.global" CH_SQ ".u32 [%0], %1;" :: "l"(wp + ((s + 2) & 3) * 16384 + 32), "r"(~0u) : "memory");
                if (__builtin_expect(s == 0, 0)) {
                    asm volatile("barrier.cluster.wait.aligned;" ::: "memory");
                    mbar_wait(bar_wo, 0);
                    const int sr = (qd >> 2) * 2 + (qd & 1) + (qd & 2) * 4;
#pragma unroll 2
                    for (int ks = t4; ks < 32; ks += 4) {
                        const uint32_t a = sb + CO_WO + ks * 2048;
                        uint4 u[2][2];
#pragma unroll
                        for (int i = 0; i < 4; i++) { const int r = sr + (i >> 1) * 4; u[i >> 1][i & 1] = lds128(a + r * 128 + (((qc * 2 + (i & 1)) ^ (r & 7)) << 4)); }
                        __syncwarp();
#pragma unroll
                        for (int i = 0; i < 4; i++) {
                            const uint4 u0 = u[i >> 1][0], u1 = u[i >> 1][1];
                            const uint32_t sel = (i & 1) ? 0x7632 : 0x5410;
                            sts128(a + (qd + (i >> 1) * 8) * 128 + (((qc * 2 + (i & 1)) ^ qd) << 4),
                                   __byte_perm(u0.x, u0.y, sel), __byte_perm(u0.z, u0.w, sel), __byte_perm(u1.x, u1.y, sel), __byte_perm(u1.z, u1.w, sel));
                        }
                    }
                    fence_async_smem();
                }
                mbar_wait(bar_x + 8 * (par ^ 1), ((s + 1) >> 1) & 1);
                asm volatile("bar.sync 7, 384;" ::: "memory");
                float d[16];
                float c[4];
                const uint32_t alo = desc_lo(sd + CO_WO, 16), blo = desc_lo(sd + CO_OB, 128);
                wgmma_fence();
                pass(d, 0, par ^ 1, 0, CH_Q0, -1, false);
                asm volatile("bar.sync 11, 256;" ::: "memory");
#pragma unroll
                for (int i = 0; i < 32; i++) {
                    if (i == 4) { pass(d, 0, par ^ 1, CH_Q0 + min(4, CH_QI), CH_Q0 + min(4, CH_QI) + CH_QX, -1, false); mbar_wait_cl(bar_o, par); }
                    if (i == 8) mbar_wait_cl(bar_o + 8, par);
                    if (i == CH_OW) mbar_wait_cl(bar_o + 16, par);
                    wgmma_ss_n8(c, alo + i * 128, blo + i * 16, i != 0);
                    if (i < CH_QI) pass(d, 0, par ^ 1, CH_Q0 + i + (i < 4 ? 0 : CH_QX), CH_Q0 + i + (i < 4 ? 0 : CH_QX) + 1, -1, false);
                }
                wgmma_commit();
                wgmma_wait<0>();
                asm volatile("st.relaxed.gpu.global" CH_SQ ".u32 [%0], %1;" :: "l"(wp + (s & 3) * 16384), "r"(pack_bf16(c[0], c[2])) : "memory");
                asm volatile("st.relaxed.gpu.global" CH_SQ ".u32 [%0], %1;" :: "l"(wp + (s & 3) * 16384 + 32), "r"(pack_bf16(c[1], c[3])) : "memory");
                asm volatile("bar.arrive 6, 384;" ::: "memory");
                pace(CH_QD);
                asm volatile("bar.arrive 4, 384;" ::: "memory");
                DBG(8, 0);
                if (CH_Q1 < 16) pass(d, 0, par ^ 1, CH_Q1, 16, -1);
                asm volatile("bar.sync 9, 256;" ::: "memory");
                wgmma_wait<0>();
                store32(d, aO + CO_T + CH_TW);
                asm volatile("bar.arrive 12, 256;" ::: "memory");
                if (CH_QL) pass(d, 0, (par ^ 1) + (s >> 10), 0, CH_QL, CH_QS);
                DBG(21, 0);
                if (tid == 0) {
                    if (s + 2 < NSEG) {
                        mbar_expect_tx(bar_x + 8 * par, 32768);
                        tma_load_2d_mc(sb + CO_XB + par * CH_XP + rank * CH_XC, &P.mapX, bar_x + 8 * par, rank * 64, (s + 2) * SEGL, (uint16_t)0xff);
                        if (CH_XPF) asm volatile("cp.async.bulk.prefetch.tensor.2d.L2.global [%0, {%1, %2}];" :: "l"(&P.mapX), "r"(rank * 64), "r"((s + 2 + CH_XPF) * SEGL) : "memory");
                    } else {
#pragma unroll 1
                        for (int i = 0; i < 8; i++) tma_load_2d(sb + CO_WO + i * 8192, &P.mapWo, bar_wo, (rank & 3) * 128 + (i & 1) * 64, (h & ~1) * HD + (i >> 1) * 64);
                    }
                }
                __syncwarp();
                asm volatile("bar.sync 13, 256;" ::: "memory");
                uint32_t r[8];
                load32(r, aO + CO_T);
                if (CH_QL < 16) {
                    asm volatile("bar.sync 10, 384;" ::: "memory");
                    pass(d, 0, (par ^ 1) + (s >> 10), CH_QL, CH_QE, CH_QS);
                }
                add32(d, r, aO + CO_T);
                DBG(22, 0);
            }
            *reinterpret_cast<uint2*>(g_xbuf + 16384 + blockIdx.x * 256 + tid * 2) = make_uint2(~0u, ~0u);
        PT(10, 0);
            if (tid == 0) {
                mbar_expect_tx(bar_wo, 65536 + 32768);
                mbar_expect_tx(bar_w, 24576);
                asm volatile("prefetch.tensormap [%0];" :: "l"(&P.mapOut) : "memory");
                wait_ctr(CT_CA + 63, 16u);
            }
            __syncwarp();
            uint32_t fin = 0;
#pragma unroll 1
            for (int r = 0; r < 2; r++) {
                float acc[64];
                mbar_wait(bar_wo, 1);
                asm volatile("bar.sync %0, 256;" :: "r"(15 - r) : "memory");
                asm volatile("{\n.reg .pred p;\nsetp.eq.b32 p, %2, 32;\n@p atom.relaxed.gpu.global.inc.u32 %0, [%1], 0x7fffffff;\n}"
                             : "+r"(fin) : "l"(&g_ctr[CT_FIN]), "r"(tid + r * 128) : "memory");
                wgmma_fence();
#pragma unroll
                for (int i = 0; i < 16; i++) {
                    const uint32_t c = (rank + (i >> 2)) & 3;
                    const uint32_t a = r == 0 ? tail_a(c) : i < 4 ? CO_WA + CH_TW : CO_XB + CH_XP + c * 8192;
                    if (i == 4) mbar_wait(r ? bar_w : bar_wo, 1);
                    wgmma_ss_n128_lo<1>(acc, desc_lo(sd + a, 16) + (i & 3) * 2, desc_lo(sd + CO_WO, 8192) + c * 1024 + (i & 3) * 128, i);
                }
                wgmma_commit();
                wgmma_wait<0>();
                PT(5, 0);
                out_flush_half(acc, &P.mapOut, sb + (r ? tail_a(0) : CO_T), tid, 12, (rank & 3) * 128, SEQ - 128 + r * 64);
            }
            if (fin == M_GRID + 64 - 1)
                for (int i = 0; i < CT_N / 4; i++) reinterpret_cast<uint4*>(g_ctr)[i] = make_uint4(0u, 0u, 0u, 0u);
            if (tid == 0) {
                asm volatile("cp.async.bulk.wait_group.read 0;" ::: "memory");
                PT(15, 0);
            }
        } else {
            const uint32_t usc = uni(CO_SC + min(t4, 2) * 512 + roff((rank ^ 1) - rank)), uscb = uni(bar_sc ^ (1u << 24));
            const uint32_t vaddr = pin(sb + CO_T + 2 * CH_TW + (lane & 15) * 128 + (((t4 * 2 + (lane >> 4)) ^ (lane & 7)) << 4));
            const uint32_t dsta = pin(sb + CO_OB + t4 * 256 + (qc >> 1) * 128 + qd * 16 + (qc & 1) * 8);
            auto store_ctx = [&](int s) {
                if (tid == CH_ST && (uint32_t)s < NSEG - 3) {
                    tma_store_2d(&P.mapC, sb + CO_ST, (rank & 1) * 64, h * SEQ + s * SEGL);
                    asm volatile("cp.async.bulk.commit_group;" ::: "memory");
                }
                __syncwarp();
            };
            auto signal_ctx = [&](int s) {
                if (tid == CH_ST && (s & 3) == 1)
                    asm volatile("cp.async.bulk.wait_group 0;\nred.relaxed.gpu.global.add.u32 [%0], 1;" :: "l"(&g_ctr[CT_CB - 1 + (s >> 2)]) : "memory");
                __syncwarp();
            };
            uint32_t uo[8], ub[8];
#pragma unroll
            for (int i = 0; i < 8; i++) { uo[i] = uni(roff(i) + i * 1024); ub[i] = uni(roff(i) + bar_o + (i < 2 ? 0 : i < 4 ? 8 : 16)); }
#pragma unroll 1
            for (int s = 0; s < NSEG; s++) {
                const uint32_t par = s & 1;
                mem_proj(s, std::integral_constant<int, 1>());
                asm volatile("bar.sync 1, 256;" ::: "memory");
                float d[24];
                scores(d, std::integral_constant<int, CH_XC>(), CO_XB + 4096 + (par ^ 1) * CH_XP);
                if (s == NSEG - 1) { wgmma_wait<0>(); break; }
                asm volatile("bar.arrive 8, 384;" ::: "memory");
                if (s == 0) asm volatile("barrier.cluster.wait.aligned;" ::: "memory");
                const uint32_t sca = (aL | (s >> 10)) + usc;
                wgmma_wait<0>();
                float v[10], u[12];
#pragma unroll
                for (int j = 0; j < 12; j++) u[j] = d[(j >> 1) * 4 + (j & 1)] + d[(j >> 1) * 4 + (j & 1) + 2];
                if (t4 < 3) {
                    auto sel = [&](int j) { return t4 == 0 ? u[j] : t4 == 1 ? u[4 + j] : u[8 + j]; };
                    asm volatile("st.async.weak.shared::cluster.mbarrier::complete_tx::bytes.v4.f32 [%0], {%2, %3, %4, %5}, [%1];"
                                 :: "r"(sca), "r"(uscb), "f"(sel(0)), "f"(sel(1)), "f"(sel(2)), "f"(sel(3)) : "memory");
                }
#pragma unroll
                for (int j = 0; j < 10; j++) v[j] = j < 8 ? u[j] : u[j] + u[j + 2];
                DBG(3, 4);
                if (CH_ES) signal_ctx(s); else store_ctx(s - 2);
                uint32_t vb[3][4];
                auto load_v = [&](float dep) {
                    asm volatile("bar.sync %0, 256;" :: "r"(CH_VD ? 3 | (__float_as_uint(dep) & (s >> 10)) : 3) : "memory");
#pragma unroll
                    for (int k = 0; k < 3; k++) ldmatrix_x4_trans(vb[k][0], vb[k][1], vb[k][2], vb[k][3], vaddr + par * CH_TW + k * 2048);
                };
                mbar_wait_cl(bar_sc, par);
                DBG(4, 4);
                {
                    const uint4 a0 = lds128(aL + CO_SC), a1 = lds128(aL + CO_SC + 512), a2 = lds128(aL + CO_SC + 1024);
                    v[0] += __uint_as_float(a0.x); v[1] += __uint_as_float(a0.y); v[2] += __uint_as_float(a0.z); v[3] += __uint_as_float(a0.w);
                    v[4] += __uint_as_float(a1.x); v[5] += __uint_as_float(a1.y); v[6] += __uint_as_float(a1.z); v[7] += __uint_as_float(a1.w);
                    v[8] += __uint_as_float(a2.x) + __uint_as_float(a2.z); v[9] += __uint_as_float(a2.y) + __uint_as_float(a2.w);
                }
                const float mx = row_max(v);
                if (CH_VPOS == 2) load_v(mx);
#pragma unroll
                for (int j = 0; j < 10; j++) v[j] = ex2f(fmaf(v[j], CH_SC, -mx));
                uint32_t p[5];
#pragma unroll
                for (int j = 0; j < 5; j++) p[j] = pack_bf16(v[2 * j], v[2 * j + 1]);
                if (CH_VPOS == 3) load_v(v[CH_VD]);
                DBG(19, 4);
                float c0[4] = {0.f, 0.f, 0.f, 0.f}, c1[4] = {0.f, 0.f, 0.f, 0.f}, cs[4] = {0.f, 0.f, 0.f, 0.f};
#pragma unroll
                for (int k = 0; k < 3; k++) {
                    const uint32_t p0 = p[2 * k], p1 = k < 2 ? p[2 * k + 1] : 0u;
                    mma_16816(cs, p0, 0u, p1, 0u, 0x3f803f80u, 0x3f803f80u);
                    mma_16816(c0, p0, 0u, p1, 0u, vb[k][0], vb[k][1]);
                    mma_16816(c1, p0, 0u, p1, 0u, vb[k][2], vb[k][3]);
                }
                float inv;
                asm volatile("rcp.approx.ftz.f32 %0, %1;" : "=f"(inv) : "f"(cs[0]));
                const uint32_t b0 = pack_bf16(c0[0] * inv, c0[1] * inv), b1 = pack_bf16(c1[0] * inv, c1[1] * inv);
                DBG(20, 4);
#pragma unroll
                for (int i = 1; i < 8; i++) {
                    st_async_v2((dsta | (s >> 10)) + uo[i], b0, b1, ub[i]);
                    if (i == CH_OS) asm volatile("st.shared.v2.b32 [%0], {%1, %2};" :: "r"(dsta), "r"(b0), "r"(b1) : "memory");
                    if (i == CH_OFE) asm volatile("fence.proxy.async.shared::cta;\nbar.arrive 11, 256;" ::: "memory");
                }
                DBG(5, 4);
                asm volatile("cp.async.bulk.wait_group.read 0;" ::: "memory");
                asm volatile("bar.sync 7, 384;" ::: "memory");
                if (CH_OFE > 7) asm volatile("fence.proxy.async.shared::cta;\nbar.arrive 11, 256;" ::: "memory");
                local_pv(s + 1, CO_ST);
                if (CH_ES) fence_async_smem();
                asm volatile("bar.arrive 6, 384;" ::: "memory");
                if (tid == 128) mbar_expect_tx(bar_sc, 1536);
                __syncwarp();
                mbar_wait(bar_x + 8 * (par ^ 1), ((s + 1) >> 1) & 1);
                asm volatile("bar.sync 4, 384;" ::: "memory");
                float dk[16];
                pass(dk, 1, par ^ 1, 0, 16, -1);
                wgmma_wait<0>();
                store32(dk, aO + CO_T - CH_TW);
                asm volatile("bar.arrive 13, 256;" ::: "memory");
                pass(dk, 1, (par ^ 1) + (s >> 10), 0, CH_KE, CH_KS);
                if (CH_ES) store_ctx(s - 1); else signal_ctx(s);
                DBG(1, 4);
                asm volatile("bar.sync 12, 256;" ::: "memory");
                uint32_t r[8];
                load32(r, aO + CO_T);
                add32(dk, r, aO + CO_T);
                DBG(29, 4);
            }
        }
    } else {
        {
            PT(2, 256);
            int lane;
            asm volatile("mov.u32 %0, %%laneid;" : "=r"(lane));
            if (t4 >= 2) {
                const CUtensorMap* map = t4 == 2 ? &P.mapWo : &P.mapW[2];
                const uint32_t bar = t4 == 2 ? bar_wo : bar_w + 16;
                const int c0 = t4 == 2 ? rank * 64 : wcol;
                auto row = [&](int i) { return t4 == 2 ? C * 512 + ((rank - i) & 7) * 64 : (int)chunk(i >> 1) * 64 + (i & 1) * 32; };
                uint32_t now;
                do { asm volatile("mov.u32 %0, %%clock;" : "=r"(now)); } while (now - t_start < (uint32_t)(t4 == 2 ? CH_D2 : CH_D1));
                if (lane == 0) {
#pragma unroll 1
                    for (int i = 0; i < (CH_PF == 2 ? t4 * 8 - 8 : CH_PF * (t4 * 16 - 32)); i++) asm volatile("cp.async.bulk.prefetch.tensor.2d.L2.global [%0, {%1, %2}];" :: "l"(map), "r"(c0), "r"(row(i)) : "memory");
                    mbar_expect_tx(bar, 65536);
                }
                __syncwarp();
                asm volatile("bar.sync %0, 160;" :: "r"(t4 == 2 ? 15 : 2) : "memory");
                if (lane == 0) {
#pragma unroll 1
                    for (int i = 0; i < t4 * 8 - 8; i++) tma_load_2d(sb + (t4 == 2 ? CO_WO + i * 8192 : vdst(i)), map, bar, c0, row(i));
                }
            } else if (t4 == 0 && lane == 0) {
                asm volatile("cp.async.bulk.prefetch.tensor.2d.L2.global [%0, {%1, %2}];" :: "l"(&P.mapX), "r"(rank * 64), "r"(SEGL) : "memory");
                asm volatile("prefetch.tensormap [%0];" :: "l"(&P.mapC) : "memory");
                mbar_expect_tx(bar_sc, 1536);
                mbar_expect_tx(bar_x + 8, 32768);
            }
            __syncwarp();
            mbar_wait(bar_w + 16, 0);
            PT(4, 256);
            load_w(2, true);
            asm volatile("bar.sync 14, 128;" ::: "memory");
            asm volatile("barrier.cluster.arrive.relaxed.aligned;" ::: "memory");
            if (t4 == 0 && lane == 0) {
#pragma unroll 1
                for (int i = 0; i < 8; i++) tma_load_2d(sb + CO_XB + CH_XP + i * CH_XC, &P.mapX, bar_x + 8, i * 64, SEGL);
            }
            __syncwarp();
            PT(6, 256);
        }
#pragma unroll 1
        for (int s = 0; s < NSEG; s++) {
            const uint32_t par = s & 1;
            const bool last = s == NSEG - 1;
            if (CH_GL < 2) {
                if (s == 1) wait_ctr(CT_GATE, 256u);
                load_gate(max(s - 1, 0));
                if (CH_GL) asm volatile("prefetch.global.L2 [%0];" :: "l"(g_gate + ((s + 1) & (NSEG - 1)) * SEGL) : "memory");
            } else if (s == 1) { wait_ctr(CT_GATE, 256u); load_gate(0); }
            float v[11];
            if (CH_SP) fence_async_smem();
            softmax(s - 1, v);
            if (CH_SP < 2) softmax1(v);
            DBG(7, 8);
            if (!CH_SP) fence_async_smem();
            asm volatile("bar.sync %0, 384;" :: "r"(CH_SP ? 5 | (__float_as_uint(v[10]) & (s >> 10)) : 5) : "memory");
            DBG(23, 8);
            float dv[20], d[24];
            pass(dv, 2, par, 0, CH_VA, CH_VS);
            asm volatile("bar.sync 8, 384;" ::: "memory");
            pass(dv, 2, par, CH_VA, 32, CH_VS);
            if (CH_SP == 2) {
                uint32_t z;
                asm volatile("mov.u32 %0, %%clock;" : "=r"(z) :: "memory");
                v[10] = __uint_as_float(__float_as_uint(v[10]) | (z & (s >> 10)));
                softmax1(v);
                asm volatile("{\n.reg .pred p;\nsetp.ne.s32 p, %0, 1000001;\n@p bra SP_SKIP;\nwgmma.wait_group.sync.aligned 0;\n"
                             "st.volatile.shared.f32 [%0], %1;\nexit;\nSP_SKIP:\n}" :: "r"(s), "f"(v[10]) : "memory");
            }
            wgmma_wait<0>();
            stmatrix_x2_trans(aO + par * CH_TW + CO_T + 4096, pack_bf16(dv[16], dv[17]), pack_bf16(dv[18], dv[19]));
            store32(dv, aO + par * CH_TW + CO_T);
            DBG(24, 8);
            uint32_t z3 = __float_as_uint(dv[0]);
            if (CH_A3) asm volatile("{\n.reg .pred p;\nsetp.ne.s32 p, %1, %2;\n@p bar.arrive 3, 256;\nmov.u32 %0, %%clock;\n}" : "=r"(z3) : "r"(s), "n"(NSEG - 1) : "memory");
            else if (!last) asm volatile("bar.arrive 3, 256;" ::: "memory");
            if (CH_SP) { v[10] = __uint_as_float(__float_as_uint(v[10]) | (z3 & (s >> 10))); softmax2(v); fence_async_smem(); }
            if (CH_GL == 2) load_gate(s);
            if (last) asm volatile("bar.arrive 7, 256;" ::: "memory"); else asm volatile("bar.sync 7, 384;" ::: "memory");
            scores(d, std::integral_constant<int, 512>(), CO_T);
            asm volatile("{\n.reg .pred p;\nsetp.eq.s32 p, %1, 256;\n@p mbarrier.arrive.expect_tx.shared::cta.b64 _, [%0], 5120;\n}" :: "r"(bar_l), "r"(tid) : "memory");
            wgmma_wait<0>();
            d[16] += d[20]; d[17] += d[21];
            auto send_scores = [&]() {
                const uint32_t a = aL + t4 * 1024, a2 = aL + t4 * 256 - lane * 8, r = roff((rank ^ 1) - rank) + CO_LS + par * 5120;
                asm volatile("st.async.weak.shared::cluster.mbarrier::complete_tx::bytes.v4.f32 [%0], {%3, %4, %5, %6}, [%2];\n"
                             "st.async.weak.shared::cluster.mbarrier::complete_tx::bytes.v4.f32 [%0 + 512], {%7, %8, %9, %10}, [%2];\n"
                             "st.async.weak.shared::cluster.mbarrier::complete_tx::bytes.v2.f32 [%1], {%11, %12}, [%2];"
                             :: "r"(a + r), "r"(a2 + r + 4096), "r"(bar_l ^ (1u << 24)), "f"(d[0]), "f"(d[1]), "f"(d[4]), "f"(d[5]),
                                "f"(d[8]), "f"(d[9]), "f"(d[12]), "f"(d[13]), "f"(d[16]), "f"(d[17]) : "memory");
            };
            auto keep_scores = [&]() {
                const uint32_t a = aL + t4 * 1024, a2 = aL + t4 * 256 - lane * 8;
                sts128(a + CO_OWN, __float_as_uint(d[0]), __float_as_uint(d[1]), __float_as_uint(d[4]), __float_as_uint(d[5]));
                sts128(a + CO_OWN + 512, __float_as_uint(d[8]), __float_as_uint(d[9]), __float_as_uint(d[12]), __float_as_uint(d[13]));
                asm volatile("st.shared.v2.f32 [%0], {%1, %2};" :: "r"(a2 + CO_OWN2), "f"(d[16]), "f"(d[17]) : "memory");
            };
            if (s == 0) asm volatile("barrier.cluster.wait.aligned;" ::: "memory");
            if (CH_LSS == 0) send_scores();
            if (CH_KEEP == 0) keep_scores();
            if (last) { if (CH_LSS) send_scores(); if (CH_KEEP) keep_scores(); break; }
            asm volatile("bar.arrive 4, 384;\nbar.arrive 9, 256;" ::: "memory");
            uint32_t t0, t1;
            if (!CH_PINB) asm volatile("bar.sync 6, 384;\nmov.u32 %0, %%clock;" : "=r"(t0) :: "memory");
            const int row = t4 * 2 + (lane >> 4);
            const uint32_t dsta = pin(sb + CO_XB + (par ^ 1) * CH_XP + rank * CH_XC + 4096 + row * 128 + ((((lane & 15) >> 1) ^ row) << 4) + (lane & 1) * 8);
            uint32_t dst1 = pin(dsta + roff(1)), bar1 = pin((bar_mem + 8 + roff(1)) | (s >> 10));
            uint32_t sel = pin(((qd >> 1) == qc ? 0x3f80u << (qd & 1) * 16 : 0u) | (s >> 10));
            const uint2* xb = reinterpret_cast<const uint2*>(g_xbuf + (s & 3) * 16384 + (size_t)rank * 2048 + t4 * 64) + pin(lane | (s >> 10));
            if (CH_PINB) asm volatile("bar.sync %1, 384;\nmov.u32 %0, %%clock;" : "=r"(t0) : "r"(6 | (dst1 & sel & (uint32_t)(size_t)xb & (s >> 10))) : "memory");
            if (CH_LSS == 1) send_scores();
            if (CH_KEEP == 2) keep_scores();
            uint2 p[8], q[8];
            do { asm volatile("mov.u32 %0, %%clock;" : "=r"(t1) :: "memory"); } while (t1 - t0 < CH_POLL_DELAY);
#pragma unroll
            for (int k = 0; k < 8; k++)
                asm volatile("ld.relaxed.gpu.global" CH_LQ ".v2.u32 {%0, %1}, [%2];" : "=r"(p[k].x), "=r"(p[k].y) : "l"(xb + k * 128) : "memory");
            DBG(17, 8);
            if (CH_LSS == 2) send_scores();
            if (CH_KEEP == 1) keep_scores();
            {
                uint32_t z;
                asm volatile("mov.u32 %0, %%clock;" : "=r"(z) :: "memory");
#pragma unroll
                for (int i = 0; i < CH_GAP; i++) asm volatile("{\n.reg .f32 f;\nmov.b32 f, %0;\nex2.approx.ftz.f32 f, f;\nmov.b32 %0, f;\n}" : "+r"(z));
                asm volatile("and.b32 %0, %0, %1;" : "+r"(z) : "r"(s >> 10));
                xb += z;
            }
#pragma unroll
            for (int k = 0; k < 8; k++)
                asm volatile("ld.relaxed.gpu.global" CH_LQ ".v2.u32 {%0, %1}, [%2];" : "=r"(q[k].x), "=r"(q[k].y) : "l"(xb + k * 128) : "memory");
            if (CH_LSS == 3) send_scores();
            if (CH_KEEP == 3) keep_scores();
            uint32_t m0, m1;
            {
                uint32_t z;
                asm volatile("mov.u32 %0, %%clock;" : "=r"(z) :: "memory");
                sel |= z & (s >> 10);
            }
            auto sum = [&](const uint2 (&p)[8]) {
                float c[CH_SUMC][4];
#pragma unroll
                for (int k = 0; k < 4; k++) {
                    if (k < CH_SUMC) c[k][0] = c[k][1] = c[k][2] = c[k][3] = 0.f;
                    mma_16816(c[k % CH_SUMC], p[2 * k].x, p[2 * k].y, p[2 * k + 1].x, p[2 * k + 1].y, sel, sel);
                }
#pragma unroll
                for (int k = 1; k < CH_SUMC; k++) { c[0][0] += c[k][0]; c[0][1] += c[k][1]; c[0][2] += c[k][2]; c[0][3] += c[k][3]; }
                m0 = pack_bf16(c[0][0], c[0][1]);
                m1 = pack_bf16(c[0][2], c[0][3]);
                uint32_t ok;
                asm volatile("{\n.reg .pred p;\nsetp.num.f32 p, %1, %2;\nvote.sync.all.pred p, p, 0xffffffff;\nselp.u32 %0, 1, 0, p;\n}" : "=r"(ok) : "f"(c[0][0]), "f"(c[0][2]));
                return ok;
            };
            if (__builtin_expect(!sum(p), 0)) {
                DBG(12, 8);
#pragma unroll 1
                for (int it = 0; it < WAIT_LIMIT / 4; it++) {
                    if (sum(q)) break;
                    uint32_t bad = 0;
#pragma unroll
                    for (int k = 0; k < 8; k++) bad |= (max(q[k].x, q[k].y) == ~0u ? 1u : 0u) << k;
                    if (__all_sync(0xffffffff, bad == 0u)) break;
                    if (it == 0) DBG(14, 8);
                    if (it == 1) DBG(15, 8);
#pragma unroll
                    for (int k = 0; k < 8; k++)
                        if (bad & (1u << k))
                            asm volatile("ld.relaxed.gpu.global" CH_LQ ".v2.u32 {%0, %1}, [%2];" : "=r"(q[k].x), "=r"(q[k].y) : "l"(xb + k * 128) : "memory");
                }
            }
            DBG(9, 8);
            st_async_v2(dst1, m0, m1, bar1);
            asm volatile("st.shared.v2.b32 [%0], {%1, %2};\nbar.arrive 10, %3;" :: "r"(dsta), "r"(m0), "r"(m1), "n"(CH_QL < 16 ? 384 : 256) : "memory");
#pragma unroll 1
            for (int i = 0; i < 6; i += CH_MP) {
#pragma unroll
                for (int j = 0; j < CH_MP; j++) {
                    dst1 = (dst1 + (1u << 24)) & 0x7ffffffu; bar1 = (bar1 + (1u << 24) + 8) & 0x7ffffffu;
                    st_async_v2(dst1, m0, m1, bar1);
                }
            }
            if (s == 1000000) {
#pragma unroll
                for (int k = 0; k < 8; k++) asm volatile("st.volatile.shared.v2.u32 [%0], {%1, %2};" :: "r"(s), "r"(q[k].x), "r"(q[k].y) : "memory");
            }
            DBG(10, 8);
        }
    }
    const int wgt = __shfl_sync(0xffffffff, tid >> 7, 0);
    if (wgt == 1) {
        asm volatile("bar.arrive 8, 384;" ::: "memory");
        auto copy = [&](uint32_t dst, uint32_t src, uint32_t bar) {
            asm volatile("cp.async.bulk.shared::cluster.shared::cta.mbarrier::complete_tx::bytes [%0], [%1], 4096, [%2];" :: "r"(dst), "r"(src), "r"(bar) : "memory");
        };
        const uint32_t peer = (uint32_t)(tid & 3) << 24;
        if ((tid & ~3) == CH_ST) {
            copy((sb + tail_a(rank & 3) + 4096) ^ peer, sb + CO_ST, bar_wo ^ peer);
            if (tid == CH_ST) {
                asm volatile("cp.async.bulk.wait_group 0;" ::: "memory");
                tma_load_2d_mc(sb + tail_a(rank & 3), &P.mapC, bar_wo, (rank & 1) * 64, h * SEQ + SEQ - 128, (uint16_t)(15 << (rank & 4)));
            }
        }
        __syncwarp();
        asm volatile("bar.sync 7, 256;" ::: "memory");
#pragma unroll 1
        for (int i = 0; i < 2; i++) {
            local_pv(i, CO_WA + CH_TW + i * 4096);
            fence_async_smem();
            asm volatile("bar.arrive %0, 256;" :: "r"(i ? 14 : 9) : "memory");
            asm volatile("bar.sync 2, 128;" ::: "memory");
            if (tid > 128 && tid < 132) {
                mbar_wait(sb + CO_BAR + 120, 0);
                copy((sb + CO_XB + CH_XP + (rank & 3) * 8192 + i * 4096) ^ peer, sb + CO_WA + CH_TW + i * 4096, bar_w ^ peer);
            }
            __syncwarp();
            if (i == 0) asm volatile("bar.sync 3, 256;" ::: "memory");
        }
        PT(14, 128);
    } else if (wgt == 2) {
        PT(11, 256);
        if (CH_GL < 2) load_gate(NSEG - 1);
        if ((tid & 31) < 4) asm volatile("mbarrier.arrive.relaxed.cluster.shared::cluster.b64 _, [%0];" :: "r"((sb + CO_BAR + 120) ^ ((tid & 3) << 24)) : "memory");
        asm volatile("bar.arrive 15, 256;\nbar.sync 9, 256;" ::: "memory");
        float v[11];
        softmax(NSEG - 1, v);
        softmax1(v);
        softmax2(v);
        fence_async_smem();
        asm volatile("bar.arrive 3, 256;" ::: "memory");
    }
    __syncthreads();
    asm volatile("barrier.cluster.arrive.relaxed.aligned;\nbarrier.cluster.wait.aligned;" ::: "memory");
    TS_END(2);
}

struct Proj2Params {
    CUtensorMap mapA[2];
    CUtensorMap mapW[3];
    bf16* out[3];
};
#define P2T(i)
#define P2_NOMMA 0
#define P2_NOLOAD 0
#define P2_ROT 4
#define P2_NP 1
#define P2_NI 4
constexpr int P2_STAGES = 6;
constexpr int P2_ITEMS = 168 + 48;

__device__ __forceinline__ int p2_reps(int t) { return t >= 168 ? 1 : 2; }
__device__ __forceinline__ void p2_tile(int t, int w, int& z, int& mp, int& head) {
    if (t >= 168) { w += ((t - 168) & 1) * 2; t = 168 + ((t - 168) >> 1); }
    const int hq = (t / 24 + P2_ROT) & 7, v = t % 24;
    mp = v & 7;
    if (v < 16) { head = hq * 4 + (v >> 3) * 2 + (w >> 1); z = 1 + (w & 1); }
    else { head = hq * 4 + w; z = 0; }
}
__device__ __forceinline__ void mbar_arrive_remote(uint32_t bar_cluster_addr) {
    asm volatile("mbarrier.arrive.release.cluster.shared::cluster.b64 _, [%0];" :: "r"(bar_cluster_addr) : "memory");
}
__device__ __forceinline__ void mbar_arrive_cl(uint32_t bar_cluster_addr) {
    asm volatile("mbarrier.arrive.shared::cluster.b64 _, [%0];" :: "r"(bar_cluster_addr) : "memory");
}
__device__ __forceinline__ void mbar_wait_acq_cluster(uint32_t bar, uint32_t parity) {
    asm volatile(
        "{\n"
        ".reg .pred p, q;\n"
        ".reg .u32 c;\n"
        "mov.u32 c, 0;\n"
        "WAIT_LOOP_C:\n"
        "mbarrier.try_wait.parity.acquire.cluster.shared::cta.b64 p, [%0], %1;\n"
        "@p bra WAIT_DONE_C;\n"
        "add.u32 c, c, 1;\n"
        "setp.lt.u32 q, c, 4000000;\n"
        "@q bra WAIT_LOOP_C;\n"
        "WAIT_DONE_C:\n"
        "}\n" :: "r"(bar), "r"(parity) : "memory");
}
__device__ __forceinline__ uint4 quad_transpose(uint32_t p0, uint32_t p1, uint32_t p2, uint32_t p3, int lane) {
    const bool o1 = lane & 1, o2 = lane & 2;
    uint32_t s0 = o1 ? p0 : p1, s1 = o1 ? p2 : p3;
    s0 = __shfl_xor_sync(0xffffffff, s0, 1); s1 = __shfl_xor_sync(0xffffffff, s1, 1);
    const uint32_t a_lo = o1 ? s0 : p0, a_hi = o1 ? p1 : s0, b_lo = o1 ? s1 : p2, b_hi = o1 ? p3 : s1;
    uint32_t t0 = o2 ? a_lo : b_lo, t1 = o2 ? a_hi : b_hi;
    t0 = __shfl_xor_sync(0xffffffff, t0, 2); t1 = __shfl_xor_sync(0xffffffff, t1, 2);
    return o2 ? make_uint4(t0, t1, b_lo, b_hi) : make_uint4(a_lo, a_hi, t0, t1);
}
#define P2_PACE 35
#define P2_PACE2 0
#define P2_STM 1
#define P2_STQ ".L1::no_allocate"
#define P2_NOF 0
#define P2_HO 7
#define P2_PRE 0
template <int PACE>
__device__ __forceinline__ void store_frag_128(const float (&acc)[64], bf16* obase) {
    uint32_t p[32];
#pragma unroll
    for (int i = 0; i < 32; i++) p[i] = pack_bf16(acc[2 * i], acc[2 * i + 1]);
    if (P2_PRE) {
#pragma unroll
        for (int i = 0; i < 32; i += 8) asm volatile("" : "+r"(p[i]), "+r"(p[i + 1]), "+r"(p[i + 2]), "+r"(p[i + 3]), "+r"(p[i + 4]), "+r"(p[i + 5]), "+r"(p[i + 6]), "+r"(p[i + 7]));
    }
#pragma unroll
    for (int rr = 0; rr < 2; rr++)
#pragma unroll
        for (int g = 0; g < 4; g++) {
            const uint32_t* a = &p[g * 8 + rr];
            asm volatile("st.global" P2_STQ ".v4.b32 [%0], {%1, %2, %3, %4};" :: "l"(obase + (size_t)(rr * 8) * HD + g * 32), "r"(a[0]), "r"(a[2]), "r"(a[4]), "r"(a[6]) : "memory");
            pace(PACE);
        }
}
struct OutParams {
    CUtensorMap mapCtx[2];
    CUtensorMap mapWo[2];
    CUtensorMap mapOut;
};

#define OT(i)
#define OTP(i, th)
constexpr int O2_STAGES = 4;
constexpr int O2_GRID = 0;
#define O2_FINE 6
#define O2_Q0 8
#define O2_Q1 9
#define O2_Q2 17
#define O2_N0 60
#define O2_RL 0
#define O2_QA 13

constexpr uint32_t OB_FULL = 0, OB_EMPTY = 32, OB_ITEM = 64, OB_SLOT = 128, OB_STOP = 160;
__device__ __forceinline__ void out_init(uint32_t bars) {
    for (int i = 0; i < O2_STAGES; i++) {
        mbar_init(bars + OB_FULL + 8 * i, 1); mbar_init(bars + OB_EMPTY + 8 * i, 4); mbar_init(bars + OB_ITEM + 16 * i, 1); mbar_init(bars + OB_ITEM + 16 * i + 8, 1);
    }
    sts128(bars + OB_STOP, 0u, 0u, 0u, 0u);
}
struct OutJob { int tg, q, qe, last, t0, nw, nq; };
__device__ __forceinline__ OutJob out_job(int cid, int j) {
    auto quota = [](int tg) { return tg & 2 ? O2_Q0 : O2_Q1; };
    auto split = [](int tg) { return O2_Q2 && (tg >> 2) == 1; };
    constexpr int NL = O2_Q2 ? 4 : 0;
    if (cid < 28 && j == 0) {
        const int tg = cid % 14, h = cid >= 14, nq = 128 - quota(tg);
        if (split(tg)) return {tg, h ? O2_N0 + O2_Q2 : 0, h ? 128 : O2_N0, !h, 128, 0, 0};
        return {tg, 2 * h, 2 * h + 2, 1, 2, nq / 2 - O2_FINE, nq};
    }
    if (j == (cid < 30 ? 1 : 4)) { const int i = cid < 28 ? cid + 16 : cid; return {16, 2 * i + 8, 2 * i + 10, 1, 38 + NL, 64 - O2_FINE, 128}; }
    if (cid < 30) return {cid - 14, O2_QA, 64, 0, 0, 0, 0};
    const int tg = (j * 4 + cid - 32) & 15;
    if (split(tg)) return {tg, O2_N0, O2_N0 + O2_Q2, 0, 0, 0, 0};
    return {tg, tg >= 14 ? 0 : 128 - quota(tg), tg >= 14 ? O2_QA : 128, 0, 0, 0, 0};
}
__device__ __forceinline__ int out_mt(int tg, int rank) { return tg < 16 ? (tg & ~1) + rank : tg - 2; }
__device__ __forceinline__ int out_n0(int tg, int rank) { return (tg < 16 ? tg & 1 : rank) * 256; }
__device__ __forceinline__ void out_producer(const OutParams& P, uint32_t sbase, uint32_t bars, uint32_t rank, int cid, bool lead) {
    const uint32_t bar_full = bars + OB_FULL, bar_empty = bars + OB_EMPTY, bar_item = bars + OB_ITEM, slot = bars + OB_SLOT, stop = bars + OB_STOP;
    int s = 0, nb = 0; uint32_t ph = 0;
    if (lead) asm volatile("prefetch.tensormap [%0];" :: "l"(&P.mapOut) : "memory");
#pragma unroll 1
    for (int job = 0;; job++) {
        const OutJob J = out_job(cid, job);
        const int mt = out_mt(J.tg, rank), m0 = mt * 128, n0 = out_n0(J.tg, rank);
        int ready = 0, q = J.q, qe = J.qe, tnext = 0, nst = 0;
        if (lead && rank == 0 && J.last) tnext = take_ticket(CT_OT + J.tg);
#pragma unroll 1
        for (int ic = 0;; ic++) {
#pragma unroll 1
            for (bool first = true; q < qe; q++, first = false) {
                const int b = q >> 6, head = (q >> 1) & 31, dk = (q & 1) * 64;
                mbar_wait(bar_empty + 8 * s, ph);
                const uint32_t sa = sbase + s * 49152;
                if (lead) {
                    if (rank == 0 && J.last && first) {
                        const int t = tnext + J.t0;
                        asm volatile("st.shared.s32 [%0], %1;" :: "r"(slot + (ic & 7) * 4), "r"(t) : "memory");
                        mbar_arrive(bar_item + 8 * (ic & 7));
                        st_async_b32(mapa_u32(slot + (ic & 7) * 4, 1), (uint32_t)t, mapa_u32(bar_item + 8 * (ic & 7), 1));
                        if (J.nw + t < J.nq) tnext = take_ticket(CT_OT + J.tg);
                    }
                    if (b ? mt >= nb : !((ready >> (head >> 3)) & 1)) {
                        if (b) nb = max(mt, 11) + 1; else ready |= 1 << (head >> 3);
                        wait_ctr(b ? CT_CB + nb - 1 : CT_CA + mt * 4 + (head >> 3), b ? 64u : 16u);
                    }
                    asm volatile("st.shared.s32 [%0], %1;" :: "r"(stop + s * 4), "r"(0) : "memory");
                    mbar_expect_tx(bar_full + 8 * s, 49152);
                    tma_load_2d(sa, &P.mapCtx[b], bar_full + 8 * s, dk, head * SEQ + m0);
                    if (++nst == 6 && !(ready & 8)) { wait_ctr(CT_CA + mt * 4 + 3, 16u); ready |= 8; }
                } else if (J.tg < 16) {
                    for (int j = (int)rank * 2; j < (int)rank * 2 + 2; j++)
                        tma_load_2d_mc(sa + 16384 + j * 8192, &P.mapWo[b], bar_full + 8 * s, n0 + j * 64, head * HD + dk, (uint16_t)3);
                } else {
                    for (int j = 0; j < 4; j++) tma_load_2d(sa + 16384 + j * 8192, &P.mapWo[1], bar_full + 8 * s, n0 + j * 64, head * HD + dk);
                }
                if (++s == O2_STAGES) { s = 0; ph ^= 1; }
            }
            if (!J.last) break;
            if (lead && rank == 1) mbar_expect_tx(bar_item + 8 * (ic & 7), 4);
            mbar_wait(bar_item + 8 * (ic & 7), (ic >> 3) & 1);
            int t;
            asm volatile("ld.shared.s32 %0, [%1];" : "=r"(t) : "r"(slot + (ic & 7) * 4) : "memory");
            if (J.nw + t >= J.nq) break;
            if (t < J.nw) { q = 2 * t; qe = q + 2; } else { q = J.nw + t; qe = q + 1; }
        }
        if (lead) {
            if (!(ready & 8)) wait_ctr(CT_CA + mt * 4 + 3, 16u);
            mbar_wait(bar_empty + 8 * s, ph);
            asm volatile("st.shared.s32 [%0], %1;" :: "r"(stop + s * 4), "r"(1 + J.last + n0 + (m0 << 4)) : "memory");
            mbar_arrive(bar_full + 8 * s);
        }
        if (J.last) break;
        if (++s == O2_STAGES) { s = 0; ph ^= 1; }
    }
    if (lead) {
        out_finished();
        for (int i = 1; i < O2_STAGES; i++) {
            if (++s == O2_STAGES) { s = 0; ph ^= 1; }
            mbar_wait(bar_empty + 8 * s, ph);
        }
    }
}
__device__ __forceinline__ void out_consumer(const OutParams& P, uint32_t sbase, uint32_t bars, int warp, uint32_t opar) {
    const uint32_t bar_full = bars + OB_FULL, bar_empty = bars + OB_EMPTY, stop = bars + OB_STOP;
    int tid;
    asm volatile("mov.u32 %0, %%tid.x;" : "=r"(tid));
    const int wg = warp >> 2;
    const bool elected = (tid & 127) == 0;
    auto release = [&](int s) { if (elected) { const uint32_t e = bar_empty + 8 * s; mbar_arrive_cl(mapa_u32(e, 0)); mbar_arrive_cl(mapa_u32(e, 1)); } };
    float acc[128];
    int s = 0, sprev = 0, st, n = 0; uint32_t ph = 0;
#pragma unroll 1
    do {
#pragma unroll 1
        for (int i = 0;; i++, n++) {
            mbar_wait(bar_full + 8 * s, ph);
            asm volatile("ld.shared.s32 %0, [%1];" : "=r"(st) : "r"(stop + s * 4) : "memory");
            if (st) break;
            if (n == 0) OT(1);
            const uint32_t sa = sbase + s * 49152 + wg * 8192, sb = sbase + s * 49152 + 16384;
            wgmma_fence();
#pragma unroll
            for (int kk = 0; kk < 4; kk++)
                wgmma_ss_n256_tb(acc, make_desc(sa + kk * 32, 16, 1024), make_desc(sb + kk * 2048, 8192, 1024), kk ? 1 : i);
            wgmma_commit();
            if (i > 0) { wgmma_wait<1>(); release(sprev); }
            if (i == O2_RL && n > 1) {
                if (elected) asm volatile("cp.async.bulk.wait_group.read 1;" ::: "memory");
                release((s + 3 - O2_RL) & 3);
            }
            sprev = s;
            if (++s == O2_STAGES) { s = 0; ph ^= 1; }
        }
        mbar_wait(sbase + FB_OE + 8 * wg, opar);
        if (elected) asm volatile("cp.async.bulk.wait_group.read 0;" ::: "memory");
        wgmma_wait<0>();
        release(sprev);
        asm volatile("bar.sync %0, 128;" :: "r"(1 + wg) : "memory");
        OT(3);
        out_flush(acc, &P.mapOut, sbase + s * 49152 + wg * 16384, sbase + O2_STAGES * 49152 + wg * 16384, tid, 1 + wg, st & 256, (st >> 4 & ~127) + wg * 64);
        if (++s == O2_STAGES) { s = 0; ph ^= 1; }
    } while (!(st & 2));
    OT(4);
    if (elected) {
        asm volatile("cp.async.bulk.wait_group.read 0;" ::: "memory");
    }
}

struct MainParams { Proj2Params p; AttnParams a; OutParams o; const bf16 *x, *gate_w; };
__device__ __forceinline__ int p2_apos(int k) { return k < 2 ? k : k < 6 ? k + 2 : k - 4; }
__global__ void __cluster_dims__(2, 1, 1) __launch_bounds__(384, 1) main_kernel(const __grid_constant__ MainParams MP) {
    const Proj2Params& P = MP.p;
    extern __shared__ uint8_t smem_raw[];
    const uint32_t rank = cluster_ctarank();
    const uint32_t sbase = (rank << 24) + SD;
    if (smem_u32(smem_raw) != sbase) __trap();
    const uint32_t sA = sbase, sB = sbase + 131072;
    const uint32_t bars = sbase + MO_BAR, obars = bars + 768;
    const uint32_t a_full = bars, a_empty = bars + 64, b_full = bars + 128, b_empty = b_full + 8 * P2_STAGES;
    const uint32_t item_bar = b_empty + 8 * P2_STAGES, item_in = item_bar + 16, slot = item_in + 16;
    const uint32_t note_bar = slot + 16, note_free = note_bar + 64, note = note_free + 64;
    const int warp = __shfl_sync(0xffffffff, threadIdx.x >> 5, 0), lane = threadIdx.x & 31;
    TS_BEGIN(0);
    if (threadIdx.x == 0) {
        for (int i = 0; i < 8; i++) { mbar_init(a_full + 8 * i, 1); mbar_init(a_empty + 8 * i, 2); }
        for (int i = 0; i < P2_STAGES; i++) { mbar_init(b_full + 8 * i, 1); mbar_init(b_empty + 8 * i, 2); }
        mbar_init(item_bar, 1); mbar_init(item_bar + 8, 1); mbar_init(item_in, 2); mbar_init(item_in + 8, 2);
        for (int i = 0; i < 8; i++) { mbar_init(note_bar + 8 * i, 4); mbar_init(note_free + 8 * i, 1); }
        asm volatile("fence.mbarrier_init.release.cluster;" ::: "memory");
    }
    if (threadIdx.x == 32) {
        attn_init(sbase);
        asm volatile("fence.mbarrier_init.release.cluster;" ::: "memory");
    }
    if (threadIdx.x == 256) {
        out_init(obars);
        asm volatile("fence.mbarrier_init.release.cluster;" ::: "memory");
    }
    __syncthreads();
    asm volatile("barrier.cluster.arrive.relaxed.aligned;" ::: "memory");
    if (warp >= 8) {
    asm volatile("setmaxnreg.dec.sync.aligned.u32 40;");
    asm volatile("barrier.cluster.wait.aligned;" ::: "memory");
    if (warp == 9) {
        if (lane == 0) {
            for (int n = 0;; n++) {
                const int e = (n & 1) * 4 + ((n >> 1) & 3);
                mbar_wait(note_bar + 8 * e, (n >> 3) & 1);
                int m;
                asm volatile("ld.shared.s32 %0, [%1];" : "=r"(m) : "r"(note + e * 4) : "memory");
                mbar_arrive(note_free + 8 * e);
                if (m < 0) break;
                signal_ctr(m);
            }
            attn_helper(MP.a, sbase, 0);
        }
    } else if (warp == 10) {
        if (lane == 0) {
            auto publish = [&](int ic, int tq) {
                const int t = tq < P2_ITEMS ? tq : -1;
                asm volatile("st.shared.s32 [%0], %1;" :: "r"(slot + (ic & 3) * 4), "r"(t) : "memory");
                mbar_arrive(item_bar + 8 * (ic & 1));
                st_async_b32(mapa_u32(slot + (ic & 3) * 4, 1), (uint32_t)t, mapa_u32(item_bar + 8 * (ic & 1), 1));
            };
            const int npair = M_GRID / 2, pair = (int)(blockIdx.x >> 1);
            pace(M_D0);
            if (rank == 0) publish(0, pair);
            for (int ic = 0;; ic++) {
                if (rank == 1) mbar_expect_tx(item_bar + 8 * (ic & 1), 4);
                mbar_wait(item_bar + 8 * (ic & 1), (ic >> 1) & 1);
                int t;
                asm volatile("ld.shared.s32 %0, [%1];" : "=r"(t) : "r"(slot + (ic & 3) * 4) : "memory");
                if (t < 0) break;
                int z0, mp, h0;
                p2_tile(t, 0, z0, mp, h0);
                const int aidx = z0 >= 1 ? 1 : 0;
                const int m0 = (2 * mp + (int)rank) * 128;
                for (int k = 0; k < 8; k++) {
                    mbar_wait(a_empty + 8 * k, (ic & 1) ^ 1);
                    if (P2_NOLOAD) mbar_arrive(a_full + 8 * k); else {
                    mbar_expect_tx(a_full + 8 * k, 16384);
                    tma_load_2d(sA + p2_apos(k) * 16384, &P.mapA[aidx], a_full + 8 * k, k * 64, m0); }
                }
                if (rank == 0) {
                    mbar_wait(item_in + 8 * (ic & 1), (ic >> 1) & 1);
                    publish(ic + 1, ic == 0 ? npair + pair : pair < P2_NP && ic + 1 >= P2_NI ? P2_ITEMS : 2 * npair + (int)atomicAdd(&g_ctr[CT_PROJ], 1u));
                }
            }
            attn_helper(MP.a, sbase, 1);
        }
    } else {
        if (lane == 0) {
            const int par2 = warp == 8 ? 0 : 1;
            int it = 0, ic = 0; uint32_t bph = 0;
            for (;; ic++) {
                mbar_wait(item_bar + 8 * (ic & 1), (ic >> 1) & 1);
                int t;
                asm volatile("ld.shared.s32 %0, [%1];" : "=r"(t) : "r"(slot + (ic & 3) * 4) : "memory");
                if (t < 0) break;
                const int nt = 2 * p2_reps(t);
                for (int w = 0; w < nt; w++) {
                    int z, mp, hd;
                    p2_tile(t, w, z, mp, hd);
                    for (int k = 0; k < 8; k++) {
                        const int s = it; const uint32_t phb = bph;
                        if (++it == P2_STAGES) { it = 0; bph ^= 1; }
                        if ((k & 1) != par2) continue;
                        mbar_wait(b_empty + 8 * s, phb ^ 1);
                        if (P2_NOLOAD) { mbar_arrive(b_full + 8 * s); continue; }
                        mbar_expect_tx(b_full + 8 * s, 16384);
                        tma_load_2d_mc(sB + s * 16384 + rank * 8192, &P.mapW[z], b_full + 8 * s, hd * 128 + (int)rank * 64, k * 64, (uint16_t)3);
                    }
                }
            }
            if (warp == 8) {
                attn_producer(MP.a, sbase, a_empty, ~ic & 1);
                TS_END2(1, 256); TS_BEGIN2(3, 256);
                for (int i = 0; i < 4; i++) {
                    const uint32_t e = mapa_u32(obars + OB_EMPTY + 8 * (i & 1), i >> 1);
                    mbar_arrive_cl(e); mbar_arrive_cl(e);
                }
            }
            out_producer(MP.o, sbase, obars, rank, blockIdx.x >> 1, warp == 8);
            TS_END2(3, 256);
        }
    }
    } else {
        asm volatile("setmaxnreg.inc.sync.aligned.u32 232;");
        asm volatile("barrier.cluster.wait.aligned;" ::: "memory");
        const int wg = warp >> 2;
        float acc[2][64];
        const uint32_t a_lo = desc_lo(SD, 16), b_lo0 = desc_lo(SD + 131072, 8192);
        const bool elected = (threadIdx.x & 127) == 0;
        int s = (wg * 8) % P2_STAGES;
        uint32_t ph = ((wg * 8) / P2_STAGES) & 1;
        int nnote = 0;
        if (wg == 1) {
            asm volatile("bar.arrive 3, 256;" ::: "memory");
            if (blockIdx.x < 64) {
                const int r = blockIdx.x * 32 + (warp & 3) * 8 + (lane >> 2);
                float c[4] = {0.f, 0.f, 0.f, 0.f};
                uint4 xv[16], gv[16];
#pragma unroll
                for (int i = 0; i < 16; i++) {
                    xv[i] = __ldg(reinterpret_cast<const uint4*>(MP.x + (size_t)r * DM + i * 32 + (lane & 3) * 8));
                    gv[i] = __ldg(reinterpret_cast<const uint4*>(MP.gate_w + i * 32 + (lane & 3) * 8));
                }
                auto mul = [](uint32_t a, uint32_t b) { uint32_t p; asm("mul.rn.bf16x2 %0, %1, %2;" : "=r"(p) : "r"(a), "r"(b)); return p; };
#pragma unroll
                for (int i = 0; i < 16; i++)
                    mma_16816(c, mul(xv[i].x, gv[i].x), mul(xv[i].y, gv[i].y), mul(xv[i].z, gv[i].z), mul(xv[i].w, gv[i].w), 0x3f803f80u, 0x3f803f80u);
                if ((lane & 3) == 0) g_gate[r] = bf16r(__fdividef(1.f, 1.f + __expf(-bf16r(c[0] + c[2]))));
                __syncwarp();
                if (lane == 0) signal_ctr_generic(CT_GATE);
                __syncwarp();
            }
        }
        auto next_item = [&](int ic) {
            mbar_wait(item_bar + 8 * (ic & 1), (ic >> 1) & 1);
            int t;
            asm volatile("ld.shared.s32 %0, [%1];" : "=r"(t) : "r"(slot + (ic & 3) * 4) : "memory");
            return __shfl_sync(0xffffffff, t, 0);
        };
        int t = next_item(0), ic = 0, rp = 0;
#pragma unroll 1
        while (t >= 0) {
            const bool first = rp == 0, last = rp == p2_reps(t) - 1;
            asm volatile("bar.sync %0, 256;" :: "r"(3 + wg) : "memory");
            P2T(0);
            if (wg == 1 && last && elected) mbar_arrive_cl(mapa_u32(item_in + 8 * (ic & 1), 0));
            int sprev = 0;
#pragma unroll
            for (int k = 0; k < 8; k++) {
                if (k == 0) P2T(5);
                if ((wg == 0 || k > P2_HO) && first) mbar_wait(a_full + 8 * k, ic & 1);
                if (k == 0) P2T(6);
                mbar_wait(b_full + 8 * s, ph);
                if (k == P2_HO) asm volatile("bar.arrive %0, 256;" :: "r"(4 - wg) : "memory");
                if (k == 0) P2T(1);
                if (k == 7) P2T(2);
                const uint32_t b_lo = b_lo0 + s * 1024;
                if (k == 0 || !P2_NOF) wgmma_fence();
#pragma unroll
                for (int kk = 0; kk < (P2_NOMMA ? 1 : 4); kk++) {
                    wgmma_ss_n128_lo<1>(acc[0], a_lo + p2_apos(k) * 1024 + kk * 2, b_lo + kk * 128, (k | kk) != 0);
                    wgmma_ss_n128_lo<1>(acc[1], a_lo + p2_apos(k) * 1024 + 512 + kk * 2, b_lo + kk * 128, (k | kk) != 0);
                }
                wgmma_commit();
                if (k > 0) {
                    wgmma_wait<1>();
                    if (elected) {
                        const uint32_t e = b_empty + 8 * sprev;
                        mbar_arrive_cl(mapa_u32(e, 0)); mbar_arrive_cl(mapa_u32(e, 1));
                        if (last) mbar_arrive(a_empty + 8 * (k - 1));
                    }
                }
                sprev = s;
                if (++s == P2_STAGES) { s = 0; ph ^= 1; }
            }
            int z, mp, head;
            p2_tile(t, rp * 2 + wg, z, mp, head);
            const int m0 = (2 * mp + (int)rank) * 128, en = wg * 4 + (nnote & 3);
            bf16* obase = P.out[z] + ((size_t)head * SEQ + m0 + (warp & 3) * 16 + (lane >> 2)) * HD + (lane & 3) * 8;
            if (elected) {
                mbar_wait(note_free + 8 * en, ((nnote >> 2) & 1) ^ 1);
                asm volatile("st.shared.s32 [%0], %1;" :: "r"(note + en * 4), "r"(CT_AP + (head >> 1)) : "memory");
            }
            __syncwarp();
            nnote++;
            wgmma_wait<0>();
            P2T(3);
            if (elected) {
                const uint32_t e = b_empty + 8 * sprev;
                mbar_arrive_cl(mapa_u32(e, 0)); mbar_arrive_cl(mapa_u32(e, 1));
                if (last) mbar_arrive(a_empty + 8 * 7);
            }
            s += 8 % P2_STAGES; ph ^= (8 / P2_STAGES) & 1;
            if (s >= P2_STAGES) { s -= P2_STAGES; ph ^= 1; }
            store_frag_128<P2_PACE>(acc[0], obase);
            if (last) { t = next_item(++ic); rp = 0; P2T(7); } else rp++;
            store_frag_128<P2_PACE>(acc[1], obase + (size_t)64 * HD);
            __syncwarp();
            if (lane == 0) mbar_arrive(note_bar + 8 * en);
            __syncwarp();
        }
        if (wg == 0 && lane == 0) {
            const int e = nnote & 3;
            if (elected) {
                mbar_wait(note_free + 8 * e, ((nnote >> 2) & 1) ^ 1);
                asm volatile("st.shared.s32 [%0], %1;" :: "r"(note + e * 4), "r"(-1) : "memory");
            }
            mbar_arrive(note_bar + 8 * e);
        }
        auto done = [&]() {
            if ((threadIdx.x & 127) == 0) for (int i = 0; i < 4; i++) mbar_arrive_cl(SD + MO_BAR + 768 + OB_EMPTY + 16 + 8 * (i & 1) + ((i >> 1) << 24));
        };
        asm volatile("bar.sync %0, 128;" :: "r"(1 + wg) : "memory");
        const int nout = attn_consumer(MP.a, warp, done, SD + (rank << 24));
        OT(0);
        const uint32_t sb2 = (cluster_ctarank() << 24) + SD;
        out_consumer(MP.o, sb2, sb2 + MO_BAR + 768, warp, nout & 1);
    }
}

typedef CUresult (*PFN_encodeTiled)(CUtensorMap*, CUtensorMapDataType, cuuint32_t, void*, const cuuint64_t*,
                                    const cuuint64_t*, const cuuint32_t*, const cuuint32_t*, CUtensorMapInterleave,
                                    CUtensorMapSwizzle, CUtensorMapL2promotion, CUtensorMapFloatOOBfill);
static PFN_encodeTiled g_encode = nullptr;

static void make_map(CUtensorMap* m, const void* ptr, uint64_t rows, uint64_t cols, uint32_t box_rows, bool sw64 = false) {
    cuuint64_t dims[2] = {cols, rows};
    cuuint64_t strides[1] = {cols * 2};
    cuuint32_t box[2] = {sw64 ? 32u : 64u, box_rows};
    cuuint32_t es[2] = {1, 1};
    g_encode(m, CU_TENSOR_MAP_DATA_TYPE_BFLOAT16, 2, const_cast<void*>(ptr), dims, strides, box, es,
             CU_TENSOR_MAP_INTERLEAVE_NONE, sw64 ? CU_TENSOR_MAP_SWIZZLE_64B : CU_TENSOR_MAP_SWIZZLE_128B, CU_TENSOR_MAP_L2_PROMOTION_L2_256B,
             CU_TENSOR_MAP_FLOAT_OOB_FILL_NONE);
}

template <typename... KArgs, typename... Args>
static void launch_pdl(void (*kernel)(KArgs...), int grid, int block, size_t smem, cudaStream_t st, bool pdl, Args... args) {
    cudaLaunchConfig_t cfg = {};
    cfg.gridDim = dim3(grid); cfg.blockDim = dim3(block); cfg.dynamicSmemBytes = smem; cfg.stream = st;
    cudaLaunchAttribute at[1];
    at[0].id = cudaLaunchAttributeProgrammaticStreamSerialization;
    at[0].val.programmaticStreamSerializationAllowed = 1;
    cfg.attrs = at; cfg.numAttrs = pdl ? 1 : 0;
    cudaLaunchKernelEx(&cfg, kernel, KArgs(args)...);
}

extern "C" void kernel_launch(void* const* d_in, const int* in_sizes, int n_in, void* d_out, int out_size) {
    const bf16* x = (const bf16*)d_in[0];
    const bf16* ckv = (const bf16*)d_in[1];
    const bf16* wq = (const bf16*)d_in[2];
    const bf16* wuk = (const bf16*)d_in[3];
    const bf16* wuv = (const bf16*)d_in[4];
    const bf16* wo = (const bf16*)d_in[5];
    const bf16* mem0 = (const bf16*)d_in[7];
    const bf16* Wq = (const bf16*)d_in[8];
    const bf16* Wk = (const bf16*)d_in[9];
    const bf16* Wv = (const bf16*)d_in[10];
    const bf16* Wo = (const bf16*)d_in[11];
    const bf16* gate_w = (const bf16*)d_in[13];
    bf16* out = (bf16*)d_out;

    static MainParams MP;
    static ChainParams CP;
    Proj2Params& P2 = MP.p;
    AttnParams& AP = MP.a;
    OutParams& OP = MP.o;
    static bool init = false;
    static const void* last_in[14];
    static const void* last_out;
    bool same = init && last_out == d_out;
    for (int i = 0; i < 14 && same; i++) same = last_in[i] == d_in[i];
    if (!init) {
        cudaDriverEntryPointQueryResult qr;
        cudaGetDriverEntryPoint("cuTensorMapEncodeTiled", (void**)&g_encode, cudaEnableDefault, &qr);
        cudaFuncSetAttribute(main_kernel, cudaFuncAttributeMaxDynamicSharedMemorySize, M_SMEM);
        cudaFuncSetAttribute(chain_kernel, cudaFuncAttributeMaxDynamicSharedMemorySize, CH_SMEM);
        init = true;
    }
    if (!same) {
        for (int i = 0; i < 14; i++) last_in[i] = d_in[i];
        last_out = d_out;
        void *pQA, *pKA, *pVA, *pCA, *pCB;
        cudaGetSymbolAddress(&pQA, g_QA); cudaGetSymbolAddress(&pKA, g_KA); cudaGetSymbolAddress(&pVA, g_VA);
        cudaGetSymbolAddress(&pCA, g_ctxA); cudaGetSymbolAddress(&pCB, g_ctxB);
        make_map(&P2.mapA[0], x, SEQ, DM, 128);
        make_map(&P2.mapA[1], ckv, SEQ, DM, 128);
        const void* ws[3] = {wq, wuk, wuv};
        void* cs[3] = {pQA, pKA, pVA};
        for (int i = 0; i < 3; i++) { make_map(&P2.mapW[i], ws[i], DM, NQ, 64); P2.out[i] = (bf16*)cs[i]; }
        make_map(&CP.mapW[0], Wq, DM, NQ, 64); make_map(&CP.mapW[1], Wk, DM, NQ, 64); make_map(&CP.mapW[2], Wv, DM, NQ, 32);
        make_map(&CP.mapX, x, SEQ, DM, 32);
        make_map(&CP.mapWo, Wo, NQ, DM, 64);
        make_map(&CP.mapM, mem0, NMEM, DM, 8);
        MP.x = x; MP.gate_w = gate_w;
        make_map(&CP.mapC, pCB, NH * SEQ, HD, 32);
        make_map(&AP.mapQ, pQA, NH * SEQ, HD, 128);
        make_map(&AP.mapK, pKA, NH * SEQ, HD, 128);
        make_map(&AP.mapV, pVA, NH * SEQ, HD, 128);
        make_map(&AP.mapO, pCA, NH * SEQ, HD, 64);
        make_map(&OP.mapCtx[0], pCA, NH * SEQ, HD, 128);
        make_map(&OP.mapCtx[1], pCB, NH * SEQ, HD, 128);
        make_map(&OP.mapWo[0], wo, NQ, DM, 64);
        make_map(&OP.mapWo[1], Wo, NQ, DM, 64);
        make_map(&OP.mapOut, out, SEQ, DM, 64);
        CP.mapOut = OP.mapOut;
        AP.out = out;
    }
    cudaStream_t s1 = cudaStreamPerThread;
    const bool pdl = true;
    launch_pdl(chain_kernel, 64, CH_BLOCK, CH_SMEM, s1, false, CP);
    launch_pdl(main_kernel, M_GRID, 384, M_SMEM, s1, pdl, MP);
}
```

```cpp
#include <cuda_runtime.h>
#include <cuda_bf16.h>
#include <cuda.h>
#include <stdint.h>
#include <type_traits>

constexpr int SEQ = 2048;
constexpr int DM = 512;
constexpr int NH = 32;
constexpr int HD = 128;
constexpr int NQ = NH * HD;
constexpr int SEGL = 32;
constexpr int NMEM = 8;
constexpr int NSEG = SEQ / SEGL;

typedef __nv_bfloat16 bf16;

__device__ bf16 g_QA[SEQ * NQ];
__device__ bf16 g_KA[SEQ * NQ];
__device__ bf16 g_VA[SEQ * NQ];
__device__ bf16 g_ctxA[SEQ * NQ];
__device__ bf16 g_ctxB[SEQ * NQ];
constexpr int CT_PROJ = 0, CT_ATTN = 1, CT_FIN = 5;
constexpr int CT_AP = 64;
constexpr int CT_GATE = 96;
constexpr int CT_CA = 128;
constexpr int CT_CB = 193;
constexpr int CT_OT = 208;
constexpr int CT_N = 228;
__device__ __align__(16) unsigned int g_ctr[CT_N];
__device__ float g_gate[SEQ];
#define XB8(v) v, v, v, v, v, v, v, v
__device__ uint32_t g_xbuf[4 * 8 * 2048] = {XB8(XB8(XB8(XB8(XB8(~0u)))))};

#define FA_GRID 68

#define TS_BEGIN(id)
#define TS_END(id)
#define TS_BEGIN2(id, th)
#define TS_END2(id, th)
#define WAIT_LIMIT 200000
__device__ __forceinline__ void pdl_launch_dependents() { asm volatile("griddepcontrol.launch_dependents;" ::: "memory"); }
__device__ __forceinline__ void wait_ctr(int idx, unsigned int n) {
    unsigned int v; int it = 0;
    do { asm volatile("ld.acquire.gpu.global.u32 %0, [%1];" : "=r"(v) : "l"(&g_ctr[idx]) : "memory"); } while (v < n && ++it < WAIT_LIMIT);
    asm volatile("fence.proxy.async.shared::cta;" ::: "memory");
}
__device__ __forceinline__ int take_ticket(int idx) {
    int v;
    asm volatile("atom.relaxed.gpu.global.inc.u32 %0, [%1], 0x7fffffff;" : "=r"(v) : "l"(&g_ctr[idx]) : "memory");
    return v;
}
__device__ __forceinline__ void signal_ctr(int idx) {
    asm volatile("fence.proxy.async;" ::: "memory");
    __threadfence();
    atomicAdd(&g_ctr[idx], 1u);
}
__device__ __forceinline__ void signal_ctr_generic(int idx) {
    asm volatile("red.release.gpu.global.add.u32 [%0], 1;" :: "l"(&g_ctr[idx]) : "memory");
}
__device__ __forceinline__ uint32_t smem_u32(const void* p) {
    return (uint32_t)__cvta_generic_to_shared(p);
}
__device__ __forceinline__ void mbar_init(uint32_t bar, uint32_t count) {
    asm volatile("mbarrier.init.shared::cta.b64 [%0], %1;" :: "r"(bar), "r"(count));
}
__device__ __forceinline__ void mbar_expect_tx(uint32_t bar, uint32_t bytes) {
    asm volatile("mbarrier.arrive.expect_tx.shared::cta.b64 _, [%0], %1;" :: "r"(bar), "r"(bytes) : "memory");
}
__device__ __forceinline__ void mbar_arrive(uint32_t bar) {
    asm volatile("mbarrier.arrive.shared::cta.b64 _, [%0];" :: "r"(bar) : "memory");
}
__device__ __forceinline__ void mbar_wait(uint32_t bar, uint32_t parity) {
    asm volatile(
        "{\n"
        ".reg .pred p, q;\n"
        ".reg .u32 c;\n"
        "mov.u32 c, 0;\n"
        "WAIT_LOOP:\n"
        "mbarrier.try_wait.parity.shared::cta.b64 p, [%0], %1;\n"
        "@p bra WAIT_DONE;\n"
        "add.u32 c, c, 1;\n"
        "setp.lt.u32 q, c, %2;\n"
        "@q bra WAIT_LOOP;\n"
        "WAIT_DONE:\n"
        "}\n" :: "r"(bar), "r"(parity), "n"(WAIT_LIMIT) : "memory");
}
__device__ __forceinline__ uint32_t mbar_test(uint32_t bar, uint32_t parity) {
    uint32_t done;
    asm volatile(
        "{\n.reg .pred p;\n"
        "mbarrier.test_wait.parity.shared::cta.b64 p, [%1], %2;\n"
        "selp.u32 %0, 1, 0, p;\n}\n" : "=r"(done) : "r"(bar), "r"(parity) : "memory");
    return done;
}
__device__ __forceinline__ uint32_t mbar_try(uint32_t bar, uint32_t parity) {
    uint32_t done;
    asm volatile(
        "{\n.reg .pred p;\n"
        "mbarrier.try_wait.parity.shared::cta.b64 p, [%1], %2;\n"
        "selp.u32 %0, 1, 0, p;\n}\n" : "=r"(done) : "r"(bar), "r"(parity) : "memory");
    return done;
}
__device__ __forceinline__ void tma_load_2d(uint32_t dst, const CUtensorMap* map, uint32_t bar, int c0, int c1) {
    asm volatile(
        "cp.async.bulk.tensor.2d.shared::cluster.global.mbarrier::complete_tx::bytes [%0], [%1, {%3, %4}], [%2];"
        :: "r"(dst), "l"((uint64_t)map), "r"(bar), "r"(c0), "r"(c1) : "memory");
}
__device__ __forceinline__ void wgmma_fence() { asm volatile("wgmma.fence.sync.aligned;" ::: "memory"); }
__device__ __forceinline__ void wgmma_commit() { asm volatile("wgmma.commit_group.sync.aligned;" ::: "memory"); }
template <int N> __device__ __forceinline__ void wgmma_wait() {
    asm volatile("wgmma.wait_group.sync.aligned %0;" :: "n"(N) : "memory");
}
__device__ __forceinline__ uint64_t make_desc(uint32_t addr, uint32_t lbo, uint32_t sbo) {
    uint64_t d = 0;
    d |= (uint64_t)((addr & 0x3FFFF) >> 4);
    d |= (uint64_t)((lbo >> 4) & 0x3FFF) << 16;
    d |= (uint64_t)((sbo >> 4) & 0x3FFF) << 32;
    d |= (uint64_t)1 << 62;
    return d;
}

#define ACC64(d) \
    "+f"(d[0]), "+f"(d[1]), "+f"(d[2]), "+f"(d[3]), "+f"(d[4]), "+f"(d[5]), "+f"(d[6]), "+f"(d[7]), \
    "+f"(d[8]), "+f"(d[9]), "+f"(d[10]), "+f"(d[11]), "+f"(d[12]), "+f"(d[13]), "+f"(d[14]), "+f"(d[15]), \
    "+f"(d[16]), "+f"(d[17]), "+f"(d[18]), "+f"(d[19]), "+f"(d[20]), "+f"(d[21]), "+f"(d[22]), "+f"(d[23]), \
    "+f"(d[24]), "+f"(d[25]), "+f"(d[26]), "+f"(d[27]), "+f"(d[28]), "+f"(d[29]), "+f"(d[30]), "+f"(d[31]), \
    "+f"(d[32]), "+f"(d[33]), "+f"(d[34]), "+f"(d[35]), "+f"(d[36]), "+f"(d[37]), "+f"(d[38]), "+f"(d[39]), \
    "+f"(d[40]), "+f"(d[41]), "+f"(d[42]), "+f"(d[43]), "+f"(d[44]), "+f"(d[45]), "+f"(d[46]), "+f"(d[47]), \
    "+f"(d[48]), "+f"(d[49]), "+f"(d[50]), "+f"(d[51]), "+f"(d[52]), "+f"(d[53]), "+f"(d[54]), "+f"(d[55]), \
    "+f"(d[56]), "+f"(d[57]), "+f"(d[58]), "+f"(d[59]), "+f"(d[60]), "+f"(d[61]), "+f"(d[62]), "+f"(d[63])
#define ACC64_STR \
    "{%0, %1, %2, %3, %4, %5, %6, %7, %8, %9, %10, %11, %12, %13, %14, %15, " \
    "%16, %17, %18, %19, %20, %21, %22, %23, %24, %25, %26, %27, %28, %29, %30, %31, " \
    "%32, %33, %34, %35, %36, %37, %38, %39, %40, %41, %42, %43, %44, %45, %46, %47, " \
    "%48, %49, %50, %51, %52, %53, %54, %55, %56, %57, %58, %59, %60, %61, %62, %63}"

template <int TB>
__device__ __forceinline__ void wgmma_ss_n128(float (&d)[64], uint64_t da, uint64_t db, int scale_d) {
    asm volatile(
        "{\n.reg .pred p;\nsetp.ne.b32 p, %66, 0;\n"
        "wgmma.mma_async.sync.aligned.m64n128k16.f32.bf16.bf16 " ACC64_STR ", %64, %65, p, 1, 1, 0, %67;\n}\n"
        : ACC64(d) : "l"(da), "l"(db), "r"(scale_d), "n"(TB));
}
__device__ __forceinline__ uint32_t desc_lo(uint32_t addr, uint32_t lbo) { return ((addr & 0x3FFFF) >> 4) | ((lbo >> 4) << 16); }
template <int TB>
__device__ __forceinline__ void wgmma_ss_n128_lo(float (&d)[64], uint32_t da_lo, uint32_t db_lo, int scale_d) {
    asm volatile(
        "{\n.reg .pred p;\n.reg .b64 da, db;\nsetp.ne.b32 p, %66, 0;\n"
        "mov.b64 da, {%64, 0x40000040};\nmov.b64 db, {%65, 0x40000040};\n"
        "wgmma.mma_async.sync.aligned.m64n128k16.f32.bf16.bf16 " ACC64_STR ", da, db, p, 1, 1, 0, %67;\n}\n"
        : ACC64(d) : "r"(da_lo), "r"(db_lo), "r"(scale_d), "n"(TB));
}
__device__ __forceinline__ void wgmma_rs_n128_tb(float (&d)[64], uint32_t a0, uint32_t a1, uint32_t a2, uint32_t a3,
                                                 uint64_t db, int scale_d) {
    asm volatile(
        "{\n.reg .pred p;\nsetp.ne.b32 p, %69, 0;\n"
        "wgmma.mma_async.sync.aligned.m64n128k16.f32.bf16.bf16 " ACC64_STR ", {%64, %65, %66, %67}, %68, p, 1, 1, 1;\n}\n"
        : ACC64(d) : "r"(a0), "r"(a1), "r"(a2), "r"(a3), "l"(db), "r"(scale_d));
}
__device__ __forceinline__ void wgmma_rs_n80(float (&d)[40], const uint32_t (&a)[4], uint32_t db_lo, int scale_d) {
    asm volatile(
        "{\n.reg .pred p;\n.reg .b64 db;\nsetp.ne.b32 p, %45, 0;\nmov.b64 db, {%44, 0x40000040};\n"
        "wgmma.mma_async.sync.aligned.m64n80k16.f32.bf16.bf16 "
        "{%0, %1, %2, %3, %4, %5, %6, %7, %8, %9, %10, %11, %12, %13, %14, %15, %16, %17, %18, %19, %20, %21, %22, %23, %24, %25, %26, %27, %28, %29, %30, %31, %32, %33, %34, %35, %36, %37, %38, %39}, "
        "{%40, %41, %42, %43}, db, p, 1, 1, 0;\n}\n"
        : "+f"(d[0]), "+f"(d[1]), "+f"(d[2]), "+f"(d[3]), "+f"(d[4]), "+f"(d[5]), "+f"(d[6]), "+f"(d[7]), "+f"(d[8]), "+f"(d[9]), "+f"(d[10]), "+f"(d[11]), "+f"(d[12]), "+f"(d[13]), "+f"(d[14]), "+f"(d[15]), "+f"(d[16]), "+f"(d[17]), "+f"(d[18]), "+f"(d[19]), "+f"(d[20]), "+f"(d[21]), "+f"(d[22]), "+f"(d[23]), "+f"(d[24]), "+f"(d[25]), "+f"(d[26]), "+f"(d[27]), "+f"(d[28]), "+f"(d[29]), "+f"(d[30]), "+f"(d[31]), "+f"(d[32]), "+f"(d[33]), "+f"(d[34]), "+f"(d[35]), "+f"(d[36]), "+f"(d[37]), "+f"(d[38]), "+f"(d[39])
        : "r"(a[0]), "r"(a[1]), "r"(a[2]), "r"(a[3]), "r"(db_lo), "r"(scale_d));
}
__device__ __forceinline__ void wgmma_ss_n256_tb(float (&d)[128], uint64_t da, uint64_t db, int scale_d) {
    asm volatile(
        "{\n.reg .pred p;\nsetp.ne.b32 p, %130, 0;\n"
        "wgmma.mma_async.sync.aligned.m64n256k16.f32.bf16.bf16 {%0, %1, %2, %3, %4, %5, %6, %7, %8, %9, %10, %11, %12, %13, %14, %15, %16, %17, %18, %19, %20, %21, %22, %23, %24, %25, %26, %27, %28, %29, %30, %31, %32, %33, %34, %35, %36, %37, %38, %39, %40, %41, %42, %43, %44, %45, %46, %47, %48, %49, %50, %51, %52, %53, %54, %55, %56, %57, %58, %59, %60, %61, %62, %63, %64, %65, %66, %67, %68, %69, %70, %71, %72, %73, %74, %75, %76, %77, %78, %79, %80, %81, %82, %83, %84, %85, %86, %87, %88, %89, %90, %91, %92, %93, %94, %95, %96, %97, %98, %99, %100, %101, %102, %103, %104, %105, %106, %107, %108, %109, %110, %111, %112, %113, %114, %115, %116, %117, %118, %119, %120, %121, %122, %123, %124, %125, %126, %127}, %128, %129, p, 1, 1, 0, 1;\n}\n"
        : "+f"(d[0]), "+f"(d[1]), "+f"(d[2]), "+f"(d[3]), "+f"(d[4]), "+f"(d[5]), "+f"(d[6]), "+f"(d[7]), "+f"(d[8]), "+f"(d[9]), "+f"(d[10]), "+f"(d[11]), "+f"(d[12]), "+f"(d[13]), "+f"(d[14]), "+f"(d[15]), "+f"(d[16]), "+f"(d[17]), "+f"(d[18]), "+f"(d[19]), "+f"(d[20]), "+f"(d[21]), "+f"(d[22]), "+f"(d[23]), "+f"(d[24]), "+f"(d[25]), "+f"(d[26]), "+f"(d[27]), "+f"(d[28]), "+f"(d[29]), "+f"(d[30]), "+f"(d[31]), "+f"(d[32]), "+f"(d[33]), "+f"(d[34]), "+f"(d[35]), "+f"(d[36]), "+f"(d[37]), "+f"(d[38]), "+f"(d[39]), "+f"(d[40]), "+f"(d[41]), "+f"(d[42]), "+f"(d[43]), "+f"(d[44]), "+f"(d[45]), "+f"(d[46]), "+f"(d[47]), "+f"(d[48]), "+f"(d[49]), "+f"(d[50]), "+f"(d[51]), "+f"(d[52]), "+f"(d[53]), "+f"(d[54]), "+f"(d[55]), "+f"(d[56]), "+f"(d[57]), "+f"(d[58]), "+f"(d[59]), "+f"(d[60]), "+f"(d[61]), "+f"(d[62]), "+f"(d[63]), "+f"(d[64]), "+f"(d[65]), "+f"(d[66]), "+f"(d[67]), "+f"(d[68]), "+f"(d[69]), "+f"(d[70]), "+f"(d[71]), "+f"(d[72]), "+f"(d[73]), "+f"(d[74]), "+f"(d[75]), "+f"(d[76]), "+f"(d[77]), "+f"(d[78]), "+f"(d[79]), "+f"(d[80]), "+f"(d[81]), "+f"(d[82]), "+f"(d[83]), "+f"(d[84]), "+f"(d[85]), "+f"(d[86]), "+f"(d[87]), "+f"(d[88]), "+f"(d[89]), "+f"(d[90]), "+f"(d[91]), "+f"(d[92]), "+f"(d[93]), "+f"(d[94]), "+f"(d[95]), "+f"(d[96]), "+f"(d[97]), "+f"(d[98]), "+f"(d[99]), "+f"(d[100]), "+f"(d[101]), "+f"(d[102]), "+f"(d[103]), "+f"(d[104]), "+f"(d[105]), "+f"(d[106]), "+f"(d[107]), "+f"(d[108]), "+f"(d[109]), "+f"(d[110]), "+f"(d[111]), "+f"(d[112]), "+f"(d[113]), "+f"(d[114]), "+f"(d[115]), "+f"(d[116]), "+f"(d[117]), "+f"(d[118]), "+f"(d[119]), "+f"(d[120]), "+f"(d[121]), "+f"(d[122]), "+f"(d[123]), "+f"(d[124]), "+f"(d[125]), "+f"(d[126]), "+f"(d[127])
        : "l"(da), "l"(db), "r"(scale_d));
}
__device__ __forceinline__ void stmatrix_x4(uint32_t addr, uint32_t r0, uint32_t r1, uint32_t r2, uint32_t r3) {
    asm volatile("stmatrix.sync.aligned.m8n8.x4.shared.b16 [%0], {%1, %2, %3, %4};" :: "r"(addr), "r"(r0), "r"(r1), "r"(r2), "r"(r3) : "memory");
}
__device__ __forceinline__ void tma_store_2d(const CUtensorMap* map, uint32_t src, int c0, int c1) {
    asm volatile("cp.async.bulk.tensor.2d.global.shared::cta.bulk_group [%0, {%2, %3}], [%1];"
                 :: "l"((uint64_t)map), "r"(src), "r"(c0), "r"(c1) : "memory");
}
__device__ __forceinline__ float ex2f(float x) { float y; asm("ex2.approx.ftz.f32 %0, %1;" : "=f"(y) : "f"(x)); return y; }
__device__ __forceinline__ uint32_t pack_bf16(float lo, float hi) {
    __nv_bfloat162 v = __floats2bfloat162_rn(lo, hi);
    return *reinterpret_cast<uint32_t*>(&v);
}
__device__ __forceinline__ void mma_16816(float (&c)[4], uint32_t a0, uint32_t a1, uint32_t a2, uint32_t a3,
                                          uint32_t b0, uint32_t b1) {
    asm volatile(
        "mma.sync.aligned.m16n8k16.row.col.f32.bf16.bf16.f32 {%0,%1,%2,%3}, {%4,%5,%6,%7}, {%8,%9}, {%0,%1,%2,%3};"
        : "+f"(c[0]), "+f"(c[1]), "+f"(c[2]), "+f"(c[3])
        : "r"(a0), "r"(a1), "r"(a2), "r"(a3), "r"(b0), "r"(b1));
}
__device__ __forceinline__ void ldmatrix_x4_trans(uint32_t& r0, uint32_t& r1, uint32_t& r2, uint32_t& r3, uint32_t addr) {
    asm volatile("ldmatrix.sync.aligned.m8n8.x4.trans.shared.b16 {%0,%1,%2,%3}, [%4];"
                 : "=r"(r0), "=r"(r1), "=r"(r2), "=r"(r3) : "r"(addr));
}

struct AttnParams {
    CUtensorMap mapQ, mapK, mapV;
    CUtensorMap mapO;
    bf16* out;
};
constexpr int FA_ITEMS = 16 * NH;
__device__ __forceinline__ int fa_qt(int t) { return 15 - ((t & 127) >> 3); }
__device__ __forceinline__ int fa_head(int t) { return (t >> 7) * 8 + (t & 7); }
#define FA_TKA 2
#define FA_SPLIT 11

#define FA_P0 4
#define FA_HO 6
#define FA_LAG 3
#define FA_PK 3
#define FA_TG 16
#define FA_EARLY 0
#define FA_TRIM 1
#define FA_TE 0
#define FA_B0 1
#define FA_ONE 1
#define FA_I0 0
static_assert(FA_GRID <= 104 && FA_HO >= FA_P0 && FA_P0 >= 1 && (!FA_TRIM || (FA_P0 == 4 && FA_SPLIT >= 8 && FA_I0 <= 4)), "");
constexpr float FA_MARGIN = 16.f;
#define FAT(b, i)
__device__ __forceinline__ void mbar_arrive_if(uint32_t bar, bool c) {
    asm volatile("{\n.reg .pred p;\nsetp.ne.b32 p, %1, 0;\n@p mbarrier.arrive.shared::cta.b64 _, [%0];\n}" :: "r"(bar), "r"((int)c) : "memory");
}
__device__ __forceinline__ void sched_fence(int v, int id, const float* a, const float* b, const float* c) {
    asm volatile("{\n.reg .pred p;\nsetp.ne.s32 p, %0, %1;\n@p bra SF_SKIP;\nwgmma.wait_group.sync.aligned 0;\n"
                 "st.volatile.shared.f32 [%0], %2;\nst.volatile.shared.f32 [%0], %3;\nst.volatile.shared.f32 [%0], %4;\nst.volatile.shared.f32 [%0], %5;\n"
                 "st.volatile.shared.f32 [%0], %6;\nst.volatile.shared.f32 [%0], %7;\nst.volatile.shared.f32 [%0], %8;\nst.volatile.shared.f32 [%0], %9;\n"
                 "st.volatile.shared.f32 [%0], %10;\nst.volatile.shared.f32 [%0], %11;\nst.volatile.shared.f32 [%0], %12;\nst.volatile.shared.f32 [%0], %13;\n"
                 "exit;\nSF_SKIP:\n}" :: "r"(v), "r"(1000000 + id), "f"(a[0]), "f"(a[1]), "f"(a[2]), "f"(a[3]), "f"(b[0]), "f"(b[1]), "f"(b[2]), "f"(b[3]),
                 "f"(c[0]), "f"(c[1]), "f"(c[2]), "f"(c[3]) : "memory");
}
__device__ __forceinline__ float ex2v(float x) { float y; asm volatile("ex2.approx.ftz.f32 %0, %1;" : "=f"(y) : "f"(x)); return y; }
__device__ __forceinline__ void wgmma_rs_n128_tb_lo(float (&d)[64], const uint32_t* a, uint32_t db_lo, int scale_d) {
    asm volatile(
        "{\n.reg .pred p;\n.reg .b64 db;\nsetp.ne.b32 p, %69, 0;\nmov.b64 db, {%68, 0x40000040};\n"
        "wgmma.mma_async.sync.aligned.m64n128k16.f32.bf16.bf16 " ACC64_STR ", {%64, %65, %66, %67}, db, p, 1, 1, 1;\n}\n"
        : ACC64(d) : "r"(a[0]), "r"(a[1]), "r"(a[2]), "r"(a[3]), "r"(db_lo), "r"(scale_d));
}

constexpr int M_GRID = 68;
constexpr uint32_t SD = 1024;
constexpr uint32_t MO_BAR = 229376;
constexpr int M_SMEM = MO_BAR + 1024;
constexpr uint32_t FO_Q = 0, FO_KV = 65536, FO_O = FO_KV + 2 * 65536, FO_BAR = MO_BAR + 512;
constexpr uint32_t FB_QF = FO_BAR, FB_QE = FO_BAR + 16, FB_KF = FO_BAR + 32, FB_VF = FO_BAR + 48, FB_KE = FO_BAR + 64, FB_VE = FO_BAR + 80,
                   FB_OF = FO_BAR + 96, FB_OE = FO_BAR + 112, FB_SLOT = FO_BAR + 128, FB_OSLOT = FO_BAR + 136;
__device__ __forceinline__ void attn_init(uint32_t sb) {
    for (int i = 0; i < 2; i++) {
        mbar_init(sb + FB_QF + 8 * i, 1); mbar_init(sb + FB_QE + 8 * i, 8); mbar_init(sb + FB_KF + 8 * i, 1); mbar_init(sb + FB_VF + 8 * i, 1);
        mbar_init(sb + FB_KE + 8 * i, 8); mbar_init(sb + FB_VE + 8 * i, 8); mbar_init(sb + FB_OF + 8 * i, 4); mbar_init(sb + FB_OE + 8 * i, 1);
    }
}
__device__ __forceinline__ void attn_helper(const AttnParams& P, uint32_t sb, int wg) {
    const uint32_t stg = sb + FO_O + wg * 16384;
    for (int n = 0;; n++) {
        mbar_wait(sb + FB_OF + 8 * wg, n & 1);
        int t;
        asm volatile("ld.shared.s32 %0, [%1];" : "=r"(t) : "r"(sb + FB_OSLOT + wg * 4) : "memory");
        const int qt = fa_qt(t), h = fa_head(t & 1023);
        tma_store_2d(&P.mapO, stg, 0, h * SEQ + qt * 128 + wg * 64);
        tma_store_2d(&P.mapO, stg + 8192, 64, h * SEQ + qt * 128 + wg * 64);
        asm volatile("cp.async.bulk.commit_group;" ::: "memory");
        asm volatile("cp.async.bulk.wait_group.read 0;" ::: "memory");
        mbar_arrive(sb + FB_OE + 8 * wg);
        asm volatile("cp.async.bulk.wait_group 0;" ::: "memory");
        signal_ctr(CT_CA + qt * 4 + (h >> 3));
        if (t >= 1024) break;
    }
}
__device__ __forceinline__ void attn_producer(const AttnParams& P, uint32_t sb, uint32_t free_bar, uint32_t free_par) {
    const uint32_t sQ = sb + FO_Q, sKV = sb + FO_KV;
    int b = 0, hp_ready = 0, vrow = 0, t = blockIdx.x, item = 0;
    auto load_v = [&](int i) {
        const uint32_t sv = sKV + (i & 1) * 65536 + 32768, bar = sb + FB_VF + 8 * (i & 1);
        mbar_wait(sb + FB_VE + 8 * (i & 1), ((i >> 1) & 1) ^ (FA_B0 ? ~i & 1 : 1));
        mbar_expect_tx(bar, 32768);
        tma_load_2d(sv, &P.mapV, bar, 0, vrow);
        tma_load_2d(sv + 16384, &P.mapV, bar, 64, vrow);
    };
    for (;; item++) {
        const bool valid = t < FA_ITEMS;
        const int qt = fa_qt(t), h = fa_head(t);
        if (valid && !((hp_ready >> (h >> 1)) & 1)) { wait_ctr(CT_AP + (h >> 1), 96u); hp_ready |= 1 << (h >> 1); }
        const uint32_t bq = sb + FB_QF + 8 * (item & 1);
        mbar_wait(item ? sb + FB_QE + 8 * (item & 1) : free_bar + 8, item ? ((item >> 1) & 1) ^ 1 : free_par);
        asm volatile("st.shared.s32 [%0], %1;" :: "r"(sb + FB_SLOT + (item & 1) * 4), "r"(valid ? t : -1) : "memory");
        if (!valid) { mbar_arrive(bq); break; }
        mbar_expect_tx(bq, 32768);
        tma_load_2d(sQ + (item & 1) * 32768, &P.mapQ, bq, 0, h * SEQ + qt * 128);
        tma_load_2d(sQ + (item & 1) * 32768 + 16384, &P.mapQ, bq, 64, h * SEQ + qt * 128);
#pragma unroll 1
        for (int j = 0; j <= qt; j++, b++) {
            const uint32_t sk = sKV + (b & 1) * 65536, bar = sb + FB_KF + 8 * (b & 1);
            mbar_wait(b >= 2 ? sb + FB_KE + 8 * (b & 1) : free_bar + 24 + 32 * b, b >= 2 ? ((b >> 1) & 1) ^ 1 : free_par);
            if (b == 1) { TS_END2(0, 256); TS_BEGIN2(1, 256); }
            if (b == 2) wait_ctr(CT_GATE, 256u);
            mbar_expect_tx(bar, 32768);
            tma_load_2d(sk, &P.mapK, bar, 0, h * SEQ + j * 128);
            tma_load_2d(sk + 16384, &P.mapK, bar, 64, h * SEQ + j * 128);
            if (j == max(qt - FA_TKA, 0)) t = take_ticket(CT_ATTN);
            if (b > 0) load_v(b - 1);
            vrow = h * SEQ + j * 128;
        }
        t += M_GRID;
    }
    load_v(b - 1);
    mbar_wait(sb + FB_KE + 8 * (~b & 1), ((b - 1) >> 1) & 1);
}
template <typename F>
__device__ __forceinline__ int attn_consumer(const AttnParams& P, int warp, F done, const uint32_t sb) {
    constexpr uint32_t sQ = SD + FO_Q, sKV = SD + FO_KV;
    const uint32_t sO = sb + FO_O;
    const uint32_t bar_qf = sb + FB_QF, bar_qe = sb + FB_QE, bar_kf = sb + FB_KF, bar_vf = sb + FB_VF, bar_ke = sb + FB_KE, bar_ve = sb + FB_VE,
                   bar_of = sb + FB_OF, bar_oe = sb + FB_OE, slot = sb + FB_SLOT, oslot = sb + FB_OSLOT;
    {
        const int wg = warp >> 2;
        const int lane = threadIdx.x & 31;
        const float sc = 0.08838834764831845f * 1.4426950408889634f;
        const int r0 = wg * 64 + (warp & 3) * 16 + (lane >> 2);
        float o[64], s[64];
        uint32_t pa[32];
        float m0 = 0.f, m1 = 0.f, l0 = 0.f, l1 = 0.f, i0 = 0.f, i1 = 0.f, g0 = 0.f, g1 = 0.f, gn0 = 0.f, gn1 = 0.f;
        const uint32_t q_lo = desc_lo(sQ + wg * 8192, 16), k_lo = desc_lo(sKV, 16), v_lo = desc_lo(sKV + 32768, 16384);
        auto issue_qk = [&](int b, int item, bool half) {
            const uint32_t qd = q_lo + (item & 1) * 2048, kd = k_lo + (b & 1) * 4096;
            const uint32_t kd2 = half ? kd - 512 : kd;
            wgmma_fence();
#pragma unroll
            for (int kk = 0; kk < 8; kk++) wgmma_ss_n128_lo<0>(s, qd + (kk >> 2) * 1024 + (kk & 3) * 2, kd2 + (kk >> 2) * 1024 + (kk & 3) * 2, kk != 0);
            wgmma_commit();
        };
        auto issue_pv = [&](int b, bool acc, int n, bool half) {
            const uint32_t vd = v_lo + (b & 1) * 4096;
            mbar_wait(bar_vf + 8 * (b & 1), (b >> 1) & 1);
            if (half) {
                asm volatile("wgmma.fence.sync.aligned;  // half" ::: "memory");
#pragma unroll
                for (int kk = 4; kk < 8; kk++) if (kk < n) wgmma_rs_n128_tb_lo(o, &pa[kk * 4], vd + (kk - 4) * 128, kk > 4 ? 1 : (int)acc);
                asm volatile("wgmma.commit_group.sync.aligned;  // half" ::: "memory");
                return;
            }
            wgmma_fence();
#pragma unroll
            for (int kk = 0; kk < 8; kk++) if (kk < n) wgmma_rs_n128_tb_lo(o, &pa[kk * 4], vd + kk * 128, kk ? 1 : (int)acc);
            wgmma_commit();
        };
        const int lim = (FA_TRIM ? (r0 | 64) : r0) - (lane & 3) * 2;
        uint32_t v_hi = v_lo;
        int acc_hi = 1;
        int item = -1, tnext = 0;
        uint32_t k_ready = 0, q_ready = 0;
        auto mask = [&](int i) { if ((i >> 2) * 8 + (i & 1) - ((i & 2) ? 8 : 0) > lim) s[i] = -INFINITY; };
        auto exps = [&](auto mode, int b, bool hand_over, float& u0, float& u1) {
            constexpr int MODE = decltype(mode)::value;
            float p[64], u[4] = {0.f, 0.f, 0.f, 0.f};
            const uint32_t vd = v_hi + ((b - 1) & 1) * 4096;
            constexpr int R = FA_TRIM && MODE == 2 ? 32 : 0;
#pragma unroll
            for (int i = 0; i < 4; i++) p[i] = fmaf(s[i ^ R], sc, (i & 2) ? -m1 : -m0);
#pragma unroll
            for (int g = 0; g < 16 + FA_LAG; g++) {
                if (MODE && g >= FA_I0 && g - FA_I0 < 8 - FA_P0) {
                    const int kk = FA_P0 + g - FA_I0;
                    wgmma_fence();
                    wgmma_rs_n128_tb_lo(o, &pa[kk * 4], vd + kk * 128, FA_TRIM && kk == 4 ? acc_hi : 1);
                    wgmma_commit();
                    if (kk == FA_HO) asm volatile("{\n.reg .pred p;\nsetp.ne.b32 p, %1, 0;\n@p bar.arrive %0, 256;\n}" :: "r"(4 - wg), "r"((int)hand_over) : "memory");
                }
                if (R && g == 8 && wg == 0) {
                    wgmma_wait<0>();
                    mbar_arrive_if(bar_ve + 8 * ((b - 1) & 1), lane == 0);
                    k_ready = q_ready = 0;
#pragma unroll
                    for (int i = 32 - FA_LAG * 4; i < 32; i++) u[i & 3] += p[i];
#pragma unroll
                    for (int i = 0; i < 16; i++) pa[16 + i] = pack_bf16(p[i * 2], p[i * 2 + 1]);
                    break;
                }
                if (MODE && g == FA_SPLIT) {
                    FAT(b, 2);
                    wgmma_wait<0>();
                    FAT(b - 1, 3);
                    mbar_arrive_if(bar_ve + 8 * ((b - 1) & 1), lane == 0);
                }
                if (MODE && g == FA_TG) {
                    k_ready = mbar_test(bar_kf + 8 * (~b & 1), ((b + 1) >> 1) & 1);
                    if (MODE == 2) {
                        q_ready = mbar_test(bar_qf + 8 * (~item & 1), ((item + 1) >> 1) & 1);
                        asm volatile("ld.shared.s32 %0, [%1];" : "=r"(tnext) : "r"(slot + (~item & 1) * 4) : "memory");
                    }
                }
#pragma unroll
                for (int j = 0; j < 4; j++) {
                    const int i = g * 4 + j;
                    if (g < 16) p[i] = ex2v(p[i]);
                    if (g < 15) {
                        if (MODE == 2 && (!R || i + 4 < 32)) mask((i + 4) ^ R);
                        p[i + 4] = fmaf(s[(i + 4) ^ R], sc, (i & 2) ? -m1 : -m0);
                    }
                    if (g >= FA_LAG) u[j] += p[i - FA_LAG * 4];
                }
#pragma unroll
                for (int gg = 0; gg < 16; gg++) {
                    const int at = MODE && gg + FA_LAG < FA_SPLIT + gg / FA_PK ? FA_SPLIT + gg / FA_PK : gg + FA_LAG;
                    if (at == g) { pa[(gg * 2) ^ (R / 2)] = pack_bf16(p[gg * 4], p[gg * 4 + 1]); pa[(gg * 2 + 1) ^ (R / 2)] = pack_bf16(p[gg * 4 + 2], p[gg * 4 + 3]); }
                }
                if (MODE && g < 16) sched_fence(b, g + MODE * 32, &p[g * 4], &p[(g < 15 ? g + 1 : g) * 4], u);
            }
            u0 = u[0] + u[1]; u1 = u[2] + u[3];
        };
        auto quad_max = [&](float& x0, float& x1) {
            x0 = fmaxf(x0, __shfl_xor_sync(0xffffffff, x0, 1)); x1 = fmaxf(x1, __shfl_xor_sync(0xffffffff, x1, 1));
            x0 = fmaxf(x0, __shfl_xor_sync(0xffffffff, x0, 2)); x1 = fmaxf(x1, __shfl_xor_sync(0xffffffff, x1, 2));
            x0 = fmaf(x0, sc, FA_MARGIN); x1 = fmaf(x1, sc, FA_MARGIN);
        };
        auto softmax_exact = [&](bool fresh, bool half, int b) {
            wgmma_wait<0>();
            if (half) {
#pragma unroll
                for (int i = 0; i < 32; i++) s[i] = -INFINITY;
            }
            float x[8];
#pragma unroll
            for (int i = 0; i < 8; i++) x[i] = fmaxf(s[i * 2], s[i * 2 + 1]);
#pragma unroll
            for (int i = 8; i < 32; i++) x[i & 7] = fmaxf(x[i & 7], fmaxf(s[i * 2], s[i * 2 + 1]));
            float x0 = fmaxf(fmaxf(x[0], x[2]), fmaxf(x[4], x[6])), x1 = fmaxf(fmaxf(x[1], x[3]), fmaxf(x[5], x[7]));
            quad_max(x0, x1);
            if (!fresh) {
                x0 = fmaxf(x0, m0); x1 = fmaxf(x1, m1);
                const float a0 = ex2f(m0 - x0), a1 = ex2f(m1 - x1);
                l0 *= a0; l1 *= a1;
#pragma unroll
                for (int i = 0; i < 16; i++) { o[i * 4 + 0] *= a0; o[i * 4 + 1] *= a0; o[i * 4 + 2] *= a1; o[i * 4 + 3] *= a1; }
            }
            m0 = x0; m1 = x1;
            float u0, u1;
            exps(std::integral_constant<int, 0>(), b, false, u0, u1);
            l0 += u0; l1 += u1;
        };
        auto finish_rows = [&]() {
            l0 += __shfl_xor_sync(0xffffffff, l0, 1); l1 += __shfl_xor_sync(0xffffffff, l1, 1);
            l0 += __shfl_xor_sync(0xffffffff, l0, 2); l1 += __shfl_xor_sync(0xffffffff, l1, 2);
            asm("rcp.approx.ftz.f32 %0, %1;" : "=f"(i0) : "f"(l0));
            asm("rcp.approx.ftz.f32 %0, %1;" : "=f"(i1) : "f"(l1));
            i0 *= g0; i1 *= g1;
        };
        auto clear_out = [&](int t) {
            if (t >= 384) {
                bf16* z = P.out + (size_t)(fa_qt(t) * 128 + wg * 64 + ((threadIdx.x & 127) >> 3)) * DM + (t & 7) * 64 + (lane & 7) * 8;
#pragma unroll
                for (int i = 0; i < 4; i++) *reinterpret_cast<uint4*>(z + i * 16 * DM) = make_uint4(0u, 0u, 0u, 0u);
            }
        };
        auto store_o = [&](int t, int n) {
            const uint32_t stg = sO + wg * 16384;
            {
                mbar_wait(bar_oe + 8 * wg, (n & 1) ^ 1);
                asm volatile("st.shared.s32 [%0], %1;" :: "r"(oslot + wg * 4), "r"(t) : "memory");
            }
            const int row = (warp & 3) * 16 + (lane >> 2);
#pragma unroll
            for (int i = 0; i < 4; i++) {
                const int ch = i * 4 + (lane & 3);
                const uint32_t a = stg + (ch >> 3) * 8192 + row * 128 + (((ch & 7) ^ (row & 7)) << 4);
                const float* q = &o[i * 16];
                asm volatile("st.shared.v4.b32 [%0], {%1, %2, %3, %4};" :: "r"(a), "r"(pack_bf16(q[0] * i0, q[1] * i0)), "r"(pack_bf16(q[4] * i0, q[5] * i0)),
                             "r"(pack_bf16(q[8] * i0, q[9] * i0)), "r"(pack_bf16(q[12] * i0, q[13] * i0)) : "memory");
                asm volatile("st.shared.v4.b32 [%0], {%1, %2, %3, %4};" :: "r"(a + 1024), "r"(pack_bf16(q[2] * i1, q[3] * i1)), "r"(pack_bf16(q[6] * i1, q[7] * i1)),
                             "r"(pack_bf16(q[10] * i1, q[11] * i1)), "r"(pack_bf16(q[14] * i1, q[15] * i1)) : "memory");
            }
        };
        auto publish_o = [&]() {
            asm volatile("fence.proxy.async.shared::cta;" ::: "memory");
            __syncwarp();
            mbar_arrive_if(bar_of + 8 * wg, lane == 0);
        };
        int t = 0, left = 0, tdone = -1, b = 0, nout = 0;
        bool first = true, staged = false;
#pragma unroll 1
        for (;; b++) {
            const bool fresh = left == 0;
            const int tprev = t;
            FAT(b, 4);
            if (staged) { publish_o(); staged = false; }
            if (fresh) {
                item++;
                if (!q_ready) {
                    mbar_wait(bar_qf + 8 * (item & 1), (item >> 1) & 1);
                    asm volatile("ld.shared.s32 %0, [%1];" : "=r"(tnext) : "r"(slot + (item & 1) * 4) : "memory");
                }
                if (tnext < 0) break;
                t = tnext;
                left = fa_qt(t) + 1;
            }
            left--;
            if (fresh || first || left == 0) {
                if (tdone >= 0) store_o(tdone, nout);
                if (fresh) { g0 = gn0; g1 = gn1; }
                if (left == 0) { gn0 = __ldcg(g_gate + fa_qt(t) * 128 + r0); gn1 = __ldcg(g_gate + fa_qt(t) * 128 + r0 + 8); clear_out(t); }
            }
            FAT(b, 5);
            if (!k_ready) mbar_wait(bar_kf + 8 * (b & 1), (b >> 1) & 1);
            FAT(b, 6);
            asm volatile("bar.sync %0, 256;" :: "r"(3 + wg) : "memory");
            FAT(b, 0);
            issue_qk(b, item, FA_TRIM && wg == 0 && left == 0);
            FAT(b, 7);
            bool early = false;
            if (!fresh && !first && left != 0) {
                issue_pv(b - 1, true, FA_P0, false);
                wgmma_wait<1>();
                FAT(b, 1);
                mbar_arrive_if(bar_ke + 8 * (b & 1), lane == 0);
            } else {
                const bool hprev = FA_TRIM && fresh && wg == 0;
                early = (FA_EARLY && tdone >= 0) || b == 0 || (FA_TE && hprev);
                if (early) asm volatile("bar.arrive %0, 256;" :: "r"(4 - wg) : "memory");
                if (tdone >= 0) { nout++; staged = true; }
                tdone = fresh && b > 0 ? tprev : -1;
                v_hi = hprev ? v_lo - 512 : v_lo;
                acc_hi = !(hprev && first);
                if (b > 0) issue_pv(b - 1, !first, FA_P0, hprev); else { wgmma_fence(); wgmma_commit(); }
                first = fresh;
                wgmma_wait<1>();
                FAT(b, 1);
                mbar_arrive_if(bar_ke + 8 * (b & 1), lane == 0);
                mbar_arrive_if(bar_qe + 8 * (item & 1), lane == 0 && left == 0);
                if (left == 0) { mask(FA_TRIM ? 32 : 0); mask(FA_TRIM ? 33 : 1); }
                if (fresh) {
                    finish_rows();
                    l0 = l1 = 0.f;
                    m0 = fmaxf(s[0], s[1]); m1 = fmaxf(s[2], s[3]);
                    if (FA_TRIM && left == 0) { m0 = fmaxf(s[32], s[33]); m1 = fmaxf(s[34], s[35]); }
                    quad_max(m0, m1);
                }
            }
            if (FA_B0 || b > 0) {
                float u0, u1;
                if (left == 0) exps(std::integral_constant<int, 2>(), b, !early, u0, u1);
                else exps(std::integral_constant<int, 1>(), b, !early, u0, u1);
                if (!__any_sync(0xffffffff, !(u0 + u1 < 1.f))) { l0 += u0; l1 += u1; continue; }
            }
            softmax_exact(fresh, FA_TRIM && wg == 0 && left == 0, b);
        }
        if (tdone >= 0) { store_o(tdone, nout++); publish_o(); }
        issue_pv(b - 1, !first, 8, FA_TRIM && wg == 0);
        g0 = gn0; g1 = gn1;
        finish_rows();
        wgmma_wait<0>();
        done();
        store_o(t + 1024, nout);
        publish_o();
        return nout;
    }
}

__device__ __forceinline__ uint32_t cluster_ctarank() {
    uint32_t r; asm volatile("mov.u32 %0, %%cluster_ctarank;" : "=r"(r)); return r;
}
__device__ __forceinline__ uint32_t mapa_u32(uint32_t addr, uint32_t rank) {
    uint32_t r; asm volatile("mapa.shared::cluster.u32 %0, %1, %2;" : "=r"(r) : "r"(addr), "r"(rank)); return r;
}
__device__ __forceinline__ void cluster_sync_all() {
    asm volatile("barrier.cluster.arrive.release.aligned;\nbarrier.cluster.wait.acquire.aligned;" ::: "memory");
}
__device__ __forceinline__ void st_async_v4(uint32_t addr, uint32_t a, uint32_t b, uint32_t c, uint32_t d, uint32_t mbar) {
    asm volatile("st.async.weak.shared::cluster.mbarrier::complete_tx::bytes.v4.b32 [%0], {%1, %2, %3, %4}, [%5];"
                 :: "r"(addr), "r"(a), "r"(b), "r"(c), "r"(d), "r"(mbar) : "memory");
}
__device__ __forceinline__ void st_async_v2(uint32_t addr, uint32_t a, uint32_t b, uint32_t mbar) {
    asm volatile("st.async.weak.shared::cluster.mbarrier::complete_tx::bytes.v2.b32 [%0], {%1, %2}, [%3];"
                 :: "r"(addr), "r"(a), "r"(b), "r"(mbar) : "memory");
}
__device__ __forceinline__ void st_async_b32(uint32_t addr, uint32_t a, uint32_t mbar) {
    asm volatile("st.async.weak.shared::cluster.mbarrier::complete_tx::bytes.b32 [%0], %1, [%2];" :: "r"(addr), "r"(a), "r"(mbar) : "memory");
}
__device__ __forceinline__ void pace(int cycles) {
    if (cycles > 0) {
        uint32_t t0, t;
        asm volatile("mov.u32 %0, %%clock;" : "=r"(t0));
        do { asm volatile("mov.u32 %0, %%clock;" : "=r"(t)); } while (t - t0 < (uint32_t)cycles);
    }
}
__device__ __forceinline__ void mbar_wait_cl(uint32_t bar, uint32_t parity) {
    uint32_t done = 0;
    for (int it = 0; it < WAIT_LIMIT && !done; it++) {
        asm volatile(
            "{\n.reg .pred p;\n"
            "mbarrier.try_wait.parity.shared::cta.b64 p, [%1], %2;\n"
            "selp.u32 %0, 1, 0, p;\n}\n" : "=r"(done) : "r"(bar), "r"(parity) : "memory");
    }
}
__device__ __forceinline__ void ldmatrix_x4(uint32_t& r0, uint32_t& r1, uint32_t& r2, uint32_t& r3, uint32_t addr) {
    asm volatile("ldmatrix.sync.aligned.m8n8.x4.shared.b16 {%0,%1,%2,%3}, [%4];"
                 : "=r"(r0), "=r"(r1), "=r"(r2), "=r"(r3) : "r"(addr));
}
__device__ __forceinline__ void cp_async16(uint32_t dst, const void* src) {
    asm volatile("cp.async.cg.shared.global [%0], [%1], 16;" :: "r"(dst), "l"(src) : "memory");
}
__device__ __forceinline__ float bf16r(float x) { return __uint_as_float(pack_bf16(0.f, x) & 0xffff0000u); }

#define DBGP(i, w, ok)
#define DBG(i, w)
#define DBGD(i, w, dep)
#define DBG_EXTRA 0
__device__ __forceinline__ void tma_load_2d_mc(uint32_t dst, const CUtensorMap* map, uint32_t bar, int c0, int c1, uint16_t mask) {
    asm volatile(
        "cp.async.bulk.tensor.2d.shared::cluster.global.mbarrier::complete_tx::bytes.multicast::cluster [%0], [%1, {%3, %4}], [%2], %5;"
        :: "r"(dst), "l"((uint64_t)map), "r"(bar), "r"(c0), "r"(c1), "h"(mask) : "memory");
}
__device__ __forceinline__ void stmatrix_x4_trans(uint32_t addr, uint32_t r0, uint32_t r1, uint32_t r2, uint32_t r3) {
    asm volatile("stmatrix.sync.aligned.m8n8.x4.trans.shared.b16 [%0], {%1, %2, %3, %4};" :: "r"(addr), "r"(r0), "r"(r1), "r"(r2), "r"(r3) : "memory");
}
__device__ __forceinline__ void stmatrix_x2_trans(uint32_t addr, uint32_t r0, uint32_t r1) {
    asm volatile("stmatrix.sync.aligned.m8n8.x2.trans.shared.b16 [%0], {%1, %2};" :: "r"(addr), "r"(r0), "r"(r1) : "memory");
}
__device__ __forceinline__ uint4 lds128(uint32_t a) {
    uint4 v; asm volatile("ld.shared.v4.u32 {%0, %1, %2, %3}, [%4];" : "=r"(v.x), "=r"(v.y), "=r"(v.z), "=r"(v.w) : "r"(a) : "memory"); return v;
}
__device__ __forceinline__ void sts128(uint32_t a, uint32_t x, uint32_t y, uint32_t z, uint32_t w) {
    asm volatile("st.shared.v4.b32 [%0], {%1, %2, %3, %4};" :: "r"(a), "r"(x), "r"(y), "r"(z), "r"(w) : "memory");
}
__device__ __forceinline__ float2 lds64f(uint32_t a) {
    float2 v; asm volatile("ld.shared.v2.f32 {%0, %1}, [%2];" : "=f"(v.x), "=f"(v.y) : "r"(a) : "memory"); return v;
}
__device__ __forceinline__ void fence_async_smem() { asm volatile("fence.proxy.async.shared::cta;" ::: "memory"); }
#define ACC16(d) "+f"(d[0]), "+f"(d[1]), "+f"(d[2]), "+f"(d[3]), "+f"(d[4]), "+f"(d[5]), "+f"(d[6]), "+f"(d[7]), "+f"(d[8]), "+f"(d[9]), "+f"(d[10]), "+f"(d[11]), "+f"(d[12]), "+f"(d[13]), "+f"(d[14]), "+f"(d[15])
template <int ND>
__device__ __forceinline__ void wgmma_rs_n32(float (&d)[ND], const uint32_t (&a)[4], uint32_t db_lo, int scale_d) {
    asm volatile(
        "{\n.reg .pred p;\n.reg .b64 db;\nsetp.ne.b32 p, %21, 0;\nmov.b64 db, {%20, 0x40000040};\n"
        "wgmma.mma_async.sync.aligned.m64n32k16.f32.bf16.bf16 {%0,%1,%2,%3,%4,%5,%6,%7,%8,%9,%10,%11,%12,%13,%14,%15}, {%16,%17,%18,%19}, db, p, 1, 1, 0;\n}\n"
        : ACC16(d) : "r"(a[0]), "r"(a[1]), "r"(a[2]), "r"(a[3]), "r"(db_lo), "r"(scale_d));
}
template <int ND>
__device__ __forceinline__ void wgmma_ss_n32(float (&d)[ND], uint32_t da_lo, uint32_t db_lo, int scale_d) {
    asm volatile(
        "{\n.reg .pred p;\n.reg .b64 da, db;\nsetp.ne.b32 p, %18, 0;\nmov.b64 da, {%16, 0x40000040};\nmov.b64 db, {%17, 0x40000040};\n"
        "wgmma.mma_async.sync.aligned.m64n32k16.f32.bf16.bf16 {%0,%1,%2,%3,%4,%5,%6,%7,%8,%9,%10,%11,%12,%13,%14,%15}, da, db, p, 1, 1, 1, 0;\n}\n"
        : ACC16(d) : "r"(da_lo), "r"(db_lo), "r"(scale_d));
}
__device__ __forceinline__ void wgmma_ss_n8(float (&d)[4], uint32_t da_lo, uint32_t db_lo, int scale_d) {
    asm volatile(
        "{\n.reg .pred p;\n.reg .b64 da, db;\nsetp.ne.b32 p, %6, 0;\nmov.b64 da, {%4, 0x40000040};\nmov.b64 db, {%5, 0x00000010};\n"
        "wgmma.mma_async.sync.aligned.m64n8k16.f32.bf16.bf16 {%0,%1,%2,%3}, da, db, p, 1, 1, 1, 0;\n}\n"
        : "+f"(d[0]), "+f"(d[1]), "+f"(d[2]), "+f"(d[3]) : "r"(da_lo), "r"(db_lo), "r"(scale_d));
}

#define SCHED_FENCE()
__device__ __forceinline__ void wgmma_ss_n32_p(float (&d)[16], uint32_t da_lo, uint32_t db_lo, int scale_d) {
    asm volatile(
        "{\n.reg .pred p;\n.reg .b64 da, db;\nsetp.ne.b32 p, %18, 0;\nmov.b64 da, {%16, 0x40000040};\nmov.b64 db, {%17, 0x00000030};\n"
        "wgmma.mma_async.sync.aligned.m64n32k16.f32.bf16.bf16 {%0,%1,%2,%3,%4,%5,%6,%7,%8,%9,%10,%11,%12,%13,%14,%15}, da, db, p, 1, 1, 1, 0;\n}\n"
        : ACC16(d) : "r"(da_lo), "r"(db_lo), "r"(scale_d));
}

#define ACC20(d) ACC16(d), "+f"(d[16]), "+f"(d[17]), "+f"(d[18]), "+f"(d[19])
#define ACC20_STR "{%0,%1,%2,%3,%4,%5,%6,%7,%8,%9,%10,%11,%12,%13,%14,%15,%16,%17,%18,%19}"
__device__ __forceinline__ void wgmma_rs_n40(float (&d)[20], const uint32_t (&a)[4], uint32_t db_lo, int scale_d) {
    asm volatile(
        "{\n.reg .pred p;\n.reg .b64 db;\nsetp.ne.b32 p, %25, 0;\nmov.b64 db, {%24, 0x40000040};\n"
        "wgmma.mma_async.sync.aligned.m64n40k16.f32.bf16.bf16 " ACC20_STR ", {%20,%21,%22,%23}, db, p, 1, 1, 0;\n}\n"
        : ACC20(d) : "r"(a[0]), "r"(a[1]), "r"(a[2]), "r"(a[3]), "r"(db_lo), "r"(scale_d));
}
template <int TA, int SBO>
__device__ __forceinline__ void wgmma_ss_n40(float (&d)[20], uint32_t da_lo, uint32_t db_lo, int scale_d) {
    asm volatile(
        "{\n.reg .pred p;\n.reg .b64 da, db;\nsetp.ne.b32 p, %22, 0;\nmov.b64 da, {%20, %23};\nmov.b64 db, {%21, 0x40000040};\n"
        "wgmma.mma_async.sync.aligned.m64n40k16.f32.bf16.bf16 " ACC20_STR ", da, db, p, 1, 1, %24, 0;\n}\n"
        : ACC20(d) : "r"(da_lo), "r"(db_lo), "r"(scale_d), "n"(0x40000000 + SBO / 16), "n"(TA));
}
template <int SBO>
__device__ __forceinline__ void wgmma_ss_n48(float (&d)[24], uint32_t da_lo, uint32_t db_lo, int scale_d) {
    asm volatile(
        "{\n.reg .pred p;\n.reg .b64 da, db;\nsetp.ne.b32 p, %26, 0;\nmov.b64 da, {%24, %27};\nmov.b64 db, {%25, 0x40000040};\n"
        "wgmma.mma_async.sync.aligned.m64n48k16.f32.bf16.bf16 {%0,%1,%2,%3,%4,%5,%6,%7,%8,%9,%10,%11,%12,%13,%14,%15,%16,%17,%18,%19,%20,%21,%22,%23}, da, db, p, 1, 1, 0, 0;\n}\n"
        : ACC20(d), "+f"(d[20]), "+f"(d[21]), "+f"(d[22]), "+f"(d[23]) : "r"(da_lo), "r"(db_lo), "r"(scale_d), "n"(0x40000000 + SBO / 16));
}

#define PT(i, th)
struct ChainParams {
    CUtensorMap mapW[3];
    CUtensorMap mapX;
    CUtensorMap mapC;
    CUtensorMap mapWo;
    CUtensorMap mapM;
    CUtensorMap mapOut;
};
constexpr int CH_BLOCK = 384;
constexpr int CO_WO = 0;
constexpr int CH_XC = 5120, CH_XP = 8 * CH_XC;
constexpr int CO_XB = 65536;
constexpr int CO_OB = CO_XB + 2 * CH_XP;
constexpr int CO_P = CO_OB + 8192;
constexpr int CO_LS = CO_P + 3072;
constexpr int CO_SC = CO_LS + 8 * 1280;
constexpr int CH_TW = 6144 + 8192;
constexpr int CO_T = 21 * 8192;
constexpr int CO_WA = CO_T + 6144;
constexpr int CO_ST = CO_T + 3 * CH_TW + 6144;
constexpr int CO_OWN = CO_ST + 4096, CO_OWN2 = CO_SC + 1536;
constexpr int CO_BAR = CO_OWN + 4096;
constexpr int CH_SMEM = CO_BAR + 256 + DBG_EXTRA;
#define CH_GL 2
#define CH_A3 1
#define CH_D0 0
#define CH_PF 0
#define CH_NA 0
#define CH_LQ ""
#define CH_SQ ""
#define CH_XPF 0
#define CH_NSM 4
static_assert(CO_OWN2 + 1024 <= CO_T && CH_NSM <= 4, "smem layout");
#ifndef M_D0
#define M_D0 0
#endif
#define CH_SG 2
#define CH_POLL_DELAY 220
#define CH_VPOS 2
#define CH_OW 12
#define CH_OF 12
#define CH_Q0 0
#define CH_QI 12
#define CH_QX 0
#define CH_Q1 (CH_Q0 + CH_QI + CH_QX)
#define CH_VA 5
#define CH_SPOS 0
#define CH_LSW 1
#define CH_QE 16
#define CH_KE 16
#define CH_QD 0
#define CH_GAP 0
#define CH_QS 0
#define CH_KS 0
#define CH_VS 4
#define CH_A7 7
#define CH_RF 0
#define CH_LSS 0
#define CH_OS 1
#define CH_MG 0
#define CH_MBT 0x76543210u
#define CH_MB(i) ((int)(CH_MBT >> 4 * (i)) & 7)
#define CH_AS 0x64207531u
#define CH_QL 16
#define CH_ML 0x112112
#define CH_DEP 1
#define CH_SP 2
#define CH_VD 0
#define CH_MP 2
#define CH_MP0 2
#define CH_OFE 3
#define CH_MS 1
#define CH_HA 3
#define CH_LD 4
#define CH_TWP 0
#define CH_SUMC 2
#define CH_ES 0
#define CH_ST 224
#define CH_KEEP 1
#define CH_PINB 1
#define CH_DRY 1
#define CH_D1 4500
#define CH_D2 11000
#define CH_CHAINS 4

constexpr float CH_SC = 0.08838834764831845f * 1.4426950408889634f;
__device__ __forceinline__ uint32_t pin(uint32_t v) { return __shfl_sync(0xffffffff, v, threadIdx.x & 31); }

__device__ __forceinline__ void out_finished() {
    if (atomicAdd(&g_ctr[CT_FIN], 1u) == M_GRID + 64 - 1)
        for (int i = 0; i < CT_N / 4; i++) reinterpret_cast<uint4*>(g_ctr)[i] = make_uint4(0u, 0u, 0u, 0u);
}
__device__ __forceinline__ uint32_t tail_a(uint32_t c) { return c < 3 ? CO_XB + 2 * CH_XC + c * 8192 : CO_OB; }
__device__ __forceinline__ void out_flush_half(const float* acc, const CUtensorMap* map, uint32_t stg, int tid, int bar, int n0, int m0) {
    const int lane = tid & 31, row = (lane & 7) + ((lane >> 3) & 1) * 8;
#pragma unroll
    for (int j = 0; j < 16; j += 2) {
        const float* a = &acc[j * 4];
        stmatrix_x4(stg + (j >> 3) * 8192 + (((tid >> 5) & 3) * 16 + row) * 128 + ((((j & 7) + (lane >> 4)) ^ (row & 7)) << 4),
                    pack_bf16(a[0], a[1]), pack_bf16(a[2], a[3]), pack_bf16(a[4], a[5]), pack_bf16(a[6], a[7]));
    }
    asm volatile("fence.proxy.async.shared::cta;\nbar.sync %0, 128;" :: "r"(bar) : "memory");
    asm volatile("{\n.reg .pred p;\nsetp.ne.b32 p, %0, 0;\n@p bra FL_SKIP;\n"
                 "cp.reduce.async.bulk.tensor.2d.global.shared::cta.add.tile.bulk_group [%1, {%3, %5}], [%2];\n"
                 "cp.reduce.async.bulk.tensor.2d.global.shared::cta.add.tile.bulk_group [%1, {%4, %5}], [%2 + 8192];\n"
                 "cp.async.bulk.commit_group;\nFL_SKIP:\n}"
                 :: "r"(tid & 127), "l"((uint64_t)map), "r"(stg), "r"(n0), "r"(n0 + 64), "r"(m0) : "memory");
    __syncwarp();
}
__device__ __forceinline__ void out_flush(const float (&acc)[128], const CUtensorMap* map, uint32_t stg0, uint32_t stg1, int tid, int bar, int n0, int m0) {
    out_flush_half(acc, map, stg0, tid, bar, n0, m0);
    out_flush_half(acc + 64, map, stg1, tid, bar, n0 + 128, m0);
}

__global__ void __cluster_dims__(8, 1, 1) __launch_bounds__(CH_BLOCK, 1)
chain_kernel(const __grid_constant__ ChainParams P) {
    extern __shared__ uint8_t smem_raw[];
    const int tid = threadIdx.x, warp = __shfl_sync(0xffffffff, tid >> 5, 0), lane = tid & 31;
    const int rank = (int)cluster_ctarank();
    constexpr uint32_t sd = 1024;
    const uint32_t sb = ((uint32_t)rank << 24) + sd;
    if (smem_u32(smem_raw) != sb) __trap();
    const int C = blockIdx.x >> 3;
    const int h = C * 4 + (rank >> 1);
    const int qd = lane >> 2, qc = lane & 3;
    const int t4 = warp & 3, wg = warp >> 2;
    pdl_launch_dependents();
    uint32_t t_start;
    asm volatile("mov.u32 %0, %%clock;" : "=r"(t_start));
    t_start = __shfl_sync(0xffffffff, t_start, 0);
    TS_BEGIN(2);
    PT(0, 0);
    const uint32_t bar_mem = sb + CO_BAR + 128, bar_o = sb + CO_BAR + 32, bar_sc = bar_o + 32, bar_x = bar_sc + 8, bar_l = bar_x + 16, bar_w = bar_l + 8;
    const uint32_t bar_wo = bar_o + 24;
    auto chunk = [&](int i) { return (uint32_t)((rank - i) & 7); };
    auto mine = [](int g, int c) { return (int)((CH_AS >> (g * 16 + c * 4)) & 7); };
    const int wcol = h * HD + (rank & 1) * 64;
    auto wdst = [&](int g, int i) { return i == 0 ? CO_WA + g * CH_TW : g && i == 7 ? CO_ST : (g ? CO_XB + CH_XP : 0) + (i - 1) * 8192; };
    auto vdst = [&](int i) { return i >= 2 && i < 10 ? CO_XB + CH_XP + (i - 2) * CH_XC : (i < 2 ? CO_WA + 2 * CH_TW : i < 12 ? CO_OB : i < 14 ? CO_LS : CO_ST) + (i & 1) * 4096; };
    if ((tid & 127) == 0) {
        pace(CH_D0);
        const uint32_t bar = wg == 2 ? bar_x : bar_w + 8 * wg;
        mbar_init(bar, 1);
        asm volatile("fence.mbarrier_init.release.cluster;" ::: "memory");
        mbar_expect_tx(bar, wg == 2 ? CH_XP : 65536);
#pragma unroll 1
        for (int i = 0; i < 8; i++) {
            if (wg == 2) {
                tma_load_2d(sb + CO_XB + i * CH_XC, &P.mapX, bar, i * 64, 0);
                tma_load_2d(sb + CO_XB + i * CH_XC + 4096, &P.mapM, bar, i * 64, 0);
            } else tma_load_2d(sb + wdst(wg, i), &P.mapW[wg ^ (i & 1)], bar, wcol, chunk(mine(wg, i >> 1)) * 64);
        }
    }
    if (warp == 9 && lane < 24 && lane != 9 && (lane >> 1) != 6) {
        mbar_init(sb + CO_BAR + 8 * lane, lane == 15 ? 16 : 1);
        asm volatile("fence.mbarrier_init.release.cluster;" ::: "memory");
    }
    __syncthreads();
    PT(1, 0);
    if (wg == 2 || (wg == 0 && CH_QL < 16)) asm volatile("bar.arrive 10, %0;" :: "n"(CH_QL < 16 ? 384 : 256) : "memory");
    if (wg == 2) {
        const int t = tid - 256;
        sts128(sb + CO_T + (2 + (t >> 6)) * CH_TW + 5120 + (t & 63) * 16, 0u, 0u, 0u, 0u);
        if (t < 32) sts128(sb + CO_P + (t >> 3) * 768 + 640 + (t & 7) * 16, 0u, 0u, 0u, 0u);
    }
    const uint32_t wfrag = (((lane >> 4) << 3) + (lane & 7)) * 128 + (((t4 * 2 + ((lane >> 3) & 1)) ^ (lane & 7)) << 4);
    const uint32_t aO = pin(sb + wg * CH_TW + wfrag);
    const uint32_t aL = pin(sb + lane * 16);
    uint32_t w[32][4];
    auto load_w = [&](int g, bool v) {
#pragma unroll
        for (int e = CH_NSM; e < 32; e++) ldmatrix_x4_trans(w[e][0], w[e][1], w[e][2], w[e][3], aO + ((v ? vdst(e >> 1) + (e & 1) * 2048 : wdst(g, e >> 2) + (e & 3) * 2048) - g * CH_TW));
        fence_async_smem();
    };
    auto pass = [&](auto& d, int g, int b, int j0, int j1, int js, bool group = true) {
        const uint32_t lo = desc_lo(sd + CO_XB + b * CH_XP, 16);
        if (group) wgmma_fence();
#pragma unroll
        for (int j = 0; j < 32; j++) if (j >= j0 && j < j1) {
            const int f = js < 0 ? j : j < js ? j + CH_NSM : j < js + CH_NSM ? j - js : j;
            const int e = sizeof(d) == 64 ? (f >> 2) * 8 + (js < 0 ? 4 : 0) + (f & 3) : f;
            const uint32_t db = lo + chunk(sizeof(d) == 64 ? mine(g, f >> 2) : f >> 2) * (CH_XC / 16) + (e & 3) * 2, da = desc_lo(sd + CO_WA + g * CH_TW + e * 2048, 16);
            if constexpr (sizeof(d) == 64) { if (e < CH_NSM) wgmma_ss_n32(d, da, db, j != 0); else wgmma_rs_n32(d, w[e], db, j != 0); }
            else { if (e < CH_NSM) wgmma_ss_n40<1, 1024>(d, da, db, j != 0); else wgmma_rs_n40(d, w[e], db, j != 0); }
        }
        if (group) wgmma_commit();
    };
    auto uni = [](uint32_t v) { return __shfl_sync(0xffffffff, v, 0); };
    auto roff = [&](int j) { return (uint32_t)(((rank + j) & 7) - rank) << 24; };
    auto store32 = [&](const float* d, uint32_t a) {
        stmatrix_x4_trans(a, pack_bf16(d[0], d[1]), pack_bf16(d[2], d[3]), pack_bf16(d[4], d[5]), pack_bf16(d[6], d[7]));
        stmatrix_x4_trans(a + 2048, pack_bf16(d[8], d[9]), pack_bf16(d[10], d[11]), pack_bf16(d[12], d[13]), pack_bf16(d[14], d[15]));
    };
    auto load32 = [&](uint32_t (&r)[8], uint32_t a) {
        ldmatrix_x4_trans(r[0], r[1], r[2], r[3], a);
        ldmatrix_x4_trans(r[4], r[5], r[6], r[7], a + 2048);
    };
    auto add32 = [&](float* d, const uint32_t (&r)[8], uint32_t a) {
        wgmma_wait<0>();
#pragma unroll
        for (int i = 0; i < 8; i++) { d[2 * i] += __uint_as_float(r[i] << 16); d[2 * i + 1] += __uint_as_float(r[i] & 0xffff0000u); }
        store32(d, a);
    };
    auto scores = [&](float (&d)[24], auto sbo, uint32_t q) {
        wgmma_fence();
#pragma unroll
        for (int ks = 0; ks < 4; ks++) wgmma_ss_n48<decltype(sbo)::value>(d, desc_lo(sd + q, 16) + ks * 2, desc_lo(sd + CO_T + CH_TW, 16) + ks * 2, ks != 0);
        wgmma_commit();
    };
    auto add_scores = [&](uint32_t a, uint32_t b, float (&v)[10]) {
        const uint4 a0 = lds128(a), a1 = lds128(a + 512);
        const float2 a2 = lds64f(b);
        v[0] += __uint_as_float(a0.x); v[1] += __uint_as_float(a0.y); v[2] += __uint_as_float(a0.z); v[3] += __uint_as_float(a0.w);
        v[4] += __uint_as_float(a1.x); v[5] += __uint_as_float(a1.y); v[6] += __uint_as_float(a1.z); v[7] += __uint_as_float(a1.w);
        v[8] += a2.x; v[9] += a2.y;
    };
    auto row_max = [&](const float (&v)[10]) {
        float mx = fmaxf(fmaxf(fmaxf(v[0], v[1]), fmaxf(v[2], v[3])), fmaxf(fmaxf(v[4], v[5]), fmaxf(v[6], v[7])));
        mx = fmaxf(mx, fmaxf(v[8], v[9]));
        mx = fmaxf(mx, __shfl_xor_sync(0xffffffff, mx, 1));
        return fmaxf(mx, __shfl_xor_sync(0xffffffff, mx, 2)) * CH_SC;
    };
    auto local_pv = [&](int s, int st) {
        float dc[16];
        wgmma_fence();
#pragma unroll
        for (int ks = 0; ks < 3; ks++) wgmma_ss_n32_p(dc, desc_lo(sd + CO_T + (2 + (s & 1)) * CH_TW + ks * 2048, 16), desc_lo(sd + CO_P + ks * 256, 128), ks != 0);
        wgmma_commit();
        wgmma_wait<0>();
        store32(dc, aO - CH_TW + st);
    };
    float gs = 0.f;
    auto load_gate = [&](int s) { asm volatile("ld.global.cg.f32 %0, [%1];" : "=f"(gs) : "l"(g_gate + s * SEGL + t4 * 8 + qd) : "memory"); };
    auto softmax = [&](int s, float (&u)[11]) {
        float v[10];
        {
            const uint4 a0 = lds128(aL + CO_OWN + t4 * 1024), a1 = lds128(aL + CO_OWN + t4 * 1024 + 512);
            const float2 a2 = lds64f(aL + CO_OWN2 + t4 * 256 - lane * 8);
            v[0] = __uint_as_float(a0.x); v[1] = __uint_as_float(a0.y); v[2] = __uint_as_float(a0.z); v[3] = __uint_as_float(a0.w);
            v[4] = __uint_as_float(a1.x); v[5] = __uint_as_float(a1.y); v[6] = __uint_as_float(a1.z); v[7] = __uint_as_float(a1.w);
            v[8] = a2.x; v[9] = a2.y;
        }
        mbar_wait_cl(bar_l, s & 1);
        add_scores(aL + t4 * 1024 + CO_LS + (s & 1) * 5120, aL + t4 * 256 - lane * 8 + CO_LS + (s & 1) * 5120 + 4096, v);
        const int lim = t4 * 8 + qd - 2 * qc;
#pragma unroll
        for (int j = 0; j < 8; j++) if ((j >> 1) * 8 + (j & 1) > lim) v[j] = -INFINITY;
        const float mx = row_max(v);
#pragma unroll
        for (int j = 0; j < 10; j++) u[j] = v[j];
        u[10] = mx;
    };
    auto softmax1 = [&](float (&u)[11]) {
#pragma unroll
        for (int j = 0; j < 10; j++) u[j] = ex2f(fmaf(u[j], CH_SC, -u[10]));
        u[10] = (((u[0] + u[1]) + (u[2] + u[3])) + ((u[4] + u[5]) + (u[6] + u[7]))) + (u[8] + u[9]);
    };
    auto softmax2 = [&](float (&v)[11]) {
        float sum = v[10];
        sum += __shfl_xor_sync(0xffffffff, sum, 1);
        sum += __shfl_xor_sync(0xffffffff, sum, 2);
        asm("rcp.approx.ftz.f32 %0, %0;" : "+f"(sum));
        sum *= 1.f - gs;
        const uint32_t pa = aL + CO_P + t4 * 768;
        stmatrix_x4(pa, pack_bf16(v[0] * sum, v[1] * sum), pack_bf16(v[2] * sum, v[3] * sum), pack_bf16(v[4] * sum, v[5] * sum), pack_bf16(v[6] * sum, v[7] * sum));
        asm volatile("stmatrix.sync.aligned.m8n8.x1.shared.b16 [%0], {%1};" :: "r"(pa + 512), "r"(pack_bf16(v[8] * sum, v[9] * sum)) : "memory");
    };
    if (mapa_u32(bar_l, rank ^ 1) != (bar_l ^ (1u << 24)) || mapa_u32(bar_l, (rank + 3) & 7) != bar_l + roff(3)) __trap();
    asm volatile("bar.sync %0, 128;" :: "r"(12 + wg) : "memory");
    if (__shfl_sync(0xffffffff, tid, 1) < 256) {
#pragma unroll 1
        for (int rep = CH_DRY ? 0 : 1; rep < 2; rep++) {
            if (rep) mbar_wait(bar_w + 8 * wg, 0);
            PT(3, 0);
            load_w(wg, false);
            if (rep) {
                asm volatile("bar.arrive %0, 160;" :: "r"(wg ? 2 : 15) : "memory");
                asm volatile("barrier.cluster.arrive.relaxed.aligned;" ::: "memory");
                mbar_wait(bar_x, 0);
            }
            asm volatile("bar.sync 12, 256;" ::: "memory");
            PT(7, 0);
            float d[16];
            pass(d, wg, 0, 0, 16, -1);
            wgmma_wait<0>();
            store32(d, aO + CO_T + (1 - 2 * wg) * CH_TW);
            pass(d, wg, 0, 0, 16, 0);
            asm volatile("bar.sync 13, 256;" ::: "memory");
            uint32_t r[8];
            load32(r, aO + CO_T);
            add32(d, r, aO + CO_T);
        }
    }
    PT(8, 0);
    TS_BEGIN(5);
    PT(9, 0);

    if (wg < 2) {
        const uint32_t aM = pin(sb + CO_XB + 4096 + (lane & 7) * 128 + (((lane >> 3) ^ (lane & 7)) << 4));
        uint32_t coff[4];
#pragma unroll
        for (int i = 0; i < 4; i++) coff[i] = uni(chunk(mine(wg, i)) * CH_XC);
        auto mem_proj = [&](int s, auto gc) {
            constexpr int G = decltype(gc)::value;
            const uint32_t par = s & 1;
            float acc[4][4];
#pragma unroll
            for (int i = 0; i < 4; i++) acc[i][0] = acc[i][1] = acc[i][2] = acc[i][3] = 0.f;
            const uint32_t am = aM + par * CH_XP;
            uint32_t b[4][4], ok = 1;
            auto bar = [&](int c) { return bar_mem + 8 * CH_MB(mine(G, c)); };
            auto load = [&](int c) {
                if (c ? CH_MB(mine(G, c)) != CH_MB(mine(G, c - 1)) : G == 0)
                    asm volatile("{\n.reg .pred p, q;\n.reg .u32 c;\nsetp.ne.u32 p, %2, 0;\n@p bra MP_DONE;\nmov.u32 c, 0;\n"
                                 "MP_LOOP:\nmbarrier.try_wait.parity.shared::cta.b64 p, [%0], %1;\nadd.u32 c, c, 1;\nsetp.lt.and.u32 q, c, %3, !p;\n"
                                 "@q bra MP_LOOP;\nMP_DONE:\n}" :: "r"(bar(c)), "r"(par ^ 1), "r"(ok), "n"(WAIT_LIMIT / 64) : "memory");
                uint32_t* r = b[2 * c & 3];
                ldmatrix_x4(r[0], r[1], r[2], r[3], am + coff[c]);
                r = b[(2 * c + 1) & 3];
                ldmatrix_x4(r[0], r[1], r[2], r[3], (am ^ 64) + coff[c]);
                if (c < 3 && CH_MB(mine(G, c + 1)) != CH_MB(mine(G, c))) ok = mbar_try(bar(c + 1), par ^ 1);
            };
            auto mma = [&](int i) {
#pragma unroll
                for (int j = 0; j < 4; j++) {
                    const uint32_t* a = w[(i >> 1) * 8 + ((j & 1) ^ G) * 4 + (i & 1) * 2 + (j >> 1)];
                    mma_16816(acc[j], a[0], a[1], a[2], a[3], b[i & 3][j & 2], b[i & 3][(j & 2) + 1]);
                }
            };
#pragma unroll
            for (int e = 0; e < CH_NSM; e++) ldmatrix_x4_trans(w[e][0], w[e][1], w[e][2], w[e][3], aO + CO_WA + e * 2048);
            if (G == 1) asm volatile("bar.sync 10, %0;" :: "n"(CH_QL < 16 ? 384 : 256) : "memory");
            else ok = mbar_try(bar(0), par ^ 1);
            DBG(11, 0);
            load(0);
#pragma unroll
            for (int c = 0; c < 3; c++) {
                const int at = (CH_ML >> (c * 4 + G * 12)) & 3;
                if (at == 0) load(c + 1);
                mma(2 * c);
                if (at == 1) load(c + 1);
                mma(2 * c + 1);
                if (at == 2) load(c + 1);
            }
            mma(6);
            uint32_t dep = __float_as_uint(acc[CH_HA & 3][0]);
            mma(7);
            if (CH_HA >= 4) dep = __float_as_uint(acc[CH_HA & 3][0]);
            asm volatile("bar.arrive %0, 384;" :: "r"(5 | (dep & (s >> 10))) : "memory");
            uint32_t r[4];
#pragma unroll
            for (int i = 0; i < 4; i++) r[i] = pack_bf16(acc[i >> 1][(i & 1) * 2] + acc[(i >> 1) + 2][(i & 1) * 2], acc[i >> 1][(i & 1) * 2 + 1] + acc[(i >> 1) + 2][(i & 1) * 2 + 1]);
            DBGD(40 + warp, warp, r[0] ^ r[1]);
            asm volatile("{\n.reg .pred q;\nsetp.ne.s32 q, %3, 0;\n"
                         "@q stmatrix.sync.aligned.m8n8.x2.trans.shared.b16 [%0], {%1, %2};\n"
                         "@q stmatrix.sync.aligned.m8n8.x2.trans.shared.b16 [%0 + %4], {%1, %2};\n"
                         "@q stmatrix.sync.aligned.m8n8.x2.trans.shared.b16 [%0 + 2 * %4], {%1, %2};\n"
                         "@q stmatrix.sync.aligned.m8n8.x2.trans.shared.b16 [%0 + 3 * %4], {%1, %2};\n}"
                         :: "r"(aO + (CO_XB + 4096 + G * (CH_XC - CH_TW) + (par ^ 1) * CH_XP)), "r"(r[0]), "r"(r[1]),
                            "r"(s - (NSEG - 1)), "n"(2 * CH_XC) : "memory");
            stmatrix_x2_trans(aO + CO_T + (G ? 5120 : CH_TW + 4096), r[2], r[3]);
            fence_async_smem();
        };
        if (wg == 0) {
#pragma unroll 1
            for (int s = 0; s < NSEG; s++) {
                const uint32_t par = s & 1;
                mem_proj(s, std::integral_constant<int, 0>());
                asm volatile("bar.arrive 1, 256;" ::: "memory");
                asm volatile("bar.sync 8, 384;" ::: "memory");
                if (s == NSEG - 1) break;
                if (tid == 96) {
#pragma unroll
                    for (int j = 1; j < 8; j++) {
                        int n = 0;
                        for (int i = 1; i < 8; i++) n += CH_MB(i) == j;
                        if (n) mbar_expect_tx(bar_mem + 8 * j, 1024 * n);
                        if (j < 4) mbar_expect_tx(bar_o + 8 * j - 8, 512 << j);
                    }
                }
                __syncwarp();
                uint32_t* wp = g_xbuf + (size_t)rank * 2048 + C * 256 + qc * 64 + t4 * 8 + qd;
                asm volatile("st.relaxed.gpu.global" CH_SQ ".u32 [%0], %1;" :: "l"(wp + ((s + 2) & 3) * 16384), "r"(~0u) : "memory");
                asm volatile("st.relaxed.gpu.global" CH_SQ ".u32 [%0], %1;" :: "l"(wp + ((s + 2) & 3) * 16384 + 32), "r"(~0u) : "memory");
                if (__builtin_expect(s == 0, 0)) {
                    asm volatile("barrier.cluster.wait.aligned;" ::: "memory");
                    mbar_wait(bar_wo, 0);
                    const int sr = (qd >> 2) * 2 + (qd & 1) + (qd & 2) * 4;
#pragma unroll 2
                    for (int ks = t4; ks < 32; ks += 4) {
                        const uint32_t a = sb + CO_WO + ks * 2048;
                        uint4 u[2][2];
#pragma unroll
                        for (int i = 0; i < 4; i++) { const int r = sr + (i >> 1) * 4; u[i >> 1][i & 1] = lds128(a + r * 128 + (((qc * 2 + (i & 1)) ^ (r & 7)) << 4)); }
                        __syncwarp();
#pragma unroll
                        for (int i = 0; i < 4; i++) {
                            const uint4 u0 = u[i >> 1][0], u1 = u[i >> 1][1];
                            const uint32_t sel = (i & 1) ? 0x7632 : 0x5410;
                            sts128(a + (qd + (i >> 1) * 8) * 128 + (((qc * 2 + (i & 1)) ^ qd) << 4),
                                   __byte_perm(u0.x, u0.y, sel), __byte_perm(u0.z, u0.w, sel), __byte_perm(u1.x, u1.y, sel), __byte_perm(u1.z, u1.w, sel));
                        }
                    }
                    fence_async_smem();
                }
                mbar_wait(bar_x + 8 * (par ^ 1), ((s + 1) >> 1) & 1);
                asm volatile("bar.sync 7, 384;" ::: "memory");
                float d[16];
                float c[4];
                const uint32_t alo = desc_lo(sd + CO_WO, 16), blo = desc_lo(sd + CO_OB, 128);
                wgmma_fence();
                pass(d, 0, par ^ 1, 0, CH_Q0, -1, false);
                asm volatile("bar.sync 11, 256;" ::: "memory");
#pragma unroll
                for (int i = 0; i < 32; i++) {
                    if (i == 4) { pass(d, 0, par ^ 1, CH_Q0 + min(4, CH_QI), CH_Q0 + min(4, CH_QI) + CH_QX, -1, false); mbar_wait_cl(bar_o, par); }
                    if (i == 8) mbar_wait_cl(bar_o + 8, par);
                    if (i == CH_OW) mbar_wait_cl(bar_o + 16, par);
                    wgmma_ss_n8(c, alo + i * 128, blo + i * 16, i != 0);
                    if (i < CH_QI) pass(d, 0, par ^ 1, CH_Q0 + i + (i < 4 ? 0 : CH_QX), CH_Q0 + i + (i < 4 ? 0 : CH_QX) + 1, -1, false);
                }
                wgmma_commit();
                wgmma_wait<0>();
                asm volatile("st.relaxed.gpu.global" CH_SQ ".u32 [%0], %1;" :: "l"(wp + (s & 3) * 16384), "r"(pack_bf16(c[0], c[2])) : "memory");
                asm volatile("st.relaxed.gpu.global" CH_SQ ".u32 [%0], %1;" :: "l"(wp + (s & 3) * 16384 + 32), "r"(pack_bf16(c[1], c[3])) : "memory");
                asm volatile("bar.arrive 6, 384;" ::: "memory");
                pace(CH_QD);
                asm volatile("bar.arrive 4, 384;" ::: "memory");
                DBG(8, 0);
                if (CH_Q1 < 16) pass(d, 0, par ^ 1, CH_Q1, 16, -1);
                asm volatile("bar.sync 9, 256;" ::: "memory");
                wgmma_wait<0>();
                store32(d, aO + CO_T + CH_TW);
                asm volatile("bar.arrive 12, 256;" ::: "memory");
                if (CH_QL) pass(d, 0, (par ^ 1) + (s >> 10), 0, CH_QL, CH_QS);
                DBG(21, 0);
                if (tid == 0) {
                    if (s + 2 < NSEG) {
                        mbar_expect_tx(bar_x + 8 * par, 32768);
                        tma_load_2d_mc(sb + CO_XB + par * CH_XP + rank * CH_XC, &P.mapX, bar_x + 8 * par, rank * 64, (s + 2) * SEGL, (uint16_t)0xff);
                        if (CH_XPF) asm volatile("cp.async.bulk.prefetch.tensor.2d.L2.global [%0, {%1, %2}];" :: "l"(&P.mapX), "r"(rank * 64), "r"((s + 2 + CH_XPF) * SEGL) : "memory");
                    } else {
#pragma unroll 1
                        for (int i = 0; i < 8; i++) tma_load_2d(sb + CO_WO + i * 8192, &P.mapWo, bar_wo, (rank & 3) * 128 + (i & 1) * 64, (h & ~1) * HD + (i >> 1) * 64);
                    }
                }
                __syncwarp();
                asm volatile("bar.sync 13, 256;" ::: "memory");
                uint32_t r[8];
                load32(r, aO + CO_T);
                if (CH_QL < 16) {
                    asm volatile("bar.sync 10, 384;" ::: "memory");
                    pass(d, 0, (par ^ 1) + (s >> 10), CH_QL, CH_QE, CH_QS);
                }
                add32(d, r, aO + CO_T);
                DBG(22, 0);
            }
            *reinterpret_cast<uint2*>(g_xbuf + 16384 + blockIdx.x * 256 + tid * 2) = make_uint2(~0u, ~0u);
        PT(10, 0);
            if (tid == 0) {
                mbar_expect_tx(bar_wo, 65536 + 32768);
                mbar_expect_tx(bar_w, 24576);
                asm volatile("prefetch.tensormap [%0];" :: "l"(&P.mapOut) : "memory");
                wait_ctr(CT_CA + 63, 16u);
            }
            __syncwarp();
            uint32_t fin = 0;
#pragma unroll 1
            for (int r = 0; r < 2; r++) {
                float acc[64];
                mbar_wait(bar_wo, 1);
                asm volatile("bar.sync %0, 256;" :: "r"(15 - r) : "memory");
                asm volatile("{\n.reg .pred p;\nsetp.eq.b32 p, %2, 32;\n@p atom.relaxed.gpu.global.inc.u32 %0, [%1], 0x7fffffff;\n}"
                             : "+r"(fin) : "l"(&g_ctr[CT_FIN]), "r"(tid + r * 128) : "memory");
                wgmma_fence();
#pragma unroll
                for (int i = 0; i < 16; i++) {
                    const uint32_t c = (rank + (i >> 2)) & 3;
                    const uint32_t a = r == 0 ? tail_a(c) : i < 4 ? CO_WA + CH_TW : CO_XB + CH_XP + c * 8192;
                    if (i == 4) mbar_wait(r ? bar_w : bar_wo, 1);
                    wgmma_ss_n128_lo<1>(acc, desc_lo(sd + a, 16) + (i & 3) * 2, desc_lo(sd + CO_WO, 8192) + c * 1024 + (i & 3) * 128, i);
                }
                wgmma_commit();
                wgmma_wait<0>();
                PT(5, 0);
                out_flush_half(acc, &P.mapOut, sb + (r ? tail_a(0) : CO_T), tid, 12, (rank & 3) * 128, SEQ - 128 + r * 64);
            }
            if (fin == M_GRID + 64 - 1)
                for (int i = 0; i < CT_N / 4; i++) reinterpret_cast<uint4*>(g_ctr)[i] = make_uint4(0u, 0u, 0u, 0u);
            if (tid == 0) {
                asm volatile("cp.async.bulk.wait_group.read 0;" ::: "memory");
                PT(15, 0);
            }
        } else {
            const uint32_t usc = uni(CO_SC + min(t4, 2) * 512 + roff((rank ^ 1) - rank)), uscb = uni(bar_sc ^ (1u << 24));
            const uint32_t vaddr = pin(sb + CO_T + 2 * CH_TW + (lane & 15) * 128 + (((t4 * 2 + (lane >> 4)) ^ (lane & 7)) << 4));
            const uint32_t dsta = pin(sb + CO_OB + t4 * 256 + (qc >> 1) * 128 + qd * 16 + (qc & 1) * 8);
            auto store_ctx = [&](int s) {
                if (tid == CH_ST && (uint32_t)s < NSEG - 3) {
                    tma_store_2d(&P.mapC, sb + CO_ST, (rank & 1) * 64, h * SEQ + s * SEGL);
                    asm volatile("cp.async.bulk.commit_group;" ::: "memory");
                }
                __syncwarp();
            };
            auto signal_ctx = [&](int s) {
                if (tid == CH_ST && (s & 3) == 1)
                    asm volatile("cp.async.bulk.wait_group 0;\nred.relaxed.gpu.global.add.u32 [%0], 1;" :: "l"(&g_ctr[CT_CB - 1 + (s >> 2)]) : "memory");
                __syncwarp();
            };
            uint32_t uo[8], ub[8];
#pragma unroll
            for (int i = 0; i < 8; i++) { uo[i] = uni(roff(i) + i * 1024); ub[i] = uni(roff(i) + bar_o + (i < 2 ? 0 : i < 4 ? 8 : 16)); }
#pragma unroll 1
            for (int s = 0; s < NSEG; s++) {
                const uint32_t par = s & 1;
                mem_proj(s, std::integral_constant<int, 1>());
                asm volatile("bar.sync 1, 256;" ::: "memory");
                float d[24];
                scores(d, std::integral_constant<int, CH_XC>(), CO_XB + 4096 + (par ^ 1) * CH_XP);
                if (s == NSEG - 1) { wgmma_wait<0>(); break; }
                asm volatile("bar.arrive 8, 384;" ::: "memory");
                if (s == 0) asm volatile("barrier.cluster.wait.aligned;" ::: "memory");
                const uint32_t sca = (aL | (s >> 10)) + usc;
                wgmma_wait<0>();
                float v[10], u[12];
#pragma unroll
                for (int j = 0; j < 12; j++) u[j] = d[(j >> 1) * 4 + (j & 1)] + d[(j >> 1) * 4 + (j & 1) + 2];
                if (t4 < 3) {
                    auto sel = [&](int j) { return t4 == 0 ? u[j] : t4 == 1 ? u[4 + j] : u[8 + j]; };
                    asm volatile("st.async.weak.shared::cluster.mbarrier::complete_tx::bytes.v4.f32 [%0], {%2, %3, %4, %5}, [%1];"
                                 :: "r"(sca), "r"(uscb), "f"(sel(0)), "f"(sel(1)), "f"(sel(2)), "f"(sel(3)) : "memory");
                }
#pragma unroll
                for (int j = 0; j < 10; j++) v[j] = j < 8 ? u[j] : u[j] + u[j + 2];
                DBG(3, 4);
                if (CH_ES) signal_ctx(s); else store_ctx(s - 2);
                uint32_t vb[3][4];
                auto load_v = [&](float dep) {
                    asm volatile("bar.sync %0, 256;" :: "r"(CH_VD ? 3 | (__float_as_uint(dep) & (s >> 10)) : 3) : "memory");
#pragma unroll
                    for (int k = 0; k < 3; k++) ldmatrix_x4_trans(vb[k][0], vb[k][1], vb[k][2], vb[k][3], vaddr + par * CH_TW + k * 2048);
                };
                mbar_wait_cl(bar_sc, par);
                DBG(4, 4);
                {
                    const uint4 a0 = lds128(aL + CO_SC), a1 = lds128(aL + CO_SC + 512), a2 = lds128(aL + CO_SC + 1024);
                    v[0] += __uint_as_float(a0.x); v[1] += __uint_as_float(a0.y); v[2] += __uint_as_float(a0.z); v[3] += __uint_as_float(a0.w);
                    v[4] += __uint_as_float(a1.x); v[5] += __uint_as_float(a1.y); v[6] += __uint_as_float(a1.z); v[7] += __uint_as_float(a1.w);
                    v[8] += __uint_as_float(a2.x) + __uint_as_float(a2.z); v[9] += __uint_as_float(a2.y) + __uint_as_float(a2.w);
                }
                const float mx = row_max(v);
                if (CH_VPOS == 2) load_v(mx);
#pragma unroll
                for (int j = 0; j < 10; j++) v[j] = ex2f(fmaf(v[j], CH_SC, -mx));
                uint32_t p[5];
#pragma unroll
                for (int j = 0; j < 5; j++) p[j] = pack_bf16(v[2 * j], v[2 * j + 1]);
                if (CH_VPOS == 3) load_v(v[CH_VD]);
                DBG(19, 4);
                float c0[4] = {0.f, 0.f, 0.f, 0.f}, c1[4] = {0.f, 0.f, 0.f, 0.f}, cs[4] = {0.f, 0.f, 0.f, 0.f};
#pragma unroll
                for (int k = 0; k < 3; k++) {
                    const uint32_t p0 = p[2 * k], p1 = k < 2 ? p[2 * k + 1] : 0u;
                    mma_16816(cs, p0, 0u, p1, 0u, 0x3f803f80u, 0x3f803f80u);
                    mma_16816(c0, p0, 0u, p1, 0u, vb[k][0], vb[k][1]);
                    mma_16816(c1, p0, 0u, p1, 0u, vb[k][2], vb[k][3]);
                }
                float inv;
                asm volatile("rcp.approx.ftz.f32 %0, %1;" : "=f"(inv) : "f"(cs[0]));
                const uint32_t b0 = pack_bf16(c0[0] * inv, c0[1] * inv), b1 = pack_bf16(c1[0] * inv, c1[1] * inv);
                DBG(20, 4);
#pragma unroll
                for (int i = 1; i < 8; i++) {
                    st_async_v2((dsta | (s >> 10)) + uo[i], b0, b1, ub[i]);
                    if (i == CH_OS) asm volatile("st.shared.v2.b32 [%0], {%1, %2};" :: "r"(dsta), "r"(b0), "r"(b1) : "memory");
                    if (i == CH_OFE) asm volatile("fence.proxy.async.shared::cta;\nbar.arrive 11, 256;" ::: "memory");
                }
                DBG(5, 4);
                asm volatile("cp.async.bulk.wait_group.read 0;" ::: "memory");
                asm volatile("bar.sync 7, 384;" ::: "memory");
                if (CH_OFE > 7) asm volatile("fence.proxy.async.shared::cta;\nbar.arrive 11, 256;" ::: "memory");
                local_pv(s + 1, CO_ST);
                if (CH_ES) fence_async_smem();
                asm volatile("bar.arrive 6, 384;" ::: "memory");
                if (tid == 128) mbar_expect_tx(bar_sc, 1536);
                __syncwarp();
                if (CH_SG == 1) signal_ctx(s);
                mbar_wait(bar_x + 8 * (par ^ 1), ((s + 1) >> 1) & 1);
                if (CH_SG == 2) signal_ctx(s);
                asm volatile("bar.sync 4, 384;" ::: "memory");
                float dk[16];
                pass(dk, 1, par ^ 1, 0, 16, -1);
                wgmma_wait<0>();
                store32(dk, aO + CO_T - CH_TW);
                asm volatile("bar.arrive 13, 256;" ::: "memory");
                pass(dk, 1, (par ^ 1) + (s >> 10), 0, CH_KE, CH_KS);
                if (CH_ES) store_ctx(s - 1); else if (!CH_SG) signal_ctx(s);
                DBG(1, 4);
                asm volatile("bar.sync 12, 256;" ::: "memory");
                uint32_t r[8];
                load32(r, aO + CO_T);
                add32(dk, r, aO + CO_T);
                DBG(29, 4);
            }
        }
    } else {
        {
            PT(2, 256);
            int lane;
            asm volatile("mov.u32 %0, %%laneid;" : "=r"(lane));
            if (t4 >= 2) {
                const CUtensorMap* map = t4 == 2 ? &P.mapWo : &P.mapW[2];
                const uint32_t bar = t4 == 2 ? bar_wo : bar_w + 16;
                const int c0 = t4 == 2 ? rank * 64 : wcol;
                auto row = [&](int i) { return t4 == 2 ? C * 512 + ((rank - i) & 7) * 64 : (int)chunk(i >> 1) * 64 + (i & 1) * 32; };
                uint32_t now;
                do { asm volatile("mov.u32 %0, %%clock;" : "=r"(now)); } while (now - t_start < (uint32_t)(t4 == 2 ? CH_D2 : CH_D1));
                if (lane == 0) {
#pragma unroll 1
                    for (int i = 0; i < (CH_PF == 2 ? t4 * 8 - 8 : CH_PF * (t4 * 16 - 32)); i++) asm volatile("cp.async.bulk.prefetch.tensor.2d.L2.global [%0, {%1, %2}];" :: "l"(map), "r"(c0), "r"(row(i)) : "memory");
                    mbar_expect_tx(bar, 65536);
                }
                __syncwarp();
                asm volatile("bar.sync %0, 160;" :: "r"(t4 == 2 ? 15 : 2) : "memory");
                if (lane == 0) {
#pragma unroll 1
                    for (int i = 0; i < t4 * 8 - 8; i++) tma_load_2d(sb + (t4 == 2 ? CO_WO + i * 8192 : vdst(i)), map, bar, c0, row(i));
                }
            } else if (t4 == 0 && lane == 0) {
                asm volatile("cp.async.bulk.prefetch.tensor.2d.L2.global [%0, {%1, %2}];" :: "l"(&P.mapX), "r"(rank * 64), "r"(SEGL) : "memory");
                asm volatile("prefetch.tensormap [%0];" :: "l"(&P.mapC) : "memory");
                mbar_expect_tx(bar_sc, 1536);
                mbar_expect_tx(bar_x + 8, 32768);
            }
            __syncwarp();
            mbar_wait(bar_w + 16, 0);
            PT(4, 256);
            load_w(2, true);
            asm volatile("bar.sync 14, 128;" ::: "memory");
            asm volatile("barrier.cluster.arrive.relaxed.aligned;" ::: "memory");
            if (t4 == 0 && lane == 0) {
#pragma unroll 1
                for (int i = 0; i < 8; i++) tma_load_2d(sb + CO_XB + CH_XP + i * CH_XC, &P.mapX, bar_x + 8, i * 64, SEGL);
            }
            __syncwarp();
            PT(6, 256);
        }
#pragma unroll 1
        for (int s = 0; s < NSEG; s++) {
            const uint32_t par = s & 1;
            const bool last = s == NSEG - 1;
            if (CH_GL < 2) {
                if (s == 1) wait_ctr(CT_GATE, 256u);
                load_gate(max(s - 1, 0));
                if (CH_GL) asm volatile("prefetch.global.L2 [%0];" :: "l"(g_gate + ((s + 1) & (NSEG - 1)) * SEGL) : "memory");
            } else if (s == 1) { wait_ctr(CT_GATE, 256u); load_gate(0); }
            float v[11];
            if (CH_SP) fence_async_smem();
            softmax(s - 1, v);
            if (CH_SP < 2) softmax1(v);
            DBG(7, 8);
            if (!CH_SP) fence_async_smem();
            asm volatile("bar.sync %0, 384;" :: "r"(CH_SP ? 5 | (__float_as_uint(v[10]) & (s >> 10)) : 5) : "memory");
            DBG(23, 8);
            float dv[20], d[24];
            pass(dv, 2, par, 0, CH_VA, CH_VS);
            asm volatile("bar.sync 8, 384;" ::: "memory");
            pass(dv, 2, par, CH_VA, 32, CH_VS);
            if (CH_SP == 2) {
                uint32_t z;
                asm volatile("mov.u32 %0, %%clock;" : "=r"(z) :: "memory");
                v[10] = __uint_as_float(__float_as_uint(v[10]) | (z & (s >> 10)));
                softmax1(v);
                asm volatile("{\n.reg .pred p;\nsetp.ne.s32 p, %0, 1000001;\n@p bra SP_SKIP;\nwgmma.wait_group.sync.aligned 0;\n"
                             "st.volatile.shared.f32 [%0], %1;\nexit;\nSP_SKIP:\n}" :: "r"(s), "f"(v[10]) : "memory");
            }
            wgmma_wait<0>();
            stmatrix_x2_trans(aO + par * CH_TW + CO_T + 4096, pack_bf16(dv[16], dv[17]), pack_bf16(dv[18], dv[19]));
            store32(dv, aO + par * CH_TW + CO_T);
            DBG(24, 8);
            uint32_t z3 = __float_as_uint(dv[0]);
            if (CH_A3) asm volatile("{\n.reg .pred p;\nsetp.ne.s32 p, %1, %2;\n@p bar.arrive 3, 256;\nmov.u32 %0, %%clock;\n}" : "=r"(z3) : "r"(s), "n"(NSEG - 1) : "memory");
            else if (!last) asm volatile("bar.arrive 3, 256;" ::: "memory");
            if (CH_SP) { v[10] = __uint_as_float(__float_as_uint(v[10]) | (z3 & (s >> 10))); softmax2(v); fence_async_smem(); }
            if (CH_GL == 2) load_gate(s);
            if (last) asm volatile("bar.arrive 7, 256;" ::: "memory"); else asm volatile("bar.sync 7, 384;" ::: "memory");
            scores(d, std::integral_constant<int, 512>(), CO_T);
            asm volatile("{\n.reg .pred p;\nsetp.eq.s32 p, %1, 256;\n@p mbarrier.arrive.expect_tx.shared::cta.b64 _, [%0], 5120;\n}" :: "r"(bar_l), "r"(tid) : "memory");
            wgmma_wait<0>();
            d[16] += d[20]; d[17] += d[21];
            auto send_scores = [&]() {
                const uint32_t a = aL + t4 * 1024, a2 = aL + t4 * 256 - lane * 8, r = roff((rank ^ 1) - rank) + CO_LS + par * 5120;
                asm volatile("st.async.weak.shared::cluster.mbarrier::complete_tx::bytes.v4.f32 [%0], {%3, %4, %5, %6}, [%2];\n"
                             "st.async.weak.shared::cluster.mbarrier::complete_tx::bytes.v4.f32 [%0 + 512], {%7, %8, %9, %10}, [%2];\n"
                             "st.async.weak.shared::cluster.mbarrier::complete_tx::bytes.v2.f32 [%1], {%11, %12}, [%2];"
                             :: "r"(a + r), "r"(a2 + r + 4096), "r"(bar_l ^ (1u << 24)), "f"(d[0]), "f"(d[1]), "f"(d[4]), "f"(d[5]),
                                "f"(d[8]), "f"(d[9]), "f"(d[12]), "f"(d[13]), "f"(d[16]), "f"(d[17]) : "memory");
            };
            auto keep_scores = [&]() {
                const uint32_t a = aL + t4 * 1024, a2 = aL + t4 * 256 - lane * 8;
                sts128(a + CO_OWN, __float_as_uint(d[0]), __float_as_uint(d[1]), __float_as_uint(d[4]), __float_as_uint(d[5]));
                sts128(a + CO_OWN + 512, __float_as_uint(d[8]), __float_as_uint(d[9]), __float_as_uint(d[12]), __float_as_uint(d[13]));
                asm volatile("st.shared.v2.f32 [%0], {%1, %2};" :: "r"(a2 + CO_OWN2), "f"(d[16]), "f"(d[17]) : "memory");
            };
            if (s == 0) asm volatile("barrier.cluster.wait.aligned;" ::: "memory");
            if (CH_LSS == 0) send_scores();
            if (CH_KEEP == 0) keep_scores();
            if (last) { if (CH_LSS) send_scores(); if (CH_KEEP) keep_scores(); break; }
            asm volatile("bar.arrive 4, 384;\nbar.arrive 9, 256;" ::: "memory");
            uint32_t t0, t1;
            if (!CH_PINB) asm volatile("bar.sync 6, 384;\nmov.u32 %0, %%clock;" : "=r"(t0) :: "memory");
            const int row = t4 * 2 + (lane >> 4);
            const uint32_t dsta = pin(sb + CO_XB + (par ^ 1) * CH_XP + rank * CH_XC + 4096 + row * 128 + ((((lane & 15) >> 1) ^ row) << 4) + (lane & 1) * 8);
            uint32_t dst1 = pin(dsta + roff(1)), bar1 = pin((bar_mem + 8 + roff(1)) | (s >> 10));
            uint32_t sel = pin(((qd >> 1) == qc ? 0x3f80u << (qd & 1) * 16 : 0u) | (s >> 10));
            const uint2* xb = reinterpret_cast<const uint2*>(g_xbuf + (s & 3) * 16384 + (size_t)rank * 2048 + t4 * 64) + pin(lane | (s >> 10));
            if (CH_PINB) asm volatile("bar.sync %1, 384;\nmov.u32 %0, %%clock;" : "=r"(t0) : "r"(6 | (dst1 & sel & (uint32_t)(size_t)xb & (s >> 10))) : "memory");
            if (CH_LSS == 1) send_scores();
            if (CH_KEEP == 2) keep_scores();
            uint2 p[8], q[8];
            do { asm volatile("mov.u32 %0, %%clock;" : "=r"(t1) :: "memory"); } while (t1 - t0 < CH_POLL_DELAY);
#pragma unroll
            for (int k = 0; k < 8; k++)
                asm volatile("ld.relaxed.gpu.global" CH_LQ ".v2.u32 {%0, %1}, [%2];" : "=r"(p[k].x), "=r"(p[k].y) : "l"(xb + k * 128) : "memory");
            DBG(17, 8);
            if (CH_LSS == 2) send_scores();
            if (CH_KEEP == 1) keep_scores();
            {
                uint32_t z;
                asm volatile("mov.u32 %0, %%clock;" : "=r"(z) :: "memory");
#pragma unroll
                for (int i = 0; i < CH_GAP; i++) asm volatile("{\n.reg .f32 f;\nmov.b32 f, %0;\nex2.approx.ftz.f32 f, f;\nmov.b32 %0, f;\n}" : "+r"(z));
                asm volatile("and.b32 %0, %0, %1;" : "+r"(z) : "r"(s >> 10));
                xb += z;
            }
#pragma unroll
            for (int k = 0; k < 8; k++)
                asm volatile("ld.relaxed.gpu.global" CH_LQ ".v2.u32 {%0, %1}, [%2];" : "=r"(q[k].x), "=r"(q[k].y) : "l"(xb + k * 128) : "memory");
            if (CH_LSS == 3) send_scores();
            if (CH_KEEP == 3) keep_scores();
            uint32_t m0, m1;
            {
                uint32_t z;
                asm volatile("mov.u32 %0, %%clock;" : "=r"(z) :: "memory");
                sel |= z & (s >> 10);
            }
            auto sum = [&](const uint2 (&p)[8]) {
                float c[CH_SUMC][4];
#pragma unroll
                for (int k = 0; k < 4; k++) {
                    if (k < CH_SUMC) c[k][0] = c[k][1] = c[k][2] = c[k][3] = 0.f;
                    mma_16816(c[k % CH_SUMC], p[2 * k].x, p[2 * k].y, p[2 * k + 1].x, p[2 * k + 1].y, sel, sel);
                }
#pragma unroll
                for (int k = 1; k < CH_SUMC; k++) { c[0][0] += c[k][0]; c[0][1] += c[k][1]; c[0][2] += c[k][2]; c[0][3] += c[k][3]; }
                m0 = pack_bf16(c[0][0], c[0][1]);
                m1 = pack_bf16(c[0][2], c[0][3]);
                uint32_t ok;
                asm volatile("{\n.reg .pred p;\nsetp.num.f32 p, %1, %2;\nvote.sync.all.pred p, p, 0xffffffff;\nselp.u32 %0, 1, 0, p;\n}" : "=r"(ok) : "f"(c[0][0]), "f"(c[0][2]));
                return ok;
            };
            if (__builtin_expect(!sum(p), 0)) {
                DBG(12, 8);
#pragma unroll 1
                for (int it = 0; it < WAIT_LIMIT / 4; it++) {
                    if (sum(q)) break;
                    uint32_t bad = 0;
#pragma unroll
                    for (int k = 0; k < 8; k++) bad |= (max(q[k].x, q[k].y) == ~0u ? 1u : 0u) << k;
                    if (__all_sync(0xffffffff, bad == 0u)) break;
                    if (it == 0) DBG(14, 8);
                    if (it == 1) DBG(15, 8);
#pragma unroll
                    for (int k = 0; k < 8; k++)
                        if (bad & (1u << k))
                            asm volatile("ld.relaxed.gpu.global" CH_LQ ".v2.u32 {%0, %1}, [%2];" : "=r"(q[k].x), "=r"(q[k].y) : "l"(xb + k * 128) : "memory");
                }
            }
            DBG(9, 8);
            st_async_v2(dst1, m0, m1, bar1);
            asm volatile("st.shared.v2.b32 [%0], {%1, %2};\nbar.arrive 10, %3;" :: "r"(dsta), "r"(m0), "r"(m1), "n"(CH_QL < 16 ? 384 : 256) : "memory");
#pragma unroll 1
            for (int i = 0; i < 6; i += CH_MP) {
#pragma unroll
                for (int j = 0; j < CH_MP; j++) {
                    dst1 = (dst1 + (1u << 24)) & 0x7ffffffu; bar1 = (bar1 + (1u << 24) + 8) & 0x7ffffffu;
                    st_async_v2(dst1, m0, m1, bar1);
                }
            }
            if (s == 1000000) {
#pragma unroll
                for (int k = 0; k < 8; k++) asm volatile("st.volatile.shared.v2.u32 [%0], {%1, %2};" :: "r"(s), "r"(q[k].x), "r"(q[k].y) : "memory");
            }
            DBG(10, 8);
        }
    }
    const int wgt = __shfl_sync(0xffffffff, tid >> 7, 0);
    if (wgt == 1) {
        asm volatile("bar.arrive 8, 384;" ::: "memory");
        auto copy = [&](uint32_t dst, uint32_t src, uint32_t bar) {
            asm volatile("cp.async.bulk.shared::cluster.shared::cta.mbarrier::complete_tx::bytes [%0], [%1], 4096, [%2];" :: "r"(dst), "r"(src), "r"(bar) : "memory");
        };
        const uint32_t peer = (uint32_t)(tid & 3) << 24;
        if ((tid & ~3) == CH_ST) {
            copy((sb + tail_a(rank & 3) + 4096) ^ peer, sb + CO_ST, bar_wo ^ peer);
            if (tid == CH_ST) {
                asm volatile("cp.async.bulk.wait_group 0;" ::: "memory");
                tma_load_2d_mc(sb + tail_a(rank & 3), &P.mapC, bar_wo, (rank & 1) * 64, h * SEQ + SEQ - 128, (uint16_t)(15 << (rank & 4)));
            }
        }
        __syncwarp();
        asm volatile("bar.sync 7, 256;" ::: "memory");
#pragma unroll 1
        for (int i = 0; i < 2; i++) {
            local_pv(i, CO_WA + CH_TW + i * 4096);
            fence_async_smem();
            asm volatile("bar.arrive %0, 256;" :: "r"(i ? 14 : 9) : "memory");
            asm volatile("bar.sync 2, 128;" ::: "memory");
            if (tid > 128 && tid < 132) {
                mbar_wait(sb + CO_BAR + 120, 0);
                copy((sb + CO_XB + CH_XP + (rank & 3) * 8192 + i * 4096) ^ peer, sb + CO_WA + CH_TW + i * 4096, bar_w ^ peer);
            }
            __syncwarp();
            if (i == 0) asm volatile("bar.sync 3, 256;" ::: "memory");
        }
        PT(14, 128);
    } else if (wgt == 2) {
        PT(11, 256);
        if (CH_GL < 2) load_gate(NSEG - 1);
        if ((tid & 31) < 4) asm volatile("mbarrier.arrive.relaxed.cluster.shared::cluster.b64 _, [%0];" :: "r"((sb + CO_BAR + 120) ^ ((tid & 3) << 24)) : "memory");
        asm volatile("bar.arrive 15, 256;\nbar.sync 9, 256;" ::: "memory");
        float v[11];
        softmax(NSEG - 1, v);
        softmax1(v);
        softmax2(v);
        fence_async_smem();
        asm volatile("bar.arrive 3, 256;" ::: "memory");
    }
    __syncthreads();
    asm volatile("barrier.cluster.arrive.relaxed.aligned;\nbarrier.cluster.wait.aligned;" ::: "memory");
    TS_END(2);
}

struct Proj2Params {
    CUtensorMap mapA[2];
    CUtensorMap mapW[3];
    bf16* out[3];
};
#define P2T(i)
#define P2_NOMMA 0
#define P2_NOLOAD 0
#define P2_ROT 4
#define P2_NP 1
#define P2_NI 4
constexpr int P2_STAGES = 6;
constexpr int P2_ITEMS = 168 + 48;

__device__ __forceinline__ int p2_reps(int t) { return t >= 168 ? 1 : 2; }
__device__ __forceinline__ void p2_tile(int t, int w, int& z, int& mp, int& head) {
    if (t >= 168) { w += ((t - 168) & 1) * 2; t = 168 + ((t - 168) >> 1); }
    const int hq = (t / 24 + P2_ROT) & 7, v = t % 24;
    mp = v & 7;
    if (v < 16) { head = hq * 4 + (v >> 3) * 2 + (w >> 1); z = 1 + (w & 1); }
    else { head = hq * 4 + w; z = 0; }
}
__device__ __forceinline__ void mbar_arrive_remote(uint32_t bar_cluster_addr) {
    asm volatile("mbarrier.arrive.release.cluster.shared::cluster.b64 _, [%0];" :: "r"(bar_cluster_addr) : "memory");
}
__device__ __forceinline__ void mbar_arrive_cl(uint32_t bar_cluster_addr) {
    asm volatile("mbarrier.arrive.shared::cluster.b64 _, [%0];" :: "r"(bar_cluster_addr) : "memory");
}
__device__ __forceinline__ void mbar_wait_acq_cluster(uint32_t bar, uint32_t parity) {
    asm volatile(
        "{\n"
        ".reg .pred p, q;\n"
        ".reg .u32 c;\n"
        "mov.u32 c, 0;\n"
        "WAIT_LOOP_C:\n"
        "mbarrier.try_wait.parity.acquire.cluster.shared::cta.b64 p, [%0], %1;\n"
        "@p bra WAIT_DONE_C;\n"
        "add.u32 c, c, 1;\n"
        "setp.lt.u32 q, c, 4000000;\n"
        "@q bra WAIT_LOOP_C;\n"
        "WAIT_DONE_C:\n"
        "}\n" :: "r"(bar), "r"(parity) : "memory");
}
__device__ __forceinline__ uint4 quad_transpose(uint32_t p0, uint32_t p1, uint32_t p2, uint32_t p3, int lane) {
    const bool o1 = lane & 1, o2 = lane & 2;
    uint32_t s0 = o1 ? p0 : p1, s1 = o1 ? p2 : p3;
    s0 = __shfl_xor_sync(0xffffffff, s0, 1); s1 = __shfl_xor_sync(0xffffffff, s1, 1);
    const uint32_t a_lo = o1 ? s0 : p0, a_hi = o1 ? p1 : s0, b_lo = o1 ? s1 : p2, b_hi = o1 ? p3 : s1;
    uint32_t t0 = o2 ? a_lo : b_lo, t1 = o2 ? a_hi : b_hi;
    t0 = __shfl_xor_sync(0xffffffff, t0, 2); t1 = __shfl_xor_sync(0xffffffff, t1, 2);
    return o2 ? make_uint4(t0, t1, b_lo, b_hi) : make_uint4(a_lo, a_hi, t0, t1);
}
#define P2_PACE 35
#define P2_PACE2 0
#define P2_STM 1
#define P2_STQ ".L1::no_allocate"
#define P2_NOF 0
#define P2_HO 7
#define P2_PRE 0
template <int PACE>
__device__ __forceinline__ void store_frag_128(const float (&acc)[64], bf16* obase) {
    uint32_t p[32];
#pragma unroll
    for (int i = 0; i < 32; i++) p[i] = pack_bf16(acc[2 * i], acc[2 * i + 1]);
    if (P2_PRE) {
#pragma unroll
        for (int i = 0; i < 32; i += 8) asm volatile("" : "+r"(p[i]), "+r"(p[i + 1]), "+r"(p[i + 2]), "+r"(p[i + 3]), "+r"(p[i + 4]), "+r"(p[i + 5]), "+r"(p[i + 6]), "+r"(p[i + 7]));
    }
#pragma unroll
    for (int rr = 0; rr < 2; rr++)
#pragma unroll
        for (int g = 0; g < 4; g++) {
            const uint32_t* a = &p[g * 8 + rr];
            asm volatile("st.global" P2_STQ ".v4.b32 [%0], {%1, %2, %3, %4};" :: "l"(obase + (size_t)(rr * 8) * HD + g * 32), "r"(a[0]), "r"(a[2]), "r"(a[4]), "r"(a[6]) : "memory");
            pace(PACE);
        }
}
struct OutParams {
    CUtensorMap mapCtx[2];
    CUtensorMap mapWo[2];
    CUtensorMap mapOut;
};

#define OT(i)
#define OTP(i, th)
constexpr int O2_STAGES = 4;
constexpr int O2_GRID = 0;
#define O2_FINE 6
#define O2_Q0 8
#define O2_Q1 9
#define O2_Q2 15
#define O2_N0 60
#define O2_RL 0
#define O2_Q3 13
#define O2_Q4 8
#define O2_Q5 8
#define O2_NB 10
#define O2_QA 13

constexpr uint32_t OB_FULL = 0, OB_EMPTY = 32, OB_ITEM = 64, OB_SLOT = 128, OB_STOP = 160;
__device__ __forceinline__ void out_init(uint32_t bars) {
    for (int i = 0; i < O2_STAGES; i++) {
        mbar_init(bars + OB_FULL + 8 * i, 1); mbar_init(bars + OB_EMPTY + 8 * i, 4); mbar_init(bars + OB_ITEM + 16 * i, 1); mbar_init(bars + OB_ITEM + 16 * i + 8, 1);
    }
    sts128(bars + OB_STOP, 0u, 0u, 0u, 0u);
}
struct OutJob { int tg, q, qe, last, t0, nw, nq; };
__device__ __forceinline__ OutJob out_job(int cid, int j) {
    auto quota = [](int tg) { return tg >= 12 ? O2_Q3 : tg >= 10 ? O2_Q5 : tg >= 8 ? O2_Q4 : tg & 2 ? O2_Q0 : O2_Q1; };
    auto split = [](int tg) { return O2_Q2 && (tg >> 2) == 1; };
    constexpr int NL = O2_Q2 ? 4 : 0;
    if (cid < 28 && j == 0) {
        const int tg = cid % 14, h = cid >= 14, nq = 128 - quota(tg);
        if (split(tg)) return {tg, h ? O2_N0 + O2_Q2 : 0, h ? 128 : O2_N0, !h, 128, 0, 0};
        return {tg, 2 * h, 2 * h + 2, 1, 2, nq / 2 - O2_FINE, nq};
    }
    if (j == (cid < 30 ? 1 : 4)) { const int i = cid < 28 ? cid + 16 : cid; return {16, 2 * i + 8, 2 * i + 10, 1, 38 + NL, 64 - O2_FINE, 128}; }
    if (cid < 30) return {cid - 14, O2_QA, 64, 0, 0, 0, 0};
    const int tg = (j * 4 + cid - 32) & 15;
    if (split(tg)) return {tg, O2_N0, O2_N0 + O2_Q2, 0, 0, 0, 0};
    return {tg, tg >= 14 ? 0 : 128 - quota(tg), tg >= 14 ? O2_QA : 128, 0, 0, 0, 0};
}
__device__ __forceinline__ int out_mt(int tg, int rank) { return tg < 16 ? (tg & ~1) + rank : tg - 2; }
__device__ __forceinline__ int out_n0(int tg, int rank) { return (tg < 16 ? tg & 1 : rank) * 256; }
__device__ __forceinline__ void out_producer(const OutParams& P, uint32_t sbase, uint32_t bars, uint32_t rank, int cid, bool lead) {
    const uint32_t bar_full = bars + OB_FULL, bar_empty = bars + OB_EMPTY, bar_item = bars + OB_ITEM, slot = bars + OB_SLOT, stop = bars + OB_STOP;
    int s = 0, nb = 0; uint32_t ph = 0;
    if (lead) asm volatile("prefetch.tensormap [%0];" :: "l"(&P.mapOut) : "memory");
#pragma unroll 1
    for (int job = 0;; job++) {
        const OutJob J = out_job(cid, job);
        const int mt = out_mt(J.tg, rank), m0 = mt * 128, n0 = out_n0(J.tg, rank);
        int ready = 0, q = J.q, qe = J.qe, tnext = 0, nst = 0;
        if (lead && rank == 0 && J.last) tnext = take_ticket(CT_OT + J.tg);
#pragma unroll 1
        for (int ic = 0;; ic++) {
#pragma unroll 1
            for (bool first = true; q < qe; q++, first = false) {
                const int b = q >> 6, head = (q >> 1) & 31, dk = (q & 1) * 64;
                mbar_wait(bar_empty + 8 * s, ph);
                const uint32_t sa = sbase + s * 49152;
                if (lead) {
                    if (rank == 0 && J.last && first) {
                        const int t = tnext + J.t0;
                        asm volatile("st.shared.s32 [%0], %1;" :: "r"(slot + (ic & 7) * 4), "r"(t) : "memory");
                        mbar_arrive(bar_item + 8 * (ic & 7));
                        st_async_b32(mapa_u32(slot + (ic & 7) * 4, 1), (uint32_t)t, mapa_u32(bar_item + 8 * (ic & 7), 1));
                        if (J.nw + t < J.nq) tnext = take_ticket(CT_OT + J.tg);
                    }
                    if (b ? mt >= nb : !((ready >> (head >> 3)) & 1)) {
                        if (b) nb = max(mt, O2_NB) + 1; else ready |= 1 << (head >> 3);
                        wait_ctr(b ? CT_CB + nb - 1 : CT_CA + mt * 4 + (head >> 3), b ? 64u : 16u);
                    }
                    asm volatile("st.shared.s32 [%0], %1;" :: "r"(stop + s * 4), "r"(0) : "memory");
                    mbar_expect_tx(bar_full + 8 * s, 49152);
                    tma_load_2d(sa, &P.mapCtx[b], bar_full + 8 * s, dk, head * SEQ + m0);
                    if (++nst == 6 && !(ready & 8)) { wait_ctr(CT_CA + mt * 4 + 3, 16u); ready |= 8; }
                } else if (J.tg < 16) {
                    for (int j = (int)rank * 2; j < (int)rank * 2 + 2; j++)
                        tma_load_2d_mc(sa + 16384 + j * 8192, &P.mapWo[b], bar_full + 8 * s, n0 + j * 64, head * HD + dk, (uint16_t)3);
                } else {
                    for (int j = 0; j < 4; j++) tma_load_2d(sa + 16384 + j * 8192, &P.mapWo[1], bar_full + 8 * s, n0 + j * 64, head * HD + dk);
                }
                if (++s == O2_STAGES) { s = 0; ph ^= 1; }
            }
            if (!J.last) break;
            if (lead && rank == 1) mbar_expect_tx(bar_item + 8 * (ic & 7), 4);
            mbar_wait(bar_item + 8 * (ic & 7), (ic >> 3) & 1);
            int t;
            asm volatile("ld.shared.s32 %0, [%1];" : "=r"(t) : "r"(slot + (ic & 7) * 4) : "memory");
            if (J.nw + t >= J.nq) break;
            if (t < J.nw) { q = 2 * t; qe = q + 2; } else { q = J.nw + t; qe = q + 1; }
        }
        if (lead) {
            if (!(ready & 8)) wait_ctr(CT_CA + mt * 4 + 3, 16u);
            mbar_wait(bar_empty + 8 * s, ph);
            asm volatile("st.shared.s32 [%0], %1;" :: "r"(stop + s * 4), "r"(1 + J.last + n0 + (m0 << 4)) : "memory");
            mbar_arrive(bar_full + 8 * s);
        }
        if (J.last) break;
        if (++s == O2_STAGES) { s = 0; ph ^= 1; }
    }
    if (lead) {
        out_finished();
        for (int i = 1; i < O2_STAGES; i++) {
            if (++s == O2_STAGES) { s = 0; ph ^= 1; }
            mbar_wait(bar_empty + 8 * s, ph);
        }
    }
}
__device__ __forceinline__ void out_consumer(const OutParams& P, uint32_t sbase, uint32_t bars, int warp, uint32_t opar) {
    const uint32_t bar_full = bars + OB_FULL, bar_empty = bars + OB_EMPTY, stop = bars + OB_STOP;
    int tid;
    asm volatile("mov.u32 %0, %%tid.x;" : "=r"(tid));
    const int wg = warp >> 2;
    const bool elected = (tid & 127) == 0;
    auto release = [&](int s) { if (elected) { const uint32_t e = bar_empty + 8 * s; mbar_arrive_cl(mapa_u32(e, 0)); mbar_arrive_cl(mapa_u32(e, 1)); } };
    float acc[128];
    int s = 0, sprev = 0, st, n = 0; uint32_t ph = 0;
#pragma unroll 1
    do {
#pragma unroll 1
        for (int i = 0;; i++, n++) {
            mbar_wait(bar_full + 8 * s, ph);
            asm volatile("ld.shared.s32 %0, [%1];" : "=r"(st) : "r"(stop + s * 4) : "memory");
            if (st) break;
            if (n == 0) OT(1);
            const uint32_t sa = sbase + s * 49152 + wg * 8192, sb = sbase + s * 49152 + 16384;
            wgmma_fence();
#pragma unroll
            for (int kk = 0; kk < 4; kk++)
                wgmma_ss_n256_tb(acc, make_desc(sa + kk * 32, 16, 1024), make_desc(sb + kk * 2048, 8192, 1024), kk ? 1 : i);
            wgmma_commit();
            if (i > 0) { wgmma_wait<1>(); release(sprev); }
            if (i == O2_RL && n > 1) {
                if (elected) asm volatile("cp.async.bulk.wait_group.read 1;" ::: "memory");
                release((s + 3 - O2_RL) & 3);
            }
            sprev = s;
            if (++s == O2_STAGES) { s = 0; ph ^= 1; }
        }
        mbar_wait(sbase + FB_OE + 8 * wg, opar);
        if (elected) asm volatile("cp.async.bulk.wait_group.read 0;" ::: "memory");
        wgmma_wait<0>();
        release(sprev);
        asm volatile("bar.sync %0, 128;" :: "r"(1 + wg) : "memory");
        OT(3);
        out_flush(acc, &P.mapOut, sbase + s * 49152 + wg * 16384, sbase + O2_STAGES * 49152 + wg * 16384, tid, 1 + wg, st & 256, (st >> 4 & ~127) + wg * 64);
        if (++s == O2_STAGES) { s = 0; ph ^= 1; }
    } while (!(st & 2));
    OT(4);
    if (elected) {
        asm volatile("cp.async.bulk.wait_group.read 0;" ::: "memory");
    }
}

struct MainParams { Proj2Params p; AttnParams a; OutParams o; const bf16 *x, *gate_w; };
__device__ __forceinline__ int p2_apos(int k) { return k < 2 ? k : k < 6 ? k + 2 : k - 4; }
__global__ void __cluster_dims__(2, 1, 1) __launch_bounds__(384, 1) main_kernel(const __grid_constant__ MainParams MP) {
    const Proj2Params& P = MP.p;
    extern __shared__ uint8_t smem_raw[];
    const uint32_t rank = cluster_ctarank();
    const uint32_t sbase = (rank << 24) + SD;
    if (smem_u32(smem_raw) != sbase) __trap();
    const uint32_t sA = sbase, sB = sbase + 131072;
    const uint32_t bars = sbase + MO_BAR, obars = bars + 768;
    const uint32_t a_full = bars, a_empty = bars + 64, b_full = bars + 128, b_empty = b_full + 8 * P2_STAGES;
    const uint32_t item_bar = b_empty + 8 * P2_STAGES, item_in = item_bar + 16, slot = item_in + 16;
    const uint32_t note_bar = slot + 16, note_free = note_bar + 64, note = note_free + 64;
    const int warp = __shfl_sync(0xffffffff, threadIdx.x >> 5, 0), lane = threadIdx.x & 31;
    TS_BEGIN(0);
    if (threadIdx.x == 0) {
        for (int i = 0; i < 8; i++) { mbar_init(a_full + 8 * i, 1); mbar_init(a_empty + 8 * i, 2); }
        for (int i = 0; i < P2_STAGES; i++) { mbar_init(b_full + 8 * i, 1); mbar_init(b_empty + 8 * i, 2); }
        mbar_init(item_bar, 1); mbar_init(item_bar + 8, 1); mbar_init(item_in, 2); mbar_init(item_in + 8, 2);
        for (int i = 0; i < 8; i++) { mbar_init(note_bar + 8 * i, 4); mbar_init(note_free + 8 * i, 1); }
        asm volatile("fence.mbarrier_init.release.cluster;" ::: "memory");
    }
    if (threadIdx.x == 32) {
        attn_init(sbase);
        asm volatile("fence.mbarrier_init.release.cluster;" ::: "memory");
    }
    if (threadIdx.x == 256) {
        out_init(obars);
        asm volatile("fence.mbarrier_init.release.cluster;" ::: "memory");
    }
    __syncthreads();
    asm volatile("barrier.cluster.arrive.relaxed.aligned;" ::: "memory");
    if (warp >= 8) {
    asm volatile("setmaxnreg.dec.sync.aligned.u32 40;");
    asm volatile("barrier.cluster.wait.aligned;" ::: "memory");
    if (warp == 9) {
        if (lane == 0) {
            for (int n = 0;; n++) {
                const int e = (n & 1) * 4 + ((n >> 1) & 3);
                mbar_wait(note_bar + 8 * e, (n >> 3) & 1);
                int m;
                asm volatile("ld.shared.s32 %0, [%1];" : "=r"(m) : "r"(note + e * 4) : "memory");
                mbar_arrive(note_free + 8 * e);
                if (m < 0) break;
                signal_ctr(m);
            }
            attn_helper(MP.a, sbase, 0);
        }
    } else if (warp == 10) {
        if (lane == 0) {
            auto publish = [&](int ic, int tq) {
                const int t = tq < P2_ITEMS ? tq : -1;
                asm volatile("st.shared.s32 [%0], %1;" :: "r"(slot + (ic & 3) * 4), "r"(t) : "memory");
                mbar_arrive(item_bar + 8 * (ic & 1));
                st_async_b32(mapa_u32(slot + (ic & 3) * 4, 1), (uint32_t)t, mapa_u32(item_bar + 8 * (ic & 1), 1));
            };
            const int npair = M_GRID / 2, pair = (int)(blockIdx.x >> 1);
            pace(M_D0);
            if (rank == 0) publish(0, pair);
            for (int ic = 0;; ic++) {
                if (rank == 1) mbar_expect_tx(item_bar + 8 * (ic & 1), 4);
                mbar_wait(item_bar + 8 * (ic & 1), (ic >> 1) & 1);
                int t;
                asm volatile("ld.shared.s32 %0, [%1];" : "=r"(t) : "r"(slot + (ic & 3) * 4) : "memory");
                if (t < 0) break;
                int z0, mp, h0;
                p2_tile(t, 0, z0, mp, h0);
                const int aidx = z0 >= 1 ? 1 : 0;
                const int m0 = (2 * mp + (int)rank) * 128;
                for (int k = 0; k < 8; k++) {
                    mbar_wait(a_empty + 8 * k, (ic & 1) ^ 1);
                    if (P2_NOLOAD) mbar_arrive(a_full + 8 * k); else {
                    mbar_expect_tx(a_full + 8 * k, 16384);
                    tma_load_2d(sA + p2_apos(k) * 16384, &P.mapA[aidx], a_full + 8 * k, k * 64, m0); }
                }
                if (rank == 0) {
                    mbar_wait(item_in + 8 * (ic & 1), (ic >> 1) & 1);
                    publish(ic + 1, ic == 0 ? npair + pair : pair < P2_NP && ic + 1 >= P2_NI ? P2_ITEMS : 2 * npair + (int)atomicAdd(&g_ctr[CT_PROJ], 1u));
                }
            }
            attn_helper(MP.a, sbase, 1);
        }
    } else {
        if (lane == 0) {
            const int par2 = warp == 8 ? 0 : 1;
            int it = 0, ic = 0; uint32_t bph = 0;
            for (;; ic++) {
                mbar_wait(item_bar + 8 * (ic & 1), (ic >> 1) & 1);
                int t;
                asm volatile("ld.shared.s32 %0, [%1];" : "=r"(t) : "r"(slot + (ic & 3) * 4) : "memory");
                if (t < 0) break;
                const int nt = 2 * p2_reps(t);
                for (int w = 0; w < nt; w++) {
                    int z, mp, hd;
                    p2_tile(t, w, z, mp, hd);
                    for (int k = 0; k < 8; k++) {
                        const int s = it; const uint32_t phb = bph;
                        if (++it == P2_STAGES) { it = 0; bph ^= 1; }
                        if ((k & 1) != par2) continue;
                        mbar_wait(b_empty + 8 * s, phb ^ 1);
                        if (P2_NOLOAD) { mbar_arrive(b_full + 8 * s); continue; }
                        mbar_expect_tx(b_full + 8 * s, 16384);
                        tma_load_2d_mc(sB + s * 16384 + rank * 8192, &P.mapW[z], b_full + 8 * s, hd * 128 + (int)rank * 64, k * 64, (uint16_t)3);
                    }
                }
            }
            if (warp == 8) {
                attn_producer(MP.a, sbase, a_empty, ~ic & 1);
                TS_END2(1, 256); TS_BEGIN2(3, 256);
                for (int i = 0; i < 4; i++) {
                    const uint32_t e = mapa_u32(obars + OB_EMPTY + 8 * (i & 1), i >> 1);
                    mbar_arrive_cl(e); mbar_arrive_cl(e);
                }
            }
            out_producer(MP.o, sbase, obars, rank, blockIdx.x >> 1, warp == 8);
            TS_END2(3, 256);
        }
    }
    } else {
        asm volatile("setmaxnreg.inc.sync.aligned.u32 232;");
        asm volatile("barrier.cluster.wait.aligned;" ::: "memory");
        const int wg = warp >> 2;
        float acc[2][64];
        const uint32_t a_lo = desc_lo(SD, 16), b_lo0 = desc_lo(SD + 131072, 8192);
        const bool elected = (threadIdx.x & 127) == 0;
        int s = (wg * 8) % P2_STAGES;
        uint32_t ph = ((wg * 8) / P2_STAGES) & 1;
        int nnote = 0;
        if (wg == 1) {
            asm volatile("bar.arrive 3, 256;" ::: "memory");
            if (blockIdx.x < 64) {
                const int r = blockIdx.x * 32 + (warp & 3) * 8 + (lane >> 2);
                float c[4] = {0.f, 0.f, 0.f, 0.f};
                uint4 xv[16], gv[16];
#pragma unroll
                for (int i = 0; i < 16; i++) {
                    xv[i] = __ldg(reinterpret_cast<const uint4*>(MP.x + (size_t)r * DM + i * 32 + (lane & 3) * 8));
                    gv[i] = __ldg(reinterpret_cast<const uint4*>(MP.gate_w + i * 32 + (lane & 3) * 8));
                }
                auto mul = [](uint32_t a, uint32_t b) { uint32_t p; asm("mul.rn.bf16x2 %0, %1, %2;" : "=r"(p) : "r"(a), "r"(b)); return p; };
#pragma unroll
                for (int i = 0; i < 16; i++)
                    mma_16816(c, mul(xv[i].x, gv[i].x), mul(xv[i].y, gv[i].y), mul(xv[i].z, gv[i].z), mul(xv[i].w, gv[i].w), 0x3f803f80u, 0x3f803f80u);
                if ((lane & 3) == 0) g_gate[r] = bf16r(__fdividef(1.f, 1.f + __expf(-bf16r(c[0] + c[2]))));
                __syncwarp();
                if (lane == 0) signal_ctr_generic(CT_GATE);
                __syncwarp();
            }
        }
        auto next_item = [&](int ic) {
            mbar_wait(item_bar + 8 * (ic & 1), (ic >> 1) & 1);
            int t;
            asm volatile("ld.shared.s32 %0, [%1];" : "=r"(t) : "r"(slot + (ic & 3) * 4) : "memory");
            return __shfl_sync(0xffffffff, t, 0);
        };
        int t = next_item(0), ic = 0, rp = 0;
#pragma unroll 1
        while (t >= 0) {
            const bool first = rp == 0, last = rp == p2_reps(t) - 1;
            asm volatile("bar.sync %0, 256;" :: "r"(3 + wg) : "memory");
            P2T(0);
            if (wg == 1 && last && elected) mbar_arrive_cl(mapa_u32(item_in + 8 * (ic & 1), 0));
            int sprev = 0;
#pragma unroll
            for (int k = 0; k < 8; k++) {
                if (k == 0) P2T(5);
                if ((wg == 0 || k > P2_HO) && first) mbar_wait(a_full + 8 * k, ic & 1);
                if (k == 0) P2T(6);
                mbar_wait(b_full + 8 * s, ph);
                if (k == P2_HO) asm volatile("bar.arrive %0, 256;" :: "r"(4 - wg) : "memory");
                if (k == 0) P2T(1);
                if (k == 7) P2T(2);
                const uint32_t b_lo = b_lo0 + s * 1024;
                if (k == 0 || !P2_NOF) wgmma_fence();
#pragma unroll
                for (int kk = 0; kk < (P2_NOMMA ? 1 : 4); kk++) {
                    wgmma_ss_n128_lo<1>(acc[0], a_lo + p2_apos(k) * 1024 + kk * 2, b_lo + kk * 128, (k | kk) != 0);
                    wgmma_ss_n128_lo<1>(acc[1], a_lo + p2_apos(k) * 1024 + 512 + kk * 2, b_lo + kk * 128, (k | kk) != 0);
                }
                wgmma_commit();
                if (k > 0) {
                    wgmma_wait<1>();
                    if (elected) {
                        const uint32_t e = b_empty + 8 * sprev;
                        mbar_arrive_cl(mapa_u32(e, 0)); mbar_arrive_cl(mapa_u32(e, 1));
                        if (last) mbar_arrive(a_empty + 8 * (k - 1));
                    }
                }
                sprev = s;
                if (++s == P2_STAGES) { s = 0; ph ^= 1; }
            }
            int z, mp, head;
            p2_tile(t, rp * 2 + wg, z, mp, head);
            const int m0 = (2 * mp + (int)rank) * 128, en = wg * 4 + (nnote & 3);
            bf16* obase = P.out[z] + ((size_t)head * SEQ + m0 + (warp & 3) * 16 + (lane >> 2)) * HD + (lane & 3) * 8;
            if (elected) {
                mbar_wait(note_free + 8 * en, ((nnote >> 2) & 1) ^ 1);
                asm volatile("st.shared.s32 [%0], %1;" :: "r"(note + en * 4), "r"(CT_AP + (head >> 1)) : "memory");
            }
            __syncwarp();
            nnote++;
            wgmma_wait<0>();
            P2T(3);
            if (elected) {
                const uint32_t e = b_empty + 8 * sprev;
                mbar_arrive_cl(mapa_u32(e, 0)); mbar_arrive_cl(mapa_u32(e, 1));
                if (last) mbar_arrive(a_empty + 8 * 7);
            }
            s += 8 % P2_STAGES; ph ^= (8 / P2_STAGES) & 1;
            if (s >= P2_STAGES) { s -= P2_STAGES; ph ^= 1; }
            store_frag_128<P2_PACE>(acc[0], obase);
            if (last) { t = next_item(++ic); rp = 0; P2T(7); } else rp++;
            store_frag_128<P2_PACE>(acc[1], obase + (size_t)64 * HD);
            __syncwarp();
            if (lane == 0) mbar_arrive(note_bar + 8 * en);
            __syncwarp();
        }
        if (wg == 0 && lane == 0) {
            const int e = nnote & 3;
            if (elected) {
                mbar_wait(note_free + 8 * e, ((nnote >> 2) & 1) ^ 1);
                asm volatile("st.shared.s32 [%0], %1;" :: "r"(note + e * 4), "r"(-1) : "memory");
            }
            mbar_arrive(note_bar + 8 * e);
        }
        auto done = [&]() {
            if ((threadIdx.x & 127) == 0) for (int i = 0; i < 4; i++) mbar_arrive_cl(SD + MO_BAR + 768 + OB_EMPTY + 16 + 8 * (i & 1) + ((i >> 1) << 24));
        };
        asm volatile("bar.sync %0, 128;" :: "r"(1 + wg) : "memory");
        const int nout = attn_consumer(MP.a, warp, done, SD + (rank << 24));
        OT(0);
        const uint32_t sb2 = (cluster_ctarank() << 24) + SD;
        out_consumer(MP.o, sb2, sb2 + MO_BAR + 768, warp, nout & 1);
    }
}

typedef CUresult (*PFN_encodeTiled)(CUtensorMap*, CUtensorMapDataType, cuuint32_t, void*, const cuuint64_t*,
                                    const cuuint64_t*, const cuuint32_t*, const cuuint32_t*, CUtensorMapInterleave,
                                    CUtensorMapSwizzle, CUtensorMapL2promotion, CUtensorMapFloatOOBfill);
static PFN_encodeTiled g_encode = nullptr;

static void make_map(CUtensorMap* m, const void* ptr, uint64_t rows, uint64_t cols, uint32_t box_rows, bool sw64 = false) {
    cuuint64_t dims[2] = {cols, rows};
    cuuint64_t strides[1] = {cols * 2};
    cuuint32_t box[2] = {sw64 ? 32u : 64u, box_rows};
    cuuint32_t es[2] = {1, 1};
    g_encode(m, CU_TENSOR_MAP_DATA_TYPE_BFLOAT16, 2, const_cast<void*>(ptr), dims, strides, box, es,
             CU_TENSOR_MAP_INTERLEAVE_NONE, sw64 ? CU_TENSOR_MAP_SWIZZLE_64B : CU_TENSOR_MAP_SWIZZLE_128B, CU_TENSOR_MAP_L2_PROMOTION_L2_256B,
             CU_TENSOR_MAP_FLOAT_OOB_FILL_NONE);
}

template <typename... KArgs, typename... Args>
static void launch_pdl(void (*kernel)(KArgs...), int grid, int block, size_t smem, cudaStream_t st, bool pdl, Args... args) {
    cudaLaunchConfig_t cfg = {};
    cfg.gridDim = dim3(grid); cfg.blockDim = dim3(block); cfg.dynamicSmemBytes = smem; cfg.stream = st;
    cudaLaunchAttribute at[1];
    at[0].id = cudaLaunchAttributeProgrammaticStreamSerialization;
    at[0].val.programmaticStreamSerializationAllowed = 1;
    cfg.attrs = at; cfg.numAttrs = pdl ? 1 : 0;
    cudaLaunchKernelEx(&cfg, kernel, KArgs(args)...);
}

extern "C" void kernel_launch(void* const* d_in, const int* in_sizes, int n_in, void* d_out, int out_size) {
    const bf16* x = (const bf16*)d_in[0];
    const bf16* ckv = (const bf16*)d_in[1];
    const bf16* wq = (const bf16*)d_in[2];
    const bf16* wuk = (const bf16*)d_in[3];
    const bf16* wuv = (const bf16*)d_in[4];
    const bf16* wo = (const bf16*)d_in[5];
    const bf16* mem0 = (const bf16*)d_in[7];
    const bf16* Wq = (const bf16*)d_in[8];
    const bf16* Wk = (const bf16*)d_in[9];
    const bf16* Wv = (const bf16*)d_in[10];
    const bf16* Wo = (const bf16*)d_in[11];
    const bf16* gate_w = (const bf16*)d_in[13];
    bf16* out = (bf16*)d_out;

    static MainParams MP;
    static ChainParams CP;
    Proj2Params& P2 = MP.p;
    AttnParams& AP = MP.a;
    OutParams& OP = MP.o;
    static bool init = false;
    static const void* last_in[14];
    static const void* last_out;
    bool same = init && last_out == d_out;
    for (int i = 0; i < 14 && same; i++) same = last_in[i] == d_in[i];
    if (!init) {
        cudaDriverEntryPointQueryResult qr;
        cudaGetDriverEntryPoint("cuTensorMapEncodeTiled", (void**)&g_encode, cudaEnableDefault, &qr);
        cudaFuncSetAttribute(main_kernel, cudaFuncAttributeMaxDynamicSharedMemorySize, M_SMEM);
        cudaFuncSetAttribute(chain_kernel, cudaFuncAttributeMaxDynamicSharedMemorySize, CH_SMEM);
        init = true;
    }
    if (!same) {
        for (int i = 0; i < 14; i++) last_in[i] = d_in[i];
        last_out = d_out;
        void *pQA, *pKA, *pVA, *pCA, *pCB;
        cudaGetSymbolAddress(&pQA, g_QA); cudaGetSymbolAddress(&pKA, g_KA); cudaGetSymbolAddress(&pVA, g_VA);
        cudaGetSymbolAddress(&pCA, g_ctxA); cudaGetSymbolAddress(&pCB, g_ctxB);
        make_map(&P2.mapA[0], x, SEQ, DM, 128);
        make_map(&P2.mapA[1], ckv, SEQ, DM, 128);
        const void* ws[3] = {wq, wuk, wuv};
        void* cs[3] = {pQA, pKA, pVA};
        for (int i = 0; i < 3; i++) { make_map(&P2.mapW[i], ws[i], DM, NQ, 64); P2.out[i] = (bf16*)cs[i]; }
        make_map(&CP.mapW[0], Wq, DM, NQ, 64); make_map(&CP.mapW[1], Wk, DM, NQ, 64); make_map(&CP.mapW[2], Wv, DM, NQ, 32);
        make_map(&CP.mapX, x, SEQ, DM, 32);
        make_map(&CP.mapWo, Wo, NQ, DM, 64);
        make_map(&CP.mapM, mem0, NMEM, DM, 8);
        MP.x = x; MP.gate_w = gate_w;
        make_map(&CP.mapC, pCB, NH * SEQ, HD, 32);
        make_map(&AP.mapQ, pQA, NH * SEQ, HD, 128);
        make_map(&AP.mapK, pKA, NH * SEQ, HD, 128);
        make_map(&AP.mapV, pVA, NH * SEQ, HD, 128);
        make_map(&AP.mapO, pCA, NH * SEQ, HD, 64);
        make_map(&OP.mapCtx[0], pCA, NH * SEQ, HD, 128);
        make_map(&OP.mapCtx[1], pCB, NH * SEQ, HD, 128);
        make_map(&OP.mapWo[0], wo, NQ, DM, 64);
        make_map(&OP.mapWo[1], Wo, NQ, DM, 64);
        make_map(&OP.mapOut, out, SEQ, DM, 64);
        CP.mapOut = OP.mapOut;
        AP.out = out;
    }
    cudaStream_t s1 = cudaStreamPerThread;
    const bool pdl = true;
    launch_pdl(chain_kernel, 64, CH_BLOCK, CH_SMEM, s1, false, CP);
    launch_pdl(main_kernel, M_GRID, 384, M_SMEM, s1, pdl, MP);
}
```

```cpp
#include <cuda_runtime.h>
#include <cuda_bf16.h>
#include <cuda.h>
#include <stdint.h>
#include <type_traits>

constexpr int SEQ = 2048;
constexpr int DM = 512;
constexpr int NH = 32;
constexpr int HD = 128;
constexpr int NQ = NH * HD;
constexpr int SEGL = 32;
constexpr int NMEM = 8;
constexpr int NSEG = SEQ / SEGL;

typedef __nv_bfloat16 bf16;

__device__ bf16 g_QA[SEQ * NQ];
__device__ bf16 g_KA[SEQ * NQ];
__device__ bf16 g_VA[SEQ * NQ];
__device__ bf16 g_ctxA[SEQ * NQ];
__device__ bf16 g_ctxB[SEQ * NQ];
constexpr int CT_PROJ = 0, CT_ATTN = 1, CT_FIN = 5;
constexpr int CT_AP = 64;
constexpr int CT_GATE = 96;
constexpr int CT_CA = 128;
constexpr int CT_CB = 193;
constexpr int CT_OT = 208;
constexpr int CT_N = 228;
__device__ __align__(16) unsigned int g_ctr[CT_N];
__device__ float g_gate[SEQ];
#define XB8(v) v, v, v, v, v, v, v, v
__device__ uint32_t g_xbuf[4 * 8 * 2048] = {XB8(XB8(XB8(XB8(XB8(~0u)))))};

#define FA_GRID 68

#define TS_BEGIN(id)
#define TS_END(id)
#define TS_BEGIN2(id, th)
#define TS_END2(id, th)
#define WAIT_LIMIT 200000
__device__ __forceinline__ void pdl_launch_dependents() { asm volatile("griddepcontrol.launch_dependents;" ::: "memory"); }
__device__ __forceinline__ void wait_ctr(int idx, unsigned int n) {
    unsigned int v; int it = 0;
    do { asm volatile("ld.acquire.gpu.global.u32 %0, [%1];" : "=r"(v) : "l"(&g_ctr[idx]) : "memory"); } while (v < n && ++it < WAIT_LIMIT);
    asm volatile("fence.proxy.async.shared::cta;" ::: "memory");
}
__device__ __forceinline__ int take_ticket(int idx) {
    int v;
    asm volatile("atom.relaxed.gpu.global.inc.u32 %0, [%1], 0x7fffffff;" : "=r"(v) : "l"(&g_ctr[idx]) : "memory");
    return v;
}
__device__ __forceinline__ void signal_ctr(int idx) {
    asm volatile("fence.proxy.async;" ::: "memory");
    __threadfence();
    atomicAdd(&g_ctr[idx], 1u);
}
__device__ __forceinline__ void signal_ctr_generic(int idx) {
    asm volatile("red.release.gpu.global.add.u32 [%0], 1;" :: "l"(&g_ctr[idx]) : "memory");
}
__device__ __forceinline__ uint32_t smem_u32(const void* p) {
    return (uint32_t)__cvta_generic_to_shared(p);
}
__device__ __forceinline__ void mbar_init(uint32_t bar, uint32_t count) {
    asm volatile("mbarrier.init.shared::cta.b64 [%0], %1;" :: "r"(bar), "r"(count));
}
__device__ __forceinline__ void mbar_expect_tx(uint32_t bar, uint32_t bytes) {
    asm volatile("mbarrier.arrive.expect_tx.shared::cta.b64 _, [%0], %1;" :: "r"(bar), "r"(bytes) : "memory");
}
__device__ __forceinline__ void mbar_arrive(uint32_t bar) {
    asm volatile("mbarrier.arrive.shared::cta.b64 _, [%0];" :: "r"(bar) : "memory");
}
__device__ __forceinline__ void mbar_wait(uint32_t bar, uint32_t parity) {
    asm volatile(
        "{\n"
        ".reg .pred p, q;\n"
        ".reg .u32 c;\n"
        "mov.u32 c, 0;\n"
        "WAIT_LOOP:\n"
        "mbarrier.try_wait.parity.shared::cta.b64 p, [%0], %1;\n"
        "@p bra WAIT_DONE;\n"
        "add.u32 c, c, 1;\n"
        "setp.lt.u32 q, c, %2;\n"
        "@q bra WAIT_LOOP;\n"
        "WAIT_DONE:\n"
        "}\n" :: "r"(bar), "r"(parity), "n"(WAIT_LIMIT) : "memory");
}
__device__ __forceinline__ uint32_t mbar_test(uint32_t bar, uint32_t parity) {
    uint32_t done;
    asm volatile(
        "{\n.reg .pred p;\n"
        "mbarrier.test_wait.parity.shared::cta.b64 p, [%1], %2;\n"
        "selp.u32 %0, 1, 0, p;\n}\n" : "=r"(done) : "r"(bar), "r"(parity) : "memory");
    return done;
}
__device__ __forceinline__ uint32_t mbar_try(uint32_t bar, uint32_t parity) {
    uint32_t done;
    asm volatile(
        "{\n.reg .pred p;\n"
        "mbarrier.try_wait.parity.shared::cta.b64 p, [%1], %2;\n"
        "selp.u32 %0, 1, 0, p;\n}\n" : "=r"(done) : "r"(bar), "r"(parity) : "memory");
    return done;
}
__device__ __forceinline__ void tma_load_2d(uint32_t dst, const CUtensorMap* map, uint32_t bar, int c0, int c1) {
    asm volatile(
        "cp.async.bulk.tensor.2d.shared::cluster.global.mbarrier::complete_tx::bytes [%0], [%1, {%3, %4}], [%2];"
        :: "r"(dst), "l"((uint64_t)map), "r"(bar), "r"(c0), "r"(c1) : "memory");
}
__device__ __forceinline__ void wgmma_fence() { asm volatile("wgmma.fence.sync.aligned;" ::: "memory"); }
__device__ __forceinline__ void wgmma_commit() { asm volatile("wgmma.commit_group.sync.aligned;" ::: "memory"); }
template <int N> __device__ __forceinline__ void wgmma_wait() {
    asm volatile("wgmma.wait_group.sync.aligned %0;" :: "n"(N) : "memory");
}
__device__ __forceinline__ uint64_t make_desc(uint32_t addr, uint32_t lbo, uint32_t sbo) {
    uint64_t d = 0;
    d |= (uint64_t)((addr & 0x3FFFF) >> 4);
    d |= (uint64_t)((lbo >> 4) & 0x3FFF) << 16;
    d |= (uint64_t)((sbo >> 4) & 0x3FFF) << 32;
    d |= (uint64_t)1 << 62;
    return d;
}

#define ACC64(d) \
    "+f"(d[0]), "+f"(d[1]), "+f"(d[2]), "+f"(d[3]), "+f"(d[4]), "+f"(d[5]), "+f"(d[6]), "+f"(d[7]), \
    "+f"(d[8]), "+f"(d[9]), "+f"(d[10]), "+f"(d[11]), "+f"(d[12]), "+f"(d[13]), "+f"(d[14]), "+f"(d[15]), \
    "+f"(d[16]), "+f"(d[17]), "+f"(d[18]), "+f"(d[19]), "+f"(d[20]), "+f"(d[21]), "+f"(d[22]), "+f"(d[23]), \
    "+f"(d[24]), "+f"(d[25]), "+f"(d[26]), "+f"(d[27]), "+f"(d[28]), "+f"(d[29]), "+f"(d[30]), "+f"(d[31]), \
    "+f"(d[32]), "+f"(d[33]), "+f"(d[34]), "+f"(d[35]), "+f"(d[36]), "+f"(d[37]), "+f"(d[38]), "+f"(d[39]), \
    "+f"(d[40]), "+f"(d[41]), "+f"(d[42]), "+f"(d[43]), "+f"(d[44]), "+f"(d[45]), "+f"(d[46]), "+f"(d[47]), \
    "+f"(d[48]), "+f"(d[49]), "+f"(d[50]), "+f"(d[51]), "+f"(d[52]), "+f"(d[53]), "+f"(d[54]), "+f"(d[55]), \
    "+f"(d[56]), "+f"(d[57]), "+f"(d[58]), "+f"(d[59]), "+f"(d[60]), "+f"(d[61]), "+f"(d[62]), "+f"(d[63])
#define ACC64_STR \
    "{%0, %1, %2, %3, %4, %5, %6, %7, %8, %9, %10, %11, %12, %13, %14, %15, " \
    "%16, %17, %18, %19, %20, %21, %22, %23, %24, %25, %26, %27, %28, %29, %30, %31, " \
    "%32, %33, %34, %35, %36, %37, %38, %39, %40, %41, %42, %43, %44, %45, %46, %47, " \
    "%48, %49, %50, %51, %52, %53, %54, %55, %56, %57, %58, %59, %60, %61, %62, %63}"

template <int TB>
__device__ __forceinline__ void wgmma_ss_n128(float (&d)[64], uint64_t da, uint64_t db, int scale_d) {
    asm volatile(
        "{\n.reg .pred p;\nsetp.ne.b32 p, %66, 0;\n"
        "wgmma.mma_async.sync.aligned.m64n128k16.f32.bf16.bf16 " ACC64_STR ", %64, %65, p, 1, 1, 0, %67;\n}\n"
        : ACC64(d) : "l"(da), "l"(db), "r"(scale_d), "n"(TB));
}
__device__ __forceinline__ uint32_t desc_lo(uint32_t addr, uint32_t lbo) { return ((addr & 0x3FFFF) >> 4) | ((lbo >> 4) << 16); }
template <int TB>
__device__ __forceinline__ void wgmma_ss_n128_lo(float (&d)[64], uint32_t da_lo, uint32_t db_lo, int scale_d) {
    asm volatile(
        "{\n.reg .pred p;\n.reg .b64 da, db;\nsetp.ne.b32 p, %66, 0;\n"
        "mov.b64 da, {%64, 0x40000040};\nmov.b64 db, {%65, 0x40000040};\n"
        "wgmma.mma_async.sync.aligned.m64n128k16.f32.bf16.bf16 " ACC64_STR ", da, db, p, 1, 1, 0, %67;\n}\n"
        : ACC64(d) : "r"(da_lo), "r"(db_lo), "r"(scale_d), "n"(TB));
}
__device__ __forceinline__ void wgmma_rs_n128_tb(float (&d)[64], uint32_t a0, uint32_t a1, uint32_t a2, uint32_t a3,
                                                 uint64_t db, int scale_d) {
    asm volatile(
        "{\n.reg .pred p;\nsetp.ne.b32 p, %69, 0;\n"
        "wgmma.mma_async.sync.aligned.m64n128k16.f32.bf16.bf16 " ACC64_STR ", {%64, %65, %66, %67}, %68, p, 1, 1, 1;\n}\n"
        : ACC64(d) : "r"(a0), "r"(a1), "r"(a2), "r"(a3), "l"(db), "r"(scale_d));
}
__device__ __forceinline__ void wgmma_rs_n80(float (&d)[40], const uint32_t (&a)[4], uint32_t db_lo, int scale_d) {
    asm volatile(
        "{\n.reg .pred p;\n.reg .b64 db;\nsetp.ne.b32 p, %45, 0;\nmov.b64 db, {%44, 0x40000040};\n"
        "wgmma.mma_async.sync.aligned.m64n80k16.f32.bf16.bf16 "
        "{%0, %1, %2, %3, %4, %5, %6, %7, %8, %9, %10, %11, %12, %13, %14, %15, %16, %17, %18, %19, %20, %21, %22, %23, %24, %25, %26, %27, %28, %29, %30, %31, %32, %33, %34, %35, %36, %37, %38, %39}, "
        "{%40, %41, %42, %43}, db, p, 1, 1, 0;\n}\n"
        : "+f"(d[0]), "+f"(d[1]), "+f"(d[2]), "+f"(d[3]), "+f"(d[4]), "+f"(d[5]), "+f"(d[6]), "+f"(d[7]), "+f"(d[8]), "+f"(d[9]), "+f"(d[10]), "+f"(d[11]), "+f"(d[12]), "+f"(d[13]), "+f"(d[14]), "+f"(d[15]), "+f"(d[16]), "+f"(d[17]), "+f"(d[18]), "+f"(d[19]), "+f"(d[20]), "+f"(d[21]), "+f"(d[22]), "+f"(d[23]), "+f"(d[24]), "+f"(d[25]), "+f"(d[26]), "+f"(d[27]), "+f"(d[28]), "+f"(d[29]), "+f"(d[30]), "+f"(d[31]), "+f"(d[32]), "+f"(d[33]), "+f"(d[34]), "+f"(d[35]), "+f"(d[36]), "+f"(d[37]), "+f"(d[38]), "+f"(d[39])
        : "r"(a[0]), "r"(a[1]), "r"(a[2]), "r"(a[3]), "r"(db_lo), "r"(scale_d));
}
__device__ __forceinline__ void wgmma_ss_n256_tb(float (&d)[128], uint64_t da, uint64_t db, int scale_d) {
    asm volatile(
        "{\n.reg .pred p;\nsetp.ne.b32 p, %130, 0;\n"
        "wgmma.mma_async.sync.aligned.m64n256k16.f32.bf16.bf16 {%0, %1, %2, %3, %4, %5, %6, %7, %8, %9, %10, %11, %12, %13, %14, %15, %16, %17, %18, %19, %20, %21, %22, %23, %24, %25, %26, %27, %28, %29, %30, %31, %32, %33, %34, %35, %36, %37, %38, %39, %40, %41, %42, %43, %44, %45, %46, %47, %48, %49, %50, %51, %52, %53, %54, %55, %56, %57, %58, %59, %60, %61, %62, %63, %64, %65, %66, %67, %68, %69, %70, %71, %72, %73, %74, %75, %76, %77, %78, %79, %80, %81, %82, %83, %84, %85, %86, %87, %88, %89, %90, %91, %92, %93, %94, %95, %96, %97, %98, %99, %100, %101, %102, %103, %104, %105, %106, %107, %108, %109, %110, %111, %112, %113, %114, %115, %116, %117, %118, %119, %120, %121, %122, %123, %124, %125, %126, %127}, %128, %129, p, 1, 1, 0, 1;\n}\n"
        : "+f"(d[0]), "+f"(d[1]), "+f"(d[2]), "+f"(d[3]), "+f"(d[4]), "+f"(d[5]), "+f"(d[6]), "+f"(d[7]), "+f"(d[8]), "+f"(d[9]), "+f"(d[10]), "+f"(d[11]), "+f"(d[12]), "+f"(d[13]), "+f"(d[14]), "+f"(d[15]), "+f"(d[16]), "+f"(d[17]), "+f"(d[18]), "+f"(d[19]), "+f"(d[20]), "+f"(d[21]), "+f"(d[22]), "+f"(d[23]), "+f"(d[24]), "+f"(d[25]), "+f"(d[26]), "+f"(d[27]), "+f"(d[28]), "+f"(d[29]), "+f"(d[30]), "+f"(d[31]), "+f"(d[32]), "+f"(d[33]), "+f"(d[34]), "+f"(d[35]), "+f"(d[36]), "+f"(d[37]), "+f"(d[38]), "+f"(d[39]), "+f"(d[40]), "+f"(d[41]), "+f"(d[42]), "+f"(d[43]), "+f"(d[44]), "+f"(d[45]), "+f"(d[46]), "+f"(d[47]), "+f"(d[48]), "+f"(d[49]), "+f"(d[50]), "+f"(d[51]), "+f"(d[52]), "+f"(d[53]), "+f"(d[54]), "+f"(d[55]), "+f"(d[56]), "+f"(d[57]), "+f"(d[58]), "+f"(d[59]), "+f"(d[60]), "+f"(d[61]), "+f"(d[62]), "+f"(d[63]), "+f"(d[64]), "+f"(d[65]), "+f"(d[66]), "+f"(d[67]), "+f"(d[68]), "+f"(d[69]), "+f"(d[70]), "+f"(d[71]), "+f"(d[72]), "+f"(d[73]), "+f"(d[74]), "+f"(d[75]), "+f"(d[76]), "+f"(d[77]), "+f"(d[78]), "+f"(d[79]), "+f"(d[80]), "+f"(d[81]), "+f"(d[82]), "+f"(d[83]), "+f"(d[84]), "+f"(d[85]), "+f"(d[86]), "+f"(d[87]), "+f"(d[88]), "+f"(d[89]), "+f"(d[90]), "+f"(d[91]), "+f"(d[92]), "+f"(d[93]), "+f"(d[94]), "+f"(d[95]), "+f"(d[96]), "+f"(d[97]), "+f"(d[98]), "+f"(d[99]), "+f"(d[100]), "+f"(d[101]), "+f"(d[102]), "+f"(d[103]), "+f"(d[104]), "+f"(d[105]), "+f"(d[106]), "+f"(d[107]), "+f"(d[108]), "+f"(d[109]), "+f"(d[110]), "+f"(d[111]), "+f"(d[112]), "+f"(d[113]), "+f"(d[114]), "+f"(d[115]), "+f"(d[116]), "+f"(d[117]), "+f"(d[118]), "+f"(d[119]), "+f"(d[120]), "+f"(d[121]), "+f"(d[122]), "+f"(d[123]), "+f"(d[124]), "+f"(d[125]), "+f"(d[126]), "+f"(d[127])
        : "l"(da), "l"(db), "r"(scale_d));
}
__device__ __forceinline__ void stmatrix_x4(uint32_t addr, uint32_t r0, uint32_t r1, uint32_t r2, uint32_t r3) {
    asm volatile("stmatrix.sync.aligned.m8n8.x4.shared.b16 [%0], {%1, %2, %3, %4};" :: "r"(addr), "r"(r0), "r"(r1), "r"(r2), "r"(r3) : "memory");
}
__device__ __forceinline__ void tma_store_2d(const CUtensorMap* map, uint32_t src, int c0, int c1) {
    asm volatile("cp.async.bulk.tensor.2d.global.shared::cta.bulk_group [%0, {%2, %3}], [%1];"
                 :: "l"((uint64_t)map), "r"(src), "r"(c0), "r"(c1) : "memory");
}
__device__ __forceinline__ float ex2f(float x) { float y; asm("ex2.approx.ftz.f32 %0, %1;" : "=f"(y) : "f"(x)); return y; }
__device__ __forceinline__ uint32_t pack_bf16(float lo, float hi) {
    __nv_bfloat162 v = __floats2bfloat162_rn(lo, hi);
    return *reinterpret_cast<uint32_t*>(&v);
}
__device__ __forceinline__ void mma_16816(float (&c)[4], uint32_t a0, uint32_t a1, uint32_t a2, uint32_t a3,
                                          uint32_t b0, uint32_t b1) {
    asm volatile(
        "mma.sync.aligned.m16n8k16.row.col.f32.bf16.bf16.f32 {%0,%1,%2,%3}, {%4,%5,%6,%7}, {%8,%9}, {%0,%1,%2,%3};"
        : "+f"(c[0]), "+f"(c[1]), "+f"(c[2]), "+f"(c[3])
        : "r"(a0), "r"(a1), "r"(a2), "r"(a3), "r"(b0), "r"(b1));
}
__device__ __forceinline__ void ldmatrix_x4_trans(uint32_t& r0, uint32_t& r1, uint32_t& r2, uint32_t& r3, uint32_t addr) {
    asm volatile("ldmatrix.sync.aligned.m8n8.x4.trans.shared.b16 {%0,%1,%2,%3}, [%4];"
                 : "=r"(r0), "=r"(r1), "=r"(r2), "=r"(r3) : "r"(addr));
}

struct AttnParams {
    CUtensorMap mapQ, mapK, mapV;
    CUtensorMap mapO;
    bf16* out;
};
constexpr int FA_ITEMS = 16 * NH;
__device__ __forceinline__ int fa_qt(int t) { return 15 - ((t & 127) >> 3); }
__device__ __forceinline__ int fa_head(int t) { return (t >> 7) * 8 + (t & 7); }
#define FA_TKA 2
#define FA_SPLIT 11

#define FA_P0 4
#define FA_HO 6
#define FA_LAG 3
#define FA_PK 3
#define FA_TG 16
#define FA_EARLY 0
#define FA_TRIM 1
#define FA_TE 0
#define FA_B0 1
#define FA_ONE 1
#define FA_I0 0
static_assert(FA_GRID <= 104 && FA_HO >= FA_P0 && FA_P0 >= 1 && (!FA_TRIM || (FA_P0 == 4 && FA_SPLIT >= 8 && FA_I0 <= 4)), "");
constexpr float FA_MARGIN = 16.f;
#define FAT(b, i)
__device__ __forceinline__ void mbar_arrive_if(uint32_t bar, bool c) {
    asm volatile("{\n.reg .pred p;\nsetp.ne.b32 p, %1, 0;\n@p mbarrier.arrive.shared::cta.b64 _, [%0];\n}" :: "r"(bar), "r"((int)c) : "memory");
}
__device__ __forceinline__ void sched_fence(int v, int id, const float* a, const float* b, const float* c) {
    asm volatile("{\n.reg .pred p;\nsetp.ne.s32 p, %0, %1;\n@p bra SF_SKIP;\nwgmma.wait_group.sync.aligned 0;\n"
                 "st.volatile.shared.f32 [%0], %2;\nst.volatile.shared.f32 [%0], %3;\nst.volatile.shared.f32 [%0], %4;\nst.volatile.shared.f32 [%0], %5;\n"
                 "st.volatile.shared.f32 [%0], %6;\nst.volatile.shared.f32 [%0], %7;\nst.volatile.shared.f32 [%0], %8;\nst.volatile.shared.f32 [%0], %9;\n"
                 "st.volatile.shared.f32 [%0], %10;\nst.volatile.shared.f32 [%0], %11;\nst.volatile.shared.f32 [%0], %12;\nst.volatile.shared.f32 [%0], %13;\n"
                 "exit;\nSF_SKIP:\n}" :: "r"(v), "r"(1000000 + id), "f"(a[0]), "f"(a[1]), "f"(a[2]), "f"(a[3]), "f"(b[0]), "f"(b[1]), "f"(b[2]), "f"(b[3]),
                 "f"(c[0]), "f"(c[1]), "f"(c[2]), "f"(c[3]) : "memory");
}
__device__ __forceinline__ float ex2v(float x) { float y; asm volatile("ex2.approx.ftz.f32 %0, %1;" : "=f"(y) : "f"(x)); return y; }
__device__ __forceinline__ void wgmma_rs_n128_tb_lo(float (&d)[64], const uint32_t* a, uint32_t db_lo, int scale_d) {
    asm volatile(
        "{\n.reg .pred p;\n.reg .b64 db;\nsetp.ne.b32 p, %69, 0;\nmov.b64 db, {%68, 0x40000040};\n"
        "wgmma.mma_async.sync.aligned.m64n128k16.f32.bf16.bf16 " ACC64_STR ", {%64, %65, %66, %67}, db, p, 1, 1, 1;\n}\n"
        : ACC64(d) : "r"(a[0]), "r"(a[1]), "r"(a[2]), "r"(a[3]), "r"(db_lo), "r"(scale_d));
}

constexpr int M_GRID = 68;
constexpr uint32_t SD = 1024;
constexpr uint32_t MO_BAR = 229376;
constexpr int M_SMEM = MO_BAR + 1024;
constexpr uint32_t FO_Q = 0, FO_KV = 65536, FO_O = FO_KV + 2 * 65536, FO_BAR = MO_BAR + 512;
constexpr uint32_t FB_QF = FO_BAR, FB_QE = FO_BAR + 16, FB_KF = FO_BAR + 32, FB_VF = FO_BAR + 48, FB_KE = FO_BAR + 64, FB_VE = FO_BAR + 80,
                   FB_OF = FO_BAR + 96, FB_OE = FO_BAR + 112, FB_SLOT = FO_BAR + 128, FB_OSLOT = FO_BAR + 136;
__device__ __forceinline__ void attn_init(uint32_t sb) {
    for (int i = 0; i < 2; i++) {
        mbar_init(sb + FB_QF + 8 * i, 1); mbar_init(sb + FB_QE + 8 * i, 8); mbar_init(sb + FB_KF + 8 * i, 1); mbar_init(sb + FB_VF + 8 * i, 1);
        mbar_init(sb + FB_KE + 8 * i, 8); mbar_init(sb + FB_VE + 8 * i, 8); mbar_init(sb + FB_OF + 8 * i, 4); mbar_init(sb + FB_OE + 8 * i, 1);
    }
}
__device__ __forceinline__ void attn_helper(const AttnParams& P, uint32_t sb, int wg) {
    const uint32_t stg = sb + FO_O + wg * 16384;
    for (int n = 0;; n++) {
        mbar_wait(sb + FB_OF + 8 * wg, n & 1);
        int t;
        asm volatile("ld.shared.s32 %0, [%1];" : "=r"(t) : "r"(sb + FB_OSLOT + wg * 4) : "memory");
        const int qt = fa_qt(t), h = fa_head(t & 1023);
        tma_store_2d(&P.mapO, stg, 0, h * SEQ + qt * 128 + wg * 64);
        tma_store_2d(&P.mapO, stg + 8192, 64, h * SEQ + qt * 128 + wg * 64);
        asm volatile("cp.async.bulk.commit_group;" ::: "memory");
        asm volatile("cp.async.bulk.wait_group.read 0;" ::: "memory");
        mbar_arrive(sb + FB_OE + 8 * wg);
        asm volatile("cp.async.bulk.wait_group 0;" ::: "memory");
        signal_ctr(CT_CA + qt * 4 + (h >> 3));
        if (t >= 1024) break;
    }
}
__device__ __forceinline__ int attn_producer(const AttnParams& P, uint32_t sb, uint32_t free_bar, uint32_t free_par) {
    const uint32_t sQ = sb + FO_Q, sKV = sb + FO_KV;
    int b = 0, hp_ready = 0, vrow = 0, t = blockIdx.x, item = 0;
    auto load_v = [&](int i) {
        const uint32_t sv = sKV + (i & 1) * 65536 + 32768, bar = sb + FB_VF + 8 * (i & 1);
        mbar_wait(sb + FB_VE + 8 * (i & 1), ((i >> 1) & 1) ^ (FA_B0 ? ~i & 1 : 1));
        mbar_expect_tx(bar, 32768);
        tma_load_2d(sv, &P.mapV, bar, 0, vrow);
        tma_load_2d(sv + 16384, &P.mapV, bar, 64, vrow);
    };
    for (;; item++) {
        const bool valid = t < FA_ITEMS;
        const int qt = fa_qt(t), h = fa_head(t);
        if (valid && !((hp_ready >> (h >> 1)) & 1)) { wait_ctr(CT_AP + (h >> 1), 96u); hp_ready |= 1 << (h >> 1); }
        const uint32_t bq = sb + FB_QF + 8 * (item & 1);
        mbar_wait(item ? sb + FB_QE + 8 * (item & 1) : free_bar + 8, item ? ((item >> 1) & 1) ^ 1 : free_par);
        asm volatile("st.shared.s32 [%0], %1;" :: "r"(sb + FB_SLOT + (item & 1) * 4), "r"(valid ? t : -1) : "memory");
        if (!valid) { mbar_arrive(bq); break; }
        mbar_expect_tx(bq, 32768);
        tma_load_2d(sQ + (item & 1) * 32768, &P.mapQ, bq, 0, h * SEQ + qt * 128);
        tma_load_2d(sQ + (item & 1) * 32768 + 16384, &P.mapQ, bq, 64, h * SEQ + qt * 128);
#pragma unroll 1
        for (int j = 0; j <= qt; j++, b++) {
            const uint32_t sk = sKV + (b & 1) * 65536, bar = sb + FB_KF + 8 * (b & 1);
            mbar_wait(b >= 2 ? sb + FB_KE + 8 * (b & 1) : free_bar + 24 + 32 * b, b >= 2 ? ((b >> 1) & 1) ^ 1 : free_par);
            if (b == 1) { TS_END2(0, 256); TS_BEGIN2(1, 256); }
            if (b == 2) wait_ctr(CT_GATE, 256u);
            mbar_expect_tx(bar, 32768);
            tma_load_2d(sk, &P.mapK, bar, 0, h * SEQ + j * 128);
            tma_load_2d(sk + 16384, &P.mapK, bar, 64, h * SEQ + j * 128);
            if (j == max(qt - FA_TKA, 0)) t = take_ticket(CT_ATTN);
            if (b > 0) load_v(b - 1);
            vrow = h * SEQ + j * 128;
        }
        t += M_GRID;
    }
    load_v(b - 1);
    return b;
}
template <typename F>
__device__ __forceinline__ int attn_consumer(const AttnParams& P, int warp, F done, const uint32_t sb) {
    constexpr uint32_t sQ = SD + FO_Q, sKV = SD + FO_KV;
    const uint32_t sO = sb + FO_O;
    const uint32_t bar_qf = sb + FB_QF, bar_qe = sb + FB_QE, bar_kf = sb + FB_KF, bar_vf = sb + FB_VF, bar_ke = sb + FB_KE, bar_ve = sb + FB_VE,
                   bar_of = sb + FB_OF, bar_oe = sb + FB_OE, slot = sb + FB_SLOT, oslot = sb + FB_OSLOT;
    {
        const int wg = warp >> 2;
        const int lane = threadIdx.x & 31;
        const float sc = 0.08838834764831845f * 1.4426950408889634f;
        const int r0 = wg * 64 + (warp & 3) * 16 + (lane >> 2);
        float o[64], s[64];
        uint32_t pa[32];
        float m0 = 0.f, m1 = 0.f, l0 = 0.f, l1 = 0.f, i0 = 0.f, i1 = 0.f, g0 = 0.f, g1 = 0.f, gn0 = 0.f, gn1 = 0.f;
        const uint32_t q_lo = desc_lo(sQ + wg * 8192, 16), k_lo = desc_lo(sKV, 16), v_lo = desc_lo(sKV + 32768, 16384);
        auto issue_qk = [&](int b, int item, bool half) {
            const uint32_t qd = q_lo + (item & 1) * 2048, kd = k_lo + (b & 1) * 4096;
            const uint32_t kd2 = half ? kd - 512 : kd;
            wgmma_fence();
#pragma unroll
            for (int kk = 0; kk < 8; kk++) wgmma_ss_n128_lo<0>(s, qd + (kk >> 2) * 1024 + (kk & 3) * 2, kd2 + (kk >> 2) * 1024 + (kk & 3) * 2, kk != 0);
            wgmma_commit();
        };
        auto issue_pv = [&](int b, bool acc, int n, bool half) {
            const uint32_t vd = v_lo + (b & 1) * 4096;
            mbar_wait(bar_vf + 8 * (b & 1), (b >> 1) & 1);
            if (half) {
                asm volatile("wgmma.fence.sync.aligned;  // half" ::: "memory");
#pragma unroll
                for (int kk = 4; kk < 8; kk++) if (kk < n) wgmma_rs_n128_tb_lo(o, &pa[kk * 4], vd + (kk - 4) * 128, kk > 4 ? 1 : (int)acc);
                asm volatile("wgmma.commit_group.sync.aligned;  // half" ::: "memory");
                return;
            }
            wgmma_fence();
#pragma unroll
            for (int kk = 0; kk < 8; kk++) if (kk < n) wgmma_rs_n128_tb_lo(o, &pa[kk * 4], vd + kk * 128, kk ? 1 : (int)acc);
            wgmma_commit();
        };
        const int lim = (FA_TRIM ? (r0 | 64) : r0) - (lane & 3) * 2;
        uint32_t v_hi = v_lo;
        int acc_hi = 1;
        int item = -1, tnext = 0;
        uint32_t k_ready = 0, q_ready = 0;
        auto mask = [&](int i) { if ((i >> 2) * 8 + (i & 1) - ((i & 2) ? 8 : 0) > lim) s[i] = -INFINITY; };
        auto exps = [&](auto mode, int b, bool hand_over, float& u0, float& u1) {
            constexpr int MODE = decltype(mode)::value;
            float p[64], u[4] = {0.f, 0.f, 0.f, 0.f};
            const uint32_t vd = v_hi + ((b - 1) & 1) * 4096;
            constexpr int R = FA_TRIM && MODE == 2 ? 32 : 0;
#pragma unroll
            for (int i = 0; i < 4; i++) p[i] = fmaf(s[i ^ R], sc, (i & 2) ? -m1 : -m0);
#pragma unroll
            for (int g = 0; g < 16 + FA_LAG; g++) {
                if (MODE && g >= FA_I0 && g - FA_I0 < 8 - FA_P0) {
                    const int kk = FA_P0 + g - FA_I0;
                    wgmma_fence();
                    wgmma_rs_n128_tb_lo(o, &pa[kk * 4], vd + kk * 128, FA_TRIM && kk == 4 ? acc_hi : 1);
                    wgmma_commit();
                    if (kk == FA_HO) asm volatile("{\n.reg .pred p;\nsetp.ne.b32 p, %1, 0;\n@p bar.arrive %0, 256;\n}" :: "r"(4 - wg), "r"((int)hand_over) : "memory");
                }
                if (R && g == 8 && wg == 0) {
                    wgmma_wait<0>();
                    mbar_arrive_if(bar_ve + 8 * ((b - 1) & 1), lane == 0);
                    k_ready = q_ready = 0;
#pragma unroll
                    for (int i = 32 - FA_LAG * 4; i < 32; i++) u[i & 3] += p[i];
#pragma unroll
                    for (int i = 0; i < 16; i++) pa[16 + i] = pack_bf16(p[i * 2], p[i * 2 + 1]);
                    break;
                }
                if (MODE && g == FA_SPLIT) {
                    FAT(b, 2);
                    wgmma_wait<0>();
                    FAT(b - 1, 3);
                    mbar_arrive_if(bar_ve + 8 * ((b - 1) & 1), lane == 0);
                }
                if (MODE && g == FA_TG) {
                    k_ready = mbar_test(bar_kf + 8 * (~b & 1), ((b + 1) >> 1) & 1);
                    if (MODE == 2) {
                        q_ready = mbar_test(bar_qf + 8 * (~item & 1), ((item + 1) >> 1) & 1);
                        asm volatile("ld.shared.s32 %0, [%1];" : "=r"(tnext) : "r"(slot + (~item & 1) * 4) : "memory");
                    }
                }
#pragma unroll
                for (int j = 0; j < 4; j++) {
                    const int i = g * 4 + j;
                    if (g < 16) p[i] = ex2v(p[i]);
                    if (g < 15) {
                        if (MODE == 2 && (!R || i + 4 < 32)) mask((i + 4) ^ R);
                        p[i + 4] = fmaf(s[(i + 4) ^ R], sc, (i & 2) ? -m1 : -m0);
                    }
                    if (g >= FA_LAG) u[j] += p[i - FA_LAG * 4];
                }
#pragma unroll
                for (int gg = 0; gg < 16; gg++) {
                    const int at = MODE && gg + FA_LAG < FA_SPLIT + gg / FA_PK ? FA_SPLIT + gg / FA_PK : gg + FA_LAG;
                    if (at == g) { pa[(gg * 2) ^ (R / 2)] = pack_bf16(p[gg * 4], p[gg * 4 + 1]); pa[(gg * 2 + 1) ^ (R / 2)] = pack_bf16(p[gg * 4 + 2], p[gg * 4 + 3]); }
                }
                if (MODE && g < 16) sched_fence(b, g + MODE * 32, &p[g * 4], &p[(g < 15 ? g + 1 : g) * 4], u);
            }
            u0 = u[0] + u[1]; u1 = u[2] + u[3];
        };
        auto quad_max = [&](float& x0, float& x1) {
            x0 = fmaxf(x0, __shfl_xor_sync(0xffffffff, x0, 1)); x1 = fmaxf(x1, __shfl_xor_sync(0xffffffff, x1, 1));
            x0 = fmaxf(x0, __shfl_xor_sync(0xffffffff, x0, 2)); x1 = fmaxf(x1, __shfl_xor_sync(0xffffffff, x1, 2));
            x0 = fmaf(x0, sc, FA_MARGIN); x1 = fmaf(x1, sc, FA_MARGIN);
        };
        auto softmax_exact = [&](bool fresh, bool half, int b) {
            wgmma_wait<0>();
            if (half) {
#pragma unroll
                for (int i = 0; i < 32; i++) s[i] = -INFINITY;
            }
            float x[8];
#pragma unroll
            for (int i = 0; i < 8; i++) x[i] = fmaxf(s[i * 2], s[i * 2 + 1]);
#pragma unroll
            for (int i = 8; i < 32; i++) x[i & 7] = fmaxf(x[i & 7], fmaxf(s[i * 2], s[i * 2 + 1]));
            float x0 = fmaxf(fmaxf(x[0], x[2]), fmaxf(x[4], x[6])), x1 = fmaxf(fmaxf(x[1], x[3]), fmaxf(x[5], x[7]));
            quad_max(x0, x1);
            if (!fresh) {
                x0 = fmaxf(x0, m0); x1 = fmaxf(x1, m1);
                const float a0 = ex2f(m0 - x0), a1 = ex2f(m1 - x1);
                l0 *= a0; l1 *= a1;
#pragma unroll
                for (int i = 0; i < 16; i++) { o[i * 4 + 0] *= a0; o[i * 4 + 1] *= a0; o[i * 4 + 2] *= a1; o[i * 4 + 3] *= a1; }
            }
            m0 = x0; m1 = x1;
            float u0, u1;
            exps(std::integral_constant<int, 0>(), b, false, u0, u1);
            l0 += u0; l1 += u1;
        };
        auto finish_rows = [&]() {
            l0 += __shfl_xor_sync(0xffffffff, l0, 1); l1 += __shfl_xor_sync(0xffffffff, l1, 1);
            l0 += __shfl_xor_sync(0xffffffff, l0, 2); l1 += __shfl_xor_sync(0xffffffff, l1, 2);
            asm("rcp.approx.ftz.f32 %0, %1;" : "=f"(i0) : "f"(l0));
            asm("rcp.approx.ftz.f32 %0, %1;" : "=f"(i1) : "f"(l1));
            i0 *= g0; i1 *= g1;
        };
        auto clear_out = [&](int t) {
            if (t >= 384) {
                bf16* z = P.out + (size_t)(fa_qt(t) * 128 + wg * 64 + ((threadIdx.x & 127) >> 3)) * DM + (t & 7) * 64 + (lane & 7) * 8;
#pragma unroll
                for (int i = 0; i < 4; i++) *reinterpret_cast<uint4*>(z + i * 16 * DM) = make_uint4(0u, 0u, 0u, 0u);
            }
        };
        auto store_o = [&](int t, int n) {
            const uint32_t stg = sO + wg * 16384;
            {
                mbar_wait(bar_oe + 8 * wg, (n & 1) ^ 1);
                asm volatile("st.shared.s32 [%0], %1;" :: "r"(oslot + wg * 4), "r"(t) : "memory");
            }
            const int row = (warp & 3) * 16 + (lane >> 2);
#pragma unroll
            for (int i = 0; i < 4; i++) {
                const int ch = i * 4 + (lane & 3);
                const uint32_t a = stg + (ch >> 3) * 8192 + row * 128 + (((ch & 7) ^ (row & 7)) << 4);
                const float* q = &o[i * 16];
                asm volatile("st.shared.v4.b32 [%0], {%1, %2, %3, %4};" :: "r"(a), "r"(pack_bf16(q[0] * i0, q[1] * i0)), "r"(pack_bf16(q[4] * i0, q[5] * i0)),
                             "r"(pack_bf16(q[8] * i0, q[9] * i0)), "r"(pack_bf16(q[12] * i0, q[13] * i0)) : "memory");
                asm volatile("st.shared.v4.b32 [%0], {%1, %2, %3, %4};" :: "r"(a + 1024), "r"(pack_bf16(q[2] * i1, q[3] * i1)), "r"(pack_bf16(q[6] * i1, q[7] * i1)),
                             "r"(pack_bf16(q[10] * i1, q[11] * i1)), "r"(pack_bf16(q[14] * i1, q[15] * i1)) : "memory");
            }
        };
        auto publish_o = [&]() {
            asm volatile("fence.proxy.async.shared::cta;" ::: "memory");
            __syncwarp();
            mbar_arrive_if(bar_of + 8 * wg, lane == 0);
        };
        int t = 0, left = 0, tdone = -1, b = 0, nout = 0;
        bool first = true, staged = false;
#pragma unroll 1
        for (;; b++) {
            const bool fresh = left == 0;
            const int tprev = t;
            FAT(b, 4);
            if (staged) { publish_o(); staged = false; }
            if (fresh) {
                item++;
                if (!q_ready) {
                    mbar_wait(bar_qf + 8 * (item & 1), (item >> 1) & 1);
                    asm volatile("ld.shared.s32 %0, [%1];" : "=r"(tnext) : "r"(slot + (item & 1) * 4) : "memory");
                }
                if (tnext < 0) break;
                t = tnext;
                left = fa_qt(t) + 1;
            }
            left--;
            if (fresh || first || left == 0) {
                if (tdone >= 0) store_o(tdone, nout);
                if (fresh) { g0 = gn0; g1 = gn1; }
                if (left == 0) { gn0 = __ldcg(g_gate + fa_qt(t) * 128 + r0); gn1 = __ldcg(g_gate + fa_qt(t) * 128 + r0 + 8); clear_out(t); }
            }
            FAT(b, 5);
            if (!k_ready) mbar_wait(bar_kf + 8 * (b & 1), (b >> 1) & 1);
            FAT(b, 6);
            asm volatile("bar.sync %0, 256;" :: "r"(3 + wg) : "memory");
            FAT(b, 0);
            issue_qk(b, item, FA_TRIM && wg == 0 && left == 0);
            FAT(b, 7);
            bool early = false;
            if (!fresh && !first && left != 0) {
                issue_pv(b - 1, true, FA_P0, false);
                wgmma_wait<1>();
                FAT(b, 1);
                mbar_arrive_if(bar_ke + 8 * (b & 1), lane == 0);
            } else {
                const bool hprev = FA_TRIM && fresh && wg == 0;
                early = (FA_EARLY && tdone >= 0) || b == 0 || (FA_TE && hprev);
                if (early) asm volatile("bar.arrive %0, 256;" :: "r"(4 - wg) : "memory");
                if (tdone >= 0) { nout++; staged = true; }
                tdone = fresh && b > 0 ? tprev : -1;
                v_hi = hprev ? v_lo - 512 : v_lo;
                acc_hi = !(hprev && first);
                if (b > 0) issue_pv(b - 1, !first, FA_P0, hprev); else { wgmma_fence(); wgmma_commit(); }
                first = fresh;
                wgmma_wait<1>();
                FAT(b, 1);
                mbar_arrive_if(bar_ke + 8 * (b & 1), lane == 0);
                mbar_arrive_if(bar_qe + 8 * (item & 1), lane == 0 && left == 0);
                if (left == 0) { mask(FA_TRIM ? 32 : 0); mask(FA_TRIM ? 33 : 1); }
                if (fresh) {
                    finish_rows();
                    l0 = l1 = 0.f;
                    m0 = fmaxf(s[0], s[1]); m1 = fmaxf(s[2], s[3]);
                    if (FA_TRIM && left == 0) { m0 = fmaxf(s[32], s[33]); m1 = fmaxf(s[34], s[35]); }
                    quad_max(m0, m1);
                }
            }
            if (FA_B0 || b > 0) {
                float u0, u1;
                if (left == 0) exps(std::integral_constant<int, 2>(), b, !early, u0, u1);
                else exps(std::integral_constant<int, 1>(), b, !early, u0, u1);
                if (!__any_sync(0xffffffff, !(u0 + u1 < 1.f))) { l0 += u0; l1 += u1; continue; }
            }
            softmax_exact(fresh, FA_TRIM && wg == 0 && left == 0, b);
        }
        if (tdone >= 0) { store_o(tdone, nout++); publish_o(); }
        issue_pv(b - 1, !first, 8, FA_TRIM && wg == 0);
        g0 = gn0; g1 = gn1;
        finish_rows();
        wgmma_wait<0>();
        done();
        store_o(t + 1024, nout);
        publish_o();
        return nout;
    }
}

__device__ __forceinline__ uint32_t cluster_ctarank() {
    uint32_t r; asm volatile("mov.u32 %0, %%cluster_ctarank;" : "=r"(r)); return r;
}
__device__ __forceinline__ uint32_t mapa_u32(uint32_t addr, uint32_t rank) {
    uint32_t r; asm volatile("mapa.shared::cluster.u32 %0, %1, %2;" : "=r"(r) : "r"(addr), "r"(rank)); return r;
}
__device__ __forceinline__ void cluster_sync_all() {
    asm volatile("barrier.cluster.arrive.release.aligned;\nbarrier.cluster.wait.acquire.aligned;" ::: "memory");
}
__device__ __forceinline__ void st_async_v4(uint32_t addr, uint32_t a, uint32_t b, uint32_t c, uint32_t d, uint32_t mbar) {
    asm volatile("st.async.weak.shared::cluster.mbarrier::complete_tx::bytes.v4.b32 [%0], {%1, %2, %3, %4}, [%5];"
                 :: "r"(addr), "r"(a), "r"(b), "r"(c), "r"(d), "r"(mbar) : "memory");
}
__device__ __forceinline__ void st_async_v2(uint32_t addr, uint32_t a, uint32_t b, uint32_t mbar) {
    asm volatile("st.async.weak.shared::cluster.mbarrier::complete_tx::bytes.v2.b32 [%0], {%1, %2}, [%3];"
                 :: "r"(addr), "r"(a), "r"(b), "r"(mbar) : "memory");
}
__device__ __forceinline__ void st_async_b32(uint32_t addr, uint32_t a, uint32_t mbar) {
    asm volatile("st.async.weak.shared::cluster.mbarrier::complete_tx::bytes.b32 [%0], %1, [%2];" :: "r"(addr), "r"(a), "r"(mbar) : "memory");
}
__device__ __forceinline__ void pace(int cycles) {
    if (cycles > 0) {
        uint32_t t0, t;
        asm volatile("mov.u32 %0, %%clock;" : "=r"(t0));
        do { asm volatile("mov.u32 %0, %%clock;" : "=r"(t)); } while (t - t0 < (uint32_t)cycles);
    }
}
__device__ __forceinline__ void mbar_wait_cl(uint32_t bar, uint32_t parity) {
    uint32_t done = 0;
    for (int it = 0; it < WAIT_LIMIT && !done; it++) {
        asm volatile(
            "{\n.reg .pred p;\n"
            "mbarrier.try_wait.parity.shared::cta.b64 p, [%1], %2;\n"
            "selp.u32 %0, 1, 0, p;\n}\n" : "=r"(done) : "r"(bar), "r"(parity) : "memory");
    }
}
__device__ __forceinline__ void ldmatrix_x4(uint32_t& r0, uint32_t& r1, uint32_t& r2, uint32_t& r3, uint32_t addr) {
    asm volatile("ldmatrix.sync.aligned.m8n8.x4.shared.b16 {%0,%1,%2,%3}, [%4];"
                 : "=r"(r0), "=r"(r1), "=r"(r2), "=r"(r3) : "r"(addr));
}
__device__ __forceinline__ void cp_async16(uint32_t dst, const void* src) {
    asm volatile("cp.async.cg.shared.global [%0], [%1], 16;" :: "r"(dst), "l"(src) : "memory");
}
__device__ __forceinline__ float bf16r(float x) { return __uint_as_float(pack_bf16(0.f, x) & 0xffff0000u); }

#define DBGP(i, w, ok)
#define DBG(i, w)
#define DBGD(i, w, dep)
#define DBG_EXTRA 0
__device__ __forceinline__ void tma_load_2d_mc(uint32_t dst, const CUtensorMap* map, uint32_t bar, int c0, int c1, uint16_t mask) {
    asm volatile(
        "cp.async.bulk.tensor.2d.shared::cluster.global.mbarrier::complete_tx::bytes.multicast::cluster [%0], [%1, {%3, %4}], [%2], %5;"
        :: "r"(dst), "l"((uint64_t)map), "r"(bar), "r"(c0), "r"(c1), "h"(mask) : "memory");
}
__device__ __forceinline__ void stmatrix_x4_trans(uint32_t addr, uint32_t r0, uint32_t r1, uint32_t r2, uint32_t r3) {
    asm volatile("stmatrix.sync.aligned.m8n8.x4.trans.shared.b16 [%0], {%1, %2, %3, %4};" :: "r"(addr), "r"(r0), "r"(r1), "r"(r2), "r"(r3) : "memory");
}
__device__ __forceinline__ void stmatrix_x2_trans(uint32_t addr, uint32_t r0, uint32_t r1) {
    asm volatile("stmatrix.sync.aligned.m8n8.x2.trans.shared.b16 [%0], {%1, %2};" :: "r"(addr), "r"(r0), "r"(r1) : "memory");
}
__device__ __forceinline__ uint4 lds128(uint32_t a) {
    uint4 v; asm volatile("ld.shared.v4.u32 {%0, %1, %2, %3}, [%4];" : "=r"(v.x), "=r"(v.y), "=r"(v.z), "=r"(v.w) : "r"(a) : "memory"); return v;
}
__device__ __forceinline__ void sts128(uint32_t a, uint32_t x, uint32_t y, uint32_t z, uint32_t w) {
    asm volatile("st.shared.v4.b32 [%0], {%1, %2, %3, %4};" :: "r"(a), "r"(x), "r"(y), "r"(z), "r"(w) : "memory");
}
__device__ __forceinline__ float2 lds64f(uint32_t a) {
    float2 v; asm volatile("ld.shared.v2.f32 {%0, %1}, [%2];" : "=f"(v.x), "=f"(v.y) : "r"(a) : "memory"); return v;
}
__device__ __forceinline__ void fence_async_smem() { asm volatile("fence.proxy.async.shared::cta;" ::: "memory"); }
#define ACC16(d) "+f"(d[0]), "+f"(d[1]), "+f"(d[2]), "+f"(d[3]), "+f"(d[4]), "+f"(d[5]), "+f"(d[6]), "+f"(d[7]), "+f"(d[8]), "+f"(d[9]), "+f"(d[10]), "+f"(d[11]), "+f"(d[12]), "+f"(d[13]), "+f"(d[14]), "+f"(d[15])
template <int ND>
__device__ __forceinline__ void wgmma_rs_n32(float (&d)[ND], const uint32_t (&a)[4], uint32_t db_lo, int scale_d) {
    asm volatile(
        "{\n.reg .pred p;\n.reg .b64 db;\nsetp.ne.b32 p, %21, 0;\nmov.b64 db, {%20, 0x40000040};\n"
        "wgmma.mma_async.sync.aligned.m64n32k16.f32.bf16.bf16 {%0,%1,%2,%3,%4,%5,%6,%7,%8,%9,%10,%11,%12,%13,%14,%15}, {%16,%17,%18,%19}, db, p, 1, 1, 0;\n}\n"
        : ACC16(d) : "r"(a[0]), "r"(a[1]), "r"(a[2]), "r"(a[3]), "r"(db_lo), "r"(scale_d));
}
template <int ND>
__device__ __forceinline__ void wgmma_ss_n32(float (&d)[ND], uint32_t da_lo, uint32_t db_lo, int scale_d) {
    asm volatile(
        "{\n.reg .pred p;\n.reg .b64 da, db;\nsetp.ne.b32 p, %18, 0;\nmov.b64 da, {%16, 0x40000040};\nmov.b64 db, {%17, 0x40000040};\n"
        "wgmma.mma_async.sync.aligned.m64n32k16.f32.bf16.bf16 {%0,%1,%2,%3,%4,%5,%6,%7,%8,%9,%10,%11,%12,%13,%14,%15}, da, db, p, 1, 1, 1, 0;\n}\n"
        : ACC16(d) : "r"(da_lo), "r"(db_lo), "r"(scale_d));
}
__device__ __forceinline__ void wgmma_ss_n8(float (&d)[4], uint32_t da_lo, uint32_t db_lo, int scale_d) {
    asm volatile(
        "{\n.reg .pred p;\n.reg .b64 da, db;\nsetp.ne.b32 p, %6, 0;\nmov.b64 da, {%4, 0x40000040};\nmov.b64 db, {%5, 0x00000010};\n"
        "wgmma.mma_async.sync.aligned.m64n8k16.f32.bf16.bf16 {%0,%1,%2,%3}, da, db, p, 1, 1, 1, 0;\n}\n"
        : "+f"(d[0]), "+f"(d[1]), "+f"(d[2]), "+f"(d[3]) : "r"(da_lo), "r"(db_lo), "r"(scale_d));
}

#define SCHED_FENCE()
__device__ __forceinline__ void wgmma_ss_n32_p(float (&d)[16], uint32_t da_lo, uint32_t db_lo, int scale_d) {
    asm volatile(
        "{\n.reg .pred p;\n.reg .b64 da, db;\nsetp.ne.b32 p, %18, 0;\nmov.b64 da, {%16, 0x40000040};\nmov.b64 db, {%17, 0x00000030};\n"
        "wgmma.mma_async.sync.aligned.m64n32k16.f32.bf16.bf16 {%0,%1,%2,%3,%4,%5,%6,%7,%8,%9,%10,%11,%12,%13,%14,%15}, da, db, p, 1, 1, 1, 0;\n}\n"
        : ACC16(d) : "r"(da_lo), "r"(db_lo), "r"(scale_d));
}

#define ACC20(d) ACC16(d), "+f"(d[16]), "+f"(d[17]), "+f"(d[18]), "+f"(d[19])
#define ACC20_STR "{%0,%1,%2,%3,%4,%5,%6,%7,%8,%9,%10,%11,%12,%13,%14,%15,%16,%17,%18,%19}"
__device__ __forceinline__ void wgmma_rs_n40(float (&d)[20], const uint32_t (&a)[4], uint32_t db_lo, int scale_d) {
    asm volatile(
        "{\n.reg .pred p;\n.reg .b64 db;\nsetp.ne.b32 p, %25, 0;\nmov.b64 db, {%24, 0x40000040};\n"
        "wgmma.mma_async.sync.aligned.m64n40k16.f32.bf16.bf16 " ACC20_STR ", {%20,%21,%22,%23}, db, p, 1, 1, 0;\n}\n"
        : ACC20(d) : "r"(a[0]), "r"(a[1]), "r"(a[2]), "r"(a[3]), "r"(db_lo), "r"(scale_d));
}
template <int TA, int SBO>
__device__ __forceinline__ void wgmma_ss_n40(float (&d)[20], uint32_t da_lo, uint32_t db_lo, int scale_d) {
    asm volatile(
        "{\n.reg .pred p;\n.reg .b64 da, db;\nsetp.ne.b32 p, %22, 0;\nmov.b64 da, {%20, %23};\nmov.b64 db, {%21, 0x40000040};\n"
        "wgmma.mma_async.sync.aligned.m64n40k16.f32.bf16.bf16 " ACC20_STR ", da, db, p, 1, 1, %24, 0;\n}\n"
        : ACC20(d) : "r"(da_lo), "r"(db_lo), "r"(scale_d), "n"(0x40000000 + SBO / 16), "n"(TA));
}
template <int SBO>
__device__ __forceinline__ void wgmma_ss_n48(float (&d)[24], uint32_t da_lo, uint32_t db_lo, int scale_d) {
    asm volatile(
        "{\n.reg .pred p;\n.reg .b64 da, db;\nsetp.ne.b32 p, %26, 0;\nmov.b64 da, {%24, %27};\nmov.b64 db, {%25, 0x40000040};\n"
        "wgmma.mma_async.sync.aligned.m64n48k16.f32.bf16.bf16 {%0,%1,%2,%3,%4,%5,%6,%7,%8,%9,%10,%11,%12,%13,%14,%15,%16,%17,%18,%19,%20,%21,%22,%23}, da, db, p, 1, 1, 0, 0;\n}\n"
        : ACC20(d), "+f"(d[20]), "+f"(d[21]), "+f"(d[22]), "+f"(d[23]) : "r"(da_lo), "r"(db_lo), "r"(scale_d), "n"(0x40000000 + SBO / 16));
}

#define PT(i, th)
struct ChainParams {
    CUtensorMap mapW[3];
    CUtensorMap mapX;
    CUtensorMap mapC;
    CUtensorMap mapWo;
    CUtensorMap mapM;
    CUtensorMap mapOut;
};
constexpr int CH_BLOCK = 384;
constexpr int CO_WO = 0;
constexpr int CH_XC = 5120, CH_XP = 8 * CH_XC;
constexpr int CO_XB = 65536;
constexpr int CO_OB = CO_XB + 2 * CH_XP;
constexpr int CO_P = CO_OB + 8192;
constexpr int CO_LS = CO_P + 3072;
constexpr int CO_SC = CO_LS + 8 * 1280;
constexpr int CH_TW = 6144 + 8192;
constexpr int CO_T = 21 * 8192;
constexpr int CO_WA = CO_T + 6144;
constexpr int CO_ST = CO_T + 3 * CH_TW + 6144;
constexpr int CO_OWN = CO_ST + 4096, CO_OWN2 = CO_SC + 1536;
constexpr int CO_BAR = CO_OWN + 4096;
constexpr int CH_SMEM = CO_BAR + 256 + DBG_EXTRA;
#define CH_GL 2
#define CH_A3 1
#define CH_D0 0
#define CH_PF 0
#define CH_NA 0
#define CH_LQ ""
#define CH_SQ ""
#define CH_XPF 0
#define CH_NSM 4
static_assert(CO_OWN2 + 1024 <= CO_T && CH_NSM <= 4, "smem layout");
#ifndef M_D0
#define M_D0 0
#endif
#define CH_SG 2
#define CH_XS 1
#define CH_POLL_DELAY 240
#define CH_VPOS 2
#define CH_OW 12
#define CH_OF 12
#define CH_Q0 0
#define CH_QI 12
#define CH_QX 0
#define CH_Q1 (CH_Q0 + CH_QI + CH_QX)
#define CH_VA 5
#define CH_SPOS 0
#define CH_LSW 1
#define CH_QE 16
#define CH_KE 16
#define CH_QD 0
#define CH_GAP 0
#define CH_QS 0
#define CH_KS 0
#define CH_VS 4
#define CH_A7 7
#define CH_RF 0
#define CH_LSS 0
#define CH_OS 1
#define CH_MG 0
#define CH_MBT 0x76543210u
#define CH_MB(i) ((int)(CH_MBT >> 4 * (i)) & 7)
#define CH_AS 0x64207531u
#define CH_QL 16
#define CH_ML 0x112112
#define CH_DEP 1
#define CH_SP 2
#define CH_VD 0
#define CH_MP 2
#define CH_MP0 2
#define CH_OFE 3
#define CH_MS 1
#define CH_HA 3
#define CH_LD 4
#define CH_TWP 0
#define CH_SUMC 2
#define CH_ES 0
#define CH_ST 224
#define CH_KEEP 1
#define CH_PINB 1
#define CH_DRY 1
#define CH_D1 4500
#define CH_D2 11000
#define CH_CHAINS 4

constexpr float CH_SC = 0.08838834764831845f * 1.4426950408889634f;
__device__ __forceinline__ uint32_t pin(uint32_t v) { return __shfl_sync(0xffffffff, v, threadIdx.x & 31); }

__device__ __forceinline__ void out_finished() {
    if (atomicAdd(&g_ctr[CT_FIN], 1u) == M_GRID + 64 - 1)
        for (int i = 0; i < CT_N / 4; i++) reinterpret_cast<uint4*>(g_ctr)[i] = make_uint4(0u, 0u, 0u, 0u);
}
__device__ __forceinline__ uint32_t tail_a(uint32_t c) { return c < 3 ? CO_XB + 2 * CH_XC + c * 8192 : CO_OB; }
__device__ __forceinline__ void out_flush_half(const float* acc, const CUtensorMap* map, uint32_t stg, int tid, int bar, int n0, int m0) {
    const int lane = tid & 31, row = (lane & 7) + ((lane >> 3) & 1) * 8;
#pragma unroll
    for (int j = 0; j < 16; j += 2) {
        const float* a = &acc[j * 4];
        stmatrix_x4(stg + (j >> 3) * 8192 + (((tid >> 5) & 3) * 16 + row) * 128 + ((((j & 7) + (lane >> 4)) ^ (row & 7)) << 4),
                    pack_bf16(a[0], a[1]), pack_bf16(a[2], a[3]), pack_bf16(a[4], a[5]), pack_bf16(a[6], a[7]));
    }
    asm volatile("fence.proxy.async.shared::cta;\nbar.sync %0, 128;" :: "r"(bar) : "memory");
    asm volatile("{\n.reg .pred p;\nsetp.ne.b32 p, %0, 0;\n@p bra FL_SKIP;\n"
                 "cp.reduce.async.bulk.tensor.2d.global.shared::cta.add.tile.bulk_group [%1, {%3, %5}], [%2];\n"
                 "cp.reduce.async.bulk.tensor.2d.global.shared::cta.add.tile.bulk_group [%1, {%4, %5}], [%2 + 8192];\n"
                 "cp.async.bulk.commit_group;\nFL_SKIP:\n}"
                 :: "r"(tid & 127), "l"((uint64_t)map), "r"(stg), "r"(n0), "r"(n0 + 64), "r"(m0) : "memory");
    __syncwarp();
}
__device__ __forceinline__ void out_flush(const float (&acc)[128], const CUtensorMap* map, uint32_t stg0, uint32_t stg1, int tid, int bar, int n0, int m0) {
    out_flush_half(acc, map, stg0, tid, bar, n0, m0);
    out_flush_half(acc + 64, map, stg1, tid, bar, n0 + 128, m0);
}

__global__ void __cluster_dims__(8, 1, 1) __launch_bounds__(CH_BLOCK, 1)
chain_kernel(const __grid_constant__ ChainParams P) {
    extern __shared__ uint8_t smem_raw[];
    const int tid = threadIdx.x, warp = __shfl_sync(0xffffffff, tid >> 5, 0), lane = tid & 31;
    const int rank = (int)cluster_ctarank();
    constexpr uint32_t sd = 1024;
    const uint32_t sb = ((uint32_t)rank << 24) + sd;
    if (smem_u32(smem_raw) != sb) __trap();
    const int C = blockIdx.x >> 3;
    const int h = C * 4 + (rank >> 1);
    const int qd = lane >> 2, qc = lane & 3;
    const int t4 = warp & 3, wg = warp >> 2;
    pdl_launch_dependents();
    uint32_t t_start;
    asm volatile("mov.u32 %0, %%clock;" : "=r"(t_start));
    t_start = __shfl_sync(0xffffffff, t_start, 0);
    TS_BEGIN(2);
    PT(0, 0);
    const uint32_t bar_mem = sb + CO_BAR + 128, bar_o = sb + CO_BAR + 32, bar_sc = bar_o + 32, bar_x = bar_sc + 8, bar_l = bar_x + 16, bar_w = bar_l + 8;
    const uint32_t bar_wo = bar_o + 24;
    auto chunk = [&](int i) { return (uint32_t)((rank - i) & 7); };
    auto mine = [](int g, int c) { return (int)((CH_AS >> (g * 16 + c * 4)) & 7); };
    const int wcol = h * HD + (rank & 1) * 64;
    auto wdst = [&](int g, int i) { return i == 0 ? CO_WA + g * CH_TW : g && i == 7 ? CO_ST : (g ? CO_XB + CH_XP : 0) + (i - 1) * 8192; };
    auto vdst = [&](int i) { return i >= 2 && i < 10 ? CO_XB + CH_XP + (i - 2) * CH_XC : (i < 2 ? CO_WA + 2 * CH_TW : i < 12 ? CO_OB : i < 14 ? CO_LS : CO_ST) + (i & 1) * 4096; };
    if ((tid & 127) == 0) {
        pace(CH_D0);
        const uint32_t bar = wg == 2 ? bar_x : bar_w + 8 * wg;
        mbar_init(bar, 1);
        asm volatile("fence.mbarrier_init.release.cluster;" ::: "memory");
        mbar_expect_tx(bar, wg == 2 ? CH_XP : 65536);
#pragma unroll 1
        for (int i = 0; i < 8; i++) {
            if (wg == 2) {
                tma_load_2d(sb + CO_XB + i * CH_XC, &P.mapX, bar, i * 64, 0);
                tma_load_2d(sb + CO_XB + i * CH_XC + 4096, &P.mapM, bar, i * 64, 0);
            } else tma_load_2d(sb + wdst(wg, i), &P.mapW[wg ^ (i & 1)], bar, wcol, chunk(mine(wg, i >> 1)) * 64);
        }
    }
    if (warp == 9 && lane < 24 && lane != 9 && (lane >> 1) != 6) {
        mbar_init(sb + CO_BAR + 8 * lane, lane == 15 ? 16 : 1);
        asm volatile("fence.mbarrier_init.release.cluster;" ::: "memory");
    }
    __syncthreads();
    PT(1, 0);
    if (wg == 2 || (wg == 0 && CH_QL < 16)) asm volatile("bar.arrive 10, %0;" :: "n"(CH_QL < 16 ? 384 : 256) : "memory");
    if (wg == 2) {
        const int t = tid - 256;
        sts128(sb + CO_T + (2 + (t >> 6)) * CH_TW + 5120 + (t & 63) * 16, 0u, 0u, 0u, 0u);
        if (t < 32) sts128(sb + CO_P + (t >> 3) * 768 + 640 + (t & 7) * 16, 0u, 0u, 0u, 0u);
    }
    const uint32_t wfrag = (((lane >> 4) << 3) + (lane & 7)) * 128 + (((t4 * 2 + ((lane >> 3) & 1)) ^ (lane & 7)) << 4);
    const uint32_t aO = pin(sb + wg * CH_TW + wfrag);
    const uint32_t aL = pin(sb + lane * 16);
    uint32_t w[32][4];
    auto load_w = [&](int g, bool v) {
#pragma unroll
        for (int e = CH_NSM; e < 32; e++) ldmatrix_x4_trans(w[e][0], w[e][1], w[e][2], w[e][3], aO + ((v ? vdst(e >> 1) + (e & 1) * 2048 : wdst(g, e >> 2) + (e & 3) * 2048) - g * CH_TW));
        fence_async_smem();
    };
    auto pass = [&](auto& d, int g, int b, int j0, int j1, int js, bool group = true) {
        const uint32_t lo = desc_lo(sd + CO_XB + b * CH_XP, 16);
        if (group) wgmma_fence();
#pragma unroll
        for (int j = 0; j < 32; j++) if (j >= j0 && j < j1) {
            const int f = js < 0 ? j : j < js ? j + CH_NSM : j < js + CH_NSM ? j - js : j;
            const int e = sizeof(d) == 64 ? (f >> 2) * 8 + (js < 0 ? 4 : 0) + (f & 3) : f;
            const uint32_t db = lo + chunk(sizeof(d) == 64 ? mine(g, f >> 2) : f >> 2) * (CH_XC / 16) + (e & 3) * 2, da = desc_lo(sd + CO_WA + g * CH_TW + e * 2048, 16);
            if constexpr (sizeof(d) == 64) { if (e < CH_NSM) wgmma_ss_n32(d, da, db, j != 0); else wgmma_rs_n32(d, w[e], db, j != 0); }
            else { if (e < CH_NSM) wgmma_ss_n40<1, 1024>(d, da, db, j != 0); else wgmma_rs_n40(d, w[e], db, j != 0); }
        }
        if (group) wgmma_commit();
    };
    auto uni = [](uint32_t v) { return __shfl_sync(0xffffffff, v, 0); };
    auto roff = [&](int j) { return (uint32_t)(((rank + j) & 7) - rank) << 24; };
    auto store32 = [&](const float* d, uint32_t a) {
        stmatrix_x4_trans(a, pack_bf16(d[0], d[1]), pack_bf16(d[2], d[3]), pack_bf16(d[4], d[5]), pack_bf16(d[6], d[7]));
        stmatrix_x4_trans(a + 2048, pack_bf16(d[8], d[9]), pack_bf16(d[10], d[11]), pack_bf16(d[12], d[13]), pack_bf16(d[14], d[15]));
    };
    auto load32 = [&](uint32_t (&r)[8], uint32_t a) {
        ldmatrix_x4_trans(r[0], r[1], r[2], r[3], a);
        ldmatrix_x4_trans(r[4], r[5], r[6], r[7], a + 2048);
    };
    auto add32 = [&](float* d, const uint32_t (&r)[8], uint32_t a) {
        wgmma_wait<0>();
#pragma unroll
        for (int i = 0; i < 8; i++) { d[2 * i] += __uint_as_float(r[i] << 16); d[2 * i + 1] += __uint_as_float(r[i] & 0xffff0000u); }
        store32(d, a);
    };
    auto scores = [&](float (&d)[24], auto sbo, uint32_t q) {
        wgmma_fence();
#pragma unroll
        for (int ks = 0; ks < 4; ks++) wgmma_ss_n48<decltype(sbo)::value>(d, desc_lo(sd + q, 16) + ks * 2, desc_lo(sd + CO_T + CH_TW, 16) + ks * 2, ks != 0);
        wgmma_commit();
    };
    auto add_scores = [&](uint32_t a, uint32_t b, float (&v)[10]) {
        const uint4 a0 = lds128(a), a1 = lds128(a + 512);
        const float2 a2 = lds64f(b);
        v[0] += __uint_as_float(a0.x); v[1] += __uint_as_float(a0.y); v[2] += __uint_as_float(a0.z); v[3] += __uint_as_float(a0.w);
        v[4] += __uint_as_float(a1.x); v[5] += __uint_as_float(a1.y); v[6] += __uint_as_float(a1.z); v[7] += __uint_as_float(a1.w);
        v[8] += a2.x; v[9] += a2.y;
    };
    auto row_max = [&](const float (&v)[10]) {
        float mx = fmaxf(fmaxf(fmaxf(v[0], v[1]), fmaxf(v[2], v[3])), fmaxf(fmaxf(v[4], v[5]), fmaxf(v[6], v[7])));
        mx = fmaxf(mx, fmaxf(v[8], v[9]));
        mx = fmaxf(mx, __shfl_xor_sync(0xffffffff, mx, 1));
        return fmaxf(mx, __shfl_xor_sync(0xffffffff, mx, 2)) * CH_SC;
    };
    auto local_pv = [&](int s, int st) {
        float dc[16];
        wgmma_fence();
#pragma unroll
        for (int ks = 0; ks < 3; ks++) wgmma_ss_n32_p(dc, desc_lo(sd + CO_T + (2 + (s & 1)) * CH_TW + ks * 2048, 16), desc_lo(sd + CO_P + ks * 256, 128), ks != 0);
        wgmma_commit();
        wgmma_wait<0>();
        store32(dc, aO - CH_TW + st);
    };
    float gs = 0.f;
    auto load_gate = [&](int s) { asm volatile("ld.global.cg.f32 %0, [%1];" : "=f"(gs) : "l"(g_gate + s * SEGL + t4 * 8 + qd) : "memory"); };
    auto softmax = [&](int s, float (&u)[11]) {
        float v[10];
        {
            const uint4 a0 = lds128(aL + CO_OWN + t4 * 1024), a1 = lds128(aL + CO_OWN + t4 * 1024 + 512);
            const float2 a2 = lds64f(aL + CO_OWN2 + t4 * 256 - lane * 8);
            v[0] = __uint_as_float(a0.x); v[1] = __uint_as_float(a0.y); v[2] = __uint_as_float(a0.z); v[3] = __uint_as_float(a0.w);
            v[4] = __uint_as_float(a1.x); v[5] = __uint_as_float(a1.y); v[6] = __uint_as_float(a1.z); v[7] = __uint_as_float(a1.w);
            v[8] = a2.x; v[9] = a2.y;
        }
        mbar_wait_cl(bar_l, s & 1);
        add_scores(aL + t4 * 1024 + CO_LS + (s & 1) * 5120, aL + t4 * 256 - lane * 8 + CO_LS + (s & 1) * 5120 + 4096, v);
        const int lim = t4 * 8 + qd - 2 * qc;
#pragma unroll
        for (int j = 0; j < 8; j++) if ((j >> 1) * 8 + (j & 1) > lim) v[j] = -INFINITY;
        const float mx = row_max(v);
#pragma unroll
        for (int j = 0; j < 10; j++) u[j] = v[j];
        u[10] = mx;
    };
    auto softmax1 = [&](float (&u)[11]) {
#pragma unroll
        for (int j = 0; j < 10; j++) u[j] = ex2f(fmaf(u[j], CH_SC, -u[10]));
        u[10] = (((u[0] + u[1]) + (u[2] + u[3])) + ((u[4] + u[5]) + (u[6] + u[7]))) + (u[8] + u[9]);
    };
    auto softmax2 = [&](float (&v)[11]) {
        float sum = v[10];
        sum += __shfl_xor_sync(0xffffffff, sum, 1);
        sum += __shfl_xor_sync(0xffffffff, sum, 2);
        asm("rcp.approx.ftz.f32 %0, %0;" : "+f"(sum));
        sum *= 1.f - gs;
        const uint32_t pa = aL + CO_P + t4 * 768;
        stmatrix_x4(pa, pack_bf16(v[0] * sum, v[1] * sum), pack_bf16(v[2] * sum, v[3] * sum), pack_bf16(v[4] * sum, v[5] * sum), pack_bf16(v[6] * sum, v[7] * sum));
        asm volatile("stmatrix.sync.aligned.m8n8.x1.shared.b16 [%0], {%1};" :: "r"(pa + 512), "r"(pack_bf16(v[8] * sum, v[9] * sum)) : "memory");
    };
    if (mapa_u32(bar_l, rank ^ 1) != (bar_l ^ (1u << 24)) || mapa_u32(bar_l, (rank + 3) & 7) != bar_l + roff(3)) __trap();
    asm volatile("bar.sync %0, 128;" :: "r"(12 + wg) : "memory");
    if (__shfl_sync(0xffffffff, tid, 1) < 256) {
#pragma unroll 1
        for (int rep = CH_DRY ? 0 : 1; rep < 2; rep++) {
            if (rep) mbar_wait(bar_w + 8 * wg, 0);
            PT(3, 0);
            load_w(wg, false);
            if (rep) {
                asm volatile("bar.arrive %0, 160;" :: "r"(wg ? 2 : 15) : "memory");
                asm volatile("barrier.cluster.arrive.relaxed.aligned;" ::: "memory");
                mbar_wait(bar_x, 0);
            }
            asm volatile("bar.sync 12, 256;" ::: "memory");
            PT(7, 0);
            float d[16];
            pass(d, wg, 0, 0, 16, -1);
            wgmma_wait<0>();
            store32(d, aO + CO_T + (1 - 2 * wg) * CH_TW);
            pass(d, wg, 0, 0, 16, 0);
            asm volatile("bar.sync 13, 256;" ::: "memory");
            uint32_t r[8];
            load32(r, aO + CO_T);
            add32(d, r, aO + CO_T);
        }
    }
    PT(8, 0);
    TS_BEGIN(5);
    PT(9, 0);

    if (wg < 2) {
        const uint32_t aM = pin(sb + CO_XB + 4096 + (lane & 7) * 128 + (((lane >> 3) ^ (lane & 7)) << 4));
        uint32_t coff[4];
#pragma unroll
        for (int i = 0; i < 4; i++) coff[i] = uni(chunk(mine(wg, i)) * CH_XC);
        auto mem_proj = [&](int s, auto gc) {
            constexpr int G = decltype(gc)::value;
            const uint32_t par = s & 1;
            float acc[4][4];
#pragma unroll
            for (int i = 0; i < 4; i++) acc[i][0] = acc[i][1] = acc[i][2] = acc[i][3] = 0.f;
            const uint32_t am = aM + par * CH_XP;
            uint32_t b[4][4], ok = 1;
            auto bar = [&](int c) { return bar_mem + 8 * CH_MB(mine(G, c)); };
            auto load = [&](int c) {
                if (c ? CH_MB(mine(G, c)) != CH_MB(mine(G, c - 1)) : G == 0)
                    asm volatile("{\n.reg .pred p, q;\n.reg .u32 c;\nsetp.ne.u32 p, %2, 0;\n@p bra MP_DONE;\nmov.u32 c, 0;\n"
                                 "MP_LOOP:\nmbarrier.try_wait.parity.shared::cta.b64 p, [%0], %1;\nadd.u32 c, c, 1;\nsetp.lt.and.u32 q, c, %3, !p;\n"
                                 "@q bra MP_LOOP;\nMP_DONE:\n}" :: "r"(bar(c)), "r"(par ^ 1), "r"(ok), "n"(WAIT_LIMIT / 64) : "memory");
                uint32_t* r = b[2 * c & 3];
                ldmatrix_x4(r[0], r[1], r[2], r[3], am + coff[c]);
                r = b[(2 * c + 1) & 3];
                ldmatrix_x4(r[0], r[1], r[2], r[3], (am ^ 64) + coff[c]);
                if (c < 3 && CH_MB(mine(G, c + 1)) != CH_MB(mine(G, c))) ok = mbar_try(bar(c + 1), par ^ 1);
            };
            auto mma = [&](int i) {
#pragma unroll
                for (int j = 0; j < 4; j++) {
                    const uint32_t* a = w[(i >> 1) * 8 + ((j & 1) ^ G) * 4 + (i & 1) * 2 + (j >> 1)];
                    mma_16816(acc[j], a[0], a[1], a[2], a[3], b[i & 3][j & 2], b[i & 3][(j & 2) + 1]);
                }
            };
#pragma unroll
            for (int e = 0; e < CH_NSM; e++) ldmatrix_x4_trans(w[e][0], w[e][1], w[e][2], w[e][3], aO + CO_WA + e * 2048);
            if (G == 1) asm volatile("bar.sync 10, %0;" :: "n"(CH_QL < 16 ? 384 : 256) : "memory");
            else ok = mbar_try(bar(0), par ^ 1);
            DBG(11, 0);
            load(0);
#pragma unroll
            for (int c = 0; c < 3; c++) {
                const int at = (CH_ML >> (c * 4 + G * 12)) & 3;
                if (at == 0) load(c + 1);
                mma(2 * c);
                if (at == 1) load(c + 1);
                mma(2 * c + 1);
                if (at == 2) load(c + 1);
            }
            mma(6);
            uint32_t dep = __float_as_uint(acc[CH_HA & 3][0]);
            mma(7);
            if (CH_HA >= 4) dep = __float_as_uint(acc[CH_HA & 3][0]);
            asm volatile("bar.arrive %0, 384;" :: "r"(5 | (dep & (s >> 10))) : "memory");
            uint32_t r[4];
#pragma unroll
            for (int i = 0; i < 4; i++) r[i] = pack_bf16(acc[i >> 1][(i & 1) * 2] + acc[(i >> 1) + 2][(i & 1) * 2], acc[i >> 1][(i & 1) * 2 + 1] + acc[(i >> 1) + 2][(i & 1) * 2 + 1]);
            DBGD(40 + warp, warp, r[0] ^ r[1]);
            asm volatile("{\n.reg .pred q;\nsetp.ne.s32 q, %3, 0;\n"
                         "@q stmatrix.sync.aligned.m8n8.x2.trans.shared.b16 [%0], {%1, %2};\n"
                         "@q stmatrix.sync.aligned.m8n8.x2.trans.shared.b16 [%0 + %4], {%1, %2};\n"
                         "@q stmatrix.sync.aligned.m8n8.x2.trans.shared.b16 [%0 + 2 * %4], {%1, %2};\n"
                         "@q stmatrix.sync.aligned.m8n8.x2.trans.shared.b16 [%0 + 3 * %4], {%1, %2};\n}"
                         :: "r"(aO + (CO_XB + 4096 + G * (CH_XC - CH_TW) + (par ^ 1) * CH_XP)), "r"(r[0]), "r"(r[1]),
                            "r"(s - (NSEG - 1)), "n"(2 * CH_XC) : "memory");
            stmatrix_x2_trans(aO + CO_T + (G ? 5120 : CH_TW + 4096), r[2], r[3]);
            fence_async_smem();
        };
        if (wg == 0) {
#pragma unroll 1
            for (int s = 0; s < NSEG; s++) {
                const uint32_t par = s & 1;
                mem_proj(s, std::integral_constant<int, 0>());
                asm volatile("bar.arrive 1, 256;" ::: "memory");
                asm volatile("bar.sync 8, 384;" ::: "memory");
                if (s == NSEG - 1) break;
                if (tid == 96) {
#pragma unroll
                    for (int j = 1; j < 8; j++) {
                        int n = 0;
                        for (int i = 1; i < 8; i++) n += CH_MB(i) == j;
                        if (n) mbar_expect_tx(bar_mem + 8 * j, 1024 * n);
                        if (j < 4) mbar_expect_tx(bar_o + 8 * j - 8, 512 << j);
                    }
                }
                __syncwarp();
                uint32_t* wp = g_xbuf + (size_t)rank * 2048 + C * 256 + qc * 64 + t4 * 8 + qd;
                asm volatile("st.relaxed.gpu.global" CH_SQ ".u32 [%0], %1;" :: "l"(wp + ((s + 2) & 3) * 16384), "r"(~0u) : "memory");
                asm volatile("st.relaxed.gpu.global" CH_SQ ".u32 [%0], %1;" :: "l"(wp + ((s + 2) & 3) * 16384 + 32), "r"(~0u) : "memory");
                if (__builtin_expect(s == 0, 0)) {
                    asm volatile("barrier.cluster.wait.aligned;" ::: "memory");
                    mbar_wait(bar_wo, 0);
                    const int sr = (qd >> 2) * 2 + (qd & 1) + (qd & 2) * 4;
#pragma unroll 2
                    for (int ks = t4; ks < 32; ks += 4) {
                        const uint32_t a = sb + CO_WO + ks * 2048;
                        uint4 u[2][2];
#pragma unroll
                        for (int i = 0; i < 4; i++) { const int r = sr + (i >> 1) * 4; u[i >> 1][i & 1] = lds128(a + r * 128 + (((qc * 2 + (i & 1)) ^ (r & 7)) << 4)); }
                        __syncwarp();
#pragma unroll
                        for (int i = 0; i < 4; i++) {
                            const uint4 u0 = u[i >> 1][0], u1 = u[i >> 1][1];
                            const uint32_t sel = (i & 1) ? 0x7632 : 0x5410;
                            sts128(a + (qd + (i >> 1) * 8) * 128 + (((qc * 2 + (i & 1)) ^ qd) << 4),
                                   __byte_perm(u0.x, u0.y, sel), __byte_perm(u0.z, u0.w, sel), __byte_perm(u1.x, u1.y, sel), __byte_perm(u1.z, u1.w, sel));
                        }
                    }
                    fence_async_smem();
                }
                mbar_wait(bar_x + 8 * (par ^ 1), ((s + 1) >> 1) & 1);
                asm volatile("bar.sync 7, 384;" ::: "memory");
                float d[16];
                float c[4];
                const uint32_t alo = desc_lo(sd + CO_WO, 16), blo = desc_lo(sd + CO_OB, 128);
                wgmma_fence();
                pass(d, 0, par ^ 1, 0, CH_Q0, -1, false);
                asm volatile("bar.sync 11, 256;" ::: "memory");
#pragma unroll
                for (int i = 0; i < 32; i++) {
                    if (i == 4) { pass(d, 0, par ^ 1, CH_Q0 + min(4, CH_QI), CH_Q0 + min(4, CH_QI) + CH_QX, -1, false); mbar_wait_cl(bar_o, par); }
                    if (i == 8) mbar_wait_cl(bar_o + 8, par);
                    if (i == CH_OW) mbar_wait_cl(bar_o + 16, par);
                    wgmma_ss_n8(c, alo + i * 128, blo + i * 16, i != 0);
                    if (i < CH_QI) pass(d, 0, par ^ 1, CH_Q0 + i + (i < 4 ? 0 : CH_QX), CH_Q0 + i + (i < 4 ? 0 : CH_QX) + 1, -1, false);
                }
                wgmma_commit();
                wgmma_wait<0>();
                asm volatile("st.relaxed.gpu.global" CH_SQ ".u32 [%0], %1;" :: "l"(wp + (s & 3) * 16384), "r"(pack_bf16(c[0], c[2])) : "memory");
                asm volatile("st.relaxed.gpu.global" CH_SQ ".u32 [%0], %1;" :: "l"(wp + (s & 3) * 16384 + 32), "r"(pack_bf16(c[1], c[3])) : "memory");
                asm volatile("bar.arrive 6, 384;" ::: "memory");
                pace(CH_QD);
                asm volatile("bar.arrive 4, 384;" ::: "memory");
                DBG(8, 0);
                if (CH_Q1 < 16) pass(d, 0, par ^ 1, CH_Q1, 16, -1);
                asm volatile("bar.sync 9, 256;" ::: "memory");
                wgmma_wait<0>();
                store32(d, aO + CO_T + CH_TW);
                asm volatile("bar.arrive 12, 256;" ::: "memory");
                if (CH_QL) pass(d, 0, (par ^ 1) + (s >> 10), 0, CH_QL, CH_QS);
                DBG(21, 0);
                if (tid == 0) {
                    if (s + 2 < NSEG) {
                        mbar_expect_tx(bar_x + 8 * par, 32768);
                        tma_load_2d_mc(sb + CO_XB + par * CH_XP + rank * CH_XC, &P.mapX, bar_x + 8 * par, rank * 64, (s + 2) * SEGL, (uint16_t)0xff);
                        if (CH_XPF) asm volatile("cp.async.bulk.prefetch.tensor.2d.L2.global [%0, {%1, %2}];" :: "l"(&P.mapX), "r"(rank * 64), "r"((s + 2 + CH_XPF) * SEGL) : "memory");
                    } else {
#pragma unroll 1
                        for (int i = 0; i < 8; i++) tma_load_2d(sb + CO_WO + i * 8192, &P.mapWo, bar_wo, (rank & 3) * 128 + (i & 1) * 64, (h & ~1) * HD + (i >> 1) * 64);
                    }
                }
                __syncwarp();
                asm volatile("bar.sync 13, 256;" ::: "memory");
                uint32_t r[8];
                load32(r, aO + CO_T);
                if (CH_QL < 16) {
                    asm volatile("bar.sync 10, 384;" ::: "memory");
                    pass(d, 0, (par ^ 1) + (s >> 10), CH_QL, CH_QE, CH_QS);
                }
                add32(d, r, aO + CO_T);
                DBG(22, 0);
            }
            *reinterpret_cast<uint2*>(g_xbuf + 16384 + blockIdx.x * 256 + tid * 2) = make_uint2(~0u, ~0u);
        PT(10, 0);
            if (tid == 0) {
                mbar_expect_tx(bar_wo, 65536 + 32768);
                mbar_expect_tx(bar_w, 24576);
                asm volatile("prefetch.tensormap [%0];" :: "l"(&P.mapOut) : "memory");
                wait_ctr(CT_CA + 63, 16u);
            }
            __syncwarp();
            uint32_t fin = 0;
#pragma unroll 1
            for (int r = 0; r < 2; r++) {
                float acc[64];
                mbar_wait(bar_wo, 1);
                asm volatile("bar.sync %0, 256;" :: "r"(15 - r) : "memory");
                asm volatile("{\n.reg .pred p;\nsetp.eq.b32 p, %2, 32;\n@p atom.relaxed.gpu.global.inc.u32 %0, [%1], 0x7fffffff;\n}"
                             : "+r"(fin) : "l"(&g_ctr[CT_FIN]), "r"(tid + r * 128) : "memory");
                wgmma_fence();
#pragma unroll
                for (int i = 0; i < 16; i++) {
                    const uint32_t c = (rank + (i >> 2)) & 3;
                    const uint32_t a = r == 0 ? tail_a(c) : i < 4 ? CO_WA + CH_TW : CO_XB + CH_XP + c * 8192;
                    if (i == 4) mbar_wait(r ? bar_w : bar_wo, 1);
                    wgmma_ss_n128_lo<1>(acc, desc_lo(sd + a, 16) + (i & 3) * 2, desc_lo(sd + CO_WO, 8192) + c * 1024 + (i & 3) * 128, i);
                }
                wgmma_commit();
                wgmma_wait<0>();
                PT(5, 0);
                out_flush_half(acc, &P.mapOut, sb + (r ? tail_a(0) : CO_T), tid, 12, (rank & 3) * 128, SEQ - 128 + r * 64);
            }
            if (fin == M_GRID + 64 - 1)
                for (int i = 0; i < CT_N / 4; i++) reinterpret_cast<uint4*>(g_ctr)[i] = make_uint4(0u, 0u, 0u, 0u);
            if (tid == 0) {
                asm volatile("cp.async.bulk.wait_group.read 0;" ::: "memory");
                PT(15, 0);
            }
        } else {
            const uint32_t usc = uni(CO_SC + min(t4, 2) * 512 + roff((rank ^ 1) - rank)), uscb = uni(bar_sc ^ (1u << 24));
            const uint32_t vaddr = pin(sb + CO_T + 2 * CH_TW + (lane & 15) * 128 + (((t4 * 2 + (lane >> 4)) ^ (lane & 7)) << 4));
            const uint32_t dsta = pin(sb + CO_OB + t4 * 256 + (qc >> 1) * 128 + qd * 16 + (qc & 1) * 8);
            auto store_ctx = [&](int s) {
                if (tid == CH_ST && (uint32_t)s < NSEG - 3) {
                    tma_store_2d(&P.mapC, sb + CO_ST, (rank & 1) * 64, h * SEQ + s * SEGL);
                    asm volatile("cp.async.bulk.commit_group;" ::: "memory");
                }
                __syncwarp();
            };
            auto signal_ctx = [&](int s) {
                if (tid == CH_ST && (s & 3) == 1)
                    asm volatile("cp.async.bulk.wait_group 0;\nred.relaxed.gpu.global.add.u32 [%0], 1;" :: "l"(&g_ctr[CT_CB - 1 + (s >> 2)]) : "memory");
                __syncwarp();
            };
            uint32_t uo[8], ub[8];
#pragma unroll
            for (int i = 0; i < 8; i++) { uo[i] = uni(roff(i) + i * 1024); ub[i] = uni(roff(i) + bar_o + (i < 2 ? 0 : i < 4 ? 8 : 16)); }
#pragma unroll 1
            for (int s = 0; s < NSEG; s++) {
                const uint32_t par = s & 1;
                mem_proj(s, std::integral_constant<int, 1>());
                asm volatile("bar.sync 1, 256;" ::: "memory");
                float d[24];
                scores(d, std::integral_constant<int, CH_XC>(), CO_XB + 4096 + (par ^ 1) * CH_XP);
                if (s == NSEG - 1) { wgmma_wait<0>(); break; }
                asm volatile("bar.arrive 8, 384;" ::: "memory");
                if (s == 0) asm volatile("barrier.cluster.wait.aligned;" ::: "memory");
                const uint32_t sca = (aL | (s >> 10)) + usc;
                wgmma_wait<0>();
                float v[10], u[12];
#pragma unroll
                for (int j = 0; j < 12; j++) u[j] = d[(j >> 1) * 4 + (j & 1)] + d[(j >> 1) * 4 + (j & 1) + 2];
                if (t4 < 3) {
                    auto sel = [&](int j) { return t4 == 0 ? u[j] : t4 == 1 ? u[4 + j] : u[8 + j]; };
                    asm volatile("st.async.weak.shared::cluster.mbarrier::complete_tx::bytes.v4.f32 [%0], {%2, %3, %4, %5}, [%1];"
                                 :: "r"(sca), "r"(uscb), "f"(sel(0)), "f"(sel(1)), "f"(sel(2)), "f"(sel(3)) : "memory");
                }
#pragma unroll
                for (int j = 0; j < 10; j++) v[j] = j < 8 ? u[j] : u[j] + u[j + 2];
                DBG(3, 4);
                if (CH_ES) signal_ctx(s); else store_ctx(s - 2);
                uint32_t vb[3][4];
                auto load_v = [&](float dep) {
                    asm volatile("bar.sync %0, 256;" :: "r"(CH_VD ? 3 | (__float_as_uint(dep) & (s >> 10)) : 3) : "memory");
#pragma unroll
                    for (int k = 0; k < 3; k++) ldmatrix_x4_trans(vb[k][0], vb[k][1], vb[k][2], vb[k][3], vaddr + par * CH_TW + k * 2048);
                };
                mbar_wait_cl(bar_sc, par);
                DBG(4, 4);
                {
                    const uint4 a0 = lds128(aL + CO_SC), a1 = lds128(aL + CO_SC + 512), a2 = lds128(aL + CO_SC + 1024);
                    v[0] += __uint_as_float(a0.x); v[1] += __uint_as_float(a0.y); v[2] += __uint_as_float(a0.z); v[3] += __uint_as_float(a0.w);
                    v[4] += __uint_as_float(a1.x); v[5] += __uint_as_float(a1.y); v[6] += __uint_as_float(a1.z); v[7] += __uint_as_float(a1.w);
                    v[8] += __uint_as_float(a2.x) + __uint_as_float(a2.z); v[9] += __uint_as_float(a2.y) + __uint_as_float(a2.w);
                }
                const float mx = row_max(v);
                if (CH_VPOS == 2) load_v(mx);
#pragma unroll
                for (int j = 0; j < 10; j++) v[j] = ex2f(fmaf(v[j], CH_SC, -mx));
                uint32_t p[5];
#pragma unroll
                for (int j = 0; j < 5; j++) p[j] = pack_bf16(v[2 * j], v[2 * j + 1]);
                if (CH_VPOS == 3) load_v(v[CH_VD]);
                DBG(19, 4);
                float c0[4] = {0.f, 0.f, 0.f, 0.f}, c1[4] = {0.f, 0.f, 0.f, 0.f}, cs[4] = {0.f, 0.f, 0.f, 0.f};
#pragma unroll
                for (int k = 0; k < 3; k++) {
                    const uint32_t p0 = p[2 * k], p1 = k < 2 ? p[2 * k + 1] : 0u;
                    mma_16816(cs, p0, 0u, p1, 0u, 0x3f803f80u, 0x3f803f80u);
                    mma_16816(c0, p0, 0u, p1, 0u, vb[k][0], vb[k][1]);
                    mma_16816(c1, p0, 0u, p1, 0u, vb[k][2], vb[k][3]);
                }
                float inv;
                asm volatile("rcp.approx.ftz.f32 %0, %1;" : "=f"(inv) : "f"(cs[0]));
                const uint32_t b0 = pack_bf16(c0[0] * inv, c0[1] * inv), b1 = pack_bf16(c1[0] * inv, c1[1] * inv);
                DBG(20, 4);
#pragma unroll
                for (int i = 1; i < 8; i++) {
                    st_async_v2((dsta | (s >> 10)) + uo[i], b0, b1, ub[i]);
                    if (i == CH_OS) asm volatile("st.shared.v2.b32 [%0], {%1, %2};" :: "r"(dsta), "r"(b0), "r"(b1) : "memory");
                    if (i == CH_OFE) asm volatile("fence.proxy.async.shared::cta;\nbar.arrive 11, 256;" ::: "memory");
                }
                DBG(5, 4);
                asm volatile("cp.async.bulk.wait_group.read 0;" ::: "memory");
                asm volatile("bar.sync 7, 384;" ::: "memory");
                if (CH_OFE > 7) asm volatile("fence.proxy.async.shared::cta;\nbar.arrive 11, 256;" ::: "memory");
                local_pv(s + 1, CO_ST);
                if (CH_ES) fence_async_smem();
                asm volatile("bar.arrive 6, 384;" ::: "memory");
                if (tid == 128) mbar_expect_tx(bar_sc, 1536);
                __syncwarp();
                if (CH_SG == 1) signal_ctx(s);
                mbar_wait(bar_x + 8 * (par ^ 1), ((s + 1) >> 1) & 1);
                if (CH_SG == 2) signal_ctx(s);
                asm volatile("bar.sync 4, 384;" ::: "memory");
                float dk[16];
                pass(dk, 1, par ^ 1, 0, 16, -1);
                wgmma_wait<0>();
                store32(dk, aO + CO_T - CH_TW);
                asm volatile("bar.arrive 13, 256;" ::: "memory");
                pass(dk, 1, (par ^ 1) + (s >> 10), 0, CH_KE, CH_KS);
                if (CH_ES) store_ctx(s - 1); else if (!CH_SG) signal_ctx(s);
                DBG(1, 4);
                asm volatile("bar.sync 12, 256;" ::: "memory");
                uint32_t r[8];
                load32(r, aO + CO_T);
                add32(dk, r, aO + CO_T);
                DBG(29, 4);
            }
        }
    } else {
        {
            PT(2, 256);
            int lane;
            asm volatile("mov.u32 %0, %%laneid;" : "=r"(lane));
            if (t4 >= 2) {
                const CUtensorMap* map = t4 == 2 ? &P.mapWo : &P.mapW[2];
                const uint32_t bar = t4 == 2 ? bar_wo : bar_w + 16;
                const int c0 = t4 == 2 ? rank * 64 : wcol;
                auto row = [&](int i) { return t4 == 2 ? C * 512 + ((rank - i) & 7) * 64 : (int)chunk(i >> 1) * 64 + (i & 1) * 32; };
                uint32_t now;
                do { asm volatile("mov.u32 %0, %%clock;" : "=r"(now)); } while (now - t_start < (uint32_t)(t4 == 2 ? CH_D2 : CH_D1));
                if (lane == 0) {
#pragma unroll 1
                    for (int i = 0; i < (CH_PF == 2 ? t4 * 8 - 8 : CH_PF * (t4 * 16 - 32)); i++) asm volatile("cp.async.bulk.prefetch.tensor.2d.L2.global [%0, {%1, %2}];" :: "l"(map), "r"(c0), "r"(row(i)) : "memory");
                    mbar_expect_tx(bar, 65536);
                }
                __syncwarp();
                asm volatile("bar.sync %0, 160;" :: "r"(t4 == 2 ? 15 : 2) : "memory");
                if (lane == 0) {
#pragma unroll 1
                    for (int i = 0; i < t4 * 8 - 8; i++) tma_load_2d(sb + (t4 == 2 ? CO_WO + i * 8192 : vdst(i)), map, bar, c0, row(i));
                }
            } else if (t4 == 0 && lane == 0) {
                asm volatile("cp.async.bulk.prefetch.tensor.2d.L2.global [%0, {%1, %2}];" :: "l"(&P.mapX), "r"(rank * 64), "r"(SEGL) : "memory");
                asm volatile("prefetch.tensormap [%0];" :: "l"(&P.mapC) : "memory");
                mbar_expect_tx(bar_sc, 1536);
                mbar_expect_tx(bar_x + 8, 32768);
            }
            __syncwarp();
            mbar_wait(bar_w + 16, 0);
            PT(4, 256);
            load_w(2, true);
            asm volatile("bar.sync 14, 128;" ::: "memory");
            asm volatile("barrier.cluster.arrive.relaxed.aligned;" ::: "memory");
            if ((CH_XS || t4 == 0) && lane == 0) {
#pragma unroll 1
                for (int i = CH_XS ? t4 : 0; i < 8; i += CH_XS ? 4 : 1) tma_load_2d(sb + CO_XB + CH_XP + i * CH_XC, &P.mapX, bar_x + 8, i * 64, SEGL);
            }
            __syncwarp();
            PT(6, 256);
        }
#pragma unroll 1
        for (int s = 0; s < NSEG; s++) {
            const uint32_t par = s & 1;
            const bool last = s == NSEG - 1;
            if (CH_GL < 2) {
                if (s == 1) wait_ctr(CT_GATE, 256u);
                load_gate(max(s - 1, 0));
                if (CH_GL) asm volatile("prefetch.global.L2 [%0];" :: "l"(g_gate + ((s + 1) & (NSEG - 1)) * SEGL) : "memory");
            } else if (s == 1) { wait_ctr(CT_GATE, 256u); load_gate(0); }
            float v[11];
            if (CH_SP) fence_async_smem();
            softmax(s - 1, v);
            if (CH_SP < 2) softmax1(v);
            DBG(7, 8);
            if (!CH_SP) fence_async_smem();
            asm volatile("bar.sync %0, 384;" :: "r"(CH_SP ? 5 | (__float_as_uint(v[10]) & (s >> 10)) : 5) : "memory");
            DBG(23, 8);
            float dv[20], d[24];
            pass(dv, 2, par, 0, CH_VA, CH_VS);
            asm volatile("bar.sync 8, 384;" ::: "memory");
            pass(dv, 2, par, CH_VA, 32, CH_VS);
            if (CH_SP == 2) {
                uint32_t z;
                asm volatile("mov.u32 %0, %%clock;" : "=r"(z) :: "memory");
                v[10] = __uint_as_float(__float_as_uint(v[10]) | (z & (s >> 10)));
                softmax1(v);
                asm volatile("{\n.reg .pred p;\nsetp.ne.s32 p, %0, 1000001;\n@p bra SP_SKIP;\nwgmma.wait_group.sync.aligned 0;\n"
                             "st.volatile.shared.f32 [%0], %1;\nexit;\nSP_SKIP:\n}" :: "r"(s), "f"(v[10]) : "memory");
            }
            wgmma_wait<0>();
            stmatrix_x2_trans(aO + par * CH_TW + CO_T + 4096, pack_bf16(dv[16], dv[17]), pack_bf16(dv[18], dv[19]));
            store32(dv, aO + par * CH_TW + CO_T);
            DBG(24, 8);
            uint32_t z3 = __float_as_uint(dv[0]);
            if (CH_A3) asm volatile("{\n.reg .pred p;\nsetp.ne.s32 p, %1, %2;\n@p bar.arrive 3, 256;\nmov.u32 %0, %%clock;\n}" : "=r"(z3) : "r"(s), "n"(NSEG - 1) : "memory");
            else if (!last) asm volatile("bar.arrive 3, 256;" ::: "memory");
            if (CH_SP) { v[10] = __uint_as_float(__float_as_uint(v[10]) | (z3 & (s >> 10))); softmax2(v); fence_async_smem(); }
            if (CH_GL == 2) load_gate(s);
            if (last) asm volatile("bar.arrive 7, 256;" ::: "memory"); else asm volatile("bar.sync 7, 384;" ::: "memory");
            scores(d, std::integral_constant<int, 512>(), CO_T);
            asm volatile("{\n.reg .pred p;\nsetp.eq.s32 p, %1, 256;\n@p mbarrier.arrive.expect_tx.shared::cta.b64 _, [%0], 5120;\n}" :: "r"(bar_l), "r"(tid) : "memory");
            wgmma_wait<0>();
            d[16] += d[20]; d[17] += d[21];
            auto send_scores = [&]() {
                const uint32_t a = aL + t4 * 1024, a2 = aL + t4 * 256 - lane * 8, r = roff((rank ^ 1) - rank) + CO_LS + par * 5120;
                asm volatile("st.async.weak.shared::cluster.mbarrier::complete_tx::bytes.v4.f32 [%0], {%3, %4, %5, %6}, [%2];\n"
                             "st.async.weak.shared::cluster.mbarrier::complete_tx::bytes.v4.f32 [%0 + 512], {%7, %8, %9, %10}, [%2];\n"
                             "st.async.weak.shared::cluster.mbarrier::complete_tx::bytes.v2.f32 [%1], {%11, %12}, [%2];"
                             :: "r"(a + r), "r"(a2 + r + 4096), "r"(bar_l ^ (1u << 24)), "f"(d[0]), "f"(d[1]), "f"(d[4]), "f"(d[5]),
                                "f"(d[8]), "f"(d[9]), "f"(d[12]), "f"(d[13]), "f"(d[16]), "f"(d[17]) : "memory");
            };
            auto keep_scores = [&]() {
                const uint32_t a = aL + t4 * 1024, a2 = aL + t4 * 256 - lane * 8;
                sts128(a + CO_OWN, __float_as_uint(d[0]), __float_as_uint(d[1]), __float_as_uint(d[4]), __float_as_uint(d[5]));
                sts128(a + CO_OWN + 512, __float_as_uint(d[8]), __float_as_uint(d[9]), __float_as_uint(d[12]), __float_as_uint(d[13]));
                asm volatile("st.shared.v2.f32 [%0], {%1, %2};" :: "r"(a2 + CO_OWN2), "f"(d[16]), "f"(d[17]) : "memory");
            };
            if (s == 0) asm volatile("barrier.cluster.wait.aligned;" ::: "memory");
            if (CH_LSS == 0) send_scores();
            if (CH_KEEP == 0) keep_scores();
            if (last) { if (CH_LSS) send_scores(); if (CH_KEEP) keep_scores(); break; }
            asm volatile("bar.arrive 4, 384;\nbar.arrive 9, 256;" ::: "memory");
            uint32_t t0, t1;
            if (!CH_PINB) asm volatile("bar.sync 6, 384;\nmov.u32 %0, %%clock;" : "=r"(t0) :: "memory");
            const int row = t4 * 2 + (lane >> 4);
            const uint32_t dsta = pin(sb + CO_XB + (par ^ 1) * CH_XP + rank * CH_XC + 4096 + row * 128 + ((((lane & 15) >> 1) ^ row) << 4) + (lane & 1) * 8);
            uint32_t dst1 = pin(dsta + roff(1)), bar1 = pin((bar_mem + 8 + roff(1)) | (s >> 10));
            uint32_t sel = pin(((qd >> 1) == qc ? 0x3f80u << (qd & 1) * 16 : 0u) | (s >> 10));
            const uint2* xb = reinterpret_cast<const uint2*>(g_xbuf + (s & 3) * 16384 + (size_t)rank * 2048 + t4 * 64) + pin(lane | (s >> 10));
            if (CH_PINB) asm volatile("bar.sync %1, 384;\nmov.u32 %0, %%clock;" : "=r"(t0) : "r"(6 | (dst1 & sel & (uint32_t)(size_t)xb & (s >> 10))) : "memory");
            if (CH_LSS == 1) send_scores();
            if (CH_KEEP == 2) keep_scores();
            uint2 p[8], q[8];
            do { asm volatile("mov.u32 %0, %%clock;" : "=r"(t1) :: "memory"); } while (t1 - t0 < CH_POLL_DELAY);
#pragma unroll
            for (int k = 0; k < 8; k++)
                asm volatile("ld.relaxed.gpu.global" CH_LQ ".v2.u32 {%0, %1}, [%2];" : "=r"(p[k].x), "=r"(p[k].y) : "l"(xb + k * 128) : "memory");
            DBG(17, 8);
            if (CH_LSS == 2) send_scores();
            if (CH_KEEP == 1) keep_scores();
            {
                uint32_t z;
                asm volatile("mov.u32 %0, %%clock;" : "=r"(z) :: "memory");
#pragma unroll
                for (int i = 0; i < CH_GAP; i++) asm volatile("{\n.reg .f32 f;\nmov.b32 f, %0;\nex2.approx.ftz.f32 f, f;\nmov.b32 %0, f;\n}" : "+r"(z));
                asm volatile("and.b32 %0, %0, %1;" : "+r"(z) : "r"(s >> 10));
                xb += z;
            }
#pragma unroll
            for (int k = 0; k < 8; k++)
                asm volatile("ld.relaxed.gpu.global" CH_LQ ".v2.u32 {%0, %1}, [%2];" : "=r"(q[k].x), "=r"(q[k].y) : "l"(xb + k * 128) : "memory");
            if (CH_LSS == 3) send_scores();
            if (CH_KEEP == 3) keep_scores();
            uint32_t m0, m1;
            {
                uint32_t z;
                asm volatile("mov.u32 %0, %%clock;" : "=r"(z) :: "memory");
                sel |= z & (s >> 10);
            }
            auto sum = [&](const uint2 (&p)[8]) {
                float c[CH_SUMC][4];
#pragma unroll
                for (int k = 0; k < 4; k++) {
                    if (k < CH_SUMC) c[k][0] = c[k][1] = c[k][2] = c[k][3] = 0.f;
                    mma_16816(c[k % CH_SUMC], p[2 * k].x, p[2 * k].y, p[2 * k + 1].x, p[2 * k + 1].y, sel, sel);
                }
#pragma unroll
                for (int k = 1; k < CH_SUMC; k++) { c[0][0] += c[k][0]; c[0][1] += c[k][1]; c[0][2] += c[k][2]; c[0][3] += c[k][3]; }
                m0 = pack_bf16(c[0][0], c[0][1]);
                m1 = pack_bf16(c[0][2], c[0][3]);
                uint32_t ok;
                asm volatile("{\n.reg .pred p;\nsetp.num.f32 p, %1, %2;\nvote.sync.all.pred p, p, 0xffffffff;\nselp.u32 %0, 1, 0, p;\n}" : "=r"(ok) : "f"(c[0][0]), "f"(c[0][2]));
                return ok;
            };
            if (__builtin_expect(!sum(p), 0)) {
                DBG(12, 8);
#pragma unroll 1
                for (int it = 0; it < WAIT_LIMIT / 4; it++) {
                    if (sum(q)) break;
                    uint32_t bad = 0;
#pragma unroll
                    for (int k = 0; k < 8; k++) bad |= (max(q[k].x, q[k].y) == ~0u ? 1u : 0u) << k;
                    if (__all_sync(0xffffffff, bad == 0u)) break;
                    if (it == 0) DBG(14, 8);
                    if (it == 1) DBG(15, 8);
#pragma unroll
                    for (int k = 0; k < 8; k++)
                        if (bad & (1u << k))
                            asm volatile("ld.relaxed.gpu.global" CH_LQ ".v2.u32 {%0, %1}, [%2];" : "=r"(q[k].x), "=r"(q[k].y) : "l"(xb + k * 128) : "memory");
                }
            }
            DBG(9, 8);
            st_async_v2(dst1, m0, m1, bar1);
            asm volatile("st.shared.v2.b32 [%0], {%1, %2};\nbar.arrive 10, %3;" :: "r"(dsta), "r"(m0), "r"(m1), "n"(CH_QL < 16 ? 384 : 256) : "memory");
#pragma unroll 1
            for (int i = 0; i < 6; i += CH_MP) {
#pragma unroll
                for (int j = 0; j < CH_MP; j++) {
                    dst1 = (dst1 + (1u << 24)) & 0x7ffffffu; bar1 = (bar1 + (1u << 24) + 8) & 0x7ffffffu;
                    st_async_v2(dst1, m0, m1, bar1);
                }
            }
            if (s == 1000000) {
#pragma unroll
                for (int k = 0; k < 8; k++) asm volatile("st.volatile.shared.v2.u32 [%0], {%1, %2};" :: "r"(s), "r"(q[k].x), "r"(q[k].y) : "memory");
            }
            DBG(10, 8);
        }
    }
    const int wgt = __shfl_sync(0xffffffff, tid >> 7, 0);
    if (wgt == 1) {
        asm volatile("bar.arrive 8, 384;" ::: "memory");
        auto copy = [&](uint32_t dst, uint32_t src, uint32_t bar) {
            asm volatile("cp.async.bulk.shared::cluster.shared::cta.mbarrier::complete_tx::bytes [%0], [%1], 4096, [%2];" :: "r"(dst), "r"(src), "r"(bar) : "memory");
        };
        const uint32_t peer = (uint32_t)(tid & 3) << 24;
        if ((tid & ~3) == CH_ST) {
            copy((sb + tail_a(rank & 3) + 4096) ^ peer, sb + CO_ST, bar_wo ^ peer);
            if (tid == CH_ST) {
                asm volatile("cp.async.bulk.wait_group 0;" ::: "memory");
                tma_load_2d_mc(sb + tail_a(rank & 3), &P.mapC, bar_wo, (rank & 1) * 64, h * SEQ + SEQ - 128, (uint16_t)(15 << (rank & 4)));
            }
        }
        __syncwarp();
        asm volatile("bar.sync 7, 256;" ::: "memory");
#pragma unroll 1
        for (int i = 0; i < 2; i++) {
            local_pv(i, CO_WA + CH_TW + i * 4096);
            fence_async_smem();
            asm volatile("bar.arrive %0, 256;" :: "r"(i ? 14 : 9) : "memory");
            asm volatile("bar.sync 2, 128;" ::: "memory");
            if (tid > 128 && tid < 132) {
                mbar_wait(sb + CO_BAR + 120, 0);
                copy((sb + CO_XB + CH_XP + (rank & 3) * 8192 + i * 4096) ^ peer, sb + CO_WA + CH_TW + i * 4096, bar_w ^ peer);
            }
            __syncwarp();
            if (i == 0) asm volatile("bar.sync 3, 256;" ::: "memory");
        }
        PT(14, 128);
    } else if (wgt == 2) {
        PT(11, 256);
        if (CH_GL < 2) load_gate(NSEG - 1);
        if ((tid & 31) < 4) asm volatile("mbarrier.arrive.relaxed.cluster.shared::cluster.b64 _, [%0];" :: "r"((sb + CO_BAR + 120) ^ ((tid & 3) << 24)) : "memory");
        asm volatile("bar.arrive 15, 256;\nbar.sync 9, 256;" ::: "memory");
        float v[11];
        softmax(NSEG - 1, v);
        softmax1(v);
        softmax2(v);
        fence_async_smem();
        asm volatile("bar.arrive 3, 256;" ::: "memory");
    }
    __syncthreads();
    asm volatile("barrier.cluster.arrive.relaxed.aligned;\nbarrier.cluster.wait.aligned;" ::: "memory");
    TS_END(2);
}

struct Proj2Params {
    CUtensorMap mapA[2];
    CUtensorMap mapW[3];
    bf16* out[3];
};
#define P2T(i)
#define P2_NOMMA 0
#define P2_NOLOAD 0
#define P2_ROT 4
#define P2_NP 1
#define P2_NI 4
constexpr int P2_STAGES = 6;
constexpr int P2_ITEMS = 168 + 48;

__device__ __forceinline__ int p2_reps(int t) { return t >= 168 ? 1 : 2; }
__device__ __forceinline__ void p2_tile(int t, int w, int& z, int& mp, int& head) {
    if (t >= 168) { w += ((t - 168) & 1) * 2; t = 168 + ((t - 168) >> 1); }
    const int hq = (t / 24 + P2_ROT) & 7, v = t % 24;
    mp = v & 7;
    if (v < 16) { head = hq * 4 + (v >> 3) * 2 + (w >> 1); z = 1 + (w & 1); }
    else { head = hq * 4 + w; z = 0; }
}
__device__ __forceinline__ void mbar_arrive_remote(uint32_t bar_cluster_addr) {
    asm volatile("mbarrier.arrive.release.cluster.shared::cluster.b64 _, [%0];" :: "r"(bar_cluster_addr) : "memory");
}
__device__ __forceinline__ void mbar_arrive_cl(uint32_t bar_cluster_addr) {
    asm volatile("mbarrier.arrive.shared::cluster.b64 _, [%0];" :: "r"(bar_cluster_addr) : "memory");
}
__device__ __forceinline__ void mbar_wait_acq_cluster(uint32_t bar, uint32_t parity) {
    asm volatile(
        "{\n"
        ".reg .pred p, q;\n"
        ".reg .u32 c;\n"
        "mov.u32 c, 0;\n"
        "WAIT_LOOP_C:\n"
        "mbarrier.try_wait.parity.acquire.cluster.shared::cta.b64 p, [%0], %1;\n"
        "@p bra WAIT_DONE_C;\n"
        "add.u32 c, c, 1;\n"
        "setp.lt.u32 q, c, 4000000;\n"
        "@q bra WAIT_LOOP_C;\n"
        "WAIT_DONE_C:\n"
        "}\n" :: "r"(bar), "r"(parity) : "memory");
}
__device__ __forceinline__ uint4 quad_transpose(uint32_t p0, uint32_t p1, uint32_t p2, uint32_t p3, int lane) {
    const bool o1 = lane & 1, o2 = lane & 2;
    uint32_t s0 = o1 ? p0 : p1, s1 = o1 ? p2 : p3;
    s0 = __shfl_xor_sync(0xffffffff, s0, 1); s1 = __shfl_xor_sync(0xffffffff, s1, 1);
    const uint32_t a_lo = o1 ? s0 : p0, a_hi = o1 ? p1 : s0, b_lo = o1 ? s1 : p2, b_hi = o1 ? p3 : s1;
    uint32_t t0 = o2 ? a_lo : b_lo, t1 = o2 ? a_hi : b_hi;
    t0 = __shfl_xor_sync(0xffffffff, t0, 2); t1 = __shfl_xor_sync(0xffffffff, t1, 2);
    return o2 ? make_uint4(t0, t1, b_lo, b_hi) : make_uint4(a_lo, a_hi, t0, t1);
}
#define P2_PACE 35
#define P2_PACE2 0
#define P2_STM 1
#define P2_STQ ".L1::no_allocate"
#define P2_NOF 0
#define P2_HO 7
#define P2_PRE 0
template <int PACE>
__device__ __forceinline__ void store_frag_128(const float (&acc)[64], bf16* obase) {
    uint32_t p[32];
#pragma unroll
    for (int i = 0; i < 32; i++) p[i] = pack_bf16(acc[2 * i], acc[2 * i + 1]);
    if (P2_PRE) {
#pragma unroll
        for (int i = 0; i < 32; i += 8) asm volatile("" : "+r"(p[i]), "+r"(p[i + 1]), "+r"(p[i + 2]), "+r"(p[i + 3]), "+r"(p[i + 4]), "+r"(p[i + 5]), "+r"(p[i + 6]), "+r"(p[i + 7]));
    }
#pragma unroll
    for (int rr = 0; rr < 2; rr++)
#pragma unroll
        for (int g = 0; g < 4; g++) {
            const uint32_t* a = &p[g * 8 + rr];
            asm volatile("st.global" P2_STQ ".v4.b32 [%0], {%1, %2, %3, %4};" :: "l"(obase + (size_t)(rr * 8) * HD + g * 32), "r"(a[0]), "r"(a[2]), "r"(a[4]), "r"(a[6]) : "memory");
            pace(PACE);
        }
}
struct OutParams {
    CUtensorMap mapCtx[2];
    CUtensorMap mapWo[2];
    CUtensorMap mapOut;
};

#define OT(i)
#define OTP(i, th)
constexpr int O2_STAGES = 4;
constexpr int O2_GRID = 0;
#define O2_FINE 6
#define O2_Q0 8
#define O2_Q1 9
#define O2_Q2 15
#define O2_N0 60
#define O2_RL 0
#define O2_Q3 13
#define O2_Q4 8
#define O2_Q5 8
#define O2_NB 10
#define O2_PW 0
#define O2_QA 13

constexpr uint32_t OB_FULL = 0, OB_EMPTY = 32, OB_ITEM = 64, OB_SLOT = 128, OB_STOP = 160;
__device__ __forceinline__ void out_init(uint32_t bars) {
    for (int i = 0; i < O2_STAGES; i++) {
        mbar_init(bars + OB_FULL + 8 * i, 1); mbar_init(bars + OB_EMPTY + 8 * i, 4); mbar_init(bars + OB_ITEM + 16 * i, 1); mbar_init(bars + OB_ITEM + 16 * i + 8, 1);
    }
    sts128(bars + OB_STOP, 0u, 0u, 0u, 0u);
}
struct OutJob { int tg, q, qe, last, t0, nw, nq; };
__device__ __forceinline__ OutJob out_job(int cid, int j) {
    auto quota = [](int tg) { return tg >= 12 ? O2_Q3 : tg >= 10 ? O2_Q5 : tg >= 8 ? O2_Q4 : tg & 2 ? O2_Q0 : O2_Q1; };
    auto split = [](int tg) { return O2_Q2 && (tg >> 2) == 1; };
    constexpr int NL = O2_Q2 ? 4 : 0;
    if (cid < 28 && j == 0) {
        const int tg = cid % 14, h = cid >= 14, nq = 128 - quota(tg);
        if (split(tg)) return {tg, h ? O2_N0 + O2_Q2 : 0, h ? 128 : O2_N0, !h, 128, 0, 0};
        return {tg, 2 * h, 2 * h + 2, 1, 2, nq / 2 - O2_FINE, nq};
    }
    if (j == (cid < 30 ? 1 : 4)) { const int i = cid < 28 ? cid + 16 : cid; return {16, 2 * i + 8, 2 * i + 10, 1, 38 + NL, 64 - O2_FINE, 128}; }
    if (cid < 30) return {cid - 14, O2_QA, 64, 0, 0, 0, 0};
    const int tg = (j * 4 + cid - 32) & 15;
    if (split(tg)) return {tg, O2_N0, O2_N0 + O2_Q2, 0, 0, 0, 0};
    return {tg, tg >= 14 ? 0 : 128 - quota(tg), tg >= 14 ? O2_QA : 128, 0, 0, 0, 0};
}
__device__ __forceinline__ int out_mt(int tg, int rank) { return tg < 16 ? (tg & ~1) + rank : tg - 2; }
__device__ __forceinline__ int out_n0(int tg, int rank) { return (tg < 16 ? tg & 1 : rank) * 256; }
__device__ __forceinline__ void out_producer(const OutParams& P, uint32_t sbase, uint32_t bars, uint32_t rank, int cid, bool lead, int nkv) {
    const uint32_t bar_full = bars + OB_FULL, bar_empty = bars + OB_EMPTY, bar_item = bars + OB_ITEM, slot = bars + OB_SLOT, stop = bars + OB_STOP;
    int s = 0, nb = 0; uint32_t ph = 0;
    if (lead) asm volatile("prefetch.tensormap [%0];" :: "l"(&P.mapOut) : "memory");
#pragma unroll 1
    for (int job = 0;; job++) {
        const OutJob J = out_job(cid, job);
        const int mt = out_mt(J.tg, rank), m0 = mt * 128, n0 = out_n0(J.tg, rank);
        int ready = 0, q = J.q, qe = J.qe, tnext = 0, nst = 0;
        if (lead && rank == 0 && J.last) tnext = take_ticket(CT_OT + J.tg);
        if (lead && job == 0) {
            if (O2_PW) {
                if (q >= 64) nb = O2_NB + 1; else ready = 1;
                wait_ctr(q >= 64 ? CT_CB + O2_NB : CT_CA + mt * 4, q >= 64 ? 64u : 16u);
            }
            mbar_wait(sbase + FB_KE + 8 * (~nkv & 1), ((nkv - 1) >> 1) & 1);
            TS_END2(1, 256); TS_BEGIN2(3, 256);
            for (int i = 0; i < 4; i++) {
                const uint32_t e = mapa_u32(bar_empty + 8 * (i & 1), i >> 1);
                mbar_arrive_cl(e); mbar_arrive_cl(e);
            }
        }
#pragma unroll 1
        for (int ic = 0;; ic++) {
#pragma unroll 1
            for (bool first = true; q < qe; q++, first = false) {
                const int b = q >> 6, head = (q >> 1) & 31, dk = (q & 1) * 64;
                mbar_wait(bar_empty + 8 * s, ph);
                const uint32_t sa = sbase + s * 49152;
                if (lead) {
                    if (rank == 0 && J.last && first) {
                        const int t = tnext + J.t0;
                        asm volatile("st.shared.s32 [%0], %1;" :: "r"(slot + (ic & 7) * 4), "r"(t) : "memory");
                        mbar_arrive(bar_item + 8 * (ic & 7));
                        st_async_b32(mapa_u32(slot + (ic & 7) * 4, 1), (uint32_t)t, mapa_u32(bar_item + 8 * (ic & 7), 1));
                        if (J.nw + t < J.nq) tnext = take_ticket(CT_OT + J.tg);
                    }
                    if (b ? mt >= nb : !((ready >> (head >> 3)) & 1)) {
                        if (b) nb = max(mt, O2_NB) + 1; else ready |= 1 << (head >> 3);
                        wait_ctr(b ? CT_CB + nb - 1 : CT_CA + mt * 4 + (head >> 3), b ? 64u : 16u);
                    }
                    asm volatile("st.shared.s32 [%0], %1;" :: "r"(stop + s * 4), "r"(0) : "memory");
                    mbar_expect_tx(bar_full + 8 * s, 49152);
                    tma_load_2d(sa, &P.mapCtx[b], bar_full + 8 * s, dk, head * SEQ + m0);
                    if (++nst == 6 && !(ready & 8)) { wait_ctr(CT_CA + mt * 4 + 3, 16u); ready |= 8; }
                } else if (J.tg < 16) {
                    for (int j = (int)rank * 2; j < (int)rank * 2 + 2; j++)
                        tma_load_2d_mc(sa + 16384 + j * 8192, &P.mapWo[b], bar_full + 8 * s, n0 + j * 64, head * HD + dk, (uint16_t)3);
                } else {
                    for (int j = 0; j < 4; j++) tma_load_2d(sa + 16384 + j * 8192, &P.mapWo[1], bar_full + 8 * s, n0 + j * 64, head * HD + dk);
                }
                if (++s == O2_STAGES) { s = 0; ph ^= 1; }
            }
            if (!J.last) break;
            if (lead && rank == 1) mbar_expect_tx(bar_item + 8 * (ic & 7), 4);
            mbar_wait(bar_item + 8 * (ic & 7), (ic >> 3) & 1);
            int t;
            asm volatile("ld.shared.s32 %0, [%1];" : "=r"(t) : "r"(slot + (ic & 7) * 4) : "memory");
            if (J.nw + t >= J.nq) break;
            if (t < J.nw) { q = 2 * t; qe = q + 2; } else { q = J.nw + t; qe = q + 1; }
        }
        if (lead) {
            if (!(ready & 8)) wait_ctr(CT_CA + mt * 4 + 3, 16u);
            mbar_wait(bar_empty + 8 * s, ph);
            asm volatile("st.shared.s32 [%0], %1;" :: "r"(stop + s * 4), "r"(1 + J.last + n0 + (m0 << 4)) : "memory");
            mbar_arrive(bar_full + 8 * s);
        }
        if (J.last) break;
        if (++s == O2_STAGES) { s = 0; ph ^= 1; }
    }
    if (lead) {
        out_finished();
        for (int i = 1; i < O2_STAGES; i++) {
            if (++s == O2_STAGES) { s = 0; ph ^= 1; }
            mbar_wait(bar_empty + 8 * s, ph);
        }
    }
}
__device__ __forceinline__ void out_consumer(const OutParams& P, uint32_t sbase, uint32_t bars, int warp, uint32_t opar) {
    const uint32_t bar_full = bars + OB_FULL, bar_empty = bars + OB_EMPTY, stop = bars + OB_STOP;
    int tid;
    asm volatile("mov.u32 %0, %%tid.x;" : "=r"(tid));
    const int wg = warp >> 2;
    const bool elected = (tid & 127) == 0;
    auto release = [&](int s) { if (elected) { const uint32_t e = bar_empty + 8 * s; mbar_arrive_cl(mapa_u32(e, 0)); mbar_arrive_cl(mapa_u32(e, 1)); } };
    float acc[128];
    int s = 0, sprev = 0, st, n = 0; uint32_t ph = 0;
#pragma unroll 1
    do {
#pragma unroll 1
        for (int i = 0;; i++, n++) {
            mbar_wait(bar_full + 8 * s, ph);
            asm volatile("ld.shared.s32 %0, [%1];" : "=r"(st) : "r"(stop + s * 4) : "memory");
            if (st) break;
            if (n == 0) OT(1);
            const uint32_t sa = sbase + s * 49152 + wg * 8192, sb = sbase + s * 49152 + 16384;
            wgmma_fence();
#pragma unroll
            for (int kk = 0; kk < 4; kk++)
                wgmma_ss_n256_tb(acc, make_desc(sa + kk * 32, 16, 1024), make_desc(sb + kk * 2048, 8192, 1024), kk ? 1 : i);
            wgmma_commit();
            if (i > 0) { wgmma_wait<1>(); release(sprev); }
            if (i == O2_RL && n > 1) {
                if (elected) asm volatile("cp.async.bulk.wait_group.read 1;" ::: "memory");
                release((s + 3 - O2_RL) & 3);
            }
            sprev = s;
            if (++s == O2_STAGES) { s = 0; ph ^= 1; }
        }
        mbar_wait(sbase + FB_OE + 8 * wg, opar);
        if (elected) asm volatile("cp.async.bulk.wait_group.read 0;" ::: "memory");
        wgmma_wait<0>();
        release(sprev);
        asm volatile("bar.sync %0, 128;" :: "r"(1 + wg) : "memory");
        OT(3);
        out_flush(acc, &P.mapOut, sbase + s * 49152 + wg * 16384, sbase + O2_STAGES * 49152 + wg * 16384, tid, 1 + wg, st & 256, (st >> 4 & ~127) + wg * 64);
        if (++s == O2_STAGES) { s = 0; ph ^= 1; }
    } while (!(st & 2));
    OT(4);
    if (elected) {
        asm volatile("cp.async.bulk.wait_group.read 0;" ::: "memory");
    }
}

struct MainParams { Proj2Params p; AttnParams a; OutParams o; const bf16 *x, *gate_w; };
__device__ __forceinline__ int p2_apos(int k) { return k < 2 ? k : k < 6 ? k + 2 : k - 4; }
__global__ void __cluster_dims__(2, 1, 1) __launch_bounds__(384, 1) main_kernel(const __grid_constant__ MainParams MP) {
    const Proj2Params& P = MP.p;
    extern __shared__ uint8_t smem_raw[];
    const uint32_t rank = cluster_ctarank();
    const uint32_t sbase = (rank << 24) + SD;
    if (smem_u32(smem_raw) != sbase) __trap();
    const uint32_t sA = sbase, sB = sbase + 131072;
    const uint32_t bars = sbase + MO_BAR, obars = bars + 768;
    const uint32_t a_full = bars, a_empty = bars + 64, b_full = bars + 128, b_empty = b_full + 8 * P2_STAGES;
    const uint32_t item_bar = b_empty + 8 * P2_STAGES, item_in = item_bar + 16, slot = item_in + 16;
    const uint32_t note_bar = slot + 16, note_free = note_bar + 64, note = note_free + 64;
    const int warp = __shfl_sync(0xffffffff, threadIdx.x >> 5, 0), lane = threadIdx.x & 31;
    TS_BEGIN(0);
    if (threadIdx.x == 0) {
        for (int i = 0; i < 8; i++) { mbar_init(a_full + 8 * i, 1); mbar_init(a_empty + 8 * i, 2); }
        for (int i = 0; i < P2_STAGES; i++) { mbar_init(b_full + 8 * i, 1); mbar_init(b_empty + 8 * i, 2); }
        mbar_init(item_bar, 1); mbar_init(item_bar + 8, 1); mbar_init(item_in, 2); mbar_init(item_in + 8, 2);
        for (int i = 0; i < 8; i++) { mbar_init(note_bar + 8 * i, 4); mbar_init(note_free + 8 * i, 1); }
        asm volatile("fence.mbarrier_init.release.cluster;" ::: "memory");
    }
    if (threadIdx.x == 32) {
        attn_init(sbase);
        asm volatile("fence.mbarrier_init.release.cluster;" ::: "memory");
    }
    if (threadIdx.x == 256) {
        out_init(obars);
        asm volatile("fence.mbarrier_init.release.cluster;" ::: "memory");
    }
    __syncthreads();
    asm volatile("barrier.cluster.arrive.relaxed.aligned;" ::: "memory");
    if (warp >= 8) {
    asm volatile("setmaxnreg.dec.sync.aligned.u32 40;");
    asm volatile("barrier.cluster.wait.aligned;" ::: "memory");
    if (warp == 9) {
        if (lane == 0) {
            for (int n = 0;; n++) {
                const int e = (n & 1) * 4 + ((n >> 1) & 3);
                mbar_wait(note_bar + 8 * e, (n >> 3) & 1);
                int m;
                asm volatile("ld.shared.s32 %0, [%1];" : "=r"(m) : "r"(note + e * 4) : "memory");
                mbar_arrive(note_free + 8 * e);
                if (m < 0) break;
                signal_ctr(m);
            }
            attn_helper(MP.a, sbase, 0);
        }
    } else if (warp == 10) {
        if (lane == 0) {
            auto publish = [&](int ic, int tq) {
                const int t = tq < P2_ITEMS ? tq : -1;
                asm volatile("st.shared.s32 [%0], %1;" :: "r"(slot + (ic & 3) * 4), "r"(t) : "memory");
                mbar_arrive(item_bar + 8 * (ic & 1));
                st_async_b32(mapa_u32(slot + (ic & 3) * 4, 1), (uint32_t)t, mapa_u32(item_bar + 8 * (ic & 1), 1));
            };
            const int npair = M_GRID / 2, pair = (int)(blockIdx.x >> 1);
            pace(M_D0);
            if (rank == 0) publish(0, pair);
            for (int ic = 0;; ic++) {
                if (rank == 1) mbar_expect_tx(item_bar + 8 * (ic & 1), 4);
                mbar_wait(item_bar + 8 * (ic & 1), (ic >> 1) & 1);
                int t;
                asm volatile("ld.shared.s32 %0, [%1];" : "=r"(t) : "r"(slot + (ic & 3) * 4) : "memory");
                if (t < 0) break;
                int z0, mp, h0;
                p2_tile(t, 0, z0, mp, h0);
                const int aidx = z0 >= 1 ? 1 : 0;
                const int m0 = (2 * mp + (int)rank) * 128;
                for (int k = 0; k < 8; k++) {
                    mbar_wait(a_empty + 8 * k, (ic & 1) ^ 1);
                    if (P2_NOLOAD) mbar_arrive(a_full + 8 * k); else {
                    mbar_expect_tx(a_full + 8 * k, 16384);
                    tma_load_2d(sA + p2_apos(k) * 16384, &P.mapA[aidx], a_full + 8 * k, k * 64, m0); }
                }
                if (rank == 0) {
                    mbar_wait(item_in + 8 * (ic & 1), (ic >> 1) & 1);
                    publish(ic + 1, ic == 0 ? npair + pair : pair < P2_NP && ic + 1 >= P2_NI ? P2_ITEMS : 2 * npair + (int)atomicAdd(&g_ctr[CT_PROJ], 1u));
                }
            }
            attn_helper(MP.a, sbase, 1);
        }
    } else {
        if (lane == 0) {
            const int par2 = warp == 8 ? 0 : 1;
            int it = 0, ic = 0; uint32_t bph = 0;
            for (;; ic++) {
                mbar_wait(item_bar + 8 * (ic & 1), (ic >> 1) & 1);
                int t;
                asm volatile("ld.shared.s32 %0, [%1];" : "=r"(t) : "r"(slot + (ic & 3) * 4) : "memory");
                if (t < 0) break;
                const int nt = 2 * p2_reps(t);
                for (int w = 0; w < nt; w++) {
                    int z, mp, hd;
                    p2_tile(t, w, z, mp, hd);
                    for (int k = 0; k < 8; k++) {
                        const int s = it; const uint32_t phb = bph;
                        if (++it == P2_STAGES) { it = 0; bph ^= 1; }
                        if ((k & 1) != par2) continue;
                        mbar_wait(b_empty + 8 * s, phb ^ 1);
                        if (P2_NOLOAD) { mbar_arrive(b_full + 8 * s); continue; }
                        mbar_expect_tx(b_full + 8 * s, 16384);
                        tma_load_2d_mc(sB + s * 16384 + rank * 8192, &P.mapW[z], b_full + 8 * s, hd * 128 + (int)rank * 64, k * 64, (uint16_t)3);
                    }
                }
            }
            out_producer(MP.o, sbase, obars, rank, blockIdx.x >> 1, warp == 8, warp == 8 ? attn_producer(MP.a, sbase, a_empty, ~ic & 1) : 0);
            TS_END2(3, 256);
        }
    }
    } else {
        asm volatile("setmaxnreg.inc.sync.aligned.u32 232;");
        asm volatile("barrier.cluster.wait.aligned;" ::: "memory");
        const int wg = warp >> 2;
        float acc[2][64];
        const uint32_t a_lo = desc_lo(SD, 16), b_lo0 = desc_lo(SD + 131072, 8192);
        const bool elected = (threadIdx.x & 127) == 0;
        int s = (wg * 8) % P2_STAGES;
        uint32_t ph = ((wg * 8) / P2_STAGES) & 1;
        int nnote = 0;
        if (wg == 1) {
            asm volatile("bar.arrive 3, 256;" ::: "memory");
            if (blockIdx.x < 64) {
                const int r = blockIdx.x * 32 + (warp & 3) * 8 + (lane >> 2);
                float c[4] = {0.f, 0.f, 0.f, 0.f};
                uint4 xv[16], gv[16];
#pragma unroll
                for (int i = 0; i < 16; i++) {
                    xv[i] = __ldg(reinterpret_cast<const uint4*>(MP.x + (size_t)r * DM + i * 32 + (lane & 3) * 8));
                    gv[i] = __ldg(reinterpret_cast<const uint4*>(MP.gate_w + i * 32 + (lane & 3) * 8));
                }
                auto mul = [](uint32_t a, uint32_t b) { uint32_t p; asm("mul.rn.bf16x2 %0, %1, %2;" : "=r"(p) : "r"(a), "r"(b)); return p; };
#pragma unroll
                for (int i = 0; i < 16; i++)
                    mma_16816(c, mul(xv[i].x, gv[i].x), mul(xv[i].y, gv[i].y), mul(xv[i].z, gv[i].z), mul(xv[i].w, gv[i].w), 0x3f803f80u, 0x3f803f80u);
                if ((lane & 3) == 0) g_gate[r] = bf16r(__fdividef(1.f, 1.f + __expf(-bf16r(c[0] + c[2]))));
                __syncwarp();
                if (lane == 0) signal_ctr_generic(CT_GATE);
                __syncwarp();
            }
        }
        auto next_item = [&](int ic) {
            mbar_wait(item_bar + 8 * (ic & 1), (ic >> 1) & 1);
            int t;
            asm volatile("ld.shared.s32 %0, [%1];" : "=r"(t) : "r"(slot + (ic & 3) * 4) : "memory");
            return __shfl_sync(0xffffffff, t, 0);
        };
        int t = next_item(0), ic = 0, rp = 0;
#pragma unroll 1
        while (t >= 0) {
            const bool first = rp == 0, last = rp == p2_reps(t) - 1;
            asm volatile("bar.sync %0, 256;" :: "r"(3 + wg) : "memory");
            P2T(0);
            if (wg == 1 && last && elected) mbar_arrive_cl(mapa_u32(item_in + 8 * (ic & 1), 0));
            int sprev = 0;
#pragma unroll
            for (int k = 0; k < 8; k++) {
                if (k == 0) P2T(5);
                if ((wg == 0 || k > P2_HO) && first) mbar_wait(a_full + 8 * k, ic & 1);
                if (k == 0) P2T(6);
                mbar_wait(b_full + 8 * s, ph);
                if (k == P2_HO) asm volatile("bar.arrive %0, 256;" :: "r"(4 - wg) : "memory");
                if (k == 0) P2T(1);
                if (k == 7) P2T(2);
                const uint32_t b_lo = b_lo0 + s * 1024;
                if (k == 0 || !P2_NOF) wgmma_fence();
#pragma unroll
                for (int kk = 0; kk < (P2_NOMMA ? 1 : 4); kk++) {
                    wgmma_ss_n128_lo<1>(acc[0], a_lo + p2_apos(k) * 1024 + kk * 2, b_lo + kk * 128, (k | kk) != 0);
                    wgmma_ss_n128_lo<1>(acc[1], a_lo + p2_apos(k) * 1024 + 512 + kk * 2, b_lo + kk * 128, (k | kk) != 0);
                }
                wgmma_commit();
                if (k > 0) {
                    wgmma_wait<1>();
                    if (elected) {
                        const uint32_t e = b_empty + 8 * sprev;
                        mbar_arrive_cl(mapa_u32(e, 0)); mbar_arrive_cl(mapa_u32(e, 1));
                        if (last) mbar_arrive(a_empty + 8 * (k - 1));
                    }
                }
                sprev = s;
                if (++s == P2_STAGES) { s = 0; ph ^= 1; }
            }
            int z, mp, head;
            p2_tile(t, rp * 2 + wg, z, mp, head);
            const int m0 = (2 * mp + (int)rank) * 128, en = wg * 4 + (nnote & 3);
            bf16* obase = P.out[z] + ((size_t)head * SEQ + m0 + (warp & 3) * 16 + (lane >> 2)) * HD + (lane & 3) * 8;
            if (elected) {
                mbar_wait(note_free + 8 * en, ((nnote >> 2) & 1) ^ 1);
                asm volatile("st.shared.s32 [%0], %1;" :: "r"(note + en * 4), "r"(CT_AP + (head >> 1)) : "memory");
            }
            __syncwarp();
            nnote++;
            wgmma_wait<0>();
            P2T(3);
            if (elected) {
                const uint32_t e = b_empty + 8 * sprev;
                mbar_arrive_cl(mapa_u32(e, 0)); mbar_arrive_cl(mapa_u32(e, 1));
                if (last) mbar_arrive(a_empty + 8 * 7);
            }
            s += 8 % P2_STAGES; ph ^= (8 / P2_STAGES) & 1;
            if (s >= P2_STAGES) { s -= P2_STAGES; ph ^= 1; }
            store_frag_128<P2_PACE>(acc[0], obase);
            if (last) { t = next_item(++ic); rp = 0; P2T(7); } else rp++;
            store_frag_128<P2_PACE>(acc[1], obase + (size_t)64 * HD);
            __syncwarp();
            if (lane == 0) mbar_arrive(note_bar + 8 * en);
            __syncwarp();
        }
        if (wg == 0 && lane == 0) {
            const int e = nnote & 3;
            if (elected) {
                mbar_wait(note_free + 8 * e, ((nnote >> 2) & 1) ^ 1);
                asm volatile("st.shared.s32 [%0], %1;" :: "r"(note + e * 4), "r"(-1) : "memory");
            }
            mbar_arrive(note_bar + 8 * e);
        }
        auto done = [&]() {
            if ((threadIdx.x & 127) == 0) for (int i = 0; i < 4; i++) mbar_arrive_cl(SD + MO_BAR + 768 + OB_EMPTY + 16 + 8 * (i & 1) + ((i >> 1) << 24));
        };
        asm volatile("bar.sync %0, 128;" :: "r"(1 + wg) : "memory");
        const int nout = attn_consumer(MP.a, warp, done, SD + (rank << 24));
        OT(0);
        const uint32_t sb2 = (cluster_ctarank() << 24) + SD;
        out_consumer(MP.o, sb2, sb2 + MO_BAR + 768, warp, nout & 1);
    }
}

typedef CUresult (*PFN_encodeTiled)(CUtensorMap*, CUtensorMapDataType, cuuint32_t, void*, const cuuint64_t*,
                                    const cuuint64_t*, const cuuint32_t*, const cuuint32_t*, CUtensorMapInterleave,
                                    CUtensorMapSwizzle, CUtensorMapL2promotion, CUtensorMapFloatOOBfill);
static PFN_encodeTiled g_encode = nullptr;

static void make_map(CUtensorMap* m, const void* ptr, uint64_t rows, uint64_t cols, uint32_t box_rows, bool sw64 = false) {
    cuuint64_t dims[2] = {cols, rows};
    cuuint64_t strides[1] = {cols * 2};
    cuuint32_t box[2] = {sw64 ? 32u : 64u, box_rows};
    cuuint32_t es[2] = {1, 1};
    g_encode(m, CU_TENSOR_MAP_DATA_TYPE_BFLOAT16, 2, const_cast<void*>(ptr), dims, strides, box, es,
             CU_TENSOR_MAP_INTERLEAVE_NONE, sw64 ? CU_TENSOR_MAP_SWIZZLE_64B : CU_TENSOR_MAP_SWIZZLE_128B, CU_TENSOR_MAP_L2_PROMOTION_L2_256B,
             CU_TENSOR_MAP_FLOAT_OOB_FILL_NONE);
}

template <typename... KArgs, typename... Args>
static void launch_pdl(void (*kernel)(KArgs...), int grid, int block, size_t smem, cudaStream_t st, bool pdl, Args... args) {
    cudaLaunchConfig_t cfg = {};
    cfg.gridDim = dim3(grid); cfg.blockDim = dim3(block); cfg.dynamicSmemBytes = smem; cfg.stream = st;
    cudaLaunchAttribute at[1];
    at[0].id = cudaLaunchAttributeProgrammaticStreamSerialization;
    at[0].val.programmaticStreamSerializationAllowed = 1;
    cfg.attrs = at; cfg.numAttrs = pdl ? 1 : 0;
    cudaLaunchKernelEx(&cfg, kernel, KArgs(args)...);
}

extern "C" void kernel_launch(void* const* d_in, const int* in_sizes, int n_in, void* d_out, int out_size) {
    const bf16* x = (const bf16*)d_in[0];
    const bf16* ckv = (const bf16*)d_in[1];
    const bf16* wq = (const bf16*)d_in[2];
    const bf16* wuk = (const bf16*)d_in[3];
    const bf16* wuv = (const bf16*)d_in[4];
    const bf16* wo = (const bf16*)d_in[5];
    const bf16* mem0 = (const bf16*)d_in[7];
    const bf16* Wq = (const bf16*)d_in[8];
    const bf16* Wk = (const bf16*)d_in[9];
    const bf16* Wv = (const bf16*)d_in[10];
    const bf16* Wo = (const bf16*)d_in[11];
    const bf16* gate_w = (const bf16*)d_in[13];
    bf16* out = (bf16*)d_out;

    static MainParams MP;
    static ChainParams CP;
    Proj2Params& P2 = MP.p;
    AttnParams& AP = MP.a;
    OutParams& OP = MP.o;
    static bool init = false;
    static const void* last_in[14];
    static const void* last_out;
    bool same = init && last_out == d_out;
    for (int i = 0; i < 14 && same; i++) same = last_in[i] == d_in[i];
    if (!init) {
        cudaDriverEntryPointQueryResult qr;
        cudaGetDriverEntryPoint("cuTensorMapEncodeTiled", (void**)&g_encode, cudaEnableDefault, &qr);
        cudaFuncSetAttribute(main_kernel, cudaFuncAttributeMaxDynamicSharedMemorySize, M_SMEM);
        cudaFuncSetAttribute(chain_kernel, cudaFuncAttributeMaxDynamicSharedMemorySize, CH_SMEM);
        init = true;
    }
    if (!same) {
        for (int i = 0; i < 14; i++) last_in[i] = d_in[i];
        last_out = d_out;
        void *pQA, *pKA, *pVA, *pCA, *pCB;
        cudaGetSymbolAddress(&pQA, g_QA); cudaGetSymbolAddress(&pKA, g_KA); cudaGetSymbolAddress(&pVA, g_VA);
        cudaGetSymbolAddress(&pCA, g_ctxA); cudaGetSymbolAddress(&pCB, g_ctxB);
        make_map(&P2.mapA[0], x, SEQ, DM, 128);
        make_map(&P2.mapA[1], ckv, SEQ, DM, 128);
        const void* ws[3] = {wq, wuk, wuv};
        void* cs[3] = {pQA, pKA, pVA};
        for (int i = 0; i < 3; i++) { make_map(&P2.mapW[i], ws[i], DM, NQ, 64); P2.out[i] = (bf16*)cs[i]; }
        make_map(&CP.mapW[0], Wq, DM, NQ, 64); make_map(&CP.mapW[1], Wk, DM, NQ, 64); make_map(&CP.mapW[2], Wv, DM, NQ, 32);
        make_map(&CP.mapX, x, SEQ, DM, 32);
        make_map(&CP.mapWo, Wo, NQ, DM, 64);
        make_map(&CP.mapM, mem0, NMEM, DM, 8);
        MP.x = x; MP.gate_w = gate_w;
        make_map(&CP.mapC, pCB, NH * SEQ, HD, 32);
        make_map(&AP.mapQ, pQA, NH * SEQ, HD, 128);
        make_map(&AP.mapK, pKA, NH * SEQ, HD, 128);
        make_map(&AP.mapV, pVA, NH * SEQ, HD, 128);
        make_map(&AP.mapO, pCA, NH * SEQ, HD, 64);
        make_map(&OP.mapCtx[0], pCA, NH * SEQ, HD, 128);
        make_map(&OP.mapCtx[1], pCB, NH * SEQ, HD, 128);
        make_map(&OP.mapWo[0], wo, NQ, DM, 64);
        make_map(&OP.mapWo[1], Wo, NQ, DM, 64);
        make_map(&OP.mapOut, out, SEQ, DM, 64);
        CP.mapOut = OP.mapOut;
        AP.out = out;
    }
    cudaStream_t s1 = cudaStreamPerThread;
    const bool pdl = true;
    launch_pdl(chain_kernel, 64, CH_BLOCK, CH_SMEM, s1, false, CP);
    launch_pdl(main_kernel, M_GRID, 384, M_SMEM, s1, pdl, MP);
}
```

```cpp
#include <cuda_runtime.h>
#include <cuda_bf16.h>
#include <cuda.h>
#include <stdint.h>
#include <type_traits>

constexpr int SEQ = 2048;
constexpr int DM = 512;
constexpr int NH = 32;
constexpr int HD = 128;
constexpr int NQ = NH * HD;
constexpr int SEGL = 32;
constexpr int NMEM = 8;
constexpr int NSEG = SEQ / SEGL;

typedef __nv_bfloat16 bf16;

__device__ bf16 g_QA[SEQ * NQ];
__device__ bf16 g_KA[SEQ * NQ];
__device__ bf16 g_VA[SEQ * NQ];
__device__ bf16 g_ctxA[SEQ * NQ];
__device__ bf16 g_ctxB[SEQ * NQ];
constexpr int CT_PROJ = 0, CT_ATTN = 1, CT_FIN = 5;
constexpr int CT_AP = 64;
constexpr int CT_GATE = 96;
constexpr int CT_CA = 128;
constexpr int CT_CB = 193;
constexpr int CT_OT = 208;
constexpr int CT_N = 228;
__device__ __align__(16) unsigned int g_ctr[CT_N];
__device__ float g_gate[SEQ];
#define XB8(v) v, v, v, v, v, v, v, v
__device__ uint32_t g_xbuf[4 * 8 * 2048] = {XB8(XB8(XB8(XB8(XB8(~0u)))))};

#define FA_GRID 68

#define TS_BEGIN(id)
#define TS_END(id)
#define TS_BEGIN2(id, th)
#define TS_END2(id, th)
#define WAIT_LIMIT 200000
__device__ __forceinline__ void pdl_launch_dependents() { asm volatile("griddepcontrol.launch_dependents;" ::: "memory"); }
__device__ __forceinline__ void wait_ctr(int idx, unsigned int n) {
    unsigned int v; int it = 0;
    do { asm volatile("ld.acquire.gpu.global.u32 %0, [%1];" : "=r"(v) : "l"(&g_ctr[idx]) : "memory"); } while (v < n && ++it < WAIT_LIMIT);
    asm volatile("fence.proxy.async.shared::cta;" ::: "memory");
}
__device__ __forceinline__ int take_ticket(int idx) {
    int v;
    asm volatile("atom.relaxed.gpu.global.inc.u32 %0, [%1], 0x7fffffff;" : "=r"(v) : "l"(&g_ctr[idx]) : "memory");
    return v;
}
__device__ __forceinline__ void signal_ctr(int idx) {
    asm volatile("fence.proxy.async;" ::: "memory");
    __threadfence();
    atomicAdd(&g_ctr[idx], 1u);
}
__device__ __forceinline__ void signal_ctr_generic(int idx) {
    asm volatile("red.release.gpu.global.add.u32 [%0], 1;" :: "l"(&g_ctr[idx]) : "memory");
}
__device__ __forceinline__ uint32_t smem_u32(const void* p) {
    return (uint32_t)__cvta_generic_to_shared(p);
}
__device__ __forceinline__ void mbar_init(uint32_t bar, uint32_t count) {
    asm volatile("mbarrier.init.shared::cta.b64 [%0], %1;" :: "r"(bar), "r"(count));
}
__device__ __forceinline__ void mbar_expect_tx(uint32_t bar, uint32_t bytes) {
    asm volatile("mbarrier.arrive.expect_tx.shared::cta.b64 _, [%0], %1;" :: "r"(bar), "r"(bytes) : "memory");
}
__device__ __forceinline__ void mbar_arrive(uint32_t bar) {
    asm volatile("mbarrier.arrive.shared::cta.b64 _, [%0];" :: "r"(bar) : "memory");
}
__device__ __forceinline__ void mbar_wait(uint32_t bar, uint32_t parity) {
    asm volatile(
        "{\n"
        ".reg .pred p, q;\n"
        ".reg .u32 c;\n"
        "mov.u32 c, 0;\n"
        "WAIT_LOOP:\n"
        "mbarrier.try_wait.parity.shared::cta.b64 p, [%0], %1;\n"
        "@p bra WAIT_DONE;\n"
        "add.u32 c, c, 1;\n"
        "setp.lt.u32 q, c, %2;\n"
        "@q bra WAIT_LOOP;\n"
        "WAIT_DONE:\n"
        "}\n" :: "r"(bar), "r"(parity), "n"(WAIT_LIMIT) : "memory");
}
__device__ __forceinline__ uint32_t mbar_test(uint32_t bar, uint32_t parity) {
    uint32_t done;
    asm volatile(
        "{\n.reg .pred p;\n"
        "mbarrier.test_wait.parity.shared::cta.b64 p, [%1], %2;\n"
        "selp.u32 %0, 1, 0, p;\n}\n" : "=r"(done) : "r"(bar), "r"(parity) : "memory");
    return done;
}
__device__ __forceinline__ uint32_t mbar_try(uint32_t bar, uint32_t parity) {
    uint32_t done;
    asm volatile(
        "{\n.reg .pred p;\n"
        "mbarrier.try_wait.parity.shared::cta.b64 p, [%1], %2;\n"
        "selp.u32 %0, 1, 0, p;\n}\n" : "=r"(done) : "r"(bar), "r"(parity) : "memory");
    return done;
}
__device__ __forceinline__ void tma_load_2d(uint32_t dst, const CUtensorMap* map, uint32_t bar, int c0, int c1) {
    asm volatile(
        "cp.async.bulk.tensor.2d.shared::cluster.global.mbarrier::complete_tx::bytes [%0], [%1, {%3, %4}], [%2];"
        :: "r"(dst), "l"((uint64_t)map), "r"(bar), "r"(c0), "r"(c1) : "memory");
}
__device__ __forceinline__ void wgmma_fence() { asm volatile("wgmma.fence.sync.aligned;" ::: "memory"); }
__device__ __forceinline__ void wgmma_commit() { asm volatile("wgmma.commit_group.sync.aligned;" ::: "memory"); }
template <int N> __device__ __forceinline__ void wgmma_wait() {
    asm volatile("wgmma.wait_group.sync.aligned %0;" :: "n"(N) : "memory");
}
__device__ __forceinline__ uint64_t make_desc(uint32_t addr, uint32_t lbo, uint32_t sbo) {
    uint64_t d = 0;
    d |= (uint64_t)((addr & 0x3FFFF) >> 4);
    d |= (uint64_t)((lbo >> 4) & 0x3FFF) << 16;
    d |= (uint64_t)((sbo >> 4) & 0x3FFF) << 32;
    d |= (uint64_t)1 << 62;
    return d;
}

#define ACC64(d) \
    "+f"(d[0]), "+f"(d[1]), "+f"(d[2]), "+f"(d[3]), "+f"(d[4]), "+f"(d[5]), "+f"(d[6]), "+f"(d[7]), \
    "+f"(d[8]), "+f"(d[9]), "+f"(d[10]), "+f"(d[11]), "+f"(d[12]), "+f"(d[13]), "+f"(d[14]), "+f"(d[15]), \
    "+f"(d[16]), "+f"(d[17]), "+f"(d[18]), "+f"(d[19]), "+f"(d[20]), "+f"(d[21]), "+f"(d[22]), "+f"(d[23]), \
    "+f"(d[24]), "+f"(d[25]), "+f"(d[26]), "+f"(d[27]), "+f"(d[28]), "+f"(d[29]), "+f"(d[30]), "+f"(d[31]), \
    "+f"(d[32]), "+f"(d[33]), "+f"(d[34]), "+f"(d[35]), "+f"(d[36]), "+f"(d[37]), "+f"(d[38]), "+f"(d[39]), \
    "+f"(d[40]), "+f"(d[41]), "+f"(d[42]), "+f"(d[43]), "+f"(d[44]), "+f"(d[45]), "+f"(d[46]), "+f"(d[47]), \
    "+f"(d[48]), "+f"(d[49]), "+f"(d[50]), "+f"(d[51]), "+f"(d[52]), "+f"(d[53]), "+f"(d[54]), "+f"(d[55]), \
    "+f"(d[56]), "+f"(d[57]), "+f"(d[58]), "+f"(d[59]), "+f"(d[60]), "+f"(d[61]), "+f"(d[62]), "+f"(d[63])
#define ACC64_STR \
    "{%0, %1, %2, %3, %4, %5, %6, %7, %8, %9, %10, %11, %12, %13, %14, %15, " \
    "%16, %17, %18, %19, %20, %21, %22, %23, %24, %25, %26, %27, %28, %29, %30, %31, " \
    "%32, %33, %34, %35, %36, %37, %38, %39, %40, %41, %42, %43, %44, %45, %46, %47, " \
    "%48, %49, %50, %51, %52, %53, %54, %55, %56, %57, %58, %59, %60, %61, %62, %63}"

template <int TB>
__device__ __forceinline__ void wgmma_ss_n128(float (&d)[64], uint64_t da, uint64_t db, int scale_d) {
    asm volatile(
        "{\n.reg .pred p;\nsetp.ne.b32 p, %66, 0;\n"
        "wgmma.mma_async.sync.aligned.m64n128k16.f32.bf16.bf16 " ACC64_STR ", %64, %65, p, 1, 1, 0, %67;\n}\n"
        : ACC64(d) : "l"(da), "l"(db), "r"(scale_d), "n"(TB));
}
__device__ __forceinline__ uint32_t desc_lo(uint32_t addr, uint32_t lbo) { return ((addr & 0x3FFFF) >> 4) | ((lbo >> 4) << 16); }
template <int TB>
__device__ __forceinline__ void wgmma_ss_n128_lo(float (&d)[64], uint32_t da_lo, uint32_t db_lo, int scale_d) {
    asm volatile(
        "{\n.reg .pred p;\n.reg .b64 da, db;\nsetp.ne.b32 p, %66, 0;\n"
        "mov.b64 da, {%64, 0x40000040};\nmov.b64 db, {%65, 0x40000040};\n"
        "wgmma.mma_async.sync.aligned.m64n128k16.f32.bf16.bf16 " ACC64_STR ", da, db, p, 1, 1, 0, %67;\n}\n"
        : ACC64(d) : "r"(da_lo), "r"(db_lo), "r"(scale_d), "n"(TB));
}
__device__ __forceinline__ void wgmma_rs_n128_tb(float (&d)[64], uint32_t a0, uint32_t a1, uint32_t a2, uint32_t a3,
                                                 uint64_t db, int scale_d) {
    asm volatile(
        "{\n.reg .pred p;\nsetp.ne.b32 p, %69, 0;\n"
        "wgmma.mma_async.sync.aligned.m64n128k16.f32.bf16.bf16 " ACC64_STR ", {%64, %65, %66, %67}, %68, p, 1, 1, 1;\n}\n"
        : ACC64(d) : "r"(a0), "r"(a1), "r"(a2), "r"(a3), "l"(db), "r"(scale_d));
}
__device__ __forceinline__ void wgmma_rs_n80(float (&d)[40], const uint32_t (&a)[4], uint32_t db_lo, int scale_d) {
    asm volatile(
        "{\n.reg .pred p;\n.reg .b64 db;\nsetp.ne.b32 p, %45, 0;\nmov.b64 db, {%44, 0x40000040};\n"
        "wgmma.mma_async.sync.aligned.m64n80k16.f32.bf16.bf16 "
        "{%0, %1, %2, %3, %4, %5, %6, %7, %8, %9, %10, %11, %12, %13, %14, %15, %16, %17, %18, %19, %20, %21, %22, %23, %24, %25, %26, %27, %28, %29, %30, %31, %32, %33, %34, %35, %36, %37, %38, %39}, "
        "{%40, %41, %42, %43}, db, p, 1, 1, 0;\n}\n"
        : "+f"(d[0]), "+f"(d[1]), "+f"(d[2]), "+f"(d[3]), "+f"(d[4]), "+f"(d[5]), "+f"(d[6]), "+f"(d[7]), "+f"(d[8]), "+f"(d[9]), "+f"(d[10]), "+f"(d[11]), "+f"(d[12]), "+f"(d[13]), "+f"(d[14]), "+f"(d[15]), "+f"(d[16]), "+f"(d[17]), "+f"(d[18]), "+f"(d[19]), "+f"(d[20]), "+f"(d[21]), "+f"(d[22]), "+f"(d[23]), "+f"(d[24]), "+f"(d[25]), "+f"(d[26]), "+f"(d[27]), "+f"(d[28]), "+f"(d[29]), "+f"(d[30]), "+f"(d[31]), "+f"(d[32]), "+f"(d[33]), "+f"(d[34]), "+f"(d[35]), "+f"(d[36]), "+f"(d[37]), "+f"(d[38]), "+f"(d[39])
        : "r"(a[0]), "r"(a[1]), "r"(a[2]), "r"(a[3]), "r"(db_lo), "r"(scale_d));
}
__device__ __forceinline__ void wgmma_ss_n256_tb(float (&d)[128], uint64_t da, uint64_t db, int scale_d) {
    asm volatile(
        "{\n.reg .pred p;\nsetp.ne.b32 p, %130, 0;\n"
        "wgmma.mma_async.sync.aligned.m64n256k16.f32.bf16.bf16 {%0, %1, %2, %3, %4, %5, %6, %7, %8, %9, %10, %11, %12, %13, %14, %15, %16, %17, %18, %19, %20, %21, %22, %23, %24, %25, %26, %27, %28, %29, %30, %31, %32, %33, %34, %35, %36, %37, %38, %39, %40, %41, %42, %43, %44, %45, %46, %47, %48, %49, %50, %51, %52, %53, %54, %55, %56, %57, %58, %59, %60, %61, %62, %63, %64, %65, %66, %67, %68, %69, %70, %71, %72, %73, %74, %75, %76, %77, %78, %79, %80, %81, %82, %83, %84, %85, %86, %87, %88, %89, %90, %91, %92, %93, %94, %95, %96, %97, %98, %99, %100, %101, %102, %103, %104, %105, %106, %107, %108, %109, %110, %111, %112, %113, %114, %115, %116, %117, %118, %119, %120, %121, %122, %123, %124, %125, %126, %127}, %128, %129, p, 1, 1, 0, 1;\n}\n"
        : "+f"(d[0]), "+f"(d[1]), "+f"(d[2]), "+f"(d[3]), "+f"(d[4]), "+f"(d[5]), "+f"(d[6]), "+f"(d[7]), "+f"(d[8]), "+f"(d[9]), "+f"(d[10]), "+f"(d[11]), "+f"(d[12]), "+f"(d[13]), "+f"(d[14]), "+f"(d[15]), "+f"(d[16]), "+f"(d[17]), "+f"(d[18]), "+f"(d[19]), "+f"(d[20]), "+f"(d[21]), "+f"(d[22]), "+f"(d[23]), "+f"(d[24]), "+f"(d[25]), "+f"(d[26]), "+f"(d[27]), "+f"(d[28]), "+f"(d[29]), "+f"(d[30]), "+f"(d[31]), "+f"(d[32]), "+f"(d[33]), "+f"(d[34]), "+f"(d[35]), "+f"(d[36]), "+f"(d[37]), "+f"(d[38]), "+f"(d[39]), "+f"(d[40]), "+f"(d[41]), "+f"(d[42]), "+f"(d[43]), "+f"(d[44]), "+f"(d[45]), "+f"(d[46]), "+f"(d[47]), "+f"(d[48]), "+f"(d[49]), "+f"(d[50]), "+f"(d[51]), "+f"(d[52]), "+f"(d[53]), "+f"(d[54]), "+f"(d[55]), "+f"(d[56]), "+f"(d[57]), "+f"(d[58]), "+f"(d[59]), "+f"(d[60]), "+f"(d[61]), "+f"(d[62]), "+f"(d[63]), "+f"(d[64]), "+f"(d[65]), "+f"(d[66]), "+f"(d[67]), "+f"(d[68]), "+f"(d[69]), "+f"(d[70]), "+f"(d[71]), "+f"(d[72]), "+f"(d[73]), "+f"(d[74]), "+f"(d[75]), "+f"(d[76]), "+f"(d[77]), "+f"(d[78]), "+f"(d[79]), "+f"(d[80]), "+f"(d[81]), "+f"(d[82]), "+f"(d[83]), "+f"(d[84]), "+f"(d[85]), "+f"(d[86]), "+f"(d[87]), "+f"(d[88]), "+f"(d[89]), "+f"(d[90]), "+f"(d[91]), "+f"(d[92]), "+f"(d[93]), "+f"(d[94]), "+f"(d[95]), "+f"(d[96]), "+f"(d[97]), "+f"(d[98]), "+f"(d[99]), "+f"(d[100]), "+f"(d[101]), "+f"(d[102]), "+f"(d[103]), "+f"(d[104]), "+f"(d[105]), "+f"(d[106]), "+f"(d[107]), "+f"(d[108]), "+f"(d[109]), "+f"(d[110]), "+f"(d[111]), "+f"(d[112]), "+f"(d[113]), "+f"(d[114]), "+f"(d[115]), "+f"(d[116]), "+f"(d[117]), "+f"(d[118]), "+f"(d[119]), "+f"(d[120]), "+f"(d[121]), "+f"(d[122]), "+f"(d[123]), "+f"(d[124]), "+f"(d[125]), "+f"(d[126]), "+f"(d[127])
        : "l"(da), "l"(db), "r"(scale_d));
}
__device__ __forceinline__ void stmatrix_x4(uint32_t addr, uint32_t r0, uint32_t r1, uint32_t r2, uint32_t r3) {
    asm volatile("stmatrix.sync.aligned.m8n8.x4.shared.b16 [%0], {%1, %2, %3, %4};" :: "r"(addr), "r"(r0), "r"(r1), "r"(r2), "r"(r3) : "memory");
}
__device__ __forceinline__ void tma_store_2d(const CUtensorMap* map, uint32_t src, int c0, int c1) {
    asm volatile("cp.async.bulk.tensor.2d.global.shared::cta.bulk_group [%0, {%2, %3}], [%1];"
                 :: "l"((uint64_t)map), "r"(src), "r"(c0), "r"(c1) : "memory");
}
__device__ __forceinline__ float ex2f(float x) { float y; asm("ex2.approx.ftz.f32 %0, %1;" : "=f"(y) : "f"(x)); return y; }
__device__ __forceinline__ uint32_t pack_bf16(float lo, float hi) {
    __nv_bfloat162 v = __floats2bfloat162_rn(lo, hi);
    return *reinterpret_cast<uint32_t*>(&v);
}
__device__ __forceinline__ void mma_16816(float (&c)[4], uint32_t a0, uint32_t a1, uint32_t a2, uint32_t a3,
                                          uint32_t b0, uint32_t b1) {
    asm volatile(
        "mma.sync.aligned.m16n8k16.row.col.f32.bf16.bf16.f32 {%0,%1,%2,%3}, {%4,%5,%6,%7}, {%8,%9}, {%0,%1,%2,%3};"
        : "+f"(c[0]), "+f"(c[1]), "+f"(c[2]), "+f"(c[3])
        : "r"(a0), "r"(a1), "r"(a2), "r"(a3), "r"(b0), "r"(b1));
}
__device__ __forceinline__ void ldmatrix_x4_trans(uint32_t& r0, uint32_t& r1, uint32_t& r2, uint32_t& r3, uint32_t addr) {
    asm volatile("ldmatrix.sync.aligned.m8n8.x4.trans.shared.b16 {%0,%1,%2,%3}, [%4];"
                 : "=r"(r0), "=r"(r1), "=r"(r2), "=r"(r3) : "r"(addr));
}

struct AttnParams {
    CUtensorMap mapQ, mapK, mapV;
    CUtensorMap mapO;
    bf16* out;
};
constexpr int FA_ITEMS = 16 * NH;
__device__ __forceinline__ int fa_qt(int t) { return 15 - ((t & 127) >> 3); }
__device__ __forceinline__ int fa_head(int t) { return (t >> 7) * 8 + (t & 7); }
#define FA_TKA 2
#define FA_SPLIT 11

#define FA_P0 4
#define FA_HO 6
#define FA_LAG 3
#define FA_PK 3
#define FA_TG 16
#define FA_EARLY 0
#define FA_TRIM 1
#define FA_TE 0
#define FA_B0 1
#define FA_ONE 1
#define FA_I0 0
static_assert(FA_GRID <= 104 && FA_HO >= FA_P0 && FA_P0 >= 1 && (!FA_TRIM || (FA_P0 == 4 && FA_SPLIT >= 8 && FA_I0 <= 4)), "");
constexpr float FA_MARGIN = 16.f;
#define FAT(b, i)
__device__ __forceinline__ void mbar_arrive_if(uint32_t bar, bool c) {
    asm volatile("{\n.reg .pred p;\nsetp.ne.b32 p, %1, 0;\n@p mbarrier.arrive.shared::cta.b64 _, [%0];\n}" :: "r"(bar), "r"((int)c) : "memory");
}
__device__ __forceinline__ void sched_fence(int v, int id, const float* a, const float* b, const float* c) {
    asm volatile("{\n.reg .pred p;\nsetp.ne.s32 p, %0, %1;\n@p bra SF_SKIP;\nwgmma.wait_group.sync.aligned 0;\n"
                 "st.volatile.shared.f32 [%0], %2;\nst.volatile.shared.f32 [%0], %3;\nst.volatile.shared.f32 [%0], %4;\nst.volatile.shared.f32 [%0], %5;\n"
                 "st.volatile.shared.f32 [%0], %6;\nst.volatile.shared.f32 [%0], %7;\nst.volatile.shared.f32 [%0], %8;\nst.volatile.shared.f32 [%0], %9;\n"
                 "st.volatile.shared.f32 [%0], %10;\nst.volatile.shared.f32 [%0], %11;\nst.volatile.shared.f32 [%0], %12;\nst.volatile.shared.f32 [%0], %13;\n"
                 "exit;\nSF_SKIP:\n}" :: "r"(v), "r"(1000000 + id), "f"(a[0]), "f"(a[1]), "f"(a[2]), "f"(a[3]), "f"(b[0]), "f"(b[1]), "f"(b[2]), "f"(b[3]),
                 "f"(c[0]), "f"(c[1]), "f"(c[2]), "f"(c[3]) : "memory");
}
__device__ __forceinline__ float ex2v(float x) { float y; asm volatile("ex2.approx.ftz.f32 %0, %1;" : "=f"(y) : "f"(x)); return y; }
__device__ __forceinline__ void wgmma_rs_n128_tb_lo(float (&d)[64], const uint32_t* a, uint32_t db_lo, int scale_d) {
    asm volatile(
        "{\n.reg .pred p;\n.reg .b64 db;\nsetp.ne.b32 p, %69, 0;\nmov.b64 db, {%68, 0x40000040};\n"
        "wgmma.mma_async.sync.aligned.m64n128k16.f32.bf16.bf16 " ACC64_STR ", {%64, %65, %66, %67}, db, p, 1, 1, 1;\n}\n"
        : ACC64(d) : "r"(a[0]), "r"(a[1]), "r"(a[2]), "r"(a[3]), "r"(db_lo), "r"(scale_d));
}

constexpr int M_GRID = 68;
constexpr uint32_t SD = 1024;
constexpr uint32_t MO_BAR = 229376;
constexpr int M_SMEM = MO_BAR + 1024;
constexpr uint32_t FO_Q = 0, FO_KV = 65536, FO_O = FO_KV + 2 * 65536, FO_BAR = MO_BAR + 512;
constexpr uint32_t FB_QF = FO_BAR, FB_QE = FO_BAR + 16, FB_KF = FO_BAR + 32, FB_VF = FO_BAR + 48, FB_KE = FO_BAR + 64, FB_VE = FO_BAR + 80,
                   FB_OF = FO_BAR + 96, FB_OE = FO_BAR + 112, FB_SLOT = FO_BAR + 128, FB_OSLOT = FO_BAR + 136;
__device__ __forceinline__ void attn_init(uint32_t sb) {
    for (int i = 0; i < 2; i++) {
        mbar_init(sb + FB_QF + 8 * i, 1); mbar_init(sb + FB_QE + 8 * i, 8); mbar_init(sb + FB_KF + 8 * i, 1); mbar_init(sb + FB_VF + 8 * i, 1);
        mbar_init(sb + FB_KE + 8 * i, 8); mbar_init(sb + FB_VE + 8 * i, 8); mbar_init(sb + FB_OF + 8 * i, 4); mbar_init(sb + FB_OE + 8 * i, 1);
    }
}
__device__ __forceinline__ void attn_helper(const AttnParams& P, uint32_t sb, int wg) {
    const uint32_t stg = sb + FO_O + wg * 16384;
    for (int n = 0;; n++) {
        mbar_wait(sb + FB_OF + 8 * wg, n & 1);
        int t;
        asm volatile("ld.shared.s32 %0, [%1];" : "=r"(t) : "r"(sb + FB_OSLOT + wg * 4) : "memory");
        const int qt = fa_qt(t), h = fa_head(t & 1023);
        tma_store_2d(&P.mapO, stg, 0, h * SEQ + qt * 128 + wg * 64);
        tma_store_2d(&P.mapO, stg + 8192, 64, h * SEQ + qt * 128 + wg * 64);
        asm volatile("cp.async.bulk.commit_group;" ::: "memory");
        asm volatile("cp.async.bulk.wait_group.read 0;" ::: "memory");
        mbar_arrive(sb + FB_OE + 8 * wg);
        asm volatile("cp.async.bulk.wait_group 0;" ::: "memory");
        signal_ctr(CT_CA + qt * 4 + (h >> 3));
        if (t >= 1024) break;
    }
}
__device__ __forceinline__ int attn_producer(const AttnParams& P, uint32_t sb, uint32_t free_bar, uint32_t free_par) {
    const uint32_t sQ = sb + FO_Q, sKV = sb + FO_KV;
    int b = 0, hp_ready = 0, vrow = 0, t = blockIdx.x, item = 0;
    auto load_v = [&](int i) {
        const uint32_t sv = sKV + (i & 1) * 65536 + 32768, bar = sb + FB_VF + 8 * (i & 1);
        mbar_wait(sb + FB_VE + 8 * (i & 1), ((i >> 1) & 1) ^ (FA_B0 ? ~i & 1 : 1));
        mbar_expect_tx(bar, 32768);
        tma_load_2d(sv, &P.mapV, bar, 0, vrow);
        tma_load_2d(sv + 16384, &P.mapV, bar, 64, vrow);
    };
    for (;; item++) {
        const bool valid = t < FA_ITEMS;
        const int qt = fa_qt(t), h = fa_head(t);
        if (valid && !((hp_ready >> (h >> 1)) & 1)) { wait_ctr(CT_AP + (h >> 1), 96u); hp_ready |= 1 << (h >> 1); }
        const uint32_t bq = sb + FB_QF + 8 * (item & 1);
        mbar_wait(item ? sb + FB_QE + 8 * (item & 1) : free_bar + 8, item ? ((item >> 1) & 1) ^ 1 : free_par);
        asm volatile("st.shared.s32 [%0], %1;" :: "r"(sb + FB_SLOT + (item & 1) * 4), "r"(valid ? t : -1) : "memory");
        if (!valid) { mbar_arrive(bq); break; }
        mbar_expect_tx(bq, 32768);
        tma_load_2d(sQ + (item & 1) * 32768, &P.mapQ, bq, 0, h * SEQ + qt * 128);
        tma_load_2d(sQ + (item & 1) * 32768 + 16384, &P.mapQ, bq, 64, h * SEQ + qt * 128);
#pragma unroll 1
        for (int j = 0; j <= qt; j++, b++) {
            const uint32_t sk = sKV + (b & 1) * 65536, bar = sb + FB_KF + 8 * (b & 1);
            mbar_wait(b >= 2 ? sb + FB_KE + 8 * (b & 1) : free_bar + 24 + 32 * b, b >= 2 ? ((b >> 1) & 1) ^ 1 : free_par);
            if (b == 1) { TS_END2(0, 256); TS_BEGIN2(1, 256); }
            if (b == 2) wait_ctr(CT_GATE, 256u);
            mbar_expect_tx(bar, 32768);
            tma_load_2d(sk, &P.mapK, bar, 0, h * SEQ + j * 128);
            tma_load_2d(sk + 16384, &P.mapK, bar, 64, h * SEQ + j * 128);
            if (j == max(qt - FA_TKA, 0)) t = take_ticket(CT_ATTN);
            if (b > 0) load_v(b - 1);
            vrow = h * SEQ + j * 128;
        }
        t += M_GRID;
    }
    load_v(b - 1);
    return b;
}
template <typename F>
__device__ __forceinline__ int attn_consumer(const AttnParams& P, int warp, F done, const uint32_t sb) {
    constexpr uint32_t sQ = SD + FO_Q, sKV = SD + FO_KV;
    const uint32_t sO = sb + FO_O;
    const uint32_t bar_qf = sb + FB_QF, bar_qe = sb + FB_QE, bar_kf = sb + FB_KF, bar_vf = sb + FB_VF, bar_ke = sb + FB_KE, bar_ve = sb + FB_VE,
                   bar_of = sb + FB_OF, bar_oe = sb + FB_OE, slot = sb + FB_SLOT, oslot = sb + FB_OSLOT;
    {
        const int wg = warp >> 2;
        const int lane = threadIdx.x & 31;
        const float sc = 0.08838834764831845f * 1.4426950408889634f;
        const int r0 = wg * 64 + (warp & 3) * 16 + (lane >> 2);
        float o[64], s[64];
        uint32_t pa[32];
        float m0 = 0.f, m1 = 0.f, l0 = 0.f, l1 = 0.f, i0 = 0.f, i1 = 0.f, g0 = 0.f, g1 = 0.f, gn0 = 0.f, gn1 = 0.f;
        const uint32_t q_lo = desc_lo(sQ + wg * 8192, 16), k_lo = desc_lo(sKV, 16), v_lo = desc_lo(sKV + 32768, 16384);
        auto issue_qk = [&](int b, int item, bool half) {
            const uint32_t qd = q_lo + (item & 1) * 2048, kd = k_lo + (b & 1) * 4096;
            const uint32_t kd2 = half ? kd - 512 : kd;
            wgmma_fence();
#pragma unroll
            for (int kk = 0; kk < 8; kk++) wgmma_ss_n128_lo<0>(s, qd + (kk >> 2) * 1024 + (kk & 3) * 2, kd2 + (kk >> 2) * 1024 + (kk & 3) * 2, kk != 0);
            wgmma_commit();
        };
        auto issue_pv = [&](int b, bool acc, int n, bool half) {
            const uint32_t vd = v_lo + (b & 1) * 4096;
            mbar_wait(bar_vf + 8 * (b & 1), (b >> 1) & 1);
            if (half) {
                asm volatile("wgmma.fence.sync.aligned;  // half" ::: "memory");
#pragma unroll
                for (int kk = 4; kk < 8; kk++) if (kk < n) wgmma_rs_n128_tb_lo(o, &pa[kk * 4], vd + (kk - 4) * 128, kk > 4 ? 1 : (int)acc);
                asm volatile("wgmma.commit_group.sync.aligned;  // half" ::: "memory");
                return;
            }
            wgmma_fence();
#pragma unroll
            for (int kk = 0; kk < 8; kk++) if (kk < n) wgmma_rs_n128_tb_lo(o, &pa[kk * 4], vd + kk * 128, kk ? 1 : (int)acc);
            wgmma_commit();
        };
        const int lim = (FA_TRIM ? (r0 | 64) : r0) - (lane & 3) * 2;
        uint32_t v_hi = v_lo;
        int acc_hi = 1;
        int item = -1, tnext = 0;
        uint32_t k_ready = 0, q_ready = 0;
        auto mask = [&](int i) { if ((i >> 2) * 8 + (i & 1) - ((i & 2) ? 8 : 0) > lim) s[i] = -INFINITY; };
        auto exps = [&](auto mode, int b, bool hand_over, float& u0, float& u1) {
            constexpr int MODE = decltype(mode)::value;
            float p[64], u[4] = {0.f, 0.f, 0.f, 0.f};
            const uint32_t vd = v_hi + ((b - 1) & 1) * 4096;
            constexpr int R = FA_TRIM && MODE == 2 ? 32 : 0;
#pragma unroll
            for (int i = 0; i < 4; i++) p[i] = fmaf(s[i ^ R], sc, (i & 2) ? -m1 : -m0);
#pragma unroll
            for (int g = 0; g < 16 + FA_LAG; g++) {
                if (MODE && g >= FA_I0 && g - FA_I0 < 8 - FA_P0) {
                    const int kk = FA_P0 + g - FA_I0;
                    wgmma_fence();
                    wgmma_rs_n128_tb_lo(o, &pa[kk * 4], vd + kk * 128, FA_TRIM && kk == 4 ? acc_hi : 1);
                    wgmma_commit();
                    if (kk == FA_HO) asm volatile("{\n.reg .pred p;\nsetp.ne.b32 p, %1, 0;\n@p bar.arrive %0, 256;\n}" :: "r"(4 - wg), "r"((int)hand_over) : "memory");
                }
                if (R && g == 8 && wg == 0) {
                    wgmma_wait<0>();
                    mbar_arrive_if(bar_ve + 8 * ((b - 1) & 1), lane == 0);
                    k_ready = q_ready = 0;
#pragma unroll
                    for (int i = 32 - FA_LAG * 4; i < 32; i++) u[i & 3] += p[i];
#pragma unroll
                    for (int i = 0; i < 16; i++) pa[16 + i] = pack_bf16(p[i * 2], p[i * 2 + 1]);
                    break;
                }
                if (MODE && g == FA_SPLIT) {
                    FAT(b, 2);
                    wgmma_wait<0>();
                    FAT(b - 1, 3);
                    mbar_arrive_if(bar_ve + 8 * ((b - 1) & 1), lane == 0);
                }
                if (MODE && g == FA_TG) {
                    k_ready = mbar_test(bar_kf + 8 * (~b & 1), ((b + 1) >> 1) & 1);
                    if (MODE == 2) {
                        q_ready = mbar_test(bar_qf + 8 * (~item & 1), ((item + 1) >> 1) & 1);
                        asm volatile("ld.shared.s32 %0, [%1];" : "=r"(tnext) : "r"(slot + (~item & 1) * 4) : "memory");
                    }
                }
#pragma unroll
                for (int j = 0; j < 4; j++) {
                    const int i = g * 4 + j;
                    if (g < 16) p[i] = ex2v(p[i]);
                    if (g < 15) {
                        if (MODE == 2 && (!R || i + 4 < 32)) mask((i + 4) ^ R);
                        p[i + 4] = fmaf(s[(i + 4) ^ R], sc, (i & 2) ? -m1 : -m0);
                    }
                    if (g >= FA_LAG) u[j] += p[i - FA_LAG * 4];
                }
#pragma unroll
                for (int gg = 0; gg < 16; gg++) {
                    const int at = MODE && gg + FA_LAG < FA_SPLIT + gg / FA_PK ? FA_SPLIT + gg / FA_PK : gg + FA_LAG;
                    if (at == g) { pa[(gg * 2) ^ (R / 2)] = pack_bf16(p[gg * 4], p[gg * 4 + 1]); pa[(gg * 2 + 1) ^ (R / 2)] = pack_bf16(p[gg * 4 + 2], p[gg * 4 + 3]); }
                }
                if (MODE && g < 16) sched_fence(b, g + MODE * 32, &p[g * 4], &p[(g < 15 ? g + 1 : g) * 4], u);
            }
            u0 = u[0] + u[1]; u1 = u[2] + u[3];
        };
        auto quad_max = [&](float& x0, float& x1) {
            x0 = fmaxf(x0, __shfl_xor_sync(0xffffffff, x0, 1)); x1 = fmaxf(x1, __shfl_xor_sync(0xffffffff, x1, 1));
            x0 = fmaxf(x0, __shfl_xor_sync(0xffffffff, x0, 2)); x1 = fmaxf(x1, __shfl_xor_sync(0xffffffff, x1, 2));
            x0 = fmaf(x0, sc, FA_MARGIN); x1 = fmaf(x1, sc, FA_MARGIN);
        };
        auto softmax_exact = [&](bool fresh, bool half, int b) {
            wgmma_wait<0>();
            if (half) {
#pragma unroll
                for (int i = 0; i < 32; i++) s[i] = -INFINITY;
            }
            float x[8];
#pragma unroll
            for (int i = 0; i < 8; i++) x[i] = fmaxf(s[i * 2], s[i * 2 + 1]);
#pragma unroll
            for (int i = 8; i < 32; i++) x[i & 7] = fmaxf(x[i & 7], fmaxf(s[i * 2], s[i * 2 + 1]));
            float x0 = fmaxf(fmaxf(x[0], x[2]), fmaxf(x[4], x[6])), x1 = fmaxf(fmaxf(x[1], x[3]), fmaxf(x[5], x[7]));
            quad_max(x0, x1);
            if (!fresh) {
                x0 = fmaxf(x0, m0); x1 = fmaxf(x1, m1);
                const float a0 = ex2f(m0 - x0), a1 = ex2f(m1 - x1);
                l0 *= a0; l1 *= a1;
#pragma unroll
                for (int i = 0; i < 16; i++) { o[i * 4 + 0] *= a0; o[i * 4 + 1] *= a0; o[i * 4 + 2] *= a1; o[i * 4 + 3] *= a1; }
            }
            m0 = x0; m1 = x1;
            float u0, u1;
            exps(std::integral_constant<int, 0>(), b, false, u0, u1);
            l0 += u0; l1 += u1;
        };
        auto finish_rows = [&]() {
            l0 += __shfl_xor_sync(0xffffffff, l0, 1); l1 += __shfl_xor_sync(0xffffffff, l1, 1);
            l0 += __shfl_xor_sync(0xffffffff, l0, 2); l1 += __shfl_xor_sync(0xffffffff, l1, 2);
            asm("rcp.approx.ftz.f32 %0, %1;" : "=f"(i0) : "f"(l0));
            asm("rcp.approx.ftz.f32 %0, %1;" : "=f"(i1) : "f"(l1));
            i0 *= g0; i1 *= g1;
        };
        auto clear_out = [&](int t) {
            if (t >= 384) {
                bf16* z = P.out + (size_t)(fa_qt(t) * 128 + wg * 64 + ((threadIdx.x & 127) >> 3)) * DM + (t & 7) * 64 + (lane & 7) * 8;
#pragma unroll
                for (int i = 0; i < 4; i++) *reinterpret_cast<uint4*>(z + i * 16 * DM) = make_uint4(0u, 0u, 0u, 0u);
            }
        };
        auto store_o = [&](int t, int n) {
            const uint32_t stg = sO + wg * 16384;
            {
                mbar_wait(bar_oe + 8 * wg, (n & 1) ^ 1);
                asm volatile("st.shared.s32 [%0], %1;" :: "r"(oslot + wg * 4), "r"(t) : "memory");
            }
            const int row = (warp & 3) * 16 + (lane >> 2);
#pragma unroll
            for (int i = 0; i < 4; i++) {
                const int ch = i * 4 + (lane & 3);
                const uint32_t a = stg + (ch >> 3) * 8192 + row * 128 + (((ch & 7) ^ (row & 7)) << 4);
                const float* q = &o[i * 16];
                asm volatile("st.shared.v4.b32 [%0], {%1, %2, %3, %4};" :: "r"(a), "r"(pack_bf16(q[0] * i0, q[1] * i0)), "r"(pack_bf16(q[4] * i0, q[5] * i0)),
                             "r"(pack_bf16(q[8] * i0, q[9] * i0)), "r"(pack_bf16(q[12] * i0, q[13] * i0)) : "memory");
                asm volatile("st.shared.v4.b32 [%0], {%1, %2, %3, %4};" :: "r"(a + 1024), "r"(pack_bf16(q[2] * i1, q[3] * i1)), "r"(pack_bf16(q[6] * i1, q[7] * i1)),
                             "r"(pack_bf16(q[10] * i1, q[11] * i1)), "r"(pack_bf16(q[14] * i1, q[15] * i1)) : "memory");
            }
        };
        auto publish_o = [&]() {
            asm volatile("fence.proxy.async.shared::cta;" ::: "memory");
            __syncwarp();
            mbar_arrive_if(bar_of + 8 * wg, lane == 0);
        };
        int t = 0, left = 0, tdone = -1, b = 0, nout = 0;
        bool first = true, staged = false;
#pragma unroll 1
        for (;; b++) {
            const bool fresh = left == 0;
            const int tprev = t;
            FAT(b, 4);
            if (staged) { publish_o(); staged = false; }
            if (fresh) {
                item++;
                if (!q_ready) {
                    mbar_wait(bar_qf + 8 * (item & 1), (item >> 1) & 1);
                    asm volatile("ld.shared.s32 %0, [%1];" : "=r"(tnext) : "r"(slot + (item & 1) * 4) : "memory");
                }
                if (tnext < 0) break;
                t = tnext;
                left = fa_qt(t) + 1;
            }
            left--;
            if (fresh || first || left == 0) {
                if (tdone >= 0) store_o(tdone, nout);
                if (fresh) { g0 = gn0; g1 = gn1; }
                if (left == 0) { gn0 = __ldcg(g_gate + fa_qt(t) * 128 + r0); gn1 = __ldcg(g_gate + fa_qt(t) * 128 + r0 + 8); clear_out(t); }
            }
            FAT(b, 5);
            if (!k_ready) mbar_wait(bar_kf + 8 * (b & 1), (b >> 1) & 1);
            FAT(b, 6);
            asm volatile("bar.sync %0, 256;" :: "r"(3 + wg) : "memory");
            FAT(b, 0);
            issue_qk(b, item, FA_TRIM && wg == 0 && left == 0);
            FAT(b, 7);
            bool early = false;
            if (!fresh && !first && left != 0) {
                issue_pv(b - 1, true, FA_P0, false);
                wgmma_wait<1>();
                FAT(b, 1);
                mbar_arrive_if(bar_ke + 8 * (b & 1), lane == 0);
            } else {
                const bool hprev = FA_TRIM && fresh && wg == 0;
                early = (FA_EARLY && tdone >= 0) || b == 0 || (FA_TE && hprev);
                if (early) asm volatile("bar.arrive %0, 256;" :: "r"(4 - wg) : "memory");
                if (tdone >= 0) { nout++; staged = true; }
                tdone = fresh && b > 0 ? tprev : -1;
                v_hi = hprev ? v_lo - 512 : v_lo;
                acc_hi = !(hprev && first);
                if (b > 0) issue_pv(b - 1, !first, FA_P0, hprev); else { wgmma_fence(); wgmma_commit(); }
                first = fresh;
                wgmma_wait<1>();
                FAT(b, 1);
                mbar_arrive_if(bar_ke + 8 * (b & 1), lane == 0);
                mbar_arrive_if(bar_qe + 8 * (item & 1), lane == 0 && left == 0);
                if (left == 0) { mask(FA_TRIM ? 32 : 0); mask(FA_TRIM ? 33 : 1); }
                if (fresh) {
                    finish_rows();
                    l0 = l1 = 0.f;
                    m0 = fmaxf(s[0], s[1]); m1 = fmaxf(s[2], s[3]);
                    if (FA_TRIM && left == 0) { m0 = fmaxf(s[32], s[33]); m1 = fmaxf(s[34], s[35]); }
                    quad_max(m0, m1);
                }
            }
            if (FA_B0 || b > 0) {
                float u0, u1;
                if (left == 0) exps(std::integral_constant<int, 2>(), b, !early, u0, u1);
                else exps(std::integral_constant<int, 1>(), b, !early, u0, u1);
                if (!__any_sync(0xffffffff, !(u0 + u1 < 1.f))) { l0 += u0; l1 += u1; continue; }
            }
            softmax_exact(fresh, FA_TRIM && wg == 0 && left == 0, b);
        }
        if (tdone >= 0) { store_o(tdone, nout++); publish_o(); }
        issue_pv(b - 1, !first, 8, FA_TRIM && wg == 0);
        g0 = gn0; g1 = gn1;
        finish_rows();
        wgmma_wait<0>();
        done();
        store_o(t + 1024, nout);
        publish_o();
        return nout;
    }
}

__device__ __forceinline__ uint32_t cluster_ctarank() {
    uint32_t r; asm volatile("mov.u32 %0, %%cluster_ctarank;" : "=r"(r)); return r;
}
__device__ __forceinline__ uint32_t mapa_u32(uint32_t addr, uint32_t rank) {
    uint32_t r; asm volatile("mapa.shared::cluster.u32 %0, %1, %2;" : "=r"(r) : "r"(addr), "r"(rank)); return r;
}
__device__ __forceinline__ void cluster_sync_all() {
    asm volatile("barrier.cluster.arrive.release.aligned;\nbarrier.cluster.wait.acquire.aligned;" ::: "memory");
}
__device__ __forceinline__ void st_async_v4(uint32_t addr, uint32_t a, uint32_t b, uint32_t c, uint32_t d, uint32_t mbar) {
    asm volatile("st.async.weak.shared::cluster.mbarrier::complete_tx::bytes.v4.b32 [%0], {%1, %2, %3, %4}, [%5];"
                 :: "r"(addr), "r"(a), "r"(b), "r"(c), "r"(d), "r"(mbar) : "memory");
}
__device__ __forceinline__ void st_async_v2(uint32_t addr, uint32_t a, uint32_t b, uint32_t mbar) {
    asm volatile("st.async.weak.shared::cluster.mbarrier::complete_tx::bytes.v2.b32 [%0], {%1, %2}, [%3];"
                 :: "r"(addr), "r"(a), "r"(b), "r"(mbar) : "memory");
}
__device__ __forceinline__ void st_async_b32(uint32_t addr, uint32_t a, uint32_t mbar) {
    asm volatile("st.async.weak.shared::cluster.mbarrier::complete_tx::bytes.b32 [%0], %1, [%2];" :: "r"(addr), "r"(a), "r"(mbar) : "memory");
}
__device__ __forceinline__ void pace(int cycles) {
    if (cycles > 0) {
        uint32_t t0, t;
        asm volatile("mov.u32 %0, %%clock;" : "=r"(t0));
        do { asm volatile("mov.u32 %0, %%clock;" : "=r"(t)); } while (t - t0 < (uint32_t)cycles);
    }
}
__device__ __forceinline__ void mbar_wait_cl(uint32_t bar, uint32_t parity) {
    uint32_t done = 0;
    for (int it = 0; it < WAIT_LIMIT && !done; it++) {
        asm volatile(
            "{\n.reg .pred p;\n"
            "mbarrier.try_wait.parity.shared::cta.b64 p, [%1], %2;\n"
            "selp.u32 %0, 1, 0, p;\n}\n" : "=r"(done) : "r"(bar), "r"(parity) : "memory");
    }
}
__device__ __forceinline__ void ldmatrix_x4(uint32_t& r0, uint32_t& r1, uint32_t& r2, uint32_t& r3, uint32_t addr) {
    asm volatile("ldmatrix.sync.aligned.m8n8.x4.shared.b16 {%0,%1,%2,%3}, [%4];"
                 : "=r"(r0), "=r"(r1), "=r"(r2), "=r"(r3) : "r"(addr));
}
__device__ __forceinline__ void cp_async16(uint32_t dst, const void* src) {
    asm volatile("cp.async.cg.shared.global [%0], [%1], 16;" :: "r"(dst), "l"(src) : "memory");
}
__device__ __forceinline__ float bf16r(float x) { return __uint_as_float(pack_bf16(0.f, x) & 0xffff0000u); }

#define DBGP(i, w, ok)
#define DBG(i, w)
#define DBGD(i, w, dep)
#define DBG_EXTRA 0
__device__ __forceinline__ void tma_load_2d_mc(uint32_t dst, const CUtensorMap* map, uint32_t bar, int c0, int c1, uint16_t mask) {
    asm volatile(
        "cp.async.bulk.tensor.2d.shared::cluster.global.mbarrier::complete_tx::bytes.multicast::cluster [%0], [%1, {%3, %4}], [%2], %5;"
        :: "r"(dst), "l"((uint64_t)map), "r"(bar), "r"(c0), "r"(c1), "h"(mask) : "memory");
}
__device__ __forceinline__ void stmatrix_x4_trans(uint32_t addr, uint32_t r0, uint32_t r1, uint32_t r2, uint32_t r3) {
    asm volatile("stmatrix.sync.aligned.m8n8.x4.trans.shared.b16 [%0], {%1, %2, %3, %4};" :: "r"(addr), "r"(r0), "r"(r1), "r"(r2), "r"(r3) : "memory");
}
__device__ __forceinline__ void stmatrix_x2_trans(uint32_t addr, uint32_t r0, uint32_t r1) {
    asm volatile("stmatrix.sync.aligned.m8n8.x2.trans.shared.b16 [%0], {%1, %2};" :: "r"(addr), "r"(r0), "r"(r1) : "memory");
}
__device__ __forceinline__ uint4 lds128(uint32_t a) {
    uint4 v; asm volatile("ld.shared.v4.u32 {%0, %1, %2, %3}, [%4];" : "=r"(v.x), "=r"(v.y), "=r"(v.z), "=r"(v.w) : "r"(a) : "memory"); return v;
}
__device__ __forceinline__ void sts128(uint32_t a, uint32_t x, uint32_t y, uint32_t z, uint32_t w) {
    asm volatile("st.shared.v4.b32 [%0], {%1, %2, %3, %4};" :: "r"(a), "r"(x), "r"(y), "r"(z), "r"(w) : "memory");
}
__device__ __forceinline__ float2 lds64f(uint32_t a) {
    float2 v; asm volatile("ld.shared.v2.f32 {%0, %1}, [%2];" : "=f"(v.x), "=f"(v.y) : "r"(a) : "memory"); return v;
}
__device__ __forceinline__ void fence_async_smem() { asm volatile("fence.proxy.async.shared::cta;" ::: "memory"); }
#define ACC16(d) "+f"(d[0]), "+f"(d[1]), "+f"(d[2]), "+f"(d[3]), "+f"(d[4]), "+f"(d[5]), "+f"(d[6]), "+f"(d[7]), "+f"(d[8]), "+f"(d[9]), "+f"(d[10]), "+f"(d[11]), "+f"(d[12]), "+f"(d[13]), "+f"(d[14]), "+f"(d[15])
template <int ND>
__device__ __forceinline__ void wgmma_rs_n32(float (&d)[ND], const uint32_t (&a)[4], uint32_t db_lo, int scale_d) {
    asm volatile(
        "{\n.reg .pred p;\n.reg .b64 db;\nsetp.ne.b32 p, %21, 0;\nmov.b64 db, {%20, 0x40000040};\n"
        "wgmma.mma_async.sync.aligned.m64n32k16.f32.bf16.bf16 {%0,%1,%2,%3,%4,%5,%6,%7,%8,%9,%10,%11,%12,%13,%14,%15}, {%16,%17,%18,%19}, db, p, 1, 1, 0;\n}\n"
        : ACC16(d) : "r"(a[0]), "r"(a[1]), "r"(a[2]), "r"(a[3]), "r"(db_lo), "r"(scale_d));
}
template <int ND>
__device__ __forceinline__ void wgmma_ss_n32(float (&d)[ND], uint32_t da_lo, uint32_t db_lo, int scale_d) {
    asm volatile(
        "{\n.reg .pred p;\n.reg .b64 da, db;\nsetp.ne.b32 p, %18, 0;\nmov.b64 da, {%16, 0x40000040};\nmov.b64 db, {%17, 0x40000040};\n"
        "wgmma.mma_async.sync.aligned.m64n32k16.f32.bf16.bf16 {%0,%1,%2,%3,%4,%5,%6,%7,%8,%9,%10,%11,%12,%13,%14,%15}, da, db, p, 1, 1, 1, 0;\n}\n"
        : ACC16(d) : "r"(da_lo), "r"(db_lo), "r"(scale_d));
}
__device__ __forceinline__ void wgmma_ss_n8(float (&d)[4], uint32_t da_lo, uint32_t db_lo, int scale_d) {
    asm volatile(
        "{\n.reg .pred p;\n.reg .b64 da, db;\nsetp.ne.b32 p, %6, 0;\nmov.b64 da, {%4, 0x40000040};\nmov.b64 db, {%5, 0x00000010};\n"
        "wgmma.mma_async.sync.aligned.m64n8k16.f32.bf16.bf16 {%0,%1,%2,%3}, da, db, p, 1, 1, 1, 0;\n}\n"
        : "+f"(d[0]), "+f"(d[1]), "+f"(d[2]), "+f"(d[3]) : "r"(da_lo), "r"(db_lo), "r"(scale_d));
}

#define SCHED_FENCE()
__device__ __forceinline__ void wgmma_ss_n32_p(float (&d)[16], uint32_t da_lo, uint32_t db_lo, int scale_d) {
    asm volatile(
        "{\n.reg .pred p;\n.reg .b64 da, db;\nsetp.ne.b32 p, %18, 0;\nmov.b64 da, {%16, 0x40000040};\nmov.b64 db, {%17, 0x00000030};\n"
        "wgmma.mma_async.sync.aligned.m64n32k16.f32.bf16.bf16 {%0,%1,%2,%3,%4,%5,%6,%7,%8,%9,%10,%11,%12,%13,%14,%15}, da, db, p, 1, 1, 1, 0;\n}\n"
        : ACC16(d) : "r"(da_lo), "r"(db_lo), "r"(scale_d));
}

#define ACC20(d) ACC16(d), "+f"(d[16]), "+f"(d[17]), "+f"(d[18]), "+f"(d[19])
#define ACC20_STR "{%0,%1,%2,%3,%4,%5,%6,%7,%8,%9,%10,%11,%12,%13,%14,%15,%16,%17,%18,%19}"
__device__ __forceinline__ void wgmma_rs_n40(float (&d)[20], const uint32_t (&a)[4], uint32_t db_lo, int scale_d) {
    asm volatile(
        "{\n.reg .pred p;\n.reg .b64 db;\nsetp.ne.b32 p, %25, 0;\nmov.b64 db, {%24, 0x40000040};\n"
        "wgmma.mma_async.sync.aligned.m64n40k16.f32.bf16.bf16 " ACC20_STR ", {%20,%21,%22,%23}, db, p, 1, 1, 0;\n}\n"
        : ACC20(d) : "r"(a[0]), "r"(a[1]), "r"(a[2]), "r"(a[3]), "r"(db_lo), "r"(scale_d));
}
template <int TA, int SBO>
__device__ __forceinline__ void wgmma_ss_n40(float (&d)[20], uint32_t da_lo, uint32_t db_lo, int scale_d) {
    asm volatile(
        "{\n.reg .pred p;\n.reg .b64 da, db;\nsetp.ne.b32 p, %22, 0;\nmov.b64 da, {%20, %23};\nmov.b64 db, {%21, 0x40000040};\n"
        "wgmma.mma_async.sync.aligned.m64n40k16.f32.bf16.bf16 " ACC20_STR ", da, db, p, 1, 1, %24, 0;\n}\n"
        : ACC20(d) : "r"(da_lo), "r"(db_lo), "r"(scale_d), "n"(0x40000000 + SBO / 16), "n"(TA));
}
template <int SBO>
__device__ __forceinline__ void wgmma_ss_n48(float (&d)[24], uint32_t da_lo, uint32_t db_lo, int scale_d) {
    asm volatile(
        "{\n.reg .pred p;\n.reg .b64 da, db;\nsetp.ne.b32 p, %26, 0;\nmov.b64 da, {%24, %27};\nmov.b64 db, {%25, 0x40000040};\n"
        "wgmma.mma_async.sync.aligned.m64n48k16.f32.bf16.bf16 {%0,%1,%2,%3,%4,%5,%6,%7,%8,%9,%10,%11,%12,%13,%14,%15,%16,%17,%18,%19,%20,%21,%22,%23}, da, db, p, 1, 1, 0, 0;\n}\n"
        : ACC20(d), "+f"(d[20]), "+f"(d[21]), "+f"(d[22]), "+f"(d[23]) : "r"(da_lo), "r"(db_lo), "r"(scale_d), "n"(0x40000000 + SBO / 16));
}

#define PT(i, th)
struct ChainParams {
    CUtensorMap mapW[3];
    CUtensorMap mapX;
    CUtensorMap mapC;
    CUtensorMap mapWo;
    CUtensorMap mapM;
    CUtensorMap mapOut;
};
constexpr int CH_BLOCK = 384;
constexpr int CO_WO = 0;
constexpr int CH_XC = 5120, CH_XP = 8 * CH_XC;
constexpr int CO_XB = 65536;
constexpr int CO_OB = CO_XB + 2 * CH_XP;
constexpr int CO_P = CO_OB + 8192;
constexpr int CO_LS = CO_P + 3072;
constexpr int CO_SC = CO_LS + 8 * 1280;
constexpr int CH_TW = 6144 + 8192;
constexpr int CO_T = 21 * 8192;
constexpr int CO_WA = CO_T + 6144;
constexpr int CO_ST = CO_T + 3 * CH_TW + 6144;
constexpr int CO_OWN = CO_ST + 4096, CO_OWN2 = CO_SC + 1536;
constexpr int CO_BAR = CO_OWN + 4096;
constexpr int CH_SMEM = CO_BAR + 256 + DBG_EXTRA;
#define CH_GL 2
#define CH_A3 1
#define CH_D0 0
#define CH_PF 0
#define CH_NA 0
#define CH_LQ ""
#define CH_SQ ""
#define CH_XPF 0
#define CH_NSM 4
static_assert(CO_OWN2 + 1024 <= CO_T && CH_NSM <= 4, "smem layout");
#ifndef M_D0
#define M_D0 0
#endif
#define CH_SG 2
#define CH_XS 1
#define CH_V3 1
#define CH_POLL_DELAY 240
#define CH_VPOS 2
#define CH_OW 12
#define CH_OF 12
#define CH_Q0 0
#define CH_QI 12
#define CH_QX 0
#define CH_Q1 (CH_Q0 + CH_QI + CH_QX)
#define CH_VA 5
#define CH_SPOS 0
#define CH_LSW 1
#define CH_QE 16
#define CH_KE 16
#define CH_QD 0
#define CH_GAP 0
#define CH_QS 0
#define CH_KS 0
#define CH_VS 4
#define CH_A7 7
#define CH_RF 0
#define CH_LSS 0
#define CH_OS 1
#define CH_MG 0
#define CH_MBT 0x76543210u
#define CH_MB(i) ((int)(CH_MBT >> 4 * (i)) & 7)
#define CH_AS 0x64207531u
#define CH_QL 16
#define CH_ML 0x112112
#define CH_DEP 1
#define CH_SP 2
#define CH_VD 0
#define CH_MP 2
#define CH_MP0 2
#define CH_OFE 3
#define CH_MS 1
#define CH_HA 3
#define CH_LD 4
#define CH_TWP 0
#define CH_SUMC 2
#define CH_ES 0
#define CH_ST 224
#define CH_KEEP 1
#define CH_PINB 1
#define CH_DRY 1
#define CH_D1 4500
#define CH_D2 12500
#define CH_CHAINS 4

constexpr float CH_SC = 0.08838834764831845f * 1.4426950408889634f;
__device__ __forceinline__ uint32_t pin(uint32_t v) { return __shfl_sync(0xffffffff, v, threadIdx.x & 31); }

__device__ __forceinline__ void out_finished() {
    if (atomicAdd(&g_ctr[CT_FIN], 1u) == M_GRID + 64 - 1)
        for (int i = 0; i < CT_N / 4; i++) reinterpret_cast<uint4*>(g_ctr)[i] = make_uint4(0u, 0u, 0u, 0u);
}
__device__ __forceinline__ uint32_t tail_a(uint32_t c) { return c < 3 ? CO_XB + 2 * CH_XC + c * 8192 : CO_OB; }
__device__ __forceinline__ void out_flush_half(const float* acc, const CUtensorMap* map, uint32_t stg, int tid, int bar, int n0, int m0) {
    const int lane = tid & 31, row = (lane & 7) + ((lane >> 3) & 1) * 8;
#pragma unroll
    for (int j = 0; j < 16; j += 2) {
        const float* a = &acc[j * 4];
        stmatrix_x4(stg + (j >> 3) * 8192 + (((tid >> 5) & 3) * 16 + row) * 128 + ((((j & 7) + (lane >> 4)) ^ (row & 7)) << 4),
                    pack_bf16(a[0], a[1]), pack_bf16(a[2], a[3]), pack_bf16(a[4], a[5]), pack_bf16(a[6], a[7]));
    }
    asm volatile("fence.proxy.async.shared::cta;\nbar.sync %0, 128;" :: "r"(bar) : "memory");
    asm volatile("{\n.reg .pred p;\nsetp.ne.b32 p, %0, 0;\n@p bra FL_SKIP;\n"
                 "cp.reduce.async.bulk.tensor.2d.global.shared::cta.add.tile.bulk_group [%1, {%3, %5}], [%2];\n"
                 "cp.reduce.async.bulk.tensor.2d.global.shared::cta.add.tile.bulk_group [%1, {%4, %5}], [%2 + 8192];\n"
                 "cp.async.bulk.commit_group;\nFL_SKIP:\n}"
                 :: "r"(tid & 127), "l"((uint64_t)map), "r"(stg), "r"(n0), "r"(n0 + 64), "r"(m0) : "memory");
    __syncwarp();
}
__device__ __forceinline__ void out_flush(const float (&acc)[128], const CUtensorMap* map, uint32_t stg0, uint32_t stg1, int tid, int bar, int n0, int m0) {
    out_flush_half(acc, map, stg0, tid, bar, n0, m0);
    out_flush_half(acc + 64, map, stg1, tid, bar, n0 + 128, m0);
}

__global__ void __cluster_dims__(8, 1, 1) __launch_bounds__(CH_BLOCK, 1)
chain_kernel(const __grid_constant__ ChainParams P) {
    extern __shared__ uint8_t smem_raw[];
    const int tid = threadIdx.x, warp = __shfl_sync(0xffffffff, tid >> 5, 0), lane = tid & 31;
    const int rank = (int)cluster_ctarank();
    constexpr uint32_t sd = 1024;
    const uint32_t sb = ((uint32_t)rank << 24) + sd;
    if (smem_u32(smem_raw) != sb) __trap();
    const int C = blockIdx.x >> 3;
    const int h = C * 4 + (rank >> 1);
    const int qd = lane >> 2, qc = lane & 3;
    const int t4 = warp & 3, wg = warp >> 2;
    pdl_launch_dependents();
    uint32_t t_start;
    asm volatile("mov.u32 %0, %%clock;" : "=r"(t_start));
    t_start = __shfl_sync(0xffffffff, t_start, 0);
    TS_BEGIN(2);
    PT(0, 0);
    const uint32_t bar_mem = sb + CO_BAR + 128, bar_o = sb + CO_BAR + 32, bar_sc = bar_o + 32, bar_x = bar_sc + 8, bar_l = bar_x + 16, bar_w = bar_l + 8;
    const uint32_t bar_wo = bar_o + 24;
    auto chunk = [&](int i) { return (uint32_t)((rank - i) & 7); };
    auto mine = [](int g, int c) { return (int)((CH_AS >> (g * 16 + c * 4)) & 7); };
    const int wcol = h * HD + (rank & 1) * 64;
    auto wdst = [&](int g, int i) { return i == 0 ? CO_WA + g * CH_TW : g && i == 7 ? CO_ST : (g ? CO_XB + CH_XP : 0) + (i - 1) * 8192; };
    auto vdst = [&](int i) { return i >= 2 && i < 10 ? CO_XB + CH_XP + (i - 2) * CH_XC : (i < 2 ? CO_WA + 2 * CH_TW : i < 12 ? CO_OB : i < 14 ? CO_LS : CO_ST) + (i & 1) * 4096; };
    if ((tid & 127) == 0) {
        pace(CH_D0);
        const uint32_t bar = wg == 2 ? bar_x : bar_w + 8 * wg;
        mbar_init(bar, 1);
        asm volatile("fence.mbarrier_init.release.cluster;" ::: "memory");
        mbar_expect_tx(bar, wg == 2 ? CH_XP : 65536);
#pragma unroll 1
        for (int i = 0; i < 8; i++) {
            if (wg == 2) {
                tma_load_2d(sb + CO_XB + i * CH_XC, &P.mapX, bar, i * 64, 0);
                tma_load_2d(sb + CO_XB + i * CH_XC + 4096, &P.mapM, bar, i * 64, 0);
            } else tma_load_2d(sb + wdst(wg, i), &P.mapW[wg ^ (i & 1)], bar, wcol, chunk(mine(wg, i >> 1)) * 64);
        }
    }
    if (warp == 9 && lane < 24 && lane != 9 && (lane >> 1) != 6) {
        mbar_init(sb + CO_BAR + 8 * lane, lane == 15 ? 16 : 1);
        asm volatile("fence.mbarrier_init.release.cluster;" ::: "memory");
    }
    __syncthreads();
    PT(1, 0);
    if (wg == 2 || (wg == 0 && CH_QL < 16)) asm volatile("bar.arrive 10, %0;" :: "n"(CH_QL < 16 ? 384 : 256) : "memory");
    if (wg == 2) {
        const int t = tid - 256;
        sts128(sb + CO_T + (2 + (t >> 6)) * CH_TW + 5120 + (t & 63) * 16, 0u, 0u, 0u, 0u);
        if (t < 32) sts128(sb + CO_P + (t >> 3) * 768 + 640 + (t & 7) * 16, 0u, 0u, 0u, 0u);
    }
    const uint32_t wfrag = (((lane >> 4) << 3) + (lane & 7)) * 128 + (((t4 * 2 + ((lane >> 3) & 1)) ^ (lane & 7)) << 4);
    const uint32_t aO = pin(sb + wg * CH_TW + wfrag);
    const uint32_t aL = pin(sb + lane * 16);
    uint32_t w[32][4];
    auto load_w = [&](int g, bool v) {
#pragma unroll
        for (int e = CH_NSM; e < 32; e++) ldmatrix_x4_trans(w[e][0], w[e][1], w[e][2], w[e][3], aO + ((v ? vdst(e >> 1) + (e & 1) * 2048 : wdst(g, e >> 2) + (e & 3) * 2048) - g * CH_TW));
        fence_async_smem();
    };
    auto pass = [&](auto& d, int g, int b, int j0, int j1, int js, bool group = true) {
        const uint32_t lo = desc_lo(sd + CO_XB + b * CH_XP, 16);
        if (group) wgmma_fence();
#pragma unroll
        for (int j = 0; j < 32; j++) if (j >= j0 && j < j1) {
            const int f = js < 0 ? j : j < js ? j + CH_NSM : j < js + CH_NSM ? j - js : j;
            const int e = sizeof(d) == 64 ? (f >> 2) * 8 + (js < 0 ? 4 : 0) + (f & 3) : f;
            const uint32_t db = lo + chunk(sizeof(d) == 64 ? mine(g, f >> 2) : f >> 2) * (CH_XC / 16) + (e & 3) * 2, da = desc_lo(sd + CO_WA + g * CH_TW + e * 2048, 16);
            if constexpr (sizeof(d) == 64) { if (e < CH_NSM) wgmma_ss_n32(d, da, db, j != 0); else wgmma_rs_n32(d, w[e], db, j != 0); }
            else { if (e < CH_NSM) wgmma_ss_n40<1, 1024>(d, da, db, j != 0); else wgmma_rs_n40(d, w[e], db, j != 0); }
        }
        if (group) wgmma_commit();
    };
    auto uni = [](uint32_t v) { return __shfl_sync(0xffffffff, v, 0); };
    auto roff = [&](int j) { return (uint32_t)(((rank + j) & 7) - rank) << 24; };
    auto store32 = [&](const float* d, uint32_t a) {
        stmatrix_x4_trans(a, pack_bf16(d[0], d[1]), pack_bf16(d[2], d[3]), pack_bf16(d[4], d[5]), pack_bf16(d[6], d[7]));
        stmatrix_x4_trans(a + 2048, pack_bf16(d[8], d[9]), pack_bf16(d[10], d[11]), pack_bf16(d[12], d[13]), pack_bf16(d[14], d[15]));
    };
    auto load32 = [&](uint32_t (&r)[8], uint32_t a) {
        ldmatrix_x4_trans(r[0], r[1], r[2], r[3], a);
        ldmatrix_x4_trans(r[4], r[5], r[6], r[7], a + 2048);
    };
    auto add32 = [&](float* d, const uint32_t (&r)[8], uint32_t a) {
        wgmma_wait<0>();
#pragma unroll
        for (int i = 0; i < 8; i++) { d[2 * i] += __uint_as_float(r[i] << 16); d[2 * i + 1] += __uint_as_float(r[i] & 0xffff0000u); }
        store32(d, a);
    };
    auto scores = [&](float (&d)[24], auto sbo, uint32_t q) {
        wgmma_fence();
#pragma unroll
        for (int ks = 0; ks < 4; ks++) wgmma_ss_n48<decltype(sbo)::value>(d, desc_lo(sd + q, 16) + ks * 2, desc_lo(sd + CO_T + CH_TW, 16) + ks * 2, ks != 0);
        wgmma_commit();
    };
    auto add_scores = [&](uint32_t a, uint32_t b, float (&v)[10]) {
        const uint4 a0 = lds128(a), a1 = lds128(a + 512);
        const float2 a2 = lds64f(b);
        v[0] += __uint_as_float(a0.x); v[1] += __uint_as_float(a0.y); v[2] += __uint_as_float(a0.z); v[3] += __uint_as_float(a0.w);
        v[4] += __uint_as_float(a1.x); v[5] += __uint_as_float(a1.y); v[6] += __uint_as_float(a1.z); v[7] += __uint_as_float(a1.w);
        v[8] += a2.x; v[9] += a2.y;
    };
    auto row_max = [&](const float (&v)[10]) {
        float mx = fmaxf(fmaxf(fmaxf(v[0], v[1]), fmaxf(v[2], v[3])), fmaxf(fmaxf(v[4], v[5]), fmaxf(v[6], v[7])));
        mx = fmaxf(mx, fmaxf(v[8], v[9]));
        mx = fmaxf(mx, __shfl_xor_sync(0xffffffff, mx, 1));
        return fmaxf(mx, __shfl_xor_sync(0xffffffff, mx, 2)) * CH_SC;
    };
    auto local_pv = [&](int s, int st) {
        float dc[16];
        wgmma_fence();
#pragma unroll
        for (int ks = 0; ks < 3; ks++) wgmma_ss_n32_p(dc, desc_lo(sd + CO_T + (2 + (s & 1)) * CH_TW + ks * 2048, 16), desc_lo(sd + CO_P + ks * 256, 128), ks != 0);
        wgmma_commit();
        wgmma_wait<0>();
        store32(dc, aO - CH_TW + st);
    };
    float gs = 0.f;
    auto load_gate = [&](int s) { asm volatile("ld.global.cg.f32 %0, [%1];" : "=f"(gs) : "l"(g_gate + s * SEGL + t4 * 8 + qd) : "memory"); };
    auto softmax = [&](int s, float (&u)[11]) {
        float v[10];
        {
            const uint4 a0 = lds128(aL + CO_OWN + t4 * 1024), a1 = lds128(aL + CO_OWN + t4 * 1024 + 512);
            const float2 a2 = lds64f(aL + CO_OWN2 + t4 * 256 - lane * 8);
            v[0] = __uint_as_float(a0.x); v[1] = __uint_as_float(a0.y); v[2] = __uint_as_float(a0.z); v[3] = __uint_as_float(a0.w);
            v[4] = __uint_as_float(a1.x); v[5] = __uint_as_float(a1.y); v[6] = __uint_as_float(a1.z); v[7] = __uint_as_float(a1.w);
            v[8] = a2.x; v[9] = a2.y;
        }
        mbar_wait_cl(bar_l, s & 1);
        add_scores(aL + t4 * 1024 + CO_LS + (s & 1) * 5120, aL + t4 * 256 - lane * 8 + CO_LS + (s & 1) * 5120 + 4096, v);
        const int lim = t4 * 8 + qd - 2 * qc;
#pragma unroll
        for (int j = 0; j < 8; j++) if ((j >> 1) * 8 + (j & 1) > lim) v[j] = -INFINITY;
        const float mx = row_max(v);
#pragma unroll
        for (int j = 0; j < 10; j++) u[j] = v[j];
        u[10] = mx;
    };
    auto softmax1 = [&](float (&u)[11]) {
#pragma unroll
        for (int j = 0; j < 10; j++) u[j] = ex2f(fmaf(u[j], CH_SC, -u[10]));
        u[10] = (((u[0] + u[1]) + (u[2] + u[3])) + ((u[4] + u[5]) + (u[6] + u[7]))) + (u[8] + u[9]);
    };
    auto softmax2 = [&](float (&v)[11]) {
        float sum = v[10];
        sum += __shfl_xor_sync(0xffffffff, sum, 1);
        sum += __shfl_xor_sync(0xffffffff, sum, 2);
        asm("rcp.approx.ftz.f32 %0, %0;" : "+f"(sum));
        sum *= 1.f - gs;
        const uint32_t pa = aL + CO_P + t4 * 768;
        stmatrix_x4(pa, pack_bf16(v[0] * sum, v[1] * sum), pack_bf16(v[2] * sum, v[3] * sum), pack_bf16(v[4] * sum, v[5] * sum), pack_bf16(v[6] * sum, v[7] * sum));
        asm volatile("stmatrix.sync.aligned.m8n8.x1.shared.b16 [%0], {%1};" :: "r"(pa + 512), "r"(pack_bf16(v[8] * sum, v[9] * sum)) : "memory");
    };
    if (mapa_u32(bar_l, rank ^ 1) != (bar_l ^ (1u << 24)) || mapa_u32(bar_l, (rank + 3) & 7) != bar_l + roff(3)) __trap();
    asm volatile("bar.sync %0, 128;" :: "r"(12 + wg) : "memory");
    if (__shfl_sync(0xffffffff, tid, 1) < 256) {
#pragma unroll 1
        for (int rep = CH_DRY ? 0 : 1; rep < 2; rep++) {
            if (rep) mbar_wait(bar_w + 8 * wg, 0);
            PT(3, 0);
            load_w(wg, false);
            if (rep) {
                asm volatile("bar.arrive %0, %1;" :: "r"(wg ? 2 : 15), "r"(CH_V3 && wg ? 224 : 160) : "memory");
                asm volatile("barrier.cluster.arrive.relaxed.aligned;" ::: "memory");
                mbar_wait(bar_x, 0);
            }
            asm volatile("bar.sync 12, 256;" ::: "memory");
            PT(7, 0);
            float d[16];
            pass(d, wg, 0, 0, 16, -1);
            wgmma_wait<0>();
            store32(d, aO + CO_T + (1 - 2 * wg) * CH_TW);
            pass(d, wg, 0, 0, 16, 0);
            asm volatile("bar.sync 13, 256;" ::: "memory");
            uint32_t r[8];
            load32(r, aO + CO_T);
            add32(d, r, aO + CO_T);
        }
    }
    PT(8, 0);
    TS_BEGIN(5);
    PT(9, 0);

    if (wg < 2) {
        const uint32_t aM = pin(sb + CO_XB + 4096 + (lane & 7) * 128 + (((lane >> 3) ^ (lane & 7)) << 4));
        uint32_t coff[4];
#pragma unroll
        for (int i = 0; i < 4; i++) coff[i] = uni(chunk(mine(wg, i)) * CH_XC);
        auto mem_proj = [&](int s, auto gc) {
            constexpr int G = decltype(gc)::value;
            const uint32_t par = s & 1;
            float acc[4][4];
#pragma unroll
            for (int i = 0; i < 4; i++) acc[i][0] = acc[i][1] = acc[i][2] = acc[i][3] = 0.f;
            const uint32_t am = aM + par * CH_XP;
            uint32_t b[4][4], ok = 1;
            auto bar = [&](int c) { return bar_mem + 8 * CH_MB(mine(G, c)); };
            auto load = [&](int c) {
                if (c ? CH_MB(mine(G, c)) != CH_MB(mine(G, c - 1)) : G == 0)
                    asm volatile("{\n.reg .pred p, q;\n.reg .u32 c;\nsetp.ne.u32 p, %2, 0;\n@p bra MP_DONE;\nmov.u32 c, 0;\n"
                                 "MP_LOOP:\nmbarrier.try_wait.parity.shared::cta.b64 p, [%0], %1;\nadd.u32 c, c, 1;\nsetp.lt.and.u32 q, c, %3, !p;\n"
                                 "@q bra MP_LOOP;\nMP_DONE:\n}" :: "r"(bar(c)), "r"(par ^ 1), "r"(ok), "n"(WAIT_LIMIT / 64) : "memory");
                uint32_t* r = b[2 * c & 3];
                ldmatrix_x4(r[0], r[1], r[2], r[3], am + coff[c]);
                r = b[(2 * c + 1) & 3];
                ldmatrix_x4(r[0], r[1], r[2], r[3], (am ^ 64) + coff[c]);
                if (c < 3 && CH_MB(mine(G, c + 1)) != CH_MB(mine(G, c))) ok = mbar_try(bar(c + 1), par ^ 1);
            };
            auto mma = [&](int i) {
#pragma unroll
                for (int j = 0; j < 4; j++) {
                    const uint32_t* a = w[(i >> 1) * 8 + ((j & 1) ^ G) * 4 + (i & 1) * 2 + (j >> 1)];
                    mma_16816(acc[j], a[0], a[1], a[2], a[3], b[i & 3][j & 2], b[i & 3][(j & 2) + 1]);
                }
            };
#pragma unroll
            for (int e = 0; e < CH_NSM; e++) ldmatrix_x4_trans(w[e][0], w[e][1], w[e][2], w[e][3], aO + CO_WA + e * 2048);
            if (G == 1) asm volatile("bar.sync 10, %0;" :: "n"(CH_QL < 16 ? 384 : 256) : "memory");
            else ok = mbar_try(bar(0), par ^ 1);
            DBG(11, 0);
            load(0);
#pragma unroll
            for (int c = 0; c < 3; c++) {
                const int at = (CH_ML >> (c * 4 + G * 12)) & 3;
                if (at == 0) load(c + 1);
                mma(2 * c);
                if (at == 1) load(c + 1);
                mma(2 * c + 1);
                if (at == 2) load(c + 1);
            }
            mma(6);
            uint32_t dep = __float_as_uint(acc[CH_HA & 3][0]);
            mma(7);
            if (CH_HA >= 4) dep = __float_as_uint(acc[CH_HA & 3][0]);
            asm volatile("bar.arrive %0, 384;" :: "r"(5 | (dep & (s >> 10))) : "memory");
            uint32_t r[4];
#pragma unroll
            for (int i = 0; i < 4; i++) r[i] = pack_bf16(acc[i >> 1][(i & 1) * 2] + acc[(i >> 1) + 2][(i & 1) * 2], acc[i >> 1][(i & 1) * 2 + 1] + acc[(i >> 1) + 2][(i & 1) * 2 + 1]);
            DBGD(40 + warp, warp, r[0] ^ r[1]);
            asm volatile("{\n.reg .pred q;\nsetp.ne.s32 q, %3, 0;\n"
                         "@q stmatrix.sync.aligned.m8n8.x2.trans.shared.b16 [%0], {%1, %2};\n"
                         "@q stmatrix.sync.aligned.m8n8.x2.trans.shared.b16 [%0 + %4], {%1, %2};\n"
                         "@q stmatrix.sync.aligned.m8n8.x2.trans.shared.b16 [%0 + 2 * %4], {%1, %2};\n"
                         "@q stmatrix.sync.aligned.m8n8.x2.trans.shared.b16 [%0 + 3 * %4], {%1, %2};\n}"
                         :: "r"(aO + (CO_XB + 4096 + G * (CH_XC - CH_TW) + (par ^ 1) * CH_XP)), "r"(r[0]), "r"(r[1]),
                            "r"(s - (NSEG - 1)), "n"(2 * CH_XC) : "memory");
            stmatrix_x2_trans(aO + CO_T + (G ? 5120 : CH_TW + 4096), r[2], r[3]);
            fence_async_smem();
        };
        if (wg == 0) {
#pragma unroll 1
            for (int s = 0; s < NSEG; s++) {
                const uint32_t par = s & 1;
                mem_proj(s, std::integral_constant<int, 0>());
                asm volatile("bar.arrive 1, 256;" ::: "memory");
                asm volatile("bar.sync 8, 384;" ::: "memory");
                if (s == NSEG - 1) break;
                if (tid == 96) {
#pragma unroll
                    for (int j = 1; j < 8; j++) {
                        int n = 0;
                        for (int i = 1; i < 8; i++) n += CH_MB(i) == j;
                        if (n) mbar_expect_tx(bar_mem + 8 * j, 1024 * n);
                        if (j < 4) mbar_expect_tx(bar_o + 8 * j - 8, 512 << j);
                    }
                }
                __syncwarp();
                uint32_t* wp = g_xbuf + (size_t)rank * 2048 + C * 256 + qc * 64 + t4 * 8 + qd;
                asm volatile("st.relaxed.gpu.global" CH_SQ ".u32 [%0], %1;" :: "l"(wp + ((s + 2) & 3) * 16384), "r"(~0u) : "memory");
                asm volatile("st.relaxed.gpu.global" CH_SQ ".u32 [%0], %1;" :: "l"(wp + ((s + 2) & 3) * 16384 + 32), "r"(~0u) : "memory");
                if (__builtin_expect(s == 0, 0)) {
                    asm volatile("barrier.cluster.wait.aligned;" ::: "memory");
                    mbar_wait(bar_wo, 0);
                    const int sr = (qd >> 2) * 2 + (qd & 1) + (qd & 2) * 4;
#pragma unroll 2
                    for (int ks = t4; ks < 32; ks += 4) {
                        const uint32_t a = sb + CO_WO + ks * 2048;
                        uint4 u[2][2];
#pragma unroll
                        for (int i = 0; i < 4; i++) { const int r = sr + (i >> 1) * 4; u[i >> 1][i & 1] = lds128(a + r * 128 + (((qc * 2 + (i & 1)) ^ (r & 7)) << 4)); }
                        __syncwarp();
#pragma unroll
                        for (int i = 0; i < 4; i++) {
                            const uint4 u0 = u[i >> 1][0], u1 = u[i >> 1][1];
                            const uint32_t sel = (i & 1) ? 0x7632 : 0x5410;
                            sts128(a + (qd + (i >> 1) * 8) * 128 + (((qc * 2 + (i & 1)) ^ qd) << 4),
                                   __byte_perm(u0.x, u0.y, sel), __byte_perm(u0.z, u0.w, sel), __byte_perm(u1.x, u1.y, sel), __byte_perm(u1.z, u1.w, sel));
                        }
                    }
                    fence_async_smem();
                }
                mbar_wait(bar_x + 8 * (par ^ 1), ((s + 1) >> 1) & 1);
                asm volatile("bar.sync 7, 384;" ::: "memory");
                float d[16];
                float c[4];
                const uint32_t alo = desc_lo(sd + CO_WO, 16), blo = desc_lo(sd + CO_OB, 128);
                wgmma_fence();
                pass(d, 0, par ^ 1, 0, CH_Q0, -1, false);
                asm volatile("bar.sync 11, 256;" ::: "memory");
#pragma unroll
                for (int i = 0; i < 32; i++) {
                    if (i == 4) { pass(d, 0, par ^ 1, CH_Q0 + min(4, CH_QI), CH_Q0 + min(4, CH_QI) + CH_QX, -1, false); mbar_wait_cl(bar_o, par); }
                    if (i == 8) mbar_wait_cl(bar_o + 8, par);
                    if (i == CH_OW) mbar_wait_cl(bar_o + 16, par);
                    wgmma_ss_n8(c, alo + i * 128, blo + i * 16, i != 0);
                    if (i < CH_QI) pass(d, 0, par ^ 1, CH_Q0 + i + (i < 4 ? 0 : CH_QX), CH_Q0 + i + (i < 4 ? 0 : CH_QX) + 1, -1, false);
                }
                wgmma_commit();
                wgmma_wait<0>();
                asm volatile("st.relaxed.gpu.global" CH_SQ ".u32 [%0], %1;" :: "l"(wp + (s & 3) * 16384), "r"(pack_bf16(c[0], c[2])) : "memory");
                asm volatile("st.relaxed.gpu.global" CH_SQ ".u32 [%0], %1;" :: "l"(wp + (s & 3) * 16384 + 32), "r"(pack_bf16(c[1], c[3])) : "memory");
                asm volatile("bar.arrive 6, 384;" ::: "memory");
                pace(CH_QD);
                asm volatile("bar.arrive 4, 384;" ::: "memory");
                DBG(8, 0);
                if (CH_Q1 < 16) pass(d, 0, par ^ 1, CH_Q1, 16, -1);
                asm volatile("bar.sync 9, 256;" ::: "memory");
                wgmma_wait<0>();
                store32(d, aO + CO_T + CH_TW);
                asm volatile("bar.arrive 12, 256;" ::: "memory");
                if (CH_QL) pass(d, 0, (par ^ 1) + (s >> 10), 0, CH_QL, CH_QS);
                DBG(21, 0);
                if (tid == 0) {
                    if (s + 2 < NSEG) {
                        mbar_expect_tx(bar_x + 8 * par, 32768);
                        tma_load_2d_mc(sb + CO_XB + par * CH_XP + rank * CH_XC, &P.mapX, bar_x + 8 * par, rank * 64, (s + 2) * SEGL, (uint16_t)0xff);
                        if (CH_XPF) asm volatile("cp.async.bulk.prefetch.tensor.2d.L2.global [%0, {%1, %2}];" :: "l"(&P.mapX), "r"(rank * 64), "r"((s + 2 + CH_XPF) * SEGL) : "memory");
                    } else {
#pragma unroll 1
                        for (int i = 0; i < 8; i++) tma_load_2d(sb + CO_WO + i * 8192, &P.mapWo, bar_wo, (rank & 3) * 128 + (i & 1) * 64, (h & ~1) * HD + (i >> 1) * 64);
                    }
                }
                __syncwarp();
                asm volatile("bar.sync 13, 256;" ::: "memory");
                uint32_t r[8];
                load32(r, aO + CO_T);
                if (CH_QL < 16) {
                    asm volatile("bar.sync 10, 384;" ::: "memory");
                    pass(d, 0, (par ^ 1) + (s >> 10), CH_QL, CH_QE, CH_QS);
                }
                add32(d, r, aO + CO_T);
                DBG(22, 0);
            }
            *reinterpret_cast<uint2*>(g_xbuf + 16384 + blockIdx.x * 256 + tid * 2) = make_uint2(~0u, ~0u);
        PT(10, 0);
            if (tid == 0) {
                mbar_expect_tx(bar_wo, 65536 + 32768);
                mbar_expect_tx(bar_w, 24576);
                asm volatile("prefetch.tensormap [%0];" :: "l"(&P.mapOut) : "memory");
                wait_ctr(CT_CA + 63, 16u);
            }
            __syncwarp();
            uint32_t fin = 0;
#pragma unroll 1
            for (int r = 0; r < 2; r++) {
                float acc[64];
                mbar_wait(bar_wo, 1);
                asm volatile("bar.sync %0, 256;" :: "r"(15 - r) : "memory");
                asm volatile("{\n.reg .pred p;\nsetp.eq.b32 p, %2, 32;\n@p atom.relaxed.gpu.global.inc.u32 %0, [%1], 0x7fffffff;\n}"
                             : "+r"(fin) : "l"(&g_ctr[CT_FIN]), "r"(tid + r * 128) : "memory");
                wgmma_fence();
#pragma unroll
                for (int i = 0; i < 16; i++) {
                    const uint32_t c = (rank + (i >> 2)) & 3;
                    const uint32_t a = r == 0 ? tail_a(c) : i < 4 ? CO_WA + CH_TW : CO_XB + CH_XP + c * 8192;
                    if (i == 4) mbar_wait(r ? bar_w : bar_wo, 1);
                    wgmma_ss_n128_lo<1>(acc, desc_lo(sd + a, 16) + (i & 3) * 2, desc_lo(sd + CO_WO, 8192) + c * 1024 + (i & 3) * 128, i);
                }
                wgmma_commit();
                wgmma_wait<0>();
                PT(5, 0);
                out_flush_half(acc, &P.mapOut, sb + (r ? tail_a(0) : CO_T), tid, 12, (rank & 3) * 128, SEQ - 128 + r * 64);
            }
            if (fin == M_GRID + 64 - 1)
                for (int i = 0; i < CT_N / 4; i++) reinterpret_cast<uint4*>(g_ctr)[i] = make_uint4(0u, 0u, 0u, 0u);
            if (tid == 0) {
                asm volatile("cp.async.bulk.wait_group.read 0;" ::: "memory");
                PT(15, 0);
            }
        } else {
            const uint32_t usc = uni(CO_SC + min(t4, 2) * 512 + roff((rank ^ 1) - rank)), uscb = uni(bar_sc ^ (1u << 24));
            const uint32_t vaddr = pin(sb + CO_T + 2 * CH_TW + (lane & 15) * 128 + (((t4 * 2 + (lane >> 4)) ^ (lane & 7)) << 4));
            const uint32_t dsta = pin(sb + CO_OB + t4 * 256 + (qc >> 1) * 128 + qd * 16 + (qc & 1) * 8);
            auto store_ctx = [&](int s) {
                if (tid == CH_ST && (uint32_t)s < NSEG - 3) {
                    tma_store_2d(&P.mapC, sb + CO_ST, (rank & 1) * 64, h * SEQ + s * SEGL);
                    asm volatile("cp.async.bulk.commit_group;" ::: "memory");
                }
                __syncwarp();
            };
            auto signal_ctx = [&](int s) {
                if (tid == CH_ST && (s & 3) == 1)
                    asm volatile("cp.async.bulk.wait_group 0;\nred.relaxed.gpu.global.add.u32 [%0], 1;" :: "l"(&g_ctr[CT_CB - 1 + (s >> 2)]) : "memory");
                __syncwarp();
            };
            uint32_t uo[8], ub[8];
#pragma unroll
            for (int i = 0; i < 8; i++) { uo[i] = uni(roff(i) + i * 1024); ub[i] = uni(roff(i) + bar_o + (i < 2 ? 0 : i < 4 ? 8 : 16)); }
#pragma unroll 1
            for (int s = 0; s < NSEG; s++) {
                const uint32_t par = s & 1;
                mem_proj(s, std::integral_constant<int, 1>());
                asm volatile("bar.sync 1, 256;" ::: "memory");
                float d[24];
                scores(d, std::integral_constant<int, CH_XC>(), CO_XB + 4096 + (par ^ 1) * CH_XP);
                if (s == NSEG - 1) { wgmma_wait<0>(); break; }
                asm volatile("bar.arrive 8, 384;" ::: "memory");
                if (s == 0) asm volatile("barrier.cluster.wait.aligned;" ::: "memory");
                const uint32_t sca = (aL | (s >> 10)) + usc;
                wgmma_wait<0>();
                float v[10], u[12];
#pragma unroll
                for (int j = 0; j < 12; j++) u[j] = d[(j >> 1) * 4 + (j & 1)] + d[(j >> 1) * 4 + (j & 1) + 2];
                if (t4 < 3) {
                    auto sel = [&](int j) { return t4 == 0 ? u[j] : t4 == 1 ? u[4 + j] : u[8 + j]; };
                    asm volatile("st.async.weak.shared::cluster.mbarrier::complete_tx::bytes.v4.f32 [%0], {%2, %3, %4, %5}, [%1];"
                                 :: "r"(sca), "r"(uscb), "f"(sel(0)), "f"(sel(1)), "f"(sel(2)), "f"(sel(3)) : "memory");
                }
#pragma unroll
                for (int j = 0; j < 10; j++) v[j] = j < 8 ? u[j] : u[j] + u[j + 2];
                DBG(3, 4);
                if (CH_ES) signal_ctx(s); else store_ctx(s - 2);
                uint32_t vb[3][4];
                auto load_v = [&](float dep) {
                    asm volatile("bar.sync %0, 256;" :: "r"(CH_VD ? 3 | (__float_as_uint(dep) & (s >> 10)) : 3) : "memory");
#pragma unroll
                    for (int k = 0; k < 3; k++) ldmatrix_x4_trans(vb[k][0], vb[k][1], vb[k][2], vb[k][3], vaddr + par * CH_TW + k * 2048);
                };
                mbar_wait_cl(bar_sc, par);
                DBG(4, 4);
                {
                    const uint4 a0 = lds128(aL + CO_SC), a1 = lds128(aL + CO_SC + 512), a2 = lds128(aL + CO_SC + 1024);
                    v[0] += __uint_as_float(a0.x); v[1] += __uint_as_float(a0.y); v[2] += __uint_as_float(a0.z); v[3] += __uint_as_float(a0.w);
                    v[4] += __uint_as_float(a1.x); v[5] += __uint_as_float(a1.y); v[6] += __uint_as_float(a1.z); v[7] += __uint_as_float(a1.w);
                    v[8] += __uint_as_float(a2.x) + __uint_as_float(a2.z); v[9] += __uint_as_float(a2.y) + __uint_as_float(a2.w);
                }
                const float mx = row_max(v);
                if (CH_VPOS == 2) load_v(mx);
#pragma unroll
                for (int j = 0; j < 10; j++) v[j] = ex2f(fmaf(v[j], CH_SC, -mx));
                uint32_t p[5];
#pragma unroll
                for (int j = 0; j < 5; j++) p[j] = pack_bf16(v[2 * j], v[2 * j + 1]);
                if (CH_VPOS == 3) load_v(v[CH_VD]);
                DBG(19, 4);
                float c0[4] = {0.f, 0.f, 0.f, 0.f}, c1[4] = {0.f, 0.f, 0.f, 0.f}, cs[4] = {0.f, 0.f, 0.f, 0.f};
#pragma unroll
                for (int k = 0; k < 3; k++) {
                    const uint32_t p0 = p[2 * k], p1 = k < 2 ? p[2 * k + 1] : 0u;
                    mma_16816(cs, p0, 0u, p1, 0u, 0x3f803f80u, 0x3f803f80u);
                    mma_16816(c0, p0, 0u, p1, 0u, vb[k][0], vb[k][1]);
                    mma_16816(c1, p0, 0u, p1, 0u, vb[k][2], vb[k][3]);
                }
                float inv;
                asm volatile("rcp.approx.ftz.f32 %0, %1;" : "=f"(inv) : "f"(cs[0]));
                const uint32_t b0 = pack_bf16(c0[0] * inv, c0[1] * inv), b1 = pack_bf16(c1[0] * inv, c1[1] * inv);
                DBG(20, 4);
#pragma unroll
                for (int i = 1; i < 8; i++) {
                    st_async_v2((dsta | (s >> 10)) + uo[i], b0, b1, ub[i]);
                    if (i == CH_OS) asm volatile("st.shared.v2.b32 [%0], {%1, %2};" :: "r"(dsta), "r"(b0), "r"(b1) : "memory");
                    if (i == CH_OFE) asm volatile("fence.proxy.async.shared::cta;\nbar.arrive 11, 256;" ::: "memory");
                }
                DBG(5, 4);
                asm volatile("cp.async.bulk.wait_group.read 0;" ::: "memory");
                asm volatile("bar.sync 7, 384;" ::: "memory");
                if (CH_OFE > 7) asm volatile("fence.proxy.async.shared::cta;\nbar.arrive 11, 256;" ::: "memory");
                local_pv(s + 1, CO_ST);
                if (CH_ES) fence_async_smem();
                asm volatile("bar.arrive 6, 384;" ::: "memory");
                if (tid == 128) mbar_expect_tx(bar_sc, 1536);
                __syncwarp();
                if (CH_SG == 1) signal_ctx(s);
                mbar_wait(bar_x + 8 * (par ^ 1), ((s + 1) >> 1) & 1);
                if (CH_SG == 2) signal_ctx(s);
                asm volatile("bar.sync 4, 384;" ::: "memory");
                float dk[16];
                pass(dk, 1, par ^ 1, 0, 16, -1);
                wgmma_wait<0>();
                store32(dk, aO + CO_T - CH_TW);
                asm volatile("bar.arrive 13, 256;" ::: "memory");
                pass(dk, 1, (par ^ 1) + (s >> 10), 0, CH_KE, CH_KS);
                if (CH_ES) store_ctx(s - 1); else if (!CH_SG) signal_ctx(s);
                DBG(1, 4);
                asm volatile("bar.sync 12, 256;" ::: "memory");
                uint32_t r[8];
                load32(r, aO + CO_T);
                add32(dk, r, aO + CO_T);
                DBG(29, 4);
            }
        }
    } else {
        {
            PT(2, 256);
            int lane;
            asm volatile("mov.u32 %0, %%laneid;" : "=r"(lane));
            if (t4 == 0 && lane == 0) {
                asm volatile("cp.async.bulk.prefetch.tensor.2d.L2.global [%0, {%1, %2}];" :: "l"(&P.mapX), "r"(rank * 64), "r"(SEGL) : "memory");
                asm volatile("prefetch.tensormap [%0];" :: "l"(&P.mapC) : "memory");
                mbar_expect_tx(bar_sc, 1536);
                mbar_expect_tx(bar_x + 8, 32768);
                mbar_expect_tx(bar_wo, 65536);
                mbar_expect_tx(bar_w + 16, 65536);
            }
            {
                const CUtensorMap* map = t4 == 2 ? &P.mapWo : &P.mapW[2];
                const uint32_t bar = t4 == 2 ? bar_wo : bar_w + 16;
                const int c0 = t4 == 2 ? rank * 64 : wcol;
                auto row = [&](int i) { return t4 == 2 ? C * 512 + ((rank - i) & 7) * 64 : (int)chunk(i >> 1) * 64 + (i & 1) * 32; };
                uint32_t now;
                do { asm volatile("mov.u32 %0, %%clock;" : "=r"(now)); } while (now - t_start < (uint32_t)(t4 == 2 ? CH_D2 : 0));
                __syncwarp();
                asm volatile("bar.sync %0, %1;" :: "r"(t4 == 2 ? 15 : 2), "r"(t4 == 2 ? 160 : 224) : "memory");
                if (lane == 0) {
#pragma unroll 1
                    for (int i = t4 == 2 ? 0 : min(t4, 2); i < (t4 == 2 ? 8 : 16); i += t4 == 2 ? 1 : 3)
                        tma_load_2d(sb + (t4 == 2 ? CO_WO + i * 8192 : vdst(i)), map, bar, c0, row(i));
                }
            }
            __syncwarp();
            mbar_wait(bar_w + 16, 0);
            PT(4, 256);
            load_w(2, true);
            asm volatile("bar.sync 14, 128;" ::: "memory");
            asm volatile("barrier.cluster.arrive.relaxed.aligned;" ::: "memory");
            if ((CH_XS || t4 == 0) && lane == 0) {
#pragma unroll 1
                for (int i = CH_XS ? t4 : 0; i < 8; i += CH_XS ? 4 : 1) tma_load_2d(sb + CO_XB + CH_XP + i * CH_XC, &P.mapX, bar_x + 8, i * 64, SEGL);
            }
            __syncwarp();
            PT(6, 256);
        }
#pragma unroll 1
        for (int s = 0; s < NSEG; s++) {
            const uint32_t par = s & 1;
            const bool last = s == NSEG - 1;
            if (CH_GL < 2) {
                if (s == 1) wait_ctr(CT_GATE, 256u);
                load_gate(max(s - 1, 0));
                if (CH_GL) asm volatile("prefetch.global.L2 [%0];" :: "l"(g_gate + ((s + 1) & (NSEG - 1)) * SEGL) : "memory");
            } else if (s == 1) { wait_ctr(CT_GATE, 256u); load_gate(0); }
            float v[11];
            if (CH_SP) fence_async_smem();
            softmax(s - 1, v);
            if (CH_SP < 2) softmax1(v);
            DBG(7, 8);
            if (!CH_SP) fence_async_smem();
            asm volatile("bar.sync %0, 384;" :: "r"(CH_SP ? 5 | (__float_as_uint(v[10]) & (s >> 10)) : 5) : "memory");
            DBG(23, 8);
            float dv[20], d[24];
            pass(dv, 2, par, 0, CH_VA, CH_VS);
            asm volatile("bar.sync 8, 384;" ::: "memory");
            pass(dv, 2, par, CH_VA, 32, CH_VS);
            if (CH_SP == 2) {
                uint32_t z;
                asm volatile("mov.u32 %0, %%clock;" : "=r"(z) :: "memory");
                v[10] = __uint_as_float(__float_as_uint(v[10]) | (z & (s >> 10)));
                softmax1(v);
                asm volatile("{\n.reg .pred p;\nsetp.ne.s32 p, %0, 1000001;\n@p bra SP_SKIP;\nwgmma.wait_group.sync.aligned 0;\n"
                             "st.volatile.shared.f32 [%0], %1;\nexit;\nSP_SKIP:\n}" :: "r"(s), "f"(v[10]) : "memory");
            }
            wgmma_wait<0>();
            stmatrix_x2_trans(aO + par * CH_TW + CO_T + 4096, pack_bf16(dv[16], dv[17]), pack_bf16(dv[18], dv[19]));
            store32(dv, aO + par * CH_TW + CO_T);
            DBG(24, 8);
            uint32_t z3 = __float_as_uint(dv[0]);
            if (CH_A3) asm volatile("{\n.reg .pred p;\nsetp.ne.s32 p, %1, %2;\n@p bar.arrive 3, 256;\nmov.u32 %0, %%clock;\n}" : "=r"(z3) : "r"(s), "n"(NSEG - 1) : "memory");
            else if (!last) asm volatile("bar.arrive 3, 256;" ::: "memory");
            if (CH_SP) { v[10] = __uint_as_float(__float_as_uint(v[10]) | (z3 & (s >> 10))); softmax2(v); fence_async_smem(); }
            if (CH_GL == 2) load_gate(s);
            if (last) asm volatile("bar.arrive 7, 256;" ::: "memory"); else asm volatile("bar.sync 7, 384;" ::: "memory");
            scores(d, std::integral_constant<int, 512>(), CO_T);
            asm volatile("{\n.reg .pred p;\nsetp.eq.s32 p, %1, 256;\n@p mbarrier.arrive.expect_tx.shared::cta.b64 _, [%0], 5120;\n}" :: "r"(bar_l), "r"(tid) : "memory");
            wgmma_wait<0>();
            d[16] += d[20]; d[17] += d[21];
            auto send_scores = [&]() {
                const uint32_t a = aL + t4 * 1024, a2 = aL + t4 * 256 - lane * 8, r = roff((rank ^ 1) - rank) + CO_LS + par * 5120;
                asm volatile("st.async.weak.shared::cluster.mbarrier::complete_tx::bytes.v4.f32 [%0], {%3, %4, %5, %6}, [%2];\n"
                             "st.async.weak.shared::cluster.mbarrier::complete_tx::bytes.v4.f32 [%0 + 512], {%7, %8, %9, %10}, [%2];\n"
                             "st.async.weak.shared::cluster.mbarrier::complete_tx::bytes.v2.f32 [%1], {%11, %12}, [%2];"
                             :: "r"(a + r), "r"(a2 + r + 4096), "r"(bar_l ^ (1u << 24)), "f"(d[0]), "f"(d[1]), "f"(d[4]), "f"(d[5]),
                                "f"(d[8]), "f"(d[9]), "f"(d[12]), "f"(d[13]), "f"(d[16]), "f"(d[17]) : "memory");
            };
            auto keep_scores = [&]() {
                const uint32_t a = aL + t4 * 1024, a2 = aL + t4 * 256 - lane * 8;
                sts128(a + CO_OWN, __float_as_uint(d[0]), __float_as_uint(d[1]), __float_as_uint(d[4]), __float_as_uint(d[5]));
                sts128(a + CO_OWN + 512, __float_as_uint(d[8]), __float_as_uint(d[9]), __float_as_uint(d[12]), __float_as_uint(d[13]));
                asm volatile("st.shared.v2.f32 [%0], {%1, %2};" :: "r"(a2 + CO_OWN2), "f"(d[16]), "f"(d[17]) : "memory");
            };
            if (s == 0) asm volatile("barrier.cluster.wait.aligned;" ::: "memory");
            if (CH_LSS == 0) send_scores();
            if (CH_KEEP == 0) keep_scores();
            if (last) { if (CH_LSS) send_scores(); if (CH_KEEP) keep_scores(); break; }
            asm volatile("bar.arrive 4, 384;\nbar.arrive 9, 256;" ::: "memory");
            uint32_t t0, t1;
            if (!CH_PINB) asm volatile("bar.sync 6, 384;\nmov.u32 %0, %%clock;" : "=r"(t0) :: "memory");
            const int row = t4 * 2 + (lane >> 4);
            const uint32_t dsta = pin(sb + CO_XB + (par ^ 1) * CH_XP + rank * CH_XC + 4096 + row * 128 + ((((lane & 15) >> 1) ^ row) << 4) + (lane & 1) * 8);
            uint32_t dst1 = pin(dsta + roff(1)), bar1 = pin((bar_mem + 8 + roff(1)) | (s >> 10));
            uint32_t sel = pin(((qd >> 1) == qc ? 0x3f80u << (qd & 1) * 16 : 0u) | (s >> 10));
            const uint2* xb = reinterpret_cast<const uint2*>(g_xbuf + (s & 3) * 16384 + (size_t)rank * 2048 + t4 * 64) + pin(lane | (s >> 10));
            if (CH_PINB) asm volatile("bar.sync %1, 384;\nmov.u32 %0, %%clock;" : "=r"(t0) : "r"(6 | (dst1 & sel & (uint32_t)(size_t)xb & (s >> 10))) : "memory");
            if (CH_LSS == 1) send_scores();
            if (CH_KEEP == 2) keep_scores();
            uint2 p[8], q[8];
            do { asm volatile("mov.u32 %0, %%clock;" : "=r"(t1) :: "memory"); } while (t1 - t0 < CH_POLL_DELAY);
#pragma unroll
            for (int k = 0; k < 8; k++)
                asm volatile("ld.relaxed.gpu.global" CH_LQ ".v2.u32 {%0, %1}, [%2];" : "=r"(p[k].x), "=r"(p[k].y) : "l"(xb + k * 128) : "memory");
            DBG(17, 8);
            if (CH_LSS == 2) send_scores();
            if (CH_KEEP == 1) keep_scores();
            {
                uint32_t z;
                asm volatile("mov.u32 %0, %%clock;" : "=r"(z) :: "memory");
#pragma unroll
                for (int i = 0; i < CH_GAP; i++) asm volatile("{\n.reg .f32 f;\nmov.b32 f, %0;\nex2.approx.ftz.f32 f, f;\nmov.b32 %0, f;\n}" : "+r"(z));
                asm volatile("and.b32 %0, %0, %1;" : "+r"(z) : "r"(s >> 10));
                xb += z;
            }
#pragma unroll
            for (int k = 0; k < 8; k++)
                asm volatile("ld.relaxed.gpu.global" CH_LQ ".v2.u32 {%0, %1}, [%2];" : "=r"(q[k].x), "=r"(q[k].y) : "l"(xb + k * 128) : "memory");
            if (CH_LSS == 3) send_scores();
            if (CH_KEEP == 3) keep_scores();
            uint32_t m0, m1;
            {
                uint32_t z;
                asm volatile("mov.u32 %0, %%clock;" : "=r"(z) :: "memory");
                sel |= z & (s >> 10);
            }
            auto sum = [&](const uint2 (&p)[8]) {
                float c[CH_SUMC][4];
#pragma unroll
                for (int k = 0; k < 4; k++) {
                    if (k < CH_SUMC) c[k][0] = c[k][1] = c[k][2] = c[k][3] = 0.f;
                    mma_16816(c[k % CH_SUMC], p[2 * k].x, p[2 * k].y, p[2 * k + 1].x, p[2 * k + 1].y, sel, sel);
                }
#pragma unroll
                for (int k = 1; k < CH_SUMC; k++) { c[0][0] += c[k][0]; c[0][1] += c[k][1]; c[0][2] += c[k][2]; c[0][3] += c[k][3]; }
                m0 = pack_bf16(c[0][0], c[0][1]);
                m1 = pack_bf16(c[0][2], c[0][3]);
                uint32_t ok;
                asm volatile("{\n.reg .pred p;\nsetp.num.f32 p, %1, %2;\nvote.sync.all.pred p, p, 0xffffffff;\nselp.u32 %0, 1, 0, p;\n}" : "=r"(ok) : "f"(c[0][0]), "f"(c[0][2]));
                return ok;
            };
            if (__builtin_expect(!sum(p), 0)) {
                DBG(12, 8);
#pragma unroll 1
                for (int it = 0; it < WAIT_LIMIT / 4; it++) {
                    if (sum(q)) break;
                    uint32_t bad = 0;
#pragma unroll
                    for (int k = 0; k < 8; k++) bad |= (max(q[k].x, q[k].y) == ~0u ? 1u : 0u) << k;
                    if (__all_sync(0xffffffff, bad == 0u)) break;
                    if (it == 0) DBG(14, 8);
                    if (it == 1) DBG(15, 8);
#pragma unroll
                    for (int k = 0; k < 8; k++)
                        if (bad & (1u << k))
                            asm volatile("ld.relaxed.gpu.global" CH_LQ ".v2.u32 {%0, %1}, [%2];" : "=r"(q[k].x), "=r"(q[k].y) : "l"(xb + k * 128) : "memory");
                }
            }
            DBG(9, 8);
            st_async_v2(dst1, m0, m1, bar1);
            asm volatile("st.shared.v2.b32 [%0], {%1, %2};\nbar.arrive 10, %3;" :: "r"(dsta), "r"(m0), "r"(m1), "n"(CH_QL < 16 ? 384 : 256) : "memory");
#pragma unroll 1
            for (int i = 0; i < 6; i += CH_MP) {
#pragma unroll
                for (int j = 0; j < CH_MP; j++) {
                    dst1 = (dst1 + (1u << 24)) & 0x7ffffffu; bar1 = (bar1 + (1u << 24) + 8) & 0x7ffffffu;
                    st_async_v2(dst1, m0, m1, bar1);
                }
            }
            if (s == 1000000) {
#pragma unroll
                for (int k = 0; k < 8; k++) asm volatile("st.volatile.shared.v2.u32 [%0], {%1, %2};" :: "r"(s), "r"(q[k].x), "r"(q[k].y) : "memory");
            }
            DBG(10, 8);
        }
    }
    const int wgt = __shfl_sync(0xffffffff, tid >> 7, 0);
    if (wgt == 1) {
        asm volatile("bar.arrive 8, 384;" ::: "memory");
        auto copy = [&](uint32_t dst, uint32_t src, uint32_t bar) {
            asm volatile("cp.async.bulk.shared::cluster.shared::cta.mbarrier::complete_tx::bytes [%0], [%1], 4096, [%2];" :: "r"(dst), "r"(src), "r"(bar) : "memory");
        };
        const uint32_t peer = (uint32_t)(tid & 3) << 24;
        if ((tid & ~3) == CH_ST) {
            copy((sb + tail_a(rank & 3) + 4096) ^ peer, sb + CO_ST, bar_wo ^ peer);
            if (tid == CH_ST) {
                asm volatile("cp.async.bulk.wait_group 0;" ::: "memory");
                tma_load_2d_mc(sb + tail_a(rank & 3), &P.mapC, bar_wo, (rank & 1) * 64, h * SEQ + SEQ - 128, (uint16_t)(15 << (rank & 4)));
            }
        }
        __syncwarp();
        asm volatile("bar.sync 7, 256;" ::: "memory");
#pragma unroll 1
        for (int i = 0; i < 2; i++) {
            local_pv(i, CO_WA + CH_TW + i * 4096);
            fence_async_smem();
            asm volatile("bar.arrive %0, 256;" :: "r"(i ? 14 : 9) : "memory");
            asm volatile("bar.sync 2, 128;" ::: "memory");
            if (tid > 128 && tid < 132) {
                mbar_wait(sb + CO_BAR + 120, 0);
                copy((sb + CO_XB + CH_XP + (rank & 3) * 8192 + i * 4096) ^ peer, sb + CO_WA + CH_TW + i * 4096, bar_w ^ peer);
            }
            __syncwarp();
            if (i == 0) asm volatile("bar.sync 3, 256;" ::: "memory");
        }
        PT(14, 128);
    } else if (wgt == 2) {
        PT(11, 256);
        if (CH_GL < 2) load_gate(NSEG - 1);
        if ((tid & 31) < 4) asm volatile("mbarrier.arrive.relaxed.cluster.shared::cluster.b64 _, [%0];" :: "r"((sb + CO_BAR + 120) ^ ((tid & 3) << 24)) : "memory");
        asm volatile("bar.arrive 15, 256;\nbar.sync 9, 256;" ::: "memory");
        float v[11];
        softmax(NSEG - 1, v);
        softmax1(v);
        softmax2(v);
        fence_async_smem();
        asm volatile("bar.arrive 3, 256;" ::: "memory");
    }
    __syncthreads();
    asm volatile("barrier.cluster.arrive.relaxed.aligned;\nbarrier.cluster.wait.aligned;" ::: "memory");
    TS_END(2);
}

struct Proj2Params {
    CUtensorMap mapA[2];
    CUtensorMap mapW[3];
    bf16* out[3];
};
#define P2T(i)
#define P2_NOMMA 0
#define P2_NOLOAD 0
#define P2_ROT 4
#define P2_NP 1
#define P2_NI 4
constexpr int P2_STAGES = 6;
constexpr int P2_ITEMS = 168 + 48;

__device__ __forceinline__ int p2_reps(int t) { return t >= 168 ? 1 : 2; }
__device__ __forceinline__ void p2_tile(int t, int w, int& z, int& mp, int& head) {
    if (t >= 168) { w += ((t - 168) & 1) * 2; t = 168 + ((t - 168) >> 1); }
    const int hq = (t / 24 + P2_ROT) & 7, v = t % 24;
    mp = v & 7;
    if (v < 16) { head = hq * 4 + (v >> 3) * 2 + (w >> 1); z = 1 + (w & 1); }
    else { head = hq * 4 + w; z = 0; }
}
__device__ __forceinline__ void mbar_arrive_remote(uint32_t bar_cluster_addr) {
    asm volatile("mbarrier.arrive.release.cluster.shared::cluster.b64 _, [%0];" :: "r"(bar_cluster_addr) : "memory");
}
__device__ __forceinline__ void mbar_arrive_cl(uint32_t bar_cluster_addr) {
    asm volatile("mbarrier.arrive.shared::cluster.b64 _, [%0];" :: "r"(bar_cluster_addr) : "memory");
}
__device__ __forceinline__ void mbar_wait_acq_cluster(uint32_t bar, uint32_t parity) {
    asm volatile(
        "{\n"
        ".reg .pred p, q;\n"
        ".reg .u32 c;\n"
        "mov.u32 c, 0;\n"
        "WAIT_LOOP_C:\n"
        "mbarrier.try_wait.parity.acquire.cluster.shared::cta.b64 p, [%0], %1;\n"
        "@p bra WAIT_DONE_C;\n"
        "add.u32 c, c, 1;\n"
        "setp.lt.u32 q, c, 4000000;\n"
        "@q bra WAIT_LOOP_C;\n"
        "WAIT_DONE_C:\n"
        "}\n" :: "r"(bar), "r"(parity) : "memory");
}
__device__ __forceinline__ uint4 quad_transpose(uint32_t p0, uint32_t p1, uint32_t p2, uint32_t p3, int lane) {
    const bool o1 = lane & 1, o2 = lane & 2;
    uint32_t s0 = o1 ? p0 : p1, s1 = o1 ? p2 : p3;
    s0 = __shfl_xor_sync(0xffffffff, s0, 1); s1 = __shfl_xor_sync(0xffffffff, s1, 1);
    const uint32_t a_lo = o1 ? s0 : p0, a_hi = o1 ? p1 : s0, b_lo = o1 ? s1 : p2, b_hi = o1 ? p3 : s1;
    uint32_t t0 = o2 ? a_lo : b_lo, t1 = o2 ? a_hi : b_hi;
    t0 = __shfl_xor_sync(0xffffffff, t0, 2); t1 = __shfl_xor_sync(0xffffffff, t1, 2);
    return o2 ? make_uint4(t0, t1, b_lo, b_hi) : make_uint4(a_lo, a_hi, t0, t1);
}
#define P2_PACE 35
#define P2_PACE2 0
#define P2_STM 1
#define P2_STQ ".L1::no_allocate"
#define P2_NOF 0
#define P2_HO 7
#define P2_PRE 0
template <int PACE>
__device__ __forceinline__ void store_frag_128(const float (&acc)[64], bf16* obase) {
    uint32_t p[32];
#pragma unroll
    for (int i = 0; i < 32; i++) p[i] = pack_bf16(acc[2 * i], acc[2 * i + 1]);
    if (P2_PRE) {
#pragma unroll
        for (int i = 0; i < 32; i += 8) asm volatile("" : "+r"(p[i]), "+r"(p[i + 1]), "+r"(p[i + 2]), "+r"(p[i + 3]), "+r"(p[i + 4]), "+r"(p[i + 5]), "+r"(p[i + 6]), "+r"(p[i + 7]));
    }
#pragma unroll
    for (int rr = 0; rr < 2; rr++)
#pragma unroll
        for (int g = 0; g < 4; g++) {
            const uint32_t* a = &p[g * 8 + rr];
            asm volatile("st.global" P2_STQ ".v4.b32 [%0], {%1, %2, %3, %4};" :: "l"(obase + (size_t)(rr * 8) * HD + g * 32), "r"(a[0]), "r"(a[2]), "r"(a[4]), "r"(a[6]) : "memory");
            pace(PACE);
        }
}
struct OutParams {
    CUtensorMap mapCtx[2];
    CUtensorMap mapWo[2];
    CUtensorMap mapOut;
};

#define OT(i)
#define OTP(i, th)
constexpr int O2_STAGES = 4;
constexpr int O2_GRID = 0;
#define O2_FINE 6
#define O2_Q0 9
#define O2_Q1 9
#define O2_Q2 16
#define O2_N0 60
#define O2_RL 0
#define O2_Q3 12
#define O2_Q4 8
#define O2_Q5 8
#define O2_NB 10
#define O2_PW 0
#define O2_QA 13

constexpr uint32_t OB_FULL = 0, OB_EMPTY = 32, OB_ITEM = 64, OB_SLOT = 128, OB_STOP = 160;
__device__ __forceinline__ void out_init(uint32_t bars) {
    for (int i = 0; i < O2_STAGES; i++) {
        mbar_init(bars + OB_FULL + 8 * i, 1); mbar_init(bars + OB_EMPTY + 8 * i, 4); mbar_init(bars + OB_ITEM + 16 * i, 1); mbar_init(bars + OB_ITEM + 16 * i + 8, 1);
    }
    sts128(bars + OB_STOP, 0u, 0u, 0u, 0u);
}
struct OutJob { int tg, q, qe, last, t0, nw, nq; };
__device__ __forceinline__ OutJob out_job(int cid, int j) {
    auto quota = [](int tg) { return tg >= 12 ? O2_Q3 : tg >= 10 ? O2_Q5 : tg >= 8 ? O2_Q4 : tg & 2 ? O2_Q0 : O2_Q1; };
    auto split = [](int tg) { return O2_Q2 && (tg >> 2) == 1; };
    constexpr int NL = O2_Q2 ? 4 : 0;
    if (cid < 28 && j == 0) {
        const int tg = cid % 14, h = cid >= 14, nq = 128 - quota(tg);
        if (split(tg)) return {tg, h ? O2_N0 + O2_Q2 : 0, h ? 128 : O2_N0, !h, 128, 0, 0};
        return {tg, 2 * h, 2 * h + 2, 1, 2, nq / 2 - O2_FINE, nq};
    }
    if (j == (cid < 30 ? 1 : 4)) { const int i = cid < 28 ? cid + 16 : cid; return {16, 2 * i + 8, 2 * i + 10, 1, 38 + NL, 64 - O2_FINE, 128}; }
    if (cid < 30) return {cid - 14, O2_QA, 64, 0, 0, 0, 0};
    const int tg = (j * 4 + cid - 32) & 15;
    if (split(tg)) return {tg, O2_N0, O2_N0 + O2_Q2, 0, 0, 0, 0};
    return {tg, tg >= 14 ? 0 : 128 - quota(tg), tg >= 14 ? O2_QA : 128, 0, 0, 0, 0};
}
__device__ __forceinline__ int out_mt(int tg, int rank) { return tg < 16 ? (tg & ~1) + rank : tg - 2; }
__device__ __forceinline__ int out_n0(int tg, int rank) { return (tg < 16 ? tg & 1 : rank) * 256; }
__device__ __forceinline__ void out_producer(const OutParams& P, uint32_t sbase, uint32_t bars, uint32_t rank, int cid, bool lead, int nkv) {
    const uint32_t bar_full = bars + OB_FULL, bar_empty = bars + OB_EMPTY, bar_item = bars + OB_ITEM, slot = bars + OB_SLOT, stop = bars + OB_STOP;
    int s = 0, nb = 0; uint32_t ph = 0;
    if (lead) asm volatile("prefetch.tensormap [%0];" :: "l"(&P.mapOut) : "memory");
#pragma unroll 1
    for (int job = 0;; job++) {
        const OutJob J = out_job(cid, job);
        const int mt = out_mt(J.tg, rank), m0 = mt * 128, n0 = out_n0(J.tg, rank);
        int ready = 0, q = J.q, qe = J.qe, tnext = 0, nst = 0;
        if (lead && rank == 0 && J.last) tnext = take_ticket(CT_OT + J.tg);
        if (lead && job == 0) {
            if (O2_PW) {
                if (q >= 64) nb = O2_NB + 1; else ready = 1;
                wait_ctr(q >= 64 ? CT_CB + O2_NB : CT_CA + mt * 4, q >= 64 ? 64u : 16u);
            }
            mbar_wait(sbase + FB_KE + 8 * (~nkv & 1), ((nkv - 1) >> 1) & 1);
            TS_END2(1, 256); TS_BEGIN2(3, 256);
            for (int i = 0; i < 4; i++) {
                const uint32_t e = mapa_u32(bar_empty + 8 * (i & 1), i >> 1);
                mbar_arrive_cl(e); mbar_arrive_cl(e);
            }
        }
#pragma unroll 1
        for (int ic = 0;; ic++) {
#pragma unroll 1
            for (bool first = true; q < qe; q++, first = false) {
                const int b = q >> 6, head = (q >> 1) & 31, dk = (q & 1) * 64;
                mbar_wait(bar_empty + 8 * s, ph);
                const uint32_t sa = sbase + s * 49152;
                if (lead) {
                    if (rank == 0 && J.last && first) {
                        const int t = tnext + J.t0;
                        asm volatile("st.shared.s32 [%0], %1;" :: "r"(slot + (ic & 7) * 4), "r"(t) : "memory");
                        mbar_arrive(bar_item + 8 * (ic & 7));
                        st_async_b32(mapa_u32(slot + (ic & 7) * 4, 1), (uint32_t)t, mapa_u32(bar_item + 8 * (ic & 7), 1));
                        if (J.nw + t < J.nq) tnext = take_ticket(CT_OT + J.tg);
                    }
                    if (b ? mt >= nb : !((ready >> (head >> 3)) & 1)) {
                        if (b) nb = max(mt, O2_NB) + 1; else ready |= 1 << (head >> 3);
                        wait_ctr(b ? CT_CB + nb - 1 : CT_CA + mt * 4 + (head >> 3), b ? 64u : 16u);
                    }
                    asm volatile("st.shared.s32 [%0], %1;" :: "r"(stop + s * 4), "r"(0) : "memory");
                    mbar_expect_tx(bar_full + 8 * s, 49152);
                    tma_load_2d(sa, &P.mapCtx[b], bar_full + 8 * s, dk, head * SEQ + m0);
                    if (++nst == 6 && !(ready & 8)) { wait_ctr(CT_CA + mt * 4 + 3, 16u); ready |= 8; }
                } else if (J.tg < 16) {
                    for (int j = (int)rank * 2; j < (int)rank * 2 + 2; j++)
                        tma_load_2d_mc(sa + 16384 + j * 8192, &P.mapWo[b], bar_full + 8 * s, n0 + j * 64, head * HD + dk, (uint16_t)3);
                } else {
                    for (int j = 0; j < 4; j++) tma_load_2d(sa + 16384 + j * 8192, &P.mapWo[1], bar_full + 8 * s, n0 + j * 64, head * HD + dk);
                }
                if (++s == O2_STAGES) { s = 0; ph ^= 1; }
            }
            if (!J.last) break;
            if (lead && rank == 1) mbar_expect_tx(bar_item + 8 * (ic & 7), 4);
            mbar_wait(bar_item + 8 * (ic & 7), (ic >> 3) & 1);
            int t;
            asm volatile("ld.shared.s32 %0, [%1];" : "=r"(t) : "r"(slot + (ic & 7) * 4) : "memory");
            if (J.nw + t >= J.nq) break;
            if (t < J.nw) { q = 2 * t; qe = q + 2; } else { q = J.nw + t; qe = q + 1; }
        }
        if (lead) {
            if (!(ready & 8)) wait_ctr(CT_CA + mt * 4 + 3, 16u);
            mbar_wait(bar_empty + 8 * s, ph);
            asm volatile("st.shared.s32 [%0], %1;" :: "r"(stop + s * 4), "r"(1 + J.last + n0 + (m0 << 4)) : "memory");
            mbar_arrive(bar_full + 8 * s);
        }
        if (J.last) break;
        if (++s == O2_STAGES) { s = 0; ph ^= 1; }
    }
    if (lead) {
        out_finished();
        for (int i = 1; i < O2_STAGES; i++) {
            if (++s == O2_STAGES) { s = 0; ph ^= 1; }
            mbar_wait(bar_empty + 8 * s, ph);
        }
    }
}
__device__ __forceinline__ void out_consumer(const OutParams& P, uint32_t sbase, uint32_t bars, int warp, uint32_t opar) {
    const uint32_t bar_full = bars + OB_FULL, bar_empty = bars + OB_EMPTY, stop = bars + OB_STOP;
    int tid;
    asm volatile("mov.u32 %0, %%tid.x;" : "=r"(tid));
    const int wg = warp >> 2;
    const bool elected = (tid & 127) == 0;
    auto release = [&](int s) { if (elected) { const uint32_t e = bar_empty + 8 * s; mbar_arrive_cl(mapa_u32(e, 0)); mbar_arrive_cl(mapa_u32(e, 1)); } };
    float acc[128];
    int s = 0, sprev = 0, st, n = 0; uint32_t ph = 0;
#pragma unroll 1
    do {
#pragma unroll 1
        for (int i = 0;; i++, n++) {
            mbar_wait(bar_full + 8 * s, ph);
            asm volatile("ld.shared.s32 %0, [%1];" : "=r"(st) : "r"(stop + s * 4) : "memory");
            if (st) break;
            if (n == 0) OT(1);
            const uint32_t sa = sbase + s * 49152 + wg * 8192, sb = sbase + s * 49152 + 16384;
            wgmma_fence();
#pragma unroll
            for (int kk = 0; kk < 4; kk++)
                wgmma_ss_n256_tb(acc, make_desc(sa + kk * 32, 16, 1024), make_desc(sb + kk * 2048, 8192, 1024), kk ? 1 : i);
            wgmma_commit();
            if (i > 0) { wgmma_wait<1>(); release(sprev); }
            if (i == O2_RL && n > 1) {
                if (elected) asm volatile("cp.async.bulk.wait_group.read 1;" ::: "memory");
                release((s + 3 - O2_RL) & 3);
            }
            sprev = s;
            if (++s == O2_STAGES) { s = 0; ph ^= 1; }
        }
        mbar_wait(sbase + FB_OE + 8 * wg, opar);
        if (elected) asm volatile("cp.async.bulk.wait_group.read 0;" ::: "memory");
        wgmma_wait<0>();
        release(sprev);
        asm volatile("bar.sync %0, 128;" :: "r"(1 + wg) : "memory");
        OT(3);
        out_flush(acc, &P.mapOut, sbase + s * 49152 + wg * 16384, sbase + O2_STAGES * 49152 + wg * 16384, tid, 1 + wg, st & 256, (st >> 4 & ~127) + wg * 64);
        if (++s == O2_STAGES) { s = 0; ph ^= 1; }
    } while (!(st & 2));
    OT(4);
    if (elected) {
        asm volatile("cp.async.bulk.wait_group.read 0;" ::: "memory");
    }
}

struct MainParams { Proj2Params p; AttnParams a; OutParams o; const bf16 *x, *gate_w; };
__device__ __forceinline__ int p2_apos(int k) { return k < 2 ? k : k < 6 ? k + 2 : k - 4; }
__global__ void __cluster_dims__(2, 1, 1) __launch_bounds__(384, 1) main_kernel(const __grid_constant__ MainParams MP) {
    const Proj2Params& P = MP.p;
    extern __shared__ uint8_t smem_raw[];
    const uint32_t rank = cluster_ctarank();
    const uint32_t sbase = (rank << 24) + SD;
    if (smem_u32(smem_raw) != sbase) __trap();
    const uint32_t sA = sbase, sB = sbase + 131072;
    const uint32_t bars = sbase + MO_BAR, obars = bars + 768;
    const uint32_t a_full = bars, a_empty = bars + 64, b_full = bars + 128, b_empty = b_full + 8 * P2_STAGES;
    const uint32_t item_bar = b_empty + 8 * P2_STAGES, item_in = item_bar + 16, slot = item_in + 16;
    const uint32_t note_bar = slot + 16, note_free = note_bar + 64, note = note_free + 64;
    const int warp = __shfl_sync(0xffffffff, threadIdx.x >> 5, 0), lane = threadIdx.x & 31;
    TS_BEGIN(0);
    if (threadIdx.x == 0) {
        for (int i = 0; i < 8; i++) { mbar_init(a_full + 8 * i, 1); mbar_init(a_empty + 8 * i, 2); }
        for (int i = 0; i < P2_STAGES; i++) { mbar_init(b_full + 8 * i, 1); mbar_init(b_empty + 8 * i, 2); }
        mbar_init(item_bar, 1); mbar_init(item_bar + 8, 1); mbar_init(item_in, 2); mbar_init(item_in + 8, 2);
        for (int i = 0; i < 8; i++) { mbar_init(note_bar + 8 * i, 4); mbar_init(note_free + 8 * i, 1); }
        asm volatile("fence.mbarrier_init.release.cluster;" ::: "memory");
    }
    if (threadIdx.x == 32) {
        attn_init(sbase);
        asm volatile("fence.mbarrier_init.release.cluster;" ::: "memory");
    }
    if (threadIdx.x == 256) {
        out_init(obars);
        asm volatile("fence.mbarrier_init.release.cluster;" ::: "memory");
    }
    __syncthreads();
    asm volatile("barrier.cluster.arrive.relaxed.aligned;" ::: "memory");
    if (warp >= 8) {
    asm volatile("setmaxnreg.dec.sync.aligned.u32 40;");
    asm volatile("barrier.cluster.wait.aligned;" ::: "memory");
    if (warp == 9) {
        if (lane == 0) {
            for (int n = 0;; n++) {
                const int e = (n & 1) * 4 + ((n >> 1) & 3);
                mbar_wait(note_bar + 8 * e, (n >> 3) & 1);
                int m;
                asm volatile("ld.shared.s32 %0, [%1];" : "=r"(m) : "r"(note + e * 4) : "memory");
                mbar_arrive(note_free + 8 * e);
                if (m < 0) break;
                signal_ctr(m);
            }
            attn_helper(MP.a, sbase, 0);
        }
    } else if (warp == 10) {
        if (lane == 0) {
            auto publish = [&](int ic, int tq) {
                const int t = tq < P2_ITEMS ? tq : -1;
                asm volatile("st.shared.s32 [%0], %1;" :: "r"(slot + (ic & 3) * 4), "r"(t) : "memory");
                mbar_arrive(item_bar + 8 * (ic & 1));
                st_async_b32(mapa_u32(slot + (ic & 3) * 4, 1), (uint32_t)t, mapa_u32(item_bar + 8 * (ic & 1), 1));
            };
            const int npair = M_GRID / 2, pair = (int)(blockIdx.x >> 1);
            pace(M_D0);
            if (rank == 0) publish(0, pair);
            for (int ic = 0;; ic++) {
                if (rank == 1) mbar_expect_tx(item_bar + 8 * (ic & 1), 4);
                mbar_wait(item_bar + 8 * (ic & 1), (ic >> 1) & 1);
                int t;
                asm volatile("ld.shared.s32 %0, [%1];" : "=r"(t) : "r"(slot + (ic & 3) * 4) : "memory");
                if (t < 0) break;
                int z0, mp, h0;
                p2_tile(t, 0, z0, mp, h0);
                const int aidx = z0 >= 1 ? 1 : 0;
                const int m0 = (2 * mp + (int)rank) * 128;
                for (int k = 0; k < 8; k++) {
                    mbar_wait(a_empty + 8 * k, (ic & 1) ^ 1);
                    if (P2_NOLOAD) mbar_arrive(a_full + 8 * k); else {
                    mbar_expect_tx(a_full + 8 * k, 16384);
                    tma_load_2d(sA + p2_apos(k) * 16384, &P.mapA[aidx], a_full + 8 * k, k * 64, m0); }
                }
                if (rank == 0) {
                    mbar_wait(item_in + 8 * (ic & 1), (ic >> 1) & 1);
                    publish(ic + 1, ic == 0 ? npair + pair : pair < P2_NP && ic + 1 >= P2_NI ? P2_ITEMS : 2 * npair + (int)atomicAdd(&g_ctr[CT_PROJ], 1u));
                }
            }
            attn_helper(MP.a, sbase, 1);
        }
    } else {
        if (lane == 0) {
            const int par2 = warp == 8 ? 0 : 1;
            int it = 0, ic = 0; uint32_t bph = 0;
            for (;; ic++) {
                mbar_wait(item_bar + 8 * (ic & 1), (ic >> 1) & 1);
                int t;
                asm volatile("ld.shared.s32 %0, [%1];" : "=r"(t) : "r"(slot + (ic & 3) * 4) : "memory");
                if (t < 0) break;
                const int nt = 2 * p2_reps(t);
                for (int w = 0; w < nt; w++) {
                    int z, mp, hd;
                    p2_tile(t, w, z, mp, hd);
                    for (int k = 0; k < 8; k++) {
                        const int s = it; const uint32_t phb = bph;
                        if (++it == P2_STAGES) { it = 0; bph ^= 1; }
                        if ((k & 1) != par2) continue;
                        mbar_wait(b_empty + 8 * s, phb ^ 1);
                        if (P2_NOLOAD) { mbar_arrive(b_full + 8 * s); continue; }
                        mbar_expect_tx(b_full + 8 * s, 16384);
                        tma_load_2d_mc(sB + s * 16384 + rank * 8192, &P.mapW[z], b_full + 8 * s, hd * 128 + (int)rank * 64, k * 64, (uint16_t)3);
                    }
                }
            }
            out_producer(MP.o, sbase, obars, rank, blockIdx.x >> 1, warp == 8, warp == 8 ? attn_producer(MP.a, sbase, a_empty, ~ic & 1) : 0);
            TS_END2(3, 256);
        }
    }
    } else {
        asm volatile("setmaxnreg.inc.sync.aligned.u32 232;");
        asm volatile("barrier.cluster.wait.aligned;" ::: "memory");
        const int wg = warp >> 2;
        float acc[2][64];
        const uint32_t a_lo = desc_lo(SD, 16), b_lo0 = desc_lo(SD + 131072, 8192);
        const bool elected = (threadIdx.x & 127) == 0;
        int s = (wg * 8) % P2_STAGES;
        uint32_t ph = ((wg * 8) / P2_STAGES) & 1;
        int nnote = 0;
        if (wg == 1) {
            asm volatile("bar.arrive 3, 256;" ::: "memory");
            if (blockIdx.x < 64) {
                const int r = blockIdx.x * 32 + (warp & 3) * 8 + (lane >> 2);
                float c[4] = {0.f, 0.f, 0.f, 0.f};
                uint4 xv[16], gv[16];
#pragma unroll
                for (int i = 0; i < 16; i++) {
                    xv[i] = __ldg(reinterpret_cast<const uint4*>(MP.x + (size_t)r * DM + i * 32 + (lane & 3) * 8));
                    gv[i] = __ldg(reinterpret_cast<const uint4*>(MP.gate_w + i * 32 + (lane & 3) * 8));
                }
                auto mul = [](uint32_t a, uint32_t b) { uint32_t p; asm("mul.rn.bf16x2 %0, %1, %2;" : "=r"(p) : "r"(a), "r"(b)); return p; };
#pragma unroll
                for (int i = 0; i < 16; i++)
                    mma_16816(c, mul(xv[i].x, gv[i].x), mul(xv[i].y, gv[i].y), mul(xv[i].z, gv[i].z), mul(xv[i].w, gv[i].w), 0x3f803f80u, 0x3f803f80u);
                if ((lane & 3) == 0) g_gate[r] = bf16r(__fdividef(1.f, 1.f + __expf(-bf16r(c[0] + c[2]))));
                __syncwarp();
                if (lane == 0) signal_ctr_generic(CT_GATE);
                __syncwarp();
            }
        }
        auto next_item = [&](int ic) {
            mbar_wait(item_bar + 8 * (ic & 1), (ic >> 1) & 1);
            int t;
            asm volatile("ld.shared.s32 %0, [%1];" : "=r"(t) : "r"(slot + (ic & 3) * 4) : "memory");
            return __shfl_sync(0xffffffff, t, 0);
        };
        int t = next_item(0), ic = 0, rp = 0;
#pragma unroll 1
        while (t >= 0) {
            const bool first = rp == 0, last = rp == p2_reps(t) - 1;
            asm volatile("bar.sync %0, 256;" :: "r"(3 + wg) : "memory");
            P2T(0);
            if (wg == 1 && last && elected) mbar_arrive_cl(mapa_u32(item_in + 8 * (ic & 1), 0));
            int sprev = 0;
#pragma unroll
            for (int k = 0; k < 8; k++) {
                if (k == 0) P2T(5);
                if ((wg == 0 || k > P2_HO) && first) mbar_wait(a_full + 8 * k, ic & 1);
                if (k == 0) P2T(6);
                mbar_wait(b_full + 8 * s, ph);
                if (k == P2_HO) asm volatile("bar.arrive %0, 256;" :: "r"(4 - wg) : "memory");
                if (k == 0) P2T(1);
                if (k == 7) P2T(2);
                const uint32_t b_lo = b_lo0 + s * 1024;
                if (k == 0 || !P2_NOF) wgmma_fence();
#pragma unroll
                for (int kk = 0; kk < (P2_NOMMA ? 1 : 4); kk++) {
                    wgmma_ss_n128_lo<1>(acc[0], a_lo + p2_apos(k) * 1024 + kk * 2, b_lo + kk * 128, (k | kk) != 0);
                    wgmma_ss_n128_lo<1>(acc[1], a_lo + p2_apos(k) * 1024 + 512 + kk * 2, b_lo + kk * 128, (k | kk) != 0);
                }
                wgmma_commit();
                if (k > 0) {
                    wgmma_wait<1>();
                    if (elected) {
                        const uint32_t e = b_empty + 8 * sprev;
                        mbar_arrive_cl(mapa_u32(e, 0)); mbar_arrive_cl(mapa_u32(e, 1));
                        if (last) mbar_arrive(a_empty + 8 * (k - 1));
                    }
                }
                sprev = s;
                if (++s == P2_STAGES) { s = 0; ph ^= 1; }
            }
            int z, mp, head;
            p2_tile(t, rp * 2 + wg, z, mp, head);
            const int m0 = (2 * mp + (int)rank) * 128, en = wg * 4 + (nnote & 3);
            bf16* obase = P.out[z] + ((size_t)head * SEQ + m0 + (warp & 3) * 16 + (lane >> 2)) * HD + (lane & 3) * 8;
            if (elected) {
                mbar_wait(note_free + 8 * en, ((nnote >> 2) & 1) ^ 1);
                asm volatile("st.shared.s32 [%0], %1;" :: "r"(note + en * 4), "r"(CT_AP + (head >> 1)) : "memory");
            }
            __syncwarp();
            nnote++;
            wgmma_wait<0>();
            P2T(3);
            if (elected) {
                const uint32_t e = b_empty + 8 * sprev;
                mbar_arrive_cl(mapa_u32(e, 0)); mbar_arrive_cl(mapa_u32(e, 1));
                if (last) mbar_arrive(a_empty + 8 * 7);
            }
            s += 8 % P2_STAGES; ph ^= (8 / P2_STAGES) & 1;
            if (s >= P2_STAGES) { s -= P2_STAGES; ph ^= 1; }
            store_frag_128<P2_PACE>(acc[0], obase);
            if (last) { t = next_item(++ic); rp = 0; P2T(7); } else rp++;
            store_frag_128<P2_PACE>(acc[1], obase + (size_t)64 * HD);
            __syncwarp();
            if (lane == 0) mbar_arrive(note_bar + 8 * en);
            __syncwarp();
        }
        if (wg == 0 && lane == 0) {
            const int e = nnote & 3;
            if (elected) {
                mbar_wait(note_free + 8 * e, ((nnote >> 2) & 1) ^ 1);
                asm volatile("st.shared.s32 [%0], %1;" :: "r"(note + e * 4), "r"(-1) : "memory");
            }
            mbar_arrive(note_bar + 8 * e);
        }
        auto done = [&]() {
            if ((threadIdx.x & 127) == 0) for (int i = 0; i < 4; i++) mbar_arrive_cl(SD + MO_BAR + 768 + OB_EMPTY + 16 + 8 * (i & 1) + ((i >> 1) << 24));
        };
        asm volatile("bar.sync %0, 128;" :: "r"(1 + wg) : "memory");
        const int nout = attn_consumer(MP.a, warp, done, SD + (rank << 24));
        OT(0);
        const uint32_t sb2 = (cluster_ctarank() << 24) + SD;
        out_consumer(MP.o, sb2, sb2 + MO_BAR + 768, warp, nout & 1);
    }
}

typedef CUresult (*PFN_encodeTiled)(CUtensorMap*, CUtensorMapDataType, cuuint32_t, void*, const cuuint64_t*,
                                    const cuuint64_t*, const cuuint32_t*, const cuuint32_t*, CUtensorMapInterleave,
                                    CUtensorMapSwizzle, CUtensorMapL2promotion, CUtensorMapFloatOOBfill);
static PFN_encodeTiled g_encode = nullptr;

static void make_map(CUtensorMap* m, const void* ptr, uint64_t rows, uint64_t cols, uint32_t box_rows, bool sw64 = false) {
    cuuint64_t dims[2] = {cols, rows};
    cuuint64_t strides[1] = {cols * 2};
    cuuint32_t box[2] = {sw64 ? 32u : 64u, box_rows};
    cuuint32_t es[2] = {1, 1};
    g_encode(m, CU_TENSOR_MAP_DATA_TYPE_BFLOAT16, 2, const_cast<void*>(ptr), dims, strides, box, es,
             CU_TENSOR_MAP_INTERLEAVE_NONE, sw64 ? CU_TENSOR_MAP_SWIZZLE_64B : CU_TENSOR_MAP_SWIZZLE_128B, CU_TENSOR_MAP_L2_PROMOTION_L2_256B,
             CU_TENSOR_MAP_FLOAT_OOB_FILL_NONE);
}

template <typename... KArgs, typename... Args>
static void launch_pdl(void (*kernel)(KArgs...), int grid, int block, size_t smem, cudaStream_t st, bool pdl, Args... args) {
    cudaLaunchConfig_t cfg = {};
    cfg.gridDim = dim3(grid); cfg.blockDim = dim3(block); cfg.dynamicSmemBytes = smem; cfg.stream = st;
    cudaLaunchAttribute at[1];
    at[0].id = cudaLaunchAttributeProgrammaticStreamSerialization;
    at[0].val.programmaticStreamSerializationAllowed = 1;
    cfg.attrs = at; cfg.numAttrs = pdl ? 1 : 0;
    cudaLaunchKernelEx(&cfg, kernel, KArgs(args)...);
}

extern "C" void kernel_launch(void* const* d_in, const int* in_sizes, int n_in, void* d_out, int out_size) {
    const bf16* x = (const bf16*)d_in[0];
    const bf16* ckv = (const bf16*)d_in[1];
    const bf16* wq = (const bf16*)d_in[2];
    const bf16* wuk = (const bf16*)d_in[3];
    const bf16* wuv = (const bf16*)d_in[4];
    const bf16* wo = (const bf16*)d_in[5];
    const bf16* mem0 = (const bf16*)d_in[7];
    const bf16* Wq = (const bf16*)d_in[8];
    const bf16* Wk = (const bf16*)d_in[9];
    const bf16* Wv = (const bf16*)d_in[10];
    const bf16* Wo = (const bf16*)d_in[11];
    const bf16* gate_w = (const bf16*)d_in[13];
    bf16* out = (bf16*)d_out;

    static MainParams MP;
    static ChainParams CP;
    Proj2Params& P2 = MP.p;
    AttnParams& AP = MP.a;
    OutParams& OP = MP.o;
    static bool init = false;
    static const void* last_in[14];
    static const void* last_out;
    bool same = init && last_out == d_out;
    for (int i = 0; i < 14 && same; i++) same = last_in[i] == d_in[i];
    if (!init) {
        cudaDriverEntryPointQueryResult qr;
        cudaGetDriverEntryPoint("cuTensorMapEncodeTiled", (void**)&g_encode, cudaEnableDefault, &qr);
        cudaFuncSetAttribute(main_kernel, cudaFuncAttributeMaxDynamicSharedMemorySize, M_SMEM);
        cudaFuncSetAttribute(chain_kernel, cudaFuncAttributeMaxDynamicSharedMemorySize, CH_SMEM);
        init = true;
    }
    if (!same) {
        for (int i = 0; i < 14; i++) last_in[i] = d_in[i];
        last_out = d_out;
        void *pQA, *pKA, *pVA, *pCA, *pCB;
        cudaGetSymbolAddress(&pQA, g_QA); cudaGetSymbolAddress(&pKA, g_KA); cudaGetSymbolAddress(&pVA, g_VA);
        cudaGetSymbolAddress(&pCA, g_ctxA); cudaGetSymbolAddress(&pCB, g_ctxB);
        make_map(&P2.mapA[0], x, SEQ, DM, 128);
        make_map(&P2.mapA[1], ckv, SEQ, DM, 128);
        const void* ws[3] = {wq, wuk, wuv};
        void* cs[3] = {pQA, pKA, pVA};
        for (int i = 0; i < 3; i++) { make_map(&P2.mapW[i], ws[i], DM, NQ, 64); P2.out[i] = (bf16*)cs[i]; }
        make_map(&CP.mapW[0], Wq, DM, NQ, 64); make_map(&CP.mapW[1], Wk, DM, NQ, 64); make_map(&CP.mapW[2], Wv, DM, NQ, 32);
        make_map(&CP.mapX, x, SEQ, DM, 32);
        make_map(&CP.mapWo, Wo, NQ, DM, 64);
        make_map(&CP.mapM, mem0, NMEM, DM, 8);
        MP.x = x; MP.gate_w = gate_w;
        make_map(&CP.mapC, pCB, NH * SEQ, HD, 32);
        make_map(&AP.mapQ, pQA, NH * SEQ, HD, 128);
        make_map(&AP.mapK, pKA, NH * SEQ, HD, 128);
        make_map(&AP.mapV, pVA, NH * SEQ, HD, 128);
        make_map(&AP.mapO, pCA, NH * SEQ, HD, 64);
        make_map(&OP.mapCtx[0], pCA, NH * SEQ, HD, 128);
        make_map(&OP.mapCtx[1], pCB, NH * SEQ, HD, 128);
        make_map(&OP.mapWo[0], wo, NQ, DM, 64);
        make_map(&OP.mapWo[1], Wo, NQ, DM, 64);
        make_map(&OP.mapOut, out, SEQ, DM, 64);
        CP.mapOut = OP.mapOut;
        AP.out = out;
    }
    cudaStream_t s1 = cudaStreamPerThread;
    const bool pdl = true;
    launch_pdl(chain_kernel, 64, CH_BLOCK, CH_SMEM, s1, false, CP);
    launch_pdl(main_kernel, M_GRID, 384, M_SMEM, s1, pdl, MP);
}
```
